```python
import torch

def _softmax(x, axis=-1):
    return torch.softmax(x, dim=axis)
def _gelu(x):
    return torch.nn.functional.gelu(x, approximate="tanh")
def _silu(x):
    return torch.nn.functional.silu(x)
def _sigmoid(x):
    return torch.sigmoid(x)
def _layernorm(x, axis=-1, eps=1e-5):
    m = x.mean(dim=axis, keepdim=True)
    v = x.var(dim=axis, keepdim=True, unbiased=False)
    return (x - m) / torch.sqrt(v + eps)
def _scatter_add(tgt, idx, src, axis=0):
    return tgt.clone().index_add_(axis, idx, src)
def _segment_sum(src, seg, n):
    out = torch.zeros((n,) + src.shape[1:], dtype=src.dtype)
    return out.index_add_(0, seg, src)
def _pad(x, pw):
    flat = tuple(v for pair in reversed(pw) for v in pair)
    return torch.nn.functional.pad(x, flat)

kernel_name = 'interleave_layers__sliding_block__moe_arch_mod__prompt'

def setup_inputs():

    _w = (lambda a: (lambda t: t.to(torch.bfloat16) if t.is_floating_point() else t)(torch.as_tensor(a)))
    def _A_setup():
        B, S, D = 1, 2048, 1024
        return {
            "x": _w((lambda *s: torch.randn(*s, dtype=torch.bfloat16) * 0.05)(B, S, D)),
            "wqkv": _w((lambda *s: torch.randn(*s, dtype=torch.bfloat16) * 0.05)(D, 3 * D)),
            "wo": _w((lambda *s: torch.randn(*s, dtype=torch.bfloat16) * 0.05)(D, D)),
        }
    _A_in = _A_setup()

    def _B_setup():
        B, S, D, F, C = 1, 2048, 1024, 3584, 1
        return {
            "x": _w((lambda *s: torch.randn(*s, dtype=torch.bfloat16) * 0.05)(B, S, D)),
            "w_r": _w((lambda *s: torch.randn(*s, dtype=torch.bfloat16) * 1.6)(D)),
            "w_gate": _w((lambda *s: torch.randn(*s, dtype=torch.bfloat16) * 0.1)(D, F)),
            "w_up": _w((lambda *s: torch.randn(*s, dtype=torch.bfloat16) * 0.1)(D, F)),
            "w_down": _w((lambda *s: torch.randn(*s, dtype=torch.bfloat16) * 0.1)(F, D)),
        }
    _B_in = _B_setup()

    return {
        "A_x": _A_in["x"],
        "A_wqkv": _A_in["wqkv"],
        "A_wo": _A_in["wo"],
        "B_x": _B_in["x"],
        "B_w_r": _B_in["w_r"],
        "B_w_gate": _B_in["w_gate"],
        "B_w_up": _B_in["w_up"],
        "B_w_down": _B_in["w_down"],
    }

def reference(A_x, A_wqkv, A_wo, B_x, B_w_r, B_w_gate, B_w_up, B_w_down):
    def _A_ref(x, wqkv, wo):
        B, S, D = x.shape
        H = 32; Dh = D // H; W = 256
        qkv = (lambda x, *d: x.permute(*d))((x @ wqkv).reshape(B, S, 3, H, Dh), 2, 0, 3, 1, 4)
        q, k, v = qkv[0], qkv[1], qkv[2]
        scores = torch.einsum("bhqd,bhkd->bhqk", q, k) * (Dh ** -0.5)
        idx = torch.arange(S)
        mask = (idx[:, None] - idx[None, :] >= 0) & (idx[:, None] - idx[None, :] < W)
        scores = torch.where(mask[None, None], scores, -1e9)
        p = _softmax(scores, axis=-1)
        o = torch.einsum("bhqk,bhkd->bhqd", p, v)
        return (lambda x, *d: x.permute(*d))(o, 0, 2, 1, 3).reshape(B, S, D) @ wo

    def _B_ref(x, w_r, w_gate, w_up, w_down):
        B, S, D = x.shape
        C = 1
        r = x @ w_r
        idx = torch.argsort(-r, axis=-1)[:, :C]
        idx_e = (lambda x, n, axis: torch.repeat_interleave(x, n, dim=axis))(idx.reshape(B, C, 1), D, axis=2)
        x_sel = (lambda x, i, axis: torch.take_along_dim(x, i, dim=axis))(x, idx_e, axis=1)
        g = _silu(x_sel @ w_gate)
        u = x_sel @ w_up
        y = (g * u) @ w_down
        r_sel = _sigmoid((lambda x, i, axis: torch.take_along_dim(x, i, dim=axis))(r, idx, axis=1))
        y = y * r_sel.reshape(B, C, 1)
        b_off = (torch.arange(B) * S).reshape(B, 1)
        flat_idx = (idx + b_off).reshape(B * C)
        zero = (x * 0.0).reshape(B * S, D)
        upd = _scatter_add(zero, flat_idx, y.reshape(B * C, D), axis=0)
        return x + upd.reshape(B, S, D)

    x = A_x
    x = x + _A_ref(_layernorm(x, axis=-1), A_wqkv, A_wo)
    x = x + _B_ref(_layernorm(x, axis=-1), B_w_r, B_w_gate, B_w_up, B_w_down)
    x = x + _A_ref(_layernorm(x, axis=-1), A_wqkv, A_wo)
    x = x + _B_ref(_layernorm(x, axis=-1), B_w_r, B_w_gate, B_w_up, B_w_down)
    return x
```

```cpp
#include <cuda_runtime.h>
#include <cuda_bf16.h>
#include <cuda.h>
#include <stdint.h>
typedef __nv_bfloat16 bf16;

template<int TB, int TA = 0> __device__ __forceinline__ void wgmma_ss_n192(float (&d)[96], uint64_t da, uint64_t db, int scale_d) {
  asm volatile("{\n.reg .pred p;\nsetp.ne.b32 p, %98, 0;\n"
    "wgmma.mma_async.sync.aligned.m64n192k16.f32.bf16.bf16 {%0, %1, %2, %3, %4, %5, %6, %7, %8, %9, %10, %11, %12, %13, %14, %15, %16, %17, %18, %19, %20, %21, %22, %23, %24, %25, %26, %27, %28, %29, %30, %31, %32, %33, %34, %35, %36, %37, %38, %39, %40, %41, %42, %43, %44, %45, %46, %47, %48, %49, %50, %51, %52, %53, %54, %55, %56, %57, %58, %59, %60, %61, %62, %63, %64, %65, %66, %67, %68, %69, %70, %71, %72, %73, %74, %75, %76, %77, %78, %79, %80, %81, %82, %83, %84, %85, %86, %87, %88, %89, %90, %91, %92, %93, %94, %95}, %96, %97, p, 1, 1, %100, %99;\n}\n"
    : "+f"(d[0]), "+f"(d[1]), "+f"(d[2]), "+f"(d[3]), "+f"(d[4]), "+f"(d[5]), "+f"(d[6]), "+f"(d[7]), "+f"(d[8]), "+f"(d[9]), "+f"(d[10]), "+f"(d[11]), "+f"(d[12]), "+f"(d[13]), "+f"(d[14]), "+f"(d[15]), "+f"(d[16]), "+f"(d[17]), "+f"(d[18]), "+f"(d[19]), "+f"(d[20]), "+f"(d[21]), "+f"(d[22]), "+f"(d[23]), "+f"(d[24]), "+f"(d[25]), "+f"(d[26]), "+f"(d[27]), "+f"(d[28]), "+f"(d[29]), "+f"(d[30]), "+f"(d[31]), "+f"(d[32]), "+f"(d[33]), "+f"(d[34]), "+f"(d[35]), "+f"(d[36]), "+f"(d[37]), "+f"(d[38]), "+f"(d[39]), "+f"(d[40]), "+f"(d[41]), "+f"(d[42]), "+f"(d[43]), "+f"(d[44]), "+f"(d[45]), "+f"(d[46]), "+f"(d[47]), "+f"(d[48]), "+f"(d[49]), "+f"(d[50]), "+f"(d[51]), "+f"(d[52]), "+f"(d[53]), "+f"(d[54]), "+f"(d[55]), "+f"(d[56]), "+f"(d[57]), "+f"(d[58]), "+f"(d[59]), "+f"(d[60]), "+f"(d[61]), "+f"(d[62]), "+f"(d[63]), "+f"(d[64]), "+f"(d[65]), "+f"(d[66]), "+f"(d[67]), "+f"(d[68]), "+f"(d[69]), "+f"(d[70]), "+f"(d[71]), "+f"(d[72]), "+f"(d[73]), "+f"(d[74]), "+f"(d[75]), "+f"(d[76]), "+f"(d[77]), "+f"(d[78]), "+f"(d[79]), "+f"(d[80]), "+f"(d[81]), "+f"(d[82]), "+f"(d[83]), "+f"(d[84]), "+f"(d[85]), "+f"(d[86]), "+f"(d[87]), "+f"(d[88]), "+f"(d[89]), "+f"(d[90]), "+f"(d[91]), "+f"(d[92]), "+f"(d[93]), "+f"(d[94]), "+f"(d[95])
    : "l"(da), "l"(db), "r"(scale_d), "n"(TB), "n"(TA));
}

template<int TB, int TA = 0> __device__ __forceinline__ void wgmma_ss_n128(float (&d)[64], uint64_t da, uint64_t db, int scale_d) {
  asm volatile("{\n.reg .pred p;\nsetp.ne.b32 p, %66, 0;\n"
    "wgmma.mma_async.sync.aligned.m64n128k16.f32.bf16.bf16 {%0, %1, %2, %3, %4, %5, %6, %7, %8, %9, %10, %11, %12, %13, %14, %15, %16, %17, %18, %19, %20, %21, %22, %23, %24, %25, %26, %27, %28, %29, %30, %31, %32, %33, %34, %35, %36, %37, %38, %39, %40, %41, %42, %43, %44, %45, %46, %47, %48, %49, %50, %51, %52, %53, %54, %55, %56, %57, %58, %59, %60, %61, %62, %63}, %64, %65, p, 1, 1, %68, %67;\n}\n"
    : "+f"(d[0]), "+f"(d[1]), "+f"(d[2]), "+f"(d[3]), "+f"(d[4]), "+f"(d[5]), "+f"(d[6]), "+f"(d[7]), "+f"(d[8]), "+f"(d[9]), "+f"(d[10]), "+f"(d[11]), "+f"(d[12]), "+f"(d[13]), "+f"(d[14]), "+f"(d[15]), "+f"(d[16]), "+f"(d[17]), "+f"(d[18]), "+f"(d[19]), "+f"(d[20]), "+f"(d[21]), "+f"(d[22]), "+f"(d[23]), "+f"(d[24]), "+f"(d[25]), "+f"(d[26]), "+f"(d[27]), "+f"(d[28]), "+f"(d[29]), "+f"(d[30]), "+f"(d[31]), "+f"(d[32]), "+f"(d[33]), "+f"(d[34]), "+f"(d[35]), "+f"(d[36]), "+f"(d[37]), "+f"(d[38]), "+f"(d[39]), "+f"(d[40]), "+f"(d[41]), "+f"(d[42]), "+f"(d[43]), "+f"(d[44]), "+f"(d[45]), "+f"(d[46]), "+f"(d[47]), "+f"(d[48]), "+f"(d[49]), "+f"(d[50]), "+f"(d[51]), "+f"(d[52]), "+f"(d[53]), "+f"(d[54]), "+f"(d[55]), "+f"(d[56]), "+f"(d[57]), "+f"(d[58]), "+f"(d[59]), "+f"(d[60]), "+f"(d[61]), "+f"(d[62]), "+f"(d[63])
    : "l"(da), "l"(db), "r"(scale_d), "n"(TB), "n"(TA));
}

template<int TB, int TA = 0> __device__ __forceinline__ void wgmma_ss_n64(float (&d)[32], uint64_t da, uint64_t db, int scale_d) {
  asm volatile("{\n.reg .pred p;\nsetp.ne.b32 p, %34, 0;\n"
    "wgmma.mma_async.sync.aligned.m64n64k16.f32.bf16.bf16 {%0, %1, %2, %3, %4, %5, %6, %7, %8, %9, %10, %11, %12, %13, %14, %15, %16, %17, %18, %19, %20, %21, %22, %23, %24, %25, %26, %27, %28, %29, %30, %31}, %32, %33, p, 1, 1, %36, %35;\n}\n"
    : "+f"(d[0]), "+f"(d[1]), "+f"(d[2]), "+f"(d[3]), "+f"(d[4]), "+f"(d[5]), "+f"(d[6]), "+f"(d[7]), "+f"(d[8]), "+f"(d[9]), "+f"(d[10]), "+f"(d[11]), "+f"(d[12]), "+f"(d[13]), "+f"(d[14]), "+f"(d[15]), "+f"(d[16]), "+f"(d[17]), "+f"(d[18]), "+f"(d[19]), "+f"(d[20]), "+f"(d[21]), "+f"(d[22]), "+f"(d[23]), "+f"(d[24]), "+f"(d[25]), "+f"(d[26]), "+f"(d[27]), "+f"(d[28]), "+f"(d[29]), "+f"(d[30]), "+f"(d[31])
    : "l"(da), "l"(db), "r"(scale_d), "n"(TB), "n"(TA));
}

template<int TB> __device__ __forceinline__ void wgmma_rs_n40(float (&d)[20], uint32_t a0, uint32_t a1, uint32_t a2, uint32_t a3, uint64_t db, int scale_d) {
  asm volatile("{\n.reg .pred p;\nsetp.ne.b32 p, %25, 0;\n"
    "wgmma.mma_async.sync.aligned.m64n40k16.f32.bf16.bf16 {%0, %1, %2, %3, %4, %5, %6, %7, %8, %9, %10, %11, %12, %13, %14, %15, %16, %17, %18, %19}, {%20, %21, %22, %23}, %24, p, 1, 1, %26;\n}\n"
    : "+f"(d[0]), "+f"(d[1]), "+f"(d[2]), "+f"(d[3]), "+f"(d[4]), "+f"(d[5]), "+f"(d[6]), "+f"(d[7]), "+f"(d[8]), "+f"(d[9]), "+f"(d[10]), "+f"(d[11]), "+f"(d[12]), "+f"(d[13]), "+f"(d[14]), "+f"(d[15]), "+f"(d[16]), "+f"(d[17]), "+f"(d[18]), "+f"(d[19])
    : "r"(a0), "r"(a1), "r"(a2), "r"(a3), "l"(db), "r"(scale_d), "n"(TB));
}

#define DEVI __device__ __forceinline__
DEVI uint32_t smem_u32(const void* p) { return (uint32_t)__cvta_generic_to_shared(p); }
DEVI void mbar_init(uint32_t bar, uint32_t cnt) { asm volatile("mbarrier.init.shared::cta.b64 [%0], %1;" :: "r"(bar), "r"(cnt)); }
DEVI void mbar_expect_tx(uint32_t bar, uint32_t bytes) { asm volatile("mbarrier.arrive.expect_tx.shared::cta.b64 _, [%0], %1;" :: "r"(bar), "r"(bytes) : "memory"); }
DEVI void mbar_arrive(uint32_t bar) { asm volatile("mbarrier.arrive.shared::cta.b64 _, [%0];" :: "r"(bar) : "memory"); }
DEVI void mbar_wait(uint32_t bar, uint32_t parity) {
  asm volatile("{\n.reg .pred p;\n.reg .u32 it;\nmov.u32 it, 0;\nLW:\nmbarrier.try_wait.parity.shared::cta.b64 p, [%0], %1;\n@p bra LD;\n"
               "add.u32 it, it, 1;\nsetp.lt.u32 p, it, 0x2000000;\n@p bra LW;\ntrap;\nLD:\n}" :: "r"(bar), "r"(parity) : "memory");
}
DEVI void tma_2d(uint32_t dst, const CUtensorMap* m, int c0, int c1, uint32_t bar) {
  asm volatile("cp.async.bulk.tensor.2d.shared::cluster.global.mbarrier::complete_tx::bytes [%0], [%1, {%3, %4}], [%2];"
    :: "r"(dst), "l"(m), "r"(bar), "r"(c0), "r"(c1) : "memory");
}
DEVI void tma_3d(uint32_t dst, const CUtensorMap* m, int c0, int c1, int c2, uint32_t bar) {
  asm volatile("cp.async.bulk.tensor.3d.shared::cluster.global.mbarrier::complete_tx::bytes [%0], [%1, {%3, %4, %5}], [%2];"
    :: "r"(dst), "l"(m), "r"(bar), "r"(c0), "r"(c1), "r"(c2) : "memory");
}
DEVI void tma_5d(uint32_t dst, const CUtensorMap* m, int c0, int c1, int c2, int c3, int c4, uint32_t bar) {
  asm volatile("cp.async.bulk.tensor.5d.shared::cluster.global.mbarrier::complete_tx::bytes [%0], [%1, {%3, %4, %5, %6, %7}], [%2];"
    :: "r"(dst), "l"(m), "r"(bar), "r"(c0), "r"(c1), "r"(c2), "r"(c3), "r"(c4) : "memory");
}
DEVI void tma_prefetch_2d(const CUtensorMap* m, int c0, int c1) {
  asm volatile("cp.async.bulk.prefetch.tensor.2d.L2.global.tile [%0, {%1, %2}];" :: "l"(m), "r"(c0), "r"(c1) : "memory");
}
DEVI void bulk_prefetch(const void* g, uint32_t bytes) { asm volatile("cp.async.bulk.prefetch.L2.global [%0], %1;" :: "l"(g), "r"(bytes) : "memory"); }
DEVI void bulk_g2s(uint32_t s, const void* g, uint32_t bytes, uint32_t bar) {
  asm volatile("cp.async.bulk.shared::cluster.global.mbarrier::complete_tx::bytes [%0], [%1], %2, [%3];" :: "r"(s), "l"(g), "r"(bytes), "r"(bar) : "memory");
}
DEVI void bulk_s2g(void* g, uint32_t s, uint32_t bytes) {
  asm volatile("cp.async.bulk.global.shared::cta.bulk_group [%0], [%1], %2;\ncp.async.bulk.commit_group;" :: "l"(g), "r"(s), "r"(bytes) : "memory");
}
template<int N> DEVI void bulk_wait() { asm volatile("cp.async.bulk.wait_group %0;" :: "n"(N) : "memory"); }
DEVI void fence_async_smem() { asm volatile("fence.proxy.async.shared::cta;" ::: "memory"); }
DEVI void fence_async_glob() { asm volatile("fence.proxy.async.global;" ::: "memory"); }
DEVI unsigned ld_rlx(const unsigned* p) { unsigned v; asm volatile("ld.relaxed.gpu.global.u32 %0, [%1];" : "=r"(v) : "l"(p) : "memory"); return v; }
DEVI void st_rlx(unsigned* p, unsigned v) { asm volatile("st.relaxed.gpu.global.u32 [%0], %1;" :: "l"(p), "r"(v) : "memory"); }
DEVI uint4 ld_ll(const uint4* p) {
  uint4 v;
  asm volatile("{\n.reg .b128 t;\n.reg .b64 a, b;\nld.relaxed.gpu.global.b128 t, [%4];\nmov.b128 {a, b}, t;\nmov.b64 {%0, %1}, a;\nmov.b64 {%2, %3}, b;\n}"
               : "=r"(v.x), "=r"(v.y), "=r"(v.z), "=r"(v.w) : "l"(p) : "memory");
  return v;
}
DEVI void st_ll(uint4* p, uint32_t x, uint32_t y, uint32_t z, uint32_t w) {
  asm volatile("{\n.reg .b128 t;\n.reg .b64 a, b;\nmov.b64 a, {%1, %2};\nmov.b64 b, {%3, %4};\nmov.b128 t, {a, b};\nst.relaxed.gpu.global.b128 [%0], t;\n}"
               :: "l"(p), "r"(x), "r"(y), "r"(z), "r"(w) : "memory");
}
#define SPIN_MAX 0x1000000
DEVI uint4 poll_ll(const uint4* p, uint32_t mask, uint32_t tag) {
  uint4 v; int it = 0;
  do { v = ld_ll(p); if (++it > SPIN_MAX) __trap(); } while ((v.w & mask) != tag);
  return v;
}
DEVI void bar_sync(int id, int n) { asm volatile("bar.sync %0, %1;" :: "r"(id), "r"(n) : "memory"); }
DEVI void wg_fence() { asm volatile("wgmma.fence.sync.aligned;" ::: "memory"); }
DEVI void wg_commit() { asm volatile("wgmma.commit_group.sync.aligned;" ::: "memory"); }
template<int N> DEVI void wg_wait() { asm volatile("wgmma.wait_group.sync.aligned %0;" :: "n"(N) : "memory"); }
template<int N> DEVI void reg_inc() { asm volatile("setmaxnreg.inc.sync.aligned.u32 %0;" :: "n"(N)); }
template<int N> DEVI void reg_dec() { asm volatile("setmaxnreg.dec.sync.aligned.u32 %0;" :: "n"(N)); }
DEVI float ex2f(float x) { float y; asm("ex2.approx.ftz.f32 %0, %1;" : "=f"(y) : "f"(x)); return y; }
DEVI uint32_t pack_bf16(float lo, float hi) { uint32_t r; asm("cvt.rn.bf16x2.f32 %0, %1, %2;" : "=r"(r) : "f"(hi), "f"(lo)); return r; }
DEVI float bf_lo(uint32_t v) { return __uint_as_float(v << 16); }
DEVI float bf_hi(uint32_t v) { return __uint_as_float(v & 0xffff0000u); }
DEVI float bf_round(float x) { return bf_lo(pack_bf16(x, 0.f)); }
DEVI void stsm_x4(uint32_t addr, uint32_t a, uint32_t b, uint32_t c, uint32_t d) {
  asm volatile("stmatrix.sync.aligned.m8n8.x4.shared.b16 [%0], {%1,%2,%3,%4};" :: "r"(addr), "r"(a), "r"(b), "r"(c), "r"(d) : "memory");
}
DEVI void ldsm_x4(uint32_t addr, uint32_t& a, uint32_t& b, uint32_t& c, uint32_t& d) {
  asm volatile("ldmatrix.sync.aligned.m8n8.x4.shared.b16 {%0,%1,%2,%3}, [%4];" : "=r"(a), "=r"(b), "=r"(c), "=r"(d) : "r"(addr) : "memory");
}
DEVI uint4 lds128(uint32_t a) { uint4 v; asm volatile("ld.shared.v4.u32 {%0,%1,%2,%3}, [%4];" : "=r"(v.x), "=r"(v.y), "=r"(v.z), "=r"(v.w) : "r"(a) : "memory"); return v; }
DEVI void sts128(uint32_t a, uint4 v) { asm volatile("st.shared.v4.u32 [%0], {%1,%2,%3,%4};" :: "r"(a), "r"(v.x), "r"(v.y), "r"(v.z), "r"(v.w) : "memory"); }
DEVI float2 lds64f(uint32_t a) { float2 v; asm volatile("ld.shared.v2.f32 {%0,%1}, [%2];" : "=f"(v.x), "=f"(v.y) : "r"(a) : "memory"); return v; }
DEVI void sts64f(uint32_t a, float x, float y) { asm volatile("st.shared.v2.f32 [%0], {%1,%2};" :: "r"(a), "f"(x), "f"(y) : "memory"); }
DEVI uint32_t lds32(uint32_t a) { uint32_t v; asm volatile("ld.shared.u32 %0, [%1];" : "=r"(v) : "r"(a) : "memory"); return v; }
DEVI float lds32f(uint32_t a) { return __uint_as_float(lds32(a)); }
DEVI void sts32(uint32_t a, uint32_t v) { asm volatile("st.shared.u32 [%0], %1;" :: "r"(a), "r"(v) : "memory"); }
DEVI void sts32f(uint32_t a, float v) { sts32(a, __float_as_uint(v)); }
DEVI void sts16(uint32_t a, uint32_t v) { asm volatile("st.shared.u16 [%0], %1;" :: "r"(a), "h"((unsigned short)v) : "memory"); }
template<int N> DEVI void keep(float (&d)[N]) {
  #pragma unroll
  for (int i = 0; i < N; i++) asm volatile("" : "+f"(d[i]) :: "memory");
}
template<int N> DEVI void keep(uint32_t (&d)[N]) {
  #pragma unroll
  for (int i = 0; i < N; i++) asm volatile("" : "+r"(d[i]) :: "memory");
}
template<uint32_t HI> DEVI uint64_t mkd(uint32_t lo) { uint64_t r; asm("mov.b64 %0, {%1, %2};" : "=l"(r) : "r"(lo), "n"(HI)); return r; }
constexpr uint32_t HI128 = (1u << 30) | (1024 >> 4), HI64 = (2u << 30) | (512 >> 4);
#define VOFF(x) ((uint32_t)(x) * (uint32_t)(1 - 65536))
DEVI void warp_signal(uint32_t bar) { fence_async_smem(); __syncwarp(); if ((threadIdx.x & 31) == 0) mbar_arrive(bar); }

__device__ uint4 g_kv[128][8][512];
__device__ uint4 g_zero[512];
__device__ uint4 g_o[8][2][8][2][1024];
__device__ uint4 g_x[8][16][2048];
__device__ unsigned g_flagKV[128][32];
__device__ unsigned g_flagO[8][2][2][32];
__device__ unsigned g_flagX[8][64];
__device__ uint4 g_statP[8][2048];
__device__ uint4 g_statF[2048];
__device__ uint4 g_csP[16][8][64];
__device__ uint4 g_best[128];
__device__ uint4 g_yP[112][256];
__device__ uint4 g_x2[256];
__device__ uint4 g_patch[768];
__device__ unsigned g_epoch;
#define PROFT(cond, slot)

constexpr uint32_t SB0 = 65536, HOLE = 90112, SA2 = 98304, SB1 = 131072, SB2 = 155648, STG = 180224;
constexpr uint32_t KVA = 98304, KVB = 0, QO = 65536;
constexpr uint32_t MISC = 229376, ONES = MISC, BARS = MISC + 1024, INFO = BARS + 352, CS = MISC + 1408, WR = MISC + 2176, PATCH = MISC + 2432, X2SEG = MISC + 2816;
constexpr uint32_t PAR = HOLE, HV = HOLE + 2048, RED = HOLE + 6144;
constexpr uint32_t SMEM_BYTES = 232448;
enum { B_FULLQ = 0, B_EMPTYQ = 3, B_FULLW = 6, B_EMPTYW = 10, B_KVFULL = 14, B_KVRDY = 22, B_ORDY = 26, B_XRDY = 34,
       B_HAFREE = 36, B_OFREE = 37, B_XFREE = 38, B_RES = 39, B_PAR = 40, B_STG = 41, B_COUNT = 44 };
#define BAR(x) (sb + BARS + 8 * (x))
DEVI uint32_t qa_off(int s) { return s == 2 ? SA2 : (uint32_t)s * 32768u; }
DEVI uint32_t qb_off(int s) { return s == 0 ? SB0 : (s == 1 ? SB1 : SB2); }
DEVI uint32_t w_off(int s) { return 98304u + (uint32_t)((s + 2) & 3) * 32768u; }

struct Params {
  CUtensorMap mX, mXh, mWq, mWo, mWg, mWu, mWp;
  const bf16 *x0, *wo, *wr, *wd;
  bf16* out;
};
constexpr float LN_EPS = 1e-5f;
constexpr float QSCALE = 0.17677669529663687f * 1.4426950408889634f;

DEVI void qk_issue(float (&s)[32], uint32_t qd, uint32_t kd) {
  wgmma_ss_n64<0>(s, mkd<HI64>(qd), mkd<HI64>(kd), 0);
  wgmma_ss_n64<0>(s, mkd<HI64>(qd + 2), mkd<HI64>(kd + 2), 1);
}
template<bool FIRST> DEVI void pv_issue(float (&o)[20], const uint32_t (&p)[16], uint32_t vd) {
  #pragma unroll
  for (int ks = 0; ks < 4; ks++)
    wgmma_rs_n40<1>(o, p[ks * 4], p[ks * 4 + 1], p[ks * 4 + 2], p[ks * 4 + 3], mkd<HI64>(vd + VOFF(ks * 64)), (FIRST && ks == 0) ? 0 : 1);
}
DEVI void exp_pack(const float (&s)[32], uint32_t (&p)[16]) {
  #pragma unroll
  for (int j = 0; j < 16; j++) p[j] = pack_bf16(ex2f(s[2 * j]), ex2f(s[2 * j + 1]));
}
DEVI bool attn_finish(const float (&o)[20], uint32_t st, uint32_t bar) {
  const float lo = 5.421010862427522e-20f, hi = 1.8446744073709552e19f;
  bool ok = o[16] >= lo && o[16] <= hi && o[18] >= lo && o[18] <= hi;
  if (!__all_sync(0xffffffffu, ok)) return false;
  float i0 = __fdividef(1.f, o[16]), i1 = __fdividef(1.f, o[18]);
  int lane = threadIdx.x & 31, row = ((threadIdx.x >> 5) & 3) * 16 + (lane & 15);
  #pragma unroll
  for (int h = 0; h < 2; h++) {
    int c = 2 * h + (lane >> 4);
    stsm_x4(st + row * 64 + ((c ^ ((row >> 1) & 3)) << 4),
      pack_bf16(o[8 * h] * i0, o[8 * h + 1] * i0), pack_bf16(o[8 * h + 2] * i1, o[8 * h + 3] * i1),
      pack_bf16(o[8 * h + 4] * i0, o[8 * h + 5] * i0), pack_bf16(o[8 * h + 6] * i1, o[8 * h + 7] * i1));
  }
  warp_signal(bar);
  return true;
}
DEVI float dot32(const float (&q)[32], uint32_t a, int r) {
  float s = 0.f;
  #pragma unroll
  for (int c = 0; c < 4; c++) {
    uint4 v = lds128(a + r * 64 + ((c ^ ((r >> 1) & 3)) << 4));
    s = fmaf(q[8 * c], bf_lo(v.x), s); s = fmaf(q[8 * c + 1], bf_hi(v.x), s); s = fmaf(q[8 * c + 2], bf_lo(v.y), s); s = fmaf(q[8 * c + 3], bf_hi(v.y), s);
    s = fmaf(q[8 * c + 4], bf_lo(v.z), s); s = fmaf(q[8 * c + 5], bf_hi(v.z), s); s = fmaf(q[8 * c + 6], bf_lo(v.w), s); s = fmaf(q[8 * c + 7], bf_hi(v.w), s);
  }
  return s;
}
DEVI void attn_exact(uint32_t st, uint32_t kv, int t, bool hasprev, uint32_t bar) {
  int lane = threadIdx.x & 31, row = ((threadIdx.x >> 5) & 3) * 16 + (lane >> 1);
  float q[32], o[32];
  #pragma unroll
  for (int c = 0; c < 4; c++) {
    uint4 v = lds128(st + row * 64 + ((c ^ ((row >> 1) & 3)) << 4));
    q[8 * c] = bf_lo(v.x); q[8 * c + 1] = bf_hi(v.x); q[8 * c + 2] = bf_lo(v.y); q[8 * c + 3] = bf_hi(v.y);
    q[8 * c + 4] = bf_lo(v.z); q[8 * c + 5] = bf_hi(v.z); q[8 * c + 6] = bf_lo(v.w); q[8 * c + 7] = bf_hi(v.w);
  }
  int k1 = 256 + t * 64 + row, k0 = hasprev ? k1 - 255 : 256;
  float m = -INFINITY, l = 0.f;
  #pragma unroll 1
  for (int k = k0 + (lane & 1); k <= k1; k += 2) m = fmaxf(m, dot32(q, kv + (k >> 6) * 8192, k & 63));
  m = fmaxf(m, __shfl_xor_sync(0xffffffffu, m, 1));
  #pragma unroll
  for (int e = 0; e < 32; e++) o[e] = 0.f;
  #pragma unroll 1
  for (int k = k0 + (lane & 1); k <= k1; k += 2) {
    int r = k & 63; uint32_t a = kv + (k >> 6) * 8192;
    float pr = ex2f(dot32(q, a, r) - m);
    l += pr;
    #pragma unroll
    for (int c = 0; c < 4; c++) {
      uint4 v = lds128(a + 4096 + r * 64 + ((c ^ ((r >> 1) & 3)) << 4));
      o[8 * c] = fmaf(pr, bf_lo(v.x), o[8 * c]); o[8 * c + 1] = fmaf(pr, bf_hi(v.x), o[8 * c + 1]);
      o[8 * c + 2] = fmaf(pr, bf_lo(v.y), o[8 * c + 2]); o[8 * c + 3] = fmaf(pr, bf_hi(v.y), o[8 * c + 3]);
      o[8 * c + 4] = fmaf(pr, bf_lo(v.z), o[8 * c + 4]); o[8 * c + 5] = fmaf(pr, bf_hi(v.z), o[8 * c + 5]);
      o[8 * c + 6] = fmaf(pr, bf_lo(v.w), o[8 * c + 6]); o[8 * c + 7] = fmaf(pr, bf_hi(v.w), o[8 * c + 7]);
    }
  }
  __syncwarp();
  l += __shfl_xor_sync(0xffffffffu, l, 1);
  float inv = __fdividef(1.f, l);
  #pragma unroll
  for (int e = 0; e < 32; e++) o[e] = (o[e] + __shfl_xor_sync(0xffffffffu, o[e], 1)) * inv;
  if (!(lane & 1)) {
    #pragma unroll
    for (int c = 0; c < 4; c++)
      sts128(st + row * 64 + ((c ^ ((row >> 1) & 3)) << 4), make_uint4(pack_bf16(o[8 * c], o[8 * c + 1]), pack_bf16(o[8 * c + 2], o[8 * c + 3]),
                                                                      pack_bf16(o[8 * c + 4], o[8 * c + 5]), pack_bf16(o[8 * c + 6], o[8 * c + 7])));
  }
  warp_signal(bar);
}

template<int J0> DEVI void qkv_store(const float (&aX)[96], const float (&aY)[96], const float2 (&pr)[4], uint32_t csa, uint32_t dX, uint32_t dY, uint32_t x0) {
  #pragma unroll
  for (int hh = 0; hh < 2; hh++) {
    constexpr int dummy = 0; (void)dummy;
    const int j = J0 + 2 * hh;
    float2 ca = lds64f(csa + j * 32), cb = lds64f(csa + j * 32 + 32);
    uint32_t off = x0 ^ (hh << 5);
    #define EL(a, e, P, C) fmaf(a[4 * j + (e)], pr[P].x, pr[P].y * (C))
    stsm_x4(dX + off, pack_bf16(EL(aX, 0, 0, ca.x), EL(aX, 1, 0, ca.y)), pack_bf16(EL(aX, 2, 1, ca.x), EL(aX, 3, 1, ca.y)),
                      pack_bf16(EL(aX, 4, 0, cb.x), EL(aX, 5, 0, cb.y)), pack_bf16(EL(aX, 6, 1, cb.x), EL(aX, 7, 1, cb.y)));
    stsm_x4(dY + off, pack_bf16(EL(aY, 0, 2, ca.x), EL(aY, 1, 2, ca.y)), pack_bf16(EL(aY, 2, 3, ca.x), EL(aY, 3, 3, ca.y)),
                      pack_bf16(EL(aY, 4, 2, cb.x), EL(aY, 5, 2, cb.y)), pack_bf16(EL(aY, 6, 3, cb.x), EL(aY, 7, 3, cb.y)));
    #undef EL
  }
}

template<bool FIRST> DEVI void qkv_block(float (&aX)[96], float (&aY)[96], uint32_t sb16, int s, int tX, int tY) {
  uint32_t a16 = sb16 + (qa_off(s) >> 4), b16 = (sb16 + (qb_off(s) >> 4)) | ((8192u >> 4) << 16);
  uint32_t ax = (a16 + tX * 512) | 0x10000u, ay = (a16 + tY * 512) | 0x10000u;
  wg_fence();
  #pragma unroll
  for (int ks = 0; ks < 4; ks++) {
    wgmma_ss_n192<1>(aX, mkd<HI128>(ax + ks * 2), mkd<HI128>(b16 + ks * 128), !(FIRST && ks == 0));
    wgmma_ss_n192<1>(aY, mkd<HI128>(ay + ks * 2), mkd<HI128>(b16 + ks * 128), !(FIRST && ks == 0));
  }
  wg_commit();
}
template<bool FIRST> DEVI void wo_block(float (&acc)[64], uint32_t sb16, int s, int wg) {
  uint32_t a16 = (sb16 + (w_off(s) >> 4) + wg * 256) | 0x10000u, b16 = (sb16 + (w_off(s) >> 4) + 1024) | ((8192u >> 4) << 16);
  wg_fence();
  #pragma unroll
  for (int ks = 0; ks < 4; ks++)
    wgmma_ss_n128<1>(acc, mkd<HI64>(a16 + (ks >> 1) * 512 + (ks & 1) * 2), mkd<HI128>(b16 + ks * 128), !(FIRST && ks == 0));
  wg_commit();
}
DEVI void consumer(const Params& P, uint32_t sb, int wg, uint32_t tag0) {
  const int tid = threadIdx.x & 127, lane = tid & 31, w = tid >> 5;
  const int bi = blockIdx.x >> 4, bp = blockIdx.x & 15, rh = bp & 1, bc = bp >> 1;
  const int tX = 3 - wg, tY = wg;
  const uint32_t sb16 = (sb & 0x3FFFFu) >> 4;
  uint32_t phq = 0;
  #pragma unroll 1
  for (int L = 0; L < 2; L++) {
    const uint32_t tag = tag0 + L;
    {
      float aX[96], aY[96];
      int s = 1, ps = 0;
      mbar_wait(BAR(B_FULLQ), phq & 1);
      phq ^= 1u;
      PROFT(threadIdx.x == 0, L * 8 + 1);
      qkv_block<true>(aX, aY, sb16, 0, tX, tY);
      #pragma unroll 1
      for (int n = 1; n < 16; n++) {
        mbar_wait(BAR(B_FULLQ + s), (phq >> s) & 1);
        phq ^= 1u << s;
        qkv_block<false>(aX, aY, sb16, s, tX, tY);
        wg_wait<1>(); if (tid == 0) mbar_arrive(BAR(B_EMPTYQ + ps));
        ps = s; s = (s == 2) ? 0 : s + 1;
      }
      mbar_wait(BAR(B_PAR), L);
      float2 pr[4];
      { uint32_t pa = sb + PAR + (w * 16 + (lane >> 2)) * 8;
        pr[0] = lds64f(pa + tX * 512); pr[1] = lds64f(pa + tX * 512 + 64); pr[2] = lds64f(pa + tY * 512); pr[3] = lds64f(pa + tY * 512 + 64); }
      int prow = (int)lds32(sb + INFO) - bi * 256;
      wg_wait<0>();
      keep(aX); keep(aY);
      if (tid == 0) mbar_arrive(BAR(B_EMPTYQ + ps));
      PROFT(threadIdx.x == 0, L * 8 + 2);
      bar_sync(1, 256);
      const int srow = w * 16 + (lane & 15);
      const uint32_t x0 = srow * 64 + (((lane >> 4) ^ ((srow >> 1) & 3)) << 4);
      const uint32_t csa = sb + CS + (lane & 3) * 8;
      const bool pmine = (prow >> 4) == tX * 4 + w || (prow >> 4) == tY * 4 + w;
      const uint32_t poff = (prow & 63) * 64 + (((lane & 3) ^ ((prow >> 1) & 3)) << 4);
      qkv_store<8>(aX, aY, pr, csa, sb + KVA + (4 + tX) * 8192, sb + KVA + (4 + tY) * 8192, x0);
      qkv_store<16>(aX, aY, pr, csa, sb + KVA + (4 + tX) * 8192 + 4096, sb + KVA + (4 + tY) * 8192 + 4096, x0);
      if (pmine) { __syncwarp(); if (lane < 8) sts128(sb + KVA + (4 + (prow >> 6)) * 8192 + (lane >> 2) * 4096 + poff, lds128(sb + PATCH + 128 + (lane >> 2) * 128 + (lane & 3) * 16)); }
      warp_signal(BAR(B_KVRDY + wg * 2));
      qkv_store<12>(aX, aY, pr, csa, sb + KVB + (4 + tX) * 8192, sb + KVB + (4 + tY) * 8192, x0);
      qkv_store<20>(aX, aY, pr, csa, sb + KVB + (4 + tX) * 8192 + 4096, sb + KVB + (4 + tY) * 8192 + 4096, x0);
      if (pmine) { __syncwarp(); if (lane < 8) sts128(sb + KVB + (4 + (prow >> 6)) * 8192 + (lane >> 2) * 4096 + poff, lds128(sb + PATCH + 192 + (lane >> 2) * 128 + (lane & 3) * 16)); }
      warp_signal(BAR(B_KVRDY + wg * 2 + 1));
      #pragma unroll
      for (int e = 0; e < 4; e++) { pr[e].x *= QSCALE; pr[e].y *= QSCALE; }
      qkv_store<0>(aX, aY, pr, csa, sb + QO + tX * 4096, sb + QO + tY * 4096, x0);
      qkv_store<4>(aX, aY, pr, csa, sb + QO + 16384 + tX * 4096, sb + QO + 16384 + tY * 4096, x0);
      if (pmine) { __syncwarp(); if (lane < 8) sts128(sb + QO + (lane >> 2) * 16384 + (prow >> 6) * 4096 + poff, lds128(sb + PATCH + lane * 16)); }
      fence_async_smem();
      bar_sync(1, 256);
    }
    PROFT(threadIdx.x == 0, L * 8 + 3);
    {
      float s0[32], s1[32], sx[32], o[20];
      uint32_t p0[16], p1[16], px[16];
      const int tdiag = w * 16 + (lane >> 2) - 2 * (lane & 3);
      const uint32_t ones16 = sb16 + (ONES >> 4);
      uint32_t redo = 0;
      wg_fence();
      qk_issue(s0, (sb16 + ((QO + tX * 4096) >> 4)) | 0x10000u, (sb16 + ((KVA + (tX + 3) * 8192) >> 4)) | 0x10000u);
      wg_commit();
      #pragma unroll 1
      for (int u = 0; u < 4; u++) {
        const int h = u >> 1, t = (u & 1) ? tY : tX;
        const uint32_t k16 = sb16 + ((h ? KVB : KVA) >> 4) + t * 512, kd = k16 | 0x10000u;
        const uint32_t qd = (sb16 + (QO >> 4) + (h * 4 + t) * 256) | 0x10000u;
        const uint32_t fb = BAR(B_KVFULL + h * 4 + t);
        #define VD(b) (VOFF(k16 + (b) * 512 + 256) + (((bi == 0 && t + (b) < 4) ? k16 + (b) * 512 + 448 : ones16) << 16))
        if (t + 2 < 4) mbar_wait(fb + 16, L);
        wg_wait<0>(); keep(s0);
        wg_fence(); qk_issue(s1, qd, kd + 2 * 512); wg_commit();
        exp_pack(s0, p0);
        wg_fence(); pv_issue<true>(o, p0, VD(3)); wg_commit();
        if (t + 1 < 4) mbar_wait(fb + 8, L);
        wg_wait<1>(); keep(s1);
        wg_fence(); qk_issue(s0, qd, kd + 1 * 512); wg_commit();
        exp_pack(s1, p1);
        wg_fence(); pv_issue<false>(o, p1, VD(2)); wg_commit();
        mbar_wait(fb, L);
        wg_wait<1>(); keep(s0); keep(p0);
        wg_fence(); qk_issue(s1, qd, kd); qk_issue(sx, qd, kd + 4 * 512); wg_commit();
        exp_pack(s0, p0);
        wg_fence(); pv_issue<false>(o, p0, VD(1)); wg_commit();
        const int un = (u + 1) & 3, hn = un >> 1, tn = (un & 1) ? tY : tX;
        if (tn == 0) mbar_wait(BAR(B_KVFULL + hn * 4 + 3), L);
        wg_wait<1>(); keep(s1); keep(sx); keep(p1);
        #pragma unroll
        for (int e = 0; e < 32; e++) { int c = 8 * (e >> 2) + (e & 1) - 8 * ((e >> 1) & 1); s1[e] = (c > tdiag) ? s1[e] : sx[e]; }
        wg_fence();
        qk_issue(s0, (sb16 + (QO >> 4) + (hn * 4 + tn) * 256) | 0x10000u, (sb16 + ((u < 2 && hn == 0 ? KVA : KVB) >> 4) + (tn + 3) * 512) | 0x10000u);
        wg_commit();
        exp_pack(s1, p1);
        #pragma unroll
        for (int e = 0; e < 16; e++) {
          int c = 8 * (e >> 1) - 8 * (e & 1);
          uint32_t msk = ((c > tdiag) ? 0xFFFFu : 0u) | ((c + 1 > tdiag) ? 0xFFFF0000u : 0u);
          px[e] = p1[e] & ~msk; p1[e] &= msk;
        }
        wg_fence(); pv_issue<false>(o, p1, VD(0)); pv_issue<false>(o, px, VD(4)); wg_commit();
        wg_wait<0>(); keep(o); keep(p0); keep(p1); keep(px); keep(s0);
        #undef VD
        if (!attn_finish(o, sb + QO + (h * 4 + t) * 4096, BAR(B_ORDY + wg * 4 + u))) redo |= 1u << u;
      }
      if (redo) {
        #pragma unroll 1
        for (int u = 0; u < 4; u++) if ((redo >> u) & 1) {
          const int h = u >> 1, t = (u & 1) ? tY : tX;
          attn_exact(sb + QO + (h * 4 + t) * 4096, sb + (h ? KVB : KVA), t, bi > 0, BAR(B_ORDY + wg * 4 + u));
        }
      }
    }
    PROFT(threadIdx.x == 0, L * 8 + 4);
    {
      float acc[64];
      const int grow = bi * 256 + rh * 128 + wg * 64 + w * 16 + (lane >> 2);
      float al0 = 1.f, be0 = 0.f, al1 = 1.f, be1 = 0.f;
      const int idx0 = (int)lds32(sb + INFO);
      if (L) {
        uint4 a = ld_ll(&g_statF[grow]), b = ld_ll(&g_statF[grow + 8]);
        float r0 = rsqrtf(__uint_as_float(a.y) + LN_EPS), r1 = rsqrtf(__uint_as_float(b.y) + LN_EPS);
        if (grow != idx0) { al0 = 1.f + r0; be0 = -__uint_as_float(a.x) * r0; }
        if (grow + 8 != idx0) { al1 = 1.f + r1; be1 = -__uint_as_float(b.x) * r1; }
      }
      mbar_wait(BAR(B_FULLW), 0);
      PROFT(threadIdx.x == 0, L * 8 + 5);
      wo_block<true>(acc, sb16, 0, wg);
      #pragma unroll 1
      for (int n = 1; n < 16; n++) {
        mbar_wait(BAR(B_FULLW + (n & 3)), (n >> 2) & 1);
        wo_block<false>(acc, sb16, n & 3, wg);
        wg_wait<1>(); if (tid == 0) mbar_arrive(BAR(B_EMPTYW + ((n - 1) & 3)));
      }
      mbar_wait(BAR(B_RES), L);
      const int srow = wg * 64 + w * 16 + (lane & 15);
      const uint32_t ra = sb + rh * 16384 + srow * 128, sw = ((lane >> 4) ^ (srow & 7)) << 4;
      if ((idx0 >> 4) == (grow >> 4)) {
        int r = idx0 & 127;
        if (lane < 16) sts128(sb + (lane >> 3) * 32768 + rh * 16384 + r * 128 + (((lane & 7) ^ (r & 7)) << 4), lds128(sb + X2SEG + lane * 16));
        __syncwarp();
      }
      wg_wait<0>(); keep(acc);
      if (tid == 0) mbar_arrive(BAR(B_EMPTYW + 3));
      PROFT(threadIdx.x == 0, L * 8 + 6);
      float s1a = 0.f, s2a = 0.f, da = 0.f, s1b = 0.f, s2b = 0.f, db = 0.f;
      #pragma unroll
      for (int jj = 0; jj < 8; jj++) {
        uint32_t r0, r1, r2, r3, ad = (ra + (jj >> 2) * 32768) + (sw ^ ((jj & 3) << 5));
        ldsm_x4(ad, r0, r1, r2, r3);
        uint32_t wa = lds32(sb + WR + jj * 32 + (lane & 3) * 4), wb = lds32(sb + WR + jj * 32 + 16 + (lane & 3) * 4);
        float* a = acc + 8 * jj;
        a[0] += fmaf(bf_lo(r0), al0, be0); a[1] += fmaf(bf_hi(r0), al0, be0); a[2] += fmaf(bf_lo(r1), al1, be1); a[3] += fmaf(bf_hi(r1), al1, be1);
        a[4] += fmaf(bf_lo(r2), al0, be0); a[5] += fmaf(bf_hi(r2), al0, be0); a[6] += fmaf(bf_lo(r3), al1, be1); a[7] += fmaf(bf_hi(r3), al1, be1);
        stsm_x4(ad, pack_bf16(a[0], a[1]), pack_bf16(a[2], a[3]), pack_bf16(a[4], a[5]), pack_bf16(a[6], a[7]));
        s1a += (a[0] + a[1]) + (a[4] + a[5]); s1b += (a[2] + a[3]) + (a[6] + a[7]);
        s2a = fmaf(a[0], a[0], s2a); s2a = fmaf(a[1], a[1], s2a); s2a = fmaf(a[4], a[4], s2a); s2a = fmaf(a[5], a[5], s2a);
        s2b = fmaf(a[2], a[2], s2b); s2b = fmaf(a[3], a[3], s2b); s2b = fmaf(a[6], a[6], s2b); s2b = fmaf(a[7], a[7], s2b);
        da = fmaf(a[0], bf_lo(wa), da); da = fmaf(a[1], bf_hi(wa), da); da = fmaf(a[4], bf_lo(wb), da); da = fmaf(a[5], bf_hi(wb), da);
        db = fmaf(a[2], bf_lo(wa), db); db = fmaf(a[3], bf_hi(wa), db); db = fmaf(a[6], bf_lo(wb), db); db = fmaf(a[7], bf_hi(wb), db);
      }
      warp_signal(BAR(B_XRDY + wg));
      {
        bool odd = lane & 1;
        float u1 = (odd ? s1b : s1a) + __shfl_xor_sync(0xffffffffu, odd ? s1a : s1b, 1);
        float u2 = (odd ? s2b : s2a) + __shfl_xor_sync(0xffffffffu, odd ? s2a : s2b, 1);
        float u3 = (odd ? db : da) + __shfl_xor_sync(0xffffffffu, odd ? da : db, 1);
        u1 += __shfl_xor_sync(0xffffffffu, u1, 2); u2 += __shfl_xor_sync(0xffffffffu, u2, 2); u3 += __shfl_xor_sync(0xffffffffu, u3, 2);
        if (!(lane & 2)) st_ll(&g_statP[bc][grow + (lane & 1) * 8], __float_as_uint(u1), __float_as_uint(u2), __float_as_uint(u3), tag);
      }
      PROFT(threadIdx.x == 0, L * 8 + 7);
      if (L) {
        uint4 a = poll_ll(&g_statF[grow], 0xffffffffu, tag + 1), b = poll_ll(&g_statF[grow + 8], 0xffffffffu, tag + 1);
        float r0 = rsqrtf(__uint_as_float(a.y) + LN_EPS), r1 = rsqrtf(__uint_as_float(b.y) + LN_EPS);
        al0 = 1.f + r0; be0 = -__uint_as_float(a.x) * r0; al1 = 1.f + r1; be1 = -__uint_as_float(b.x) * r1;
        mbar_wait(BAR(B_XFREE), 1);
        #pragma unroll
        for (int jj = 0; jj < 8; jj++) {
          const float* a = acc + 8 * jj;
          stsm_x4((ra + (jj >> 2) * 32768) + (sw ^ ((jj & 3) << 5)),
                  pack_bf16(fmaf(a[0], al0, be0), fmaf(a[1], al0, be0)), pack_bf16(fmaf(a[2], al1, be1), fmaf(a[3], al1, be1)),
                  pack_bf16(fmaf(a[4], al0, be0), fmaf(a[5], al0, be0)), pack_bf16(fmaf(a[6], al1, be1), fmaf(a[7], al1, be1)));
        }
        mbar_wait(BAR(B_PAR), 0);
        const int idx1 = (int)lds32(sb + INFO + 4);
        __syncwarp();
        #pragma unroll
        for (int it = 0; it < 8; it++) {
          int r = wg * 64 + w * 16 + it * 2 + (lane >> 4), ch = lane & 15, gr = bi * 256 + rh * 128 + r;
          uint4 v = lds128(sb + (ch >> 3) * 32768 + rh * 16384 + r * 128 + (((ch & 7) ^ (r & 7)) << 4));
          if (gr != idx1) *(uint4*)(P.out + (size_t)gr * 1024 + bc * 128 + ch * 8) = v;
        }
        PROFT(threadIdx.x == 0, 16);
      }
    }
  }
}

DEVI void loader(const Params& P, uint32_t sb, uint32_t tag0) {
  const int lane = threadIdx.x & 31;
  const int bi = blockIdx.x >> 4, bp = blockIdx.x & 15, rh = bp & 1, bc = bp >> 1;
  uint32_t phq = 7;
  #pragma unroll 1
  for (int L = 0; L < 2; L++) {
    const uint32_t tag = tag0 + L;
    int s = 0;
    uint32_t rdy = 0;
    #pragma unroll 1
    for (int n = 0; n < 16; n++) {
      const int kb = L ? ((2 * bc + n) & 15) : n;
      mbar_wait(BAR(B_EMPTYQ + s), (phq >> s) & 1);
      phq ^= 1u << s;
      if (L && n == 1) { for (int q = 0; q < 4; q++) mbar_wait(BAR(B_EMPTYW + q), 1); }
      if (lane == 0) { mbar_expect_tx(BAR(B_FULLQ + s), 57344); tma_3d(sb + qb_off(s), &P.mWq, bp * 64, kb * 64, 0, BAR(B_FULLQ + s)); }
      if (L) {
        if (n == 0) mbar_wait(BAR(B_XFREE), 0);
        int it = 0;
        while (((rdy >> (2 * kb)) & 3) != 3) {
          uint32_t a = ld_rlx(&g_flagX[bi][2 * lane]), b = ld_rlx(&g_flagX[bi][2 * lane + 1]);
          rdy = __ballot_sync(0xffffffffu, a == tag0 && b == tag0);
          if (++it > SPIN_MAX) __trap();
        }
        if (lane == 0) { fence_async_glob(); bulk_g2s(sb + qa_off(s), g_x[bi][kb], 32768, BAR(B_FULLQ + s)); }
      } else if (lane == 0) tma_2d(sb + qa_off(s), &P.mX, kb * 64, bi * 256, BAR(B_FULLQ + s));
      s = (s == 2) ? 0 : s + 1;
    }
    for (int q = 0; q < 3; q++) mbar_wait(BAR(B_EMPTYQ + q), (phq >> q) & 1);
    mbar_wait(BAR(B_PAR), L);
    if (lane == 0) {
      for (int q = 0; q < 2; q++) { mbar_expect_tx(BAR(B_FULLW + q), 32768); tma_5d(sb + w_off(q) + 16384, &P.mWo, 0, 0, 0, 2 * ((bc + q) & 7), 2 * bc, BAR(B_FULLW + q)); }
    }
    rdy = bi ? 0u : 0xffu;
    #pragma unroll 1
    for (int q = 0; q < 8; q++) {
      const int ch = q ^ 3;
      int it = 0;
      while (!((rdy >> ch) & 1)) {
        rdy = __ballot_sync(0xffffffffu, ld_rlx(&g_flagKV[blockIdx.x - 16][lane & 7]) == tag);
        if (++it > SPIN_MAX) __trap();
      }
      if (lane == 0) {
        fence_async_glob();
        mbar_expect_tx(BAR(B_KVFULL + ch), 8192);
        bulk_g2s(sb + ((ch >> 2) ? KVB : KVA) + (ch & 3) * 8192, bi ? g_kv[blockIdx.x - 16][ch] : g_zero, 8192, BAR(B_KVFULL + ch));
      }
    }
    #pragma unroll 1
    for (int n = 0; n < 16; n++) {
      const int q = n & 3, hb = n >> 3, j = (bc + n) & 7;
      if ((n & 7) == 0) rdy = 0;
      if (n >= 2) {
        if (n == 2) mbar_wait(BAR(B_HAFREE), L);
        if (n >= 4) mbar_wait(BAR(B_EMPTYW + q), ((n >> 2) - 1) & 1);
        if (lane == 0) { mbar_expect_tx(BAR(B_FULLW + q), 32768); tma_5d(sb + w_off(q) + 16384, &P.mWo, 0, 0, hb, 2 * j, 2 * bc, BAR(B_FULLW + q)); }
      }
      int it = 0;
      while (((rdy >> (4 * j)) & 15) != 15) {
        rdy = __ballot_sync(0xffffffffu, ld_rlx(&g_flagO[bi][hb][rh][lane]) == tag);
        if (++it > SPIN_MAX) __trap();
      }
      if (lane == 0) { fence_async_glob(); bulk_g2s(sb + w_off(q), g_o[bi][hb][j][rh], 16384, BAR(B_FULLW + q)); }
      if (n == 10) {
        mbar_wait(BAR(B_OFREE), L);
        if (lane == 0) {
          mbar_expect_tx(BAR(B_RES), 32768);
          for (int e = 0; e < 2; e++) {
            if (L) bulk_g2s(sb + e * 32768 + rh * 16384, g_x[bi][2 * bc + e] + rh * 1024, 16384, BAR(B_RES));
            else tma_2d(sb + e * 32768 + rh * 16384, &P.mXh, bc * 128 + e * 64, bi * 256 + rh * 128, BAR(B_RES));
          }
        }
      }
    }
  }
}

DEVI void storer(uint32_t sb, int wg, uint32_t tag0) {
  const int bi = blockIdx.x >> 4, bp = blockIdx.x & 15, rh = bp & 1, bc = bp >> 1;
  const int tX = 3 - wg, tY = wg;
  #pragma unroll 1
  for (int L = 0; L < 2; L++) {
    const uint32_t tag = tag0 + L;
    if (bi < 7) {
      for (int h = 0; h < 2; h++) {
        mbar_wait(BAR(B_KVRDY + wg * 2 + h), L);
        bulk_s2g(g_kv[blockIdx.x][h * 4 + tX], sb + (h ? KVB : KVA) + (4 + tX) * 8192, 8192);
        bulk_s2g(g_kv[blockIdx.x][h * 4 + tY], sb + (h ? KVB : KVA) + (4 + tY) * 8192, 8192);
      }
      unsigned* f = g_flagKV[blockIdx.x];
      bulk_wait<3>(); st_rlx(f + tX, tag);
      bulk_wait<2>(); st_rlx(f + tY, tag);
      bulk_wait<1>(); st_rlx(f + 4 + tX, tag);
      bulk_wait<0>(); st_rlx(f + 4 + tY, tag);
    }
    #pragma unroll 1
    for (int u = 0; u < 4; u++) {
      const int h = u >> 1, t = (u & 1) ? tY : tX;
      mbar_wait(BAR(B_ORDY + wg * 4 + u), L);
      bulk_s2g(g_o[bi][h][bc][t >> 1] + (rh * 2 + (t & 1)) * 256, sb + QO + (h * 4 + t) * 4096, 4096);
      if (u == 1) mbar_arrive(BAR(B_HAFREE));
      bulk_wait<0>();
      st_rlx(&g_flagO[bi][h][t >> 1][bp * 2 + (t & 1)], tag);
    }
    mbar_arrive(BAR(B_OFREE));
    mbar_wait(BAR(B_XRDY + wg), L);
    bulk_s2g(g_x[bi][2 * bc] + rh * 1024 + wg * 512, sb + rh * 16384 + wg * 8192, 8192);
    bulk_s2g(g_x[bi][2 * bc + 1] + rh * 1024 + wg * 512, sb + 32768 + rh * 16384 + wg * 8192, 8192);
    bulk_wait<1>(); st_rlx(&g_flagX[bi][(2 * bc) * 4 + rh * 2 + wg], tag);
    bulk_wait<0>(); st_rlx(&g_flagX[bi][(2 * bc + 1) * 4 + rh * 2 + wg], tag);
    mbar_arrive(BAR(B_XFREE));
  }
}

DEVI void fma8(float (&a)[8], uint4 v, float h) {
  a[0] = fmaf(bf_lo(v.x), h, a[0]); a[1] = fmaf(bf_hi(v.x), h, a[1]); a[2] = fmaf(bf_lo(v.y), h, a[2]); a[3] = fmaf(bf_hi(v.y), h, a[3]);
  a[4] = fmaf(bf_lo(v.z), h, a[4]); a[5] = fmaf(bf_hi(v.z), h, a[5]); a[6] = fmaf(bf_lo(v.w), h, a[6]); a[7] = fmaf(bf_hi(v.w), h, a[7]);
}
DEVI float warp_sum(float v) {
  #pragma unroll
  for (int o = 16; o; o >>= 1) v += __shfl_xor_sync(0xffffffffu, v, o);
  return v;
}
DEVI float aux_sum(float v, uint32_t red) {
  v = warp_sum(v);
  if ((threadIdx.x & 31) == 0) sts32f(red + ((threadIdx.x >> 5) & 3) * 4, v);
  bar_sync(2, 128);
  uint4 r = lds128(red);
  return (__uint_as_float(r.x) + __uint_as_float(r.y)) + (__uint_as_float(r.z) + __uint_as_float(r.w));
}
DEVI void stg_issue(const Params& P, uint32_t sb, int c, int slot) {
  uint32_t d = sb + STG + slot * 16384, b = BAR(B_STG + slot);
  mbar_expect_tx(b, 16384);
  if (c < 8) { tma_2d(d, &P.mWg, blockIdx.x * 32, c * 128, b); tma_2d(d + 8192, &P.mWu, blockIdx.x * 32, c * 128, b); }
  else if (c < 12) bulk_g2s(d, P.wd + (size_t)(blockIdx.x * 32 + (c - 8) * 8) * 1024, 16384, b);
  else tma_2d(d, &P.mWp, blockIdx.x * 32, (c - 12) * 256, b);
}
DEVI void aux_argmax(float& r, int& idx, uint32_t red) {
  #pragma unroll
  for (int o = 16; o; o >>= 1) {
    float r2 = __shfl_xor_sync(0xffffffffu, r, o); int i2 = __shfl_xor_sync(0xffffffffu, idx, o);
    if (r2 > r || (r2 == r && i2 < idx)) { r = r2; idx = i2; }
  }
  if ((threadIdx.x & 31) == 0) sts64f(red + ((threadIdx.x >> 5) & 3) * 8, r, __int_as_float(idx));
  bar_sync(2, 128);
  #pragma unroll
  for (int q = 0; q < 4; q++) {
    float2 v = lds64f(red + q * 8); int i2 = __float_as_int(v.y);
    if (v.x > r || (v.x == r && i2 < idx)) { r = v.x; idx = i2; }
  }
}
DEVI void aux(const Params& P, uint32_t sb, uint32_t tag0, uint32_t epoch) {
  const int tid = threadIdx.x & 127, lane = tid & 31, w = tid >> 5;
  const int bid = blockIdx.x, bi = bid >> 4, bp = bid & 15, bc = bp >> 1;
  uint32_t phs = 0;
  float sumw;
  if (tid == 0) {
    mbar_expect_tx(BAR(B_STG), 49152);
    tma_3d(sb + STG, &P.mWq, bp * 64, bi * 128, 0, BAR(B_STG));
    tma_3d(sb + STG + 24576, &P.mWq, bp * 64, bi * 128 + 64, 0, BAR(B_STG));
    sts32(sb + INFO, 0x40000000u);
  }
  {
    uint4 v = __ldg((const uint4*)P.wr + tid);
    if ((tid >> 4) == bc) sts128(sb + WR + (tid & 15) * 16, v);
    sumw = aux_sum(((bf_lo(v.x) + bf_hi(v.x)) + (bf_lo(v.y) + bf_hi(v.y))) + ((bf_lo(v.z) + bf_hi(v.z)) + (bf_lo(v.w) + bf_hi(v.w))), sb + RED);
    sts64f(sb + ONES + tid * 8, __uint_as_float(0x3F803F80u), __uint_as_float(0x3F803F80u));
    fence_async_smem();
  }
  {
    int row = bi * 256 + bp * 16 + (tid >> 3);
    const uint4* src = (const uint4*)(P.x0 + (size_t)row * 1024) + (tid & 7);
    float s1 = 0.f, s2 = 0.f;
    #pragma unroll 4
    for (int it = 0; it < 16; it++) {
      uint4 v = __ldg(src + it * 8);
      float a;
      a = bf_lo(v.x); s1 += a; s2 = fmaf(a, a, s2); a = bf_hi(v.x); s1 += a; s2 = fmaf(a, a, s2);
      a = bf_lo(v.y); s1 += a; s2 = fmaf(a, a, s2); a = bf_hi(v.y); s1 += a; s2 = fmaf(a, a, s2);
      a = bf_lo(v.z); s1 += a; s2 = fmaf(a, a, s2); a = bf_hi(v.z); s1 += a; s2 = fmaf(a, a, s2);
      a = bf_lo(v.w); s1 += a; s2 = fmaf(a, a, s2); a = bf_hi(v.w); s1 += a; s2 = fmaf(a, a, s2);
    }
    #pragma unroll
    for (int o = 1; o < 8; o <<= 1) { s1 += __shfl_xor_sync(0xffffffffu, s1, o); s2 += __shfl_xor_sync(0xffffffffu, s2, o); }
    float m = s1 * (1.f / 1024.f), var = fmaxf(fmaf(-m, m, s2 * (1.f / 1024.f)), 0.f);
    if ((tid & 7) == 0) st_ll(&g_statF[row], __float_as_uint(m), __float_as_uint(var), 0u, tag0);
  }
  {
    mbar_wait(BAR(B_STG), 0); phs ^= 1;
    #pragma unroll 1
    for (int sec = 0; sec < 3; sec++) {
      float a[8] = {0.f, 0.f, 0.f, 0.f, 0.f, 0.f, 0.f, 0.f};
      #pragma unroll 2
      for (int n = 0; n < 8; n++) {
        int r = (tid >> 3) + (n & 3) * 16;
        fma8(a, lds128(sb + STG + (n >> 2) * 24576 + sec * 8192 + r * 128 + (((tid & 7) ^ (r & 7)) << 4)), 1.f);
      }
      #pragma unroll
      for (int e = 0; e < 8; e++) { a[e] += __shfl_xor_sync(0xffffffffu, a[e], 8); a[e] += __shfl_xor_sync(0xffffffffu, a[e], 16); }
      if (lane < 8) {
        uint32_t d = sb + HV + (w * 192 + sec * 64 + lane * 8) * 4;
        sts128(d, make_uint4(__float_as_uint(a[0]), __float_as_uint(a[1]), __float_as_uint(a[2]), __float_as_uint(a[3])));
        sts128(d + 16, make_uint4(__float_as_uint(a[4]), __float_as_uint(a[5]), __float_as_uint(a[6]), __float_as_uint(a[7])));
      }
    }
    bar_sync(2, 128);
    if (tid < 64) {
      float c[3];
      #pragma unroll
      for (int sec = 0; sec < 3; sec++) {
        uint32_t d = sb + HV + (sec * 64 + tid) * 4;
        c[sec] = (lds32f(d) + lds32f(d + 768)) + (lds32f(d + 1536) + lds32f(d + 2304));
      }
      st_ll(&g_csP[bp][bi][tid], __float_as_uint(c[0]), __float_as_uint(c[1]), __float_as_uint(c[2]), tag0);
      c[0] = c[1] = c[2] = 0.f;
      #pragma unroll 1
      for (int q = 0; q < 8; q++) {
        uint4 v = poll_ll(&g_csP[bp][q][tid], 0xffffffffu, tag0);
        c[0] += __uint_as_float(v.x); c[1] += __uint_as_float(v.y); c[2] += __uint_as_float(v.z);
      }
      sts32f(sb + CS + tid * 4, c[0]); sts32f(sb + CS + 256 + tid * 4, c[1]); sts32f(sb + CS + 512 + tid * 4, c[2]);
    }
    #pragma unroll 1
    for (int q = 0; q < 2; q++) {
      uint4 v = poll_ll(&g_statF[bi * 256 + q * 128 + tid], 0xffffffffu, tag0);
      float rs = rsqrtf(__uint_as_float(v.y) + LN_EPS);
      sts64f(sb + PAR + (q * 128 + tid) * 8, rs, -rs * __uint_as_float(v.x));
    }
    bar_sync(2, 128);
    if (tid == 0) { mbar_arrive(BAR(B_PAR)); bulk_prefetch(P.wo + bid * 8192, 16384); }
    PROFT(tid == 0, 17);
  }
  #pragma unroll 1
  for (int L = 0; L < 2; L++) {
    const uint32_t tag = tag0 + L, tag8 = (((epoch % 127u) + 1u) << 1) | L;
    const int nch = bid < 96 ? (L ? 12 : 16) : (bid < 112 ? 12 : 0);
    mbar_wait(BAR(B_KVRDY), L);
    if (bid < 112 && tid < 12) {
      if (tid < 8) { tma_prefetch_2d(&P.mWg, bid * 32, tid * 128); tma_prefetch_2d(&P.mWu, bid * 32, tid * 128); }
      else bulk_prefetch(P.wd + (size_t)(bid * 32 + (tid - 8) * 8) * 1024, 16384);
    }
    mbar_wait(BAR(B_OFREE), L); mbar_wait(BAR(B_XRDY), L); mbar_wait(BAR(B_XRDY + 1), L);
    if (tid == 0 && nch) { stg_issue(P, sb, 0, 0); stg_issue(P, sb, 1, 1); stg_issue(P, sb, 2, 2); }
    float r; int idx;
    {
      int row = bi * 256 + bp * 16 + (lane & 3) + w * 4;
      uint4 v = poll_ll(&g_statP[lane >> 2][row], 0xffffffffu, tag);
      float s1 = __uint_as_float(v.x), s2 = __uint_as_float(v.y), d = __uint_as_float(v.z);
      #pragma unroll
      for (int o = 4; o < 32; o <<= 1) { s1 += __shfl_xor_sync(0xffffffffu, s1, o); s2 += __shfl_xor_sync(0xffffffffu, s2, o); d += __shfl_xor_sync(0xffffffffu, d, o); }
      float m = s1 * (1.f / 1024.f), var = fmaxf(fmaf(-m, m, s2 * (1.f / 1024.f)), 0.f);
      if (lane < 4) st_ll(&g_statF[row], __float_as_uint(m), __float_as_uint(var), 0u, tag + 1);
      r = fmaf(-m, sumw, d) * rsqrtf(var + LN_EPS); idx = row;
      aux_argmax(r, idx, sb + RED);
      if (idx == row && lane < 4) st_ll(&g_best[bid], __float_as_uint(r), __float_as_uint(m), __float_as_uint(var), (tag << 11) | (uint32_t)row);
    }
    PROFT(tid == 0, 18 + L * 6);
    float m, rs;
    {
      uint4 v = poll_ll(&g_best[tid], 0xfffff800u, tag << 11);
      r = __uint_as_float(v.x); idx = v.w & 2047;
      int mine = idx;
      aux_argmax(r, idx, sb + RED + 64);
      if (mine == idx) { sts64f(sb + RED + 128, __uint_as_float(v.y), __uint_as_float(v.z)); if (L) sts32(sb + INFO + 4, idx); }
      if (lane < 16) { int it = 0; while (ld_rlx(&g_flagX[idx >> 8][lane * 4 + ((idx >> 6) & 3)]) != tag) if (++it > SPIN_MAX) __trap(); }
      bar_sync(2, 128);
      if (L && tid == 0) mbar_arrive(BAR(B_PAR));
      float2 mv = lds64f(sb + RED + 128);
      m = mv.x; rs = rsqrtf(mv.y + LN_EPS);
    }
    PROFT(tid == 0, 19 + L * 6);
    uint4 xr = ld_ll(&g_x[idx >> 8][tid >> 3][(idx & 255) * 8 + ((tid & 7) ^ (idx & 7))]);
    {
      uint32_t d = sb + HV + tid * 32;
      #define HN(x) __float_as_uint(bf_round(((x) - m) * rs))
      sts128(d, make_uint4(HN(bf_lo(xr.x)), HN(bf_hi(xr.x)), HN(bf_lo(xr.y)), HN(bf_hi(xr.y))));
      sts128(d + 16, make_uint4(HN(bf_lo(xr.z)), HN(bf_hi(xr.z)), HN(bf_lo(xr.w)), HN(bf_hi(xr.w))));
      #undef HN
      if (tid == bid) sts128(sb + RED + 144, xr);
      bar_sync(2, 128);
    }
    int slot = 0;
    if (nch) {
      float a[8] = {0.f, 0.f, 0.f, 0.f, 0.f, 0.f, 0.f, 0.f};
      #pragma unroll 1
      for (int c = 0; c < 8; c++) {
        mbar_wait(BAR(B_STG + slot), (phs >> slot) & 1); phs ^= 1u << slot;
        uint32_t wa = sb + STG + slot * 16384 + w * 4096 + lane * 16, ha = sb + HV + (c * 128 + (w & 1) * 64 + (lane >> 2)) * 4;
        #pragma unroll 2
        for (int n = 0; n < 8; n++) fma8(a, lds128(wa + n * 512), lds32f(ha + n * 32));
        bar_sync(2, 128);
        if (tid == 0) stg_issue(P, sb, c + 3, slot);
        slot = slot == 2 ? 0 : slot + 1;
      }
      #pragma unroll
      for (int e = 0; e < 8; e++) { a[e] += __shfl_xor_sync(0xffffffffu, a[e], 4); a[e] += __shfl_xor_sync(0xffffffffu, a[e], 8); a[e] += __shfl_xor_sync(0xffffffffu, a[e], 16); }
      if (lane < 4) {
        uint32_t d = sb + RED + 256 + w * 128 + lane * 32;
        sts128(d, make_uint4(__float_as_uint(a[0]), __float_as_uint(a[1]), __float_as_uint(a[2]), __float_as_uint(a[3])));
        sts128(d + 16, make_uint4(__float_as_uint(a[4]), __float_as_uint(a[5]), __float_as_uint(a[6]), __float_as_uint(a[7])));
      }
      bar_sync(2, 128);
      float act;
      { uint32_t d = sb + RED + 256 + lane * 4;
        float g = bf_round(lds32f(d) + lds32f(d + 128)), u = bf_round(lds32f(d + 256) + lds32f(d + 384));
        act = bf_round(bf_round(g / (1.f + __expf(-g))) * u); }
      PROFT(tid == 0, 20 + L * 6);
      #pragma unroll
      for (int e = 0; e < 8; e++) a[e] = 0.f;
      #pragma unroll 1
      for (int c = 8; c < 12; c++) {
        mbar_wait(BAR(B_STG + slot), (phs >> slot) & 1); phs ^= 1u << slot;
        uint32_t wa = sb + STG + slot * 16384 + tid * 16;
        #pragma unroll 2
        for (int n = 0; n < 8; n++) fma8(a, lds128(wa + n * 2048), __shfl_sync(0xffffffffu, act, (c - 8) * 8 + n));
        if (c + 3 < nch) { bar_sync(2, 128); if (tid == 0) stg_issue(P, sb, c + 3, slot); }
        slot = slot == 2 ? 0 : slot + 1;
      }
      st_ll(&g_yP[bid][2 * tid], __float_as_uint(a[0]), __float_as_uint(a[1]), __float_as_uint(a[2]), (__float_as_uint(a[3]) & ~255u) | tag8);
      st_ll(&g_yP[bid][2 * tid + 1], __float_as_uint(a[4]), __float_as_uint(a[5]), __float_as_uint(a[6]), (__float_as_uint(a[7]) & ~255u) | tag8);
    }
    PROFT(tid == 0, 21 + L * 6);
    {
      float a[8] = {0.f, 0.f, 0.f, 0.f, 0.f, 0.f, 0.f, 0.f};
      if (tid < 112) {
        uint4 v0 = poll_ll(&g_yP[tid][2 * bid], 255u, tag8), v1 = poll_ll(&g_yP[tid][2 * bid + 1], 255u, tag8);
        a[0] = __uint_as_float(v0.x); a[1] = __uint_as_float(v0.y); a[2] = __uint_as_float(v0.z); a[3] = __uint_as_float((v0.w & ~255u) | 128u);
        a[4] = __uint_as_float(v1.x); a[5] = __uint_as_float(v1.y); a[6] = __uint_as_float(v1.z); a[7] = __uint_as_float((v1.w & ~255u) | 128u);
      }
      __syncwarp();
      #pragma unroll
      for (int e = 0; e < 8; e++) a[e] = warp_sum(a[e]);
      if (lane == 0) {
        uint32_t d = sb + RED + 768 + w * 32;
        sts128(d, make_uint4(__float_as_uint(a[0]), __float_as_uint(a[1]), __float_as_uint(a[2]), __float_as_uint(a[3])));
        sts128(d + 16, make_uint4(__float_as_uint(a[4]), __float_as_uint(a[5]), __float_as_uint(a[6]), __float_as_uint(a[7])));
      }
      bar_sync(2, 128);
      if (w == 0) {
        uint32_t d = sb + RED + 768 + (lane & 7) * 4;
        float y = bf_round((lds32f(d) + lds32f(d + 32)) + (lds32f(d + 64) + lds32f(d + 96)));
        y = bf_round(y * bf_round(1.f / (1.f + __expf(-bf_round(r)))));
        uint32_t xw = lds32(sb + RED + 144 + ((lane & 7) >> 1) * 4);
        float x = (lane & 1) ? bf_hi(xw) : bf_lo(xw);
        uint32_t v = pack_bf16(0.f, x + bf_round(lds32f(sb + HV + (bid * 8 + (lane & 7)) * 4) + y));
        uint32_t v1 = __shfl_down_sync(0xffffffffu, v, 1), v2 = __shfl_down_sync(0xffffffffu, v, 2), v3 = __shfl_down_sync(0xffffffffu, v, 3);
        if (L == 0) { if (lane == 0 || lane == 4) st_ll(&g_x2[2 * bid + (lane >> 2)], v, v1, v2, v3 | tag); }
        else if (lane == 0 || lane == 4) *(uint2*)(P.out + (size_t)idx * 1024 + bid * 8 + lane) = make_uint2((v >> 16) | v1, (v2 >> 16) | v3);
      }
    }
    PROFT(tid == 0, 22 + L * 6);
    if (L == 0) {
      uint4 v0 = poll_ll(&g_x2[2 * tid], 0xffffu, tag), v1 = poll_ll(&g_x2[2 * tid + 1], 0xffffu, tag);
      v0.w &= 0xffff0000u; v1.w &= 0xffff0000u;
      if ((tid >> 4) == bc) sts128(sb + X2SEG + (tid & 15) * 16, make_uint4((v0.x >> 16) | v0.y, (v0.z >> 16) | v0.w, (v1.x >> 16) | v1.y, (v1.z >> 16) | v1.w));
      #define F(x) __uint_as_float(x)
      float m2 = aux_sum(((F(v0.x) + F(v0.y)) + (F(v0.z) + F(v0.w))) + ((F(v1.x) + F(v1.y)) + (F(v1.z) + F(v1.w))), sb + RED + 896) * (1.f / 1024.f);
      float e0 = F(v0.x) - m2, e1 = F(v0.y) - m2, e2 = F(v0.z) - m2, e3 = F(v0.w) - m2, e4 = F(v1.x) - m2, e5 = F(v1.y) - m2, e6 = F(v1.z) - m2, e7 = F(v1.w) - m2;
      #undef F
      float rs2 = rsqrtf(aux_sum(((e0 * e0 + e1 * e1) + (e2 * e2 + e3 * e3)) + ((e4 * e4 + e5 * e5) + (e6 * e6 + e7 * e7)), sb + RED + 912) * (1.f / 1024.f) + LN_EPS);
      #define HN(x) __float_as_uint(bf_round((x) * rs2))
      sts128(sb + HV + tid * 32, make_uint4(HN(e0), HN(e1), HN(e2), HN(e3)));
      sts128(sb + HV + tid * 32 + 16, make_uint4(HN(e4), HN(e5), HN(e6), HN(e7)));
      #undef HN
      bar_sync(2, 128);
      if (nch == 16) {
        float a[8] = {0.f, 0.f, 0.f, 0.f, 0.f, 0.f, 0.f, 0.f};
        #pragma unroll 1
        for (int c = 12; c < 16; c++) {
          mbar_wait(BAR(B_STG + slot), (phs >> slot) & 1); phs ^= 1u << slot;
          uint32_t wa = sb + STG + slot * 16384 + w * 4096 + lane * 16, ha = sb + HV + ((c - 12) * 256 + w * 64 + (lane >> 2)) * 4;
          #pragma unroll 2
          for (int n = 0; n < 8; n++) fma8(a, lds128(wa + n * 512), lds32f(ha + n * 32));
          if (c == 12) { bar_sync(2, 128); if (tid == 0) stg_issue(P, sb, 15, slot); }
          slot = slot == 2 ? 0 : slot + 1;
        }
        #pragma unroll
        for (int e = 0; e < 8; e++) { a[e] += __shfl_xor_sync(0xffffffffu, a[e], 4); a[e] += __shfl_xor_sync(0xffffffffu, a[e], 8); a[e] += __shfl_xor_sync(0xffffffffu, a[e], 16); }
        if (lane < 4) {
          uint32_t d = sb + RED + 256 + w * 128 + lane * 32;
          sts128(d, make_uint4(__float_as_uint(a[0]), __float_as_uint(a[1]), __float_as_uint(a[2]), __float_as_uint(a[3])));
          sts128(d + 16, make_uint4(__float_as_uint(a[4]), __float_as_uint(a[5]), __float_as_uint(a[6]), __float_as_uint(a[7])));
        }
        bar_sync(2, 128);
        if (w == 0) {
          uint32_t d = sb + RED + 256 + lane * 4;
          float z = (lds32f(d) + lds32f(d + 128)) + (lds32f(d + 256) + lds32f(d + 384));
          uint32_t v = pack_bf16(0.f, bid < 32 ? z * QSCALE : z);
          uint32_t v1 = __shfl_down_sync(0xffffffffu, v, 1), v2 = __shfl_down_sync(0xffffffffu, v, 2), v3 = __shfl_down_sync(0xffffffffu, v, 3);
          if ((lane & 3) == 0) st_ll(&g_patch[bid * 8 + (lane >> 2)], v, v1, v2, v3 | tag);
        }
      }
      #pragma unroll 1
      for (int q = 0; q < 2; q++) {
        uint4 v = poll_ll(&g_statF[bi * 256 + q * 128 + tid], 0xffffffffu, tag + 1);
        float var = __uint_as_float(v.y), g = 1.f + rsqrtf(var + LN_EPS), c = g * rsqrtf(fmaf(var * g, g, LN_EPS));
        sts64f(sb + PAR + (q * 128 + tid) * 8, c, -c * __uint_as_float(v.x));
      }
      if ((idx >> 8) == bi && tid < 48) {
        uint4 v = poll_ll(&g_patch[(tid >> 4) * 256 + bp * 16 + (tid & 15)], 0xffffu, tag);
        sts64f(sb + PATCH + tid * 8, __uint_as_float((v.x >> 16) | v.y), __uint_as_float((v.z >> 16) | (v.w & 0xffff0000u)));
      }
      if (tid == 0) sts32(sb + INFO, idx);
      bar_sync(2, 128);
      if (tid == 0) mbar_arrive(BAR(B_PAR));
      PROFT(tid == 0, 23);
    }
  }
  if (bid == 0 && tid == 0) g_epoch = epoch + 1;
}

__global__ void __cluster_dims__(2, 1, 1) __launch_bounds__(512, 1) fused_kernel(const __grid_constant__ Params P) {
  extern __shared__ __align__(1024) uint8_t smem_raw[];
  const uint32_t sb = smem_u32(smem_raw);
  PROFT(threadIdx.x == 0, 0);
  const uint32_t epoch = ld_rlx(&g_epoch);
  if (threadIdx.x == 0) {
    if (sb & 1023) __trap();
    for (int b = 0; b < B_COUNT; b++) {
      uint32_t cnt = 1;
      if ((b >= B_EMPTYQ && b < B_FULLW) || (b >= B_EMPTYW && b < B_KVFULL) || (b >= B_HAFREE && b <= B_XFREE)) cnt = 2;
      if (b >= B_KVRDY && b < B_HAFREE) cnt = 4;
      mbar_init(BAR(b), cnt);
    }
    asm volatile("fence.mbarrier_init.release.cluster;" ::: "memory");
  }
  __syncthreads();
  const uint32_t tag0 = ((epoch % 16383u) + 1u) << 2;
  const int wg = __shfl_sync(0xffffffffu, threadIdx.x >> 7, 0);
  if (wg < 2) { reg_inc<224>(); consumer(P, sb, wg, tag0); }
  else if (wg == 2) { reg_dec<40>(); aux(P, sb, tag0, epoch); }
  else {
    reg_dec<24>();
    const int w = __shfl_sync(0xffffffffu, (threadIdx.x >> 5) & 3, 0);
    if (w == 0) loader(P, sb, tag0);
    else if (w < 3 && (threadIdx.x & 31) == 0) storer(sb, w - 1, tag0);
  }
}

typedef CUresult (*EncFn)(CUtensorMap*, CUtensorMapDataType, cuuint32_t, void*, const cuuint64_t*, const cuuint64_t*, const cuuint32_t*, const cuuint32_t*,
                          CUtensorMapInterleave, CUtensorMapSwizzle, CUtensorMapL2promotion, CUtensorMapFloatOOBfill);
static void mk_map(EncFn enc, CUtensorMap* m, const void* ptr, int rank, const cuuint64_t* dims, const cuuint64_t* strides, const cuuint32_t* box,
                   CUtensorMapSwizzle sw, CUtensorMapL2promotion pr) {
  cuuint32_t es[5] = {1, 1, 1, 1, 1};
  enc(m, CU_TENSOR_MAP_DATA_TYPE_BFLOAT16, rank, (void*)ptr, dims, strides, box, es, CU_TENSOR_MAP_INTERLEAVE_NONE, sw, pr, CU_TENSOR_MAP_FLOAT_OOB_FILL_NONE);
}
extern "C" void kernel_launch(void* const* d_in, const int* in_sizes, int n_in, void* d_out, int out_size) {
  (void)in_sizes; (void)n_in; (void)out_size;
  void* fn = nullptr; cudaDriverEntryPointQueryResult q;
  cudaGetDriverEntryPoint("cuTensorMapEncodeTiled", &fn, cudaEnableDefault, &q);
  EncFn enc = (EncFn)fn;
  cudaFuncSetAttribute(fused_kernel, cudaFuncAttributeMaxDynamicSharedMemorySize, SMEM_BYTES);
  Params P;
  const CUtensorMapSwizzle S128 = CU_TENSOR_MAP_SWIZZLE_128B, S0 = CU_TENSOR_MAP_SWIZZLE_NONE;
  const CUtensorMapL2promotion L256 = CU_TENSOR_MAP_L2_PROMOTION_L2_256B, L128 = CU_TENSOR_MAP_L2_PROMOTION_L2_128B;
  { cuuint64_t d[2] = {1024, 2048}, s[1] = {2048}; cuuint32_t b[2] = {64, 256}, bh[2] = {64, 128};
    mk_map(enc, &P.mX, d_in[0], 2, d, s, b, S128, L256); mk_map(enc, &P.mXh, d_in[0], 2, d, s, bh, S128, L256); }
  { cuuint64_t d[3] = {1024, 1024, 3}, s[2] = {6144, 2048}; cuuint32_t b[3] = {64, 64, 3}; mk_map(enc, &P.mWq, d_in[1], 3, d, s, b, S128, L256); }
  { cuuint64_t d[5] = {64, 32, 2, 16, 16}, s[4] = {2048, 65536, 131072, 128}; cuuint32_t b[5] = {64, 32, 1, 2, 2}; mk_map(enc, &P.mWo, d_in[2], 5, d, s, b, S128, L256); }
  { cuuint64_t d[2] = {3584, 1024}, s[1] = {7168}; cuuint32_t b[2] = {32, 128};
    mk_map(enc, &P.mWg, d_in[5], 2, d, s, b, S0, L128); mk_map(enc, &P.mWu, d_in[6], 2, d, s, b, S0, L128); }
  { cuuint64_t d[2] = {3072, 1024}, s[1] = {6144}; cuuint32_t b[2] = {32, 256}; mk_map(enc, &P.mWp, d_in[1], 2, d, s, b, S0, L128); }
  P.x0 = (const bf16*)d_in[0]; P.wo = (const bf16*)d_in[2]; P.wr = (const bf16*)d_in[4]; P.wd = (const bf16*)d_in[7];
  P.out = (bf16*)d_out;
  fused_kernel<<<128, 512, SMEM_BYTES>>>(P);
}
```

```cpp
#include <cuda_runtime.h>
#include <cuda_bf16.h>
#include <cuda.h>
#include <stdint.h>
#include <stddef.h>
typedef __nv_bfloat16 bf16;

template<int TB, int TA = 0> __device__ __forceinline__ void wgmma_ss_n192(float (&d)[96], uint64_t da, uint64_t db, int scale_d) {
  asm volatile("{\n.reg .pred p;\nsetp.ne.b32 p, %98, 0;\n"
    "wgmma.mma_async.sync.aligned.m64n192k16.f32.bf16.bf16 {%0, %1, %2, %3, %4, %5, %6, %7, %8, %9, %10, %11, %12, %13, %14, %15, %16, %17, %18, %19, %20, %21, %22, %23, %24, %25, %26, %27, %28, %29, %30, %31, %32, %33, %34, %35, %36, %37, %38, %39, %40, %41, %42, %43, %44, %45, %46, %47, %48, %49, %50, %51, %52, %53, %54, %55, %56, %57, %58, %59, %60, %61, %62, %63, %64, %65, %66, %67, %68, %69, %70, %71, %72, %73, %74, %75, %76, %77, %78, %79, %80, %81, %82, %83, %84, %85, %86, %87, %88, %89, %90, %91, %92, %93, %94, %95}, %96, %97, p, 1, 1, %100, %99;\n}\n"
    : "+f"(d[0]), "+f"(d[1]), "+f"(d[2]), "+f"(d[3]), "+f"(d[4]), "+f"(d[5]), "+f"(d[6]), "+f"(d[7]), "+f"(d[8]), "+f"(d[9]), "+f"(d[10]), "+f"(d[11]), "+f"(d[12]), "+f"(d[13]), "+f"(d[14]), "+f"(d[15]), "+f"(d[16]), "+f"(d[17]), "+f"(d[18]), "+f"(d[19]), "+f"(d[20]), "+f"(d[21]), "+f"(d[22]), "+f"(d[23]), "+f"(d[24]), "+f"(d[25]), "+f"(d[26]), "+f"(d[27]), "+f"(d[28]), "+f"(d[29]), "+f"(d[30]), "+f"(d[31]), "+f"(d[32]), "+f"(d[33]), "+f"(d[34]), "+f"(d[35]), "+f"(d[36]), "+f"(d[37]), "+f"(d[38]), "+f"(d[39]), "+f"(d[40]), "+f"(d[41]), "+f"(d[42]), "+f"(d[43]), "+f"(d[44]), "+f"(d[45]), "+f"(d[46]), "+f"(d[47]), "+f"(d[48]), "+f"(d[49]), "+f"(d[50]), "+f"(d[51]), "+f"(d[52]), "+f"(d[53]), "+f"(d[54]), "+f"(d[55]), "+f"(d[56]), "+f"(d[57]), "+f"(d[58]), "+f"(d[59]), "+f"(d[60]), "+f"(d[61]), "+f"(d[62]), "+f"(d[63]), "+f"(d[64]), "+f"(d[65]), "+f"(d[66]), "+f"(d[67]), "+f"(d[68]), "+f"(d[69]), "+f"(d[70]), "+f"(d[71]), "+f"(d[72]), "+f"(d[73]), "+f"(d[74]), "+f"(d[75]), "+f"(d[76]), "+f"(d[77]), "+f"(d[78]), "+f"(d[79]), "+f"(d[80]), "+f"(d[81]), "+f"(d[82]), "+f"(d[83]), "+f"(d[84]), "+f"(d[85]), "+f"(d[86]), "+f"(d[87]), "+f"(d[88]), "+f"(d[89]), "+f"(d[90]), "+f"(d[91]), "+f"(d[92]), "+f"(d[93]), "+f"(d[94]), "+f"(d[95])
    : "l"(da), "l"(db), "r"(scale_d), "n"(TB), "n"(TA));
}

template<int TB, int TA = 0> __device__ __forceinline__ void wgmma_ss_n128(float (&d)[64], uint64_t da, uint64_t db, int scale_d) {
  asm volatile("{\n.reg .pred p;\nsetp.ne.b32 p, %66, 0;\n"
    "wgmma.mma_async.sync.aligned.m64n128k16.f32.bf16.bf16 {%0, %1, %2, %3, %4, %5, %6, %7, %8, %9, %10, %11, %12, %13, %14, %15, %16, %17, %18, %19, %20, %21, %22, %23, %24, %25, %26, %27, %28, %29, %30, %31, %32, %33, %34, %35, %36, %37, %38, %39, %40, %41, %42, %43, %44, %45, %46, %47, %48, %49, %50, %51, %52, %53, %54, %55, %56, %57, %58, %59, %60, %61, %62, %63}, %64, %65, p, 1, 1, %68, %67;\n}\n"
    : "+f"(d[0]), "+f"(d[1]), "+f"(d[2]), "+f"(d[3]), "+f"(d[4]), "+f"(d[5]), "+f"(d[6]), "+f"(d[7]), "+f"(d[8]), "+f"(d[9]), "+f"(d[10]), "+f"(d[11]), "+f"(d[12]), "+f"(d[13]), "+f"(d[14]), "+f"(d[15]), "+f"(d[16]), "+f"(d[17]), "+f"(d[18]), "+f"(d[19]), "+f"(d[20]), "+f"(d[21]), "+f"(d[22]), "+f"(d[23]), "+f"(d[24]), "+f"(d[25]), "+f"(d[26]), "+f"(d[27]), "+f"(d[28]), "+f"(d[29]), "+f"(d[30]), "+f"(d[31]), "+f"(d[32]), "+f"(d[33]), "+f"(d[34]), "+f"(d[35]), "+f"(d[36]), "+f"(d[37]), "+f"(d[38]), "+f"(d[39]), "+f"(d[40]), "+f"(d[41]), "+f"(d[42]), "+f"(d[43]), "+f"(d[44]), "+f"(d[45]), "+f"(d[46]), "+f"(d[47]), "+f"(d[48]), "+f"(d[49]), "+f"(d[50]), "+f"(d[51]), "+f"(d[52]), "+f"(d[53]), "+f"(d[54]), "+f"(d[55]), "+f"(d[56]), "+f"(d[57]), "+f"(d[58]), "+f"(d[59]), "+f"(d[60]), "+f"(d[61]), "+f"(d[62]), "+f"(d[63])
    : "l"(da), "l"(db), "r"(scale_d), "n"(TB), "n"(TA));
}

template<int TB, int TA = 0> __device__ __forceinline__ void wgmma_ss_n64(float (&d)[32], uint64_t da, uint64_t db, int scale_d) {
  asm volatile("{\n.reg .pred p;\nsetp.ne.b32 p, %34, 0;\n"
    "wgmma.mma_async.sync.aligned.m64n64k16.f32.bf16.bf16 {%0, %1, %2, %3, %4, %5, %6, %7, %8, %9, %10, %11, %12, %13, %14, %15, %16, %17, %18, %19, %20, %21, %22, %23, %24, %25, %26, %27, %28, %29, %30, %31}, %32, %33, p, 1, 1, %36, %35;\n}\n"
    : "+f"(d[0]), "+f"(d[1]), "+f"(d[2]), "+f"(d[3]), "+f"(d[4]), "+f"(d[5]), "+f"(d[6]), "+f"(d[7]), "+f"(d[8]), "+f"(d[9]), "+f"(d[10]), "+f"(d[11]), "+f"(d[12]), "+f"(d[13]), "+f"(d[14]), "+f"(d[15]), "+f"(d[16]), "+f"(d[17]), "+f"(d[18]), "+f"(d[19]), "+f"(d[20]), "+f"(d[21]), "+f"(d[22]), "+f"(d[23]), "+f"(d[24]), "+f"(d[25]), "+f"(d[26]), "+f"(d[27]), "+f"(d[28]), "+f"(d[29]), "+f"(d[30]), "+f"(d[31])
    : "l"(da), "l"(db), "r"(scale_d), "n"(TB), "n"(TA));
}

template<int TB> __device__ __forceinline__ void wgmma_rs_n40(float (&d)[20], uint32_t a0, uint32_t a1, uint32_t a2, uint32_t a3, uint64_t db, int scale_d) {
  asm volatile("{\n.reg .pred p;\nsetp.ne.b32 p, %25, 0;\n"
    "wgmma.mma_async.sync.aligned.m64n40k16.f32.bf16.bf16 {%0, %1, %2, %3, %4, %5, %6, %7, %8, %9, %10, %11, %12, %13, %14, %15, %16, %17, %18, %19}, {%20, %21, %22, %23}, %24, p, 1, 1, %26;\n}\n"
    : "+f"(d[0]), "+f"(d[1]), "+f"(d[2]), "+f"(d[3]), "+f"(d[4]), "+f"(d[5]), "+f"(d[6]), "+f"(d[7]), "+f"(d[8]), "+f"(d[9]), "+f"(d[10]), "+f"(d[11]), "+f"(d[12]), "+f"(d[13]), "+f"(d[14]), "+f"(d[15]), "+f"(d[16]), "+f"(d[17]), "+f"(d[18]), "+f"(d[19])
    : "r"(a0), "r"(a1), "r"(a2), "r"(a3), "l"(db), "r"(scale_d), "n"(TB));
}

#define DEVI __device__ __forceinline__
DEVI uint32_t smem_u32(const void* p) { return (uint32_t)__cvta_generic_to_shared(p); }
DEVI void mbar_init(uint32_t bar, uint32_t cnt) { asm volatile("mbarrier.init.shared::cta.b64 [%0], %1;" :: "r"(bar), "r"(cnt)); }
DEVI void mbar_expect_tx(uint32_t bar, uint32_t bytes) { asm volatile("mbarrier.arrive.expect_tx.shared::cta.b64 _, [%0], %1;" :: "r"(bar), "r"(bytes) : "memory"); }
DEVI void mbar_arrive(uint32_t bar) { asm volatile("mbarrier.arrive.shared::cta.b64 _, [%0];" :: "r"(bar) : "memory"); }
DEVI void mbar_arrive_peer(uint32_t bar) {
  asm volatile("{\n.reg .b32 ra;\nmapa.shared::cluster.u32 ra, %0, %1;\nmbarrier.arrive.shared::cluster.b64 _, [ra];\n}" :: "r"(bar), "r"((blockIdx.x & 1) ^ 1) : "memory");
}
DEVI void bulk_s2peer(uint32_t a, uint32_t bytes, uint32_t bar) {
  asm volatile("{\n.reg .b32 ra, rb;\nmapa.shared::cluster.u32 ra, %0, %3;\nmapa.shared::cluster.u32 rb, %2, %3;\n"
               "cp.async.bulk.shared::cluster.shared::cta.mbarrier::complete_tx::bytes [ra], [%0], %1, [rb];\n}"
               :: "r"(a), "r"(bytes), "r"(bar), "r"((blockIdx.x & 1) ^ 1) : "memory");
}
DEVI void mbar_wait(uint32_t bar, uint32_t parity) {
  asm volatile("{\n.reg .pred p;\nLW:\nmbarrier.try_wait.parity.shared::cta.b64 p, [%0], %1;\n@!p bra LW;\n}" :: "r"(bar), "r"(parity) : "memory");
}
DEVI void mbar_wait_b(uint32_t bar, uint32_t parity) {
  asm volatile("{\n.reg .pred p;\n.reg .u32 it;\nmov.u32 it, 0;\nLW:\nmbarrier.try_wait.parity.shared::cta.b64 p, [%0], %1;\n@p bra LD;\n"
               "add.u32 it, it, 1;\nsetp.lt.u32 p, it, 0x1000000;\n@p bra LW;\ntrap;\nLD:\n}" :: "r"(bar), "r"(parity) : "memory");
}
DEVI void tma_2d(uint32_t dst, const CUtensorMap* m, int c0, int c1, uint32_t bar) {
  asm volatile("cp.async.bulk.tensor.2d.shared::cluster.global.mbarrier::complete_tx::bytes [%0], [%1, {%3, %4}], [%2];"
    :: "r"(dst), "l"(m), "r"(bar), "r"(c0), "r"(c1) : "memory");
}
DEVI void tma_3d(uint32_t dst, const CUtensorMap* m, int c0, int c1, int c2, uint32_t bar) {
  asm volatile("cp.async.bulk.tensor.3d.shared::cluster.global.mbarrier::complete_tx::bytes [%0], [%1, {%3, %4, %5}], [%2];"
    :: "r"(dst), "l"(m), "r"(bar), "r"(c0), "r"(c1), "r"(c2) : "memory");
}
#define POL_EF POL_FIRST
constexpr uint64_t POL_FIRST = 0x12F0000000000000ull, POL_NORMAL = 0x1000000000000000ull;
DEVI void tma_2d_h(uint32_t dst, const CUtensorMap* m, int c0, int c1, uint32_t bar, uint64_t pol) {
  asm volatile("cp.async.bulk.tensor.2d.shared::cluster.global.mbarrier::complete_tx::bytes.L2::cache_hint [%0], [%1, {%3, %4}], [%2], %5;"
    :: "r"(dst), "l"(m), "r"(bar), "r"(c0), "r"(c1), "l"(pol) : "memory");
}
DEVI void tma_3d_h(uint32_t dst, const CUtensorMap* m, int c0, int c1, int c2, uint32_t bar, uint64_t pol) {
  asm volatile("cp.async.bulk.tensor.3d.shared::cluster.global.mbarrier::complete_tx::bytes.L2::cache_hint [%0], [%1, {%3, %4, %5}], [%2], %6;"
    :: "r"(dst), "l"(m), "r"(bar), "r"(c0), "r"(c1), "r"(c2), "l"(pol) : "memory");
}
DEVI void bulk_g2s_h(uint32_t s, const void* g, uint32_t bytes, uint32_t bar, uint64_t pol = POL_EF) {
  asm volatile("cp.async.bulk.shared::cluster.global.mbarrier::complete_tx::bytes.L2::cache_hint [%0], [%1], %2, [%3], %4;"
    :: "r"(s), "l"(g), "r"(bytes), "r"(bar), "l"(pol) : "memory");
}
DEVI void tma_5d(uint32_t dst, const CUtensorMap* m, int c0, int c1, int c2, int c3, int c4, uint32_t bar, uint64_t pol) {
  asm volatile("cp.async.bulk.tensor.5d.shared::cluster.global.mbarrier::complete_tx::bytes.L2::cache_hint [%0], [%1, {%3, %4, %5, %6, %7}], [%2], %8;"
    :: "r"(dst), "l"(m), "r"(bar), "r"(c0), "r"(c1), "r"(c2), "r"(c3), "r"(c4), "l"(pol) : "memory");
}
DEVI void tma_prefetch_2d(const CUtensorMap* m, int c0, int c1) {
  asm volatile("cp.async.bulk.prefetch.tensor.2d.L2.global.tile [%0, {%1, %2}];" :: "l"(m), "r"(c0), "r"(c1) : "memory");
}
DEVI void tma_prefetch_3d(const CUtensorMap* m, int c0, int c1, int c2) {
  asm volatile("cp.async.bulk.prefetch.tensor.3d.L2.global.tile [%0, {%1, %2, %3}];" :: "l"(m), "r"(c0), "r"(c1), "r"(c2) : "memory");
}
DEVI void bulk_prefetch(const void* g, uint32_t bytes) { asm volatile("cp.async.bulk.prefetch.L2.global [%0], %1;" :: "l"(g), "r"(bytes) : "memory"); }
DEVI void bulk_g2s(uint32_t s, const void* g, uint32_t bytes, uint32_t bar) {
  asm volatile("cp.async.bulk.shared::cluster.global.mbarrier::complete_tx::bytes [%0], [%1], %2, [%3];" :: "r"(s), "l"(g), "r"(bytes), "r"(bar) : "memory");
}
DEVI void bulk_s2g(void* g, uint32_t s, uint32_t bytes) {
  asm volatile("cp.async.bulk.global.shared::cta.bulk_group [%0], [%1], %2;\ncp.async.bulk.commit_group;" :: "l"(g), "r"(s), "r"(bytes) : "memory");
}
template<int N> DEVI void bulk_wait() { asm volatile("cp.async.bulk.wait_group %0;" :: "n"(N) : "memory"); }
DEVI void fence_async_smem() { asm volatile("fence.proxy.async.shared::cta;" ::: "memory"); }
DEVI void fence_async_glob() { asm volatile("fence.proxy.async.global;" ::: "memory"); }
DEVI unsigned ld_rlx(const unsigned* p) { unsigned v; asm volatile("ld.relaxed.gpu.global.u32 %0, [%1];" : "=r"(v) : "l"(p) : "memory"); return v; }
DEVI void st_rlx(unsigned* p, unsigned v) { asm volatile("st.relaxed.gpu.global.u32 [%0], %1;" :: "l"(p), "r"(v) : "memory"); }
DEVI void fence_rel() { asm volatile("fence.release.gpu;" ::: "memory"); }
DEVI uint4 ld_ll(const uint4* p) {
  uint4 v;
  asm volatile("{\n.reg .b128 t;\n.reg .b64 a, b;\nld.relaxed.gpu.global.b128 t, [%4];\nmov.b128 {a, b}, t;\nmov.b64 {%0, %1}, a;\nmov.b64 {%2, %3}, b;\n}"
               : "=r"(v.x), "=r"(v.y), "=r"(v.z), "=r"(v.w) : "l"(p) : "memory");
  return v;
}
DEVI void st_ll(uint4* p, uint32_t x, uint32_t y, uint32_t z, uint32_t w) {
  asm volatile("{\n.reg .b128 t;\n.reg .b64 a, b;\nmov.b64 a, {%1, %2};\nmov.b64 b, {%3, %4};\nmov.b128 t, {a, b};\nst.relaxed.gpu.global.b128 [%0], t;\n}"
               :: "l"(p), "r"(x), "r"(y), "r"(z), "r"(w) : "memory");
}
#define SPIN_MAX 0x1000000
DEVI uint4 poll_ll(const uint4* p, uint32_t mask, uint32_t tag) {
  uint4 v; int it = 0;
  do { v = ld_ll(p); if (++it > SPIN_MAX) __trap(); } while (!__all_sync(0xffffffffu, (v.w & mask) == tag));
  return v;
}
DEVI void poll_ll2(const uint4* p, const uint4* q, uint32_t mask, uint32_t tag, uint4& a, uint4& b) {
  int it = 0;
  do { a = ld_ll(p); b = ld_ll(q); if (++it > SPIN_MAX) __trap(); } while (!__all_sync(0xffffffffu, (a.w & mask) == tag && (b.w & mask) == tag));
}
DEVI void bar_sync(int id, int n) { asm volatile("bar.sync %0, %1;" :: "r"(id), "r"(n) : "memory"); }
DEVI void bar_arrive(int id, int n) { asm volatile("bar.arrive %0, %1;" :: "r"(id), "r"(n) : "memory"); }
DEVI void wg_fence() { asm volatile("wgmma.fence.sync.aligned;" ::: "memory"); }
DEVI void wg_commit() { asm volatile("wgmma.commit_group.sync.aligned;" ::: "memory"); }
template<int N> DEVI void wg_wait() { asm volatile("wgmma.wait_group.sync.aligned %0;" :: "n"(N) : "memory"); }
template<int N> DEVI void reg_inc() { asm volatile("setmaxnreg.inc.sync.aligned.u32 %0;" :: "n"(N)); }
template<int N> DEVI void reg_dec() { asm volatile("setmaxnreg.dec.sync.aligned.u32 %0;" :: "n"(N)); }
DEVI float ex2f(float x) { float y; asm("ex2.approx.ftz.f32 %0, %1;" : "=f"(y) : "f"(x)); return y; }
DEVI uint32_t pack_bf16(float lo, float hi) { uint32_t r; asm("cvt.rn.bf16x2.f32 %0, %1, %2;" : "=r"(r) : "f"(hi), "f"(lo)); return r; }
DEVI float bf_lo(uint32_t v) { return __uint_as_float(v << 16); }
DEVI float bf_hi(uint32_t v) { return __uint_as_float(v & 0xffff0000u); }
DEVI float bf_round(float x) { return bf_lo(pack_bf16(x, 0.f)); }
DEVI void stsm_x4(uint32_t addr, uint32_t a, uint32_t b, uint32_t c, uint32_t d) {
  asm volatile("stmatrix.sync.aligned.m8n8.x4.shared.b16 [%0], {%1,%2,%3,%4};" :: "r"(addr), "r"(a), "r"(b), "r"(c), "r"(d) : "memory");
}
DEVI void ldsm_x4(uint32_t addr, uint32_t& a, uint32_t& b, uint32_t& c, uint32_t& d) {
  asm volatile("ldmatrix.sync.aligned.m8n8.x4.shared.b16 {%0,%1,%2,%3}, [%4];" : "=r"(a), "=r"(b), "=r"(c), "=r"(d) : "r"(addr) : "memory");
}
DEVI uint4 lds128(uint32_t a) { uint4 v; asm volatile("ld.shared.v4.u32 {%0,%1,%2,%3}, [%4];" : "=r"(v.x), "=r"(v.y), "=r"(v.z), "=r"(v.w) : "r"(a) : "memory"); return v; }
DEVI void sts128(uint32_t a, uint4 v) { asm volatile("st.shared.v4.u32 [%0], {%1,%2,%3,%4};" :: "r"(a), "r"(v.x), "r"(v.y), "r"(v.z), "r"(v.w) : "memory"); }
DEVI float2 lds64f(uint32_t a) { float2 v; asm volatile("ld.shared.v2.f32 {%0,%1}, [%2];" : "=f"(v.x), "=f"(v.y) : "r"(a) : "memory"); return v; }
DEVI void sts64f(uint32_t a, float x, float y) { asm volatile("st.shared.v2.f32 [%0], {%1,%2};" :: "r"(a), "f"(x), "f"(y) : "memory"); }
DEVI uint32_t lds32(uint32_t a) { uint32_t v; asm volatile("ld.shared.u32 %0, [%1];" : "=r"(v) : "r"(a) : "memory"); return v; }
DEVI float lds32f(uint32_t a) { return __uint_as_float(lds32(a)); }
DEVI void sts32(uint32_t a, uint32_t v) { asm volatile("st.shared.u32 [%0], %1;" :: "r"(a), "r"(v) : "memory"); }
DEVI void sts32f(uint32_t a, float v) { sts32(a, __float_as_uint(v)); }
DEVI void sts16(uint32_t a, uint32_t v) { asm volatile("st.shared.u16 [%0], %1;" :: "r"(a), "h"((unsigned short)v) : "memory"); }
template<int N> DEVI void keep(float (&d)[N]) {
  #pragma unroll
  for (int i = 0; i < N; i++) asm volatile("" : "+f"(d[i]) :: "memory");
}
template<int N> DEVI void keep(uint32_t (&d)[N]) {
  #pragma unroll
  for (int i = 0; i < N; i++) asm volatile("" : "+r"(d[i]) :: "memory");
}
template<uint32_t HI> DEVI uint64_t mkd(uint32_t lo) { uint64_t r; asm("mov.b64 %0, {%1, %2};" : "=l"(r) : "r"(lo), "n"(HI)); return r; }
constexpr uint32_t HI128 = (1u << 30) | (1024 >> 4), HI64 = (2u << 30) | (512 >> 4);
#define VOFF(x) ((uint32_t)(x) * (uint32_t)(1 - 65536))
DEVI void warp_signal(uint32_t bar) { fence_async_smem(); __syncwarp(); if ((threadIdx.x & 31) == 0) mbar_arrive(bar); }

struct Scratch {
  uint4 kv[128][8][512];
  uint4 o[8][2][8][2][1024];
  uint4 x[8][16][2048];
  uint4 zero[1024];
  uint4 statP[8][2048];
  uint4 statF[2048];
  uint4 csP[16][8][96];
  uint4 best[8][16];
  uint4 row[16][256];
  uint4 yP[128][112][2];
  uint4 x2[256];
  uint4 patch[1024];
  unsigned flagKV[128][32];
  unsigned flagO[8][2][2][32];
  unsigned flagX[8][32];
  unsigned epoch;
};
__device__ __align__(1024) Scratch g_scr;
#define PROFT(cond, slot)
#define PROFW(cond, slot)

constexpr uint32_t SB0 = 65536, HOLE = 90112, SA2 = 98304, SB1 = 131072, SB2 = 155648, STG = 180224;
constexpr uint32_t KVA = 98304, KVB = 0, QO = 65536;
constexpr uint32_t MISC = 229376, ONES = MISC, BARS = MISC + 1024, INFO = MISC + 1440, CS = MISC + 1456, WR = MISC + 2224, X2SEG = MISC + 2736, INFO2 = MISC + 2992;
constexpr uint32_t PAR = HOLE, HV = HOLE + 2048, RED = HOLE + 6144, PATCH = 196608;
constexpr uint32_t SMEM_BYTES = 232448;
enum { B_FULLQ = 0, B_EMPTYQ = 3, B_FULLW = 6, B_EMPTYW = 10, B_HAFREE = 14, B_OFREE = 15, B_PFREE = 16, B_XFREE = 17,
       B_KVRDY = 19, B_ORDY = 23, B_XRDY = 31, B_STGE = 35,
       B_KVFULL = 38, B_RES = 42, B_PAR = 43, B_STG = 44, B_COUNT = 47 };
#define BAR(x) (sb + BARS + 8 * (x))
DEVI uint32_t qa_off(int s) { return s == 2 ? SA2 : (uint32_t)s * 32768u; }
DEVI uint32_t qb_off(int s) { return s == 0 ? SB0 : (s == 1 ? SB1 : SB2); }
DEVI int kb_order(int bc, int n) { return n < 2 ? 2 * bc + n : 2 * (bc ^ (n < 9 ? n - 1 : n - 8)) + (n >= 9); }
DEVI uint32_t w_off(int s) { return 98304u + (uint32_t)((s + 2) & 3) * 32768u; }

struct Params {
  CUtensorMap mX, mXh, mWq, mWo, mWg, mWu, mWp, mWd;
  const bf16 *x0, *wqkv, *wo, *wr, *wg, *wu, *wd;
  bf16* out;
  Scratch* g;
  unsigned map[128];
};
#define BID ((int)(P.map[blockIdx.x] & 255))
#define FID ((int)(P.map[blockIdx.x] >> 8))
DEVI uint32_t uni(uint32_t v) { return __shfl_sync(0xffffffffu, v, 0); }
#define PQ_N 8
#define PQ_T 700
#define PF0_N 10
#define PF0_T 1600
#define PF1_E 24
#define PF1_T 900
#define POL_Q1 POL_NORMAL
#define POL_X POL_NORMAL
#define PFA_BAR 0
#define PFA0_E 0
#define PFA1_S 0
#define PFA1_E 0
#define PFA_T 900
#define POL_G POL_NORMAL
#define POL_U POL_FIRST
#define POL_D POL_FIRST
#define JQ_N 6
#define POL_Q0 POL_NORMAL
constexpr float LN_EPS = 1e-5f;
constexpr float QSCALE = 0.17677669529663687f * 1.4426950408889634f;

DEVI void fma8(float (&a)[8], uint4 v, float h) {
  a[0] = fmaf(bf_lo(v.x), h, a[0]); a[1] = fmaf(bf_hi(v.x), h, a[1]); a[2] = fmaf(bf_lo(v.y), h, a[2]); a[3] = fmaf(bf_hi(v.y), h, a[3]);
  a[4] = fmaf(bf_lo(v.z), h, a[4]); a[5] = fmaf(bf_hi(v.z), h, a[5]); a[6] = fmaf(bf_lo(v.w), h, a[6]); a[7] = fmaf(bf_hi(v.w), h, a[7]);
}
DEVI void gemv8(float (&a)[8], uint32_t wa, uint32_t ha, uint32_t hs) {
  #pragma unroll
  for (int n = 0; n < 8; n += 2) {
    uint4 v0 = lds128(wa + n * 512), v1 = lds128(wa + n * 512 + 512);
    float h0 = lds32f(ha), h1 = lds32f(ha + hs);
    ha += 2 * hs;
    fma8(a, v0, h0); fma8(a, v1, h1);
  }
}
DEVI uint4 ldsv128(uint32_t a) { uint4 v; asm volatile("ld.volatile.shared.v4.u32 {%0,%1,%2,%3}, [%4];" : "=r"(v.x), "=r"(v.y), "=r"(v.z), "=r"(v.w) : "r"(a) : "memory"); return v; }
DEVI float ldsv32f(uint32_t a) { float v; asm volatile("ld.volatile.shared.f32 %0, [%1];" : "=f"(v) : "r"(a) : "memory"); return v; }
DEVI uint32_t clk() { uint32_t t; asm volatile("mov.u32 %0, %%clock;" : "=r"(t)); return t; }
DEVI int fresh_tid() { int t; asm volatile("mov.u32 %0, %%tid.x;" : "=r"(t)); return t & 127; }
DEVI float fold8(const float (&a)[8]) {
  const int lane = threadIdx.x & 31;
  const bool u = lane & 16, v = lane & 8, x = lane & 4;
  float b0 = (u ? a[4] : a[0]) + __shfl_xor_sync(0xffffffffu, u ? a[0] : a[4], 16), b1 = (u ? a[5] : a[1]) + __shfl_xor_sync(0xffffffffu, u ? a[1] : a[5], 16);
  float b2 = (u ? a[6] : a[2]) + __shfl_xor_sync(0xffffffffu, u ? a[2] : a[6], 16), b3 = (u ? a[7] : a[3]) + __shfl_xor_sync(0xffffffffu, u ? a[3] : a[7], 16);
  float c0 = (v ? b2 : b0) + __shfl_xor_sync(0xffffffffu, v ? b0 : b2, 8), c1 = (v ? b3 : b1) + __shfl_xor_sync(0xffffffffu, v ? b1 : b3, 8);
  return (x ? c1 : c0) + __shfl_xor_sync(0xffffffffu, x ? c0 : c1, 4);
}
DEVI float swiglu(float g, float u) { g = bf_round(g); return bf_round(bf_round(__fdividef(g, 1.f + __expf(-g))) * bf_round(u)); }

DEVI void qk_issue(float (&s)[32], uint32_t qd, uint32_t kd) {
  wgmma_ss_n64<0>(s, mkd<HI64>(qd), mkd<HI64>(kd), 0);
  wgmma_ss_n64<0>(s, mkd<HI64>(qd + 2), mkd<HI64>(kd + 2), 1);
}
DEVI void pv_issue(float (&o)[20], const uint32_t (&p)[16], uint32_t vd, bool accum) {
  #pragma unroll
  for (int ks = 0; ks < 4; ks++)
    wgmma_rs_n40<1>(o, p[ks * 4], p[ks * 4 + 1], p[ks * 4 + 2], p[ks * 4 + 3], mkd<HI64>(vd + VOFF(ks * 64)), ks ? 1 : accum);
}
template<int J0, int J1> DEVI void exp_pack(const float (&s)[32], uint32_t (&p)[16]) {
  #pragma unroll
  for (int j = J0; j < J1; j++) p[j] = pack_bf16(ex2f(s[2 * j]), ex2f(s[2 * j + 1]));
}
DEVI bool attn_finish(const float (&o)[20], uint32_t st, uint32_t bar) {
  const float lo = 5.421010862427522e-20f, hi = 1.8446744073709552e19f;
  bool ok = o[16] >= lo && o[16] <= hi && o[18] >= lo && o[18] <= hi;
  if (!__all_sync(0xffffffffu, ok)) return false;
  float i0 = __fdividef(1.f, o[16]), i1 = __fdividef(1.f, o[18]);
  int lane = threadIdx.x & 31, row = ((threadIdx.x >> 5) & 3) * 16 + (lane & 15);
  #pragma unroll
  for (int h = 0; h < 2; h++) {
    int c = 2 * h + (lane >> 4);
    stsm_x4(st + row * 64 + ((c ^ ((row >> 1) & 3)) << 4),
      pack_bf16(o[8 * h] * i0, o[8 * h + 1] * i0), pack_bf16(o[8 * h + 2] * i1, o[8 * h + 3] * i1),
      pack_bf16(o[8 * h + 4] * i0, o[8 * h + 5] * i0), pack_bf16(o[8 * h + 6] * i1, o[8 * h + 7] * i1));
  }
  warp_signal(bar);
  return true;
}
DEVI void attn_exact(uint32_t st, uint32_t kv, int t, bool hasprev, uint32_t bar) {
  const int lane = threadIdx.x & 31;
  #pragma unroll 1
  for (int row = ((threadIdx.x >> 5) & 3) * 16, n = 0; n < 16; n++, row++) {
    const int k1 = 256 + t * 64 + row;
    float m = -INFINITY, l = 0.f, o = 0.f;
    #pragma unroll 1
    for (int k0 = hasprev ? k1 - 255 : 256; k0 <= k1; k0 += 32) {
      const int k = min(k0 + lane, k1), r = k & 63;
      float sc = 0.f;
      #pragma unroll 1
      for (int c = 0; c < 16; c++) {
        uint32_t a = lds32(st + row * 64 + ((c * 4) ^ ((row & 6) << 3))), b = lds32(kv + (k >> 6) * 8192 + r * 64 + ((c * 4) ^ ((r & 6) << 3)));
        sc = fmaf(bf_lo(a), bf_lo(b), fmaf(bf_hi(a), bf_hi(b), sc));
      }
      float mn = fmaxf(m, sc);
      #pragma unroll 1
      for (int x = 16; x; x >>= 1) mn = fmaxf(mn, __shfl_xor_sync(0xffffffffu, mn, x));
      const float al = ex2f(m - mn), pr = ex2f(sc - mn);
      m = mn; l *= al; o *= al;
      #pragma unroll 1
      for (int q = k0; q <= min(k0 + 31, k1); q++) {
        const float z = __shfl_sync(0xffffffffu, pr, q - k0);
        uint32_t b = lds32(kv + (q >> 6) * 8192 + 4096 + (q & 63) * 64 + (((lane >> 1) * 4) ^ ((q & 6) << 3)));
        l += z; o = fmaf(z, (lane & 1) ? bf_hi(b) : bf_lo(b), o);
      }
    }
    __syncwarp();
    sts16(st + row * 64 + ((lane * 2) ^ ((row & 6) << 3)), pack_bf16(__fdividef(o, l), 0.f));
  }
  warp_signal(bar);
}

DEVI void merge_tri(float (&s)[32], const float (&sx)[32], int tdiag) {
  #pragma unroll
  for (int e = 0; e < 32; e++) { int c = 8 * (e >> 2) + (e & 1) - 8 * ((e >> 1) & 1); s[e] = (c > tdiag) ? s[e] : sx[e]; }
}
DEVI void split_tri(uint32_t (&p)[16], uint32_t (&px)[16], const uint32_t (&msk)[9]) {
  #pragma unroll
  for (int e = 0; e < 16; e++) { const uint32_t m = msk[(e >> 1) - (e & 1) + 1]; px[e] = p[e] & ~m; p[e] &= m; }
}

template<int J0> DEVI void qkv_store(const float (&aX)[96], const float (&aY)[96], const float2 (&pr)[4], uint32_t csa, uint32_t dX, uint32_t dY, uint32_t x0) {
  #pragma unroll
  for (int hh = 0; hh < 2; hh++) {
    constexpr int dummy = 0; (void)dummy;
    const int j = J0 + 2 * hh;
    float2 ca = lds64f(csa + j * 32), cb = lds64f(csa + j * 32 + 32);
    uint32_t off = x0 ^ (hh << 5);
    #define EL(a, e, P, C) fmaf(a[4 * j + (e)], pr[P].x, pr[P].y * (C))
    stsm_x4(dX + off, pack_bf16(EL(aX, 0, 0, ca.x), EL(aX, 1, 0, ca.y)), pack_bf16(EL(aX, 2, 1, ca.x), EL(aX, 3, 1, ca.y)),
                      pack_bf16(EL(aX, 4, 0, cb.x), EL(aX, 5, 0, cb.y)), pack_bf16(EL(aX, 6, 1, cb.x), EL(aX, 7, 1, cb.y)));
    stsm_x4(dY + off, pack_bf16(EL(aY, 0, 2, ca.x), EL(aY, 1, 2, ca.y)), pack_bf16(EL(aY, 2, 3, ca.x), EL(aY, 3, 3, ca.y)),
                      pack_bf16(EL(aY, 4, 2, cb.x), EL(aY, 5, 2, cb.y)), pack_bf16(EL(aY, 6, 3, cb.x), EL(aY, 7, 3, cb.y)));
    #undef EL
  }
}

template<bool FIRST> DEVI void qkv_block(float (&aX)[96], float (&aY)[96], uint32_t sb16, int s, int tX, int tY) {
  uint32_t a16 = sb16 + (qa_off(s) >> 4), b16 = (sb16 + (qb_off(s) >> 4)) | ((8192u >> 4) << 16);
  uint32_t ax = (a16 + tX * 512) | 0x10000u, ay = (a16 + tY * 512) | 0x10000u;
  wg_fence();
  #pragma unroll
  for (int ks = 0; ks < 4; ks++) {
    wgmma_ss_n192<1>(aX, mkd<HI128>(ax + ks * 2), mkd<HI128>(b16 + ks * 128), !(FIRST && ks == 0));
    wgmma_ss_n192<1>(aY, mkd<HI128>(ay + ks * 2), mkd<HI128>(b16 + ks * 128), !(FIRST && ks == 0));
  }
  wg_commit();
}
template<bool FIRST> DEVI void wo_block(float (&acc)[64], uint32_t sb16, int s, int wg) {
  uint32_t a16 = (sb16 + (w_off(s) >> 4) + wg * 256) | 0x10000u, b16 = (sb16 + (w_off(s) >> 4) + 1024) | ((8192u >> 4) << 16);
  wg_fence();
  #pragma unroll
  for (int ks = 0; ks < 4; ks++)
    wgmma_ss_n128<1>(acc, mkd<HI64>(a16 + (ks >> 1) * 512 + (ks & 1) * 2), mkd<HI128>(b16 + ks * 128), !(FIRST && ks == 0));
  wg_commit();
}
DEVI void consumer(const Params& P, uint32_t sb, int wg) {
  const int tid = threadIdx.x & 127, lane = tid & 31, w = tid >> 5;
  const int bi = BID >> 4, rh = blockIdx.x & 1, bc = (BID & 15) >> 1;
  const int tX = 3 - wg, tY = wg;
  const uint32_t sb16 = (sb & 0x3FFFFu) >> 4;
  uint32_t phq = 0;
  #pragma unroll 1
  for (int L = 0; L < 2; L++) {
    {
      float aX[96], aY[96];
      int s = 1, ps = 0;
      if (L) mbar_wait(BAR(B_XRDY + wg * 2 + 1), 0);
      PROFW(threadIdx.x == 0 && L, 46);
      mbar_wait(BAR(B_FULLQ), phq & 1);
      phq ^= 1u;
      PROFW(threadIdx.x == 0, L * 8 + 1);
      qkv_block<true>(aX, aY, sb16, 0, tX, tY);
      #pragma unroll 1
      for (int n = 1; n < 16; n++) {
        mbar_wait(BAR(B_FULLQ + s), (phq >> s) & 1);
        phq ^= 1u << s;
        PROFT(threadIdx.x == 0 && L && (n == 2 || n == 3 || n == 7 || n == 11 || n == 15), n == 2 ? 48 : 49 + (n >> 2));
        qkv_block<false>(aX, aY, sb16, s, tX, tY);
        wg_wait<1>(); if (tid == 0) mbar_arrive(BAR(B_EMPTYQ + ps));
        ps = s; s = (s == 2) ? 0 : s + 1;
      }
      mbar_wait(BAR(B_PAR), L);
      float2 pr[4];
      { uint32_t pa = sb + PAR + (w * 16 + (lane >> 2)) * 8;
        pr[0] = lds64f(pa + tX * 512); pr[1] = lds64f(pa + tX * 512 + 64); pr[2] = lds64f(pa + tY * 512); pr[3] = lds64f(pa + tY * 512 + 64); }
      int prow = (int)lds32(sb + INFO) - bi * 256;
      wg_wait<0>();
      keep(aX); keep(aY);
      if (tid == 0) mbar_arrive(BAR(B_EMPTYQ + ps));
      PROFW(threadIdx.x == 0, L * 8 + 2);
      mbar_wait(BAR(B_EMPTYQ + 1), ((phq >> 1) & 1) ^ 1); mbar_wait(BAR(B_EMPTYQ + 2), ((phq >> 2) & 1) ^ 1);
      const int srow = w * 16 + (lane & 15);
      const uint32_t x0 = srow * 64 + (((lane >> 4) ^ ((srow >> 1) & 3)) << 4);
      const uint32_t csa = sb + CS + (lane & 3) * 8;
      const bool pmine = (prow >> 4) == tX * 4 + w || (prow >> 4) == tY * 4 + w;
      const uint32_t poff = (prow & 63) * 64 + (((lane & 3) ^ ((prow >> 1) & 3)) << 4);
      qkv_store<8>(aX, aY, pr, csa, sb + KVA + (4 + tX) * 8192, sb + KVA + (4 + tY) * 8192, x0);
      qkv_store<16>(aX, aY, pr, csa, sb + KVA + (4 + tX) * 8192 + 4096, sb + KVA + (4 + tY) * 8192 + 4096, x0);
      if (pmine) { __syncwarp(); if (lane < 8) sts128(sb + KVA + (4 + (prow >> 6)) * 8192 + (lane >> 2) * 4096 + poff, lds128(sb + PATCH + 128 + (lane >> 2) * 128 + (lane & 3) * 16)); }
      warp_signal(BAR(B_KVRDY + wg * 2));
      qkv_store<12>(aX, aY, pr, csa, sb + KVB + (4 + tX) * 8192, sb + KVB + (4 + tY) * 8192, x0);
      qkv_store<20>(aX, aY, pr, csa, sb + KVB + (4 + tX) * 8192 + 4096, sb + KVB + (4 + tY) * 8192 + 4096, x0);
      if (pmine) { __syncwarp(); if (lane < 8) sts128(sb + KVB + (4 + (prow >> 6)) * 8192 + (lane >> 2) * 4096 + poff, lds128(sb + PATCH + 192 + (lane >> 2) * 128 + (lane & 3) * 16)); }
      warp_signal(BAR(B_KVRDY + wg * 2 + 1));
      #pragma unroll
      for (int e = 0; e < 4; e++) { pr[e].x *= QSCALE; pr[e].y *= QSCALE; }
      mbar_wait(BAR(B_EMPTYQ), (phq & 1) ^ 1);
      qkv_store<0>(aX, aY, pr, csa, sb + QO + tX * 4096, sb + QO + tY * 4096, x0);
      qkv_store<4>(aX, aY, pr, csa, sb + QO + 16384 + tX * 4096, sb + QO + 16384 + tY * 4096, x0);
      if (pmine) { __syncwarp(); if (lane < 8) sts128(sb + QO + (lane >> 2) * 16384 + (prow >> 6) * 4096 + poff, lds128(sb + PATCH + lane * 16)); }
      fence_async_smem();
      bar_sync(1, 256);
    }
    PROFW(threadIdx.x == 0, L * 8 + 3);
    {
      float s0[32], s1[32], sx[32], o[20], op[20];
      uint32_t p0[16], p1[16], px[16], msk[9];
      const int tdiag = w * 16 + (lane >> 2) - 2 * (lane & 3);
      #pragma unroll
      for (int e = 0; e < 9; e++) msk[e] = ((8 * e - 8 > tdiag) ? 0xFFFFu : 0u) | ((8 * e - 7 > tdiag) ? 0xFFFF0000u : 0u);
      keep(msk);
      const uint32_t ones = (sb16 + (ONES >> 4)) << 16;
      const uint32_t qX = (sb16 + (QO >> 4) + tX * 256) | 0x10000u, qY = (sb16 + (QO >> 4) + tY * 256) | 0x10000u;
      const uint32_t kXB = (sb16 + (KVB >> 4) + tX * 512) | 0x10000u;
      uint32_t redo = 0;
      #define QK(s, q, k) do { wg_fence(); qk_issue(s, q, k); wg_commit(); } while (0)
      #define QK2(q, k) do { wg_fence(); qk_issue(s1, q, k); qk_issue(sx, q, (k) + 2048); wg_commit(); } while (0)
      #define PV(o, p, v, b, acc) do { wg_fence(); pv_issue(o, p, (v) + VOFF((b) * 512), acc); wg_commit(); } while (0)
      #define PV2(v0, v4) do { wg_fence(); pv_issue(o, p1, v0, true); pv_issue(o, px, (v4) + VOFF(2048), true); wg_commit(); } while (0)
      {
        const uint32_t kXA = kXB + ((KVA - KVB) >> 4), vB = VOFF((kXB & 0xffffu) + 256) + ones, vA = vB + VOFF((KVA - KVB) >> 4);
        QK(s0, qX, kXA + 1536);
        wg_wait<0>(); keep(s0);
        QK(s1, qX, kXA + 1024);
        exp_pack<0, 16>(s0, p0);
        PV(o, p0, vA, 3, false);
        wg_wait<1>(); keep(s1);
        QK(s0, qX + 1024, kXB + 1536);
        exp_pack<0, 16>(s1, p1);
        PV(o, p1, vA, 2, true);
        wg_wait<1>(); keep(s0); keep(p0);
        QK(s1, qX + 1024, kXB + 1024);
        exp_pack<0, 16>(s0, p0);
        PV(op, p0, vB, 3, false);
        wg_wait<1>(); keep(s1); keep(p1); keep(o);
        exp_pack<0, 8>(s1, p1);
        mbar_wait(BAR(B_KVFULL), L);
        QK(s0, qX, kXA + 512);
        exp_pack<8, 16>(s1, p1);
        PV(op, p1, vB, 2, true);
        wg_wait<0>(); keep(s0); keep(p0); keep(p1); keep(op);
      }
      #pragma unroll 1
      for (int h = 0; h < 2; h++) {
        const uint32_t kb16 = sb16 + ((h ? KVB : KVA) >> 4), kX = (kb16 + tX * 512) | 0x10000u, kY = (kb16 + tY * 512) | 0x10000u;
        const uint32_t qx = qX + h * 1024, qy = qY + h * 1024;
        const uint32_t onesP = bi ? ones : (kb16 + 1984) << 16;
        const uint32_t vX = VOFF(kb16 + tX * 512 + 256), vY = VOFF(kb16 + tY * 512 + 256);
        QK2(qx, kX);
        exp_pack<0, 16>(s0, p0);
        PV(o, p0, vX + (wg ? onesP : ones), 1, true);
        wg_wait<1>(); keep(s1); keep(sx);
        merge_tri(s1, sx, tdiag);
        QK(s0, qy, kY + 1536);
        exp_pack<0, 16>(s1, p1); split_tri(p1, px, msk);
        PV2(vX + onesP, vX + ones);
        wg_wait<1>(); keep(s0); keep(p0);
        QK(s1, qy, kY + 1024);
        exp_pack<0, 10>(s0, p0);
        wg_wait<1>(); keep(o); keep(p1); keep(px);
        if (!attn_finish(o, sb + QO + (h * 4 + tX) * 4096, BAR(B_ORDY + wg * 4 + h * 2))) redo |= 1u << (h * 2);
        exp_pack<10, 16>(s0, p0);
        PV(o, p0, vY + (wg ? ones : onesP), 3, false);
        wg_wait<1>(); keep(s1);
        exp_pack<0, 8>(s1, p1);
        mbar_wait(BAR(B_KVFULL + h * 2 + 1), L);
        QK(s0, qy, kY + 512);
        exp_pack<8, 16>(s1, p1);
        PV(o, p1, vY + onesP, 2, true);
        wg_wait<1>(); keep(s0); keep(p0);
        QK2(qy, kY);
        exp_pack<0, 16>(s0, p0);
        PV(o, p0, vY + onesP, 1, true);
        wg_wait<1>(); keep(s1); keep(sx); keep(p1);
        merge_tri(s1, sx, tdiag);
        exp_pack<0, 8>(s1, p1);
        mbar_wait(BAR(B_KVFULL + 2), L);
        QK(s0, h ? qy : qX + 1024, kXB + 512);
        exp_pack<8, 16>(s1, p1); split_tri(p1, px, msk);
        PV2(vY + onesP, vY + ones);
        wg_wait<0>(); keep(o); keep(s0); keep(p0); keep(p1); keep(px);
        if (!attn_finish(o, sb + QO + (h * 4 + tY) * 4096, BAR(B_ORDY + wg * 4 + h * 2 + 1))) redo |= 2u << (h * 2);
        #pragma unroll
        for (int e = 0; e < 20; e++) o[e] = op[e];
      }
      #undef QK
      #undef QK2
      #undef PV
      #undef PV2
      if (redo) {
        #pragma unroll 1
        for (int u = 0; u < 4; u++) if ((redo >> u) & 1) {
          const int h = u >> 1, t = (u & 1) ? tY : tX;
          attn_exact(sb + QO + (h * 4 + t) * 4096, sb + (h ? KVB : KVA), t, bi > 0, BAR(B_ORDY + wg * 4 + u));
        }
      }
    }
    PROFW(threadIdx.x == 0, L * 8 + 4);
    {
      float acc[64];
      const int tt = wg ^ rh;
      const int grow = bi * 256 + rh * 128 + tt * 64 + w * 16 + (lane >> 2);
      float al0 = 1.f, be0 = 0.f, al1 = 1.f, be1 = 0.f;
      const int idx0 = (int)lds32(sb + INFO);
      const uint32_t tag = lds32(sb + INFO + 8) + L;
      uint4* const sp = &P.g->statP[bc][grow + (lane & 1) * 8];
      uint4* const yp = &P.g->yP[threadIdx.x >> 1][min(FID, 111)][threadIdx.x & 1];
      if (!(lane & 2)) st_ll(sp, 0u, 0u, 0u, 0u);
      if (L) {
        if (FID < 112) st_ll(yp, 0u, 0u, 0u, 0u);
        uint4 a = ld_ll(&P.g->statF[grow]), b = ld_ll(&P.g->statF[grow + 8]);
        float r0 = rsqrtf(__uint_as_float(a.y) + LN_EPS), r1 = rsqrtf(__uint_as_float(b.y) + LN_EPS);
        if (grow != idx0) { al0 = 1.f + r0; be0 = -__uint_as_float(a.x) * r0; }
        if (grow + 8 != idx0) { al1 = 1.f + r1; be1 = -__uint_as_float(b.x) * r1; }
      }
      mbar_wait(BAR(B_FULLW), 0);
      PROFW(threadIdx.x == 0, L * 8 + 5);
      wo_block<true>(acc, sb16, 0, tt);
      #pragma unroll 1
      for (int n = 1; n < 16; n++) {
        mbar_wait(BAR(B_FULLW + (n & 3)), (n >> 2) & 1);
        wo_block<false>(acc, sb16, n & 3, tt);
        wg_wait<1>(); if (tid == 0) mbar_arrive(BAR(B_EMPTYW + ((n - 1) & 3)));
      }
      mbar_wait(BAR(B_RES), L);
      const int srow = tt * 64 + w * 16 + (lane & 15);
      const uint32_t ra = sb + rh * 16384 + srow * 128, sw = ((lane >> 4) ^ (srow & 7)) << 4;
      if ((idx0 >> 4) == (grow >> 4)) {
        int r = idx0 & 127;
        if (lane < 16) sts128(sb + (lane >> 3) * 32768 + rh * 16384 + r * 128 + (((lane & 7) ^ (r & 7)) << 4), lds128(sb + X2SEG + lane * 16));
        __syncwarp();
      }
      uint32_t rs[32];
      #pragma unroll
      for (int jj = 0; jj < 8; jj++) ldsm_x4((ra + (jj >> 2) * 32768) + (sw ^ ((jj & 3) << 5)), rs[4 * jj], rs[4 * jj + 1], rs[4 * jj + 2], rs[4 * jj + 3]);
      wg_wait<0>(); keep(acc);
      if (tid == 0) mbar_arrive(BAR(B_EMPTYW + 3));
      PROFW(threadIdx.x == 0, L * 8 + 6);
      #pragma unroll
      for (int jj = 0; jj < 8; jj++) {
        float* a = acc + 8 * jj; const uint32_t* r = rs + 4 * jj;
        a[0] += fmaf(bf_lo(r[0]), al0, be0); a[1] += fmaf(bf_hi(r[0]), al0, be0); a[2] += fmaf(bf_lo(r[1]), al1, be1); a[3] += fmaf(bf_hi(r[1]), al1, be1);
        a[4] += fmaf(bf_lo(r[2]), al0, be0); a[5] += fmaf(bf_hi(r[2]), al0, be0); a[6] += fmaf(bf_lo(r[3]), al1, be1); a[7] += fmaf(bf_hi(r[3]), al1, be1);
        stsm_x4((ra + (jj >> 2) * 32768) + (sw ^ ((jj & 3) << 5)), pack_bf16(a[0], a[1]), pack_bf16(a[2], a[3]), pack_bf16(a[4], a[5]), pack_bf16(a[6], a[7]));
        if ((jj & 3) == 3) warp_signal(BAR(B_XRDY + wg * 2 + (jj >> 2)));
      }
      {
        float s1a = 0.f, s2a = 0.f, da = 0.f, s1b = 0.f, s2b = 0.f, db = 0.f;
        #pragma unroll
        for (int j = 0; j < 16; j++) {
          const float* a = acc + 4 * j; float2 wv = lds64f(sb + WR + j * 32 + (lane & 3) * 8);
          s1a += a[0] + a[1]; s1b += a[2] + a[3];
          s2a = fmaf(a[0], a[0], s2a); s2b = fmaf(a[2], a[2], s2b); s2a = fmaf(a[1], a[1], s2a); s2b = fmaf(a[3], a[3], s2b);
          da = fmaf(a[0], wv.x, da); db = fmaf(a[2], wv.x, db); da = fmaf(a[1], wv.y, da); db = fmaf(a[3], wv.y, db);
        }
        bool odd = lane & 1;
        float u1 = (odd ? s1b : s1a) + __shfl_xor_sync(0xffffffffu, odd ? s1a : s1b, 1);
        float u2 = (odd ? s2b : s2a) + __shfl_xor_sync(0xffffffffu, odd ? s2a : s2b, 1);
        float u3 = (odd ? db : da) + __shfl_xor_sync(0xffffffffu, odd ? da : db, 1);
        u1 += __shfl_xor_sync(0xffffffffu, u1, 2); u2 += __shfl_xor_sync(0xffffffffu, u2, 2); u3 += __shfl_xor_sync(0xffffffffu, u3, 2);
        if (!(lane & 2)) st_ll(sp, __float_as_uint(u1), __float_as_uint(u2), __float_as_uint(u3), tag);
      }
      PROFW(threadIdx.x == 0, L * 8 + 7);
      if (L) {
        uint2 wd[32];
        { const uint2* src = (const uint2*)(P.wd + (size_t)min(FID, 111) * 32768) + threadIdx.x;
          #pragma unroll
          for (int n = 0; n < 32; n++) wd[n] = __ldg(src + n * 256); }
        mbar_wait(BAR(B_PAR), 0);
        { float2 pa = lds64f(sb + PAR + (grow & 127) * 8), pb = lds64f(sb + PAR + (grow & 127) * 8 + 64); al0 = pa.x; be0 = pa.y; al1 = pb.x; be1 = pb.y; }
        #pragma unroll
        for (int j = 0; j < 16; j++) {
          rs[2 * j] = pack_bf16(fmaf(acc[4 * j], al0, be0), fmaf(acc[4 * j + 1], al0, be0));
          rs[2 * j + 1] = pack_bf16(fmaf(acc[4 * j + 2], al1, be1), fmaf(acc[4 * j + 3], al1, be1));
        }
        const int idx1 = (int)lds32(sb + INFO + 4);
        #pragma unroll
        for (int jj = 0; jj < 8; jj++) stsm_x4((ra + (jj >> 2) * 32768) + (sw ^ ((jj & 3) << 5)), rs[4 * jj], rs[4 * jj + 1], rs[4 * jj + 2], rs[4 * jj + 3]);
        __syncwarp();
        {
          const int r0 = (grow & ~15) + (lane >> 4), skip = idx1 - r0;
          const uint32_t a0 = sb + ((lane >> 3) & 1) * 32768 + (r0 & 255) * 128 + (((lane & 7) ^ (lane >> 4)) << 4);
          uint4* dst = (uint4*)(P.out + (size_t)r0 * 1024 + bc * 128) + (lane & 15);
          #pragma unroll
          for (int it = 0; it < 8; it++) { uint4 v = lds128((a0 + it * 256) ^ ((it & 3) << 5)); if (skip != 2 * it) dst[it * 256] = v; }
        }
        PROFW(threadIdx.x == 0, 16);
        if (FID < 112) {
          const int q = wg * 2 + (w >> 1);
          float g[8] = {0.f, 0.f, 0.f, 0.f, 0.f, 0.f, 0.f, 0.f};
          mbar_wait(BAR(B_FULLW + q), 0);
          bar_sync(3, 384);
          PROFW(threadIdx.x == 0, 29);
          #pragma unroll 1
          for (int n = 0; n < 4; n++) gemv8(g, sb + w_off(q) + (w & 1) * 16384 + n * 4096 + lane * 16, sb + HV + (q * 256 + n * 64 + (lane >> 2)) * 4, 32);
          sts32f(sb + PAR + 1024 + (q * 2 + (w & 1)) * 128 + ((lane & 3) * 8 + (lane >> 2)) * 4, fold8(g));
          bar_sync(1, 256);
          const uint32_t d = sb + PAR + 1024 + lane * 4;
          const float act = swiglu((lds32f(d) + lds32f(d + 256)) + (lds32f(d + 512) + lds32f(d + 768)),
                                   (lds32f(d + 128) + lds32f(d + 384)) + (lds32f(d + 640) + lds32f(d + 896)));
          PROFW(threadIdx.x == 0, 26);
          float y0 = 0.f, y1 = 0.f, y2 = 0.f, y3 = 0.f;
          #pragma unroll
          for (int n = 0; n < 32; n++) {
            float av = __shfl_sync(0xffffffffu, act, n);
            y0 = fmaf(bf_lo(wd[n].x), av, y0); y1 = fmaf(bf_hi(wd[n].x), av, y1); y2 = fmaf(bf_lo(wd[n].y), av, y2); y3 = fmaf(bf_hi(wd[n].y), av, y3);
          }
          st_ll(yp, __float_as_uint(y0), __float_as_uint(y1), __float_as_uint(y2), (__float_as_uint(y3) & ~255u) | (lds32(sb + INFO + 12) + 1));
          PROFW(threadIdx.x == 0, 27);
        }
      }
    }
  }
}

DEVI void loader(const Params& P, uint32_t sb) {
  const int lane = threadIdx.x & 31;
  const int bid = BID, bi = bid >> 4, bp = bid & 15, rh = bp & 1, bc = bp >> 1;
  uint32_t phq = 0, tag = 0;
  #pragma unroll 1
  for (int L = 0; L < 2; L++) {
    int s = 0;
    uint32_t rdy = 0;
    #pragma unroll 1
    for (int n = L ? 0 : 3; n < 16; n++) {
      int kb = L ? kb_order(bc, n) : n;
      mbar_wait(BAR(B_EMPTYQ + s), (phq >> s) & 1);
      phq ^= 1u << s;
      if (L) {
        if (n == 1) { mbar_wait(BAR(B_XRDY + 1), 0); mbar_wait(BAR(B_XRDY + 3), 0); }
        if (n >= 2) {
          if (((rdy >> (2 * kb)) & 3) != 3) {
            do { rdy = __ballot_sync(0xffffffffu, ld_rlx(&P.g->flagX[bi][lane]) == tag); } while (((rdy >> (2 * kb)) & 3) != 3);
            fence_async_glob();
          }
          if (n == 3 || n == 4) mbar_wait(BAR(B_XFREE + n - 3), 0);
        }
      }
      if (lane == 0) {
        mbar_expect_tx(BAR(B_FULLQ + s), L && n < 2 ? 40960 : 57344);
        if (L && n >= 2) bulk_g2s_h(sb + qa_off(s), P.g->x[bi][kb], 32768, BAR(B_FULLQ + s), POL_X);
        if (!L) tma_2d(sb + qa_off(s), &P.mX, kb * 64, bi * 256, BAR(B_FULLQ + s));
        tma_3d_h(sb + qb_off(s), &P.mWq, bp * 64, kb * 64, 0, BAR(B_FULLQ + s), L ? POL_Q1 : POL_Q0);
      }
      PROFW(L && lane == 0 && (n == 2 || n == 3 || n == 9), n == 9 ? 60 : 56 + n);
      if (L && n == 2) { mbar_wait(BAR(B_FULLQ), 0); mbar_wait(BAR(B_FULLQ + 1), 1); if (lane < 2) mbar_arrive_peer(BAR(B_XFREE + lane)); }
      s = (s == 2) ? 0 : s + 1;
    }
    for (int q = 0; q < 3; q++) mbar_wait(BAR(B_EMPTYQ + q), (phq >> q) & 1);
    mbar_wait(BAR(B_PAR), L);
    tag = lds32(sb + INFO + 8) + L;
    rdy = bi ? 0u : 0xffu;
    {
      const uint4* src = bi ? P.g->kv[bid - 16][0] : P.g->zero;
      const unsigned* fl = &P.g->flagKV[bid - 16][lane & 7];
      #pragma unroll 1
      for (int q = 0; q < 4; q++) {
        const int ch = (2 * q) ^ 2;
        if (lane == 0) mbar_expect_tx(BAR(B_KVFULL + q), 16384);
        if (((rdy >> ch) & 3) != 3) {
          do { rdy = __ballot_sync(0xffffffffu, ld_rlx(fl) == tag); } while (((rdy >> ch) & 3) != 3);
          fence_async_glob();
        }
        if (lane == 0) bulk_g2s_h(sb + ((ch >> 2) ? KVB : KVA) + (ch & 3) * 8192, src + (bi ? ch * 512 : 0), 16384, BAR(B_KVFULL + q));
        PROFW(!L && lane == 0 && bi && q != 2, 34 + (q + 1) / 2);
      }
    }
    mbar_wait(BAR(B_ORDY), L); mbar_wait(BAR(B_ORDY + 4), L);
    {
      const uint4* src = P.g->o[bi][0][0][rh];
      const unsigned* fl = &P.g->flagO[bi][0][rh][lane];
      rdy = 0;
      #pragma unroll 1
      for (int n = 0; n < 16; n++) {
        const int q = n & 3, j = n & 7;
        if (n == 8) { rdy = 0; src += 16384; fl += 64; }
        if (((rdy >> (4 * j)) & 15) != 15) {
          do { rdy = __ballot_sync(0xffffffffu, ld_rlx(fl) == tag); } while (((rdy >> (4 * j)) & 15) != 15);
          fence_async_glob();
        }
        if (n >= 2) mbar_wait(n < 4 ? BAR(B_HAFREE) : BAR(B_EMPTYW + q), n < 4 ? L : ((n >> 2) + 1) & 1);
        if (lane == 0) { mbar_expect_tx(BAR(B_FULLW + q), 16384); bulk_g2s_h(sb + w_off(q), src + j * 2048, 16384, BAR(B_FULLW + q)); }
      }
    }
    mbar_wait(BAR(B_OFREE), L);
  }
}

DEVI void ffn_prefetch(const Params& P, int q) {
  bulk_prefetch(q < 16 ? ((q & 1) ? P.wu : P.wg) + ((q >> 1) * 128 + blockIdx.x) * 3584 : P.wd + (blockIdx.x * 8 + q - 16) * 3584, 7168);
}
DEVI void storer(const Params& P, uint32_t sb, int wg) {
  const int bid = uni(BID), bi = bid >> 4, rh = bid & 1, bc = (bid & 15) >> 1;
  const bool one = (threadIdx.x & 31) == 0;
  char* const g = (char*)P.g;
  #pragma unroll 1
  for (int L = 0; L < 2; L++) {
    mbar_wait(BAR(B_KVRDY + wg * 2), L);
    const uint32_t tag = lds32(sb + INFO + 8) + L;
    #pragma unroll 1
    for (int u = bi < 7 ? 0 : 4; u < 8; u++) {
      const int h = (u >> 1) & 1, t = (u & 1) ? wg : 3 - wg;
      uint32_t src, dst, fl;
      if (u < 4) {
        src = (h ? KVB : KVA) + (4 + t) * 8192; dst = offsetof(Scratch, kv) + (bid * 8 + h * 4 + t) * 8192; fl = offsetof(Scratch, flagKV) + (bid * 32 + h * 4 + t) * 4;
      } else {
        src = QO + (h * 4 + t) * 4096; dst = offsetof(Scratch, o) + ((((bi * 2 + h) * 8 + bc) * 2 + (t >> 1)) * 4 + rh * 2 + (t & 1)) * 4096;
        fl = offsetof(Scratch, flagO) + (((bi * 2 + h) * 2 + (t >> 1)) * 32 + (bid & 15) * 2 + (t & 1)) * 4;
      }
      if (u >= 2) mbar_wait(u < 4 ? BAR(B_KVRDY + wg * 2 + 1) : BAR(B_ORDY + wg * 4 + u - 4), L);
      if (one) { bulk_s2g(g + dst, sb + src, u < 4 ? 8192 : 4096); if (u == 5) mbar_arrive(BAR(B_HAFREE)); }
      bulk_wait<0>(); fence_rel();
      if (one) st_rlx((unsigned*)(g + fl), tag);
      PROFT(one && !L && wg == 0 && (u == 0 || u == 3), 32 + (u & 1));
    }
    if (one) mbar_arrive(BAR(B_OFREE));
    if (L == 0) {
      if (one) mbar_arrive_peer(BAR(B_PFREE));
      char* dst = g + (offsetof(Scratch, x) + (bi * 16 + 2 * bc) * 32768 + rh * 16384);
      unsigned* f = (unsigned*)(g + (offsetof(Scratch, flagX) + (bi * 32 + bc * 4 + rh) * 4));
      mbar_wait(BAR(B_PFREE), 0);
      #pragma unroll 1
      for (int e = 0; e < 2; e++) {
        const uint32_t a = sb + rh * 16384 + e * 32768;
        mbar_wait(BAR(B_XRDY + e), 0); mbar_wait(BAR(B_XRDY + 2 + e), 0);
        PROFT(one && wg == 0 && e == 0, 41);
        if (wg) { if (one) bulk_s2peer(a, 16384, BAR(B_FULLQ + e)); }
        else {
          if (one) bulk_s2g(dst + e * 32768, a, 16384);
          bulk_wait<0>();
          PROFT(one && e == 0, 45);
          if (one) mbar_arrive(BAR(B_XFREE + e));
          fence_rel();
          if (one) st_rlx(f + 2 * e, tag);
          PROFT(one, 56 + e);
        }
      }
      if (wg == 0) {
        uint32_t t0 = clk();
        #pragma unroll 1
        for (int q = PF0_N; q < PF1_E; q++) { if (one) ffn_prefetch(P, q); while (clk() - t0 < PF1_T); t0 += PF1_T; }
      }
    }
  }
}

DEVI void stg_issue(const Params& P, int c, uint32_t d, uint32_t du, uint32_t b) {
  mbar_expect_tx(b, 16384);
  if (c < 8) { tma_2d_h(d, &P.mWg, FID * 32, c * 128, b, POL_G); tma_2d_h(d + du, &P.mWu, FID * 32, c * 128, b, POL_U); }
  else if (c < 12) tma_3d_h(d, &P.mWd, 0, FID * 32 + (c - 8) * 8, 0, b, POL_D);
  else tma_2d_h(d, &P.mWp, FID * 32, (c - 12) * 256, b, POL_EF);
}
DEVI void stager(const Params& P, uint32_t sb) {
  {
    const int b = blockIdx.x;
    uint32_t t0 = clk();
    #pragma unroll 1
    for (int q = 0; q < PQ_N; q++) { bulk_prefetch(P.wqkv + (q * 128 + b) * 3072, 6144); while (clk() - t0 < PQ_T); t0 += PQ_T; }
    bulk_prefetch(P.wo + b * 8192, 16384);
    #pragma unroll 1
    for (int q = 0; q < PF0_N; q++) {
      while (clk() - t0 < PF0_T);
      t0 += PF0_T;
      ffn_prefetch(P, q);
    }
  }
  const int bid = BID, bi = bid >> 4, rh = bid & 1, bc = (bid & 15) >> 1;
  uint32_t phe = 7;
  #pragma unroll 1
  for (int L = 0; L < 2; L++) {
    const int nch = FID >= 112 ? 0 : (FID < 96 ? 16 : 12);
    mbar_wait(BAR(B_KVRDY), L); mbar_wait(BAR(B_KVRDY + 2), L);
    #pragma unroll 1
    for (int n = 0; n < 16; n++) {
      const int q = n & 3;
      if (n >= 2) mbar_wait(n < 4 ? BAR(B_HAFREE) : BAR(B_EMPTYW + q), n < 4 ? L : ((n >> 2) + 1) & 1);
      mbar_expect_tx(BAR(B_FULLW + q), 16384);
      tma_5d(sb + w_off(q) + 16384, &P.mWo, 0, 0, n >> 3, 2 * (n & 7), 2 * bc, BAR(B_FULLW + q), L ? POL_EF : POL_NORMAL);
      if (n == 10) {
        mbar_wait(BAR(B_OFREE), L);
        mbar_expect_tx(BAR(B_RES), 32768);
        #pragma unroll 1
        for (int e = 0; e < 2; e++) {
          if (L) bulk_g2s_h(sb + e * 32768 + rh * 16384, P.g->x[bi][2 * bc + e] + rh * 1024, 16384, BAR(B_RES));
          else tma_2d_h(sb + e * 32768 + rh * 16384, &P.mXh, bc * 128 + e * 64, bi * 256 + rh * 128, BAR(B_RES), POL_EF);
        }
      }
    }
    if (L == 0) {
      mbar_wait(BAR(B_XFREE), 0);
      int slot = 0;
      #pragma unroll 1
      for (int c = 0; c < nch; c++) {
        mbar_wait(BAR(B_STGE + slot), (phe >> slot) & 1); phe ^= 1u << slot;
        stg_issue(P, c, sb + STG + slot * 16384, 8192, BAR(B_STG + slot));
        slot = slot == 2 ? 0 : slot + 1;
      }
    } else if (nch) {
      #pragma unroll 1
      for (int c = 0; c < 8; c++) {
        mbar_wait(BAR(B_EMPTYW + (c >> 1)), 1);
        stg_issue(P, c, sb + w_off(c >> 1) + (c & 1) * 8192, 16384, BAR(B_FULLW + (c >> 1)));
      }
    }
  }
}
DEVI void sum8(uint4 v, float& s1, float& s2) {
  float e[8] = {bf_lo(v.x), bf_hi(v.x), bf_lo(v.y), bf_hi(v.y), bf_lo(v.z), bf_hi(v.z), bf_lo(v.w), bf_hi(v.w)};
  #pragma unroll
  for (int q = 0; q < 8; q++) { s1 += e[q]; s2 = fmaf(e[q], e[q], s2); }
}
DEVI uint4 norm8(uint4 x, float m, float rs, uint32_t d) {
  #define HN(v) pack_bf16((bf_lo(v) - m) * rs, (bf_hi(v) - m) * rs)
  uint4 b = make_uint4(HN(x.x), HN(x.y), HN(x.z), HN(x.w));
  #undef HN
  sts128(d, make_uint4(b.x << 16, b.x & 0xffff0000u, b.y << 16, b.y & 0xffff0000u));
  sts128(d + 16, make_uint4(b.z << 16, b.z & 0xffff0000u, b.w << 16, b.w & 0xffff0000u));
  return b;
}
DEVI uint4 best4(uint32_t p) {
  uint4 a = lds128(p), b = lds128(p + 16), c = lds128(p + 32), d = lds128(p + 48);
  if (b.x > a.x) a = b;
  if (d.x > c.x) c = d;
  return c.x > a.x ? c : a;
}
#define FL(x) __uint_as_float(x)
#define UI(x) __float_as_uint(x)
DEVI void qkv_params(const Params& P, uint32_t sb, int row, uint32_t tag, bool second) {
  uint4 v0, v1; poll_ll2(&P.g->statF[row], &P.g->statF[row + 128], 0xffffffffu, tag, v0, v1);
  #pragma unroll 1
  for (int q = 0; q < 2; q++) {
    float var = FL(v0.y), c = rsqrtf(var + LN_EPS);
    if (second) { c += 1.f; c *= rsqrtf(fmaf(var * c, c, LN_EPS)); }
    sts64f(sb + PAR + q * 1024 + (row & 127) * 8, c, -c * FL(v0.x));
    v0 = v1;
  }
}
DEVI void aux(const Params& P, uint32_t sb) {
  int tid = fresh_tid();
  #define lane (tid & 31)
  #define wq (tid >> 5)
  uint32_t ids = P.map[blockIdx.x], tag;
  #define bid ((int)(ids & 255))
  #define fid ((int)(ids >> 8))
  #define bi (bid >> 4)
  #define bp (bid & 15)
  #define bc (bp >> 1)
  #define FRESH() do { tid = fresh_tid(); uint4 z_ = ldsv128(sb + INFO2 + 16); ids = z_.y; tag = z_.z + L; idx = z_.w; } while (0)
  {
    const uint32_t epoch = ld_rlx(&P.g->epoch);
    if (tid == 0) {
      mbar_expect_tx(BAR(B_STG), 49152);
      tma_3d(sb + STG, &P.mWq, bp * 64, bi * 128, 0, BAR(B_STG));
      tma_3d(sb + STG + 24576, &P.mWq, bp * 64, bi * 128 + 64, 0, BAR(B_STG));
    }
    __syncwarp();
    sts64f(sb + ONES + tid * 8, FL(0x3F803F80u), FL(0x3F803F80u));
    fence_async_smem();
    float s1 = 0.f, s2 = 0.f;
    { uint4 v = __ldg((const uint4*)P.wr + tid);
      if ((tid >> 4) == bc) norm8(v, 0.f, 1.f, sb + WR + (tid & 15) * 32);
      sum8(v, s1, s2);
      #pragma unroll 1
      for (int o = 16; o; o >>= 1) s1 += __shfl_xor_sync(0xffffffffu, s1, o);
      sts32f(sb + INFO2 + wq * 4, s1); }
    const uint4* src = (const uint4*)(P.x0 + (size_t)bid * 16384) + (tid >> 3) * 128 + (tid & 7);
    s1 = 0.f; s2 = 0.f;
    #pragma unroll 1
    for (int it = 0; it < 16; it += 4) {
      uint4 v0 = __ldg(src + it * 8), v1 = __ldg(src + it * 8 + 8), v2 = __ldg(src + it * 8 + 16), v3 = __ldg(src + it * 8 + 24);
      #pragma unroll 1
      for (int q = 0; q < 4; q++) { sum8(v0, s1, s2); v0 = v1; v1 = v2; v2 = v3; }
    }
    #pragma unroll 1
    for (int o = 1; o < 8; o <<= 1) { s1 += __shfl_xor_sync(0xffffffffu, s1, o); s2 += __shfl_xor_sync(0xffffffffu, s2, o); }
    tag = ((epoch % 16383u) + 1u) << 2;
    if (tid == 0) { sts128(sb + INFO, make_uint4(0x40000000u, 0u, tag, ((epoch % 127u) + 1u) << 1)); sts128(sb + INFO2 + 16, make_uint4(epoch, ids, tag, 0x40000000u)); }
    float m = s1 * (1.f / 1024.f);
    if ((tid & 7) == 0) st_ll(&P.g->statF[bid * 16 + (tid >> 3)], UI(m), UI(fmaxf(fmaf(-m, m, s2 * (1.f / 1024.f)), 0.f)), 0u, tag);
    bar_sync(2, 128);
    mbar_wait_b(BAR(B_STG), 0);
    if (tid < 96) {
      s1 = 0.f; s2 = 0.f;
      #pragma unroll 4
      for (int r = 0; r < 128; r++) {
        uint32_t v = lds32(sb + STG + (r >> 6) * 24576 + wq * 8192 + (r & 63) * 128 + ((lane * 4) ^ ((r & 7) << 4)));
        s1 += bf_lo(v); s2 += bf_hi(v);
      }
      st_ll(&P.g->csP[bp][bi][tid], UI(s1), UI(s2), 0u, tag);
      s1 = 0.f; s2 = 0.f;
      #pragma unroll 1
      for (int q = 0; q < 8; q += 2) {
        uint4 a, b; poll_ll2(&P.g->csP[bp][q][tid], &P.g->csP[bp][q + 1][tid], 0xffffffffu, tag, a, b);
        s1 += FL(a.x) + FL(b.x); s2 += FL(a.y) + FL(b.y);
      }
      sts64f(sb + CS + tid * 8, s1, s2);
    }
    qkv_params(P, sb, bi * 256 + tid, tag, false);
  }
  int idx;
  #pragma unroll 1
  for (int L = 0; L < 2; L++) {
    FRESH();
    {
      if ((idx >> 8) == bi && wq < 3) {
        uint4 v = poll_ll(&P.g->patch[wq * 256 + bp * 16 + (lane & 15)], 0xffffffffu, tag);
        sts64f(sb + PATCH + (wq * 16 + (lane & 15)) * 8, FL(v.x), FL(v.y));
      }
      sts32(sb + INFO, idx);
      bar_sync(2, 128);
      if (tid == 0) mbar_arrive(BAR(B_PAR));
      PROFW(tid == 0, L ? 23 : 17);
    }
    if (wq == 3) {
      mbar_wait_b(BAR(B_KVFULL + PFA_BAR), L);
      uint32_t t0 = clk();
      #pragma unroll 1
      for (int q = L ? PFA1_S : PF0_N; q < (L ? PFA1_E : PFA0_E); q++) {
        if (lane == 0) { if (q < 24) ffn_prefetch(P, q); else bulk_prefetch(P.wqkv + ((q - 24) * 128 + blockIdx.x) * 3072, 6144); }
        while (clk() - t0 < PFA_T) __nanosleep(50);
        t0 += PFA_T;
      }
    }
    FRESH();
    mbar_wait_b(BAR(B_OFREE), L);
    #define blk (bi * 2 + (bid & 1))
    if (tid < 33) st_ll(tid < 32 ? &P.g->row[blk][bc * 32 + tid] : &P.g->best[bc][blk], 0u, 0u, 0u, 0u);
    mbar_wait_b(BAR(B_XRDY + 1), L); mbar_wait_b(BAR(B_XRDY + 3), L);
    PROFW(tid == 0, 37 + L * 16);
    FRESH();
    {
      float s1 = 0.f, s2 = 0.f, d = 0.f;
      #pragma unroll 1
      for (int q = 0; q < 8; q += 4) {
        const uint4* src = &P.g->statP[q][blk * 128 + tid];
        uint4 v0, v1, v2, v3; int it = 0;
        do { v0 = ld_ll(src); v1 = ld_ll(src + 2048); v2 = ld_ll(src + 4096); v3 = ld_ll(src + 6144); if (++it > SPIN_MAX) __trap(); }
        while (!__all_sync(0xffffffffu, v0.w == tag && v1.w == tag && v2.w == tag && v3.w == tag));
        s1 += (FL(v0.x) + FL(v1.x)) + (FL(v2.x) + FL(v3.x)); s2 += (FL(v0.y) + FL(v1.y)) + (FL(v2.y) + FL(v3.y)); d += (FL(v0.z) + FL(v1.z)) + (FL(v2.z) + FL(v3.z));
      }
      PROFW(tid == 0, 39 + L * 16);
      uint4 a = lds128(sb + INFO2), b, c;
      float m = s1 * (1.f / 1024.f), var = fmaxf(fmaf(-m, m, s2 * (1.f / 1024.f)), 0.f), rs = rsqrtf(var + LN_EPS);
      uint32_t key = UI(fmaf(-m, (FL(a.x) + FL(a.y)) + (FL(a.z) + FL(a.w)), d) * rs);
      key ^= (uint32_t)((int)key >> 31) | 0x80000000u;
      uint32_t win = __ballot_sync(0xffffffffu, key == __reduce_max_sync(0xffffffffu, key));
      if (lane == __ffs(win) - 1) sts128(sb + RED + wq * 16, make_uint4(key, UI(m), UI(rs), (tag << 11) | (uint32_t)(blk * 128 + tid)));
      if (L) sts64f(sb + PAR + tid * 8, 1.f + rs, -m * rs);
      bar_sync(2, 128);
      if (wq == 0) {
        a = best4(sb + RED);
        float2 v = lds64f(sb + (lane >> 4) * 32768 + (a.w & 255) * 128 + (((lane & 15) * 8) ^ ((a.w & 7) << 4)));
        st_ll(&P.g->row[blk][bc * 32 + lane], UI(v.x), UI(v.y), 0u, tag);
        if (lane == 0) { st_ll(&P.g->best[bc][blk], a.x, a.y, a.z, a.w); sts32(sb + INFO + 4, a.w & 2047); }
        __syncwarp();
        if (L) {
          const float al = 1.f + FL(a.z), be = -FL(a.y) * FL(a.z);
          sts64f(sb + RED + 1792 + lane * 8, FL(pack_bf16(fmaf(bf_lo(UI(v.x)), al, be), fmaf(bf_hi(UI(v.x)), al, be))),
                                             FL(pack_bf16(fmaf(bf_lo(UI(v.y)), al, be), fmaf(bf_hi(UI(v.y)), al, be))));
        }
        if (lane < 2 - L) mbar_arrive(L ? BAR(B_PAR) : BAR(B_XFREE + lane));
      }
      if (!L && (tid >> 4) == bc) st_ll(&P.g->statF[blk * 128 + tid], UI(m), UI(var), 0u, tag + 1);
      PROFW(tid == 0, 18 + L * 6);
      FRESH();
      a = poll_ll(&P.g->best[bc][lane & 15], 0xfffff800u, tag << 11);
      win = __ffs(__ballot_sync(0xffffffffu, a.x == __reduce_max_sync(0xffffffffu, a.x))) - 1;
      idx = __shfl_sync(0xffffffffu, a.w, win) & 2047;
      PROFW(tid == 0, 19 + L * 6);
      poll_ll2(&P.g->row[win][2 * tid], &P.g->row[win][2 * tid + 1], 0xffffffffu, tag, c, b);
      c.z = b.x; c.w = b.y;
      a.x = __shfl_sync(0xffffffffu, a.x, win); a.y = __shfl_sync(0xffffffffu, a.y, win); a.z = __shfl_sync(0xffffffffu, a.z, win);
      sts32(sb + INFO2 + 28, idx);
      PROFW(tid == 0, 61 + L);
      b = norm8(c, FL(a.y), FL(a.z), sb + HV + tid * 32);
      if (L && fid < 112) bar_arrive(3, 384);
      if (tid == bid) {
        float r = FL(a.x ^ (~(uint32_t)((int)a.x >> 31) | 0x80000000u));
        sts128(sb + RED + 64, c); sts128(sb + RED + 80, b);
        sts32f(sb + RED + 96, bf_round(__fdividef(1.f, 1.f + __expf(-bf_round(r)))));
      }
      if (L) {
        if (wq == 0 && win != blk) *(float2*)(P.out + (size_t)lds32(sb + INFO + 4) * 1024 + bc * 128 + lane * 4) = lds64f(sb + RED + 1792 + lane * 8);
      } else {
        if (fid < 112) { st_ll(&P.g->yP[tid & ~1][fid][tid & 1], 0u, 0u, 0u, 0u); st_ll(&P.g->yP[tid | 1][fid][tid & 1], 0u, 0u, 0u, 0u); }
        if (tid < 10) st_ll(tid < 2 ? &P.g->x2[2 * bid + tid] : &P.g->patch[fid * 8 + tid - 2], 0u, 0u, 0u, 0u);
      }
      bar_sync(2, 128);
    }
    #pragma unroll 1
    for (int st = L; st < 3; st++) {
      FRESH();
      float a[8] = {0.f, 0.f, 0.f, 0.f, 0.f, 0.f, 0.f, 0.f};
      if (L == 0 && fid < (st == 2 ? 96 : 112)) {
        uint32_t ha = st == 1 ? sb + RED + 768 : sb + HV + ((st ? wq : wq & 1) * 64 + (lane >> 2)) * 4;
        uint32_t ph = (st ? (st == 1 ? 0x1cu : 0x11u) : 0x171u), bar = st == 1 ? BAR(B_STG + 2) : BAR(B_STG);
        uint32_t wa = sb + STG + tid * 16 + wq * 3584 + (st == 1 ? 32768 : 0);
        const uint32_t hx = st == 1 ? 256 : (st ? 1024 : 512);
        const bool lead = lane == 0;
        #pragma unroll 1
        do {
          mbar_wait(bar, ph & 1);
          PROFW(lead && threadIdx.x == 256 && st == 0 && (ph > 255 || ph < 4), 40 - 23 + __clz(ph));
          gemv8(a, wa, ha, 32);
          __syncwarp();
          if (lead) mbar_arrive(bar - 8 * (B_STG - B_STGE));
          const bool wrap = bar == BAR(B_STG + 2);
          bar += wrap ? -16 : 8; wa += wrap ? -32768 : 16384; ha += hx;
          ph >>= 1;
        } while (ph != 1);
      }
      FRESH();
      if (st == 1) {
        const uint32_t t8 = lds32(sb + INFO + 12) + L;
        if (L == 0 && fid < 112) {
          const bool odd = lane & 1;
          #pragma unroll
          for (int e = 0; e < 4; e++) { float z = __shfl_xor_sync(0xffffffffu, odd ? a[e] : a[4 + e], 1); if (odd) a[e] = z; else a[4 + e] = z; }
          uint4* dst = &P.g->yP[tid & ~1][fid][tid & 1];
          st_ll(dst, UI(a[0]), UI(a[1]), UI(a[2]), (UI(a[3]) & ~255u) | t8);
          st_ll(dst + 224, UI(a[4]), UI(a[5]), UI(a[6]), (UI(a[7]) & ~255u) | t8);
          PROFW(tid == 0, 21);
        }
        if (!L) qkv_params(P, sb, bi * 256 + tid, tag + 1, true);
        uint4 v0, v1;
        poll_ll2(&P.g->yP[bid][min(tid, 111)][0], &P.g->yP[bid][min(tid, 111)][1], 255u, t8, v0, v1);
        const float on = tid < 112 ? 1.f : 0.f;
        a[0] = FL(v0.x) * on; a[1] = FL(v0.y) * on; a[2] = FL(v0.z) * on; a[3] = FL((v0.w & ~255u) | 128u) * on;
        a[4] = FL(v1.x) * on; a[5] = FL(v1.y) * on; a[6] = FL(v1.z) * on; a[7] = FL((v1.w & ~255u) | 128u) * on;
      }
      sts32f(sb + RED + 256 + wq * 128 + ((lane & 3) * 8 + (lane >> 2)) * 4, fold8(a));
      bar_sync(2, 128);
      const uint32_t d = sb + RED + 256 + lane * 4;
      float z0 = lds32f(d) + lds32f(d + 128), z1 = lds32f(d + 256) + lds32f(d + 384);
      if (st == 0) { sts32f(sb + RED + 768 + lane * 32 + wq * 4, swiglu(z0, z1)); bar_sync(2, 128); PROFW(tid == 0, 20); continue; }
      z0 += z1;
      if (st == 1) {
        z0 += __shfl_xor_sync(0xffffffffu, z0, 8); z0 += __shfl_xor_sync(0xffffffffu, z0, 16);
        uint32_t xw = lds32(sb + RED + 64 + (lane & 6) * 2), hw = lds32(sb + RED + 80 + (lane & 6) * 2);
        z0 = bf_round(((lane & 1) ? bf_hi(hw) : bf_lo(hw)) + bf_round(bf_round(z0) * lds32f(sb + RED + 96))) + ((lane & 1) ? bf_hi(xw) : bf_lo(xw));
      } else if (fid < 32) z0 *= QSCALE;
      uint32_t v = pack_bf16(z0, __shfl_down_sync(0xffffffffu, z0, 1)), v2 = __shfl_down_sync(0xffffffffu, v, 2);
      if (L) { if (tid == 0 || tid == 4) *(uint2*)(P.out + (size_t)idx * 1024 + bid * 8 + tid) = make_uint2(v, v2); PROFW(tid == 0, 28); break; }
      if ((tid & 3) == 0 && tid < (st == 1 ? 8 : 32)) st_ll(st == 1 ? &P.g->x2[2 * bid + (tid >> 2)] : &P.g->patch[fid * 8 + (tid >> 2)], v, v2, 0u, tag + 1);
      PROFW(tid == 0, st == 1 ? 22 : 31);
      if (st == 1) {
        uint4 x, y; poll_ll2(&P.g->x2[2 * tid], &P.g->x2[2 * tid + 1], 0xffffffffu, tag + 1, x, y);
        x.z = y.x; x.w = y.y;
        if ((tid >> 4) == bc) sts128(sb + X2SEG + (tid & 15) * 16, x);
        float s1 = 0.f, s2 = 0.f;
        sum8(x, s1, s2);
        #pragma unroll
        for (int o = 16; o; o >>= 1) { s1 += __shfl_xor_sync(0xffffffffu, s1, o); s2 += __shfl_xor_sync(0xffffffffu, s2, o); }
        sts64f(sb + RED + wq * 8, s1, s2);
        bar_sync(2, 128);
        y = lds128(sb + RED); uint4 y2 = lds128(sb + RED + 16);
        float m = ((FL(y.x) + FL(y.z)) + (FL(y2.x) + FL(y2.z))) * (1.f / 1024.f);
        norm8(x, m, rsqrtf(fmaxf(fmaf(-m, m, ((FL(y.y) + FL(y.w)) + (FL(y2.y) + FL(y2.w))) * (1.f / 1024.f)), 0.f) + LN_EPS), sb + HV + tid * 32);
        bar_sync(2, 128);
        PROFW(tid == 0, 30);
      }
    }
  }
  if (bid == 0 && tid == 0) P.g->epoch = lds32(sb + INFO2 + 16) + 1;
  #undef blk
  #undef bid
  #undef fid
  #undef bi
  #undef bp
  #undef bc
  #undef FRESH
  #undef lane
  #undef wq
}

__global__ void __cluster_dims__(2, 1, 1) __launch_bounds__(512, 1) fused_kernel(const __grid_constant__ Params P) {
  extern __shared__ __align__(1024) uint8_t smem_raw[];
  const uint32_t sb = smem_u32(smem_raw);
  PROFT(threadIdx.x == 0, 0);
  if (threadIdx.x == 0) {
    for (int s = 0; s < 3; s++) mbar_init(BAR(B_FULLQ + s), 1);
    asm volatile("fence.mbarrier_init.release.cluster;" ::: "memory");
    for (int s = 0; s < 3; s++) {
      mbar_expect_tx(BAR(B_FULLQ + s), 57344);
      tma_2d(sb + qa_off(s), &P.mX, s * 64, (BID >> 4) * 256, BAR(B_FULLQ + s));
      tma_3d(sb + qb_off(s), &P.mWq, (BID & 15) * 64, s * 64, 0, BAR(B_FULLQ + s));
    }
    if ((sb & 4095) != 1024) __trap();
  } else if (threadIdx.x >= 32 + B_EMPTYQ && threadIdx.x < 32 + B_COUNT) {
    const int b = threadIdx.x - 32;
    const uint32_t cnt = b < B_XFREE ? 2 : (b < B_KVRDY ? 3 : (b < B_KVFULL ? 4 : 1));
    mbar_init(BAR(b), cnt);
    asm volatile("fence.mbarrier_init.release.cluster;" ::: "memory");
  }
  __syncthreads();
  asm volatile("barrier.cluster.arrive.relaxed.aligned;" ::: "memory");
  const int wg = __shfl_sync(0xffffffffu, threadIdx.x >> 7, 0);
  if (wg < 2) { reg_inc<224>(); consumer(P, sb, wg); }
  else if (wg == 2) { reg_dec<40>(); aux(P, sb); }
  else {
    reg_dec<24>();
    asm volatile("barrier.cluster.wait.aligned;" ::: "memory");
    const int w = __shfl_sync(0xffffffffu, (threadIdx.x >> 5) & 3, 0);
    if (w == 0) loader(P, sb);
    else if (w < 3) storer(P, sb, w - 1);
    else if ((threadIdx.x & 31) == 0) stager(P, sb);
  }
}

typedef CUresult (*EncFn)(CUtensorMap*, CUtensorMapDataType, cuuint32_t, void*, const cuuint64_t*, const cuuint64_t*, const cuuint32_t*, const cuuint32_t*,
                          CUtensorMapInterleave, CUtensorMapSwizzle, CUtensorMapL2promotion, CUtensorMapFloatOOBfill);
static void mk_map(EncFn enc, CUtensorMap* m, const void* ptr, int rank, const cuuint64_t* dims, const cuuint64_t* strides, const cuuint32_t* box,
                   CUtensorMapSwizzle sw, CUtensorMapL2promotion pr) {
  cuuint32_t es[5] = {1, 1, 1, 1, 1};
  enc(m, CU_TENSOR_MAP_DATA_TYPE_BFLOAT16, rank, (void*)ptr, dims, strides, box, es, CU_TENSOR_MAP_INTERLEAVE_NONE, sw, pr, CU_TENSOR_MAP_FLOAT_OOB_FILL_NONE);
}
extern "C" void kernel_launch(void* const* d_in, const int* in_sizes, int n_in, void* d_out, int out_size) {
  (void)in_sizes; (void)n_in; (void)out_size;
  void* fn = nullptr; cudaDriverEntryPointQueryResult q;
  cudaGetDriverEntryPoint("cuTensorMapEncodeTiled", &fn, cudaEnableDefault, &q);
  EncFn enc = (EncFn)fn;
  cudaFuncSetAttribute(fused_kernel, cudaFuncAttributeMaxDynamicSharedMemorySize, SMEM_BYTES);
  Params P;
  const CUtensorMapSwizzle S128 = CU_TENSOR_MAP_SWIZZLE_128B, S0 = CU_TENSOR_MAP_SWIZZLE_NONE;
  const CUtensorMapL2promotion L256 = CU_TENSOR_MAP_L2_PROMOTION_L2_256B, L128 = CU_TENSOR_MAP_L2_PROMOTION_L2_128B;
  { cuuint64_t d[2] = {1024, 2048}, s[1] = {2048}; cuuint32_t b[2] = {64, 256}, bh[2] = {64, 128};
    mk_map(enc, &P.mX, d_in[0], 2, d, s, b, S128, L256); mk_map(enc, &P.mXh, d_in[0], 2, d, s, bh, S128, L256); }
  { cuuint64_t d[3] = {1024, 1024, 3}, s[2] = {6144, 2048}; cuuint32_t b[3] = {64, 64, 3}; mk_map(enc, &P.mWq, d_in[1], 3, d, s, b, S128, L256); }
  { cuuint64_t d[5] = {64, 32, 2, 16, 16}, s[4] = {2048, 65536, 131072, 128}; cuuint32_t b[5] = {64, 32, 1, 2, 2}; mk_map(enc, &P.mWo, d_in[2], 5, d, s, b, S128, L256); }
  { cuuint64_t d[2] = {3584, 1024}, s[1] = {7168}; cuuint32_t b[2] = {32, 128};
    mk_map(enc, &P.mWg, d_in[5], 2, d, s, b, S0, L128); mk_map(enc, &P.mWu, d_in[6], 2, d, s, b, S0, L128); }
  { cuuint64_t d[2] = {3072, 1024}, s[1] = {6144}; cuuint32_t b[2] = {32, 256}; mk_map(enc, &P.mWp, d_in[1], 2, d, s, b, S0, L128); }
  { cuuint64_t d[3] = {256, 3584, 4}, s[2] = {2048, 512}; cuuint32_t b[3] = {256, 8, 4}; mk_map(enc, &P.mWd, d_in[7], 3, d, s, b, S0, L128); }
  P.x0 = (const bf16*)d_in[0]; P.wqkv = (const bf16*)d_in[1]; P.wo = (const bf16*)d_in[2]; P.wr = (const bf16*)d_in[4]; P.wg = (const bf16*)d_in[5]; P.wu = (const bf16*)d_in[6]; P.wd = (const bf16*)d_in[7];
  P.out = (bf16*)d_out;
  cudaGetSymbolAddress((void**)&P.g, g_scr);
  for (int b = 0; b < 128; b++) {
    int j = b >> 1, quad = j < 4 ? 0 : (j < 36 ? 1 + (j - 4) % 8 : 9 + (j - 36) % 7), pos = j < 4 ? j : (j < 36 ? (j - 4) / 8 : (j - 36) / 7);
    int bid = ((quad >> 2) * 2 + (pos >> 1)) * 16 + ((quad & 3) * 2 + (pos & 1)) * 2 + (b & 1);
    int e = pos * 2 + (b & 1), fid = e < 6 ? quad * 6 + e : e * 16 + quad;
    P.map[b] = bid | fid << 8;
  }
  fused_kernel<<<128, 512, SMEM_BYTES>>>(P);
}
```

```cpp
#include <cuda_runtime.h>
#include <cuda_bf16.h>
#include <cuda.h>
#include <stdint.h>
#include <stddef.h>
typedef __nv_bfloat16 bf16;

template<int TB, int TA = 0> __device__ __forceinline__ void wgmma_ss_n192(float (&d)[96], uint64_t da, uint64_t db, int scale_d) {
  asm volatile("{\n.reg .pred p;\nsetp.ne.b32 p, %98, 0;\n"
    "wgmma.mma_async.sync.aligned.m64n192k16.f32.bf16.bf16 {%0, %1, %2, %3, %4, %5, %6, %7, %8, %9, %10, %11, %12, %13, %14, %15, %16, %17, %18, %19, %20, %21, %22, %23, %24, %25, %26, %27, %28, %29, %30, %31, %32, %33, %34, %35, %36, %37, %38, %39, %40, %41, %42, %43, %44, %45, %46, %47, %48, %49, %50, %51, %52, %53, %54, %55, %56, %57, %58, %59, %60, %61, %62, %63, %64, %65, %66, %67, %68, %69, %70, %71, %72, %73, %74, %75, %76, %77, %78, %79, %80, %81, %82, %83, %84, %85, %86, %87, %88, %89, %90, %91, %92, %93, %94, %95}, %96, %97, p, 1, 1, %100, %99;\n}\n"
    : "+f"(d[0]), "+f"(d[1]), "+f"(d[2]), "+f"(d[3]), "+f"(d[4]), "+f"(d[5]), "+f"(d[6]), "+f"(d[7]), "+f"(d[8]), "+f"(d[9]), "+f"(d[10]), "+f"(d[11]), "+f"(d[12]), "+f"(d[13]), "+f"(d[14]), "+f"(d[15]), "+f"(d[16]), "+f"(d[17]), "+f"(d[18]), "+f"(d[19]), "+f"(d[20]), "+f"(d[21]), "+f"(d[22]), "+f"(d[23]), "+f"(d[24]), "+f"(d[25]), "+f"(d[26]), "+f"(d[27]), "+f"(d[28]), "+f"(d[29]), "+f"(d[30]), "+f"(d[31]), "+f"(d[32]), "+f"(d[33]), "+f"(d[34]), "+f"(d[35]), "+f"(d[36]), "+f"(d[37]), "+f"(d[38]), "+f"(d[39]), "+f"(d[40]), "+f"(d[41]), "+f"(d[42]), "+f"(d[43]), "+f"(d[44]), "+f"(d[45]), "+f"(d[46]), "+f"(d[47]), "+f"(d[48]), "+f"(d[49]), "+f"(d[50]), "+f"(d[51]), "+f"(d[52]), "+f"(d[53]), "+f"(d[54]), "+f"(d[55]), "+f"(d[56]), "+f"(d[57]), "+f"(d[58]), "+f"(d[59]), "+f"(d[60]), "+f"(d[61]), "+f"(d[62]), "+f"(d[63]), "+f"(d[64]), "+f"(d[65]), "+f"(d[66]), "+f"(d[67]), "+f"(d[68]), "+f"(d[69]), "+f"(d[70]), "+f"(d[71]), "+f"(d[72]), "+f"(d[73]), "+f"(d[74]), "+f"(d[75]), "+f"(d[76]), "+f"(d[77]), "+f"(d[78]), "+f"(d[79]), "+f"(d[80]), "+f"(d[81]), "+f"(d[82]), "+f"(d[83]), "+f"(d[84]), "+f"(d[85]), "+f"(d[86]), "+f"(d[87]), "+f"(d[88]), "+f"(d[89]), "+f"(d[90]), "+f"(d[91]), "+f"(d[92]), "+f"(d[93]), "+f"(d[94]), "+f"(d[95])
    : "l"(da), "l"(db), "r"(scale_d), "n"(TB), "n"(TA));
}

template<int TB, int TA = 0> __device__ __forceinline__ void wgmma_ss_n128(float (&d)[64], uint64_t da, uint64_t db, int scale_d) {
  asm volatile("{\n.reg .pred p;\nsetp.ne.b32 p, %66, 0;\n"
    "wgmma.mma_async.sync.aligned.m64n128k16.f32.bf16.bf16 {%0, %1, %2, %3, %4, %5, %6, %7, %8, %9, %10, %11, %12, %13, %14, %15, %16, %17, %18, %19, %20, %21, %22, %23, %24, %25, %26, %27, %28, %29, %30, %31, %32, %33, %34, %35, %36, %37, %38, %39, %40, %41, %42, %43, %44, %45, %46, %47, %48, %49, %50, %51, %52, %53, %54, %55, %56, %57, %58, %59, %60, %61, %62, %63}, %64, %65, p, 1, 1, %68, %67;\n}\n"
    : "+f"(d[0]), "+f"(d[1]), "+f"(d[2]), "+f"(d[3]), "+f"(d[4]), "+f"(d[5]), "+f"(d[6]), "+f"(d[7]), "+f"(d[8]), "+f"(d[9]), "+f"(d[10]), "+f"(d[11]), "+f"(d[12]), "+f"(d[13]), "+f"(d[14]), "+f"(d[15]), "+f"(d[16]), "+f"(d[17]), "+f"(d[18]), "+f"(d[19]), "+f"(d[20]), "+f"(d[21]), "+f"(d[22]), "+f"(d[23]), "+f"(d[24]), "+f"(d[25]), "+f"(d[26]), "+f"(d[27]), "+f"(d[28]), "+f"(d[29]), "+f"(d[30]), "+f"(d[31]), "+f"(d[32]), "+f"(d[33]), "+f"(d[34]), "+f"(d[35]), "+f"(d[36]), "+f"(d[37]), "+f"(d[38]), "+f"(d[39]), "+f"(d[40]), "+f"(d[41]), "+f"(d[42]), "+f"(d[43]), "+f"(d[44]), "+f"(d[45]), "+f"(d[46]), "+f"(d[47]), "+f"(d[48]), "+f"(d[49]), "+f"(d[50]), "+f"(d[51]), "+f"(d[52]), "+f"(d[53]), "+f"(d[54]), "+f"(d[55]), "+f"(d[56]), "+f"(d[57]), "+f"(d[58]), "+f"(d[59]), "+f"(d[60]), "+f"(d[61]), "+f"(d[62]), "+f"(d[63])
    : "l"(da), "l"(db), "r"(scale_d), "n"(TB), "n"(TA));
}

template<int TB, int TA = 0> __device__ __forceinline__ void wgmma_ss_n64(float (&d)[32], uint64_t da, uint64_t db, int scale_d) {
  asm volatile("{\n.reg .pred p;\nsetp.ne.b32 p, %34, 0;\n"
    "wgmma.mma_async.sync.aligned.m64n64k16.f32.bf16.bf16 {%0, %1, %2, %3, %4, %5, %6, %7, %8, %9, %10, %11, %12, %13, %14, %15, %16, %17, %18, %19, %20, %21, %22, %23, %24, %25, %26, %27, %28, %29, %30, %31}, %32, %33, p, 1, 1, %36, %35;\n}\n"
    : "+f"(d[0]), "+f"(d[1]), "+f"(d[2]), "+f"(d[3]), "+f"(d[4]), "+f"(d[5]), "+f"(d[6]), "+f"(d[7]), "+f"(d[8]), "+f"(d[9]), "+f"(d[10]), "+f"(d[11]), "+f"(d[12]), "+f"(d[13]), "+f"(d[14]), "+f"(d[15]), "+f"(d[16]), "+f"(d[17]), "+f"(d[18]), "+f"(d[19]), "+f"(d[20]), "+f"(d[21]), "+f"(d[22]), "+f"(d[23]), "+f"(d[24]), "+f"(d[25]), "+f"(d[26]), "+f"(d[27]), "+f"(d[28]), "+f"(d[29]), "+f"(d[30]), "+f"(d[31])
    : "l"(da), "l"(db), "r"(scale_d), "n"(TB), "n"(TA));
}

template<int TB> __device__ __forceinline__ void wgmma_rs_n40(float (&d)[20], uint32_t a0, uint32_t a1, uint32_t a2, uint32_t a3, uint64_t db, int scale_d) {
  asm volatile("{\n.reg .pred p;\nsetp.ne.b32 p, %25, 0;\n"
    "wgmma.mma_async.sync.aligned.m64n40k16.f32.bf16.bf16 {%0, %1, %2, %3, %4, %5, %6, %7, %8, %9, %10, %11, %12, %13, %14, %15, %16, %17, %18, %19}, {%20, %21, %22, %23}, %24, p, 1, 1, %26;\n}\n"
    : "+f"(d[0]), "+f"(d[1]), "+f"(d[2]), "+f"(d[3]), "+f"(d[4]), "+f"(d[5]), "+f"(d[6]), "+f"(d[7]), "+f"(d[8]), "+f"(d[9]), "+f"(d[10]), "+f"(d[11]), "+f"(d[12]), "+f"(d[13]), "+f"(d[14]), "+f"(d[15]), "+f"(d[16]), "+f"(d[17]), "+f"(d[18]), "+f"(d[19])
    : "r"(a0), "r"(a1), "r"(a2), "r"(a3), "l"(db), "r"(scale_d), "n"(TB));
}

#define DEVI __device__ __forceinline__
DEVI uint32_t smem_u32(const void* p) { return (uint32_t)__cvta_generic_to_shared(p); }
DEVI void mbar_init(uint32_t bar, uint32_t cnt) { asm volatile("mbarrier.init.shared::cta.b64 [%0], %1;" :: "r"(bar), "r"(cnt)); }
DEVI void mbar_expect_tx(uint32_t bar, uint32_t bytes) { asm volatile("mbarrier.arrive.expect_tx.shared::cta.b64 _, [%0], %1;" :: "r"(bar), "r"(bytes) : "memory"); }
DEVI void mbar_arrive(uint32_t bar) { asm volatile("mbarrier.arrive.shared::cta.b64 _, [%0];" :: "r"(bar) : "memory"); }
DEVI void mbar_arrive_peer(uint32_t bar) {
  asm volatile("{\n.reg .b32 ra;\nmapa.shared::cluster.u32 ra, %0, %1;\nmbarrier.arrive.shared::cluster.b64 _, [ra];\n}" :: "r"(bar), "r"((blockIdx.x & 1) ^ 1) : "memory");
}
DEVI void bulk_s2peer(uint32_t a, uint32_t bytes, uint32_t bar) {
  asm volatile("{\n.reg .b32 ra, rb;\nmapa.shared::cluster.u32 ra, %0, %3;\nmapa.shared::cluster.u32 rb, %2, %3;\n"
               "cp.async.bulk.shared::cluster.shared::cta.mbarrier::complete_tx::bytes [ra], [%0], %1, [rb];\n}"
               :: "r"(a), "r"(bytes), "r"(bar), "r"((blockIdx.x & 1) ^ 1) : "memory");
}
DEVI void mbar_wait(uint32_t bar, uint32_t parity) {
  asm volatile("{\n.reg .pred p;\nLW:\nmbarrier.try_wait.parity.shared::cta.b64 p, [%0], %1;\n@!p bra LW;\n}" :: "r"(bar), "r"(parity) : "memory");
}
DEVI void mbar_wait_b(uint32_t bar, uint32_t parity) {
  asm volatile("{\n.reg .pred p;\n.reg .u32 it;\nmov.u32 it, 0;\nLW:\nmbarrier.try_wait.parity.shared::cta.b64 p, [%0], %1;\n@p bra LD;\n"
               "add.u32 it, it, 1;\nsetp.lt.u32 p, it, 0x1000000;\n@p bra LW;\ntrap;\nLD:\n}" :: "r"(bar), "r"(parity) : "memory");
}
DEVI void tma_2d(uint32_t dst, const CUtensorMap* m, int c0, int c1, uint32_t bar) {
  asm volatile("cp.async.bulk.tensor.2d.shared::cluster.global.mbarrier::complete_tx::bytes [%0], [%1, {%3, %4}], [%2];"
    :: "r"(dst), "l"(m), "r"(bar), "r"(c0), "r"(c1) : "memory");
}
DEVI void tma_3d(uint32_t dst, const CUtensorMap* m, int c0, int c1, int c2, uint32_t bar) {
  asm volatile("cp.async.bulk.tensor.3d.shared::cluster.global.mbarrier::complete_tx::bytes [%0], [%1, {%3, %4, %5}], [%2];"
    :: "r"(dst), "l"(m), "r"(bar), "r"(c0), "r"(c1), "r"(c2) : "memory");
}
#define POL_EF POL_FIRST
constexpr uint64_t POL_FIRST = 0x12F0000000000000ull, POL_NORMAL = 0x1000000000000000ull;
DEVI void tma_2d_h(uint32_t dst, const CUtensorMap* m, int c0, int c1, uint32_t bar, uint64_t pol) {
  asm volatile("cp.async.bulk.tensor.2d.shared::cluster.global.mbarrier::complete_tx::bytes.L2::cache_hint [%0], [%1, {%3, %4}], [%2], %5;"
    :: "r"(dst), "l"(m), "r"(bar), "r"(c0), "r"(c1), "l"(pol) : "memory");
}
DEVI void tma_3d_h(uint32_t dst, const CUtensorMap* m, int c0, int c1, int c2, uint32_t bar, uint64_t pol) {
  asm volatile("cp.async.bulk.tensor.3d.shared::cluster.global.mbarrier::complete_tx::bytes.L2::cache_hint [%0], [%1, {%3, %4, %5}], [%2], %6;"
    :: "r"(dst), "l"(m), "r"(bar), "r"(c0), "r"(c1), "r"(c2), "l"(pol) : "memory");
}
DEVI void bulk_g2s_h(uint32_t s, const void* g, uint32_t bytes, uint32_t bar, uint64_t pol = POL_EF) {
  asm volatile("cp.async.bulk.shared::cluster.global.mbarrier::complete_tx::bytes.L2::cache_hint [%0], [%1], %2, [%3], %4;"
    :: "r"(s), "l"(g), "r"(bytes), "r"(bar), "l"(pol) : "memory");
}
DEVI void tma_5d(uint32_t dst, const CUtensorMap* m, int c0, int c1, int c2, int c3, int c4, uint32_t bar, uint64_t pol) {
  asm volatile("cp.async.bulk.tensor.5d.shared::cluster.global.mbarrier::complete_tx::bytes.L2::cache_hint [%0], [%1, {%3, %4, %5, %6, %7}], [%2], %8;"
    :: "r"(dst), "l"(m), "r"(bar), "r"(c0), "r"(c1), "r"(c2), "r"(c3), "r"(c4), "l"(pol) : "memory");
}
DEVI void tma_prefetch_2d(const CUtensorMap* m, int c0, int c1) {
  asm volatile("cp.async.bulk.prefetch.tensor.2d.L2.global.tile [%0, {%1, %2}];" :: "l"(m), "r"(c0), "r"(c1) : "memory");
}
DEVI void tma_prefetch_3d(const CUtensorMap* m, int c0, int c1, int c2) {
  asm volatile("cp.async.bulk.prefetch.tensor.3d.L2.global.tile [%0, {%1, %2, %3}];" :: "l"(m), "r"(c0), "r"(c1), "r"(c2) : "memory");
}
DEVI void bulk_prefetch(const void* g, uint32_t bytes) { asm volatile("cp.async.bulk.prefetch.L2.global [%0], %1;" :: "l"(g), "r"(bytes) : "memory"); }
DEVI void bulk_g2s(uint32_t s, const void* g, uint32_t bytes, uint32_t bar) {
  asm volatile("cp.async.bulk.shared::cluster.global.mbarrier::complete_tx::bytes [%0], [%1], %2, [%3];" :: "r"(s), "l"(g), "r"(bytes), "r"(bar) : "memory");
}
DEVI void bulk_s2g(void* g, uint32_t s, uint32_t bytes) {
  asm volatile("cp.async.bulk.global.shared::cta.bulk_group [%0], [%1], %2;\ncp.async.bulk.commit_group;" :: "l"(g), "r"(s), "r"(bytes) : "memory");
}
template<int N> DEVI void bulk_wait() { asm volatile("cp.async.bulk.wait_group %0;" :: "n"(N) : "memory"); }
DEVI void fence_async_smem() { asm volatile("fence.proxy.async.shared::cta;" ::: "memory"); }
DEVI void fence_async_glob() { asm volatile("fence.proxy.async.global;" ::: "memory"); }
DEVI unsigned ld_rlx(const unsigned* p) { unsigned v; asm volatile("ld.relaxed.gpu.global.u32 %0, [%1];" : "=r"(v) : "l"(p) : "memory"); return v; }
DEVI void st_rlx(unsigned* p, unsigned v) { asm volatile("st.relaxed.gpu.global.u32 [%0], %1;" :: "l"(p), "r"(v) : "memory"); }
DEVI uint2 ldg_stream(const uint2* p) { uint2 v; asm volatile("ld.global.nc.L1::no_allocate.v2.u32 {%0, %1}, [%2];" : "=r"(v.x), "=r"(v.y) : "l"(p)); return v; }
DEVI void fence_rel() { asm volatile("fence.release.gpu;" ::: "memory"); }
DEVI uint4 ld_ll(const uint4* p) {
  uint4 v;
  asm volatile("{\n.reg .b128 t;\n.reg .b64 a, b;\nld.relaxed.gpu.global.b128 t, [%4];\nmov.b128 {a, b}, t;\nmov.b64 {%0, %1}, a;\nmov.b64 {%2, %3}, b;\n}"
               : "=r"(v.x), "=r"(v.y), "=r"(v.z), "=r"(v.w) : "l"(p) : "memory");
  return v;
}
DEVI void st_ll(uint4* p, uint32_t x, uint32_t y, uint32_t z, uint32_t w) {
  asm volatile("{\n.reg .b128 t;\n.reg .b64 a, b;\nmov.b64 a, {%1, %2};\nmov.b64 b, {%3, %4};\nmov.b128 t, {a, b};\nst.relaxed.gpu.global.b128 [%0], t;\n}"
               :: "l"(p), "r"(x), "r"(y), "r"(z), "r"(w) : "memory");
}
#define SPIN_MAX 0x1000000
DEVI uint4 poll_ll(const uint4* p, uint32_t mask, uint32_t tag) {
  uint4 v; int it = 0;
  do { v = ld_ll(p); if (++it > SPIN_MAX) __trap(); } while (!__all_sync(0xffffffffu, (v.w & mask) == tag));
  return v;
}
DEVI void poll_ll2(const uint4* p, const uint4* q, uint32_t mask, uint32_t tag, uint4& a, uint4& b) {
  int it = 0;
  do { a = ld_ll(p); b = ld_ll(q); if (++it > SPIN_MAX) __trap(); } while (!__all_sync(0xffffffffu, (a.w & mask) == tag && (b.w & mask) == tag));
}
DEVI void bar_sync(int id, int n) { asm volatile("bar.sync %0, %1;" :: "r"(id), "r"(n) : "memory"); }
DEVI void bar_arrive(int id, int n) { asm volatile("bar.arrive %0, %1;" :: "r"(id), "r"(n) : "memory"); }
DEVI void wg_fence() { asm volatile("wgmma.fence.sync.aligned;" ::: "memory"); }
DEVI void wg_commit() { asm volatile("wgmma.commit_group.sync.aligned;" ::: "memory"); }
template<int N> DEVI void wg_wait() { asm volatile("wgmma.wait_group.sync.aligned %0;" :: "n"(N) : "memory"); }
template<int N> DEVI void reg_inc() { asm volatile("setmaxnreg.inc.sync.aligned.u32 %0;" :: "n"(N)); }
template<int N> DEVI void reg_dec() { asm volatile("setmaxnreg.dec.sync.aligned.u32 %0;" :: "n"(N)); }
DEVI float ex2f(float x) { float y; asm("ex2.approx.ftz.f32 %0, %1;" : "=f"(y) : "f"(x)); return y; }
DEVI uint32_t pack_bf16(float lo, float hi) { uint32_t r; asm("cvt.rn.bf16x2.f32 %0, %1, %2;" : "=r"(r) : "f"(hi), "f"(lo)); return r; }
DEVI float bf_lo(uint32_t v) { return __uint_as_float(v << 16); }
DEVI float bf_hi(uint32_t v) { return __uint_as_float(v & 0xffff0000u); }
DEVI float bf_round(float x) { return bf_lo(pack_bf16(x, 0.f)); }
DEVI void stsm_x4(uint32_t addr, uint32_t a, uint32_t b, uint32_t c, uint32_t d) {
  asm volatile("stmatrix.sync.aligned.m8n8.x4.shared.b16 [%0], {%1,%2,%3,%4};" :: "r"(addr), "r"(a), "r"(b), "r"(c), "r"(d) : "memory");
}
DEVI void ldsm_x4(uint32_t addr, uint32_t& a, uint32_t& b, uint32_t& c, uint32_t& d) {
  asm volatile("ldmatrix.sync.aligned.m8n8.x4.shared.b16 {%0,%1,%2,%3}, [%4];" : "=r"(a), "=r"(b), "=r"(c), "=r"(d) : "r"(addr) : "memory");
}
DEVI uint4 lds128(uint32_t a) { uint4 v; asm volatile("ld.shared.v4.u32 {%0,%1,%2,%3}, [%4];" : "=r"(v.x), "=r"(v.y), "=r"(v.z), "=r"(v.w) : "r"(a) : "memory"); return v; }
DEVI void sts128(uint32_t a, uint4 v) { asm volatile("st.shared.v4.u32 [%0], {%1,%2,%3,%4};" :: "r"(a), "r"(v.x), "r"(v.y), "r"(v.z), "r"(v.w) : "memory"); }
DEVI float2 lds64f(uint32_t a) { float2 v; asm volatile("ld.shared.v2.f32 {%0,%1}, [%2];" : "=f"(v.x), "=f"(v.y) : "r"(a) : "memory"); return v; }
DEVI void sts64f(uint32_t a, float x, float y) { asm volatile("st.shared.v2.f32 [%0], {%1,%2};" :: "r"(a), "f"(x), "f"(y) : "memory"); }
DEVI uint32_t lds32(uint32_t a) { uint32_t v; asm volatile("ld.shared.u32 %0, [%1];" : "=r"(v) : "r"(a) : "memory"); return v; }
DEVI float lds32f(uint32_t a) { return __uint_as_float(lds32(a)); }
DEVI void sts32(uint32_t a, uint32_t v) { asm volatile("st.shared.u32 [%0], %1;" :: "r"(a), "r"(v) : "memory"); }
DEVI void sts32f(uint32_t a, float v) { sts32(a, __float_as_uint(v)); }
DEVI void sts16(uint32_t a, uint32_t v) { asm volatile("st.shared.u16 [%0], %1;" :: "r"(a), "h"((unsigned short)v) : "memory"); }
template<int N> DEVI void keep(float (&d)[N]) {
  #pragma unroll
  for (int i = 0; i < N; i++) asm volatile("" : "+f"(d[i]) :: "memory");
}
template<int N> DEVI void keep(uint32_t (&d)[N]) {
  #pragma unroll
  for (int i = 0; i < N; i++) asm volatile("" : "+r"(d[i]) :: "memory");
}
template<uint32_t HI> DEVI uint64_t mkd(uint32_t lo) { uint64_t r; asm("mov.b64 %0, {%1, %2};" : "=l"(r) : "r"(lo), "n"(HI)); return r; }
constexpr uint32_t HI128 = (1u << 30) | (1024 >> 4), HI64 = (2u << 30) | (512 >> 4);
#define VOFF(x) ((uint32_t)(x) * (uint32_t)(1 - 65536))
DEVI void warp_signal(uint32_t bar) { fence_async_smem(); __syncwarp(); if ((threadIdx.x & 31) == 0) mbar_arrive(bar); }

struct Scratch {
  uint4 kv[128][8][512];
  uint4 o[8][2][8][2][1024];
  uint4 x[8][16][2048];
  uint4 zero[1024];
  uint4 statP[8][2048];
  uint4 statF[2048];
  uint4 csP[16][8][96];
  uint4 best[8][16];
  uint4 row[16][256];
  uint4 yP[128][112][2];
  uint4 x2[8][256];
  uint4 patch[1024];
  unsigned flagKV[128][32];
  unsigned flagO[8][2][2][32];
  unsigned flagX[8][32];
  unsigned epoch;
};
static_assert(offsetof(Scratch, flagO) % 256 == 0, "");
__device__ __align__(1024) Scratch g_scr;
#define PROFT(cond, slot)
#define PROFW(cond, slot)
#define PROFD(cond, slot)
#define PROFX(cond, slot)
#define PROFY(cond, slot)

constexpr uint32_t SB0 = 65536, HOLE = 90112, SA2 = 98304, SB1 = 131072, SB2 = 155648, STG = 180224;
constexpr uint32_t KVA = 98304, KVB = 0, QO = 65536;
constexpr uint32_t MISC = 229376, ONES = MISC, BARS = MISC + 1024, INFO = MISC + 1440, CS = MISC + 1456, WR = MISC + 2224, X2SEG = MISC + 2736, INFO2 = MISC + 2992;
constexpr uint32_t PAR = HOLE, HV = HOLE + 2048, RED = HOLE + 6144, PATCH = 196608;
constexpr uint32_t SMEM_BYTES = 232448;
enum { B_FULLQ = 0, B_EMPTYQ = 3, B_FULLW = 6, B_EMPTYW = 12, B_HAFREE = 18, B_OFREE = 20,
       B_XFREE = 21,
       B_KVRDY = 23, B_ORDY = 27, B_XRDY = 35, B_STGE = 39,
       B_KVFULL = 42, B_RES = 46, B_PAR = 47, B_STG = 48, B_PFREE = 51, B_COUNT = 52 };
#define BAR(x) (sb + BARS + 8 * (x))
DEVI uint32_t qa_off(int s) { return s == 2 ? SA2 : (uint32_t)s * 32768u; }
DEVI uint32_t qb_off(int s) { return s == 0 ? SB0 : (s == 1 ? SB1 : SB2); }
DEVI int kb_order(int bc, int n) {
  const int e = n < 9 ? n - 2 : n - 9;
  return n < 2 ? 2 * bc + n : 2 * (((e < 4 ? e + 4 : e - 4 + (e - 4 >= (bc & 3))) + (bc & 4)) & 7) + (n >= 9);
}
DEVI uint32_t w_off(int s) { return (uint32_t)((0x104365 >> (4 * s)) & 7) * 32768u; }
DEVI uint32_t w_par(int n, int s, int L) { return ((n >= 6 && n < 12) ^ (s < 4 && L)); }

struct Params {
  CUtensorMap mX, mXh, mWq, mWo, mWg, mWu, mWp, mWd;
  const bf16 *x0, *wqkv, *wo, *wr, *wg, *wu, *wd;
  bf16* out;
  Scratch* g;
  unsigned map[128];
};
#define BID ((int)(P.map[blockIdx.x] & 255))
#define FID ((int)(P.map[blockIdx.x] >> 8))
DEVI uint32_t uni(uint32_t v) { return __shfl_sync(0xffffffffu, v, 0); }
#define PQ_N 8
#define PQ_T 700
#define PF0_N 10
#define PF0_T 1600
#define PF1_E 24
#define PF1_T 900
#define POL_Q1 POL_NORMAL
#define POL_X POL_NORMAL
#define PFA0_BAR 3
#define PFA1_BAR 0
#define PFA0_M 0
#define PFA1_M 0
#define PFA0_T 900
#define PFA1_T 700
#define PF1_S PF0_N
#define PF1_D 0
#define POL_G POL_NORMAL
#define POL_U POL_FIRST
#define POL_D POL_FIRST
#define JQ_N 6
#define WDSRC (P.wd + (size_t)min(FID, 111) * 32768)
#define WD_N 4
#define THR_N 6
#define POL_Q0 POL_NORMAL
constexpr float LN_EPS = 1e-5f;
constexpr float QSCALE = 0.17677669529663687f * 1.4426950408889634f;

DEVI void fma8(float (&a)[8], uint4 v, float h) {
  a[0] = fmaf(bf_lo(v.x), h, a[0]); a[1] = fmaf(bf_hi(v.x), h, a[1]); a[2] = fmaf(bf_lo(v.y), h, a[2]); a[3] = fmaf(bf_hi(v.y), h, a[3]);
  a[4] = fmaf(bf_lo(v.z), h, a[4]); a[5] = fmaf(bf_hi(v.z), h, a[5]); a[6] = fmaf(bf_lo(v.w), h, a[6]); a[7] = fmaf(bf_hi(v.w), h, a[7]);
}
DEVI void gemv8(float (&a)[8], uint32_t wa, uint32_t ha, uint32_t hs) {
  #pragma unroll
  for (int n = 0; n < 8; n += 2) {
    uint4 v0 = lds128(wa + n * 512), v1 = lds128(wa + n * 512 + 512);
    float h0 = lds32f(ha), h1 = lds32f(ha + hs);
    ha += 2 * hs;
    fma8(a, v0, h0); fma8(a, v1, h1);
  }
}
DEVI uint4 ldsv128(uint32_t a) { uint4 v; asm volatile("ld.volatile.shared.v4.u32 {%0,%1,%2,%3}, [%4];" : "=r"(v.x), "=r"(v.y), "=r"(v.z), "=r"(v.w) : "r"(a) : "memory"); return v; }
DEVI float ldsv32f(uint32_t a) { float v; asm volatile("ld.volatile.shared.f32 %0, [%1];" : "=f"(v) : "r"(a) : "memory"); return v; }
DEVI uint32_t clk() { uint32_t t; asm volatile("mov.u32 %0, %%clock;" : "=r"(t)); return t; }
DEVI int fresh_tid() { int t; asm volatile("mov.u32 %0, %%tid.x;" : "=r"(t)); return t & 127; }
DEVI float fold8(const float (&a)[8]) {
  const int lane = threadIdx.x & 31;
  const bool u = lane & 16, v = lane & 8, x = lane & 4;
  float b0 = (u ? a[4] : a[0]) + __shfl_xor_sync(0xffffffffu, u ? a[0] : a[4], 16), b1 = (u ? a[5] : a[1]) + __shfl_xor_sync(0xffffffffu, u ? a[1] : a[5], 16);
  float b2 = (u ? a[6] : a[2]) + __shfl_xor_sync(0xffffffffu, u ? a[2] : a[6], 16), b3 = (u ? a[7] : a[3]) + __shfl_xor_sync(0xffffffffu, u ? a[3] : a[7], 16);
  float c0 = (v ? b2 : b0) + __shfl_xor_sync(0xffffffffu, v ? b0 : b2, 8), c1 = (v ? b3 : b1) + __shfl_xor_sync(0xffffffffu, v ? b1 : b3, 8);
  return (x ? c1 : c0) + __shfl_xor_sync(0xffffffffu, x ? c0 : c1, 4);
}
DEVI float swiglu(float g, float u) { g = bf_round(g); return bf_round(bf_round(__fdividef(g, 1.f + __expf(-g))) * bf_round(u)); }

DEVI void qk_issue(float (&s)[32], uint32_t qd, uint32_t kd) {
  wgmma_ss_n64<0>(s, mkd<HI64>(qd), mkd<HI64>(kd), 0);
  wgmma_ss_n64<0>(s, mkd<HI64>(qd + 2), mkd<HI64>(kd + 2), 1);
}
DEVI void pv_issue(float (&o)[20], const uint32_t (&p)[16], uint32_t vd, bool accum) {
  #pragma unroll
  for (int ks = 0; ks < 4; ks++)
    wgmma_rs_n40<1>(o, p[ks * 4], p[ks * 4 + 1], p[ks * 4 + 2], p[ks * 4 + 3], mkd<HI64>(vd + VOFF(ks * 64)), ks ? 1 : accum);
}
template<int J0, int J1> DEVI void exp_pack(const float (&s)[32], uint32_t (&p)[16]) {
  #pragma unroll
  for (int j = J0; j < J1; j++) p[j] = pack_bf16(ex2f(s[2 * j]), ex2f(s[2 * j + 1]));
}
DEVI bool attn_finish(const float (&o)[20], uint32_t st, uint32_t bar) {
  const float lo = 5.421010862427522e-20f, hi = 1.8446744073709552e19f;
  bool ok = o[16] >= lo && o[16] <= hi && o[18] >= lo && o[18] <= hi;
  if (!__all_sync(0xffffffffu, ok)) return false;
  float i0 = __fdividef(1.f, o[16]), i1 = __fdividef(1.f, o[18]);
  int lane = threadIdx.x & 31, row = ((threadIdx.x >> 5) & 3) * 16 + (lane & 15);
  #pragma unroll
  for (int h = 0; h < 2; h++) {
    int c = 2 * h + (lane >> 4);
    stsm_x4(st + row * 64 + ((c ^ ((row >> 1) & 3)) << 4),
      pack_bf16(o[8 * h] * i0, o[8 * h + 1] * i0), pack_bf16(o[8 * h + 2] * i1, o[8 * h + 3] * i1),
      pack_bf16(o[8 * h + 4] * i0, o[8 * h + 5] * i0), pack_bf16(o[8 * h + 6] * i1, o[8 * h + 7] * i1));
  }
  warp_signal(bar);
  return true;
}
DEVI void attn_exact(uint32_t st, uint32_t kv, int t, bool hasprev, uint32_t bar) {
  const int lane = threadIdx.x & 31;
  #pragma unroll 1
  for (int row = ((threadIdx.x >> 5) & 3) * 16, n = 0; n < 16; n++, row++) {
    const int k1 = 256 + t * 64 + row;
    float m = -INFINITY, l = 0.f, o = 0.f;
    #pragma unroll 1
    for (int k0 = hasprev ? k1 - 255 : 256; k0 <= k1; k0 += 32) {
      const int k = min(k0 + lane, k1), r = k & 63;
      float sc = 0.f;
      #pragma unroll 1
      for (int c = 0; c < 16; c++) {
        uint32_t a = lds32(st + row * 64 + ((c * 4) ^ ((row & 6) << 3))), b = lds32(kv + (k >> 6) * 8192 + r * 64 + ((c * 4) ^ ((r & 6) << 3)));
        sc = fmaf(bf_lo(a), bf_lo(b), fmaf(bf_hi(a), bf_hi(b), sc));
      }
      float mn = fmaxf(m, sc);
      #pragma unroll 1
      for (int x = 16; x; x >>= 1) mn = fmaxf(mn, __shfl_xor_sync(0xffffffffu, mn, x));
      const float al = ex2f(m - mn), pr = ex2f(sc - mn);
      m = mn; l *= al; o *= al;
      #pragma unroll 1
      for (int q = k0; q <= min(k0 + 31, k1); q++) {
        const float z = __shfl_sync(0xffffffffu, pr, q - k0);
        uint32_t b = lds32(kv + (q >> 6) * 8192 + 4096 + (q & 63) * 64 + (((lane >> 1) * 4) ^ ((q & 6) << 3)));
        l += z; o = fmaf(z, (lane & 1) ? bf_hi(b) : bf_lo(b), o);
      }
    }
    __syncwarp();
    sts16(st + row * 64 + ((lane * 2) ^ ((row & 6) << 3)), pack_bf16(__fdividef(o, l), 0.f));
  }
  warp_signal(bar);
}

DEVI void merge_tri(float (&s)[32], const float (&sx)[32], int tdiag) {
  #pragma unroll
  for (int e = 0; e < 32; e++) { int c = 8 * (e >> 2) + (e & 1) - 8 * ((e >> 1) & 1); s[e] = (c > tdiag) ? s[e] : sx[e]; }
}
DEVI void split_tri(uint32_t (&p)[16], uint32_t (&px)[16], const uint32_t (&msk)[9]) {
  #pragma unroll
  for (int e = 0; e < 16; e++) { const uint32_t m = msk[(e >> 1) - (e & 1) + 1]; px[e] = p[e] & ~m; p[e] &= m; }
}

template<int J0> DEVI void qkv_store(const float (&aX)[96], const float (&aY)[96], const float2 (&pr)[4], uint32_t csa, uint32_t dX, uint32_t dY, uint32_t x0) {
  #pragma unroll
  for (int hh = 0; hh < 2; hh++) {
    constexpr int dummy = 0; (void)dummy;
    const int j = J0 + 2 * hh;
    float2 ca = lds64f(csa + j * 32), cb = lds64f(csa + j * 32 + 32);
    uint32_t off = x0 ^ (hh << 5);
    #define EL(a, e, P, C) fmaf(a[4 * j + (e)], pr[P].x, pr[P].y * (C))
    stsm_x4(dX + off, pack_bf16(EL(aX, 0, 0, ca.x), EL(aX, 1, 0, ca.y)), pack_bf16(EL(aX, 2, 1, ca.x), EL(aX, 3, 1, ca.y)),
                      pack_bf16(EL(aX, 4, 0, cb.x), EL(aX, 5, 0, cb.y)), pack_bf16(EL(aX, 6, 1, cb.x), EL(aX, 7, 1, cb.y)));
    stsm_x4(dY + off, pack_bf16(EL(aY, 0, 2, ca.x), EL(aY, 1, 2, ca.y)), pack_bf16(EL(aY, 2, 3, ca.x), EL(aY, 3, 3, ca.y)),
                      pack_bf16(EL(aY, 4, 2, cb.x), EL(aY, 5, 2, cb.y)), pack_bf16(EL(aY, 6, 3, cb.x), EL(aY, 7, 3, cb.y)));
    #undef EL
  }
}

template<bool FIRST> DEVI void qkv_block(float (&aX)[96], float (&aY)[96], uint32_t sb16, int s, int tX, int tY) {
  uint32_t a16 = sb16 + (qa_off(s) >> 4), b16 = (sb16 + (qb_off(s) >> 4)) | ((8192u >> 4) << 16);
  uint32_t ax = (a16 + tX * 512) | 0x10000u, ay = (a16 + tY * 512) | 0x10000u;
  wg_fence();
  #pragma unroll
  for (int ks = 0; ks < 4; ks++) {
    wgmma_ss_n192<1>(aX, mkd<HI128>(ax + ks * 2), mkd<HI128>(b16 + ks * 128), !(FIRST && ks == 0));
    wgmma_ss_n192<1>(aY, mkd<HI128>(ay + ks * 2), mkd<HI128>(b16 + ks * 128), !(FIRST && ks == 0));
  }
  wg_commit();
}
template<bool FIRST> DEVI void wo_block(float (&acc)[64], uint32_t sb16, int s, int wg) {
  uint32_t a16 = (sb16 + (w_off(s) >> 4) + wg * 256) | 0x10000u, b16 = (sb16 + (w_off(s) >> 4) + 1024) | ((8192u >> 4) << 16);
  wg_fence();
  #pragma unroll
  for (int ks = 0; ks < 4; ks++)
    wgmma_ss_n128<1>(acc, mkd<HI64>(a16 + (ks >> 1) * 512 + (ks & 1) * 2), mkd<HI128>(b16 + ks * 128), !(FIRST && ks == 0));
  wg_commit();
}
DEVI void consumer(const Params& P, uint32_t sb, int wg) {
  const int tid = threadIdx.x & 127, lane = tid & 31, w = tid >> 5;
  const int bi = BID >> 4, rh = blockIdx.x & 1, bc = (BID & 15) >> 1;
  const int tX = 3 - wg, tY = wg;
  const uint32_t sb16 = (sb & 0x3FFFFu) >> 4;
  uint32_t phq = 0;
  #pragma unroll 1
  for (int L = 0; L < 2; L++) {
    {
      float aX[96], aY[96];
      int s = 1, ps = 0;
      if (L) mbar_wait(BAR(B_XRDY + wg * 2 + 1), 0);
      PROFW(threadIdx.x == 0 && L, 46);
      mbar_wait(BAR(B_FULLQ), phq & 1);
      phq ^= 1u;
      PROFW(threadIdx.x == 0, L * 8 + 1);
      qkv_block<true>(aX, aY, sb16, 0, tX, tY);
      #pragma unroll 1
      for (int n = 1; n < 16; n++) {
        mbar_wait(BAR(B_FULLQ + s), (phq >> s) & 1);
        phq ^= 1u << s;
        PROFD(threadIdx.x == 0 && L && (n == 2 || n == 3 || n == 7 || n == 11 || n == 15), n == 2 ? 48 : 49 + (n >> 2));
        qkv_block<false>(aX, aY, sb16, s, tX, tY);
        wg_wait<1>(); if (tid == 0) mbar_arrive(BAR(B_EMPTYQ + ps));
        ps = s; s = (s == 2) ? 0 : s + 1;
      }
      mbar_wait(BAR(B_PAR), L);
      float2 pr[4];
      { uint32_t pa = sb + PAR + (w * 16 + (lane >> 2)) * 8;
        pr[0] = lds64f(pa + tX * 512); pr[1] = lds64f(pa + tX * 512 + 64); pr[2] = lds64f(pa + tY * 512); pr[3] = lds64f(pa + tY * 512 + 64); }
      int prow = (int)lds32(sb + INFO) - bi * 256;
      wg_wait<0>();
      keep(aX); keep(aY);
      if (tid == 0) mbar_arrive(BAR(B_EMPTYQ + ps));
      PROFW(threadIdx.x == 0, L * 8 + 2);
      mbar_wait(BAR(B_EMPTYQ + 1), ((phq >> 1) & 1) ^ 1); mbar_wait(BAR(B_EMPTYQ + 2), ((phq >> 2) & 1) ^ 1);
      const int srow = w * 16 + (lane & 15);
      const uint32_t x0 = srow * 64 + (((lane >> 4) ^ ((srow >> 1) & 3)) << 4);
      const uint32_t csa = sb + CS + (lane & 3) * 8;
      const bool pmine = (prow >> 4) == tX * 4 + w || (prow >> 4) == tY * 4 + w;
      const uint32_t poff = (prow & 63) * 64 + (((lane & 3) ^ ((prow >> 1) & 3)) << 4);
      qkv_store<8>(aX, aY, pr, csa, sb + KVA + (4 + tX) * 8192, sb + KVA + (4 + tY) * 8192, x0);
      qkv_store<16>(aX, aY, pr, csa, sb + KVA + (4 + tX) * 8192 + 4096, sb + KVA + (4 + tY) * 8192 + 4096, x0);
      if (pmine) { __syncwarp(); if (lane < 8) sts128(sb + KVA + (4 + (prow >> 6)) * 8192 + (lane >> 2) * 4096 + poff, lds128(sb + PATCH + 128 + (lane >> 2) * 128 + (lane & 3) * 16)); }
      warp_signal(BAR(B_KVRDY + wg * 2));
      qkv_store<12>(aX, aY, pr, csa, sb + KVB + (4 + tX) * 8192, sb + KVB + (4 + tY) * 8192, x0);
      qkv_store<20>(aX, aY, pr, csa, sb + KVB + (4 + tX) * 8192 + 4096, sb + KVB + (4 + tY) * 8192 + 4096, x0);
      if (pmine) { __syncwarp(); if (lane < 8) sts128(sb + KVB + (4 + (prow >> 6)) * 8192 + (lane >> 2) * 4096 + poff, lds128(sb + PATCH + 192 + (lane >> 2) * 128 + (lane & 3) * 16)); }
      warp_signal(BAR(B_KVRDY + wg * 2 + 1));
      #pragma unroll
      for (int e = 0; e < 4; e++) { pr[e].x *= QSCALE; pr[e].y *= QSCALE; }
      mbar_wait(BAR(B_EMPTYQ), (phq & 1) ^ 1);
      qkv_store<0>(aX, aY, pr, csa, sb + QO + tX * 4096, sb + QO + tY * 4096, x0);
      qkv_store<4>(aX, aY, pr, csa, sb + QO + 16384 + tX * 4096, sb + QO + 16384 + tY * 4096, x0);
      if (pmine) { __syncwarp(); if (lane < 8) sts128(sb + QO + (lane >> 2) * 16384 + (prow >> 6) * 4096 + poff, lds128(sb + PATCH + lane * 16)); }
      fence_async_smem();
      bar_sync(1, 256);
    }
    PROFW(threadIdx.x == 0, L * 8 + 3);
    {
      float s0[32], s1[32], sx[32], o[20], op[20];
      uint32_t p0[16], p1[16], px[16], msk[9];
      const int tdiag = w * 16 + (lane >> 2) - 2 * (lane & 3);
      #pragma unroll
      for (int e = 0; e < 9; e++) msk[e] = ((8 * e - 8 > tdiag) ? 0xFFFFu : 0u) | ((8 * e - 7 > tdiag) ? 0xFFFF0000u : 0u);
      keep(msk);
      const uint32_t ones = (sb16 + (ONES >> 4)) << 16;
      const uint32_t qX = (sb16 + (QO >> 4) + tX * 256) | 0x10000u, qY = (sb16 + (QO >> 4) + tY * 256) | 0x10000u;
      const uint32_t kXB = (sb16 + (KVB >> 4) + tX * 512) | 0x10000u;
      uint32_t redo = 0;
      #define QK(s, q, k) do { wg_fence(); qk_issue(s, q, k); wg_commit(); } while (0)
      #define QK2(q, k) do { wg_fence(); qk_issue(s1, q, k); qk_issue(sx, q, (k) + 2048); wg_commit(); } while (0)
      #define PV(o, p, v, b, acc) do { wg_fence(); pv_issue(o, p, (v) + VOFF((b) * 512), acc); wg_commit(); } while (0)
      #define PV2(v0, v4) do { wg_fence(); pv_issue(o, p1, v0, true); pv_issue(o, px, (v4) + VOFF(2048), true); wg_commit(); } while (0)
      {
        const uint32_t kXA = kXB + ((KVA - KVB) >> 4), vB = VOFF((kXB & 0xffffu) + 256) + ones, vA = vB + VOFF((KVA - KVB) >> 4);
        QK(s0, qX, kXA + 1536);
        wg_wait<0>(); keep(s0);
        QK(s1, qX, kXA + 1024);
        exp_pack<0, 16>(s0, p0);
        PV(o, p0, vA, 3, false);
        wg_wait<1>(); keep(s1);
        QK(s0, qX + 1024, kXB + 1536);
        exp_pack<0, 16>(s1, p1);
        PV(o, p1, vA, 2, true);
        wg_wait<1>(); keep(s0); keep(p0);
        QK(s1, qX + 1024, kXB + 1024);
        exp_pack<0, 16>(s0, p0);
        PV(op, p0, vB, 3, false);
        wg_wait<1>(); keep(s1); keep(p1); keep(o);
        exp_pack<0, 8>(s1, p1);
        mbar_wait(BAR(B_KVFULL), L);
        QK(s0, qX, kXA + 512);
        exp_pack<8, 16>(s1, p1);
        PV(op, p1, vB, 2, true);
        wg_wait<0>(); keep(s0); keep(p0); keep(p1); keep(op);
      }
      #pragma unroll 1
      for (int h = 0; h < 2; h++) {
        const uint32_t kb16 = sb16 + ((h ? KVB : KVA) >> 4), kX = (kb16 + tX * 512) | 0x10000u, kY = (kb16 + tY * 512) | 0x10000u;
        const uint32_t qx = qX + h * 1024, qy = qY + h * 1024;
        const uint32_t onesP = bi ? ones : (kb16 + 1984) << 16;
        const uint32_t vX = VOFF(kb16 + tX * 512 + 256), vY = VOFF(kb16 + tY * 512 + 256);
        QK2(qx, kX);
        exp_pack<0, 16>(s0, p0);
        PV(o, p0, vX + (wg ? onesP : ones), 1, true);
        wg_wait<1>(); keep(s1); keep(sx);
        merge_tri(s1, sx, tdiag);
        QK(s0, qy, kY + 1536);
        exp_pack<0, 16>(s1, p1); split_tri(p1, px, msk);
        PV2(vX + onesP, vX + ones);
        wg_wait<1>(); keep(s0); keep(p0);
        QK(s1, qy, kY + 1024);
        exp_pack<0, 10>(s0, p0);
        wg_wait<1>(); keep(o); keep(p1); keep(px);
        if (!attn_finish(o, sb + QO + (h * 4 + tX) * 4096, BAR(B_ORDY + wg * 4 + h * 2))) redo |= 1u << (h * 2);
        exp_pack<10, 16>(s0, p0);
        PV(o, p0, vY + (wg ? ones : onesP), 3, false);
        wg_wait<1>(); keep(s1);
        exp_pack<0, 8>(s1, p1);
        mbar_wait(BAR(B_KVFULL + h * 2 + 1), L);
        QK(s0, qy, kY + 512);
        exp_pack<8, 16>(s1, p1);
        PV(o, p1, vY + onesP, 2, true);
        wg_wait<1>(); keep(s0); keep(p0);
        QK2(qy, kY);
        exp_pack<0, 16>(s0, p0);
        PV(o, p0, vY + onesP, 1, true);
        wg_wait<1>(); keep(s1); keep(sx); keep(p1);
        merge_tri(s1, sx, tdiag);
        exp_pack<0, 8>(s1, p1);
        mbar_wait(BAR(B_KVFULL + 2), L);
        QK(s0, h ? qy : qX + 1024, kXB + 512);
        exp_pack<8, 16>(s1, p1); split_tri(p1, px, msk);
        PV2(vY + onesP, vY + ones);
        wg_wait<0>(); keep(o); keep(s0); keep(p0); keep(p1); keep(px);
        if (!attn_finish(o, sb + QO + (h * 4 + tY) * 4096, BAR(B_ORDY + wg * 4 + h * 2 + 1))) redo |= 2u << (h * 2);
        #pragma unroll
        for (int e = 0; e < 20; e++) o[e] = op[e];
      }
      #undef QK
      #undef QK2
      #undef PV
      #undef PV2
      if (redo) {
        #pragma unroll 1
        for (int u = 0; u < 4; u++) if ((redo >> u) & 1) {
          const int h = u >> 1, t = (u & 1) ? tY : tX;
          attn_exact(sb + QO + (h * 4 + t) * 4096, sb + (h ? KVB : KVA), t, bi > 0, BAR(B_ORDY + wg * 4 + u));
        }
      }
    }
    PROFW(threadIdx.x == 0, L * 8 + 4);
    {
      float acc[64];
      const int tt = wg ^ rh;
      const int grow = bi * 256 + rh * 128 + tt * 64 + w * 16 + (lane >> 2);
      float al0 = 1.f, be0 = 0.f, al1 = 1.f, be1 = 0.f;
      const int idx0 = (int)lds32(sb + INFO);
      const uint32_t tag = lds32(sb + INFO + 8) + L;
      uint4* const sp = &P.g->statP[bc][grow + (lane & 1) * 8];
      uint4* const yp = &P.g->yP[threadIdx.x >> 1][min(FID, 111)][threadIdx.x & 1];
      mbar_wait(BAR(B_FULLW), L);
      PROFW(threadIdx.x == 0, L * 8 + 5);
      wo_block<true>(acc, sb16, 0, tt);
      if (!(lane & 2)) st_ll(sp, 0u, 0u, 0u, 0u);
      uint4 fa = make_uint4(0u, 0u, 0u, 0u), fb = fa;
      uint2 wd[32];
      if (L) {
        if (FID < 112) st_ll(yp, 0u, 0u, 0u, 0u);
        fa = ld_ll(&P.g->statF[grow]); fb = ld_ll(&P.g->statF[grow + 8]);
      }
      #pragma unroll
      for (int n = 0; n < 32; n++) wd[n] = make_uint2(0u, 0u);
      #pragma unroll 1
      for (int n = 1, q = 1, pq = 0; n < 16; n++) {
        mbar_wait(BAR(B_FULLW + q), w_par(n, q, L));
        PROFD(threadIdx.x == 0 && !L && (n == 4 || n == 7 || n == 8 || n == 12), (n == 7 ? 63 : 41 + (n >> 2)));
        wo_block<false>(acc, sb16, q, tt);
        if (L && n == WD_N) {
          const uint2* src = (const uint2*)(WDSRC) + threadIdx.x;
          #pragma unroll
          for (int e = 0; e < 32; e++) wd[e] = ldg_stream(src + e * 256);
        }
        wg_wait<1>(); if (tid == 0) mbar_arrive(BAR(B_EMPTYW + pq));
        pq = q; q = q == 5 ? 0 : q + 1;
      }
      if (L) {
        float r0 = rsqrtf(__uint_as_float(fa.y) + LN_EPS), r1 = rsqrtf(__uint_as_float(fb.y) + LN_EPS);
        if (grow != idx0) { al0 = 1.f + r0; be0 = -__uint_as_float(fa.x) * r0; }
        if (grow + 8 != idx0) { al1 = 1.f + r1; be1 = -__uint_as_float(fb.x) * r1; }
      }
      mbar_wait(BAR(B_RES), L);
      const int srow = tt * 64 + w * 16 + (lane & 15);
      const uint32_t ra = sb + rh * 16384 + srow * 128, sw = ((lane >> 4) ^ (srow & 7)) << 4;
      if ((idx0 >> 4) == (grow >> 4)) {
        int r = idx0 & 127;
        if (lane < 16) sts128(sb + (lane >> 3) * 32768 + rh * 16384 + r * 128 + (((lane & 7) ^ (r & 7)) << 4), lds128(sb + X2SEG + lane * 16));
        __syncwarp();
      }
      uint32_t rs[32];
      #pragma unroll
      for (int jj = 0; jj < 8; jj++) ldsm_x4((ra + (jj >> 2) * 32768) + (sw ^ ((jj & 3) << 5)), rs[4 * jj], rs[4 * jj + 1], rs[4 * jj + 2], rs[4 * jj + 3]);
      float rf[64];
      #pragma unroll
      for (int e = 0; e < 32; e++) { rf[2 * e] = fmaf(bf_lo(rs[e]), (e & 1) ? al1 : al0, (e & 1) ? be1 : be0); rf[2 * e + 1] = fmaf(bf_hi(rs[e]), (e & 1) ? al1 : al0, (e & 1) ? be1 : be0); }
      keep(rf);
      wg_wait<0>(); keep(acc);
      if (tid == 0) mbar_arrive(BAR(B_EMPTYW + 3));
      PROFW(threadIdx.x == 0, L * 8 + 6);
      #pragma unroll
      for (int jj = 0; jj < 8; jj++) {
        float* a = acc + 8 * jj;
        #pragma unroll
        for (int e = 0; e < 8; e++) a[e] += rf[8 * jj + e];
        stsm_x4((ra + (jj >> 2) * 32768) + (sw ^ ((jj & 3) << 5)), pack_bf16(a[0], a[1]), pack_bf16(a[2], a[3]), pack_bf16(a[4], a[5]), pack_bf16(a[6], a[7]));
        if ((jj & 3) == 3) warp_signal(BAR(B_XRDY + wg * 2 + (jj >> 2)));
      }
      {
        float s1a = 0.f, s2a = 0.f, da = 0.f, s1b = 0.f, s2b = 0.f, db = 0.f;
        #pragma unroll
        for (int j = 0; j < 16; j++) {
          const float* a = acc + 4 * j; float2 wv = lds64f(sb + WR + j * 32 + (lane & 3) * 8);
          s1a += a[0] + a[1]; s1b += a[2] + a[3];
          s2a = fmaf(a[0], a[0], s2a); s2b = fmaf(a[2], a[2], s2b); s2a = fmaf(a[1], a[1], s2a); s2b = fmaf(a[3], a[3], s2b);
          da = fmaf(a[0], wv.x, da); db = fmaf(a[2], wv.x, db); da = fmaf(a[1], wv.y, da); db = fmaf(a[3], wv.y, db);
        }
        bool odd = lane & 1;
        float u1 = (odd ? s1b : s1a) + __shfl_xor_sync(0xffffffffu, odd ? s1a : s1b, 1);
        float u2 = (odd ? s2b : s2a) + __shfl_xor_sync(0xffffffffu, odd ? s2a : s2b, 1);
        float u3 = (odd ? db : da) + __shfl_xor_sync(0xffffffffu, odd ? da : db, 1);
        u1 += __shfl_xor_sync(0xffffffffu, u1, 2); u2 += __shfl_xor_sync(0xffffffffu, u2, 2); u3 += __shfl_xor_sync(0xffffffffu, u3, 2);
        if (!(lane & 2)) st_ll(sp, __float_as_uint(u1), __float_as_uint(u2), __float_as_uint(u3), tag);
      }
      PROFW(threadIdx.x == 0, L * 8 + 7);
      if (L) {
        mbar_wait(BAR(B_PAR), 0);
        { float2 pa = lds64f(sb + PAR + (grow & 127) * 8), pb = lds64f(sb + PAR + (grow & 127) * 8 + 64); al0 = pa.x; be0 = pa.y; al1 = pb.x; be1 = pb.y; }
        #pragma unroll
        for (int j = 0; j < 16; j++) {
          rs[2 * j] = pack_bf16(fmaf(acc[4 * j], al0, be0), fmaf(acc[4 * j + 1], al0, be0));
          rs[2 * j + 1] = pack_bf16(fmaf(acc[4 * j + 2], al1, be1), fmaf(acc[4 * j + 3], al1, be1));
        }
        const int idx1 = (int)lds32(sb + INFO + 4);
        #pragma unroll
        for (int jj = 0; jj < 8; jj++) stsm_x4((ra + (jj >> 2) * 32768) + (sw ^ ((jj & 3) << 5)), rs[4 * jj], rs[4 * jj + 1], rs[4 * jj + 2], rs[4 * jj + 3]);
        __syncwarp();
        {
          const int r0 = (grow & ~15) + (lane >> 4), skip = idx1 - r0;
          const uint32_t a0 = sb + ((lane >> 3) & 1) * 32768 + (r0 & 255) * 128 + (((lane & 7) ^ (lane >> 4)) << 4);
          uint4* dst = (uint4*)(P.out + (size_t)r0 * 1024 + bc * 128) + (lane & 15);
          #pragma unroll
          for (int it = 0; it < 8; it++) { uint4 v = lds128((a0 + it * 256) ^ ((it & 3) << 5)); if (skip != 2 * it) dst[it * 256] = v; }
        }
        PROFW(threadIdx.x == 0, 16);
        if (FID < 112) {
          const int q = wg * 2 + (w >> 1);
          float g[8] = {0.f, 0.f, 0.f, 0.f, 0.f, 0.f, 0.f, 0.f};
          mbar_wait(BAR(B_FULLW + q), 0);
          bar_sync(3, 384);
          PROFW(threadIdx.x == 0, 29);
          #pragma unroll 1
          for (int n = 0; n < 4; n++) gemv8(g, sb + w_off(q) + (w & 1) * 16384 + n * 4096 + lane * 16, sb + HV + (q * 256 + n * 64 + (lane >> 2)) * 4, 32);
          sts32f(sb + PAR + 1024 + (q * 2 + (w & 1)) * 128 + ((lane & 3) * 8 + (lane >> 2)) * 4, fold8(g));
          bar_sync(1, 256);
          const uint32_t d = sb + PAR + 1024 + lane * 4;
          const float act = swiglu((lds32f(d) + lds32f(d + 256)) + (lds32f(d + 512) + lds32f(d + 768)),
                                   (lds32f(d + 128) + lds32f(d + 384)) + (lds32f(d + 640) + lds32f(d + 896)));
          PROFW(threadIdx.x == 0, 26);
          float y0 = 0.f, y1 = 0.f, y2 = 0.f, y3 = 0.f;
          #pragma unroll
          for (int n = 0; n < 32; n++) {
            float av = __shfl_sync(0xffffffffu, act, n);
            y0 = fmaf(bf_lo(wd[n].x), av, y0); y1 = fmaf(bf_hi(wd[n].x), av, y1); y2 = fmaf(bf_lo(wd[n].y), av, y2); y3 = fmaf(bf_hi(wd[n].y), av, y3);
          }
          st_ll(yp, __float_as_uint(y0), __float_as_uint(y1), __float_as_uint(y2), (__float_as_uint(y3) & ~255u) | (lds32(sb + INFO + 12) + 1));
          PROFW(threadIdx.x == 0, 27);
        }
      }
    }
  }
}

DEVI void loader(const Params& P, uint32_t sb) {
  const int lane = threadIdx.x & 31;
  const int bid = BID, bi = bid >> 4, bp = bid & 15, rh = bp & 1, bc = bp >> 1;
  uint32_t phq = 0, tag = 0;
  #pragma unroll 1
  for (int L = 0; L < 2; L++) {
    int s = 0;
    uint32_t rdy = 0;
    #pragma unroll 1
    for (int n = L ? 0 : 3; n < 16; n++) {
      int kb = L ? kb_order(bc, n) : n;
      mbar_wait(BAR(B_EMPTYQ + s), (phq >> s) & 1);
      phq ^= 1u << s;
      if (L) {
        if (n == 1) { mbar_wait(BAR(B_XRDY + 1), 0); mbar_wait(BAR(B_XRDY + 3), 0); }
        if (n >= 2) {
          if (((rdy >> (2 * kb)) & 3) != 3) {
            do { rdy = __ballot_sync(0xffffffffu, ld_rlx(&P.g->flagX[bi][lane]) == tag); } while (((rdy >> (2 * kb)) & 3) != 3);
            fence_async_glob();
          }
          if (n == 3 || n == 4) mbar_wait(BAR(B_XFREE + n - 3), 0);
        }
      }
      if (lane == 0) {
        mbar_expect_tx(BAR(B_FULLQ + s), L && n < 2 ? 40960 : 57344);
        if (L && n >= 2) bulk_g2s_h(sb + qa_off(s), P.g->x[bi][kb], 32768, BAR(B_FULLQ + s), POL_X);
        if (!L) tma_2d(sb + qa_off(s), &P.mX, kb * 64, bi * 256, BAR(B_FULLQ + s));
        tma_3d_h(sb + qb_off(s), &P.mWq, bp * 64, kb * 64, 0, BAR(B_FULLQ + s), L ? POL_Q1 : POL_Q0);
      }
      PROFY(L && lane == 0 && (n == 2 || n == 3 || n == 9), n == 9 ? 60 : 56 + n);
      if (L && n == 2) { mbar_wait(BAR(B_FULLQ), 0); mbar_wait(BAR(B_FULLQ + 1), 1); if (lane < 2) mbar_arrive_peer(BAR(B_XFREE + lane)); }
      s = (s == 2) ? 0 : s + 1;
    }
    for (int q = 0; q < 3; q++) mbar_wait(BAR(B_EMPTYQ + q), (phq >> q) & 1);
    mbar_wait(BAR(B_PAR), L);
    tag = lds32(sb + INFO + 8) + L;
    rdy = bi ? 0u : 0xffu;
    {
      const uint4* src = bi ? P.g->kv[bid - 16][0] : P.g->zero;
      const unsigned* fl = &P.g->flagKV[bid - 16][lane & 7];
      #pragma unroll 1
      for (int q = 0; q < 4; q++) {
        const int ch = (2 * q) ^ 2;
        if (lane == 0) mbar_expect_tx(BAR(B_KVFULL + q), 16384);
        if (((rdy >> ch) & 3) != 3) {
          do { rdy = __ballot_sync(0xffffffffu, ld_rlx(fl) == tag); } while (((rdy >> ch) & 3) != 3);
          fence_async_glob();
        }
        if (lane == 0) bulk_g2s_h(sb + ((ch >> 2) ? KVB : KVA) + (ch & 3) * 8192, src + (bi ? ch * 512 : 0), 16384, BAR(B_KVFULL + q));
        PROFY(!L && lane == 0 && bi && q != 2, 34 + (q + 1) / 2);
      }
    }
    mbar_wait(BAR(B_ORDY), L); mbar_wait(BAR(B_ORDY + 4), L);
    {
      const uint4* src = P.g->o[bi][0][0][rh];
      const unsigned* fl = &P.g->flagO[bi][0][rh][lane];
      rdy = 0;
      #pragma unroll 1
      for (int n = 0, q = 0; n < 16; n++, q = q == 5 ? 0 : q + 1) {
        const int j = n & 7;
        if (n == 8) { rdy = 0; src += 16384; fl += 64; }
        if (((rdy >> (4 * j)) & 15) != 15) {
          do { rdy = __ballot_sync(0xffffffffu, ld_rlx(fl) == tag); } while (((rdy >> (4 * j)) & 15) != 15);
          fence_async_glob();
        }
        if (n >= 2) mbar_wait(n < 6 ? BAR(B_HAFREE + (n >> 2)) : BAR(B_EMPTYW + q), n < 6 ? L : w_par(n - 6, q, L));
        if (n == THR_N) mbar_wait(BAR(B_OFREE), L);
        if (lane == 0) { mbar_expect_tx(BAR(B_FULLW + q), 16384); bulk_g2s_h(sb + w_off(q), src + j * 2048, 16384, BAR(B_FULLW + q)); }
      }
    }
    mbar_wait(BAR(B_OFREE), L);
  }
}

DEVI void ffn_prefetch(const Params& P, int q) {
  bulk_prefetch(q < 16 ? ((q & 1) ? P.wu : P.wg) + ((q >> 1) * 128 + blockIdx.x) * 3584 : P.wd + (blockIdx.x * 8 + q - 16) * 3584, 7168);
}
DEVI void storer(const Params& P, uint32_t sb, int wg) {
  const int bid = uni(BID), bi = bid >> 4, rh = bid & 1, bc = (bid & 15) >> 1;
  const bool one = (threadIdx.x & 31) == 0;
  char* const g = (char*)P.g;
  #pragma unroll 1
  for (int L = 0; L < 2; L++) {
    mbar_wait(BAR(B_KVRDY + wg * 2), L);
    const uint32_t tag = lds32(sb + INFO + 8) + L;
    #pragma unroll 1
    for (int u = bi < 7 ? 0 : 4; u < 8; u++) {
      const int h = (u >> 1) & 1, t = (u & 1) ? wg : 3 - wg;
      uint32_t src, dst, fl;
      if (u < 4) {
        src = (h ? KVB : KVA) + (4 + t) * 8192; dst = offsetof(Scratch, kv) + (bid * 8 + h * 4 + t) * 8192; fl = offsetof(Scratch, flagKV) + (bid * 32 + h * 4 + t) * 4;
      } else {
        src = QO + (h * 4 + t) * 4096; dst = offsetof(Scratch, o) + ((((bi * 2 + h) * 8 + bc) * 2 + (t >> 1)) * 4 + rh * 2 + (t & 1)) * 4096;
        fl = offsetof(Scratch, flagO) + (((bi * 2 + h) * 2 + (t >> 1)) * 32 + (bid & 15) * 2 + (t & 1)) * 4;
      }
      if (u >= 2) mbar_wait(u < 4 ? BAR(B_KVRDY + wg * 2 + 1) : BAR(B_ORDY + wg * 4 + u - 4), L);
      if (one) { bulk_s2g(g + dst, sb + src, u < 4 ? 8192 : 4096); if (u == 5 || u == 7) mbar_arrive(BAR(B_HAFREE + h)); }
      if (u == 4 || u == 6) continue;
      bulk_wait<0>(); fence_rel();
      if (one) { st_rlx((unsigned*)(g + fl), tag); if (u > 4) st_rlx((unsigned*)(g + (fl ^ 132u)), tag); }
      PROFY(one && !L && wg == 0 && (u == 0 || u == 3 || u == 5 || u == 7), u == 5 ? 38 : (u == 7 ? 54 : 32 + (u & 1)));
    }
    if (one) mbar_arrive(BAR(B_OFREE));
    if (L == 0) {
      char* dst = g + (offsetof(Scratch, x) + (bi * 16 + 2 * bc) * 32768 + rh * 16384);
      unsigned* f = (unsigned*)(g + (offsetof(Scratch, flagX) + (bi * 32 + bc * 4 + rh) * 4));
      if (wg == 0) {
        const uint32_t a = sb + rh * 16384;
        mbar_wait(BAR(B_PFREE), 0);
        mbar_wait(BAR(B_XRDY), 0); mbar_wait(BAR(B_XRDY + 2), 0);
        PROFY(one, 41);
        if (one) { bulk_s2peer(a, 16384, BAR(B_FULLQ)); bulk_s2g(dst, a, 16384); }
        mbar_wait(BAR(B_XRDY + 1), 0); mbar_wait(BAR(B_XRDY + 3), 0);
        bulk_wait<0>();
        PROFY(one, 45);
        if (one) { bulk_s2peer(a + 32768, 16384, BAR(B_FULLQ + 1)); mbar_arrive(BAR(B_XFREE)); }
        fence_rel();
        if (one) { st_rlx(f, tag); bulk_s2g(dst + 32768, a + 32768, 16384); }
        PROFY(one, 56);
        bulk_wait<0>();
        if (one) mbar_arrive(BAR(B_XFREE + 1));
        fence_rel();
        if (one) st_rlx(f + 2, tag);
        PROFY(one, 57);
      }
      if (wg == 0) {
        uint32_t t0 = clk() + PF1_D;
        #pragma unroll 1
        for (int q = PF1_S; q < PF1_E; q++) { while ((int)(clk() - t0) < 0) __nanosleep(50); if (one) ffn_prefetch(P, q); t0 += PF1_T; }
      }
    }
  }
}

DEVI void stg_issue(const Params& P, int c, uint32_t d, uint32_t du, uint32_t b) {
  mbar_expect_tx(b, 16384);
  if (c < 8) { tma_2d_h(d, &P.mWg, FID * 32, c * 128, b, POL_G); tma_2d_h(d + du, &P.mWu, FID * 32, c * 128, b, POL_U); }
  else if (c < 12) tma_3d_h(d, &P.mWd, 0, FID * 32 + (c - 8) * 8, 0, b, POL_D);
  else tma_2d_h(d, &P.mWp, FID * 32, (c - 12) * 256, b, POL_EF);
}
DEVI void stager(const Params& P, uint32_t sb) {
  {
    const int b = blockIdx.x;
    uint32_t t0 = clk();
    #pragma unroll 1
    for (int q = 0; q < PQ_N; q++) { bulk_prefetch(P.wqkv + (q * 128 + b) * 3072, 6144); while (clk() - t0 < PQ_T); t0 += PQ_T; }
    bulk_prefetch(P.wo + b * 8192, 16384);
    #pragma unroll 1
    for (int q = 0; q < PF0_N; q++) {
      while (clk() - t0 < PF0_T);
      t0 += PF0_T;
      ffn_prefetch(P, q);
    }
  }
  const int bid = BID, bi = bid >> 4, rh = bid & 1, bc = (bid & 15) >> 1;
  uint32_t phe = 7;
  #pragma unroll 1
  for (int L = 0; L < 2; L++) {
    const int nch = FID >= 112 ? 0 : (FID < 96 ? 16 : 12);
    mbar_wait(BAR(B_KVRDY), L); mbar_wait(BAR(B_KVRDY + 2), L);
    #pragma unroll 1
    for (int n = 0, q = 0; n < 16; n++, q = q == 5 ? 0 : q + 1) {
      if (n >= 2) mbar_wait(n < 6 ? BAR(B_HAFREE + (n >> 2)) : BAR(B_EMPTYW + q), n < 6 ? L : w_par(n - 6, q, L));
      if (n == THR_N) mbar_wait(BAR(B_OFREE), L);
      mbar_expect_tx(BAR(B_FULLW + q), 16384);
      tma_5d(sb + w_off(q) + 16384, &P.mWo, 0, 0, n >> 3, 2 * (n & 7), 2 * bc, BAR(B_FULLW + q), L ? POL_EF : POL_NORMAL);
    }
    mbar_expect_tx(BAR(B_RES), 32768);
    #pragma unroll 1
    for (int e = 0; e < 2; e++) {
      mbar_wait(BAR(B_EMPTYW + 4 + e), 1);
      if (L) bulk_g2s_h(sb + e * 32768 + rh * 16384, P.g->x[bi][2 * bc + e] + rh * 1024, 16384, BAR(B_RES));
      else tma_2d_h(sb + e * 32768 + rh * 16384, &P.mXh, bc * 128 + e * 64, bi * 256 + rh * 128, BAR(B_RES), POL_EF);
    }
    if (L == 0) {
      mbar_arrive_peer(BAR(B_PFREE));
      mbar_wait(BAR(B_XFREE), 0);
      int slot = 0;
      #pragma unroll 1
      for (int c = 0; c < nch; c++) {
        mbar_wait(BAR(B_STGE + slot), (phe >> slot) & 1); phe ^= 1u << slot;
        stg_issue(P, c, sb + STG + slot * 16384, 8192, BAR(B_STG + slot));
        slot = slot == 2 ? 0 : slot + 1;
      }
    } else if (nch) {
      #pragma unroll 1
      for (int c = 0; c < 8; c++) {
        mbar_wait(BAR(B_EMPTYW + (c >> 1)), 1);
        stg_issue(P, c, sb + w_off(c >> 1) + (c & 1) * 8192, 16384, BAR(B_FULLW + (c >> 1)));
      }
    }
  }
}
DEVI void sum8(uint4 v, float& s1, float& s2) {
  float e[8] = {bf_lo(v.x), bf_hi(v.x), bf_lo(v.y), bf_hi(v.y), bf_lo(v.z), bf_hi(v.z), bf_lo(v.w), bf_hi(v.w)};
  #pragma unroll
  for (int q = 0; q < 8; q++) { s1 += e[q]; s2 = fmaf(e[q], e[q], s2); }
}
DEVI uint4 norm8(uint4 x, float m, float rs, uint32_t d, uint32_t d2) {
  #define HN(v) pack_bf16((bf_lo(v) - m) * rs, (bf_hi(v) - m) * rs)
  uint4 b = make_uint4(HN(x.x), HN(x.y), HN(x.z), HN(x.w));
  #undef HN
  sts128(d, make_uint4(b.x << 16, b.x & 0xffff0000u, b.y << 16, b.y & 0xffff0000u));
  sts128(d + d2, make_uint4(b.z << 16, b.z & 0xffff0000u, b.w << 16, b.w & 0xffff0000u));
  return b;
}
DEVI uint4 best4(uint32_t p) {
  uint4 a = lds128(p), b = lds128(p + 16), c = lds128(p + 32), d = lds128(p + 48);
  if (b.x > a.x) a = b;
  if (d.x > c.x) c = d;
  return c.x > a.x ? c : a;
}
#define FL(x) __uint_as_float(x)
#define UI(x) __float_as_uint(x)
DEVI void qkv_params(const Params& P, uint32_t sb, int row, uint32_t tag, bool second) {
  uint4 v0, v1; poll_ll2(&P.g->statF[row], &P.g->statF[row + 128], 0xffffffffu, tag, v0, v1);
  #pragma unroll 1
  for (int q = 0; q < 2; q++) {
    float var = FL(v0.y), c = rsqrtf(var + LN_EPS);
    if (second) { c += 1.f; c *= rsqrtf(fmaf(var * c, c, LN_EPS)); }
    sts64f(sb + PAR + q * 1024 + (row & 127) * 8, c, -c * FL(v0.x));
    v0 = v1;
  }
}
DEVI void aux(const Params& P, uint32_t sb) {
  int tid = fresh_tid();
  #define lane (tid & 31)
  #define wq (tid >> 5)
  uint32_t ids = P.map[blockIdx.x], tag;
  #define bid ((int)(ids & 255))
  #define fid ((int)(ids >> 8))
  #define bi (bid >> 4)
  #define bp (bid & 15)
  #define bc (bp >> 1)
  #define FRESH() do { tid = fresh_tid(); uint4 z_ = ldsv128(sb + INFO2 + 16); ids = z_.y; tag = z_.z + L; idx = z_.w; } while (0)
  {
    const uint32_t epoch = ld_rlx(&P.g->epoch);
    if (tid == 0) {
      mbar_expect_tx(BAR(B_STG), 49152);
      tma_3d(sb + STG, &P.mWq, bp * 64, bi * 128, 0, BAR(B_STG));
      tma_3d(sb + STG + 24576, &P.mWq, bp * 64, bi * 128 + 64, 0, BAR(B_STG));
    }
    __syncwarp();
    sts64f(sb + ONES + tid * 8, FL(0x3F803F80u), FL(0x3F803F80u));
    fence_async_smem();
    float s1 = 0.f, s2 = 0.f;
    { uint4 v = __ldg((const uint4*)P.wr + tid);
      if ((tid >> 4) == bc) norm8(v, 0.f, 1.f, sb + WR + (tid & 15) * 32, 16);
      sum8(v, s1, s2);
      #pragma unroll 1
      for (int o = 16; o; o >>= 1) s1 += __shfl_xor_sync(0xffffffffu, s1, o);
      sts32f(sb + INFO2 + wq * 4, s1); }
    const uint4* src = (const uint4*)(P.x0 + (size_t)bid * 16384) + (tid >> 3) * 128 + (tid & 7);
    s1 = 0.f; s2 = 0.f;
    #pragma unroll 1
    for (int it = 0; it < 16; it += 4) {
      uint4 v0 = __ldg(src + it * 8), v1 = __ldg(src + it * 8 + 8), v2 = __ldg(src + it * 8 + 16), v3 = __ldg(src + it * 8 + 24);
      #pragma unroll 1
      for (int q = 0; q < 4; q++) { sum8(v0, s1, s2); v0 = v1; v1 = v2; v2 = v3; }
    }
    #pragma unroll 1
    for (int o = 1; o < 8; o <<= 1) { s1 += __shfl_xor_sync(0xffffffffu, s1, o); s2 += __shfl_xor_sync(0xffffffffu, s2, o); }
    tag = ((epoch % 16383u) + 1u) << 2;
    if (tid == 0) { sts128(sb + INFO, make_uint4(0x40000000u, 0u, tag, ((epoch % 127u) + 1u) << 1)); sts128(sb + INFO2 + 16, make_uint4(epoch, ids, tag, 0x40000000u)); }
    float m = s1 * (1.f / 1024.f);
    if ((tid & 7) == 0) st_ll(&P.g->statF[bid * 16 + (tid >> 3)], UI(m), UI(fmaxf(fmaf(-m, m, s2 * (1.f / 1024.f)), 0.f)), 0u, tag);
    bar_sync(2, 128);
    mbar_wait_b(BAR(B_STG), 0);
    if (tid < 96) {
      s1 = 0.f; s2 = 0.f;
      #pragma unroll 4
      for (int r = 0; r < 128; r++) {
        uint32_t v = lds32(sb + STG + (r >> 6) * 24576 + wq * 8192 + (r & 63) * 128 + ((lane * 4) ^ ((r & 7) << 4)));
        s1 += bf_lo(v); s2 += bf_hi(v);
      }
      st_ll(&P.g->csP[bp][bi][tid], UI(s1), UI(s2), 0u, tag);
      s1 = 0.f; s2 = 0.f;
      #pragma unroll 1
      for (int q = 0; q < 8; q += 2) {
        uint4 a, b; poll_ll2(&P.g->csP[bp][q][tid], &P.g->csP[bp][q + 1][tid], 0xffffffffu, tag, a, b);
        s1 += FL(a.x) + FL(b.x); s2 += FL(a.y) + FL(b.y);
      }
      sts64f(sb + CS + tid * 8, s1, s2);
    }
    qkv_params(P, sb, bi * 256 + tid, tag, false);
  }
  int idx;
  #pragma unroll 1
  for (int L = 0; L < 2; L++) {
    FRESH();
    {
      if ((idx >> 8) == bi && wq < 3) {
        uint4 v = poll_ll(&P.g->patch[wq * 256 + bp * 16 + (lane & 15)], 0xffffffffu, tag);
        sts64f(sb + PATCH + (wq * 16 + (lane & 15)) * 8, FL(v.x), FL(v.y));
      }
      sts32(sb + INFO, idx);
      bar_sync(2, 128);
      if (tid == 0) mbar_arrive(BAR(B_PAR));
      PROFX(tid == 0, L ? 23 : 17);
    }
    if (wq == 3) {
      mbar_wait_b(BAR(B_KVFULL + (L ? PFA1_BAR : PFA0_BAR)), L);
      uint32_t t0 = clk();
      #pragma unroll 1
      for (uint32_t m = L ? PFA1_M : PFA0_M; m; m &= m - 1) {
        if (lane == 0) ffn_prefetch(P, __ffs(m) - 1);
        while (clk() - t0 < (L ? PFA1_T : PFA0_T)) __nanosleep(50);
        t0 += L ? PFA1_T : PFA0_T;
      }
    }
    FRESH();
    mbar_wait_b(BAR(B_OFREE), L);
    #define blk (bi * 2 + (bid & 1))
    if (tid < 33) st_ll(tid < 32 ? &P.g->row[blk][bc * 32 + tid] : &P.g->best[bc][blk], 0u, 0u, 0u, 0u);
    mbar_wait_b(BAR(B_XRDY + 1), L); mbar_wait_b(BAR(B_XRDY + 3), L);
    PROFX(tid == 0, 37 + L * 16);
    FRESH();
    {
      float s1 = 0.f, s2 = 0.f, d = 0.f;
      #pragma unroll 1
      for (int q = 0; q < 8; q += 4) {
        const uint4* src = &P.g->statP[q][blk * 128 + tid];
        uint4 v0, v1, v2, v3; int it = 0;
        do { v0 = ld_ll(src); v1 = ld_ll(src + 2048); v2 = ld_ll(src + 4096); v3 = ld_ll(src + 6144); if (++it > SPIN_MAX) __trap(); }
        while (!__all_sync(0xffffffffu, v0.w == tag && v1.w == tag && v2.w == tag && v3.w == tag));
        s1 += (FL(v0.x) + FL(v1.x)) + (FL(v2.x) + FL(v3.x)); s2 += (FL(v0.y) + FL(v1.y)) + (FL(v2.y) + FL(v3.y)); d += (FL(v0.z) + FL(v1.z)) + (FL(v2.z) + FL(v3.z));
      }
      PROFX(tid == 0, 39 + L * 16);
      uint4 a = lds128(sb + INFO2), b, c;
      float m = s1 * (1.f / 1024.f), var = fmaxf(fmaf(-m, m, s2 * (1.f / 1024.f)), 0.f), rs = rsqrtf(var + LN_EPS);
      uint32_t key = UI(fmaf(-m, (FL(a.x) + FL(a.y)) + (FL(a.z) + FL(a.w)), d) * rs);
      key ^= (uint32_t)((int)key >> 31) | 0x80000000u;
      uint32_t win = __ballot_sync(0xffffffffu, key == __reduce_max_sync(0xffffffffu, key));
      if (lane == __ffs(win) - 1) sts128(sb + RED + wq * 16, make_uint4(key, UI(m), UI(rs), (tag << 11) | (uint32_t)(blk * 128 + tid)));
      if (L) sts64f(sb + PAR + tid * 8, 1.f + rs, -m * rs);
      bar_sync(2, 128);
      if (wq == 0) {
        a = best4(sb + RED);
        float2 v = lds64f(sb + (lane >> 4) * 32768 + (a.w & 255) * 128 + (((lane & 15) * 8) ^ ((a.w & 7) << 4)));
        st_ll(&P.g->row[blk][bc * 32 + lane], UI(v.x), UI(v.y), 0u, tag);
        if (lane == 0) { st_ll(&P.g->best[bc][blk], a.x, a.y, a.z, a.w); sts32(sb + INFO + 4, a.w & 2047); }
        __syncwarp();
        if (L) {
          const float al = 1.f + FL(a.z), be = -FL(a.y) * FL(a.z);
          sts64f(sb + RED + 1792 + lane * 8, FL(pack_bf16(fmaf(bf_lo(UI(v.x)), al, be), fmaf(bf_hi(UI(v.x)), al, be))),
                                             FL(pack_bf16(fmaf(bf_lo(UI(v.y)), al, be), fmaf(bf_hi(UI(v.y)), al, be))));
        }
        if (lane < 2 - L) mbar_arrive(L ? BAR(B_PAR) : BAR(B_XFREE + lane));
      }
      if (!L && (tid >> 4) == bc) st_ll(&P.g->statF[blk * 128 + tid], UI(m), UI(var), 0u, tag + 1);
      PROFX(tid == 0, 18 + L * 6);
      FRESH();
      if (!L) {
        if (fid < 112) { st_ll(&P.g->yP[tid & ~1][fid][tid & 1], 0u, 0u, 0u, 0u); st_ll(&P.g->yP[tid | 1][fid][tid & 1], 0u, 0u, 0u, 0u); }
        if (tid < 24) st_ll(tid < 16 ? &P.g->x2[tid >> 1][2 * bid + (tid & 1)] : &P.g->patch[fid * 8 + tid - 16], 0u, 0u, 0u, 0u);
      }
      a = poll_ll(&P.g->best[bc][lane & 15], 0xfffff800u, tag << 11);
      win = __ffs(__ballot_sync(0xffffffffu, a.x == __reduce_max_sync(0xffffffffu, a.x))) - 1;
      idx = __shfl_sync(0xffffffffu, a.w, win) & 2047;
      PROFX(tid == 0, 19 + L * 6);
      poll_ll2(&P.g->row[win][tid], &P.g->row[win][tid + 128], 0xffffffffu, tag, c, b);
      c.z = b.x; c.w = b.y;
      a.x = __shfl_sync(0xffffffffu, a.x, win); a.y = __shfl_sync(0xffffffffu, a.y, win); a.z = __shfl_sync(0xffffffffu, a.z, win);
      sts32(sb + INFO2 + 28, idx);
      PROFX(tid == 0, 61 + L);
      b = norm8(c, FL(a.y), FL(a.z), sb + HV + tid * 16, 2048);
      if (L && fid < 112) bar_arrive(3, 384);
      if ((tid >> 1) == (bid & 63)) {
        sts128(sb + RED + 64 + (tid & 1) * 16, bid < 64 ? make_uint4(c.x, c.y, b.x, b.y) : make_uint4(c.z, c.w, b.z, b.w));
        sts32(sb + RED + 96, a.x);
      }
      if (L && wq == 0 && win != blk) *(float2*)(P.out + (size_t)lds32(sb + INFO + 4) * 1024 + bc * 128 + lane * 4) = lds64f(sb + RED + 1792 + lane * 8);
      bar_sync(2, 128);
    }
    #pragma unroll 1
    for (int st = L; st < 3; st++) {
      FRESH();
      float a[8] = {0.f, 0.f, 0.f, 0.f, 0.f, 0.f, 0.f, 0.f};
      if (L == 0 && fid < (st == 2 ? 96 : 112)) {
        uint32_t ha = st == 1 ? sb + RED + 768 : sb + HV + ((st ? wq : wq & 1) * 64 + (lane >> 2)) * 4;
        uint32_t ph = (st ? (st == 1 ? 0x1cu : 0x11u) : 0x171u), bar = st == 1 ? BAR(B_STG + 2) : BAR(B_STG);
        uint32_t wa = sb + STG + tid * 16 + wq * 3584 + (st == 1 ? 32768 : 0);
        const uint32_t hx = st == 1 ? 256 : (st ? 1024 : 512);
        const bool lead = lane == 0;
        #pragma unroll 1
        do {
          mbar_wait(bar, ph & 1);
          PROFX(lead && threadIdx.x == 256 && st == 0 && (ph > 255 || ph < 4), 40 - 23 + __clz(ph));
          gemv8(a, wa, ha, 32);
          __syncwarp();
          if (lead) mbar_arrive(bar - 8 * (B_STG - B_STGE));
          const bool wrap = bar == BAR(B_STG + 2);
          bar += wrap ? -16 : 8; wa += wrap ? -32768 : 16384; ha += hx;
          ph >>= 1;
        } while (ph != 1);
      }
      FRESH();
      if (st == 1) {
        const uint32_t t8 = lds32(sb + INFO + 12) + L;
        if (L == 0 && fid < 112) {
          const bool odd = lane & 1;
          #pragma unroll
          for (int e = 0; e < 4; e++) { float z = __shfl_xor_sync(0xffffffffu, odd ? a[e] : a[4 + e], 1); if (odd) a[e] = z; else a[4 + e] = z; }
          uint4* dst = &P.g->yP[tid & ~1][fid][tid & 1];
          st_ll(dst, UI(a[0]), UI(a[1]), UI(a[2]), (UI(a[3]) & ~255u) | t8);
          st_ll(dst + 224, UI(a[4]), UI(a[5]), UI(a[6]), (UI(a[7]) & ~255u) | t8);
          PROFX(tid == 0, 21);
        }
        if (!L) qkv_params(P, sb, bi * 256 + tid, tag + 1, true);
        if (tid == 0) { uint32_t k = lds32(sb + RED + 96); sts32f(sb + RED + 100, bf_round(__fdividef(1.f, 1.f + __expf(-bf_round(FL(k ^ (~(uint32_t)((int)k >> 31) | 0x80000000u))))))); }
        uint4 v0, v1;
        poll_ll2(&P.g->yP[bid][0][min(tid, 111)], &P.g->yP[bid][0][min(tid, 111) + 112], 255u, t8, v0, v1);
        const float lo = (tid < 112 && !(tid & 1)) ? 1.f : 0.f, hi = (tid < 112 && (tid & 1)) ? 1.f : 0.f;
        const float y0 = FL(v0.x) + FL(v1.x), y1 = FL(v0.y) + FL(v1.y), y2 = FL(v0.z) + FL(v1.z), y3 = FL((v0.w & ~255u) | 128u) + FL((v1.w & ~255u) | 128u);
        a[0] = y0 * lo; a[1] = y1 * lo; a[2] = y2 * lo; a[3] = y3 * lo; a[4] = y0 * hi; a[5] = y1 * hi; a[6] = y2 * hi; a[7] = y3 * hi;
      }
      sts32f(sb + RED + 256 + wq * 128 + ((lane & 3) * 8 + (lane >> 2)) * 4, fold8(a));
      bar_sync(2, 128);
      const uint32_t d = sb + RED + 256 + lane * 4;
      float z0 = lds32f(d) + lds32f(d + 128), z1 = lds32f(d + 256) + lds32f(d + 384);
      if (st == 0) { sts32f(sb + RED + 768 + lane * 32 + wq * 4, swiglu(z0, z1)); bar_sync(2, 128); PROFX(tid == 0, 20); continue; }
      z0 += z1;
      if (st == 1) {
        z0 += __shfl_xor_sync(0xffffffffu, z0, 8); z0 += __shfl_xor_sync(0xffffffffu, z0, 16);
        uint32_t xw = lds32(sb + RED + 64 + (lane & 4) * 4 + (lane & 2) * 2), hw = lds32(sb + RED + 72 + (lane & 4) * 4 + (lane & 2) * 2);
        z0 = bf_round(((lane & 1) ? bf_hi(hw) : bf_lo(hw)) + bf_round(bf_round(z0) * lds32f(sb + RED + 100))) + ((lane & 1) ? bf_hi(xw) : bf_lo(xw));
      } else if (fid < 32) z0 *= QSCALE;
      uint32_t v = pack_bf16(z0, __shfl_down_sync(0xffffffffu, z0, 1)), v2 = __shfl_down_sync(0xffffffffu, v, 2);
      if (L) { if (tid == 0 || tid == 4) *(uint2*)(P.out + (size_t)idx * 1024 + bid * 8 + tid) = make_uint2(v, v2); PROFW(tid == 0, 28); break; }
      if ((tid & 3) == 0 && tid < (st == 1 ? 64 : 32)) st_ll(st == 1 ? &P.g->x2[tid >> 3][2 * bid + ((tid >> 2) & 1)] : &P.g->patch[fid * 8 + (tid >> 2)], v, v2, 0u, tag + 1);
      PROFX(tid == 0, st == 1 ? 22 : 31);
      if (st == 1) {
        uint4 x, y; poll_ll2(&P.g->x2[bi][tid], &P.g->x2[bi][tid + 128], 0xffffffffu, tag + 1, x, y);
        x.z = y.x; x.w = y.y;
        if (wq == (bc & 3)) sts64f(sb + X2SEG + lane * 8, FL(bc < 4 ? x.x : x.z), FL(bc < 4 ? x.y : x.w));
        float s1 = 0.f, s2 = 0.f;
        sum8(x, s1, s2);
        #pragma unroll
        for (int o = 16; o; o >>= 1) { s1 += __shfl_xor_sync(0xffffffffu, s1, o); s2 += __shfl_xor_sync(0xffffffffu, s2, o); }
        sts64f(sb + RED + wq * 8, s1, s2);
        bar_sync(2, 128);
        y = lds128(sb + RED); uint4 y2 = lds128(sb + RED + 16);
        float m = ((FL(y.x) + FL(y.z)) + (FL(y2.x) + FL(y2.z))) * (1.f / 1024.f);
        norm8(x, m, rsqrtf(fmaxf(fmaf(-m, m, ((FL(y.y) + FL(y.w)) + (FL(y2.y) + FL(y2.w))) * (1.f / 1024.f)), 0.f) + LN_EPS), sb + HV + tid * 16, 2048);
        bar_sync(2, 128);
        PROFX(tid == 0, 30);
      }
    }
  }
  if (bid == 0 && tid == 0) P.g->epoch = lds32(sb + INFO2 + 16) + 1;
  #undef blk
  #undef bid
  #undef fid
  #undef bi
  #undef bp
  #undef bc
  #undef FRESH
  #undef lane
  #undef wq
}

__global__ void __cluster_dims__(2, 1, 1) __launch_bounds__(512, 1) fused_kernel(const __grid_constant__ Params P) {
  extern __shared__ __align__(1024) uint8_t smem_raw[];
  const uint32_t sb = smem_u32(smem_raw);
  PROFT(threadIdx.x == 0, 0);
  if (threadIdx.x == 0) {
    for (int s = 0; s < 3; s++) mbar_init(BAR(B_FULLQ + s), 1);
    asm volatile("fence.mbarrier_init.release.cluster;" ::: "memory");
    for (int s = 0; s < 3; s++) {
      mbar_expect_tx(BAR(B_FULLQ + s), 57344);
      tma_2d(sb + qa_off(s), &P.mX, s * 64, (BID >> 4) * 256, BAR(B_FULLQ + s));
      tma_3d(sb + qb_off(s), &P.mWq, (BID & 15) * 64, s * 64, 0, BAR(B_FULLQ + s));
    }
    if ((sb & 4095) != 1024) __trap();
  } else if (threadIdx.x >= 32 + B_EMPTYQ && threadIdx.x < 32 + B_COUNT) {
    const int b = threadIdx.x - 32;
    const uint32_t cnt = b < B_XFREE ? 2 : (b < B_KVRDY ? 3 : (b < B_KVFULL ? 4 : 1));
    mbar_init(BAR(b), cnt);
    asm volatile("fence.mbarrier_init.release.cluster;" ::: "memory");
  }
  __syncthreads();
  asm volatile("barrier.cluster.arrive.relaxed.aligned;" ::: "memory");
  const int wg = __shfl_sync(0xffffffffu, threadIdx.x >> 7, 0);
  if (wg < 2) { reg_inc<224>(); consumer(P, sb, wg); }
  else if (wg == 2) { reg_dec<40>(); aux(P, sb); }
  else {
    reg_dec<24>();
    asm volatile("barrier.cluster.wait.aligned;" ::: "memory");
    const int w = __shfl_sync(0xffffffffu, (threadIdx.x >> 5) & 3, 0);
    if (w == 0) loader(P, sb);
    else if (w < 3) storer(P, sb, w - 1);
    else if ((threadIdx.x & 31) == 0) stager(P, sb);
  }
}

typedef CUresult (*EncFn)(CUtensorMap*, CUtensorMapDataType, cuuint32_t, void*, const cuuint64_t*, const cuuint64_t*, const cuuint32_t*, const cuuint32_t*,
                          CUtensorMapInterleave, CUtensorMapSwizzle, CUtensorMapL2promotion, CUtensorMapFloatOOBfill);
static void mk_map(EncFn enc, CUtensorMap* m, const void* ptr, int rank, const cuuint64_t* dims, const cuuint64_t* strides, const cuuint32_t* box,
                   CUtensorMapSwizzle sw, CUtensorMapL2promotion pr) {
  cuuint32_t es[5] = {1, 1, 1, 1, 1};
  enc(m, CU_TENSOR_MAP_DATA_TYPE_BFLOAT16, rank, (void*)ptr, dims, strides, box, es, CU_TENSOR_MAP_INTERLEAVE_NONE, sw, pr, CU_TENSOR_MAP_FLOAT_OOB_FILL_NONE);
}
extern "C" void kernel_launch(void* const* d_in, const int* in_sizes, int n_in, void* d_out, int out_size) {
  (void)in_sizes; (void)n_in; (void)out_size;
  void* fn = nullptr; cudaDriverEntryPointQueryResult q;
  cudaGetDriverEntryPoint("cuTensorMapEncodeTiled", &fn, cudaEnableDefault, &q);
  EncFn enc = (EncFn)fn;
  cudaFuncSetAttribute(fused_kernel, cudaFuncAttributeMaxDynamicSharedMemorySize, SMEM_BYTES);
  Params P;
  const CUtensorMapSwizzle S128 = CU_TENSOR_MAP_SWIZZLE_128B, S0 = CU_TENSOR_MAP_SWIZZLE_NONE;
  const CUtensorMapL2promotion L256 = CU_TENSOR_MAP_L2_PROMOTION_L2_256B, L128 = CU_TENSOR_MAP_L2_PROMOTION_L2_128B;
  { cuuint64_t d[2] = {1024, 2048}, s[1] = {2048}; cuuint32_t b[2] = {64, 256}, bh[2] = {64, 128};
    mk_map(enc, &P.mX, d_in[0], 2, d, s, b, S128, L256); mk_map(enc, &P.mXh, d_in[0], 2, d, s, bh, S128, L256); }
  { cuuint64_t d[3] = {1024, 1024, 3}, s[2] = {6144, 2048}; cuuint32_t b[3] = {64, 64, 3}; mk_map(enc, &P.mWq, d_in[1], 3, d, s, b, S128, L256); }
  { cuuint64_t d[5] = {64, 32, 2, 16, 16}, s[4] = {2048, 65536, 131072, 128}; cuuint32_t b[5] = {64, 32, 1, 2, 2}; mk_map(enc, &P.mWo, d_in[2], 5, d, s, b, S128, L256); }
  { cuuint64_t d[2] = {3584, 1024}, s[1] = {7168}; cuuint32_t b[2] = {32, 128};
    mk_map(enc, &P.mWg, d_in[5], 2, d, s, b, S0, L128); mk_map(enc, &P.mWu, d_in[6], 2, d, s, b, S0, L128); }
  { cuuint64_t d[2] = {3072, 1024}, s[1] = {6144}; cuuint32_t b[2] = {32, 256}; mk_map(enc, &P.mWp, d_in[1], 2, d, s, b, S0, L128); }
  { cuuint64_t d[3] = {256, 3584, 4}, s[2] = {2048, 512}; cuuint32_t b[3] = {256, 8, 4}; mk_map(enc, &P.mWd, d_in[7], 3, d, s, b, S0, L128); }
  P.x0 = (const bf16*)d_in[0]; P.wqkv = (const bf16*)d_in[1]; P.wo = (const bf16*)d_in[2]; P.wr = (const bf16*)d_in[4]; P.wg = (const bf16*)d_in[5]; P.wu = (const bf16*)d_in[6]; P.wd = (const bf16*)d_in[7];
  P.out = (bf16*)d_out;
  cudaGetSymbolAddress((void**)&P.g, g_scr);
  for (int b = 0; b < 128; b++) {
    int j = b >> 1, quad = j < 4 ? 0 : (j < 36 ? 1 + (j - 4) % 8 : 9 + (j - 36) % 7), pos = j < 4 ? j : (j < 36 ? (j - 4) / 8 : (j - 36) / 7);
    int bid = ((quad >> 2) * 2 + (pos >> 1)) * 16 + ((quad & 3) * 2 + (pos & 1)) * 2 + (b & 1);
    int e = pos * 2 + (b & 1), fid = e < 6 ? quad * 6 + e : e * 16 + quad;
    P.map[b] = bid | fid << 8;
  }
  fused_kernel<<<128, 512, SMEM_BYTES>>>(P);
}
```

```cpp
#include <cuda_runtime.h>
#include <cuda_bf16.h>
#include <cuda.h>
#include <stdint.h>
#include <stddef.h>
typedef __nv_bfloat16 bf16;

template<int TB, int TA = 0> __device__ __forceinline__ void wgmma_ss_n192(float (&d)[96], uint64_t da, uint64_t db, int scale_d) {
  asm volatile("{\n.reg .pred p;\nsetp.ne.b32 p, %98, 0;\n"
    "wgmma.mma_async.sync.aligned.m64n192k16.f32.bf16.bf16 {%0, %1, %2, %3, %4, %5, %6, %7, %8, %9, %10, %11, %12, %13, %14, %15, %16, %17, %18, %19, %20, %21, %22, %23, %24, %25, %26, %27, %28, %29, %30, %31, %32, %33, %34, %35, %36, %37, %38, %39, %40, %41, %42, %43, %44, %45, %46, %47, %48, %49, %50, %51, %52, %53, %54, %55, %56, %57, %58, %59, %60, %61, %62, %63, %64, %65, %66, %67, %68, %69, %70, %71, %72, %73, %74, %75, %76, %77, %78, %79, %80, %81, %82, %83, %84, %85, %86, %87, %88, %89, %90, %91, %92, %93, %94, %95}, %96, %97, p, 1, 1, %100, %99;\n}\n"
    : "+f"(d[0]), "+f"(d[1]), "+f"(d[2]), "+f"(d[3]), "+f"(d[4]), "+f"(d[5]), "+f"(d[6]), "+f"(d[7]), "+f"(d[8]), "+f"(d[9]), "+f"(d[10]), "+f"(d[11]), "+f"(d[12]), "+f"(d[13]), "+f"(d[14]), "+f"(d[15]), "+f"(d[16]), "+f"(d[17]), "+f"(d[18]), "+f"(d[19]), "+f"(d[20]), "+f"(d[21]), "+f"(d[22]), "+f"(d[23]), "+f"(d[24]), "+f"(d[25]), "+f"(d[26]), "+f"(d[27]), "+f"(d[28]), "+f"(d[29]), "+f"(d[30]), "+f"(d[31]), "+f"(d[32]), "+f"(d[33]), "+f"(d[34]), "+f"(d[35]), "+f"(d[36]), "+f"(d[37]), "+f"(d[38]), "+f"(d[39]), "+f"(d[40]), "+f"(d[41]), "+f"(d[42]), "+f"(d[43]), "+f"(d[44]), "+f"(d[45]), "+f"(d[46]), "+f"(d[47]), "+f"(d[48]), "+f"(d[49]), "+f"(d[50]), "+f"(d[51]), "+f"(d[52]), "+f"(d[53]), "+f"(d[54]), "+f"(d[55]), "+f"(d[56]), "+f"(d[57]), "+f"(d[58]), "+f"(d[59]), "+f"(d[60]), "+f"(d[61]), "+f"(d[62]), "+f"(d[63]), "+f"(d[64]), "+f"(d[65]), "+f"(d[66]), "+f"(d[67]), "+f"(d[68]), "+f"(d[69]), "+f"(d[70]), "+f"(d[71]), "+f"(d[72]), "+f"(d[73]), "+f"(d[74]), "+f"(d[75]), "+f"(d[76]), "+f"(d[77]), "+f"(d[78]), "+f"(d[79]), "+f"(d[80]), "+f"(d[81]), "+f"(d[82]), "+f"(d[83]), "+f"(d[84]), "+f"(d[85]), "+f"(d[86]), "+f"(d[87]), "+f"(d[88]), "+f"(d[89]), "+f"(d[90]), "+f"(d[91]), "+f"(d[92]), "+f"(d[93]), "+f"(d[94]), "+f"(d[95])
    : "l"(da), "l"(db), "r"(scale_d), "n"(TB), "n"(TA));
}

template<int TB> __device__ __forceinline__ void wgmma_rs_n192(float (&d)[96], uint32_t a0, uint32_t a1, uint32_t a2, uint32_t a3, uint64_t db, int scale_d) {
  asm volatile("{\n.reg .pred p;\nsetp.ne.b32 p, %101, 0;\n"
    "wgmma.mma_async.sync.aligned.m64n192k16.f32.bf16.bf16 {%0, %1, %2, %3, %4, %5, %6, %7, %8, %9, %10, %11, %12, %13, %14, %15, %16, %17, %18, %19, %20, %21, %22, %23, %24, %25, %26, %27, %28, %29, %30, %31, %32, %33, %34, %35, %36, %37, %38, %39, %40, %41, %42, %43, %44, %45, %46, %47, %48, %49, %50, %51, %52, %53, %54, %55, %56, %57, %58, %59, %60, %61, %62, %63, %64, %65, %66, %67, %68, %69, %70, %71, %72, %73, %74, %75, %76, %77, %78, %79, %80, %81, %82, %83, %84, %85, %86, %87, %88, %89, %90, %91, %92, %93, %94, %95}, {%96, %97, %98, %99}, %100, p, 1, 1, %102;\n}\n"
    : "+f"(d[0]), "+f"(d[1]), "+f"(d[2]), "+f"(d[3]), "+f"(d[4]), "+f"(d[5]), "+f"(d[6]), "+f"(d[7]), "+f"(d[8]), "+f"(d[9]), "+f"(d[10]), "+f"(d[11]), "+f"(d[12]), "+f"(d[13]), "+f"(d[14]), "+f"(d[15]), "+f"(d[16]), "+f"(d[17]), "+f"(d[18]), "+f"(d[19]), "+f"(d[20]), "+f"(d[21]), "+f"(d[22]), "+f"(d[23]), "+f"(d[24]), "+f"(d[25]), "+f"(d[26]), "+f"(d[27]), "+f"(d[28]), "+f"(d[29]), "+f"(d[30]), "+f"(d[31]), "+f"(d[32]), "+f"(d[33]), "+f"(d[34]), "+f"(d[35]), "+f"(d[36]), "+f"(d[37]), "+f"(d[38]), "+f"(d[39]), "+f"(d[40]), "+f"(d[41]), "+f"(d[42]), "+f"(d[43]), "+f"(d[44]), "+f"(d[45]), "+f"(d[46]), "+f"(d[47]), "+f"(d[48]), "+f"(d[49]), "+f"(d[50]), "+f"(d[51]), "+f"(d[52]), "+f"(d[53]), "+f"(d[54]), "+f"(d[55]), "+f"(d[56]), "+f"(d[57]), "+f"(d[58]), "+f"(d[59]), "+f"(d[60]), "+f"(d[61]), "+f"(d[62]), "+f"(d[63]), "+f"(d[64]), "+f"(d[65]), "+f"(d[66]), "+f"(d[67]), "+f"(d[68]), "+f"(d[69]), "+f"(d[70]), "+f"(d[71]), "+f"(d[72]), "+f"(d[73]), "+f"(d[74]), "+f"(d[75]), "+f"(d[76]), "+f"(d[77]), "+f"(d[78]), "+f"(d[79]), "+f"(d[80]), "+f"(d[81]), "+f"(d[82]), "+f"(d[83]), "+f"(d[84]), "+f"(d[85]), "+f"(d[86]), "+f"(d[87]), "+f"(d[88]), "+f"(d[89]), "+f"(d[90]), "+f"(d[91]), "+f"(d[92]), "+f"(d[93]), "+f"(d[94]), "+f"(d[95])
    : "r"(a0), "r"(a1), "r"(a2), "r"(a3), "l"(db), "r"(scale_d), "n"(TB));
}

template<int TB, int TA = 0> __device__ __forceinline__ void wgmma_ss_n128(float (&d)[64], uint64_t da, uint64_t db, int scale_d) {
  asm volatile("{\n.reg .pred p;\nsetp.ne.b32 p, %66, 0;\n"
    "wgmma.mma_async.sync.aligned.m64n128k16.f32.bf16.bf16 {%0, %1, %2, %3, %4, %5, %6, %7, %8, %9, %10, %11, %12, %13, %14, %15, %16, %17, %18, %19, %20, %21, %22, %23, %24, %25, %26, %27, %28, %29, %30, %31, %32, %33, %34, %35, %36, %37, %38, %39, %40, %41, %42, %43, %44, %45, %46, %47, %48, %49, %50, %51, %52, %53, %54, %55, %56, %57, %58, %59, %60, %61, %62, %63}, %64, %65, p, 1, 1, %68, %67;\n}\n"
    : "+f"(d[0]), "+f"(d[1]), "+f"(d[2]), "+f"(d[3]), "+f"(d[4]), "+f"(d[5]), "+f"(d[6]), "+f"(d[7]), "+f"(d[8]), "+f"(d[9]), "+f"(d[10]), "+f"(d[11]), "+f"(d[12]), "+f"(d[13]), "+f"(d[14]), "+f"(d[15]), "+f"(d[16]), "+f"(d[17]), "+f"(d[18]), "+f"(d[19]), "+f"(d[20]), "+f"(d[21]), "+f"(d[22]), "+f"(d[23]), "+f"(d[24]), "+f"(d[25]), "+f"(d[26]), "+f"(d[27]), "+f"(d[28]), "+f"(d[29]), "+f"(d[30]), "+f"(d[31]), "+f"(d[32]), "+f"(d[33]), "+f"(d[34]), "+f"(d[35]), "+f"(d[36]), "+f"(d[37]), "+f"(d[38]), "+f"(d[39]), "+f"(d[40]), "+f"(d[41]), "+f"(d[42]), "+f"(d[43]), "+f"(d[44]), "+f"(d[45]), "+f"(d[46]), "+f"(d[47]), "+f"(d[48]), "+f"(d[49]), "+f"(d[50]), "+f"(d[51]), "+f"(d[52]), "+f"(d[53]), "+f"(d[54]), "+f"(d[55]), "+f"(d[56]), "+f"(d[57]), "+f"(d[58]), "+f"(d[59]), "+f"(d[60]), "+f"(d[61]), "+f"(d[62]), "+f"(d[63])
    : "l"(da), "l"(db), "r"(scale_d), "n"(TB), "n"(TA));
}

template<int TB, int TA = 0> __device__ __forceinline__ void wgmma_ss_n64(float (&d)[32], uint64_t da, uint64_t db, int scale_d) {
  asm volatile("{\n.reg .pred p;\nsetp.ne.b32 p, %34, 0;\n"
    "wgmma.mma_async.sync.aligned.m64n64k16.f32.bf16.bf16 {%0, %1, %2, %3, %4, %5, %6, %7, %8, %9, %10, %11, %12, %13, %14, %15, %16, %17, %18, %19, %20, %21, %22, %23, %24, %25, %26, %27, %28, %29, %30, %31}, %32, %33, p, 1, 1, %36, %35;\n}\n"
    : "+f"(d[0]), "+f"(d[1]), "+f"(d[2]), "+f"(d[3]), "+f"(d[4]), "+f"(d[5]), "+f"(d[6]), "+f"(d[7]), "+f"(d[8]), "+f"(d[9]), "+f"(d[10]), "+f"(d[11]), "+f"(d[12]), "+f"(d[13]), "+f"(d[14]), "+f"(d[15]), "+f"(d[16]), "+f"(d[17]), "+f"(d[18]), "+f"(d[19]), "+f"(d[20]), "+f"(d[21]), "+f"(d[22]), "+f"(d[23]), "+f"(d[24]), "+f"(d[25]), "+f"(d[26]), "+f"(d[27]), "+f"(d[28]), "+f"(d[29]), "+f"(d[30]), "+f"(d[31])
    : "l"(da), "l"(db), "r"(scale_d), "n"(TB), "n"(TA));
}

template<int TB> __device__ __forceinline__ void wgmma_rs_n40(float (&d)[20], uint32_t a0, uint32_t a1, uint32_t a2, uint32_t a3, uint64_t db, int scale_d) {
  asm volatile("{\n.reg .pred p;\nsetp.ne.b32 p, %25, 0;\n"
    "wgmma.mma_async.sync.aligned.m64n40k16.f32.bf16.bf16 {%0, %1, %2, %3, %4, %5, %6, %7, %8, %9, %10, %11, %12, %13, %14, %15, %16, %17, %18, %19}, {%20, %21, %22, %23}, %24, p, 1, 1, %26;\n}\n"
    : "+f"(d[0]), "+f"(d[1]), "+f"(d[2]), "+f"(d[3]), "+f"(d[4]), "+f"(d[5]), "+f"(d[6]), "+f"(d[7]), "+f"(d[8]), "+f"(d[9]), "+f"(d[10]), "+f"(d[11]), "+f"(d[12]), "+f"(d[13]), "+f"(d[14]), "+f"(d[15]), "+f"(d[16]), "+f"(d[17]), "+f"(d[18]), "+f"(d[19])
    : "r"(a0), "r"(a1), "r"(a2), "r"(a3), "l"(db), "r"(scale_d), "n"(TB));
}

#define DEVI __device__ __forceinline__
DEVI uint32_t smem_u32(const void* p) { return (uint32_t)__cvta_generic_to_shared(p); }
DEVI void mbar_init(uint32_t bar, uint32_t cnt) { asm volatile("mbarrier.init.shared::cta.b64 [%0], %1;" :: "r"(bar), "r"(cnt)); }
DEVI void mbar_expect_tx(uint32_t bar, uint32_t bytes) { asm volatile("mbarrier.arrive.expect_tx.shared::cta.b64 _, [%0], %1;" :: "r"(bar), "r"(bytes) : "memory"); }
DEVI void mbar_arrive(uint32_t bar) { asm volatile("mbarrier.arrive.shared::cta.b64 _, [%0];" :: "r"(bar) : "memory"); }
DEVI void mbar_arrive_peer(uint32_t bar) {
  asm volatile("{\n.reg .b32 ra;\nmapa.shared::cluster.u32 ra, %0, %1;\nmbarrier.arrive.shared::cluster.b64 _, [ra];\n}" :: "r"(bar), "r"((blockIdx.x & 1) ^ 1) : "memory");
}
DEVI void bulk_s2peer(uint32_t a, uint32_t bytes, uint32_t bar) {
  asm volatile("{\n.reg .b32 ra, rb;\nmapa.shared::cluster.u32 ra, %0, %3;\nmapa.shared::cluster.u32 rb, %2, %3;\n"
               "cp.async.bulk.shared::cluster.shared::cta.mbarrier::complete_tx::bytes [ra], [%0], %1, [rb];\n}"
               :: "r"(a), "r"(bytes), "r"(bar), "r"((blockIdx.x & 1) ^ 1) : "memory");
}
DEVI void mbar_wait(uint32_t bar, uint32_t parity) {
  asm volatile("{\n.reg .pred p;\nLW:\nmbarrier.try_wait.parity.shared::cta.b64 p, [%0], %1;\n@!p bra LW;\n}" :: "r"(bar), "r"(parity) : "memory");
}
DEVI void mbar_wait_b(uint32_t bar, uint32_t parity) {
  asm volatile("{\n.reg .pred p;\n.reg .u32 it;\nmov.u32 it, 0;\nLW:\nmbarrier.try_wait.parity.shared::cta.b64 p, [%0], %1;\n@p bra LD;\n"
               "add.u32 it, it, 1;\nsetp.lt.u32 p, it, 0x1000000;\n@p bra LW;\ntrap;\nLD:\n}" :: "r"(bar), "r"(parity) : "memory");
}
DEVI void tma_2d(uint32_t dst, const CUtensorMap* m, int c0, int c1, uint32_t bar) {
  asm volatile("cp.async.bulk.tensor.2d.shared::cluster.global.mbarrier::complete_tx::bytes [%0], [%1, {%3, %4}], [%2];"
    :: "r"(dst), "l"(m), "r"(bar), "r"(c0), "r"(c1) : "memory");
}
DEVI void tma_3d(uint32_t dst, const CUtensorMap* m, int c0, int c1, int c2, uint32_t bar) {
  asm volatile("cp.async.bulk.tensor.3d.shared::cluster.global.mbarrier::complete_tx::bytes [%0], [%1, {%3, %4, %5}], [%2];"
    :: "r"(dst), "l"(m), "r"(bar), "r"(c0), "r"(c1), "r"(c2) : "memory");
}
#define POL_EF POL_FIRST
constexpr uint64_t POL_FIRST = 0x12F0000000000000ull, POL_NORMAL = 0x1000000000000000ull;
DEVI void tma_2d_h(uint32_t dst, const CUtensorMap* m, int c0, int c1, uint32_t bar, uint64_t pol) {
  asm volatile("cp.async.bulk.tensor.2d.shared::cluster.global.mbarrier::complete_tx::bytes.L2::cache_hint [%0], [%1, {%3, %4}], [%2], %5;"
    :: "r"(dst), "l"(m), "r"(bar), "r"(c0), "r"(c1), "l"(pol) : "memory");
}
DEVI void tma_3d_h(uint32_t dst, const CUtensorMap* m, int c0, int c1, int c2, uint32_t bar, uint64_t pol) {
  asm volatile("cp.async.bulk.tensor.3d.shared::cluster.global.mbarrier::complete_tx::bytes.L2::cache_hint [%0], [%1, {%3, %4, %5}], [%2], %6;"
    :: "r"(dst), "l"(m), "r"(bar), "r"(c0), "r"(c1), "r"(c2), "l"(pol) : "memory");
}
DEVI void bulk_g2s_h(uint32_t s, const void* g, uint32_t bytes, uint32_t bar, uint64_t pol = POL_EF) {
  asm volatile("cp.async.bulk.shared::cluster.global.mbarrier::complete_tx::bytes.L2::cache_hint [%0], [%1], %2, [%3], %4;"
    :: "r"(s), "l"(g), "r"(bytes), "r"(bar), "l"(pol) : "memory");
}
DEVI void tma_5d(uint32_t dst, const CUtensorMap* m, int c0, int c1, int c2, int c3, int c4, uint32_t bar, uint64_t pol) {
  asm volatile("cp.async.bulk.tensor.5d.shared::cluster.global.mbarrier::complete_tx::bytes.L2::cache_hint [%0], [%1, {%3, %4, %5, %6, %7}], [%2], %8;"
    :: "r"(dst), "l"(m), "r"(bar), "r"(c0), "r"(c1), "r"(c2), "r"(c3), "r"(c4), "l"(pol) : "memory");
}
DEVI void tma_prefetch_2d(const CUtensorMap* m, int c0, int c1) {
  asm volatile("cp.async.bulk.prefetch.tensor.2d.L2.global.tile [%0, {%1, %2}];" :: "l"(m), "r"(c0), "r"(c1) : "memory");
}
DEVI void tma_prefetch_3d(const CUtensorMap* m, int c0, int c1, int c2) {
  asm volatile("cp.async.bulk.prefetch.tensor.3d.L2.global.tile [%0, {%1, %2, %3}];" :: "l"(m), "r"(c0), "r"(c1), "r"(c2) : "memory");
}
DEVI void bulk_prefetch(const void* g, uint32_t bytes) { asm volatile("cp.async.bulk.prefetch.L2.global [%0], %1;" :: "l"(g), "r"(bytes) : "memory"); }
DEVI void bulk_g2s(uint32_t s, const void* g, uint32_t bytes, uint32_t bar) {
  asm volatile("cp.async.bulk.shared::cluster.global.mbarrier::complete_tx::bytes [%0], [%1], %2, [%3];" :: "r"(s), "l"(g), "r"(bytes), "r"(bar) : "memory");
}
DEVI void bulk_s2g(void* g, uint32_t s, uint32_t bytes) {
  asm volatile("cp.async.bulk.global.shared::cta.bulk_group [%0], [%1], %2;\ncp.async.bulk.commit_group;" :: "l"(g), "r"(s), "r"(bytes) : "memory");
}
template<int N> DEVI void bulk_wait() { asm volatile("cp.async.bulk.wait_group %0;" :: "n"(N) : "memory"); }
DEVI void fence_async_smem() { asm volatile("fence.proxy.async.shared::cta;" ::: "memory"); }
DEVI void fence_async_glob() { asm volatile("fence.proxy.async.global;" ::: "memory"); }
DEVI unsigned ld_rlx(const unsigned* p) { unsigned v; asm volatile("ld.relaxed.gpu.global.u32 %0, [%1];" : "=r"(v) : "l"(p) : "memory"); return v; }
DEVI void st_rlx(unsigned* p, unsigned v) { asm volatile("st.relaxed.gpu.global.u32 [%0], %1;" :: "l"(p), "r"(v) : "memory"); }
DEVI uint2 ldg_stream(const uint2* p) { uint2 v; asm volatile("ld.global.nc.L1::no_allocate.v2.u32 {%0, %1}, [%2];" : "=r"(v.x), "=r"(v.y) : "l"(p)); return v; }
DEVI void fence_rel() { asm volatile("fence.release.gpu;" ::: "memory"); }
DEVI uint4 ld_ll(const uint4* p) {
  uint4 v;
  asm volatile("{\n.reg .b128 t;\n.reg .b64 a, b;\nld.relaxed.gpu.global.b128 t, [%4];\nmov.b128 {a, b}, t;\nmov.b64 {%0, %1}, a;\nmov.b64 {%2, %3}, b;\n}"
               : "=r"(v.x), "=r"(v.y), "=r"(v.z), "=r"(v.w) : "l"(p) : "memory");
  return v;
}
DEVI void st_ll(uint4* p, uint32_t x, uint32_t y, uint32_t z, uint32_t w) {
  asm volatile("{\n.reg .b128 t;\n.reg .b64 a, b;\nmov.b64 a, {%1, %2};\nmov.b64 b, {%3, %4};\nmov.b128 t, {a, b};\nst.relaxed.gpu.global.b128 [%0], t;\n}"
               :: "l"(p), "r"(x), "r"(y), "r"(z), "r"(w) : "memory");
}
#define SPIN_MAX 0x1000000
DEVI uint4 poll_ll(const uint4* p, uint32_t mask, uint32_t tag) {
  uint4 v; int it = 0;
  do { v = ld_ll(p); if (++it > SPIN_MAX) __trap(); } while (!__all_sync(0xffffffffu, (v.w & mask) == tag));
  return v;
}
DEVI void poll_ll2(const uint4* p, const uint4* q, uint32_t mask, uint32_t tag, uint4& a, uint4& b) {
  int it = 0;
  do { a = ld_ll(p); b = ld_ll(q); if (++it > SPIN_MAX) __trap(); } while (!__all_sync(0xffffffffu, (a.w & mask) == tag && (b.w & mask) == tag));
}
DEVI void bar_sync(int id, int n) { asm volatile("bar.sync %0, %1;" :: "r"(id), "r"(n) : "memory"); }
DEVI void bar_arrive(int id, int n) { asm volatile("bar.arrive %0, %1;" :: "r"(id), "r"(n) : "memory"); }
DEVI void wg_fence() { asm volatile("wgmma.fence.sync.aligned;" ::: "memory"); }
DEVI void wg_commit() { asm volatile("wgmma.commit_group.sync.aligned;" ::: "memory"); }
template<int N> DEVI void wg_wait() { asm volatile("wgmma.wait_group.sync.aligned %0;" :: "n"(N) : "memory"); }
template<int N> DEVI void reg_inc() { asm volatile("setmaxnreg.inc.sync.aligned.u32 %0;" :: "n"(N)); }
template<int N> DEVI void reg_dec() { asm volatile("setmaxnreg.dec.sync.aligned.u32 %0;" :: "n"(N)); }
DEVI float ex2f(float x) { float y; asm("ex2.approx.ftz.f32 %0, %1;" : "=f"(y) : "f"(x)); return y; }
DEVI uint32_t pack_bf16(float lo, float hi) { uint32_t r; asm("cvt.rn.bf16x2.f32 %0, %1, %2;" : "=r"(r) : "f"(hi), "f"(lo)); return r; }
DEVI float bf_lo(uint32_t v) { return __uint_as_float(v << 16); }
DEVI float bf_hi(uint32_t v) { return __uint_as_float(v & 0xffff0000u); }
DEVI float bf_round(float x) { return bf_lo(pack_bf16(x, 0.f)); }
DEVI void stsm_x4(uint32_t addr, uint32_t a, uint32_t b, uint32_t c, uint32_t d) {
  asm volatile("stmatrix.sync.aligned.m8n8.x4.shared.b16 [%0], {%1,%2,%3,%4};" :: "r"(addr), "r"(a), "r"(b), "r"(c), "r"(d) : "memory");
}
DEVI void ldsm_x4(uint32_t addr, uint32_t& a, uint32_t& b, uint32_t& c, uint32_t& d) {
  asm volatile("ldmatrix.sync.aligned.m8n8.x4.shared.b16 {%0,%1,%2,%3}, [%4];" : "=r"(a), "=r"(b), "=r"(c), "=r"(d) : "r"(addr) : "memory");
}
DEVI uint4 lds128(uint32_t a) { uint4 v; asm volatile("ld.shared.v4.u32 {%0,%1,%2,%3}, [%4];" : "=r"(v.x), "=r"(v.y), "=r"(v.z), "=r"(v.w) : "r"(a) : "memory"); return v; }
DEVI void sts128(uint32_t a, uint4 v) { asm volatile("st.shared.v4.u32 [%0], {%1,%2,%3,%4};" :: "r"(a), "r"(v.x), "r"(v.y), "r"(v.z), "r"(v.w) : "memory"); }
DEVI float2 lds64f(uint32_t a) { float2 v; asm volatile("ld.shared.v2.f32 {%0,%1}, [%2];" : "=f"(v.x), "=f"(v.y) : "r"(a) : "memory"); return v; }
DEVI void sts64f(uint32_t a, float x, float y) { asm volatile("st.shared.v2.f32 [%0], {%1,%2};" :: "r"(a), "f"(x), "f"(y) : "memory"); }
DEVI uint32_t lds32(uint32_t a) { uint32_t v; asm volatile("ld.shared.u32 %0, [%1];" : "=r"(v) : "r"(a) : "memory"); return v; }
DEVI float lds32f(uint32_t a) { return __uint_as_float(lds32(a)); }
DEVI void sts32(uint32_t a, uint32_t v) { asm volatile("st.shared.u32 [%0], %1;" :: "r"(a), "r"(v) : "memory"); }
DEVI void sts32f(uint32_t a, float v) { sts32(a, __float_as_uint(v)); }
DEVI void sts16(uint32_t a, uint32_t v) { asm volatile("st.shared.u16 [%0], %1;" :: "r"(a), "h"((unsigned short)v) : "memory"); }
template<int N> DEVI void keep(float (&d)[N]) {
  #pragma unroll
  for (int i = 0; i < N; i++) asm volatile("" : "+f"(d[i]) :: "memory");
}
template<int N> DEVI void keep(uint32_t (&d)[N]) {
  #pragma unroll
  for (int i = 0; i < N; i++) asm volatile("" : "+r"(d[i]) :: "memory");
}
template<uint32_t HI> DEVI uint64_t mkd(uint32_t lo) { uint64_t r; asm("mov.b64 %0, {%1, %2};" : "=l"(r) : "r"(lo), "n"(HI)); return r; }
constexpr uint32_t HI128 = (1u << 30) | (1024 >> 4), HI64 = (2u << 30) | (512 >> 4);
#define VOFF(x) ((uint32_t)(x) * (uint32_t)(1 - 65536))
DEVI bool elect() { uint32_t p; asm volatile("{\n.reg .pred q;\nelect.sync _|q, 0xffffffff;\nselp.u32 %0, 1, 0, q;\n}" : "=r"(p)); return p; }
DEVI void warp_signal(uint32_t bar) { fence_async_smem(); __syncwarp(); if (elect()) mbar_arrive(bar); }

struct Scratch {
  uint4 kv[128][8][512];
  uint4 o[8][2][8][2][1024];
  uint4 x[8][16][2048];
  uint4 zero[1024];
  uint4 statP[8][2048];
  uint4 statF[2048];
  uint4 csP[16][8][96];
  uint4 best[8][16];
  uint4 row[16][256];
  uint4 yP[128][112][2];
  uint4 x2[8][256];
  uint4 patch[1024];
  unsigned flagKV[128][32];
  unsigned flagO[8][2][2][32];
  unsigned flagX[8][32];
  unsigned epoch;
};
static_assert(offsetof(Scratch, flagO) % 256 == 0, "");
__device__ __align__(1024) Scratch g_scr;
#define PROFT(cond, slot)
#define PROFW(cond, slot)
#define PROFD(cond, slot)
#define PROFX(cond, slot)
#define PROFY(cond, slot)

constexpr uint32_t SB0 = 65536, HOLE = 90112, SA2 = 98304, SB1 = 131072, SB2 = 155648, STG = 180224;
constexpr uint32_t KVA = 98304, KVB = 0, QO = 65536;
constexpr uint32_t MISC = 229376, CS = MISC, ONES = MISC + 768, BARS = MISC + 1792, INFO = MISC + 2208, WR = MISC + 2224, X2SEG = MISC + 2736, INFO2 = MISC + 2992;
constexpr uint32_t PAR = HOLE, HV = HOLE + 2048, RED = HOLE + 6144, PATCH = 196608;
constexpr uint32_t SMEM_BYTES = 232448;
enum { B_FULLQ = 0, B_EMPTYQ = 3, B_FULLW = 6, B_EMPTYW = 12, B_HAFREE = 18, B_OFREE = 20,
       B_XFREE = 21,
       B_KVRDY = 23, B_ORDY = 27, B_XRDY = 35, B_STGE = 39,
       B_KVFULL = 42, B_RES = 46, B_PAR = 47, B_STG = 48, B_PFREE = 51, B_COUNT = 52 };
#define BAR(x) (sb + BARS + 8 * (x))
DEVI uint32_t qa_off(int s) { return s == 2 ? SA2 : (uint32_t)s * 32768u; }
DEVI uint32_t qb_off(int s) { return s == 0 ? SB0 : (s == 1 ? SB1 : SB2); }
DEVI int kb_order(int bc, int n) {
  const int e = n < 9 ? n - 2 : n - 9;
  return n < 2 ? 2 * bc + n : 2 * (((e < 4 ? e + 4 : e - 4 + (e - 4 >= (bc & 3))) + (bc & 4)) & 7) + (n >= 9);
}
DEVI uint32_t w_off(int s) { return (uint32_t)((0x104365 >> (4 * s)) & 7) * 32768u; }
DEVI uint32_t w_par(int n, int s, int L) { return ((n >= 6 && n < 12) ^ (s < 4 && L)); }

struct Params {
  CUtensorMap mX, mXh, mWq, mWo, mWg, mWu, mWp, mWd;
  const bf16 *x0, *wqkv, *wo, *wr, *wg, *wu, *wd;
  bf16* out;
  Scratch* g;
  unsigned map[128];
};
#define BID ((int)(P.map[blockIdx.x] & 255))
#define FID ((int)(P.map[blockIdx.x] >> 8))
DEVI uint32_t uni(uint32_t v) { return __shfl_sync(0xffffffffu, v, 0); }
#define PQ_N 8
#define PQ_T 700
#define PF0_N 10
#define PF0_T 1600
#define PF1_E 24
#define PF1_T 900
#define POL_Q1 POL_NORMAL
#define POL_X POL_NORMAL
#define PFA0_BAR 3
#define PFA1_BAR 0
#define PFA0_M 0
#define PFA1_M 0
#define PFA0_T 900
#define PFA1_T 700
#define PF1_S PF0_N
#define PF1_D 0
#define POL_G POL_NORMAL
#define POL_U POL_FIRST
#define POL_D POL_FIRST
#define JQ_N 6
#define WDSRC (P.wd + (size_t)min(fid, 111) * 32768)
#define WD_N 4
#define THR_N 6
#define POL_Q0 POL_NORMAL
constexpr float LN_EPS = 1e-5f;
constexpr float QSCALE = 0.17677669529663687f * 1.4426950408889634f;

DEVI void fma8(float (&a)[8], uint4 v, float h) {
  a[0] = fmaf(bf_lo(v.x), h, a[0]); a[1] = fmaf(bf_hi(v.x), h, a[1]); a[2] = fmaf(bf_lo(v.y), h, a[2]); a[3] = fmaf(bf_hi(v.y), h, a[3]);
  a[4] = fmaf(bf_lo(v.z), h, a[4]); a[5] = fmaf(bf_hi(v.z), h, a[5]); a[6] = fmaf(bf_lo(v.w), h, a[6]); a[7] = fmaf(bf_hi(v.w), h, a[7]);
}
DEVI void gemv8(float (&a)[8], uint32_t wa, uint32_t ha, uint32_t hs) {
  #pragma unroll
  for (int n = 0; n < 8; n += 2) {
    uint4 v0 = lds128(wa + n * 512), v1 = lds128(wa + n * 512 + 512);
    float h0 = lds32f(ha), h1 = lds32f(ha + hs);
    ha += 2 * hs;
    fma8(a, v0, h0); fma8(a, v1, h1);
  }
}
DEVI uint4 ldsv128(uint32_t a) { uint4 v; asm volatile("ld.volatile.shared.v4.u32 {%0,%1,%2,%3}, [%4];" : "=r"(v.x), "=r"(v.y), "=r"(v.z), "=r"(v.w) : "r"(a) : "memory"); return v; }
DEVI float ldsv32f(uint32_t a) { float v; asm volatile("ld.volatile.shared.f32 %0, [%1];" : "=f"(v) : "r"(a) : "memory"); return v; }
DEVI uint32_t clk() { uint32_t t; asm volatile("mov.u32 %0, %%clock;" : "=r"(t)); return t; }
DEVI int fresh_tid() { int t; asm volatile("mov.u32 %0, %%tid.x;" : "=r"(t)); return t & 127; }
DEVI float fold8(const float (&a)[8]) {
  const int lane = threadIdx.x & 31;
  const bool u = lane & 16, v = lane & 8, x = lane & 4;
  float b0 = (u ? a[4] : a[0]) + __shfl_xor_sync(0xffffffffu, u ? a[0] : a[4], 16), b1 = (u ? a[5] : a[1]) + __shfl_xor_sync(0xffffffffu, u ? a[1] : a[5], 16);
  float b2 = (u ? a[6] : a[2]) + __shfl_xor_sync(0xffffffffu, u ? a[2] : a[6], 16), b3 = (u ? a[7] : a[3]) + __shfl_xor_sync(0xffffffffu, u ? a[3] : a[7], 16);
  float c0 = (v ? b2 : b0) + __shfl_xor_sync(0xffffffffu, v ? b0 : b2, 8), c1 = (v ? b3 : b1) + __shfl_xor_sync(0xffffffffu, v ? b1 : b3, 8);
  return (x ? c1 : c0) + __shfl_xor_sync(0xffffffffu, x ? c0 : c1, 4);
}
DEVI float swiglu(float g, float u) { g = bf_round(g); return bf_round(bf_round(__fdividef(g, 1.f + __expf(-g))) * bf_round(u)); }

DEVI void qk_issue(float (&s)[32], uint32_t qd, uint32_t kd) {
  wgmma_ss_n64<0>(s, mkd<HI64>(qd), mkd<HI64>(kd), 0);
  wgmma_ss_n64<0>(s, mkd<HI64>(qd + 2), mkd<HI64>(kd + 2), 1);
}
DEVI void pv_issue(float (&o)[20], const uint32_t (&p)[16], uint32_t vd, bool accum) {
  #pragma unroll
  for (int ks = 0; ks < 4; ks++)
    wgmma_rs_n40<1>(o, p[ks * 4], p[ks * 4 + 1], p[ks * 4 + 2], p[ks * 4 + 3], mkd<HI64>(vd + VOFF(ks * 64)), ks ? 1 : accum);
}
template<int J0, int J1> DEVI void exp_pack(const float (&s)[32], uint32_t (&p)[16]) {
  #pragma unroll
  for (int j = J0; j < J1; j++) p[j] = pack_bf16(ex2f(s[2 * j]), ex2f(s[2 * j + 1]));
}
DEVI bool attn_finish(const float (&o)[20], uint32_t st, uint32_t bar) {
  const float lo = 5.421010862427522e-20f, hi = 1.8446744073709552e19f;
  bool ok = o[16] >= lo && o[16] <= hi && o[18] >= lo && o[18] <= hi;
  if (!__all_sync(0xffffffffu, ok)) return false;
  float i0, i1; asm("rcp.approx.ftz.f32 %0, %1;" : "=f"(i0) : "f"(o[16])); asm("rcp.approx.ftz.f32 %0, %1;" : "=f"(i1) : "f"(o[18]));
  #pragma unroll
  for (int h = 0; h < 2; h++) {
    stsm_x4(st ^ (h << 5),
      pack_bf16(o[8 * h] * i0, o[8 * h + 1] * i0), pack_bf16(o[8 * h + 2] * i1, o[8 * h + 3] * i1),
      pack_bf16(o[8 * h + 4] * i0, o[8 * h + 5] * i0), pack_bf16(o[8 * h + 6] * i1, o[8 * h + 7] * i1));
  }
  warp_signal(bar);
  return true;
}
DEVI void attn_exact(uint32_t st, uint32_t kv, int t, bool hasprev, uint32_t bar) {
  const int lane = threadIdx.x & 31;
  #pragma unroll 1
  for (int row = ((threadIdx.x >> 5) & 3) * 16, n = 0; n < 16; n++, row++) {
    const int k1 = 256 + t * 64 + row;
    float m = -INFINITY, l = 0.f, o = 0.f;
    #pragma unroll 1
    for (int k0 = hasprev ? k1 - 255 : 256; k0 <= k1; k0 += 32) {
      const int k = min(k0 + lane, k1), r = k & 63;
      float sc = 0.f;
      #pragma unroll 1
      for (int c = 0; c < 16; c++) {
        uint32_t a = lds32(st + row * 64 + ((c * 4) ^ ((row & 6) << 3))), b = lds32(kv + (k >> 6) * 8192 + r * 64 + ((c * 4) ^ ((r & 6) << 3)));
        sc = fmaf(bf_lo(a), bf_lo(b), fmaf(bf_hi(a), bf_hi(b), sc));
      }
      float mn = fmaxf(m, sc);
      #pragma unroll 1
      for (int x = 16; x; x >>= 1) mn = fmaxf(mn, __shfl_xor_sync(0xffffffffu, mn, x));
      const float al = ex2f(m - mn), pr = ex2f(sc - mn);
      m = mn; l *= al; o *= al;
      #pragma unroll 1
      for (int q = k0; q <= min(k0 + 31, k1); q++) {
        const float z = __shfl_sync(0xffffffffu, pr, q - k0);
        uint32_t b = lds32(kv + (q >> 6) * 8192 + 4096 + (q & 63) * 64 + (((lane >> 1) * 4) ^ ((q & 6) << 3)));
        l += z; o = fmaf(z, (lane & 1) ? bf_hi(b) : bf_lo(b), o);
      }
    }
    __syncwarp();
    sts16(st + row * 64 + ((lane * 2) ^ ((row & 6) << 3)), pack_bf16(__fdividef(o, l), 0.f));
  }
  warp_signal(bar);
}

DEVI void merge_tri(float (&s)[32], const float (&sx)[32], int tdiag) {
  #pragma unroll
  for (int e = 0; e < 32; e++) { int c = 8 * (e >> 2) + (e & 1) - 8 * ((e >> 1) & 1); s[e] = (c > tdiag) ? s[e] : sx[e]; }
}
DEVI void split_tri(uint32_t (&p)[16], uint32_t (&px)[16], const uint32_t (&msk)[9]) {
  #pragma unroll
  for (int e = 0; e < 16; e++) { const uint32_t m = msk[(e >> 1) - (e & 1) + 1]; px[e] = p[e] & ~m; p[e] &= m; }
}

template<int J0> DEVI void qkv_store(const float (&a)[96], float p0, float p1, uint32_t d) {
  #pragma unroll
  for (int hh = 0; hh < 2; hh++) {
    const int j = 4 * (J0 + 2 * hh);
    stsm_x4(d ^ (hh << 5), pack_bf16(a[j] * p0, a[j + 1] * p0), pack_bf16(a[j + 2] * p1, a[j + 3] * p1),
                           pack_bf16(a[j + 4] * p0, a[j + 5] * p0), pack_bf16(a[j + 6] * p1, a[j + 7] * p1));
  }
}
DEVI void mean_step(float (&a)[96], float m0, float m1, uint32_t cd, bool z) {
  const uint32_t u0 = z ? 0u : __float_as_uint(m0), u1 = z ? 0u : __float_as_uint(m1);
  uint32_t ma[4] = {__byte_perm(u0, 0u, 0x1010), __byte_perm(u1, 0u, 0x1010), __byte_perm(u0, 0u, 0x3232), __byte_perm(u1, 0u, 0x3232)};
  keep(ma);
  wg_fence();
  wgmma_rs_n192<1>(a, ma[0], ma[1], ma[2], ma[3], mkd<2>(cd), 1);
  wg_commit();
}

template<bool FIRST> DEVI void qkv_block(float (&aX)[96], float (&aY)[96], uint32_t sb16, int s, int tX, int tY) {
  uint32_t a16 = sb16 + (qa_off(s) >> 4), b16 = (sb16 + (qb_off(s) >> 4)) | ((8192u >> 4) << 16);
  uint32_t ax = (a16 + tX * 512) | 0x10000u, ay = (a16 + tY * 512) | 0x10000u;
  wg_fence();
  #pragma unroll
  for (int ks = 0; ks < 4; ks++) {
    wgmma_ss_n192<1>(aX, mkd<HI128>(ax + ks * 2), mkd<HI128>(b16 + ks * 128), !(FIRST && ks == 0));
    wgmma_ss_n192<1>(aY, mkd<HI128>(ay + ks * 2), mkd<HI128>(b16 + ks * 128), !(FIRST && ks == 0));
  }
  wg_commit();
}
template<bool FIRST> DEVI void wo_block(float (&acc)[64], uint32_t sb16, int s, int wg) {
  uint32_t a16 = (sb16 + (w_off(s) >> 4) + wg * 256) | 0x10000u, b16 = (sb16 + (w_off(s) >> 4) + 1024) | ((8192u >> 4) << 16);
  wg_fence();
  #pragma unroll
  for (int ks = 0; ks < 4; ks++)
    wgmma_ss_n128<1>(acc, mkd<HI64>(a16 + (ks >> 1) * 512 + (ks & 1) * 2), mkd<HI128>(b16 + ks * 128), !(FIRST && ks == 0));
  wg_commit();
}
DEVI void consumer(const Params& P, uint32_t sb, int wg) {
  #define IDS const int tid = fresh_tid(), lane = tid & 31, w = tid >> 5
  const uint32_t ids = uni(P.map[blockIdx.x]);
  const int bi = (ids >> 4) & 7, rh = ids & 1, bc = (ids & 15) >> 1, fid = ids >> 8;
  const int tX = 3 - wg, tY = wg;
  const uint32_t sb16 = (sb & 0x3FFFFu) >> 4;
  #pragma unroll 1
  for (int L = 0; L < 2; L++) {
    {
      float aX[96], aY[96];
      const bool lead = fresh_tid() == 0;
      if (L) mbar_wait(BAR(B_XRDY + wg * 2 + 1), 0);
      mbar_wait(BAR(B_FULLQ), 0);
      PROFW(threadIdx.x == 0, L * 8 + 1);
      qkv_block<true>(aX, aY, sb16, 0, tX, tY);
      #pragma unroll 1
      for (int n = 1, s = 1, ps = 0, ph = 0; n < 16; n++) {
        mbar_wait(BAR(B_FULLQ + s), ph ^ (s ? L : 0));
        PROFD(threadIdx.x == 0 && L && (n == 2 || n == 3 || n == 7 || n == 11 || n == 15), n == 2 ? 48 : 49 + (n >> 2));
        qkv_block<false>(aX, aY, sb16, s, tX, tY);
        wg_wait<1>(); if (lead) mbar_arrive(BAR(B_EMPTYQ + ps));
        ps = s; if (s == 2) { s = 0; ph ^= 1; } else s++;
      }
      mbar_wait(BAR(B_PAR), L);
      IDS;
      const uint32_t pa = sb + PAR + (w * 16 + (lane >> 2)) * 8;
      float2 p0 = lds64f(pa + tX * 512), p1 = lds64f(pa + tX * 512 + 64), p2 = lds64f(pa + tY * 512), p3 = lds64f(pa + tY * 512 + 64);
      mean_step(aX, p0.y, p1.y, sb16 + (CS >> 4), lane & 3);
      const int prow = (int)lds32(sb + INFO) - bi * 256;
      mbar_wait(BAR(B_EMPTYQ + 1), L); mbar_wait(BAR(B_EMPTYQ + 2), L);
      wg_wait<0>(); keep(aX); keep(aY);
      mean_step(aY, p2.y, p3.y, sb16 + (CS >> 4), lane & 3);
      if (tid == 0) mbar_arrive(BAR(B_EMPTYQ));
      PROFW(threadIdx.x == 0, L * 8 + 2);
      const int srow = w * 16 + (lane & 15);
      const uint32_t x0 = sb + srow * 64 + (((lane >> 4) ^ ((srow >> 1) & 3)) << 4), xX = x0 + (4 + tX) * 8192, xY = x0 + (4 + tY) * 8192;
      const bool pmine = (prow >> 4) == tX * 4 + w || (prow >> 4) == tY * 4 + w;
      const uint32_t poff = sb + (prow & 63) * 64 + (((lane & 3) ^ ((prow >> 1) & 3)) << 4);
      qkv_store<8>(aX, p0.x, p1.x, xX + KVA); qkv_store<16>(aX, p0.x, p1.x, xX + KVA + 4096);
      wg_wait<0>(); keep(aY);
      qkv_store<8>(aY, p2.x, p3.x, xY + KVA); qkv_store<16>(aY, p2.x, p3.x, xY + KVA + 4096);
      if (pmine) { __syncwarp(); if (lane < 8) sts128(poff + KVA + (4 + (prow >> 6)) * 8192 + (lane >> 2) * 4096, lds128(sb + PATCH + 128 + (lane >> 2) * 128 + (lane & 3) * 16)); }
      warp_signal(BAR(B_KVRDY + wg * 2));
      qkv_store<12>(aX, p0.x, p1.x, xX + KVB); qkv_store<20>(aX, p0.x, p1.x, xX + KVB + 4096);
      qkv_store<12>(aY, p2.x, p3.x, xY + KVB); qkv_store<20>(aY, p2.x, p3.x, xY + KVB + 4096);
      p0.x *= QSCALE; p1.x *= QSCALE; p2.x *= QSCALE; p3.x *= QSCALE;
      mbar_wait(BAR(B_EMPTYQ), 1);
      qkv_store<0>(aX, p0.x, p1.x, x0 + QO + tX * 4096); qkv_store<4>(aX, p0.x, p1.x, x0 + QO + 16384 + tX * 4096);
      qkv_store<0>(aY, p2.x, p3.x, x0 + QO + tY * 4096); qkv_store<4>(aY, p2.x, p3.x, x0 + QO + 16384 + tY * 4096);
      if (pmine) {
        __syncwarp();
        if (lane < 16) sts128(poff + (lane < 8 ? QO + (lane >> 2) * 16384 + (prow >> 6) * 4096 : KVB + (3 + (prow >> 6)) * 8192 + (lane >> 2) * 4096),
                              lds128(sb + PATCH + (lane < 8 ? lane * 16 : (lane >> 2) * 128 - 64 + (lane & 3) * 16)));
      }
      warp_signal(BAR(B_KVRDY + wg * 2 + 1));
      bar_sync(1, 256);
    }
    PROFW(threadIdx.x == 0, L * 8 + 3);
    {
      IDS;
      float s0[32], s1[32], sx[32], o[20], op[20];
      uint32_t p0[16], p1[16], px[16], msk[9];
      const int tdiag = w * 16 + (lane >> 2) - 2 * (lane & 3);
      #pragma unroll
      for (int e = 0; e < 9; e++) msk[e] = ((8 * e - 8 > tdiag) ? 0xFFFFu : 0u) | ((8 * e - 7 > tdiag) ? 0xFFFF0000u : 0u);
      keep(msk);
      const uint32_t ones = (sb16 + (ONES >> 4)) << 16;
      const uint32_t qX = (sb16 + (QO >> 4) + tX * 256) | 0x10000u, qY = (sb16 + (QO >> 4) + tY * 256) | 0x10000u;
      const uint32_t kXB = (sb16 + (KVB >> 4) + tX * 512) | 0x10000u;
      uint32_t redo = 0;
      const uint32_t ost = sb + QO + (w * 16 + (lane & 15)) * 64 + (((lane >> 4) ^ ((lane >> 1) & 3)) << 4);
      #define QK(s, q, k) do { wg_fence(); qk_issue(s, q, k); wg_commit(); } while (0)
      #define QK2(q, k) do { wg_fence(); qk_issue(s1, q, k); qk_issue(sx, q, (k) + 2048); wg_commit(); } while (0)
      #define PV(o, p, v, b, acc) do { wg_fence(); pv_issue(o, p, (v) + VOFF((b) * 512), acc); wg_commit(); } while (0)
      #define PV2(v0, v4) do { wg_fence(); pv_issue(o, p1, v0, true); pv_issue(o, px, (v4) + VOFF(2048), true); wg_commit(); } while (0)
      {
        const uint32_t kXA = kXB + ((KVA - KVB) >> 4), vB = VOFF((kXB & 0xffffu) + 256) + ones, vA = vB + VOFF((KVA - KVB) >> 4);
        QK(s0, qX, kXA + 1536);
        wg_wait<0>(); keep(s0);
        QK(s1, qX, kXA + 1024);
        exp_pack<0, 16>(s0, p0);
        PV(o, p0, vA, 3, false);
        wg_wait<1>(); keep(s1);
        QK(s0, qX + 1024, kXB + 1536);
        exp_pack<0, 16>(s1, p1);
        PV(o, p1, vA, 2, true);
        wg_wait<1>(); keep(s0); keep(p0);
        QK(s1, qX + 1024, kXB + 1024);
        exp_pack<0, 16>(s0, p0);
        PV(op, p0, vB, 3, false);
        wg_wait<1>(); keep(s1); keep(p1); keep(o);
        exp_pack<0, 8>(s1, p1);
        mbar_wait(BAR(B_KVFULL), L);
        QK(s0, qX, kXA + 512);
        exp_pack<8, 16>(s1, p1);
        PV(op, p1, vB, 2, true);
        wg_wait<0>(); keep(s0); keep(p0); keep(p1); keep(op);
      }
      #pragma unroll 1
      for (int h = 0; h < 2; h++) {
        const uint32_t kb16 = sb16 + ((h ? KVB : KVA) >> 4), kX = (kb16 + tX * 512) | 0x10000u, kY = (kb16 + tY * 512) | 0x10000u;
        const uint32_t qx = qX + h * 1024, qy = qY + h * 1024;
        const uint32_t onesP = bi ? ones : (kb16 + 1984) << 16;
        const uint32_t vX = VOFF(kb16 + tX * 512 + 256), vY = VOFF(kb16 + tY * 512 + 256);
        QK2(qx, kX);
        exp_pack<0, 16>(s0, p0);
        PV(o, p0, vX + (wg ? onesP : ones), 1, true);
        wg_wait<1>(); keep(s1); keep(sx);
        merge_tri(s1, sx, tdiag);
        QK(s0, qy, kY + 1536);
        exp_pack<0, 16>(s1, p1); split_tri(p1, px, msk);
        PV2(vX + onesP, vX + ones);
        wg_wait<1>(); keep(s0); keep(p0);
        QK(s1, qy, kY + 1024);
        exp_pack<0, 10>(s0, p0);
        wg_wait<1>(); keep(o); keep(p1); keep(px);
        if (!attn_finish(o, ost + (h * 4 + tX) * 4096, BAR(B_ORDY + wg * 4 + h * 2))) redo |= 1u << (h * 2);
        exp_pack<10, 16>(s0, p0);
        PV(o, p0, vY + (wg ? ones : onesP), 3, false);
        wg_wait<1>(); keep(s1);
        exp_pack<0, 8>(s1, p1);
        mbar_wait(BAR(B_KVFULL + h * 2 + 1), L);
        QK(s0, qy, kY + 512);
        exp_pack<8, 16>(s1, p1);
        PV(o, p1, vY + onesP, 2, true);
        wg_wait<1>(); keep(s0); keep(p0);
        QK2(qy, kY);
        exp_pack<0, 16>(s0, p0);
        PV(o, p0, vY + onesP, 1, true);
        wg_wait<1>(); keep(s1); keep(sx); keep(p1);
        merge_tri(s1, sx, tdiag);
        exp_pack<0, 8>(s1, p1);
        mbar_wait(BAR(B_KVFULL + 2), L);
        QK(s0, h ? qy : qX + 1024, kXB + 512);
        exp_pack<8, 16>(s1, p1); split_tri(p1, px, msk);
        PV2(vY + onesP, vY + ones);
        wg_wait<0>(); keep(o); keep(s0); keep(p0); keep(p1); keep(px);
        if (!attn_finish(o, ost + (h * 4 + tY) * 4096, BAR(B_ORDY + wg * 4 + h * 2 + 1))) redo |= 2u << (h * 2);
        #pragma unroll
        for (int e = 0; e < 20; e++) o[e] = op[e];
      }
      #undef QK
      #undef QK2
      #undef PV
      #undef PV2
      if (redo) {
        #pragma unroll 1
        for (int u = 0; u < 4; u++) if ((redo >> u) & 1) {
          const int h = u >> 1, t = (u & 1) ? tY : tX;
          attn_exact(sb + QO + (h * 4 + t) * 4096, sb + (h ? KVB : KVA), t, bi > 0, BAR(B_ORDY + wg * 4 + u));
        }
      }
    }
    PROFW(threadIdx.x == 0, L * 8 + 4);
    {
      IDS;
      const int t256 = wg * 128 + tid;
      float acc[64];
      const int tt = wg ^ rh;
      const int grow = bi * 256 + rh * 128 + tt * 64 + w * 16 + (lane >> 2);
      float al0 = 1.f, be0 = 0.f, al1 = 1.f, be1 = 0.f;
      const int idx0 = (int)lds32(sb + INFO);
      const uint32_t tag = lds32(sb + INFO + 8) + L;
      uint4* const sp = &P.g->statP[bc][grow + (lane & 1) * 8];
      uint4* const yp = &P.g->yP[t256 >> 1][min(fid, 111)][t256 & 1];
      mbar_wait(BAR(B_FULLW), L);
      PROFW(t256 == 0, L * 8 + 5);
      wo_block<true>(acc, sb16, 0, tt);
      if (!(lane & 2)) st_ll(sp, 0u, 0u, 0u, 0u);
      uint4 fa = make_uint4(0u, 0u, 0u, 0u), fb = fa;
      uint2 wd[32];
      if (L) {
        if (fid < 112) st_ll(yp, 0u, 0u, 0u, 0u);
        fa = ld_ll(&P.g->statF[grow]); fb = ld_ll(&P.g->statF[grow + 8]);
      }
      #pragma unroll
      for (int n = 0; n < 32; n++) wd[n] = make_uint2(0u, 0u);
      #pragma unroll 1
      for (int n = 1, q = 1, pq = 0; n < 16; n++) {
        mbar_wait(BAR(B_FULLW + q), w_par(n, q, L));
        PROFD(t256 == 0 && !L && (n == 4 || n == 7 || n == 8 || n == 12), (n == 7 ? 63 : 41 + (n >> 2)));
        wo_block<false>(acc, sb16, q, tt);
        if (L && n == WD_N) {
          const uint2* src = (const uint2*)(WDSRC) + t256;
          #pragma unroll
          for (int e = 0; e < 32; e++) wd[e] = ldg_stream(src + e * 256);
        }
        wg_wait<1>(); if (tid == 0) mbar_arrive(BAR(B_EMPTYW + pq));
        pq = q; q = q == 5 ? 0 : q + 1;
      }
      if (L) {
        float r0 = rsqrtf(__uint_as_float(fa.y) + LN_EPS), r1 = rsqrtf(__uint_as_float(fb.y) + LN_EPS);
        if (grow != idx0) { al0 = 1.f + r0; be0 = -__uint_as_float(fa.x) * r0; }
        if (grow + 8 != idx0) { al1 = 1.f + r1; be1 = -__uint_as_float(fb.x) * r1; }
      }
      mbar_wait(BAR(B_RES), L);
      const int srow = tt * 64 + w * 16 + (lane & 15);
      const uint32_t ra = sb + rh * 16384 + srow * 128, sw = ((lane >> 4) ^ (srow & 7)) << 4;
      if ((idx0 >> 4) == (grow >> 4)) {
        int r = idx0 & 127;
        if (lane < 16) sts128(sb + (lane >> 3) * 32768 + rh * 16384 + r * 128 + (((lane & 7) ^ (r & 7)) << 4), lds128(sb + X2SEG + lane * 16));
        __syncwarp();
      }
      uint32_t rs[32];
      #pragma unroll
      for (int jj = 0; jj < 8; jj++) ldsm_x4((ra + (jj >> 2) * 32768) + (sw ^ ((jj & 3) << 5)), rs[4 * jj], rs[4 * jj + 1], rs[4 * jj + 2], rs[4 * jj + 3]);
      float rf[64];
      #pragma unroll
      for (int e = 0; e < 32; e++) { rf[2 * e] = fmaf(bf_lo(rs[e]), (e & 1) ? al1 : al0, (e & 1) ? be1 : be0); rf[2 * e + 1] = fmaf(bf_hi(rs[e]), (e & 1) ? al1 : al0, (e & 1) ? be1 : be0); }
      keep(rf);
      mbar_wait(BAR(B_RES), L);
      wg_wait<0>(); keep(acc);
      if (tid == 0) mbar_arrive(BAR(B_EMPTYW + 3));
      PROFW(t256 == 0, L * 8 + 6);
      #pragma unroll
      for (int jj = 0; jj < 8; jj++) {
        float* a = acc + 8 * jj;
        #pragma unroll
        for (int e = 0; e < 8; e++) a[e] += rf[8 * jj + e];
        stsm_x4((ra + (jj >> 2) * 32768) + (sw ^ ((jj & 3) << 5)), pack_bf16(a[0], a[1]), pack_bf16(a[2], a[3]), pack_bf16(a[4], a[5]), pack_bf16(a[6], a[7]));
        if ((jj & 3) == 3) warp_signal(BAR(B_XRDY + wg * 2 + (jj >> 2)));
      }
      {
        float s1a = 0.f, s2a = 0.f, da = 0.f, s1b = 0.f, s2b = 0.f, db = 0.f;
        #pragma unroll
        for (int j = 0; j < 16; j++) {
          const float* a = acc + 4 * j; float2 wv = lds64f(sb + WR + j * 32 + (lane & 3) * 8);
          s1a += a[0] + a[1]; s1b += a[2] + a[3];
          s2a = fmaf(a[0], a[0], s2a); s2b = fmaf(a[2], a[2], s2b); s2a = fmaf(a[1], a[1], s2a); s2b = fmaf(a[3], a[3], s2b);
          da = fmaf(a[0], wv.x, da); db = fmaf(a[2], wv.x, db); da = fmaf(a[1], wv.y, da); db = fmaf(a[3], wv.y, db);
        }
        bool odd = lane & 1;
        float u1 = (odd ? s1b : s1a) + __shfl_xor_sync(0xffffffffu, odd ? s1a : s1b, 1);
        float u2 = (odd ? s2b : s2a) + __shfl_xor_sync(0xffffffffu, odd ? s2a : s2b, 1);
        float u3 = (odd ? db : da) + __shfl_xor_sync(0xffffffffu, odd ? da : db, 1);
        u1 += __shfl_xor_sync(0xffffffffu, u1, 2); u2 += __shfl_xor_sync(0xffffffffu, u2, 2); u3 += __shfl_xor_sync(0xffffffffu, u3, 2);
        if (!(lane & 2)) st_ll(sp, __float_as_uint(u1), __float_as_uint(u2), __float_as_uint(u3), tag);
      }
      PROFW(t256 == 0, L * 8 + 7);
      if (L) {
        mbar_wait(BAR(B_PAR), 0);
        { float2 pa = lds64f(sb + PAR + (grow & 127) * 8), pb = lds64f(sb + PAR + (grow & 127) * 8 + 64); al0 = pa.x; be0 = pa.y; al1 = pb.x; be1 = pb.y; }
        #pragma unroll
        for (int j = 0; j < 16; j++) {
          rs[2 * j] = pack_bf16(fmaf(acc[4 * j], al0, be0), fmaf(acc[4 * j + 1], al0, be0));
          rs[2 * j + 1] = pack_bf16(fmaf(acc[4 * j + 2], al1, be1), fmaf(acc[4 * j + 3], al1, be1));
        }
        const int idx1 = (int)lds32(sb + INFO + 4);
        #pragma unroll
        for (int jj = 0; jj < 8; jj++) stsm_x4((ra + (jj >> 2) * 32768) + (sw ^ ((jj & 3) << 5)), rs[4 * jj], rs[4 * jj + 1], rs[4 * jj + 2], rs[4 * jj + 3]);
        __syncwarp();
        {
          const int r0 = (grow & ~15) + (lane >> 4), skip = idx1 - r0;
          const uint32_t a0 = sb + ((lane >> 3) & 1) * 32768 + (r0 & 255) * 128 + (((lane & 7) ^ (lane >> 4)) << 4);
          uint4* dst = (uint4*)(P.out + (size_t)r0 * 1024 + bc * 128) + (lane & 15);
          #pragma unroll
          for (int it = 0; it < 8; it++) { uint4 v = lds128((a0 + it * 256) ^ ((it & 3) << 5)); if (skip != 2 * it) dst[it * 256] = v; }
        }
        PROFW(t256 == 0, 16);
        if (fid < 112) {
          const int q = wg * 2 + (w >> 1);
          float g[8] = {0.f, 0.f, 0.f, 0.f, 0.f, 0.f, 0.f, 0.f};
          mbar_wait(BAR(B_FULLW + q), 0);
          bar_sync(3, 384);
          PROFW(t256 == 0, 29);
          #pragma unroll 1
          for (int n = 0; n < 4; n++) gemv8(g, sb + w_off(q) + (w & 1) * 16384 + n * 4096 + lane * 16, sb + HV + (q * 256 + n * 64 + (lane >> 2)) * 4, 32);
          sts32f(sb + PAR + 1024 + (q * 2 + (w & 1)) * 128 + ((lane & 3) * 8 + (lane >> 2)) * 4, fold8(g));
          bar_sync(1, 256);
          const uint32_t d = sb + PAR + 1024 + lane * 4;
          const float act = swiglu((lds32f(d) + lds32f(d + 256)) + (lds32f(d + 512) + lds32f(d + 768)),
                                   (lds32f(d + 128) + lds32f(d + 384)) + (lds32f(d + 640) + lds32f(d + 896)));
          PROFW(t256 == 0, 26);
          float y0 = 0.f, y1 = 0.f, y2 = 0.f, y3 = 0.f;
          sts32f(sb + HV + t256 * 4, act);
          __syncwarp();
          uint4 a4;
          #pragma unroll
          for (int n = 0; n < 32; n++) {
            if (!(n & 3)) a4 = lds128(sb + HV + (t256 >> 5) * 128 + n * 4);
            float av = __uint_as_float((n & 3) == 0 ? a4.x : ((n & 3) == 1 ? a4.y : ((n & 3) == 2 ? a4.z : a4.w)));
            y0 = fmaf(bf_lo(wd[n].x), av, y0); y1 = fmaf(bf_hi(wd[n].x), av, y1); y2 = fmaf(bf_lo(wd[n].y), av, y2); y3 = fmaf(bf_hi(wd[n].y), av, y3);
          }
          st_ll(yp, __float_as_uint(y0), __float_as_uint(y1), __float_as_uint(y2), (__float_as_uint(y3) & ~255u) | (lds32(sb + INFO + 12) + 1));
          PROFW(t256 == 0, 27);
        }
      }
    }
  }
  #undef IDS
}

DEVI void loader(const Params& P, uint32_t sb) {
  const int lane = threadIdx.x & 31;
  const int bid = uni(BID), bi = bid >> 4, bp = bid & 15, rh = bp & 1, bc = bp >> 1;
  uint32_t phq = 0, tag = 0;
  #pragma unroll 1
  for (int L = 0; L < 2; L++) {
    int s = 0;
    uint32_t rdy = 0;
    #pragma unroll 1
    for (int n = L ? 0 : 3; n < 16; n++) {
      int kb = L ? kb_order(bc, n) : n;
      mbar_wait(BAR(B_EMPTYQ + s), (phq >> s) & 1);
      phq ^= 1u << s;
      if (L) {
        if (n == 1) { mbar_wait(BAR(B_XRDY + 1), 0); mbar_wait(BAR(B_XRDY + 3), 0); }
        if (n >= 2) {
          if (((rdy >> (2 * kb)) & 3) != 3) {
            do { rdy = __ballot_sync(0xffffffffu, ld_rlx(&P.g->flagX[bi][lane]) == tag); } while (((rdy >> (2 * kb)) & 3) != 3);
            fence_async_glob();
          }
          if (n == 3 || n == 4) mbar_wait(BAR(B_XFREE + n - 3), 0);
        }
      }
      if (lane == 0) {
        mbar_expect_tx(BAR(B_FULLQ + s), L && n < 2 ? 40960 : 57344);
        if (L && n >= 2) bulk_g2s_h(sb + qa_off(s), P.g->x[bi][kb], 32768, BAR(B_FULLQ + s), POL_X);
        if (!L) tma_2d(sb + qa_off(s), &P.mX, kb * 64, bi * 256, BAR(B_FULLQ + s));
        tma_3d_h(sb + qb_off(s), &P.mWq, bp * 64, kb * 64, 0, BAR(B_FULLQ + s), L ? POL_Q1 : POL_Q0);
      }
      PROFY(L && lane == 0 && (n == 2 || n == 3 || n == 9), n == 9 ? 60 : 56 + n);
      if (L && n == 2) { mbar_wait(BAR(B_FULLQ), 0); mbar_wait(BAR(B_FULLQ + 1), 1); if (lane < 2) mbar_arrive_peer(BAR(B_XFREE + lane)); }
      s = (s == 2) ? 0 : s + 1;
    }
    for (int q = 0; q < 3; q++) mbar_wait(BAR(B_EMPTYQ + q), (phq >> q) & 1);
    mbar_wait(BAR(B_PAR), L);
    tag = lds32(sb + INFO + 8) + L;
    rdy = bi ? 0u : 0xffu;
    {
      const uint4* src = bi ? P.g->kv[bid - 16][0] : P.g->zero;
      const unsigned* fl = &P.g->flagKV[bid - 16][lane & 7];
      #pragma unroll 1
      for (int q = 0; q < 4; q++) {
        const int ch = (2 * q) ^ 2;
        if (lane == 0) mbar_expect_tx(BAR(B_KVFULL + q), 16384);
        if (((rdy >> ch) & 3) != 3) {
          do { rdy = __ballot_sync(0xffffffffu, ld_rlx(fl) == tag); } while (((rdy >> ch) & 3) != 3);
          fence_async_glob();
        }
        if (lane == 0) bulk_g2s_h(sb + ((ch >> 2) ? KVB : KVA) + (ch & 3) * 8192, src + (bi ? ch * 512 : 0), 16384, BAR(B_KVFULL + q));
        PROFY(!L && lane == 0 && bi && q != 2, 34 + (q + 1) / 2);
      }
    }
    mbar_wait(BAR(B_ORDY), L); mbar_wait(BAR(B_ORDY + 4), L);
    {
      const uint4* src = P.g->o[bi][0][0][rh];
      const unsigned* fl = &P.g->flagO[bi][0][rh][lane];
      rdy = 0;
      #pragma unroll 1
      for (int n = 0, q = 0; n < 16; n++, q = q == 5 ? 0 : q + 1) {
        const int j = n & 7;
        if (n == 8) { rdy = 0; src += 16384; fl += 64; }
        if (((rdy >> (4 * j)) & 15) != 15) {
          do { rdy = __ballot_sync(0xffffffffu, ld_rlx(fl) == tag); } while (((rdy >> (4 * j)) & 15) != 15);
          fence_async_glob();
        }
        if (n >= 2) mbar_wait(n < 6 ? BAR(B_HAFREE + (n >> 2)) : BAR(B_EMPTYW + q), n < 6 ? L : w_par(n - 6, q, L));
        if (n == THR_N) mbar_wait(BAR(B_OFREE), L);
        if (lane == 0) { mbar_expect_tx(BAR(B_FULLW + q), 16384); bulk_g2s_h(sb + w_off(q), src + j * 2048, 16384, BAR(B_FULLW + q)); }
      }
    }
    mbar_wait(BAR(B_OFREE), L);
  }
}

DEVI void ffn_prefetch(const Params& P, int q) {
  bulk_prefetch(q < 16 ? ((q & 1) ? P.wu : P.wg) + ((q >> 1) * 128 + blockIdx.x) * 3584 : P.wd + (blockIdx.x * 8 + q - 16) * 3584, 7168);
}
DEVI void storer(const Params& P, uint32_t sb, int wg) {
  const int bid = uni(BID), bi = bid >> 4, rh = bid & 1, bc = (bid & 15) >> 1;
  const bool one = (threadIdx.x & 31) == 0;
  char* const g = (char*)P.g;
  #pragma unroll 1
  for (int L = 0; L < 2; L++) {
    mbar_wait(BAR(B_KVRDY + wg * 2), L);
    const uint32_t tag = lds32(sb + INFO + 8) + L;
    #pragma unroll 1
    for (int u = bi < 7 ? 0 : 4; u < 8; u++) {
      const int h = (u >> 1) & 1, t = (u & 1) ? wg : 3 - wg;
      uint32_t src, dst, fl;
      if (u < 4) {
        src = (h ? KVB : KVA) + (4 + t) * 8192; dst = offsetof(Scratch, kv) + (bid * 8 + h * 4 + t) * 8192; fl = offsetof(Scratch, flagKV) + (bid * 32 + h * 4 + t) * 4;
      } else {
        src = QO + (h * 4 + t) * 4096; dst = offsetof(Scratch, o) + ((((bi * 2 + h) * 8 + bc) * 2 + (t >> 1)) * 4 + rh * 2 + (t & 1)) * 4096;
        fl = offsetof(Scratch, flagO) + (((bi * 2 + h) * 2 + (t >> 1)) * 32 + (bid & 15) * 2 + (t & 1)) * 4;
      }
      if (u >= 2) mbar_wait(u < 4 ? BAR(B_KVRDY + wg * 2 + 1) : BAR(B_ORDY + wg * 4 + u - 4), L);
      if (one) { bulk_s2g(g + dst, sb + src, u < 4 ? 8192 : 4096); if (u == 5 || u == 7) mbar_arrive(BAR(B_HAFREE + h)); }
      if (u == 4 || u == 6) continue;
      bulk_wait<0>(); fence_rel();
      if (one) { st_rlx((unsigned*)(g + fl), tag); if (u > 4) st_rlx((unsigned*)(g + (fl ^ 132u)), tag); }
      PROFY(one && !L && wg == 0 && (u == 0 || u == 3 || u == 5 || u == 7), u == 5 ? 38 : (u == 7 ? 54 : 32 + (u & 1)));
    }
    if (one) mbar_arrive(BAR(B_OFREE));
    if (L == 0) {
      char* dst = g + (offsetof(Scratch, x) + (bi * 16 + 2 * bc) * 32768 + rh * 16384);
      unsigned* f = (unsigned*)(g + (offsetof(Scratch, flagX) + (bi * 32 + bc * 4 + rh) * 4));
      if (wg == 0) {
        const uint32_t a = sb + rh * 16384;
        mbar_wait(BAR(B_PFREE), 0);
        mbar_wait(BAR(B_XRDY), 0); mbar_wait(BAR(B_XRDY + 2), 0);
        PROFY(one, 41);
        if (one) { bulk_s2peer(a, 16384, BAR(B_FULLQ)); bulk_s2g(dst, a, 16384); }
        mbar_wait(BAR(B_XRDY + 1), 0); mbar_wait(BAR(B_XRDY + 3), 0);
        bulk_wait<0>();
        PROFY(one, 45);
        if (one) { bulk_s2peer(a + 32768, 16384, BAR(B_FULLQ + 1)); mbar_arrive(BAR(B_XFREE)); }
        fence_rel();
        if (one) { st_rlx(f, tag); bulk_s2g(dst + 32768, a + 32768, 16384); }
        PROFY(one, 56);
        bulk_wait<0>();
        if (one) mbar_arrive(BAR(B_XFREE + 1));
        fence_rel();
        if (one) st_rlx(f + 2, tag);
        PROFY(one, 57);
      }
      if (wg == 0) {
        uint32_t t0 = clk() + PF1_D;
        #pragma unroll 1
        for (int q = PF1_S; q < PF1_E; q++) { while ((int)(clk() - t0) < 0) __nanosleep(50); if (one) ffn_prefetch(P, q); t0 += PF1_T; }
      }
    }
  }
}

DEVI void stg_issue(const Params& P, int c, uint32_t d, uint32_t du, uint32_t b) {
  mbar_expect_tx(b, 16384);
  if (c < 8) { tma_2d_h(d, &P.mWg, FID * 32, c * 128, b, POL_G); tma_2d_h(d + du, &P.mWu, FID * 32, c * 128, b, POL_U); }
  else if (c < 12) tma_3d_h(d, &P.mWd, 0, FID * 32 + (c - 8) * 8, 0, b, POL_D);
  else tma_2d_h(d, &P.mWp, FID * 32, (c - 12) * 256, b, POL_EF);
}
DEVI void stager(const Params& P, uint32_t sb) {
  {
    const int b = blockIdx.x;
    uint32_t t0 = clk();
    #pragma unroll 1
    for (int q = 0; q < PQ_N; q++) { bulk_prefetch(P.wqkv + (q * 128 + b) * 3072, 6144); while (clk() - t0 < PQ_T); t0 += PQ_T; }
    bulk_prefetch(P.wo + b * 8192, 16384);
    #pragma unroll 1
    for (int q = 0; q < PF0_N; q++) {
      while (clk() - t0 < PF0_T);
      t0 += PF0_T;
      ffn_prefetch(P, q);
    }
  }
  const int bid = BID, bi = bid >> 4, rh = bid & 1, bc = (bid & 15) >> 1;
  #pragma unroll 1
  for (int L = 0; L < 2; L++) {
    const int nch = FID >= 112 ? 0 : (L ? 8 : (FID < 96 ? 16 : 12));
    mbar_wait(BAR(B_KVRDY), L); mbar_wait(BAR(B_KVRDY + 2), L);
    #pragma unroll 1
    for (int n = 0, q = 0; n < 16; n++, q = q == 5 ? 0 : q + 1) {
      if (n >= 2) mbar_wait(n < 6 ? BAR(B_HAFREE + (n >> 2)) : BAR(B_EMPTYW + q), n < 6 ? L : w_par(n - 6, q, L));
      if (n == THR_N) mbar_wait(BAR(B_OFREE), L);
      mbar_expect_tx(BAR(B_FULLW + q), 16384);
      tma_5d(sb + w_off(q) + 16384, &P.mWo, 0, 0, n >> 3, 2 * (n & 7), 2 * bc, BAR(B_FULLW + q), L ? POL_EF : POL_NORMAL);
    }
    mbar_expect_tx(BAR(B_RES), 32768);
    #pragma unroll 1
    for (int e = 0; e < 2; e++) {
      mbar_wait(BAR(B_EMPTYW + 4 + e), 1);
      if (L) bulk_g2s_h(sb + e * 32768 + rh * 16384, P.g->x[bi][2 * bc + e] + rh * 1024, 16384, BAR(B_RES));
      else tma_2d_h(sb + e * 32768 + rh * 16384, &P.mXh, bc * 128 + e * 64, bi * 256 + rh * 128, BAR(B_RES), POL_EF);
    }
    if (L == 0) { mbar_arrive_peer(BAR(B_PFREE)); mbar_wait(BAR(B_XFREE), 0); }
    #pragma unroll 1
    for (int c = 0, slot = 0; c < nch; c++, slot = slot == 2 ? 0 : slot + 1) {
      mbar_wait(L ? BAR(B_EMPTYW + (c >> 1)) : BAR(B_STGE + slot), L | ((0x71c7 >> c) & 1));
      stg_issue(P, c, L ? sb + w_off(c >> 1) + (c & 1) * 8192 : sb + STG + slot * 16384, 8192 << L, L ? BAR(B_FULLW + (c >> 1)) : BAR(B_STG + slot));
    }
  }
}
DEVI void sum8(uint4 v, float& s1, float& s2) {
  float e[8] = {bf_lo(v.x), bf_hi(v.x), bf_lo(v.y), bf_hi(v.y), bf_lo(v.z), bf_hi(v.z), bf_lo(v.w), bf_hi(v.w)};
  #pragma unroll
  for (int q = 0; q < 8; q++) { s1 += e[q]; s2 = fmaf(e[q], e[q], s2); }
}
DEVI uint4 norm8(uint4 x, float m, float rs, uint32_t d, uint32_t d2) {
  #define HN(v) pack_bf16((bf_lo(v) - m) * rs, (bf_hi(v) - m) * rs)
  uint4 b = make_uint4(HN(x.x), HN(x.y), HN(x.z), HN(x.w));
  #undef HN
  sts128(d, make_uint4(b.x << 16, b.x & 0xffff0000u, b.y << 16, b.y & 0xffff0000u));
  sts128(d + d2, make_uint4(b.z << 16, b.z & 0xffff0000u, b.w << 16, b.w & 0xffff0000u));
  return b;
}
DEVI uint4 best4(uint32_t p) {
  uint4 a = lds128(p), b = lds128(p + 16), c = lds128(p + 32), d = lds128(p + 48);
  if (b.x > a.x) a = b;
  if (d.x > c.x) c = d;
  return c.x > a.x ? c : a;
}
#define FL(x) __uint_as_float(x)
#define UI(x) __float_as_uint(x)
DEVI void qkv_params(const Params& P, uint32_t sb, int row, uint32_t tag, bool second) {
  uint4 v0, v1; poll_ll2(&P.g->statF[row], &P.g->statF[row + 128], 0xffffffffu, tag, v0, v1);
  #pragma unroll 1
  for (int q = 0; q < 2; q++) {
    float var = FL(v0.y), c = rsqrtf(var + LN_EPS);
    if (second) { c += 1.f; c *= rsqrtf(fmaf(var * c, c, LN_EPS)); }
    const float mh = bf_round(FL(v0.x));
    sts64f(sb + PAR + q * 1024 + (row & 127) * 8, c, FL(pack_bf16(mh, FL(v0.x) - mh)));
    v0 = v1;
  }
}
DEVI void aux(const Params& P, uint32_t sb) {
  int tid = fresh_tid();
  #define lane (tid & 31)
  #define wq (tid >> 5)
  uint32_t ids = P.map[blockIdx.x], tag;
  #define bid ((int)(ids & 255))
  #define fid ((int)(ids >> 8))
  #define bi (bid >> 4)
  #define bp (bid & 15)
  #define bc (bp >> 1)
  #define FRESH() do { tid = fresh_tid(); uint4 z_ = ldsv128(sb + INFO2 + 16); ids = z_.y; tag = z_.z + L; idx = z_.w; } while (0)
  {
    const uint32_t epoch = ld_rlx(&P.g->epoch);
    if (tid == 0) {
      mbar_expect_tx(BAR(B_STG), 49152);
      tma_3d(sb + STG, &P.mWq, bp * 64, bi * 128, 0, BAR(B_STG));
      tma_3d(sb + STG + 24576, &P.mWq, bp * 64, bi * 128 + 64, 0, BAR(B_STG));
    }
    __syncwarp();
    sts64f(sb + ONES + tid * 8, FL(0x3F803F80u), FL(0x3F803F80u));
    float s1 = 0.f, s2 = 0.f;
    { uint4 v = __ldg((const uint4*)P.wr + tid);
      if ((tid >> 4) == bc) norm8(v, 0.f, 1.f, sb + WR + (tid & 15) * 32, 16);
      sum8(v, s1, s2);
      #pragma unroll 1
      for (int o = 16; o; o >>= 1) s1 += __shfl_xor_sync(0xffffffffu, s1, o);
      sts32f(sb + INFO2 + wq * 4, s1); }
    const uint4* src = (const uint4*)(P.x0 + (size_t)bid * 16384) + (tid >> 3) * 128 + (tid & 7);
    s1 = 0.f; s2 = 0.f;
    #pragma unroll 1
    for (int it = 0; it < 16; it += 4) {
      uint4 v0 = __ldg(src + it * 8), v1 = __ldg(src + it * 8 + 8), v2 = __ldg(src + it * 8 + 16), v3 = __ldg(src + it * 8 + 24);
      #pragma unroll 1
      for (int q = 0; q < 4; q++) { sum8(v0, s1, s2); v0 = v1; v1 = v2; v2 = v3; }
    }
    #pragma unroll 1
    for (int o = 1; o < 8; o <<= 1) { s1 += __shfl_xor_sync(0xffffffffu, s1, o); s2 += __shfl_xor_sync(0xffffffffu, s2, o); }
    tag = ((epoch % 16383u) + 1u) << 2;
    if (tid == 0) { sts128(sb + INFO, make_uint4(0x40000000u, 0u, tag, ((epoch % 127u) + 1u) << 1)); sts128(sb + INFO2 + 16, make_uint4(epoch, ids, tag, 0x40000000u)); }
    float m = s1 * (1.f / 1024.f);
    if ((tid & 7) == 0) st_ll(&P.g->statF[bid * 16 + (tid >> 3)], UI(m), UI(fmaxf(fmaf(-m, m, s2 * (1.f / 1024.f)), 0.f)), 0u, tag);
    bar_sync(2, 128);
    mbar_wait_b(BAR(B_STG), 0);
    if (tid < 96) {
      s1 = 0.f; s2 = 0.f;
      #pragma unroll 4
      for (int r = 0; r < 128; r++) {
        uint32_t v = lds32(sb + STG + (r >> 6) * 24576 + wq * 8192 + (r & 63) * 128 + ((lane * 4) ^ ((r & 7) << 4)));
        s1 += bf_lo(v); s2 += bf_hi(v);
      }
      st_ll(&P.g->csP[bp][bi][tid], UI(s1), UI(s2), 0u, tag);
      s1 = 0.f; s2 = 0.f;
      #pragma unroll 1
      for (int q = 0; q < 8; q += 2) {
        uint4 a, b; poll_ll2(&P.g->csP[bp][q][tid], &P.g->csP[bp][q + 1][tid], 0xffffffffu, tag, a, b);
        s1 += FL(a.x) + FL(b.x); s2 += FL(a.y) + FL(b.y);
      }
      const uint32_t hi = pack_bf16(-s1, -s2);
      sts32(sb + CS + (tid >> 2) * 32 + (tid & 3) * 4, hi);
      sts32(sb + CS + (tid >> 2) * 32 + (tid & 3) * 4 + 16, pack_bf16(-s1 - bf_lo(hi), -s2 - bf_hi(hi)));
    }
    fence_async_smem();
    qkv_params(P, sb, bi * 256 + tid, tag, false);
  }
  int idx;
  #pragma unroll 1
  for (int L = 0; L < 2; L++) {
    FRESH();
    {
      if ((idx >> 8) == bi && wq < 3) {
        uint4 v = poll_ll(&P.g->patch[wq * 256 + bp * 16 + (lane & 15)], 0xffffffffu, tag);
        sts64f(sb + PATCH + (wq * 16 + (lane & 15)) * 8, FL(v.x), FL(v.y));
      }
      sts32(sb + INFO, idx);
      bar_sync(2, 128);
      if (tid == 0) mbar_arrive(BAR(B_PAR));
      PROFX(tid == 0, L ? 23 : 17);
    }
    FRESH();
    mbar_wait_b(BAR(B_OFREE), L);
    #define blk (bi * 2 + (bid & 1))
    if (tid < 33) st_ll(tid < 32 ? &P.g->row[blk][bc * 32 + tid] : &P.g->best[bc][blk], 0u, 0u, 0u, 0u);
    mbar_wait_b(BAR(B_XRDY + 1), L); mbar_wait_b(BAR(B_XRDY + 3), L);
    PROFX(tid == 0, 37 + L * 16);
    FRESH();
    {
      float s1 = 0.f, s2 = 0.f, d = 0.f;
      #pragma unroll 1
      for (int q = 0; q < 8; q += 4) {
        const uint4* src = &P.g->statP[q][blk * 128 + tid];
        uint4 v0, v1, v2, v3; int it = 0;
        do { v0 = ld_ll(src); v1 = ld_ll(src + 2048); v2 = ld_ll(src + 4096); v3 = ld_ll(src + 6144); if (++it > SPIN_MAX) __trap(); }
        while (!__all_sync(0xffffffffu, v0.w == tag && v1.w == tag && v2.w == tag && v3.w == tag));
        s1 += (FL(v0.x) + FL(v1.x)) + (FL(v2.x) + FL(v3.x)); s2 += (FL(v0.y) + FL(v1.y)) + (FL(v2.y) + FL(v3.y)); d += (FL(v0.z) + FL(v1.z)) + (FL(v2.z) + FL(v3.z));
      }
      PROFX(tid == 0, 39 + L * 16);
      uint4 a = lds128(sb + INFO2), b, c;
      float m = s1 * (1.f / 1024.f), var = fmaxf(fmaf(-m, m, s2 * (1.f / 1024.f)), 0.f), rs = rsqrtf(var + LN_EPS);
      uint32_t key = UI(fmaf(-m, (FL(a.x) + FL(a.y)) + (FL(a.z) + FL(a.w)), d) * rs);
      key ^= (uint32_t)((int)key >> 31) | 0x80000000u;
      uint32_t win = __ballot_sync(0xffffffffu, key == __reduce_max_sync(0xffffffffu, key));
      if (lane == __ffs(win) - 1) sts128(sb + RED + wq * 16, make_uint4(key, UI(m), UI(rs), (tag << 11) | (uint32_t)(blk * 128 + tid)));
      if (L) sts64f(sb + PAR + tid * 8, 1.f + rs, -m * rs);
      else if ((tid >> 4) == bc) st_ll(&P.g->statF[blk * 128 + tid], UI(m), UI(var), 0u, tag + 1);
      bar_sync(2, 128);
      if (wq == 0) {
        a = best4(sb + RED);
        float2 v = lds64f(sb + (lane >> 4) * 32768 + (a.w & 255) * 128 + (((lane & 15) * 8) ^ ((a.w & 7) << 4)));
        st_ll(&P.g->row[blk][bc * 32 + lane], UI(v.x), UI(v.y), 0u, tag);
        if (lane == 0) { st_ll(&P.g->best[bc][blk], a.x, a.y, a.z, a.w); sts32(sb + INFO + 4, a.w & 2047); }
        __syncwarp();
        if (L) {
          const float al = 1.f + FL(a.z), be = -FL(a.y) * FL(a.z);
          sts64f(sb + RED + 1792 + lane * 8, FL(pack_bf16(fmaf(bf_lo(UI(v.x)), al, be), fmaf(bf_hi(UI(v.x)), al, be))),
                                             FL(pack_bf16(fmaf(bf_lo(UI(v.y)), al, be), fmaf(bf_hi(UI(v.y)), al, be))));
        }
        if (lane < 2 - L) mbar_arrive(L ? BAR(B_PAR) : BAR(B_XFREE + lane));
      }
      PROFX(tid == 0, 18 + L * 6);
      FRESH();
      if (!L) {
        if (fid < 112) { st_ll(&P.g->yP[tid & ~1][fid][tid & 1], 0u, 0u, 0u, 0u); st_ll(&P.g->yP[tid | 1][fid][tid & 1], 0u, 0u, 0u, 0u); }
        if (tid < 24) st_ll(tid < 16 ? &P.g->x2[tid >> 1][2 * bid + (tid & 1)] : &P.g->patch[fid * 8 + tid - 16], 0u, 0u, 0u, 0u);
      }
      a = poll_ll(&P.g->best[bc][lane & 15], 0xfffff800u, tag << 11);
      win = __ffs(__ballot_sync(0xffffffffu, a.x == __reduce_max_sync(0xffffffffu, a.x))) - 1;
      idx = __shfl_sync(0xffffffffu, a.w, win) & 2047;
      PROFX(tid == 0, 19 + L * 6);
      poll_ll2(&P.g->row[win][tid], &P.g->row[win][tid + 128], 0xffffffffu, tag, c, b);
      c.z = b.x; c.w = b.y;
      a.x = __shfl_sync(0xffffffffu, a.x, win); a.y = __shfl_sync(0xffffffffu, a.y, win); a.z = __shfl_sync(0xffffffffu, a.z, win);
      sts32(sb + INFO2 + 28, idx);
      PROFX(tid == 0, 61 + L);
      b = norm8(c, FL(a.y), FL(a.z), sb + HV + tid * 16, 2048);
      if (L && fid < 112) bar_arrive(3, 384);
      if ((tid >> 1) == (bid & 63)) {
        sts128(sb + RED + 64 + (tid & 1) * 16, bid < 64 ? make_uint4(c.x, c.y, b.x, b.y) : make_uint4(c.z, c.w, b.z, b.w));
        sts32(sb + RED + 96, a.x);
      }
      if (L && wq == 0 && win != blk) *(float2*)(P.out + (size_t)lds32(sb + INFO + 4) * 1024 + bc * 128 + lane * 4) = lds64f(sb + RED + 1792 + lane * 8);
      bar_sync(2, 128);
    }
    #pragma unroll 1
    for (int st = L; st < 3; st++) {
      FRESH();
      float a[8] = {0.f, 0.f, 0.f, 0.f, 0.f, 0.f, 0.f, 0.f};
      if (L == 0 && fid < (st == 2 ? 96 : 112)) {
        uint32_t ha = st == 1 ? sb + RED + 768 : sb + HV + ((st ? wq : wq & 1) * 64 + (lane >> 2)) * 4;
        uint32_t ph = (st ? (st == 1 ? 0x1cu : 0x11u) : 0x171u), bar = st == 1 ? BAR(B_STG + 2) : BAR(B_STG);
        uint32_t wa = sb + STG + tid * 16 + wq * 3584 + (st == 1 ? 32768 : 0);
        const uint32_t hx = st == 1 ? 256 : (st ? 1024 : 512);
        const bool lead = lane == 0;
        #pragma unroll 1
        do {
          mbar_wait(bar, ph & 1);
          PROFX(lead && threadIdx.x == 256 && st == 0 && (ph > 255 || ph < 4), 40 - 23 + __clz(ph));
          gemv8(a, wa, ha, 32);
          __syncwarp();
          if (lead) mbar_arrive(bar - 8 * (B_STG - B_STGE));
          const bool wrap = bar == BAR(B_STG + 2);
          bar += wrap ? -16 : 8; wa += wrap ? -32768 : 16384; ha += hx;
          ph >>= 1;
        } while (ph != 1);
      }
      FRESH();
      if (st == 1) {
        const uint32_t t8 = lds32(sb + INFO + 12) + L;
        if (L == 0 && fid < 112) {
          const bool odd = lane & 1;
          #pragma unroll
          for (int e = 0; e < 4; e++) { float z = __shfl_xor_sync(0xffffffffu, odd ? a[e] : a[4 + e], 1); if (odd) a[e] = z; else a[4 + e] = z; }
          uint4* dst = &P.g->yP[tid & ~1][fid][tid & 1];
          st_ll(dst, UI(a[0]), UI(a[1]), UI(a[2]), (UI(a[3]) & ~255u) | t8);
          st_ll(dst + 224, UI(a[4]), UI(a[5]), UI(a[6]), (UI(a[7]) & ~255u) | t8);
          PROFX(tid == 0, 21);
        }
        if (!L) qkv_params(P, sb, bi * 256 + tid, tag + 1, true);
        if (tid == 0) { uint32_t k = lds32(sb + RED + 96); sts32f(sb + RED + 100, bf_round(__fdividef(1.f, 1.f + __expf(-bf_round(FL(k ^ (~(uint32_t)((int)k >> 31) | 0x80000000u))))))); }
        uint4 v0, v1;
        poll_ll2(&P.g->yP[bid][0][min(tid, 111)], &P.g->yP[bid][0][min(tid, 111) + 112], 255u, t8, v0, v1);
        const float lo = (tid < 112 && !(tid & 1)) ? 1.f : 0.f, hi = (tid < 112 && (tid & 1)) ? 1.f : 0.f;
        const float y0 = FL(v0.x) + FL(v1.x), y1 = FL(v0.y) + FL(v1.y), y2 = FL(v0.z) + FL(v1.z), y3 = FL((v0.w & ~255u) | 128u) + FL((v1.w & ~255u) | 128u);
        a[0] = y0 * lo; a[1] = y1 * lo; a[2] = y2 * lo; a[3] = y3 * lo; a[4] = y0 * hi; a[5] = y1 * hi; a[6] = y2 * hi; a[7] = y3 * hi;
      }
      sts32f(sb + RED + 256 + wq * 128 + ((lane & 3) * 8 + (lane >> 2)) * 4, fold8(a));
      bar_sync(2, 128);
      const uint32_t d = sb + RED + 256 + lane * 4;
      float z0 = lds32f(d) + lds32f(d + 128), z1 = lds32f(d + 256) + lds32f(d + 384);
      if (st == 0) { sts32f(sb + RED + 768 + lane * 32 + wq * 4, swiglu(z0, z1)); bar_sync(2, 128); PROFX(tid == 0, 20); continue; }
      z0 += z1;
      if (st == 1) {
        z0 += __shfl_xor_sync(0xffffffffu, z0, 8); z0 += __shfl_xor_sync(0xffffffffu, z0, 16);
        uint32_t xw = lds32(sb + RED + 64 + (lane & 4) * 4 + (lane & 2) * 2), hw = lds32(sb + RED + 72 + (lane & 4) * 4 + (lane & 2) * 2);
        z0 = bf_round(((lane & 1) ? bf_hi(hw) : bf_lo(hw)) + bf_round(bf_round(z0) * lds32f(sb + RED + 100))) + ((lane & 1) ? bf_hi(xw) : bf_lo(xw));
      } else if (fid < 32) z0 *= QSCALE;
      uint32_t v = pack_bf16(z0, __shfl_down_sync(0xffffffffu, z0, 1)), v2 = __shfl_down_sync(0xffffffffu, v, 2);
      if (L) { if (tid == 0 || tid == 4) *(uint2*)(P.out + (size_t)idx * 1024 + bid * 8 + tid) = make_uint2(v, v2); PROFW(tid == 0, 28); break; }
      if ((tid & 3) == 0 && tid < (st == 1 ? 64 : 32)) st_ll(st == 1 ? &P.g->x2[tid >> 3][2 * bid + ((tid >> 2) & 1)] : &P.g->patch[fid * 8 + (tid >> 2)], v, v2, 0u, tag + 1);
      PROFX(tid == 0, st == 1 ? 22 : 31);
      if (st == 1) {
        uint4 x, y; poll_ll2(&P.g->x2[bi][tid], &P.g->x2[bi][tid + 128], 0xffffffffu, tag + 1, x, y);
        x.z = y.x; x.w = y.y;
        if (wq == (bc & 3)) sts64f(sb + X2SEG + lane * 8, FL(bc < 4 ? x.x : x.z), FL(bc < 4 ? x.y : x.w));
        float s1 = 0.f, s2 = 0.f;
        sum8(x, s1, s2);
        #pragma unroll
        for (int o = 16; o; o >>= 1) { s1 += __shfl_xor_sync(0xffffffffu, s1, o); s2 += __shfl_xor_sync(0xffffffffu, s2, o); }
        sts64f(sb + RED + wq * 8, s1, s2);
        bar_sync(2, 128);
        y = lds128(sb + RED); uint4 y2 = lds128(sb + RED + 16);
        float m = ((FL(y.x) + FL(y.z)) + (FL(y2.x) + FL(y2.z))) * (1.f / 1024.f);
        norm8(x, m, rsqrtf(fmaxf(fmaf(-m, m, ((FL(y.y) + FL(y.w)) + (FL(y2.y) + FL(y2.w))) * (1.f / 1024.f)), 0.f) + LN_EPS), sb + HV + tid * 16, 2048);
        bar_sync(2, 128);
        PROFX(tid == 0, 30);
      }
    }
  }
  if (bid == 0 && tid == 0) P.g->epoch = lds32(sb + INFO2 + 16) + 1;
  #undef blk
  #undef bid
  #undef fid
  #undef bi
  #undef bp
  #undef bc
  #undef FRESH
  #undef lane
  #undef wq
}

__global__ void __cluster_dims__(2, 1, 1) __launch_bounds__(512, 1) fused_kernel(const __grid_constant__ Params P) {
  extern __shared__ __align__(1024) uint8_t smem_raw[];
  const uint32_t sb = smem_u32(smem_raw);
  PROFT(threadIdx.x == 0, 0);
  if (threadIdx.x == 0) {
    for (int s = 0; s < 3; s++) mbar_init(BAR(B_FULLQ + s), 1);
    asm volatile("fence.mbarrier_init.release.cluster;" ::: "memory");
    #pragma unroll 1
    for (int s = 0; s < 3; s++) {
      mbar_expect_tx(BAR(B_FULLQ + s), 57344);
      tma_2d(sb + qa_off(s), &P.mX, s * 64, (BID >> 4) * 256, BAR(B_FULLQ + s));
      tma_3d(sb + qb_off(s), &P.mWq, (BID & 15) * 64, s * 64, 0, BAR(B_FULLQ + s));
    }
    if ((sb & 4095) != 1024) __trap();
  } else if (threadIdx.x >= 32 + B_EMPTYQ && threadIdx.x < 32 + B_COUNT) {
    const int b = threadIdx.x - 32;
    const uint32_t cnt = b < B_XFREE ? 2 : (b < B_KVRDY ? 3 : (b < B_KVFULL ? 4 : 1));
    mbar_init(BAR(b), cnt);
    asm volatile("fence.mbarrier_init.release.cluster;" ::: "memory");
  }
  __syncthreads();
  asm volatile("barrier.cluster.arrive.relaxed.aligned;" ::: "memory");
  const int wg = __shfl_sync(0xffffffffu, threadIdx.x >> 7, 0);
  if (wg < 2) { reg_inc<224>(); consumer(P, sb, wg); }
  else if (wg == 2) { reg_dec<40>(); aux(P, sb); }
  else {
    reg_dec<24>();
    asm volatile("barrier.cluster.wait.aligned;" ::: "memory");
    const int w = __shfl_sync(0xffffffffu, (threadIdx.x >> 5) & 3, 0);
    if (w == 0) loader(P, sb);
    else if (w < 3) storer(P, sb, w - 1);
    else if ((threadIdx.x & 31) == 0) stager(P, sb);
  }
}

typedef CUresult (*EncFn)(CUtensorMap*, CUtensorMapDataType, cuuint32_t, void*, const cuuint64_t*, const cuuint64_t*, const cuuint32_t*, const cuuint32_t*,
                          CUtensorMapInterleave, CUtensorMapSwizzle, CUtensorMapL2promotion, CUtensorMapFloatOOBfill);
static void mk_map(EncFn enc, CUtensorMap* m, const void* ptr, int rank, const cuuint64_t* dims, const cuuint64_t* strides, const cuuint32_t* box,
                   CUtensorMapSwizzle sw, CUtensorMapL2promotion pr) {
  cuuint32_t es[5] = {1, 1, 1, 1, 1};
  enc(m, CU_TENSOR_MAP_DATA_TYPE_BFLOAT16, rank, (void*)ptr, dims, strides, box, es, CU_TENSOR_MAP_INTERLEAVE_NONE, sw, pr, CU_TENSOR_MAP_FLOAT_OOB_FILL_NONE);
}
extern "C" void kernel_launch(void* const* d_in, const int* in_sizes, int n_in, void* d_out, int out_size) {
  (void)in_sizes; (void)n_in; (void)out_size;
  void* fn = nullptr; cudaDriverEntryPointQueryResult q;
  cudaGetDriverEntryPoint("cuTensorMapEncodeTiled", &fn, cudaEnableDefault, &q);
  EncFn enc = (EncFn)fn;
  cudaFuncSetAttribute(fused_kernel, cudaFuncAttributeMaxDynamicSharedMemorySize, SMEM_BYTES);
  Params P;
  const CUtensorMapSwizzle S128 = CU_TENSOR_MAP_SWIZZLE_128B, S0 = CU_TENSOR_MAP_SWIZZLE_NONE;
  const CUtensorMapL2promotion L256 = CU_TENSOR_MAP_L2_PROMOTION_L2_256B, L128 = CU_TENSOR_MAP_L2_PROMOTION_L2_128B;
  { cuuint64_t d[2] = {1024, 2048}, s[1] = {2048}; cuuint32_t b[2] = {64, 256}, bh[2] = {64, 128};
    mk_map(enc, &P.mX, d_in[0], 2, d, s, b, S128, L256); mk_map(enc, &P.mXh, d_in[0], 2, d, s, bh, S128, L256); }
  { cuuint64_t d[3] = {1024, 1024, 3}, s[2] = {6144, 2048}; cuuint32_t b[3] = {64, 64, 3}; mk_map(enc, &P.mWq, d_in[1], 3, d, s, b, S128, L256); }
  { cuuint64_t d[5] = {64, 32, 2, 16, 16}, s[4] = {2048, 65536, 131072, 128}; cuuint32_t b[5] = {64, 32, 1, 2, 2}; mk_map(enc, &P.mWo, d_in[2], 5, d, s, b, S128, L256); }
  { cuuint64_t d[2] = {3584, 1024}, s[1] = {7168}; cuuint32_t b[2] = {32, 128};
    mk_map(enc, &P.mWg, d_in[5], 2, d, s, b, S0, L128); mk_map(enc, &P.mWu, d_in[6], 2, d, s, b, S0, L128); }
  { cuuint64_t d[2] = {3072, 1024}, s[1] = {6144}; cuuint32_t b[2] = {32, 256}; mk_map(enc, &P.mWp, d_in[1], 2, d, s, b, S0, L128); }
  { cuuint64_t d[3] = {256, 3584, 4}, s[2] = {2048, 512}; cuuint32_t b[3] = {256, 8, 4}; mk_map(enc, &P.mWd, d_in[7], 3, d, s, b, S0, L128); }
  P.x0 = (const bf16*)d_in[0]; P.wqkv = (const bf16*)d_in[1]; P.wo = (const bf16*)d_in[2]; P.wr = (const bf16*)d_in[4]; P.wg = (const bf16*)d_in[5]; P.wu = (const bf16*)d_in[6]; P.wd = (const bf16*)d_in[7];
  P.out = (bf16*)d_out;
  cudaGetSymbolAddress((void**)&P.g, g_scr);
  for (int b = 0; b < 128; b++) {
    int j = b >> 1, quad = j < 4 ? 0 : (j < 36 ? 1 + (j - 4) % 8 : 9 + (j - 36) % 7), pos = j < 4 ? j : (j < 36 ? (j - 4) / 8 : (j - 36) / 7);
    int bid = ((quad >> 2) * 2 + (pos >> 1)) * 16 + ((quad & 3) * 2 + (pos & 1)) * 2 + (b & 1);
    int e = pos * 2 + (b & 1), fid = e < 6 ? quad * 6 + e : e * 16 + quad;
    P.map[b] = bid | fid << 8;
  }
  fused_kernel<<<128, 512, SMEM_BYTES>>>(P);
}
```

```cpp
#include <cuda_runtime.h>
#include <cuda_bf16.h>
#include <cuda.h>
#include <stdint.h>
#include <stddef.h>
typedef __nv_bfloat16 bf16;

template<int TB, int TA = 0> __device__ __forceinline__ void wgmma_ss_n192(float (&d)[96], uint64_t da, uint64_t db, int scale_d) {
  asm volatile("{\n.reg .pred p;\nsetp.ne.b32 p, %98, 0;\n"
    "wgmma.mma_async.sync.aligned.m64n192k16.f32.bf16.bf16 {%0, %1, %2, %3, %4, %5, %6, %7, %8, %9, %10, %11, %12, %13, %14, %15, %16, %17, %18, %19, %20, %21, %22, %23, %24, %25, %26, %27, %28, %29, %30, %31, %32, %33, %34, %35, %36, %37, %38, %39, %40, %41, %42, %43, %44, %45, %46, %47, %48, %49, %50, %51, %52, %53, %54, %55, %56, %57, %58, %59, %60, %61, %62, %63, %64, %65, %66, %67, %68, %69, %70, %71, %72, %73, %74, %75, %76, %77, %78, %79, %80, %81, %82, %83, %84, %85, %86, %87, %88, %89, %90, %91, %92, %93, %94, %95}, %96, %97, p, 1, 1, %100, %99;\n}\n"
    : "+f"(d[0]), "+f"(d[1]), "+f"(d[2]), "+f"(d[3]), "+f"(d[4]), "+f"(d[5]), "+f"(d[6]), "+f"(d[7]), "+f"(d[8]), "+f"(d[9]), "+f"(d[10]), "+f"(d[11]), "+f"(d[12]), "+f"(d[13]), "+f"(d[14]), "+f"(d[15]), "+f"(d[16]), "+f"(d[17]), "+f"(d[18]), "+f"(d[19]), "+f"(d[20]), "+f"(d[21]), "+f"(d[22]), "+f"(d[23]), "+f"(d[24]), "+f"(d[25]), "+f"(d[26]), "+f"(d[27]), "+f"(d[28]), "+f"(d[29]), "+f"(d[30]), "+f"(d[31]), "+f"(d[32]), "+f"(d[33]), "+f"(d[34]), "+f"(d[35]), "+f"(d[36]), "+f"(d[37]), "+f"(d[38]), "+f"(d[39]), "+f"(d[40]), "+f"(d[41]), "+f"(d[42]), "+f"(d[43]), "+f"(d[44]), "+f"(d[45]), "+f"(d[46]), "+f"(d[47]), "+f"(d[48]), "+f"(d[49]), "+f"(d[50]), "+f"(d[51]), "+f"(d[52]), "+f"(d[53]), "+f"(d[54]), "+f"(d[55]), "+f"(d[56]), "+f"(d[57]), "+f"(d[58]), "+f"(d[59]), "+f"(d[60]), "+f"(d[61]), "+f"(d[62]), "+f"(d[63]), "+f"(d[64]), "+f"(d[65]), "+f"(d[66]), "+f"(d[67]), "+f"(d[68]), "+f"(d[69]), "+f"(d[70]), "+f"(d[71]), "+f"(d[72]), "+f"(d[73]), "+f"(d[74]), "+f"(d[75]), "+f"(d[76]), "+f"(d[77]), "+f"(d[78]), "+f"(d[79]), "+f"(d[80]), "+f"(d[81]), "+f"(d[82]), "+f"(d[83]), "+f"(d[84]), "+f"(d[85]), "+f"(d[86]), "+f"(d[87]), "+f"(d[88]), "+f"(d[89]), "+f"(d[90]), "+f"(d[91]), "+f"(d[92]), "+f"(d[93]), "+f"(d[94]), "+f"(d[95])
    : "l"(da), "l"(db), "r"(scale_d), "n"(TB), "n"(TA));
}

template<int TB> __device__ __forceinline__ void wgmma_rs_n192(float (&d)[96], uint32_t a0, uint32_t a1, uint32_t a2, uint32_t a3, uint64_t db, int scale_d) {
  asm volatile("{\n.reg .pred p;\nsetp.ne.b32 p, %101, 0;\n"
    "wgmma.mma_async.sync.aligned.m64n192k16.f32.bf16.bf16 {%0, %1, %2, %3, %4, %5, %6, %7, %8, %9, %10, %11, %12, %13, %14, %15, %16, %17, %18, %19, %20, %21, %22, %23, %24, %25, %26, %27, %28, %29, %30, %31, %32, %33, %34, %35, %36, %37, %38, %39, %40, %41, %42, %43, %44, %45, %46, %47, %48, %49, %50, %51, %52, %53, %54, %55, %56, %57, %58, %59, %60, %61, %62, %63, %64, %65, %66, %67, %68, %69, %70, %71, %72, %73, %74, %75, %76, %77, %78, %79, %80, %81, %82, %83, %84, %85, %86, %87, %88, %89, %90, %91, %92, %93, %94, %95}, {%96, %97, %98, %99}, %100, p, 1, 1, %102;\n}\n"
    : "+f"(d[0]), "+f"(d[1]), "+f"(d[2]), "+f"(d[3]), "+f"(d[4]), "+f"(d[5]), "+f"(d[6]), "+f"(d[7]), "+f"(d[8]), "+f"(d[9]), "+f"(d[10]), "+f"(d[11]), "+f"(d[12]), "+f"(d[13]), "+f"(d[14]), "+f"(d[15]), "+f"(d[16]), "+f"(d[17]), "+f"(d[18]), "+f"(d[19]), "+f"(d[20]), "+f"(d[21]), "+f"(d[22]), "+f"(d[23]), "+f"(d[24]), "+f"(d[25]), "+f"(d[26]), "+f"(d[27]), "+f"(d[28]), "+f"(d[29]), "+f"(d[30]), "+f"(d[31]), "+f"(d[32]), "+f"(d[33]), "+f"(d[34]), "+f"(d[35]), "+f"(d[36]), "+f"(d[37]), "+f"(d[38]), "+f"(d[39]), "+f"(d[40]), "+f"(d[41]), "+f"(d[42]), "+f"(d[43]), "+f"(d[44]), "+f"(d[45]), "+f"(d[46]), "+f"(d[47]), "+f"(d[48]), "+f"(d[49]), "+f"(d[50]), "+f"(d[51]), "+f"(d[52]), "+f"(d[53]), "+f"(d[54]), "+f"(d[55]), "+f"(d[56]), "+f"(d[57]), "+f"(d[58]), "+f"(d[59]), "+f"(d[60]), "+f"(d[61]), "+f"(d[62]), "+f"(d[63]), "+f"(d[64]), "+f"(d[65]), "+f"(d[66]), "+f"(d[67]), "+f"(d[68]), "+f"(d[69]), "+f"(d[70]), "+f"(d[71]), "+f"(d[72]), "+f"(d[73]), "+f"(d[74]), "+f"(d[75]), "+f"(d[76]), "+f"(d[77]), "+f"(d[78]), "+f"(d[79]), "+f"(d[80]), "+f"(d[81]), "+f"(d[82]), "+f"(d[83]), "+f"(d[84]), "+f"(d[85]), "+f"(d[86]), "+f"(d[87]), "+f"(d[88]), "+f"(d[89]), "+f"(d[90]), "+f"(d[91]), "+f"(d[92]), "+f"(d[93]), "+f"(d[94]), "+f"(d[95])
    : "r"(a0), "r"(a1), "r"(a2), "r"(a3), "l"(db), "r"(scale_d), "n"(TB));
}

template<int TB, int TA = 0> __device__ __forceinline__ void wgmma_ss_n128(float (&d)[64], uint64_t da, uint64_t db, int scale_d) {
  asm volatile("{\n.reg .pred p;\nsetp.ne.b32 p, %66, 0;\n"
    "wgmma.mma_async.sync.aligned.m64n128k16.f32.bf16.bf16 {%0, %1, %2, %3, %4, %5, %6, %7, %8, %9, %10, %11, %12, %13, %14, %15, %16, %17, %18, %19, %20, %21, %22, %23, %24, %25, %26, %27, %28, %29, %30, %31, %32, %33, %34, %35, %36, %37, %38, %39, %40, %41, %42, %43, %44, %45, %46, %47, %48, %49, %50, %51, %52, %53, %54, %55, %56, %57, %58, %59, %60, %61, %62, %63}, %64, %65, p, 1, 1, %68, %67;\n}\n"
    : "+f"(d[0]), "+f"(d[1]), "+f"(d[2]), "+f"(d[3]), "+f"(d[4]), "+f"(d[5]), "+f"(d[6]), "+f"(d[7]), "+f"(d[8]), "+f"(d[9]), "+f"(d[10]), "+f"(d[11]), "+f"(d[12]), "+f"(d[13]), "+f"(d[14]), "+f"(d[15]), "+f"(d[16]), "+f"(d[17]), "+f"(d[18]), "+f"(d[19]), "+f"(d[20]), "+f"(d[21]), "+f"(d[22]), "+f"(d[23]), "+f"(d[24]), "+f"(d[25]), "+f"(d[26]), "+f"(d[27]), "+f"(d[28]), "+f"(d[29]), "+f"(d[30]), "+f"(d[31]), "+f"(d[32]), "+f"(d[33]), "+f"(d[34]), "+f"(d[35]), "+f"(d[36]), "+f"(d[37]), "+f"(d[38]), "+f"(d[39]), "+f"(d[40]), "+f"(d[41]), "+f"(d[42]), "+f"(d[43]), "+f"(d[44]), "+f"(d[45]), "+f"(d[46]), "+f"(d[47]), "+f"(d[48]), "+f"(d[49]), "+f"(d[50]), "+f"(d[51]), "+f"(d[52]), "+f"(d[53]), "+f"(d[54]), "+f"(d[55]), "+f"(d[56]), "+f"(d[57]), "+f"(d[58]), "+f"(d[59]), "+f"(d[60]), "+f"(d[61]), "+f"(d[62]), "+f"(d[63])
    : "l"(da), "l"(db), "r"(scale_d), "n"(TB), "n"(TA));
}

template<int TB, int TA = 0> __device__ __forceinline__ void wgmma_ss_n64(float (&d)[32], uint64_t da, uint64_t db, int scale_d) {
  asm volatile("{\n.reg .pred p;\nsetp.ne.b32 p, %34, 0;\n"
    "wgmma.mma_async.sync.aligned.m64n64k16.f32.bf16.bf16 {%0, %1, %2, %3, %4, %5, %6, %7, %8, %9, %10, %11, %12, %13, %14, %15, %16, %17, %18, %19, %20, %21, %22, %23, %24, %25, %26, %27, %28, %29, %30, %31}, %32, %33, p, 1, 1, %36, %35;\n}\n"
    : "+f"(d[0]), "+f"(d[1]), "+f"(d[2]), "+f"(d[3]), "+f"(d[4]), "+f"(d[5]), "+f"(d[6]), "+f"(d[7]), "+f"(d[8]), "+f"(d[9]), "+f"(d[10]), "+f"(d[11]), "+f"(d[12]), "+f"(d[13]), "+f"(d[14]), "+f"(d[15]), "+f"(d[16]), "+f"(d[17]), "+f"(d[18]), "+f"(d[19]), "+f"(d[20]), "+f"(d[21]), "+f"(d[22]), "+f"(d[23]), "+f"(d[24]), "+f"(d[25]), "+f"(d[26]), "+f"(d[27]), "+f"(d[28]), "+f"(d[29]), "+f"(d[30]), "+f"(d[31])
    : "l"(da), "l"(db), "r"(scale_d), "n"(TB), "n"(TA));
}

template<int TB> __device__ __forceinline__ void wgmma_rs_n40(float (&d)[20], uint32_t a0, uint32_t a1, uint32_t a2, uint32_t a3, uint64_t db, int scale_d) {
  asm volatile("{\n.reg .pred p;\nsetp.ne.b32 p, %25, 0;\n"
    "wgmma.mma_async.sync.aligned.m64n40k16.f32.bf16.bf16 {%0, %1, %2, %3, %4, %5, %6, %7, %8, %9, %10, %11, %12, %13, %14, %15, %16, %17, %18, %19}, {%20, %21, %22, %23}, %24, p, 1, 1, %26;\n}\n"
    : "+f"(d[0]), "+f"(d[1]), "+f"(d[2]), "+f"(d[3]), "+f"(d[4]), "+f"(d[5]), "+f"(d[6]), "+f"(d[7]), "+f"(d[8]), "+f"(d[9]), "+f"(d[10]), "+f"(d[11]), "+f"(d[12]), "+f"(d[13]), "+f"(d[14]), "+f"(d[15]), "+f"(d[16]), "+f"(d[17]), "+f"(d[18]), "+f"(d[19])
    : "r"(a0), "r"(a1), "r"(a2), "r"(a3), "l"(db), "r"(scale_d), "n"(TB));
}

#define DEVI __device__ __forceinline__
DEVI uint32_t smem_u32(const void* p) { return (uint32_t)__cvta_generic_to_shared(p); }
DEVI void mbar_init(uint32_t bar, uint32_t cnt) { asm volatile("mbarrier.init.shared::cta.b64 [%0], %1;" :: "r"(bar), "r"(cnt)); }
DEVI void mbar_expect_tx(uint32_t bar, uint32_t bytes) { asm volatile("mbarrier.arrive.expect_tx.shared::cta.b64 _, [%0], %1;" :: "r"(bar), "r"(bytes) : "memory"); }
DEVI void mbar_arrive(uint32_t bar) { asm volatile("mbarrier.arrive.shared::cta.b64 _, [%0];" :: "r"(bar) : "memory"); }
DEVI void mbar_arrive_peer(uint32_t bar) {
  asm volatile("{\n.reg .b32 ra;\nmapa.shared::cluster.u32 ra, %0, %1;\nmbarrier.arrive.shared::cluster.b64 _, [ra];\n}" :: "r"(bar), "r"((blockIdx.x & 1) ^ 1) : "memory");
}
DEVI void bulk_s2peer(uint32_t a, uint32_t bytes, uint32_t bar) {
  asm volatile("{\n.reg .b32 ra, rb;\nmapa.shared::cluster.u32 ra, %0, %3;\nmapa.shared::cluster.u32 rb, %2, %3;\n"
               "cp.async.bulk.shared::cluster.shared::cta.mbarrier::complete_tx::bytes [ra], [%0], %1, [rb];\n}"
               :: "r"(a), "r"(bytes), "r"(bar), "r"((blockIdx.x & 1) ^ 1) : "memory");
}
DEVI void mbar_wait(uint32_t bar, uint32_t parity) {
  asm volatile("{\n.reg .pred p;\nLW:\nmbarrier.try_wait.parity.shared::cta.b64 p, [%0], %1;\n@!p bra LW;\n}" :: "r"(bar), "r"(parity) : "memory");
}
DEVI uint32_t mbar_test(uint32_t bar, uint32_t parity) {
  uint32_t r; asm volatile("{\n.reg .pred p;\nmbarrier.test_wait.parity.shared::cta.b64 p, [%1], %2;\nselp.u32 %0, 1, 0, p;\n}" : "=r"(r) : "r"(bar), "r"(parity) : "memory"); return r;
}
DEVI void mbar_wait_b(uint32_t bar, uint32_t parity) {
  asm volatile("{\n.reg .pred p;\n.reg .u32 it;\nmov.u32 it, 0;\nLW:\nmbarrier.try_wait.parity.shared::cta.b64 p, [%0], %1;\n@p bra LD;\n"
               "add.u32 it, it, 1;\nsetp.lt.u32 p, it, 0x1000000;\n@p bra LW;\ntrap;\nLD:\n}" :: "r"(bar), "r"(parity) : "memory");
}
DEVI void tma_2d(uint32_t dst, const CUtensorMap* m, int c0, int c1, uint32_t bar) {
  asm volatile("cp.async.bulk.tensor.2d.shared::cluster.global.mbarrier::complete_tx::bytes [%0], [%1, {%3, %4}], [%2];"
    :: "r"(dst), "l"(m), "r"(bar), "r"(c0), "r"(c1) : "memory");
}
DEVI void tma_3d(uint32_t dst, const CUtensorMap* m, int c0, int c1, int c2, uint32_t bar) {
  asm volatile("cp.async.bulk.tensor.3d.shared::cluster.global.mbarrier::complete_tx::bytes [%0], [%1, {%3, %4, %5}], [%2];"
    :: "r"(dst), "l"(m), "r"(bar), "r"(c0), "r"(c1), "r"(c2) : "memory");
}
#define POL_EF POL_FIRST
constexpr uint64_t POL_FIRST = 0x12F0000000000000ull, POL_NORMAL = 0x1000000000000000ull;
DEVI void tma_2d_h(uint32_t dst, const CUtensorMap* m, int c0, int c1, uint32_t bar, uint64_t pol) {
  asm volatile("cp.async.bulk.tensor.2d.shared::cluster.global.mbarrier::complete_tx::bytes.L2::cache_hint [%0], [%1, {%3, %4}], [%2], %5;"
    :: "r"(dst), "l"(m), "r"(bar), "r"(c0), "r"(c1), "l"(pol) : "memory");
}
DEVI void tma_3d_h(uint32_t dst, const CUtensorMap* m, int c0, int c1, int c2, uint32_t bar, uint64_t pol) {
  asm volatile("cp.async.bulk.tensor.3d.shared::cluster.global.mbarrier::complete_tx::bytes.L2::cache_hint [%0], [%1, {%3, %4, %5}], [%2], %6;"
    :: "r"(dst), "l"(m), "r"(bar), "r"(c0), "r"(c1), "r"(c2), "l"(pol) : "memory");
}
DEVI void bulk_g2s_h(uint32_t s, const void* g, uint32_t bytes, uint32_t bar, uint64_t pol = POL_EF) {
  asm volatile("cp.async.bulk.shared::cluster.global.mbarrier::complete_tx::bytes.L2::cache_hint [%0], [%1], %2, [%3], %4;"
    :: "r"(s), "l"(g), "r"(bytes), "r"(bar), "l"(pol) : "memory");
}
DEVI void tma_5d(uint32_t dst, const CUtensorMap* m, int c0, int c1, int c2, int c3, int c4, uint32_t bar, uint64_t pol) {
  asm volatile("cp.async.bulk.tensor.5d.shared::cluster.global.mbarrier::complete_tx::bytes.L2::cache_hint [%0], [%1, {%3, %4, %5, %6, %7}], [%2], %8;"
    :: "r"(dst), "l"(m), "r"(bar), "r"(c0), "r"(c1), "r"(c2), "r"(c3), "r"(c4), "l"(pol) : "memory");
}
DEVI void tma_prefetch_2d(const CUtensorMap* m, int c0, int c1) {
  asm volatile("cp.async.bulk.prefetch.tensor.2d.L2.global.tile [%0, {%1, %2}];" :: "l"(m), "r"(c0), "r"(c1) : "memory");
}
DEVI void tma_prefetch_3d(const CUtensorMap* m, int c0, int c1, int c2) {
  asm volatile("cp.async.bulk.prefetch.tensor.3d.L2.global.tile [%0, {%1, %2, %3}];" :: "l"(m), "r"(c0), "r"(c1), "r"(c2) : "memory");
}
DEVI void bulk_prefetch(const void* g, uint32_t bytes) { asm volatile("cp.async.bulk.prefetch.L2.global [%0], %1;" :: "l"(g), "r"(bytes) : "memory"); }
DEVI void bulk_g2s(uint32_t s, const void* g, uint32_t bytes, uint32_t bar) {
  asm volatile("cp.async.bulk.shared::cluster.global.mbarrier::complete_tx::bytes [%0], [%1], %2, [%3];" :: "r"(s), "l"(g), "r"(bytes), "r"(bar) : "memory");
}
DEVI void bulk_s2g(void* g, uint32_t s, uint32_t bytes) {
  asm volatile("cp.async.bulk.global.shared::cta.bulk_group [%0], [%1], %2;\ncp.async.bulk.commit_group;" :: "l"(g), "r"(s), "r"(bytes) : "memory");
}
template<int N> DEVI void bulk_wait() { asm volatile("cp.async.bulk.wait_group %0;" :: "n"(N) : "memory"); }
DEVI void fence_async_smem() { asm volatile("fence.proxy.async.shared::cta;" ::: "memory"); }
DEVI void fence_async_glob() { asm volatile("fence.proxy.async.global;" ::: "memory"); }
DEVI unsigned ld_rlx(const unsigned* p) { unsigned v; asm volatile("ld.relaxed.gpu.global.u32 %0, [%1];" : "=r"(v) : "l"(p) : "memory"); return v; }
DEVI void st_rlx(unsigned* p, unsigned v) { asm volatile("st.relaxed.gpu.global.u32 [%0], %1;" :: "l"(p), "r"(v) : "memory"); }
DEVI uint2 ldg_stream(const uint2* p) { uint2 v; asm volatile("ld.global.nc.L1::no_allocate.v2.u32 {%0, %1}, [%2];" : "=r"(v.x), "=r"(v.y) : "l"(p)); return v; }
DEVI void fence_rel() { asm volatile("fence.release.gpu;" ::: "memory"); }
DEVI uint4 ld_ll(const uint4* p) {
  uint4 v;
  asm volatile("{\n.reg .b128 t;\n.reg .b64 a, b;\nld.relaxed.gpu.global.b128 t, [%4];\nmov.b128 {a, b}, t;\nmov.b64 {%0, %1}, a;\nmov.b64 {%2, %3}, b;\n}"
               : "=r"(v.x), "=r"(v.y), "=r"(v.z), "=r"(v.w) : "l"(p) : "memory");
  return v;
}
DEVI void st_ll(uint4* p, uint32_t x, uint32_t y, uint32_t z, uint32_t w) {
  asm volatile("{\n.reg .b128 t;\n.reg .b64 a, b;\nmov.b64 a, {%1, %2};\nmov.b64 b, {%3, %4};\nmov.b128 t, {a, b};\nst.relaxed.gpu.global.b128 [%0], t;\n}"
               :: "l"(p), "r"(x), "r"(y), "r"(z), "r"(w) : "memory");
}
#define SPIN_MAX 0x1000000
DEVI uint4 poll_ll(const uint4* p, uint32_t mask, uint32_t tag) {
  uint4 v; int it = 0;
  do { v = ld_ll(p); if (++it > SPIN_MAX) __trap(); } while (!__all_sync(0xffffffffu, (v.w & mask) == tag));
  return v;
}
DEVI void poll_ll2(const uint4* p, const uint4* q, uint32_t mask, uint32_t tag, uint4& a, uint4& b) {
  int it = 0;
  do { a = ld_ll(p); b = ld_ll(q); if (++it > SPIN_MAX) __trap(); } while (!__all_sync(0xffffffffu, (a.w & mask) == tag && (b.w & mask) == tag));
}
DEVI void bar_sync(int id, int n) { asm volatile("bar.sync %0, %1;" :: "r"(id), "r"(n) : "memory"); }
DEVI void bar_arrive(int id, int n) { asm volatile("bar.arrive %0, %1;" :: "r"(id), "r"(n) : "memory"); }
DEVI void wg_fence() { asm volatile("wgmma.fence.sync.aligned;" ::: "memory"); }
DEVI void wg_commit() { asm volatile("wgmma.commit_group.sync.aligned;" ::: "memory"); }
template<int N> DEVI void wg_wait() { asm volatile("wgmma.wait_group.sync.aligned %0;" :: "n"(N) : "memory"); }
template<int N> DEVI void reg_inc() { asm volatile("setmaxnreg.inc.sync.aligned.u32 %0;" :: "n"(N)); }
template<int N> DEVI void reg_dec() { asm volatile("setmaxnreg.dec.sync.aligned.u32 %0;" :: "n"(N)); }
DEVI float ex2f(float x) { float y; asm("ex2.approx.ftz.f32 %0, %1;" : "=f"(y) : "f"(x)); return y; }
DEVI uint32_t pack_bf16(float lo, float hi) { uint32_t r; asm("cvt.rn.bf16x2.f32 %0, %1, %2;" : "=r"(r) : "f"(hi), "f"(lo)); return r; }
DEVI float bf_lo(uint32_t v) { return __uint_as_float(v << 16); }
DEVI float bf_hi(uint32_t v) { return __uint_as_float(v & 0xffff0000u); }
DEVI float bf_round(float x) { return bf_lo(pack_bf16(x, 0.f)); }
DEVI void stsm_x4(uint32_t addr, uint32_t a, uint32_t b, uint32_t c, uint32_t d) {
  asm volatile("stmatrix.sync.aligned.m8n8.x4.shared.b16 [%0], {%1,%2,%3,%4};" :: "r"(addr), "r"(a), "r"(b), "r"(c), "r"(d) : "memory");
}
DEVI void ldsm_x4(uint32_t addr, uint32_t& a, uint32_t& b, uint32_t& c, uint32_t& d) {
  asm volatile("ldmatrix.sync.aligned.m8n8.x4.shared.b16 {%0,%1,%2,%3}, [%4];" : "=r"(a), "=r"(b), "=r"(c), "=r"(d) : "r"(addr) : "memory");
}
DEVI uint4 lds128(uint32_t a) { uint4 v; asm volatile("ld.shared.v4.u32 {%0,%1,%2,%3}, [%4];" : "=r"(v.x), "=r"(v.y), "=r"(v.z), "=r"(v.w) : "r"(a) : "memory"); return v; }
DEVI void sts128(uint32_t a, uint4 v) { asm volatile("st.shared.v4.u32 [%0], {%1,%2,%3,%4};" :: "r"(a), "r"(v.x), "r"(v.y), "r"(v.z), "r"(v.w) : "memory"); }
DEVI float2 lds64f(uint32_t a) { float2 v; asm volatile("ld.shared.v2.f32 {%0,%1}, [%2];" : "=f"(v.x), "=f"(v.y) : "r"(a) : "memory"); return v; }
DEVI void sts64f(uint32_t a, float x, float y) { asm volatile("st.shared.v2.f32 [%0], {%1,%2};" :: "r"(a), "f"(x), "f"(y) : "memory"); }
DEVI uint32_t lds32(uint32_t a) { uint32_t v; asm volatile("ld.shared.u32 %0, [%1];" : "=r"(v) : "r"(a) : "memory"); return v; }
DEVI float lds32f(uint32_t a) { return __uint_as_float(lds32(a)); }
DEVI void sts32(uint32_t a, uint32_t v) { asm volatile("st.shared.u32 [%0], %1;" :: "r"(a), "r"(v) : "memory"); }
DEVI void sts32f(uint32_t a, float v) { sts32(a, __float_as_uint(v)); }
DEVI void sts16(uint32_t a, uint32_t v) { asm volatile("st.shared.u16 [%0], %1;" :: "r"(a), "h"((unsigned short)v) : "memory"); }
template<int N> DEVI void keep(float (&d)[N]) {
  #pragma unroll
  for (int i = 0; i < N; i++) asm volatile("" : "+f"(d[i]) :: "memory");
}
template<int N> DEVI void keep(uint32_t (&d)[N]) {
  #pragma unroll
  for (int i = 0; i < N; i++) asm volatile("" : "+r"(d[i]) :: "memory");
}
template<uint32_t HI> DEVI uint64_t mkd(uint32_t lo) { uint64_t r; asm("mov.b64 %0, {%1, %2};" : "=l"(r) : "r"(lo), "n"(HI)); return r; }
constexpr uint32_t HI128 = (1u << 30) | (1024 >> 4), HI64 = (2u << 30) | (512 >> 4);
#define VOFF(x) ((uint32_t)(x) * (uint32_t)(1 - 65536))
DEVI bool elect() { uint32_t p; asm volatile("{\n.reg .pred q;\nelect.sync _|q, 0xffffffff;\nselp.u32 %0, 1, 0, q;\n}" : "=r"(p)); return p; }
DEVI void warp_signal(uint32_t bar) { __syncwarp(); if (elect()) mbar_arrive(bar); }

struct Scratch {
  uint4 kv[128][4][1024];
  uint4 o[8][2][8][2][1024];
  uint4 x[8][16][2048];
  uint4 zero[1024];
  uint4 statP[8][2048];
  uint4 statF[2048];
  uint4 csP[16][8][96];
  uint4 best[8][16];
  uint4 row[16][256];
  uint4 yP[128][112][2];
  uint4 x2[8][256];
  uint4 patch[1024];
  unsigned flagKV[128][32];
  unsigned flagO[8][2][2][32];
  unsigned flagX[8][32];
  unsigned epoch;
};
static_assert(offsetof(Scratch, flagO) % 256 == 0, "");
__device__ __align__(1024) Scratch g_scr;
#define PROFT(cond, slot)
#define PROFW(cond, slot)
#define PROFD(cond, slot)
#define PROFX(cond, slot)
#define PROFY(cond, slot)

constexpr uint32_t SB0 = 65536, HOLE = 90112, SA2 = 98304, SB1 = 131072, SB2 = 155648, STG = 180224;
constexpr uint32_t KVA = 98304, KVB = 0, QO = 65536;
constexpr uint32_t MISC = 229376, CS = MISC, ONES = MISC + 768, BARS = MISC + 1792, INFO = MISC + 2208, WR = MISC + 2224, X2SEG = MISC + 2736, INFO2 = MISC + 2992;
constexpr uint32_t PAR = HOLE, HV = HOLE + 2048, RED = HOLE + 6144, PATCH = 196608;
constexpr uint32_t SMEM_BYTES = 232448;
enum { B_FULLQ = 0, B_EMPTYQ = 3, B_FULLW = 6, B_EMPTYW = 12, B_HAFREE = 18, B_OFREE = 20,
       B_XFREE = 21,
       B_KVRDY = 23, B_ORDY = 27, B_XRDY = 35, B_STGE = 39,
       B_KVFULL = 42, B_RES = 46, B_PAR = 47, B_STG = 48, B_PFREE = 51, B_COUNT = 52 };
#define BAR(x) (sb + BARS + 8 * (x))
DEVI uint32_t qa_off(int s) { return s == 2 ? SA2 : (uint32_t)s * 32768u; }
DEVI uint32_t qb_off(int s) { return s == 0 ? SB0 : (s == 1 ? SB1 : SB2); }
DEVI int kb_order(int bc, int n) {
  const int e = n < 9 ? n - 2 : n - 9;
  return n < 2 ? 2 * bc + n : 2 * (((e < 4 ? e + 4 : e - 4 + (e - 4 >= (bc & 3))) + (bc & 4)) & 7) + (n >= 9);
}
DEVI uint32_t w_off(int s) { return (uint32_t)((0x104365 >> (4 * s)) & 7) * 32768u; }
DEVI uint32_t w_par(int n, int s, int L) { return ((n >= 6 && n < 12) ^ (s < 4 && L)); }

struct Params {
  CUtensorMap mX, mXh, mWq, mWo, mWg, mWu, mWp, mWd;
  const bf16 *x0, *wqkv, *wo, *wr, *wg, *wu, *wd;
  bf16* out;
  Scratch* g;
  unsigned map[128];
};
#define BID ((int)(P.map[blockIdx.x] & 255))
#define FID ((int)(P.map[blockIdx.x] >> 8))
DEVI uint32_t uni(uint32_t v) { return __shfl_sync(0xffffffffu, v, 0); }
#define PQ_N 8
#define PQ_T 700
#define PF0_N 10
#define PF0_T 1600
#define PF1_E 24
#define PF1_T 1100
#define POL_Q1 POL_NORMAL
#define POL_X POL_NORMAL
#define PFA0_BAR 3
#define PFA1_BAR 0
#define PFA0_M 0
#define PFA1_M 0
#define PFA0_T 900
#define PFA1_T 700
#define PF1_S PF0_N
#define PF1_D 0
#define POL_G POL_NORMAL
#define POL_U POL_FIRST
#define POL_D POL_FIRST
#define JQ_N 6
#define WDSRC (P.wd + (size_t)min(fid, 111) * 32768)
#define WD_N 4
#define THR_N 6
#define KV_D 1600
#define XD_D 600
#define W0_BAR 3
#define POL_Q0 POL_NORMAL
constexpr float LN_EPS = 1e-5f;
constexpr float QSCALE = 0.17677669529663687f * 1.4426950408889634f;

DEVI void fma8(float (&a)[8], uint4 v, float h) {
  a[0] = fmaf(bf_lo(v.x), h, a[0]); a[1] = fmaf(bf_hi(v.x), h, a[1]); a[2] = fmaf(bf_lo(v.y), h, a[2]); a[3] = fmaf(bf_hi(v.y), h, a[3]);
  a[4] = fmaf(bf_lo(v.z), h, a[4]); a[5] = fmaf(bf_hi(v.z), h, a[5]); a[6] = fmaf(bf_lo(v.w), h, a[6]); a[7] = fmaf(bf_hi(v.w), h, a[7]);
}
DEVI void gemv8(float (&a)[8], uint32_t wa, uint32_t ha, uint32_t hs) {
  #pragma unroll
  for (int n = 0; n < 8; n += 2) {
    uint4 v0 = lds128(wa + n * 512), v1 = lds128(wa + n * 512 + 512);
    float h0 = lds32f(ha), h1 = lds32f(ha + hs);
    ha += 2 * hs;
    fma8(a, v0, h0); fma8(a, v1, h1);
  }
}
DEVI uint4 ldsv128(uint32_t a) { uint4 v; asm volatile("ld.volatile.shared.v4.u32 {%0,%1,%2,%3}, [%4];" : "=r"(v.x), "=r"(v.y), "=r"(v.z), "=r"(v.w) : "r"(a) : "memory"); return v; }
DEVI float ldsv32f(uint32_t a) { float v; asm volatile("ld.volatile.shared.f32 %0, [%1];" : "=f"(v) : "r"(a) : "memory"); return v; }
DEVI uint32_t clk() { uint32_t t; asm volatile("mov.u32 %0, %%clock;" : "=r"(t)); return t; }
DEVI int fresh_tid() { int t; asm volatile("mov.u32 %0, %%tid.x;" : "=r"(t)); return t & 127; }
DEVI float fold8(const float (&a)[8]) {
  const int lane = threadIdx.x & 31;
  const bool u = lane & 16, v = lane & 8, x = lane & 4;
  float b0 = (u ? a[4] : a[0]) + __shfl_xor_sync(0xffffffffu, u ? a[0] : a[4], 16), b1 = (u ? a[5] : a[1]) + __shfl_xor_sync(0xffffffffu, u ? a[1] : a[5], 16);
  float b2 = (u ? a[6] : a[2]) + __shfl_xor_sync(0xffffffffu, u ? a[2] : a[6], 16), b3 = (u ? a[7] : a[3]) + __shfl_xor_sync(0xffffffffu, u ? a[3] : a[7], 16);
  float c0 = (v ? b2 : b0) + __shfl_xor_sync(0xffffffffu, v ? b0 : b2, 8), c1 = (v ? b3 : b1) + __shfl_xor_sync(0xffffffffu, v ? b1 : b3, 8);
  return (x ? c1 : c0) + __shfl_xor_sync(0xffffffffu, x ? c0 : c1, 4);
}
DEVI float swiglu(float g, float u) { g = bf_round(g); return bf_round(bf_round(__fdividef(g, 1.f + __expf(-g))) * bf_round(u)); }

DEVI void qk_issue(float (&s)[32], uint32_t qd, uint32_t kd) {
  wgmma_ss_n64<0>(s, mkd<HI64>(qd), mkd<HI64>(kd), 0);
  wgmma_ss_n64<0>(s, mkd<HI64>(qd + 2), mkd<HI64>(kd + 2), 1);
}
DEVI void pv_issue(float (&o)[20], const uint32_t (&p)[16], uint32_t vd, bool accum) {
  #pragma unroll
  for (int ks = 0; ks < 4; ks++)
    wgmma_rs_n40<1>(o, p[ks * 4], p[ks * 4 + 1], p[ks * 4 + 2], p[ks * 4 + 3], mkd<HI64>(vd + VOFF(ks * 64)), ks ? 1 : accum);
}
template<int J0, int J1> DEVI void exp_pack(const float (&s)[32], uint32_t (&p)[16]) {
  #pragma unroll
  for (int j = J0; j < J1; j++) p[j] = pack_bf16(ex2f(s[2 * j]), ex2f(s[2 * j + 1]));
}
DEVI bool attn_pack(const float (&o)[20], uint32_t (&ob)[8]) {
  const float lo = 5.421010862427522e-20f, hi = 1.8446744073709552e19f;
  float i0, i1; asm("rcp.approx.ftz.f32 %0, %1;" : "=f"(i0) : "f"(o[16])); asm("rcp.approx.ftz.f32 %0, %1;" : "=f"(i1) : "f"(o[18]));
  #pragma unroll
  for (int e = 0; e < 8; e++) ob[e] = pack_bf16(o[2 * e] * ((e & 1) ? i1 : i0), o[2 * e + 1] * ((e & 1) ? i1 : i0));
  return __all_sync(0xffffffffu, o[16] >= lo && o[16] <= hi && o[18] >= lo && o[18] <= hi);
}
DEVI void attn_store(const uint32_t (&ob)[8], uint32_t st, uint32_t bar) {
  stsm_x4(st, ob[0], ob[1], ob[2], ob[3]); stsm_x4(st ^ 32, ob[4], ob[5], ob[6], ob[7]);
  warp_signal(bar);
}
DEVI void attn_exact(uint32_t st, uint32_t kv, int t, bool hasprev, uint32_t bar) {
  const int lane = threadIdx.x & 31;
  #pragma unroll 1
  for (int row = ((threadIdx.x >> 5) & 3) * 16, n = 0; n < 16; n++, row++) {
    const int k1 = 256 + t * 64 + row;
    float m = -INFINITY, l = 0.f, o = 0.f;
    #pragma unroll 1
    for (int k0 = hasprev ? k1 - 255 : 256; k0 <= k1; k0 += 32) {
      const int k = min(k0 + lane, k1), r = k & 63;
      float sc = 0.f;
      #pragma unroll 1
      for (int c = 0; c < 16; c++) {
        uint32_t a = lds32(st + row * 64 + ((c * 4) ^ ((row & 6) << 3))), b = lds32(kv + (k >> 6) * 8192 + r * 64 + ((c * 4) ^ ((r & 6) << 3)));
        sc = fmaf(bf_lo(a), bf_lo(b), fmaf(bf_hi(a), bf_hi(b), sc));
      }
      float mn = fmaxf(m, sc);
      #pragma unroll 1
      for (int x = 16; x; x >>= 1) mn = fmaxf(mn, __shfl_xor_sync(0xffffffffu, mn, x));
      const float al = ex2f(m - mn), pr = ex2f(sc - mn);
      m = mn; l *= al; o *= al;
      #pragma unroll 1
      for (int q = k0; q <= min(k0 + 31, k1); q++) {
        const float z = __shfl_sync(0xffffffffu, pr, q - k0);
        uint32_t b = lds32(kv + (q >> 6) * 8192 + 4096 + (q & 63) * 64 + (((lane >> 1) * 4) ^ ((q & 6) << 3)));
        l += z; o = fmaf(z, (lane & 1) ? bf_hi(b) : bf_lo(b), o);
      }
    }
    __syncwarp();
    sts16(st + row * 64 + ((lane * 2) ^ ((row & 6) << 3)), pack_bf16(__fdividef(o, l), 0.f));
  }
  warp_signal(bar);
}

DEVI void merge_tri(float (&s)[32], const float (&sx)[32], int tdiag) {
  #pragma unroll
  for (int e = 0; e < 32; e++) { int c = 8 * (e >> 2) + (e & 1) - 8 * ((e >> 1) & 1); s[e] = (c > tdiag) ? s[e] : sx[e]; }
}
DEVI void split_tri(uint32_t (&p)[16], uint32_t (&px)[16], const uint32_t (&msk)[9]) {
  #pragma unroll
  for (int e = 0; e < 16; e++) { const uint32_t m = msk[(e >> 1) - (e & 1) + 1]; px[e] = p[e] & ~m; p[e] &= m; }
}

template<int J0> DEVI void qkv_store(const float (&a)[96], float p0, float p1, uint32_t d) {
  #pragma unroll
  for (int hh = 0; hh < 2; hh++) {
    const int j = 4 * (J0 + 2 * hh);
    stsm_x4(d ^ (hh << 5), pack_bf16(a[j] * p0, a[j + 1] * p0), pack_bf16(a[j + 2] * p1, a[j + 3] * p1),
                           pack_bf16(a[j + 4] * p0, a[j + 5] * p0), pack_bf16(a[j + 6] * p1, a[j + 7] * p1));
  }
}
DEVI void mean_step(float (&a)[96], float m0, float m1, uint32_t cd, bool z) {
  const uint32_t u0 = z ? 0u : __float_as_uint(m0), u1 = z ? 0u : __float_as_uint(m1);
  uint32_t ma[4] = {__byte_perm(u0, 0u, 0x1010), __byte_perm(u1, 0u, 0x1010), __byte_perm(u0, 0u, 0x3232), __byte_perm(u1, 0u, 0x3232)};
  keep(ma);
  wg_fence();
  wgmma_rs_n192<1>(a, ma[0], ma[1], ma[2], ma[3], mkd<2>(cd), 1);
  wg_commit();
}

template<bool FIRST> DEVI void qkv_block(float (&aX)[96], float (&aY)[96], uint32_t sb16, int s, int tX, int tY) {
  uint32_t a16 = sb16 + (qa_off(s) >> 4), b16 = (sb16 + (qb_off(s) >> 4)) | ((8192u >> 4) << 16);
  uint32_t ax = (a16 + tX * 512) | 0x10000u, ay = (a16 + tY * 512) | 0x10000u;
  wg_fence();
  #pragma unroll
  for (int ks = 0; ks < 4; ks++) {
    wgmma_ss_n192<1>(aX, mkd<HI128>(ax + ks * 2), mkd<HI128>(b16 + ks * 128), !(FIRST && ks == 0));
    wgmma_ss_n192<1>(aY, mkd<HI128>(ay + ks * 2), mkd<HI128>(b16 + ks * 128), !(FIRST && ks == 0));
  }
  wg_commit();
}
template<bool FIRST> DEVI void wo_block(float (&acc)[64], uint32_t sb16, int s, int wg) {
  uint32_t a16 = (sb16 + (w_off(s) >> 4) + wg * 256) | 0x10000u, b16 = (sb16 + (w_off(s) >> 4) + 1024) | ((8192u >> 4) << 16);
  wg_fence();
  #pragma unroll
  for (int ks = 0; ks < 4; ks++)
    wgmma_ss_n128<1>(acc, mkd<HI64>(a16 + (ks >> 1) * 512 + (ks & 1) * 2), mkd<HI128>(b16 + ks * 128), !(FIRST && ks == 0));
  wg_commit();
}
DEVI void consumer(const Params& P, uint32_t sb, int wg) {
  const int w = uni((threadIdx.x >> 5) & 3);
  #define LAYER uni(mbar_test(BAR(B_RES), 0))
  #define IDS L = LAYER; const int tid = fresh_tid(), lane = tid & 31
  const uint32_t ids = uni(P.map[blockIdx.x]);
  const int bi = (ids >> 4) & 7, rh = ids & 1, bc = (ids & 15) >> 1, fid = ids >> 8;
  const int tX = 3 - wg, tY = wg;
  constexpr uint32_t sb16 = 1024 >> 4;
  #pragma unroll 1
  while (true) {
    int L = LAYER;
    {
      float aX[96], aY[96];
      const bool lead = fresh_tid() == 0;
      if (L) mbar_wait(BAR(B_XRDY + wg * 2 + 1), 0);
      mbar_wait(BAR(B_FULLQ), 0);
      PROFW(threadIdx.x == 0, L * 8 + 1);
      qkv_block<true>(aX, aY, sb16, 0, tX, tY);
      #pragma unroll 1
      for (int n = 1, s = 1, ps = 0, ph = 0; n < 16; n++) {
        mbar_wait(BAR(B_FULLQ + s), ph ^ (s ? L : 0));
        PROFD(threadIdx.x == 0 && L && (n == 2 || n == 3 || n == 7 || n == 11 || n == 15), n == 2 ? 48 : 49 + (n >> 2));
        qkv_block<false>(aX, aY, sb16, s, tX, tY);
        wg_wait<1>(); if (lead) mbar_arrive(BAR(B_EMPTYQ + ps));
        ps = s; if (s == 2) { s = 0; ph ^= 1; } else s++;
      }
      mbar_wait(BAR(B_PAR), L);
      IDS;
      const uint32_t pa = sb + PAR + (w * 16 + (lane >> 2)) * 8;
      float2 p0 = lds64f(pa + tX * 512), p1 = lds64f(pa + tX * 512 + 64), p2 = lds64f(pa + tY * 512), p3 = lds64f(pa + tY * 512 + 64);
      mean_step(aX, p0.y, p1.y, sb16 + (CS >> 4), lane & 3);
      const int prow = (int)uni(lds32(sb + INFO)) - bi * 256;
      const bool pmine = (prow >> 4) == tX * 4 + w || (prow >> 4) == tY * 4 + w;
      mbar_wait(BAR(B_EMPTYQ + 1), L); mbar_wait(BAR(B_EMPTYQ + 2), L);
      wg_wait<0>(); keep(aX); keep(aY);
      mean_step(aY, p2.y, p3.y, sb16 + (CS >> 4), fresh_tid() & 3);
      if (tid == 0) mbar_arrive(BAR(B_EMPTYQ));
      PROFW(threadIdx.x == 0, L * 8 + 2);
      PROFD(threadIdx.x == 128 && !L, 47);
      const int srow = w * 16 + (lane & 15);
      const uint32_t x0 = sb + srow * 64 + (((lane >> 4) ^ ((srow >> 1) & 3)) << 4), xX = x0 + (4 + tX) * 8192, xY = x0 + (4 + tY) * 8192;
      qkv_store<8>(aX, p0.x, p1.x, xX + KVA); qkv_store<16>(aX, p0.x, p1.x, xX + KVA + 4096);
      const int l3 = fresh_tid() & 3;
      const uint32_t poff = sb + (prow & 63) * 64 + ((l3 ^ ((prow >> 1) & 3)) << 4);
      if (pmine) { __syncwarp(); if (lane < 8) sts128(poff + KVA + (4 + (prow >> 6)) * 8192 + (lane >> 2) * 4096, lds128(sb + PATCH + 128 + (lane >> 2) * 128 + l3 * 16)); }
      warp_signal(BAR(B_KVRDY + wg * 2));
      wg_wait<0>(); keep(aY);
      qkv_store<8>(aY, p2.x, p3.x, xY + KVA); qkv_store<16>(aY, p2.x, p3.x, xY + KVA + 4096);
      qkv_store<12>(aX, p0.x, p1.x, xX + KVB); qkv_store<20>(aX, p0.x, p1.x, xX + KVB + 4096);
      qkv_store<12>(aY, p2.x, p3.x, xY + KVB); qkv_store<20>(aY, p2.x, p3.x, xY + KVB + 4096);
      p0.x *= QSCALE; p1.x *= QSCALE; p2.x *= QSCALE; p3.x *= QSCALE;
      mbar_wait(BAR(B_EMPTYQ), 1);
      qkv_store<0>(aX, p0.x, p1.x, x0 + QO + tX * 4096); qkv_store<4>(aX, p0.x, p1.x, x0 + QO + 16384 + tX * 4096);
      qkv_store<0>(aY, p2.x, p3.x, x0 + QO + tY * 4096); qkv_store<4>(aY, p2.x, p3.x, x0 + QO + 16384 + tY * 4096);
      if (pmine) {
        __syncwarp();
        if (lane < 24) sts128(poff + (lane < 8 ? QO + (lane >> 2) * 16384 + (prow >> 6) * 4096 : ((lane & 4) ? KVB : KVA) + (4 + (prow >> 6)) * 8192 + (lane >> 4) * 4096),
                              lds128(sb + PATCH + lane * 16));
      }
      fence_async_smem();
      warp_signal(BAR(B_KVRDY + wg * 2 + 1));
      bar_sync(1, 256);
    }
    PROFW(threadIdx.x == 0, L * 8 + 3);
    {
      IDS;
      float s0[32], s1[32], sx[32], o[20], op[20];
      uint32_t p0[16], p1[16], px[16], msk[9];
      const int tdiag = w * 16 + (lane >> 2) - 2 * (lane & 3);
      #pragma unroll
      for (int e = 0; e < 9; e++) msk[e] = ((8 * e - 8 > tdiag) ? 0xFFFFu : 0u) | ((8 * e - 7 > tdiag) ? 0xFFFF0000u : 0u);
      keep(msk);
      const uint32_t ones = (sb16 + (ONES >> 4)) << 16;
      const uint32_t qX = (sb16 + (QO >> 4) + tX * 256) | 0x10000u, qY = (sb16 + (QO >> 4) + tY * 256) | 0x10000u;
      const uint32_t kXB = (sb16 + (KVB >> 4) + tX * 512) | 0x10000u;
      uint32_t redo = 0;
      const uint32_t ost = sb + QO + (w * 16 + (lane & 15)) * 64 + (((lane >> 4) ^ ((lane >> 1) & 3)) << 4);
      #define QK2(q, k) do { qk_issue(s1, q, k); qk_issue(sx, q, (k) + 2048); } while (0)
      #define PV(o, p, v, b, acc) pv_issue(o, p, (v) + VOFF((b) * 512), acc)
      #define PV2(v0, v4) do { pv_issue(o, p1, v0, true); pv_issue(o, px, (v4) + VOFF(2048), true); } while (0)
      {
        const uint32_t kXA = kXB + ((KVA - KVB) >> 4), vB = VOFF((kXB & 0xffffu) + 256) + ones, vA = vB + VOFF((KVA - KVB) >> 4);
        wg_fence(); qk_issue(s0, qX, kXA + 1536); wg_commit(); qk_issue(s1, qX, kXA + 1024); wg_commit();
        wg_wait<1>(); keep(s0);
        exp_pack<0, 16>(s0, p0);
        wg_wait<0>(); keep(s1); keep(p0);
        wg_fence(); qk_issue(s0, qX + 1024, kXB + 1536); PV(o, p0, vA, 3, false); wg_commit();
        exp_pack<0, 16>(s1, p1);
        wg_wait<0>(); keep(s0); keep(o); keep(p0); keep(p1);
        wg_fence(); qk_issue(s1, qX + 1024, kXB + 1024); PV(o, p1, vA, 2, true); wg_commit();
        exp_pack<0, 16>(s0, p0);
        wg_wait<0>(); keep(s1); keep(o); keep(p0); keep(p1);
        wg_fence(); PV(op, p0, vB, 3, false); wg_commit();
        exp_pack<0, 16>(s1, p1); keep(p1);
        mbar_wait(BAR(B_KVFULL), L);
        wg_fence(); qk_issue(s0, qX, kXA + 512); PV(op, p1, vB, 2, true); wg_commit();
        wg_wait<0>(); keep(s0); keep(op); keep(p0); keep(p1);
      }
      #pragma unroll 1
      for (int h = 0; h < 2; h++) {
        const uint32_t kb16 = sb16 + ((h ? KVB : KVA) >> 4), kX = (kb16 + tX * 512) | 0x10000u, kY = (kb16 + tY * 512) | 0x10000u;
        const uint32_t qx = qX + h * 1024, qy = qY + h * 1024;
        const uint32_t onesP = bi ? ones : (kb16 + 1984) << 16;
        const uint32_t vX = VOFF(kb16 + tX * 512 + 256), vY = VOFF(kb16 + tY * 512 + 256);
        uint32_t ob[8];
        wg_fence(); QK2(qx, kX); wg_commit();
        exp_pack<0, 16>(s0, p0);
        wg_wait<0>(); keep(s1); keep(sx); keep(p0);
        wg_fence(); qk_issue(s0, qy, kY + 1536); PV(o, p0, vX + (wg ? onesP : ones), 1, true); wg_commit();
        merge_tri(s1, sx, tdiag); exp_pack<0, 16>(s1, p1); split_tri(p1, px, msk);
        wg_wait<0>(); keep(s0); keep(o); keep(p0); keep(p1); keep(px);
        wg_fence(); qk_issue(s1, qy, kY + 1024); PV2(vX + onesP, vX + ones); wg_commit();
        exp_pack<0, 16>(s0, p0);
        mbar_wait(BAR(B_KVFULL + h * 2 + 1), L);
        wg_wait<0>(); keep(s1); keep(o); keep(p0); keep(p1); keep(px);
        wg_fence(); qk_issue(s0, qy, kY + 512); wg_commit();
        bool ok = attn_pack(o, ob); keep(ob);
        wg_fence(); PV(o, p0, vY + (wg ? ones : onesP), 3, false); wg_commit();
        exp_pack<0, 16>(s1, p1);
        if (ok) attn_store(ob, ost + (h * 4 + tX) * 4096, BAR(B_ORDY + wg * 4 + h * 2)); else redo |= 1u << (h * 2);
        wg_wait<0>(); keep(s0); keep(o); keep(p0); keep(p1);
        wg_fence(); QK2(qy, kY); PV(o, p1, vY + onesP, 2, true); wg_commit();
        exp_pack<0, 16>(s0, p0);
        wg_wait<0>(); keep(s1); keep(sx); keep(o); keep(p0); keep(p1);
        wg_fence(); PV(o, p0, vY + onesP, 1, true); wg_commit();
        merge_tri(s1, sx, tdiag); exp_pack<0, 16>(s1, p1); split_tri(p1, px, msk); keep(p1); keep(px);
        mbar_wait(BAR(B_KVFULL + 2), L);
        wg_fence(); PV2(vY + onesP, vY + ones); wg_commit();
        qk_issue(s0, h ? qy : qX + 1024, kXB + 512); wg_commit();
        wg_wait<1>(); keep(o); keep(p0); keep(p1); keep(px);
        ok = attn_pack(o, ob);
        wg_wait<0>(); keep(s0);
        if (ok) attn_store(ob, ost + (h * 4 + tY) * 4096, BAR(B_ORDY + wg * 4 + h * 2 + 1)); else redo |= 2u << (h * 2);
        #pragma unroll
        for (int e = 0; e < 20; e++) o[e] = op[e];
      }
      #undef QK2
      #undef PV
      #undef PV2
      if (redo) {
        #pragma unroll 1
        for (int u = 0; u < 4; u++) if ((redo >> u) & 1) {
          const int h = u >> 1, t = (u & 1) ? tY : tX;
          attn_exact(sb + QO + (h * 4 + t) * 4096, sb + (h ? KVB : KVA), t, bi > 0, BAR(B_ORDY + wg * 4 + u));
        }
      }
    }
    PROFW(threadIdx.x == 0, L * 8 + 4);
    {
      IDS;
      const int t256 = wg * 128 + tid;
      float acc[64];
      const int tt = wg ^ rh;
      const int grow = bi * 256 + rh * 128 + tt * 64 + w * 16 + (lane >> 2);
      float al0 = 1.f, be0 = 0.f, al1 = 1.f, be1 = 0.f;
      const int idx0 = (int)uni(lds32(sb + INFO));
      const uint32_t tag = lds32(sb + INFO + 8) + L;
      uint4* const sp = &P.g->statP[bc][grow + (lane & 1) * 8];
      uint4* const yp = &P.g->yP[t256 >> 1][min(fid, 111)][t256 & 1];
      mbar_wait(BAR(B_FULLW), L);
      PROFW(t256 == 0, L * 8 + 5);
      wo_block<true>(acc, sb16, 0, tt);
      if (!(lane & 2)) st_ll(sp, 0u, 0u, 0u, 0u);
      uint4 fa = make_uint4(0u, 0u, 0u, 0u), fb = fa;
      uint2 wd[32];
      if (L) {
        if (fid < 112) st_ll(yp, 0u, 0u, 0u, 0u);
        fa = ld_ll(&P.g->statF[grow]); fb = ld_ll(&P.g->statF[grow + 8]);
      }
      #pragma unroll
      for (int n = 0; n < 32; n++) wd[n] = make_uint2(0u, 0u);
      #pragma unroll 1
      for (int n = 1, q = 1, pq = 0; n < 16; n++) {
        mbar_wait(BAR(B_FULLW + q), w_par(n, q, L));
        PROFD(t256 == 0 && !L && (n == 4 || n == 7 || n == 8 || n == 12), (n == 7 ? 63 : 41 + (n >> 2)));
        wo_block<false>(acc, sb16, q, tt);
        if (L && n == WD_N) {
          const uint2* src = (const uint2*)(WDSRC) + t256;
          #pragma unroll
          for (int e = 0; e < 32; e++) wd[e] = ldg_stream(src + e * 256);
        }
        wg_wait<1>(); if (tid == 0) mbar_arrive(BAR(B_EMPTYW + pq));
        pq = q; q = q == 5 ? 0 : q + 1;
      }
      if (L) {
        float r0 = rsqrtf(__uint_as_float(fa.y) + LN_EPS), r1 = rsqrtf(__uint_as_float(fb.y) + LN_EPS);
        if (grow != idx0) { al0 = 1.f + r0; be0 = -__uint_as_float(fa.x) * r0; }
        if (grow + 8 != idx0) { al1 = 1.f + r1; be1 = -__uint_as_float(fb.x) * r1; }
      }
      mbar_wait(BAR(B_RES), L);
      const int srow = tt * 64 + w * 16 + (lane & 15);
      const uint32_t ra = sb + rh * 16384 + srow * 128, sw = ((lane >> 4) ^ (srow & 7)) << 4;
      if ((idx0 >> 4) == bi * 16 + rh * 8 + tt * 4 + w) {
        int r = idx0 & 127;
        if (lane < 16) sts128(sb + (lane >> 3) * 32768 + rh * 16384 + r * 128 + (((lane & 7) ^ (r & 7)) << 4), lds128(sb + X2SEG + lane * 16));
        __syncwarp();
      }
      uint32_t rs[32];
      #pragma unroll
      for (int jj = 0; jj < 8; jj++) ldsm_x4((ra + (jj >> 2) * 32768) + (sw ^ ((jj & 3) << 5)), rs[4 * jj], rs[4 * jj + 1], rs[4 * jj + 2], rs[4 * jj + 3]);
      float rf[64];
      #pragma unroll
      for (int e = 0; e < 32; e++) { rf[2 * e] = fmaf(bf_lo(rs[e]), (e & 1) ? al1 : al0, (e & 1) ? be1 : be0); rf[2 * e + 1] = fmaf(bf_hi(rs[e]), (e & 1) ? al1 : al0, (e & 1) ? be1 : be0); }
      keep(rf);
      mbar_wait(BAR(B_RES), L);
      wg_wait<0>(); keep(acc);
      if (tid == 0) mbar_arrive(BAR(B_EMPTYW + 3));
      PROFW(t256 == 0, L * 8 + 6);
      #pragma unroll
      for (int jj = 0; jj < 8; jj++) {
        float* a = acc + 8 * jj;
        #pragma unroll
        for (int e = 0; e < 8; e++) a[e] += rf[8 * jj + e];
        stsm_x4((ra + (jj >> 2) * 32768) + (sw ^ ((jj & 3) << 5)), pack_bf16(a[0], a[1]), pack_bf16(a[2], a[3]), pack_bf16(a[4], a[5]), pack_bf16(a[6], a[7]));
        if (jj == 7) fence_async_smem();
        if ((jj & 3) == 3) warp_signal(BAR(B_XRDY + wg * 2 + (jj >> 2)));
      }
      {
        float s1a = 0.f, s2a = 0.f, da = 0.f, s1b = 0.f, s2b = 0.f, db = 0.f;
        #pragma unroll
        for (int j = 0; j < 16; j++) {
          const float* a = acc + 4 * j; float2 wv = lds64f(sb + WR + j * 32 + (lane & 3) * 8);
          s1a += a[0] + a[1]; s1b += a[2] + a[3];
          s2a = fmaf(a[0], a[0], s2a); s2b = fmaf(a[2], a[2], s2b); s2a = fmaf(a[1], a[1], s2a); s2b = fmaf(a[3], a[3], s2b);
          da = fmaf(a[0], wv.x, da); db = fmaf(a[2], wv.x, db); da = fmaf(a[1], wv.y, da); db = fmaf(a[3], wv.y, db);
        }
        bool odd = lane & 1;
        float u1 = (odd ? s1b : s1a) + __shfl_xor_sync(0xffffffffu, odd ? s1a : s1b, 1);
        float u2 = (odd ? s2b : s2a) + __shfl_xor_sync(0xffffffffu, odd ? s2a : s2b, 1);
        float u3 = (odd ? db : da) + __shfl_xor_sync(0xffffffffu, odd ? da : db, 1);
        u1 += __shfl_xor_sync(0xffffffffu, u1, 2); u2 += __shfl_xor_sync(0xffffffffu, u2, 2); u3 += __shfl_xor_sync(0xffffffffu, u3, 2);
        if (!(lane & 2)) st_ll(sp, __float_as_uint(u1), __float_as_uint(u2), __float_as_uint(u3), tag);
      }
      PROFW(t256 == 0, L * 8 + 7);
      if (L) {
        mbar_wait(BAR(B_PAR), 0);
        { float2 pa = lds64f(sb + PAR + (grow & 127) * 8), pb = lds64f(sb + PAR + (grow & 127) * 8 + 64); al0 = pa.x; be0 = pa.y; al1 = pb.x; be1 = pb.y; }
        #pragma unroll
        for (int j = 0; j < 16; j++) {
          rs[2 * j] = pack_bf16(fmaf(acc[4 * j], al0, be0), fmaf(acc[4 * j + 1], al0, be0));
          rs[2 * j + 1] = pack_bf16(fmaf(acc[4 * j + 2], al1, be1), fmaf(acc[4 * j + 3], al1, be1));
        }
        const int idx1 = (int)lds32(sb + INFO + 4);
        #pragma unroll
        for (int jj = 0; jj < 8; jj++) stsm_x4((ra + (jj >> 2) * 32768) + (sw ^ ((jj & 3) << 5)), rs[4 * jj], rs[4 * jj + 1], rs[4 * jj + 2], rs[4 * jj + 3]);
        __syncwarp();
        {
          const int r0 = (grow & ~15) + (lane >> 4), skip = idx1 - r0;
          const uint32_t a0 = sb + ((lane >> 3) & 1) * 32768 + (r0 & 255) * 128 + (((lane & 7) ^ (lane >> 4)) << 4);
          uint4* dst = (uint4*)(P.out + (size_t)r0 * 1024 + bc * 128) + (lane & 15);
          #pragma unroll
          for (int it = 0; it < 8; it++) { uint4 v = lds128((a0 + it * 256) ^ ((it & 3) << 5)); if (skip != 2 * it) dst[it * 256] = v; }
        }
        PROFW(t256 == 0, 16);
        if (fid < 112) {
          const int q = wg * 2 + (w >> 1);
          float g[8] = {0.f, 0.f, 0.f, 0.f, 0.f, 0.f, 0.f, 0.f};
          mbar_wait(BAR(B_FULLW + q), 0);
          bar_sync(3, 384);
          PROFW(t256 == 0, 29);
          #pragma unroll 1
          for (int n = 0; n < 4; n++) gemv8(g, sb + w_off(q) + (w & 1) * 16384 + n * 4096 + lane * 16, sb + HV + (q * 256 + n * 64 + (lane >> 2)) * 4, 32);
          sts32f(sb + PAR + 1024 + (q * 2 + (w & 1)) * 128 + ((lane & 3) * 8 + (lane >> 2)) * 4, fold8(g));
          bar_sync(1, 256);
          const uint32_t d = sb + PAR + 1024 + lane * 4;
          const float act = swiglu((lds32f(d) + lds32f(d + 256)) + (lds32f(d + 512) + lds32f(d + 768)),
                                   (lds32f(d + 128) + lds32f(d + 384)) + (lds32f(d + 640) + lds32f(d + 896)));
          PROFW(t256 == 0, 26);
          float y0 = 0.f, y1 = 0.f, y2 = 0.f, y3 = 0.f;
          sts32f(sb + HV + t256 * 4, act);
          __syncwarp();
          uint4 a4;
          #pragma unroll
          for (int n = 0; n < 32; n++) {
            if (!(n & 3)) a4 = lds128(sb + HV + (t256 >> 5) * 128 + n * 4);
            float av = __uint_as_float((n & 3) == 0 ? a4.x : ((n & 3) == 1 ? a4.y : ((n & 3) == 2 ? a4.z : a4.w)));
            y0 = fmaf(bf_lo(wd[n].x), av, y0); y1 = fmaf(bf_hi(wd[n].x), av, y1); y2 = fmaf(bf_lo(wd[n].y), av, y2); y3 = fmaf(bf_hi(wd[n].y), av, y3);
          }
          st_ll(yp, __float_as_uint(y0), __float_as_uint(y1), __float_as_uint(y2), (__float_as_uint(y3) & ~255u) | (lds32(sb + INFO + 12) + 1));
          PROFW(t256 == 0, 27);
        }
        return;
      }
    }
  }
  #undef IDS
  #undef LAYER
}

DEVI void loader(const Params& P, uint32_t sb) {
  const int lane = threadIdx.x & 31;
  const int bid = uni(BID), bi = bid >> 4, bp = bid & 15, rh = bp & 1, bc = bp >> 1;
  uint32_t phq = 0, tag = 0;
  #pragma unroll 1
  for (int L = 0; L < 2; L++) {
    int s = 0;
    uint32_t rdy = 0;
    #pragma unroll 1
    for (int n = L ? 0 : 3; n < 16; n++) {
      int kb = L ? kb_order(bc, n) : n;
      mbar_wait(BAR(B_EMPTYQ + s), (phq >> s) & 1);
      phq ^= 1u << s;
      if (L && n == 1) { mbar_wait(BAR(B_XRDY + 1), 0); mbar_wait(BAR(B_XRDY + 3), 0); }
      if (lane == 0) {
        mbar_expect_tx(BAR(B_FULLQ + s), L && n < 2 ? 40960 : 57344);
        tma_3d_h(sb + qb_off(s), &P.mWq, bp * 64, kb * 64, 0, BAR(B_FULLQ + s), L ? POL_Q1 : POL_Q0);
        if (!L) tma_2d(sb + qa_off(s), &P.mX, kb * 64, bi * 256, BAR(B_FULLQ + s));
      }
      if (L && n >= 2) {
        if (((rdy >> (2 * kb)) & 3) != 3) {
          do { rdy = __ballot_sync(0xffffffffu, ld_rlx(&P.g->flagX[bi][lane]) == tag); } while (((rdy >> (2 * kb)) & 3) != 3);
          fence_async_glob();
        }
        if (n == 3 || n == 4) mbar_wait(BAR(B_XFREE + n - 3), 0);
        if (lane == 0) bulk_g2s_h(sb + qa_off(s), P.g->x[bi][kb], 32768, BAR(B_FULLQ + s), POL_X);
      }
      PROFY(L && lane == 0 && (n == 2 || n == 3 || n == 9), n == 9 ? 60 : 56 + n);
      if (L && n == 2) { mbar_wait(BAR(B_FULLQ), 0); mbar_wait(BAR(B_FULLQ + 1), 1); if (lane < 2) mbar_arrive_peer(BAR(B_XFREE + lane)); }
      s = (s == 2) ? 0 : s + 1;
    }
    for (int q = 0; q < 3; q++) mbar_wait(BAR(B_EMPTYQ + q), (phq >> q) & 1);
    mbar_wait(BAR(B_PAR), L);
    tag = lds32(sb + INFO + 8) + L;
    #pragma unroll 1
    for (int q = 0; q < 4; q++) {
      if (bi) { while (ld_rlx(&P.g->flagKV[bid - 16][q]) != tag); fence_async_glob(); }
      if (lane == 0) {
        mbar_expect_tx(BAR(B_KVFULL + q), 16384);
        bulk_g2s_h(sb + ((q >> 1) ? KVB : KVA) + ((q & 1) ? 0 : 16384), bi ? P.g->kv[bid - 16][q] : P.g->zero, 16384, BAR(B_KVFULL + q));
      }
      PROFY(!L && lane == 0 && bi && q != 2, 34 + (q + 1) / 2);
    }
    mbar_wait(BAR(B_ORDY), L); mbar_wait(BAR(B_ORDY + 4), L);
    {
      const uint4* src = P.g->o[bi][0][0][rh];
      const unsigned* fl = &P.g->flagO[bi][0][rh][lane];
      rdy = 0;
      #pragma unroll 1
      for (int n = 0, q = 0; n < 16; n++, q = q == 5 ? 0 : q + 1) {
        const int j = n & 7;
        if (n == 8) { rdy = 0; src += 16384; fl += 64; }
        if (((rdy >> (4 * j)) & 15) != 15) {
          do { rdy = __ballot_sync(0xffffffffu, ld_rlx(fl) == tag); } while (((rdy >> (4 * j)) & 15) != 15);
          fence_async_glob();
        }
        if (n >= 2) mbar_wait(n < 6 ? BAR(B_HAFREE + (n >> 2)) : BAR(B_EMPTYW + q), n < 6 ? L : w_par(n - 6, q, L));
        if (n == THR_N) mbar_wait(BAR(B_OFREE), L);
        if (lane == 0) { mbar_expect_tx(BAR(B_FULLW + q), 16384); bulk_g2s_h(sb + w_off(q), src + j * 2048, 16384, BAR(B_FULLW + q)); }
      }
    }
    mbar_wait(BAR(B_OFREE), L);
  }
}

DEVI void ffn_prefetch(const Params& P, int q) {
  bulk_prefetch(q < 16 ? ((q & 1) ? P.wu : P.wg) + ((q >> 1) * 128 + blockIdx.x) * 3584 : P.wd + (min(FID, 111) * 8 + q - 16) * 4096, q < 16 ? 7168 : 8192);
}
DEVI void storer(const Params& P, uint32_t sb, int wg) {
  const int bid = uni(BID), bi = bid >> 4, rh = bid & 1, bc = (bid & 15) >> 1;
  const bool one = (threadIdx.x & 31) == 0;
  char* const g = (char*)P.g;
  #pragma unroll 1
  for (int L = 0; L < 2; L++) {
    mbar_wait(BAR(B_PAR), L);
    const uint32_t tag = lds32(sb + INFO + 8) + L;
    if (wg) { mbar_wait(BAR(B_KVRDY + 2), L); const uint32_t t0 = clk(); while (clk() - t0 < KV_D) __nanosleep(40); }
    #pragma unroll 1
    for (int u = bi < 7 ? 0 : 2; u < 6; u++) {
      const int h = u < 2 ? u : u >> 2, t = (u & 1) ? wg : 3 - wg;
      uint32_t src, dst, fl, b0, b1;
      if (u < 2) {
        src = (h ? KVB : KVA) + (3 - wg) * 16384; dst = offsetof(Scratch, kv) + (bid * 4 + h * 2 + wg) * 16384; fl = offsetof(Scratch, flagKV) + (bid * 32 + h * 2 + wg) * 4;
        b0 = BAR(B_KVRDY + ((u | wg) ? 1 : 0)); b1 = b0 + 16;
      } else {
        src = QO + (h * 4 + t) * 4096; dst = offsetof(Scratch, o) + ((((bi * 2 + h) * 8 + bc) * 2 + (t >> 1)) * 4 + rh * 2 + (t & 1)) * 4096;
        fl = offsetof(Scratch, flagO) + (((bi * 2 + h) * 2 + (t >> 1)) * 32 + (bid & 15) * 2 + (t & 1)) * 4;
        b0 = b1 = BAR(B_ORDY + wg * 4 + u - 2);
      }
      mbar_wait(b0, L); mbar_wait(b1, L);
      fence_async_smem();
      PROFY(one && !L && !wg && (u == 0 || u == 3), u ? 46 : 8);
      if (one) { bulk_s2g(g + dst, sb + src, u < 2 ? 16384 : 4096); if (u == 5) mbar_arrive(BAR(B_HAFREE + 1)); }
      if (u == 2 || u == 4) continue;
      bulk_wait<0>();
      PROFY(one && !L && !wg && (u == 0 || u == 3), u ? 61 : 62);
      fence_rel();
      if (one) { st_rlx((unsigned*)(g + fl), tag); if (u > 2) st_rlx((unsigned*)(g + (fl ^ 132u)), tag); if (u == 3) mbar_arrive(BAR(B_HAFREE)); }
      PROFY(one && !L && (u < 2 ? u == wg : !wg), u == 3 ? 38 : (u == 5 ? 54 : 32 + u));
    }
    if (one) mbar_arrive(BAR(B_OFREE));
    if (L == 0) {
      char* dst = g + (offsetof(Scratch, x) + (bi * 16 + 2 * bc) * 32768 + rh * 16384);
      unsigned* f = (unsigned*)(g + (offsetof(Scratch, flagX) + (bi * 32 + bc * 4 + rh) * 4));
      const uint32_t a = sb + rh * 16384;
      if (wg == 0) {
        mbar_wait(BAR(B_XRDY), 0); mbar_wait(BAR(B_XRDY + 2), 0);
        fence_async_smem();
        PROFY(one, 41);
        if (one) bulk_s2g(dst, a, 16384);
        bulk_wait<0>();
        PROFY(one, 45);
        if (one) { mbar_arrive(BAR(B_XFREE)); mbar_arrive(BAR(B_PFREE)); }
        fence_rel();
        mbar_wait(BAR(B_XRDY + 1), 0); mbar_wait(BAR(B_XRDY + 3), 0);
        if (one) { st_rlx(f, tag); bulk_s2g(dst + 32768, a + 32768, 16384); }
        PROFY(one, 56);
        bulk_wait<0>();
        if (one) mbar_arrive(BAR(B_XFREE + 1));
        fence_rel();
        if (one) st_rlx(f + 2, tag);
        PROFY(one, 57);
      } else {
        mbar_wait(BAR(B_XRDY + 1), 0); mbar_wait(BAR(B_XRDY + 3), 0);
        mbar_wait(BAR(B_PFREE), 0);
        if (one) bulk_s2peer(a, 16384, BAR(B_FULLQ));
        { const uint32_t t0 = clk(); while (clk() - t0 < XD_D); }
        if (one) bulk_s2peer(a + 32768, 16384, BAR(B_FULLQ + 1));
      }
      if (wg == 0) {
        uint32_t t0 = clk() + PF1_D;
        #pragma unroll 1
        for (int q = PF1_S; q < PF1_E; q++) { while ((int)(clk() - t0) < 0) __nanosleep(50); if (one) ffn_prefetch(P, q); t0 += PF1_T; }
      }
    }
  }
}

DEVI void stg_issue(const Params& P, int c, uint32_t d, uint32_t du, uint32_t b) {
  mbar_expect_tx(b, 16384);
  if (c < 8) { tma_2d_h(d, &P.mWg, FID * 32, c * 128, b, POL_G); tma_2d_h(d + du, &P.mWu, FID * 32, c * 128, b, POL_U); }
  else if (c < 12) tma_3d_h(d, &P.mWd, 0, FID * 32 + (c - 8) * 8, 0, b, POL_D);
  else tma_2d_h(d, &P.mWp, FID * 32, (c - 12) * 256, b, POL_EF);
}
DEVI void stager(const Params& P, uint32_t sb) {
  {
    const int b = blockIdx.x;
    uint32_t t0 = clk();
    #pragma unroll 1
    for (int q = 0; q < PQ_N; q++) { bulk_prefetch(P.wqkv + (q * 128 + b) * 3072, 6144); while (clk() - t0 < PQ_T); t0 += PQ_T; }
    bulk_prefetch(P.wo + b * 8192, 16384);
    #pragma unroll 1
    for (int q = 0; q < PF0_N; q++) {
      while (clk() - t0 < PF0_T);
      t0 += PF0_T;
      ffn_prefetch(P, q);
    }
  }
  const int bid = BID, bi = bid >> 4, rh = bid & 1, bc = (bid & 15) >> 1;
  #pragma unroll 1
  for (int L = 0; L < 2; L++) {
    const int nch = FID >= 112 ? 0 : (L ? 8 : (FID < 96 ? 16 : 12));
    mbar_wait(BAR(B_KVFULL + W0_BAR), L);
    #pragma unroll 1
    for (int n = 0, q = 0; n < 16; n++, q = q == 5 ? 0 : q + 1) {
      if (n >= 2) mbar_wait(n < 6 ? BAR(B_HAFREE + (n >> 2)) : BAR(B_EMPTYW + q), n < 6 ? L : w_par(n - 6, q, L));
      if (n == THR_N) mbar_wait(BAR(B_OFREE), L);
      mbar_expect_tx(BAR(B_FULLW + q), 16384);
      tma_5d(sb + w_off(q) + 16384, &P.mWo, 0, 0, n >> 3, 2 * (n & 7), 2 * bc, BAR(B_FULLW + q), L ? POL_EF : POL_NORMAL);
    }
    mbar_expect_tx(BAR(B_RES), 32768);
    #pragma unroll 1
    for (int e = 0; e < 2; e++) {
      mbar_wait(BAR(B_EMPTYW + 4 + e), 1);
      if (L) bulk_g2s_h(sb + e * 32768 + rh * 16384, P.g->x[bi][2 * bc + e] + rh * 1024, 16384, BAR(B_RES));
      else tma_2d_h(sb + e * 32768 + rh * 16384, &P.mXh, bc * 128 + e * 64, bi * 256 + rh * 128, BAR(B_RES), POL_EF);
    }
    if (L == 0) { mbar_arrive_peer(BAR(B_PFREE)); mbar_wait(BAR(B_EMPTYW), 0); mbar_wait(BAR(B_EMPTYW + 1), 0); }
    #pragma unroll 1
    for (int c = 0, slot = 0; c < nch; c++, slot = slot == 2 ? 0 : slot + 1) {
      mbar_wait(L ? BAR(B_EMPTYW + (c >> 1)) : BAR(B_STGE + slot), L | ((0x71c7 >> c) & 1));
      stg_issue(P, c, L ? sb + w_off(c >> 1) + (c & 1) * 8192 : sb + STG + slot * 16384, 8192 << L, L ? BAR(B_FULLW + (c >> 1)) : BAR(B_STG + slot));
    }
  }
}
DEVI void sum8(uint4 v, float& s1, float& s2) {
  float e[8] = {bf_lo(v.x), bf_hi(v.x), bf_lo(v.y), bf_hi(v.y), bf_lo(v.z), bf_hi(v.z), bf_lo(v.w), bf_hi(v.w)};
  #pragma unroll
  for (int q = 0; q < 8; q++) { s1 += e[q]; s2 = fmaf(e[q], e[q], s2); }
}
DEVI uint4 norm8(uint4 x, float m, float rs, uint32_t d, uint32_t d2) {
  #define HN(v) pack_bf16((bf_lo(v) - m) * rs, (bf_hi(v) - m) * rs)
  uint4 b = make_uint4(HN(x.x), HN(x.y), HN(x.z), HN(x.w));
  #undef HN
  sts128(d, make_uint4(b.x << 16, b.x & 0xffff0000u, b.y << 16, b.y & 0xffff0000u));
  sts128(d + d2, make_uint4(b.z << 16, b.z & 0xffff0000u, b.w << 16, b.w & 0xffff0000u));
  return b;
}
DEVI uint4 best4(uint32_t p) {
  uint4 a = lds128(p), b = lds128(p + 16), c = lds128(p + 32), d = lds128(p + 48);
  if (b.x > a.x) a = b;
  if (d.x > c.x) c = d;
  return c.x > a.x ? c : a;
}
#define FL(x) __uint_as_float(x)
#define UI(x) __float_as_uint(x)
DEVI void qkv_params(const Params& P, uint32_t sb, int row, uint32_t tag, bool second) {
  uint4 v0, v1; poll_ll2(&P.g->statF[row], &P.g->statF[row + 128], 0xffffffffu, tag, v0, v1);
  #pragma unroll 1
  for (int q = 0; q < 2; q++) {
    float var = FL(v0.y), c = rsqrtf(var + LN_EPS);
    if (second) { c += 1.f; c *= rsqrtf(fmaf(var * c, c, LN_EPS)); }
    const float mh = bf_round(FL(v0.x));
    sts64f(sb + PAR + q * 1024 + (row & 127) * 8, c, FL(pack_bf16(mh, FL(v0.x) - mh)));
    v0 = v1;
  }
}
DEVI void aux(const Params& P, uint32_t sb) {
  int tid = fresh_tid();
  #define lane (tid & 31)
  #define wq (tid >> 5)
  uint32_t ids = P.map[blockIdx.x], tag;
  #define bid ((int)(ids & 255))
  #define fid ((int)(ids >> 8))
  #define bi (bid >> 4)
  #define bp (bid & 15)
  #define bc (bp >> 1)
  #define FRESH() do { tid = fresh_tid(); uint4 z_ = ldsv128(sb + INFO2 + 16); ids = z_.y; tag = z_.z + L; idx = z_.w; } while (0)
  {
    const uint32_t epoch = ld_rlx(&P.g->epoch);
    if (tid == 0) {
      mbar_expect_tx(BAR(B_STG), 49152);
      tma_3d(sb + STG, &P.mWq, bp * 64, bi * 128, 0, BAR(B_STG));
      tma_3d(sb + STG + 24576, &P.mWq, bp * 64, bi * 128 + 64, 0, BAR(B_STG));
    }
    __syncwarp();
    sts64f(sb + ONES + tid * 8, FL(0x3F803F80u), FL(0x3F803F80u));
    float s1 = 0.f, s2 = 0.f;
    { uint4 v = __ldg((const uint4*)P.wr + tid);
      if ((tid >> 4) == bc) norm8(v, 0.f, 1.f, sb + WR + (tid & 15) * 32, 16);
      sum8(v, s1, s2);
      #pragma unroll 1
      for (int o = 16; o; o >>= 1) s1 += __shfl_xor_sync(0xffffffffu, s1, o);
      sts32f(sb + INFO2 + wq * 4, s1); }
    const uint4* src = (const uint4*)(P.x0 + (size_t)bid * 16384) + (tid >> 3) * 128 + (tid & 7);
    s1 = 0.f; s2 = 0.f;
    #pragma unroll 1
    for (int it = 0; it < 16; it += 4) {
      uint4 v0 = __ldg(src + it * 8), v1 = __ldg(src + it * 8 + 8), v2 = __ldg(src + it * 8 + 16), v3 = __ldg(src + it * 8 + 24);
      #pragma unroll 1
      for (int q = 0; q < 4; q++) { sum8(v0, s1, s2); v0 = v1; v1 = v2; v2 = v3; }
    }
    #pragma unroll 1
    for (int o = 1; o < 8; o <<= 1) { s1 += __shfl_xor_sync(0xffffffffu, s1, o); s2 += __shfl_xor_sync(0xffffffffu, s2, o); }
    tag = ((epoch % 16383u) + 1u) << 2;
    if (tid == 0) { sts128(sb + INFO, make_uint4(0x40000000u, 0u, tag, ((epoch % 127u) + 1u) << 1)); sts128(sb + INFO2 + 16, make_uint4(epoch, ids, tag, 0x40000000u)); }
    float m = s1 * (1.f / 1024.f);
    if ((tid & 7) == 0) st_ll(&P.g->statF[bid * 16 + (tid >> 3)], UI(m), UI(fmaxf(fmaf(-m, m, s2 * (1.f / 1024.f)), 0.f)), 0u, tag);
    bar_sync(2, 128);
    mbar_wait_b(BAR(B_STG), 0);
    if (tid < 96) {
      s1 = 0.f; s2 = 0.f;
      #pragma unroll 4
      for (int r = 0; r < 128; r++) {
        uint32_t v = lds32(sb + STG + (r >> 6) * 24576 + wq * 8192 + (r & 63) * 128 + ((lane * 4) ^ ((r & 7) << 4)));
        s1 += bf_lo(v); s2 += bf_hi(v);
      }
      st_ll(&P.g->csP[bp][bi][tid], UI(s1), UI(s2), 0u, tag);
      s1 = 0.f; s2 = 0.f;
      #pragma unroll 1
      for (int q = 0; q < 8; q += 2) {
        uint4 a, b; poll_ll2(&P.g->csP[bp][q][tid], &P.g->csP[bp][q + 1][tid], 0xffffffffu, tag, a, b);
        s1 += FL(a.x) + FL(b.x); s2 += FL(a.y) + FL(b.y);
      }
      const uint32_t hi = pack_bf16(-s1, -s2);
      sts32(sb + CS + (tid >> 2) * 32 + (tid & 3) * 4, hi);
      sts32(sb + CS + (tid >> 2) * 32 + (tid & 3) * 4 + 16, pack_bf16(-s1 - bf_lo(hi), -s2 - bf_hi(hi)));
    }
    fence_async_smem();
    qkv_params(P, sb, bi * 256 + tid, tag, false);
  }
  int idx;
  #pragma unroll 1
  for (int L = 0; L < 2; L++) {
    FRESH();
    {
      if ((idx >> 8) == bi && wq < 3) {
        uint4 v = poll_ll(&P.g->patch[wq * 256 + bp * 16 + (lane & 15)], 0xffffffffu, tag);
        sts64f(sb + PATCH + (wq * 16 + (lane & 15)) * 8, FL(v.x), FL(v.y));
      }
      sts32(sb + INFO, idx);
      bar_sync(2, 128);
      if (tid == 0) mbar_arrive(BAR(B_PAR));
      PROFX(tid == 0, L ? 23 : 17);
    }
    FRESH();
    mbar_wait_b(BAR(B_OFREE), L);
    #define blk (bi * 2 + (bid & 1))
    if (tid < 33) st_ll(tid < 32 ? &P.g->row[blk][bc * 32 + tid] : &P.g->best[bc][blk], 0u, 0u, 0u, 0u);
    mbar_wait_b(BAR(B_XRDY + 1), L); mbar_wait_b(BAR(B_XRDY + 3), L);
    PROFX(tid == 0, 37 + L * 16);
    FRESH();
    {
      float s1 = 0.f, s2 = 0.f, d = 0.f;
      #pragma unroll 1
      for (int q = 0; q < 8; q += 4) {
        const uint4* src = &P.g->statP[q][blk * 128 + tid];
        uint4 v0, v1, v2, v3; int it = 0;
        do { v0 = ld_ll(src); v1 = ld_ll(src + 2048); v2 = ld_ll(src + 4096); v3 = ld_ll(src + 6144); if (++it > SPIN_MAX) __trap(); }
        while (!__all_sync(0xffffffffu, v0.w == tag && v1.w == tag && v2.w == tag && v3.w == tag));
        s1 += (FL(v0.x) + FL(v1.x)) + (FL(v2.x) + FL(v3.x)); s2 += (FL(v0.y) + FL(v1.y)) + (FL(v2.y) + FL(v3.y)); d += (FL(v0.z) + FL(v1.z)) + (FL(v2.z) + FL(v3.z));
      }
      PROFX(tid == 0, 39 + L * 16);
      uint4 a = lds128(sb + INFO2), b, c;
      float m = s1 * (1.f / 1024.f), var = fmaxf(fmaf(-m, m, s2 * (1.f / 1024.f)), 0.f), rs = rsqrtf(var + LN_EPS);
      uint32_t key = UI(fmaf(-m, (FL(a.x) + FL(a.y)) + (FL(a.z) + FL(a.w)), d) * rs);
      key ^= (uint32_t)((int)key >> 31) | 0x80000000u;
      uint32_t win = __ballot_sync(0xffffffffu, key == __reduce_max_sync(0xffffffffu, key));
      if (lane == __ffs(win) - 1) sts128(sb + RED + wq * 16, make_uint4(key, UI(m), UI(rs), (tag << 11) | (uint32_t)(blk * 128 + tid)));
      if (L) sts64f(sb + PAR + tid * 8, 1.f + rs, -m * rs);
      else if ((tid >> 4) == bc) st_ll(&P.g->statF[blk * 128 + tid], UI(m), UI(var), 0u, tag + 1);
      bar_sync(2, 128);
      if (wq == 0) {
        a = best4(sb + RED);
        float2 v = lds64f(sb + (lane >> 4) * 32768 + (a.w & 255) * 128 + (((lane & 15) * 8) ^ ((a.w & 7) << 4)));
        st_ll(&P.g->row[blk][bc * 32 + lane], UI(v.x), UI(v.y), 0u, tag);
        if (lane == 0) { st_ll(&P.g->best[bc][blk], a.x, a.y, a.z, a.w); sts32(sb + INFO + 4, a.w & 2047); }
        __syncwarp();
        if (L) {
          const float al = 1.f + FL(a.z), be = -FL(a.y) * FL(a.z);
          sts64f(sb + RED + 1792 + lane * 8, FL(pack_bf16(fmaf(bf_lo(UI(v.x)), al, be), fmaf(bf_hi(UI(v.x)), al, be))),
                                             FL(pack_bf16(fmaf(bf_lo(UI(v.y)), al, be), fmaf(bf_hi(UI(v.y)), al, be))));
        }
        if (lane < 2 - L) mbar_arrive(L ? BAR(B_PAR) : BAR(B_XFREE + lane));
      }
      PROFX(tid == 0, 18 + L * 6);
      FRESH();
      a = poll_ll(&P.g->best[bc][lane & 15], 0xfffff800u, tag << 11);
      win = __ffs(__ballot_sync(0xffffffffu, a.x == __reduce_max_sync(0xffffffffu, a.x))) - 1;
      idx = __shfl_sync(0xffffffffu, a.w, win) & 2047;
      PROFX(tid == 0, 19 + L * 6);
      poll_ll2(&P.g->row[win][tid], &P.g->row[win][tid + 128], 0xffffffffu, tag, c, b);
      c.z = b.x; c.w = b.y;
      a.x = __shfl_sync(0xffffffffu, a.x, win); a.y = __shfl_sync(0xffffffffu, a.y, win); a.z = __shfl_sync(0xffffffffu, a.z, win);
      sts32(sb + INFO2 + 28, idx);
      PROFX(tid == 0, 61 + L);
      b = norm8(c, FL(a.y), FL(a.z), sb + HV + tid * 16, 2048);
      if (L && fid < 112) bar_arrive(3, 384);
      if ((tid >> 1) == (bid & 63)) {
        sts128(sb + RED + 64 + (tid & 1) * 16, bid < 64 ? make_uint4(c.x, c.y, b.x, b.y) : make_uint4(c.z, c.w, b.z, b.w));
        sts32(sb + RED + 96, a.x);
      }
      if (L && wq == 0 && win != blk) *(float2*)(P.out + (size_t)lds32(sb + INFO + 4) * 1024 + bc * 128 + lane * 4) = lds64f(sb + RED + 1792 + lane * 8);
      bar_sync(2, 128);
    }
    #pragma unroll 1
    for (int st = L; st < 3; st++) {
      FRESH();
      float a[8] = {0.f, 0.f, 0.f, 0.f, 0.f, 0.f, 0.f, 0.f};
      if (L == 0 && fid < (st == 2 ? 96 : 112)) {
        uint32_t ha = st == 1 ? sb + RED + 768 : sb + HV + ((st ? wq : wq & 1) * 64 + (lane >> 2)) * 4;
        uint32_t ph = (st ? (st == 1 ? 0x1cu : 0x11u) : 0x171u), bar = st == 1 ? BAR(B_STG + 2) : BAR(B_STG);
        uint32_t wa = sb + STG + tid * 16 + wq * 3584 + (st == 1 ? 32768 : 0);
        const uint32_t hx = st == 1 ? 256 : (st ? 1024 : 512);
        const bool lead = lane == 0;
        #pragma unroll 1
        do {
          mbar_wait(bar, ph & 1);
          PROFX(lead && threadIdx.x == 256 && st == 0 && (ph > 255 || ph < 4), 40 - 23 + __clz(ph));
          gemv8(a, wa, ha, 32);
          __syncwarp();
          if (lead) mbar_arrive(bar - 8 * (B_STG - B_STGE));
          const bool wrap = bar == BAR(B_STG + 2);
          bar += wrap ? -16 : 8; wa += wrap ? -32768 : 16384; ha += hx;
          ph >>= 1;
        } while (ph != 1);
      }
      FRESH();
      if (st == 1) {
        const uint32_t t8 = lds32(sb + INFO + 12) + L;
        if (L == 0 && fid < 112) {
          const bool odd = lane & 1;
          #pragma unroll
          for (int e = 0; e < 4; e++) { float z = __shfl_xor_sync(0xffffffffu, odd ? a[e] : a[4 + e], 1); if (odd) a[e] = z; else a[4 + e] = z; }
          uint4* dst = &P.g->yP[tid & ~1][fid][tid & 1];
          st_ll(dst, UI(a[0]), UI(a[1]), UI(a[2]), (UI(a[3]) & ~255u) | t8);
          st_ll(dst + 224, UI(a[4]), UI(a[5]), UI(a[6]), (UI(a[7]) & ~255u) | t8);
          PROFX(tid == 0, 21);
        }
        if (!L) qkv_params(P, sb, bi * 256 + tid, tag + 1, true);
        if (tid == 0) { uint32_t k = lds32(sb + RED + 96); sts32f(sb + RED + 100, bf_round(__fdividef(1.f, 1.f + __expf(-bf_round(FL(k ^ (~(uint32_t)((int)k >> 31) | 0x80000000u))))))); }
        uint4 v0, v1;
        poll_ll2(&P.g->yP[bid][0][min(tid, 111)], &P.g->yP[bid][0][min(tid, 111) + 112], 255u, t8, v0, v1);
        const float lo = (tid < 112 && !(tid & 1)) ? 1.f : 0.f, hi = (tid < 112 && (tid & 1)) ? 1.f : 0.f;
        const float y0 = FL(v0.x) + FL(v1.x), y1 = FL(v0.y) + FL(v1.y), y2 = FL(v0.z) + FL(v1.z), y3 = FL((v0.w & ~255u) | 128u) + FL((v1.w & ~255u) | 128u);
        a[0] = y0 * lo; a[1] = y1 * lo; a[2] = y2 * lo; a[3] = y3 * lo; a[4] = y0 * hi; a[5] = y1 * hi; a[6] = y2 * hi; a[7] = y3 * hi;
      }
      sts32f(sb + RED + 256 + wq * 128 + ((lane & 3) * 8 + (lane >> 2)) * 4, fold8(a));
      bar_sync(2, 128);
      const uint32_t d = sb + RED + 256 + lane * 4;
      float z0 = lds32f(d) + lds32f(d + 128), z1 = lds32f(d + 256) + lds32f(d + 384);
      if (st == 0) {
        sts32f(sb + RED + 768 + lane * 32 + wq * 4, swiglu(z0, z1));
        if (fid < 112) { st_ll(&P.g->yP[tid & ~1][fid][tid & 1], 0u, 0u, 0u, 0u); st_ll(&P.g->yP[tid | 1][fid][tid & 1], 0u, 0u, 0u, 0u); }
        if (tid < 24) st_ll(tid < 16 ? &P.g->x2[tid >> 1][2 * bid + (tid & 1)] : &P.g->patch[fid * 8 + tid - 16], 0u, 0u, 0u, 0u);
        bar_sync(2, 128); PROFX(tid == 0, 20); continue; }
      z0 += z1;
      if (st == 1) {
        z0 += __shfl_xor_sync(0xffffffffu, z0, 8); z0 += __shfl_xor_sync(0xffffffffu, z0, 16);
        uint32_t xw = lds32(sb + RED + 64 + (lane & 4) * 4 + (lane & 2) * 2), hw = lds32(sb + RED + 72 + (lane & 4) * 4 + (lane & 2) * 2);
        z0 = bf_round(((lane & 1) ? bf_hi(hw) : bf_lo(hw)) + bf_round(bf_round(z0) * lds32f(sb + RED + 100))) + ((lane & 1) ? bf_hi(xw) : bf_lo(xw));
      } else if (fid < 32) z0 *= QSCALE;
      uint32_t v = pack_bf16(z0, __shfl_down_sync(0xffffffffu, z0, 1)), v2 = __shfl_down_sync(0xffffffffu, v, 2);
      if (L) { if (tid == 0 || tid == 4) *(uint2*)(P.out + (size_t)idx * 1024 + bid * 8 + tid) = make_uint2(v, v2); PROFW(tid == 0, 28); break; }
      if ((tid & 3) == 0 && tid < (st == 1 ? 64 : 32)) st_ll(st == 1 ? &P.g->x2[tid >> 3][2 * bid + ((tid >> 2) & 1)] : &P.g->patch[fid * 8 + (tid >> 2)], v, v2, 0u, tag + 1);
      PROFX(tid == 0, st == 1 ? 22 : 31);
      if (st == 1) {
        uint4 x, y; poll_ll2(&P.g->x2[bi][tid], &P.g->x2[bi][tid + 128], 0xffffffffu, tag + 1, x, y);
        x.z = y.x; x.w = y.y;
        if (wq == (bc & 3)) sts64f(sb + X2SEG + lane * 8, FL(bc < 4 ? x.x : x.z), FL(bc < 4 ? x.y : x.w));
        float s1 = 0.f, s2 = 0.f;
        sum8(x, s1, s2);
        #pragma unroll
        for (int o = 16; o; o >>= 1) { s1 += __shfl_xor_sync(0xffffffffu, s1, o); s2 += __shfl_xor_sync(0xffffffffu, s2, o); }
        sts64f(sb + RED + wq * 8, s1, s2);
        bar_sync(2, 128);
        y = lds128(sb + RED); uint4 y2 = lds128(sb + RED + 16);
        float m = ((FL(y.x) + FL(y.z)) + (FL(y2.x) + FL(y2.z))) * (1.f / 1024.f);
        norm8(x, m, rsqrtf(fmaxf(fmaf(-m, m, ((FL(y.y) + FL(y.w)) + (FL(y2.y) + FL(y2.w))) * (1.f / 1024.f)), 0.f) + LN_EPS), sb + HV + tid * 16, 2048);
        bar_sync(2, 128);
        PROFX(tid == 0, 30);
      }
    }
  }
  if (bid == 0 && tid == 0) P.g->epoch = lds32(sb + INFO2 + 16) + 1;
  #undef blk
  #undef bid
  #undef fid
  #undef bi
  #undef bp
  #undef bc
  #undef FRESH
  #undef lane
  #undef wq
}

__global__ void __cluster_dims__(2, 1, 1) __launch_bounds__(512, 1) fused_kernel(const __grid_constant__ Params P) {
  extern __shared__ __align__(1024) uint8_t smem_raw[];
  const uint32_t sb = smem_u32(smem_raw);
  PROFT(threadIdx.x == 0, 0);
  if (threadIdx.x == 0) {
    for (int s = 0; s < 3; s++) mbar_init(BAR(B_FULLQ + s), 1);
    asm volatile("fence.mbarrier_init.release.cluster;" ::: "memory");
    #pragma unroll 1
    for (int s = 0; s < 3; s++) {
      mbar_expect_tx(BAR(B_FULLQ + s), 57344);
      tma_2d(sb + qa_off(s), &P.mX, s * 64, (BID >> 4) * 256, BAR(B_FULLQ + s));
      tma_3d(sb + qb_off(s), &P.mWq, (BID & 15) * 64, s * 64, 0, BAR(B_FULLQ + s));
    }
    if ((sb & 0x3FFFFu) != 1024) __trap();
  } else if (threadIdx.x >= 32 + B_EMPTYQ && threadIdx.x < 32 + B_COUNT) {
    const int b = threadIdx.x - 32;
    const uint32_t cnt = b < B_XFREE ? 2 : (b < B_KVRDY ? 3 : (b < B_KVFULL ? 4 : (b == B_PFREE ? 2 : 1)));
    mbar_init(BAR(b), cnt);
    asm volatile("fence.mbarrier_init.release.cluster;" ::: "memory");
  }
  __syncthreads();
  asm volatile("barrier.cluster.arrive.relaxed.aligned;" ::: "memory");
  const int wg = __shfl_sync(0xffffffffu, threadIdx.x >> 7, 0);
  if (wg < 2) { reg_inc<224>(); consumer(P, sb, wg); }
  else if (wg == 2) { reg_dec<40>(); aux(P, sb); }
  else {
    reg_dec<24>();
    asm volatile("barrier.cluster.wait.aligned;" ::: "memory");
    const int w = __shfl_sync(0xffffffffu, (threadIdx.x >> 5) & 3, 0);
    if (w == 0) loader(P, sb);
    else if (w < 3) storer(P, sb, w - 1);
    else if ((threadIdx.x & 31) == 0) stager(P, sb);
  }
}

typedef CUresult (*EncFn)(CUtensorMap*, CUtensorMapDataType, cuuint32_t, void*, const cuuint64_t*, const cuuint64_t*, const cuuint32_t*, const cuuint32_t*,
                          CUtensorMapInterleave, CUtensorMapSwizzle, CUtensorMapL2promotion, CUtensorMapFloatOOBfill);
static void mk_map(EncFn enc, CUtensorMap* m, const void* ptr, int rank, const cuuint64_t* dims, const cuuint64_t* strides, const cuuint32_t* box,
                   CUtensorMapSwizzle sw, CUtensorMapL2promotion pr) {
  cuuint32_t es[5] = {1, 1, 1, 1, 1};
  enc(m, CU_TENSOR_MAP_DATA_TYPE_BFLOAT16, rank, (void*)ptr, dims, strides, box, es, CU_TENSOR_MAP_INTERLEAVE_NONE, sw, pr, CU_TENSOR_MAP_FLOAT_OOB_FILL_NONE);
}
extern "C" void kernel_launch(void* const* d_in, const int* in_sizes, int n_in, void* d_out, int out_size) {
  (void)in_sizes; (void)n_in; (void)out_size;
  void* fn = nullptr; cudaDriverEntryPointQueryResult q;
  cudaGetDriverEntryPoint("cuTensorMapEncodeTiled", &fn, cudaEnableDefault, &q);
  EncFn enc = (EncFn)fn;
  cudaFuncSetAttribute(fused_kernel, cudaFuncAttributeMaxDynamicSharedMemorySize, SMEM_BYTES);
  Params P;
  const CUtensorMapSwizzle S128 = CU_TENSOR_MAP_SWIZZLE_128B, S0 = CU_TENSOR_MAP_SWIZZLE_NONE;
  const CUtensorMapL2promotion L256 = CU_TENSOR_MAP_L2_PROMOTION_L2_256B, L128 = CU_TENSOR_MAP_L2_PROMOTION_L2_128B;
  { cuuint64_t d[2] = {1024, 2048}, s[1] = {2048}; cuuint32_t b[2] = {64, 256}, bh[2] = {64, 128};
    mk_map(enc, &P.mX, d_in[0], 2, d, s, b, S128, L256); mk_map(enc, &P.mXh, d_in[0], 2, d, s, bh, S128, L256); }
  { cuuint64_t d[3] = {1024, 1024, 3}, s[2] = {6144, 2048}; cuuint32_t b[3] = {64, 64, 3}; mk_map(enc, &P.mWq, d_in[1], 3, d, s, b, S128, L256); }
  { cuuint64_t d[5] = {64, 32, 2, 16, 16}, s[4] = {2048, 65536, 131072, 128}; cuuint32_t b[5] = {64, 32, 1, 2, 2}; mk_map(enc, &P.mWo, d_in[2], 5, d, s, b, S128, L256); }
  { cuuint64_t d[2] = {3584, 1024}, s[1] = {7168}; cuuint32_t b[2] = {32, 128};
    mk_map(enc, &P.mWg, d_in[5], 2, d, s, b, S0, L128); mk_map(enc, &P.mWu, d_in[6], 2, d, s, b, S0, L128); }
  { cuuint64_t d[2] = {3072, 1024}, s[1] = {6144}; cuuint32_t b[2] = {32, 256}; mk_map(enc, &P.mWp, d_in[1], 2, d, s, b, S0, L128); }
  { cuuint64_t d[3] = {256, 3584, 4}, s[2] = {2048, 512}; cuuint32_t b[3] = {256, 8, 4}; mk_map(enc, &P.mWd, d_in[7], 3, d, s, b, S0, L128); }
  P.x0 = (const bf16*)d_in[0]; P.wqkv = (const bf16*)d_in[1]; P.wo = (const bf16*)d_in[2]; P.wr = (const bf16*)d_in[4]; P.wg = (const bf16*)d_in[5]; P.wu = (const bf16*)d_in[6]; P.wd = (const bf16*)d_in[7];
  P.out = (bf16*)d_out;
  cudaGetSymbolAddress((void**)&P.g, g_scr);
  for (int b = 0; b < 128; b++) {
    int j = b >> 1, quad = j < 4 ? 0 : (j < 36 ? 1 + (j - 4) % 8 : 9 + (j - 36) % 7), pos = j < 4 ? j : (j < 36 ? (j - 4) / 8 : (j - 36) / 7);
    int bid = ((quad >> 2) * 2 + (pos >> 1)) * 16 + ((quad & 3) * 2 + (pos & 1)) * 2 + (b & 1);
    int e = pos * 2 + (b & 1), fid = e < 6 ? quad * 6 + e : e * 16 + quad;
    P.map[b] = bid | fid << 8;
  }
  fused_kernel<<<128, 512, SMEM_BYTES>>>(P);
}
```

```cpp
#include <cuda_runtime.h>
#include <cuda_bf16.h>
#include <cuda.h>
#include <stdint.h>
#include <stddef.h>
typedef __nv_bfloat16 bf16;

template<int TB, int TA = 0> __device__ __forceinline__ void wgmma_ss_n192(float (&d)[96], uint64_t da, uint64_t db, int scale_d) {
  asm volatile("{\n.reg .pred p;\nsetp.ne.b32 p, %98, 0;\n"
    "wgmma.mma_async.sync.aligned.m64n192k16.f32.bf16.bf16 {%0, %1, %2, %3, %4, %5, %6, %7, %8, %9, %10, %11, %12, %13, %14, %15, %16, %17, %18, %19, %20, %21, %22, %23, %24, %25, %26, %27, %28, %29, %30, %31, %32, %33, %34, %35, %36, %37, %38, %39, %40, %41, %42, %43, %44, %45, %46, %47, %48, %49, %50, %51, %52, %53, %54, %55, %56, %57, %58, %59, %60, %61, %62, %63, %64, %65, %66, %67, %68, %69, %70, %71, %72, %73, %74, %75, %76, %77, %78, %79, %80, %81, %82, %83, %84, %85, %86, %87, %88, %89, %90, %91, %92, %93, %94, %95}, %96, %97, p, 1, 1, %100, %99;\n}\n"
    : "+f"(d[0]), "+f"(d[1]), "+f"(d[2]), "+f"(d[3]), "+f"(d[4]), "+f"(d[5]), "+f"(d[6]), "+f"(d[7]), "+f"(d[8]), "+f"(d[9]), "+f"(d[10]), "+f"(d[11]), "+f"(d[12]), "+f"(d[13]), "+f"(d[14]), "+f"(d[15]), "+f"(d[16]), "+f"(d[17]), "+f"(d[18]), "+f"(d[19]), "+f"(d[20]), "+f"(d[21]), "+f"(d[22]), "+f"(d[23]), "+f"(d[24]), "+f"(d[25]), "+f"(d[26]), "+f"(d[27]), "+f"(d[28]), "+f"(d[29]), "+f"(d[30]), "+f"(d[31]), "+f"(d[32]), "+f"(d[33]), "+f"(d[34]), "+f"(d[35]), "+f"(d[36]), "+f"(d[37]), "+f"(d[38]), "+f"(d[39]), "+f"(d[40]), "+f"(d[41]), "+f"(d[42]), "+f"(d[43]), "+f"(d[44]), "+f"(d[45]), "+f"(d[46]), "+f"(d[47]), "+f"(d[48]), "+f"(d[49]), "+f"(d[50]), "+f"(d[51]), "+f"(d[52]), "+f"(d[53]), "+f"(d[54]), "+f"(d[55]), "+f"(d[56]), "+f"(d[57]), "+f"(d[58]), "+f"(d[59]), "+f"(d[60]), "+f"(d[61]), "+f"(d[62]), "+f"(d[63]), "+f"(d[64]), "+f"(d[65]), "+f"(d[66]), "+f"(d[67]), "+f"(d[68]), "+f"(d[69]), "+f"(d[70]), "+f"(d[71]), "+f"(d[72]), "+f"(d[73]), "+f"(d[74]), "+f"(d[75]), "+f"(d[76]), "+f"(d[77]), "+f"(d[78]), "+f"(d[79]), "+f"(d[80]), "+f"(d[81]), "+f"(d[82]), "+f"(d[83]), "+f"(d[84]), "+f"(d[85]), "+f"(d[86]), "+f"(d[87]), "+f"(d[88]), "+f"(d[89]), "+f"(d[90]), "+f"(d[91]), "+f"(d[92]), "+f"(d[93]), "+f"(d[94]), "+f"(d[95])
    : "l"(da), "l"(db), "r"(scale_d), "n"(TB), "n"(TA));
}

template<int TB> __device__ __forceinline__ void wgmma_rs_n192(float (&d)[96], uint32_t a0, uint32_t a1, uint32_t a2, uint32_t a3, uint64_t db, int scale_d) {
  asm volatile("{\n.reg .pred p;\nsetp.ne.b32 p, %101, 0;\n"
    "wgmma.mma_async.sync.aligned.m64n192k16.f32.bf16.bf16 {%0, %1, %2, %3, %4, %5, %6, %7, %8, %9, %10, %11, %12, %13, %14, %15, %16, %17, %18, %19, %20, %21, %22, %23, %24, %25, %26, %27, %28, %29, %30, %31, %32, %33, %34, %35, %36, %37, %38, %39, %40, %41, %42, %43, %44, %45, %46, %47, %48, %49, %50, %51, %52, %53, %54, %55, %56, %57, %58, %59, %60, %61, %62, %63, %64, %65, %66, %67, %68, %69, %70, %71, %72, %73, %74, %75, %76, %77, %78, %79, %80, %81, %82, %83, %84, %85, %86, %87, %88, %89, %90, %91, %92, %93, %94, %95}, {%96, %97, %98, %99}, %100, p, 1, 1, %102;\n}\n"
    : "+f"(d[0]), "+f"(d[1]), "+f"(d[2]), "+f"(d[3]), "+f"(d[4]), "+f"(d[5]), "+f"(d[6]), "+f"(d[7]), "+f"(d[8]), "+f"(d[9]), "+f"(d[10]), "+f"(d[11]), "+f"(d[12]), "+f"(d[13]), "+f"(d[14]), "+f"(d[15]), "+f"(d[16]), "+f"(d[17]), "+f"(d[18]), "+f"(d[19]), "+f"(d[20]), "+f"(d[21]), "+f"(d[22]), "+f"(d[23]), "+f"(d[24]), "+f"(d[25]), "+f"(d[26]), "+f"(d[27]), "+f"(d[28]), "+f"(d[29]), "+f"(d[30]), "+f"(d[31]), "+f"(d[32]), "+f"(d[33]), "+f"(d[34]), "+f"(d[35]), "+f"(d[36]), "+f"(d[37]), "+f"(d[38]), "+f"(d[39]), "+f"(d[40]), "+f"(d[41]), "+f"(d[42]), "+f"(d[43]), "+f"(d[44]), "+f"(d[45]), "+f"(d[46]), "+f"(d[47]), "+f"(d[48]), "+f"(d[49]), "+f"(d[50]), "+f"(d[51]), "+f"(d[52]), "+f"(d[53]), "+f"(d[54]), "+f"(d[55]), "+f"(d[56]), "+f"(d[57]), "+f"(d[58]), "+f"(d[59]), "+f"(d[60]), "+f"(d[61]), "+f"(d[62]), "+f"(d[63]), "+f"(d[64]), "+f"(d[65]), "+f"(d[66]), "+f"(d[67]), "+f"(d[68]), "+f"(d[69]), "+f"(d[70]), "+f"(d[71]), "+f"(d[72]), "+f"(d[73]), "+f"(d[74]), "+f"(d[75]), "+f"(d[76]), "+f"(d[77]), "+f"(d[78]), "+f"(d[79]), "+f"(d[80]), "+f"(d[81]), "+f"(d[82]), "+f"(d[83]), "+f"(d[84]), "+f"(d[85]), "+f"(d[86]), "+f"(d[87]), "+f"(d[88]), "+f"(d[89]), "+f"(d[90]), "+f"(d[91]), "+f"(d[92]), "+f"(d[93]), "+f"(d[94]), "+f"(d[95])
    : "r"(a0), "r"(a1), "r"(a2), "r"(a3), "l"(db), "r"(scale_d), "n"(TB));
}

template<int TB, int TA = 0> __device__ __forceinline__ void wgmma_ss_n128(float (&d)[64], uint64_t da, uint64_t db, int scale_d) {
  asm volatile("{\n.reg .pred p;\nsetp.ne.b32 p, %66, 0;\n"
    "wgmma.mma_async.sync.aligned.m64n128k16.f32.bf16.bf16 {%0, %1, %2, %3, %4, %5, %6, %7, %8, %9, %10, %11, %12, %13, %14, %15, %16, %17, %18, %19, %20, %21, %22, %23, %24, %25, %26, %27, %28, %29, %30, %31, %32, %33, %34, %35, %36, %37, %38, %39, %40, %41, %42, %43, %44, %45, %46, %47, %48, %49, %50, %51, %52, %53, %54, %55, %56, %57, %58, %59, %60, %61, %62, %63}, %64, %65, p, 1, 1, %68, %67;\n}\n"
    : "+f"(d[0]), "+f"(d[1]), "+f"(d[2]), "+f"(d[3]), "+f"(d[4]), "+f"(d[5]), "+f"(d[6]), "+f"(d[7]), "+f"(d[8]), "+f"(d[9]), "+f"(d[10]), "+f"(d[11]), "+f"(d[12]), "+f"(d[13]), "+f"(d[14]), "+f"(d[15]), "+f"(d[16]), "+f"(d[17]), "+f"(d[18]), "+f"(d[19]), "+f"(d[20]), "+f"(d[21]), "+f"(d[22]), "+f"(d[23]), "+f"(d[24]), "+f"(d[25]), "+f"(d[26]), "+f"(d[27]), "+f"(d[28]), "+f"(d[29]), "+f"(d[30]), "+f"(d[31]), "+f"(d[32]), "+f"(d[33]), "+f"(d[34]), "+f"(d[35]), "+f"(d[36]), "+f"(d[37]), "+f"(d[38]), "+f"(d[39]), "+f"(d[40]), "+f"(d[41]), "+f"(d[42]), "+f"(d[43]), "+f"(d[44]), "+f"(d[45]), "+f"(d[46]), "+f"(d[47]), "+f"(d[48]), "+f"(d[49]), "+f"(d[50]), "+f"(d[51]), "+f"(d[52]), "+f"(d[53]), "+f"(d[54]), "+f"(d[55]), "+f"(d[56]), "+f"(d[57]), "+f"(d[58]), "+f"(d[59]), "+f"(d[60]), "+f"(d[61]), "+f"(d[62]), "+f"(d[63])
    : "l"(da), "l"(db), "r"(scale_d), "n"(TB), "n"(TA));
}

template<int TB, int TA = 0> __device__ __forceinline__ void wgmma_ss_n64(float (&d)[32], uint64_t da, uint64_t db, int scale_d) {
  asm volatile("{\n.reg .pred p;\nsetp.ne.b32 p, %34, 0;\n"
    "wgmma.mma_async.sync.aligned.m64n64k16.f32.bf16.bf16 {%0, %1, %2, %3, %4, %5, %6, %7, %8, %9, %10, %11, %12, %13, %14, %15, %16, %17, %18, %19, %20, %21, %22, %23, %24, %25, %26, %27, %28, %29, %30, %31}, %32, %33, p, 1, 1, %36, %35;\n}\n"
    : "+f"(d[0]), "+f"(d[1]), "+f"(d[2]), "+f"(d[3]), "+f"(d[4]), "+f"(d[5]), "+f"(d[6]), "+f"(d[7]), "+f"(d[8]), "+f"(d[9]), "+f"(d[10]), "+f"(d[11]), "+f"(d[12]), "+f"(d[13]), "+f"(d[14]), "+f"(d[15]), "+f"(d[16]), "+f"(d[17]), "+f"(d[18]), "+f"(d[19]), "+f"(d[20]), "+f"(d[21]), "+f"(d[22]), "+f"(d[23]), "+f"(d[24]), "+f"(d[25]), "+f"(d[26]), "+f"(d[27]), "+f"(d[28]), "+f"(d[29]), "+f"(d[30]), "+f"(d[31])
    : "l"(da), "l"(db), "r"(scale_d), "n"(TB), "n"(TA));
}

template<int TB> __device__ __forceinline__ void wgmma_rs_n40(float (&d)[20], uint32_t a0, uint32_t a1, uint32_t a2, uint32_t a3, uint64_t db, int scale_d) {
  asm volatile("{\n.reg .pred p;\nsetp.ne.b32 p, %25, 0;\n"
    "wgmma.mma_async.sync.aligned.m64n40k16.f32.bf16.bf16 {%0, %1, %2, %3, %4, %5, %6, %7, %8, %9, %10, %11, %12, %13, %14, %15, %16, %17, %18, %19}, {%20, %21, %22, %23}, %24, p, 1, 1, %26;\n}\n"
    : "+f"(d[0]), "+f"(d[1]), "+f"(d[2]), "+f"(d[3]), "+f"(d[4]), "+f"(d[5]), "+f"(d[6]), "+f"(d[7]), "+f"(d[8]), "+f"(d[9]), "+f"(d[10]), "+f"(d[11]), "+f"(d[12]), "+f"(d[13]), "+f"(d[14]), "+f"(d[15]), "+f"(d[16]), "+f"(d[17]), "+f"(d[18]), "+f"(d[19])
    : "r"(a0), "r"(a1), "r"(a2), "r"(a3), "l"(db), "r"(scale_d), "n"(TB));
}

#define DEVI __device__ __forceinline__
DEVI uint32_t smem_u32(const void* p) { return (uint32_t)__cvta_generic_to_shared(p); }
DEVI void mbar_init(uint32_t bar, uint32_t cnt) { asm volatile("mbarrier.init.shared::cta.b64 [%0], %1;" :: "r"(bar), "r"(cnt)); }
DEVI void mbar_expect_tx(uint32_t bar, uint32_t bytes) { asm volatile("mbarrier.arrive.expect_tx.shared::cta.b64 _, [%0], %1;" :: "r"(bar), "r"(bytes) : "memory"); }
DEVI void mbar_arrive(uint32_t bar) { asm volatile("mbarrier.arrive.shared::cta.b64 _, [%0];" :: "r"(bar) : "memory"); }
DEVI void mbar_arrive_peer(uint32_t bar) {
  asm volatile("{\n.reg .b32 ra;\nmapa.shared::cluster.u32 ra, %0, %1;\nmbarrier.arrive.shared::cluster.b64 _, [ra];\n}" :: "r"(bar), "r"((blockIdx.x & 1) ^ 1) : "memory");
}
DEVI void bulk_s2peer(uint32_t a, uint32_t bytes, uint32_t bar) {
  asm volatile("{\n.reg .b32 ra, rb;\nmapa.shared::cluster.u32 ra, %0, %3;\nmapa.shared::cluster.u32 rb, %2, %3;\n"
               "cp.async.bulk.shared::cluster.shared::cta.mbarrier::complete_tx::bytes [ra], [%0], %1, [rb];\n}"
               :: "r"(a), "r"(bytes), "r"(bar), "r"((blockIdx.x & 1) ^ 1) : "memory");
}
DEVI void mbar_wait(uint32_t bar, uint32_t parity) {
  asm volatile("{\n.reg .pred p;\nLW:\nmbarrier.try_wait.parity.shared::cta.b64 p, [%0], %1;\n@!p bra LW;\n}" :: "r"(bar), "r"(parity) : "memory");
}
DEVI uint32_t mbar_test(uint32_t bar, uint32_t parity) {
  uint32_t r; asm volatile("{\n.reg .pred p;\nmbarrier.test_wait.parity.shared::cta.b64 p, [%1], %2;\nselp.u32 %0, 1, 0, p;\n}" : "=r"(r) : "r"(bar), "r"(parity) : "memory"); return r;
}
DEVI void mbar_wait_b(uint32_t bar, uint32_t parity) {
  asm volatile("{\n.reg .pred p;\n.reg .u32 it;\nmov.u32 it, 0;\nLW:\nmbarrier.try_wait.parity.shared::cta.b64 p, [%0], %1;\n@p bra LD;\n"
               "add.u32 it, it, 1;\nsetp.lt.u32 p, it, 0x1000000;\n@p bra LW;\ntrap;\nLD:\n}" :: "r"(bar), "r"(parity) : "memory");
}
DEVI void tma_2d(uint32_t dst, const CUtensorMap* m, int c0, int c1, uint32_t bar) {
  asm volatile("cp.async.bulk.tensor.2d.shared::cluster.global.mbarrier::complete_tx::bytes [%0], [%1, {%3, %4}], [%2];"
    :: "r"(dst), "l"(m), "r"(bar), "r"(c0), "r"(c1) : "memory");
}
DEVI void tma_3d(uint32_t dst, const CUtensorMap* m, int c0, int c1, int c2, uint32_t bar) {
  asm volatile("cp.async.bulk.tensor.3d.shared::cluster.global.mbarrier::complete_tx::bytes [%0], [%1, {%3, %4, %5}], [%2];"
    :: "r"(dst), "l"(m), "r"(bar), "r"(c0), "r"(c1), "r"(c2) : "memory");
}
#define POL_EF POL_FIRST
constexpr uint64_t POL_FIRST = 0x12F0000000000000ull, POL_NORMAL = 0x1000000000000000ull;
DEVI void tma_2d_h(uint32_t dst, const CUtensorMap* m, int c0, int c1, uint32_t bar, uint64_t pol) {
  asm volatile("cp.async.bulk.tensor.2d.shared::cluster.global.mbarrier::complete_tx::bytes.L2::cache_hint [%0], [%1, {%3, %4}], [%2], %5;"
    :: "r"(dst), "l"(m), "r"(bar), "r"(c0), "r"(c1), "l"(pol) : "memory");
}
DEVI void tma_3d_h(uint32_t dst, const CUtensorMap* m, int c0, int c1, int c2, uint32_t bar, uint64_t pol) {
  asm volatile("cp.async.bulk.tensor.3d.shared::cluster.global.mbarrier::complete_tx::bytes.L2::cache_hint [%0], [%1, {%3, %4, %5}], [%2], %6;"
    :: "r"(dst), "l"(m), "r"(bar), "r"(c0), "r"(c1), "r"(c2), "l"(pol) : "memory");
}
DEVI void bulk_g2s_h(uint32_t s, const void* g, uint32_t bytes, uint32_t bar, uint64_t pol = POL_EF) {
  asm volatile("cp.async.bulk.shared::cluster.global.mbarrier::complete_tx::bytes.L2::cache_hint [%0], [%1], %2, [%3], %4;"
    :: "r"(s), "l"(g), "r"(bytes), "r"(bar), "l"(pol) : "memory");
}
DEVI void tma_5d(uint32_t dst, const CUtensorMap* m, int c0, int c1, int c2, int c3, int c4, uint32_t bar, uint64_t pol) {
  asm volatile("cp.async.bulk.tensor.5d.shared::cluster.global.mbarrier::complete_tx::bytes.L2::cache_hint [%0], [%1, {%3, %4, %5, %6, %7}], [%2], %8;"
    :: "r"(dst), "l"(m), "r"(bar), "r"(c0), "r"(c1), "r"(c2), "r"(c3), "r"(c4), "l"(pol) : "memory");
}
DEVI void tma_prefetch_2d(const CUtensorMap* m, int c0, int c1) {
  asm volatile("cp.async.bulk.prefetch.tensor.2d.L2.global.tile [%0, {%1, %2}];" :: "l"(m), "r"(c0), "r"(c1) : "memory");
}
DEVI void tma_prefetch_3d(const CUtensorMap* m, int c0, int c1, int c2) {
  asm volatile("cp.async.bulk.prefetch.tensor.3d.L2.global.tile [%0, {%1, %2, %3}];" :: "l"(m), "r"(c0), "r"(c1), "r"(c2) : "memory");
}
DEVI void bulk_prefetch(const void* g, uint32_t bytes) { asm volatile("cp.async.bulk.prefetch.L2.global [%0], %1;" :: "l"(g), "r"(bytes) : "memory"); }
DEVI void bulk_g2s(uint32_t s, const void* g, uint32_t bytes, uint32_t bar) {
  asm volatile("cp.async.bulk.shared::cluster.global.mbarrier::complete_tx::bytes [%0], [%1], %2, [%3];" :: "r"(s), "l"(g), "r"(bytes), "r"(bar) : "memory");
}
DEVI void bulk_s2g(void* g, uint32_t s, uint32_t bytes) {
  asm volatile("cp.async.bulk.global.shared::cta.bulk_group [%0], [%1], %2;\ncp.async.bulk.commit_group;" :: "l"(g), "r"(s), "r"(bytes) : "memory");
}
template<int N> DEVI void bulk_wait() { asm volatile("cp.async.bulk.wait_group %0;" :: "n"(N) : "memory"); }
DEVI void fence_async_smem() { asm volatile("fence.proxy.async.shared::cta;" ::: "memory"); }
DEVI void fence_async_glob() { asm volatile("fence.proxy.async.global;" ::: "memory"); }
DEVI unsigned ld_rlx(const unsigned* p) { unsigned v; asm volatile("ld.relaxed.gpu.global.u32 %0, [%1];" : "=r"(v) : "l"(p) : "memory"); return v; }
DEVI void st_rlx(unsigned* p, unsigned v) { asm volatile("st.relaxed.gpu.global.u32 [%0], %1;" :: "l"(p), "r"(v) : "memory"); }
DEVI uint2 ldg_stream(const uint2* p) { uint2 v; asm volatile("ld.global.nc.L1::no_allocate.v2.u32 {%0, %1}, [%2];" : "=r"(v.x), "=r"(v.y) : "l"(p)); return v; }
DEVI void fence_rel() { asm volatile("fence.release.gpu;" ::: "memory"); }
DEVI uint4 ld_ll(const uint4* p) {
  uint4 v;
  asm volatile("{\n.reg .b128 t;\n.reg .b64 a, b;\nld.relaxed.gpu.global.b128 t, [%4];\nmov.b128 {a, b}, t;\nmov.b64 {%0, %1}, a;\nmov.b64 {%2, %3}, b;\n}"
               : "=r"(v.x), "=r"(v.y), "=r"(v.z), "=r"(v.w) : "l"(p) : "memory");
  return v;
}
DEVI void st_ll(uint4* p, uint32_t x, uint32_t y, uint32_t z, uint32_t w) {
  asm volatile("{\n.reg .b128 t;\n.reg .b64 a, b;\nmov.b64 a, {%1, %2};\nmov.b64 b, {%3, %4};\nmov.b128 t, {a, b};\nst.relaxed.gpu.global.b128 [%0], t;\n}"
               :: "l"(p), "r"(x), "r"(y), "r"(z), "r"(w) : "memory");
}
#define SPIN_MAX 0x1000000
DEVI uint4 poll_ll(const uint4* p, uint32_t mask, uint32_t tag) {
  uint4 v; int it = 0;
  do { v = ld_ll(p); if (++it > SPIN_MAX) __trap(); } while (!__all_sync(0xffffffffu, (v.w & mask) == tag));
  return v;
}
DEVI void poll_ll2(const uint4* p, const uint4* q, uint32_t mask, uint32_t tag, uint4& a, uint4& b) {
  int it = 0;
  do { a = ld_ll(p); b = ld_ll(q); if (++it > SPIN_MAX) __trap(); } while (!__all_sync(0xffffffffu, (a.w & mask) == tag && (b.w & mask) == tag));
}
DEVI void bar_sync(int id, int n) { asm volatile("bar.sync %0, %1;" :: "r"(id), "r"(n) : "memory"); }
DEVI void bar_arrive(int id, int n) { asm volatile("bar.arrive %0, %1;" :: "r"(id), "r"(n) : "memory"); }
DEVI void wg_fence() { asm volatile("wgmma.fence.sync.aligned;" ::: "memory"); }
DEVI void wg_commit() { asm volatile("wgmma.commit_group.sync.aligned;" ::: "memory"); }
template<int N> DEVI void wg_wait() { asm volatile("wgmma.wait_group.sync.aligned %0;" :: "n"(N) : "memory"); }
template<int N> DEVI void reg_inc() { asm volatile("setmaxnreg.inc.sync.aligned.u32 %0;" :: "n"(N)); }
template<int N> DEVI void reg_dec() { asm volatile("setmaxnreg.dec.sync.aligned.u32 %0;" :: "n"(N)); }
DEVI float ex2f(float x) { float y; asm("ex2.approx.ftz.f32 %0, %1;" : "=f"(y) : "f"(x)); return y; }
DEVI uint32_t pack_bf16(float lo, float hi) { uint32_t r; asm("cvt.rn.bf16x2.f32 %0, %1, %2;" : "=r"(r) : "f"(hi), "f"(lo)); return r; }
DEVI float bf_lo(uint32_t v) { return __uint_as_float(v << 16); }
DEVI float bf_hi(uint32_t v) { return __uint_as_float(v & 0xffff0000u); }
DEVI float bf_round(float x) { return bf_lo(pack_bf16(x, 0.f)); }
DEVI void stsm_x4(uint32_t addr, uint32_t a, uint32_t b, uint32_t c, uint32_t d) {
  asm volatile("stmatrix.sync.aligned.m8n8.x4.shared.b16 [%0], {%1,%2,%3,%4};" :: "r"(addr), "r"(a), "r"(b), "r"(c), "r"(d) : "memory");
}
DEVI void ldsm_x4(uint32_t addr, uint32_t& a, uint32_t& b, uint32_t& c, uint32_t& d) {
  asm volatile("ldmatrix.sync.aligned.m8n8.x4.shared.b16 {%0,%1,%2,%3}, [%4];" : "=r"(a), "=r"(b), "=r"(c), "=r"(d) : "r"(addr) : "memory");
}
DEVI uint4 lds128(uint32_t a) { uint4 v; asm volatile("ld.shared.v4.u32 {%0,%1,%2,%3}, [%4];" : "=r"(v.x), "=r"(v.y), "=r"(v.z), "=r"(v.w) : "r"(a) : "memory"); return v; }
DEVI void sts128(uint32_t a, uint4 v) { asm volatile("st.shared.v4.u32 [%0], {%1,%2,%3,%4};" :: "r"(a), "r"(v.x), "r"(v.y), "r"(v.z), "r"(v.w) : "memory"); }
DEVI float2 lds64f(uint32_t a) { float2 v; asm volatile("ld.shared.v2.f32 {%0,%1}, [%2];" : "=f"(v.x), "=f"(v.y) : "r"(a) : "memory"); return v; }
DEVI void sts64f(uint32_t a, float x, float y) { asm volatile("st.shared.v2.f32 [%0], {%1,%2};" :: "r"(a), "f"(x), "f"(y) : "memory"); }
DEVI uint32_t lds32(uint32_t a) { uint32_t v; asm volatile("ld.shared.u32 %0, [%1];" : "=r"(v) : "r"(a) : "memory"); return v; }
DEVI float lds32f(uint32_t a) { return __uint_as_float(lds32(a)); }
DEVI void sts32(uint32_t a, uint32_t v) { asm volatile("st.shared.u32 [%0], %1;" :: "r"(a), "r"(v) : "memory"); }
DEVI void sts32f(uint32_t a, float v) { sts32(a, __float_as_uint(v)); }
DEVI void sts16(uint32_t a, uint32_t v) { asm volatile("st.shared.u16 [%0], %1;" :: "r"(a), "h"((unsigned short)v) : "memory"); }
template<int N> DEVI void keep(float (&d)[N]) {
  #pragma unroll
  for (int i = 0; i < N; i++) asm volatile("" : "+f"(d[i]) :: "memory");
}
template<int N> DEVI void keep(uint32_t (&d)[N]) {
  #pragma unroll
  for (int i = 0; i < N; i++) asm volatile("" : "+r"(d[i]) :: "memory");
}
template<uint32_t HI> DEVI uint64_t mkd(uint32_t lo) { uint64_t r; asm("mov.b64 %0, {%1, %2};" : "=l"(r) : "r"(lo), "n"(HI)); return r; }
constexpr uint32_t HI128 = (1u << 30) | (1024 >> 4), HI64 = (2u << 30) | (512 >> 4);
#define VOFF(x) ((uint32_t)(x) * (uint32_t)(1 - 65536))
DEVI bool elect() { uint32_t p; asm volatile("{\n.reg .pred q;\nelect.sync _|q, 0xffffffff;\nselp.u32 %0, 1, 0, q;\n}" : "=r"(p)); return p; }
DEVI void warp_signal(uint32_t bar) { __syncwarp(); if (elect()) mbar_arrive(bar); }

struct Scratch {
  uint4 kv[128][4][1024];
  uint4 o[8][2][8][2][1024];
  uint4 x[8][16][2048];
  uint4 zero[1024];
  uint4 statP[8][2048];
  uint4 statF[2048];
  uint4 csP[16][8][96];
  uint4 best[8][16];
  uint4 row[16][256];
  uint4 yP[128][112][2];
  uint4 x2[8][256];
  uint4 patch[1024];
  unsigned flagKV[128][32];
  unsigned flagO[8][32];
  unsigned flagX[8][32];
  unsigned epoch;
};
__device__ __align__(1024) Scratch g_scr;
#define PROFT(cond, slot)
#define PROFW(cond, slot)
#define PROFD(cond, slot)
#define PROFX(cond, slot)
#define PROFY(cond, slot)

constexpr uint32_t SB0 = 65536, HOLE = 90112, SA2 = 98304, SB1 = 131072, SB2 = 155648, STG = 180224;
constexpr uint32_t KVA = 98304, KVB = 0, QO = 65536;
constexpr uint32_t MISC = 229376, CS = MISC, ONES = MISC + 768, BARS = MISC + 1792, INFO = MISC + 2208, WR = MISC + 2224, X2SEG = MISC + 2736, INFO2 = MISC + 2992;
constexpr uint32_t PAR = HOLE, HV = HOLE + 2048, RED = HOLE + 6144, PATCH = 196608;
constexpr uint32_t SMEM_BYTES = 232448;
enum { B_FULLQ = 0, B_EMPTYQ = 3, B_FULLW = 6, B_EMPTYW = 12, B_HAFREE = 18, B_OFREE = 20,
       B_XFREE = 21,
       B_KVRDY = 23, B_ORDY = 27, B_XRDY = 35, B_STGE = 39,
       B_KVFULL = 42, B_RES = 46, B_PAR = 47, B_STG = 48, B_PFREE = 51, B_COUNT = 52,
       B_ROW = 154 };
#define BAR(x) (sb + BARS + 8 * (x))
DEVI uint32_t qa_off(int s) { return s == 2 ? SA2 : (uint32_t)s * 32768u; }
DEVI uint32_t qb_off(int s) { return s == 0 ? SB0 : (s == 1 ? SB1 : SB2); }
DEVI int kb_order(int bc, int n) {
  const int e = n < 9 ? n - 2 : n - 9;
  return n < 2 ? 2 * bc + n : 2 * (((e < 4 ? e + 4 : e - 4 + (e - 4 >= (bc & 3))) + (bc & 4)) & 7) + (n >= 9);
}
DEVI int wo_order(int bc, int n) { return (n & 8) | ((n + (bc & 6)) & 7); }
DEVI uint32_t w_off(int s) { return (uint32_t)((0x104365 >> (4 * s)) & 7) * 32768u; }
DEVI uint32_t w_par(int n, int s, int L) { return ((n >= 6 && n < 12) ^ (s < 4 && L)); }

struct Params {
  CUtensorMap mX, mXh, mWq, mWo, mWg, mWu, mWp, mWd;
  const bf16 *x0, *wqkv, *wo, *wr, *wg, *wu, *wd;
  bf16* out;
  Scratch* g;
  unsigned map[128];
};
#define BID ((int)(P.map[blockIdx.x] & 255))
#define FID ((int)(P.map[blockIdx.x] >> 8))
DEVI uint32_t uni(uint32_t v) { return __shfl_sync(0xffffffffu, v, 0); }
#define PQ_N 8
#define PQ_T 700
#define PF0_N 10
#define PF0_T 1600
#define PF1_E 24
#define PF1_T 1100
#define POL_Q1 POL_NORMAL
#define POL_X POL_NORMAL
#define PFA0_BAR 3
#define PFA1_BAR 0
#define PFA0_M 0
#define PFA1_M 0
#define PFA0_T 900
#define PFA1_T 700
#define PF1_S PF0_N
#define PF1_D 0
#define POL_G POL_NORMAL
#define POL_U POL_FIRST
#define POL_D POL_FIRST
#define JQ_N 6
#define WDSRC (P.wd + (size_t)min(fid, 111) * 32768)
#define WD_N 4
#define THR_N 6
#define KV_D 1600
#define XD_D 600
#define W0_BAR 3
#define POL_Q0 POL_NORMAL
constexpr float LN_EPS = 1e-5f;
constexpr float QSCALE = 0.17677669529663687f * 1.4426950408889634f;

DEVI void fma8(float (&a)[8], uint4 v, float h) {
  a[0] = fmaf(bf_lo(v.x), h, a[0]); a[1] = fmaf(bf_hi(v.x), h, a[1]); a[2] = fmaf(bf_lo(v.y), h, a[2]); a[3] = fmaf(bf_hi(v.y), h, a[3]);
  a[4] = fmaf(bf_lo(v.z), h, a[4]); a[5] = fmaf(bf_hi(v.z), h, a[5]); a[6] = fmaf(bf_lo(v.w), h, a[6]); a[7] = fmaf(bf_hi(v.w), h, a[7]);
}
DEVI void gemv8(float (&a)[8], uint32_t wa, uint32_t ha, uint32_t hs) {
  #pragma unroll
  for (int n = 0; n < 8; n += 2) {
    uint4 v0 = lds128(wa + n * 512), v1 = lds128(wa + n * 512 + 512);
    float h0 = lds32f(ha), h1 = lds32f(ha + hs);
    ha += 2 * hs;
    fma8(a, v0, h0); fma8(a, v1, h1);
  }
}
DEVI uint4 ldsv128(uint32_t a) { uint4 v; asm volatile("ld.volatile.shared.v4.u32 {%0,%1,%2,%3}, [%4];" : "=r"(v.x), "=r"(v.y), "=r"(v.z), "=r"(v.w) : "r"(a) : "memory"); return v; }
DEVI float ldsv32f(uint32_t a) { float v; asm volatile("ld.volatile.shared.f32 %0, [%1];" : "=f"(v) : "r"(a) : "memory"); return v; }
DEVI uint32_t clk() { uint32_t t; asm volatile("mov.u32 %0, %%clock;" : "=r"(t)); return t; }
DEVI int fresh_tid() { int t; asm volatile("mov.u32 %0, %%tid.x;" : "=r"(t)); return t & 127; }
DEVI float fold8(const float (&a)[8]) {
  const int lane = threadIdx.x & 31;
  const bool u = lane & 16, v = lane & 8, x = lane & 4;
  float b0 = (u ? a[4] : a[0]) + __shfl_xor_sync(0xffffffffu, u ? a[0] : a[4], 16), b1 = (u ? a[5] : a[1]) + __shfl_xor_sync(0xffffffffu, u ? a[1] : a[5], 16);
  float b2 = (u ? a[6] : a[2]) + __shfl_xor_sync(0xffffffffu, u ? a[2] : a[6], 16), b3 = (u ? a[7] : a[3]) + __shfl_xor_sync(0xffffffffu, u ? a[3] : a[7], 16);
  float c0 = (v ? b2 : b0) + __shfl_xor_sync(0xffffffffu, v ? b0 : b2, 8), c1 = (v ? b3 : b1) + __shfl_xor_sync(0xffffffffu, v ? b1 : b3, 8);
  return (x ? c1 : c0) + __shfl_xor_sync(0xffffffffu, x ? c0 : c1, 4);
}
DEVI float swiglu(float g, float u) { g = bf_round(g); return bf_round(bf_round(__fdividef(g, 1.f + __expf(-g))) * bf_round(u)); }

DEVI void qk_issue(float (&s)[32], uint32_t qd, uint32_t kd) {
  wgmma_ss_n64<0>(s, mkd<HI64>(qd), mkd<HI64>(kd), 0);
  wgmma_ss_n64<0>(s, mkd<HI64>(qd + 2), mkd<HI64>(kd + 2), 1);
}
DEVI void pv_issue(float (&o)[20], const uint32_t (&p)[16], uint32_t vd, bool accum) {
  #pragma unroll
  for (int ks = 0; ks < 4; ks++)
    wgmma_rs_n40<1>(o, p[ks * 4], p[ks * 4 + 1], p[ks * 4 + 2], p[ks * 4 + 3], mkd<HI64>(vd + VOFF(ks * 64)), ks ? 1 : accum);
}
template<int J0, int J1> DEVI void exp_pack(const float (&s)[32], uint32_t (&p)[16]) {
  #pragma unroll
  for (int j = J0; j < J1; j++) p[j] = pack_bf16(ex2f(s[2 * j]), ex2f(s[2 * j + 1]));
}
DEVI bool attn_pack(const float (&o)[20], uint32_t (&ob)[8]) {
  const float lo = 5.421010862427522e-20f, hi = 1.8446744073709552e19f;
  float i0, i1; asm("rcp.approx.ftz.f32 %0, %1;" : "=f"(i0) : "f"(o[16])); asm("rcp.approx.ftz.f32 %0, %1;" : "=f"(i1) : "f"(o[18]));
  #pragma unroll
  for (int e = 0; e < 8; e++) ob[e] = pack_bf16(o[2 * e] * ((e & 1) ? i1 : i0), o[2 * e + 1] * ((e & 1) ? i1 : i0));
  return __all_sync(0xffffffffu, o[16] >= lo && o[16] <= hi && o[18] >= lo && o[18] <= hi);
}
DEVI void attn_store(const uint32_t (&ob)[8], uint32_t st, uint32_t bar) {
  stsm_x4(st, ob[0], ob[1], ob[2], ob[3]); stsm_x4(st ^ 32, ob[4], ob[5], ob[6], ob[7]);
  warp_signal(bar);
}
DEVI void attn_exact(uint32_t st, uint32_t kv, int t, bool hasprev, uint32_t bar) {
  const int lane = threadIdx.x & 31;
  #pragma unroll 1
  for (int row = ((threadIdx.x >> 5) & 3) * 16, n = 0; n < 16; n++, row++) {
    const int k1 = 256 + t * 64 + row;
    float m = -INFINITY, l = 0.f, o = 0.f;
    #pragma unroll 1
    for (int k0 = hasprev ? k1 - 255 : 256; k0 <= k1; k0 += 32) {
      const int k = min(k0 + lane, k1), r = k & 63;
      float sc = 0.f;
      #pragma unroll 1
      for (int c = 0; c < 16; c++) {
        uint32_t a = lds32(st + row * 64 + ((c * 4) ^ ((row & 6) << 3))), b = lds32(kv + (k >> 6) * 8192 + r * 64 + ((c * 4) ^ ((r & 6) << 3)));
        sc = fmaf(bf_lo(a), bf_lo(b), fmaf(bf_hi(a), bf_hi(b), sc));
      }
      float mn = fmaxf(m, sc);
      #pragma unroll 1
      for (int x = 16; x; x >>= 1) mn = fmaxf(mn, __shfl_xor_sync(0xffffffffu, mn, x));
      const float al = ex2f(m - mn), pr = ex2f(sc - mn);
      m = mn; l *= al; o *= al;
      #pragma unroll 1
      for (int q = k0; q <= min(k0 + 31, k1); q++) {
        const float z = __shfl_sync(0xffffffffu, pr, q - k0);
        uint32_t b = lds32(kv + (q >> 6) * 8192 + 4096 + (q & 63) * 64 + (((lane >> 1) * 4) ^ ((q & 6) << 3)));
        l += z; o = fmaf(z, (lane & 1) ? bf_hi(b) : bf_lo(b), o);
      }
    }
    __syncwarp();
    sts16(st + row * 64 + ((lane * 2) ^ ((row & 6) << 3)), pack_bf16(__fdividef(o, l), 0.f));
  }
  warp_signal(bar);
}

DEVI void merge_tri(float (&s)[32], const float (&sx)[32], int tdiag) {
  #pragma unroll
  for (int e = 0; e < 32; e++) { int c = 8 * (e >> 2) + (e & 1) - 8 * ((e >> 1) & 1); s[e] = (c > tdiag) ? s[e] : sx[e]; }
}
DEVI void split_tri(uint32_t (&p)[16], uint32_t (&px)[16], const uint32_t (&msk)[9]) {
  #pragma unroll
  for (int e = 0; e < 16; e++) { const uint32_t m = msk[(e >> 1) - (e & 1) + 1]; px[e] = p[e] & ~m; p[e] &= m; }
}

template<int J0> DEVI void qkv_store(const float (&a)[96], float p0, float p1, uint32_t d) {
  #pragma unroll
  for (int hh = 0; hh < 2; hh++) {
    const int j = 4 * (J0 + 2 * hh);
    stsm_x4(d ^ (hh << 5), pack_bf16(a[j] * p0, a[j + 1] * p0), pack_bf16(a[j + 2] * p1, a[j + 3] * p1),
                           pack_bf16(a[j + 4] * p0, a[j + 5] * p0), pack_bf16(a[j + 6] * p1, a[j + 7] * p1));
  }
}
DEVI void mean_step(float (&a)[96], float m0, float m1, uint32_t cd, bool z) {
  const uint32_t u0 = z ? 0u : __float_as_uint(m0), u1 = z ? 0u : __float_as_uint(m1);
  uint32_t ma[4] = {__byte_perm(u0, 0u, 0x1010), __byte_perm(u1, 0u, 0x1010), __byte_perm(u0, 0u, 0x3232), __byte_perm(u1, 0u, 0x3232)};
  keep(ma);
  wg_fence();
  wgmma_rs_n192<1>(a, ma[0], ma[1], ma[2], ma[3], mkd<2>(cd), 1);
  wg_commit();
}

template<bool FIRST> DEVI void qkv_block(float (&aX)[96], float (&aY)[96], uint32_t sb16, int s, int tX, int tY) {
  uint32_t a16 = sb16 + (qa_off(s) >> 4), b16 = (sb16 + (qb_off(s) >> 4)) | ((8192u >> 4) << 16);
  uint32_t ax = (a16 + tX * 512) | 0x10000u, ay = (a16 + tY * 512) | 0x10000u;
  wg_fence();
  #pragma unroll
  for (int ks = 0; ks < 4; ks++) {
    wgmma_ss_n192<1>(aX, mkd<HI128>(ax + ks * 2), mkd<HI128>(b16 + ks * 128), !(FIRST && ks == 0));
    wgmma_ss_n192<1>(aY, mkd<HI128>(ay + ks * 2), mkd<HI128>(b16 + ks * 128), !(FIRST && ks == 0));
  }
  wg_commit();
}
DEVI void qkv_half(float (&a)[96], uint32_t sb16, int t) {
  wg_fence();
  #pragma unroll
  for (int ks = 0; ks < 4; ks++)
    wgmma_ss_n192<1>(a, mkd<HI128>(((sb16 + t * 512) | 0x10000u) + ks * 2), mkd<HI128>(((sb16 + (SB0 >> 4)) | ((8192u >> 4) << 16)) + ks * 128), 1);
  wg_commit();
}
template<bool FIRST> DEVI void wo_block(float (&acc)[64], uint32_t sb16, int s, int wg) {
  uint32_t a16 = (sb16 + (w_off(s) >> 4) + wg * 256) | 0x10000u, b16 = (sb16 + (w_off(s) >> 4) + 1024) | ((8192u >> 4) << 16);
  wg_fence();
  #pragma unroll
  for (int ks = 0; ks < 4; ks++)
    wgmma_ss_n128<1>(acc, mkd<HI64>(a16 + (ks >> 1) * 512 + (ks & 1) * 2), mkd<HI128>(b16 + ks * 128), !(FIRST && ks == 0));
  wg_commit();
}
DEVI void consumer(const Params& P, uint32_t sb, int wg) {
  const int w = uni((threadIdx.x >> 5) & 3);
  #define LAYER uni(mbar_test(BAR(B_RES), 0))
  #define IDS L = LAYER; const int tid = fresh_tid(), lane = tid & 31
  const uint32_t ids = uni(P.map[blockIdx.x]);
  const int bi = (ids >> 4) & 7, rh = ids & 1, bc = (ids & 15) >> 1, fid = ids >> 8;
  const int tX = 3 - wg, tY = wg;
  constexpr uint32_t sb16 = 1024 >> 4;
  #pragma unroll 1
  while (true) {
    int L = LAYER;
    {
      float aX[96], aY[96];
      const bool lead = fresh_tid() == 0;
      if (L) mbar_wait(BAR(B_XRDY + wg * 2 + 1), 0);
      mbar_wait(BAR(B_FULLQ), 0);
      PROFW(threadIdx.x == 0, L * 8 + 1);
      qkv_block<true>(aX, aY, sb16, 0, tX, tY);
      #pragma unroll 1
      for (int n = 1, s = 1, ps = 0, ph = 0; n < 15; n++) {
        mbar_wait(BAR(B_FULLQ + s), ph ^ (s ? L : 0));
        PROFD(threadIdx.x == 0 && L && (n == 2 || n == 3 || n == 7 || n == 11 || n == 14), n == 2 ? 48 : 49 + (n >> 2));
        qkv_block<false>(aX, aY, sb16, s, tX, tY);
        wg_wait<1>(); if (lead) mbar_arrive(BAR(B_EMPTYQ + ps));
        ps = s; if (s == 2) { s = 0; ph ^= 1; } else s++;
      }
      mbar_wait(BAR(B_ROW), L);
      IDS;
      const uint32_t pa = sb + PAR + (w * 16 + (lane >> 2)) * 8;
      float2 p0 = lds64f(pa + tX * 512), p1 = lds64f(pa + tX * 512 + 64), p2 = lds64f(pa + tY * 512), p3 = lds64f(pa + tY * 512 + 64);
      mean_step(aX, p0.y, p1.y, sb16 + (CS >> 4), lane & 3);
      mbar_wait(BAR(B_FULLQ), 1);
      qkv_half(aX, sb16, tX); qkv_half(aY, sb16, tY);
      wg_wait<3>(); if (lead) mbar_arrive(BAR(B_EMPTYQ + 2));
      mbar_wait(BAR(B_EMPTYQ + 1), L); mbar_wait(BAR(B_EMPTYQ + 2), L);
      wg_wait<1>(); keep(aX);
      mean_step(aY, p2.y, p3.y, sb16 + (CS >> 4), fresh_tid() & 3);
      const int srow = w * 16 + (lane & 15);
      const uint32_t x0 = sb + srow * 64 + (((lane >> 4) ^ ((srow >> 1) & 3)) << 4), xX = x0 + (4 + tX) * 8192, xY = x0 + (4 + tY) * 8192;
      qkv_store<8>(aX, p0.x, p1.x, xX + KVA); qkv_store<16>(aX, p0.x, p1.x, xX + KVA + 4096);
      mbar_wait(BAR(B_PAR), L);
      const int l3 = fresh_tid() & 3, prow = (int)uni(lds32(sb + INFO)) - bi * 256;
      const bool pmine = (prow >> 4) == tX * 4 + w || (prow >> 4) == tY * 4 + w;
      const uint32_t poff = sb + (prow & 63) * 64 + ((l3 ^ ((prow >> 1) & 3)) << 4);
      if (pmine) { __syncwarp(); if (lane < 8) sts128(poff + KVA + (4 + (prow >> 6)) * 8192 + (lane >> 2) * 4096, lds128(sb + PATCH + 128 + (lane >> 2) * 128 + l3 * 16)); }
      warp_signal(BAR(B_KVRDY + wg * 2));
      qkv_store<12>(aX, p0.x, p1.x, xX + KVB); qkv_store<20>(aX, p0.x, p1.x, xX + KVB + 4096);
      wg_wait<0>(); keep(aY);
      if (lead) mbar_arrive(BAR(B_EMPTYQ));
      PROFW(threadIdx.x == 0, L * 8 + 2);
      qkv_store<8>(aY, p2.x, p3.x, xY + KVA); qkv_store<16>(aY, p2.x, p3.x, xY + KVA + 4096);
      qkv_store<12>(aY, p2.x, p3.x, xY + KVB); qkv_store<20>(aY, p2.x, p3.x, xY + KVB + 4096);
      p0.x *= QSCALE; p1.x *= QSCALE; p2.x *= QSCALE; p3.x *= QSCALE;
      mbar_wait(BAR(B_EMPTYQ), 1);
      qkv_store<0>(aX, p0.x, p1.x, x0 + QO + tX * 4096); qkv_store<4>(aX, p0.x, p1.x, x0 + QO + 16384 + tX * 4096);
      qkv_store<0>(aY, p2.x, p3.x, x0 + QO + tY * 4096); qkv_store<4>(aY, p2.x, p3.x, x0 + QO + 16384 + tY * 4096);
      if (pmine) {
        __syncwarp();
        if (lane < 24) sts128(poff + (lane < 8 ? QO + (lane >> 2) * 16384 + (prow >> 6) * 4096 : ((lane & 4) ? KVB : KVA) + (4 + (prow >> 6)) * 8192 + (lane >> 4) * 4096),
                              lds128(sb + PATCH + lane * 16));
      }
      fence_async_smem();
      warp_signal(BAR(B_KVRDY + wg * 2 + 1));
      bar_sync(1, 256);
    }
    PROFW(threadIdx.x == 0, L * 8 + 3);
    {
      IDS;
      float s0[32], s1[32], sx[32], o[20], op[20];
      uint32_t p0[16], p1[16], px[16], msk[9];
      const int tdiag = w * 16 + (lane >> 2) - 2 * (lane & 3);
      #pragma unroll
      for (int e = 0; e < 9; e++) msk[e] = ((8 * e - 8 > tdiag) ? 0xFFFFu : 0u) | ((8 * e - 7 > tdiag) ? 0xFFFF0000u : 0u);
      keep(msk);
      const uint32_t ones = (sb16 + (ONES >> 4)) << 16;
      const uint32_t qX = (sb16 + (QO >> 4) + tX * 256) | 0x10000u, qY = (sb16 + (QO >> 4) + tY * 256) | 0x10000u;
      const uint32_t kXB = (sb16 + (KVB >> 4) + tX * 512) | 0x10000u;
      uint32_t redo = 0;
      const uint32_t ost = sb + QO + (w * 16 + (lane & 15)) * 64 + (((lane >> 4) ^ ((lane >> 1) & 3)) << 4);
      #define QK2(q, k) do { qk_issue(s1, q, k); qk_issue(sx, q, (k) + 2048); } while (0)
      #define PV(o, p, v, b, acc) pv_issue(o, p, (v) + VOFF((b) * 512), acc)
      #define PV2(v0, v4) do { pv_issue(o, p1, v0, true); pv_issue(o, px, (v4) + VOFF(2048), true); } while (0)
      {
        const uint32_t kXA = kXB + ((KVA - KVB) >> 4), vB = VOFF((kXB & 0xffffu) + 256) + ones, vA = vB + VOFF((KVA - KVB) >> 4);
        wg_fence(); qk_issue(s0, qX, kXA + 1536); wg_commit(); qk_issue(s1, qX, kXA + 1024); wg_commit();
        wg_wait<1>(); keep(s0);
        exp_pack<0, 16>(s0, p0);
        wg_wait<0>(); keep(s1); keep(p0);
        wg_fence(); qk_issue(s0, qX + 1024, kXB + 1536); PV(o, p0, vA, 3, false); wg_commit();
        exp_pack<0, 16>(s1, p1);
        wg_wait<0>(); keep(s0); keep(o); keep(p0); keep(p1);
        wg_fence(); qk_issue(s1, qX + 1024, kXB + 1024); PV(o, p1, vA, 2, true); wg_commit();
        exp_pack<0, 16>(s0, p0);
        wg_wait<0>(); keep(s1); keep(o); keep(p0); keep(p1);
        wg_fence(); PV(op, p0, vB, 3, false); wg_commit();
        exp_pack<0, 16>(s1, p1); keep(p1);
        mbar_wait(BAR(B_KVFULL), L);
        wg_fence(); qk_issue(s0, qX, kXA + 512); PV(op, p1, vB, 2, true); wg_commit();
        wg_wait<0>(); keep(s0); keep(op); keep(p0); keep(p1);
      }
      #pragma unroll 1
      for (int h = 0; h < 2; h++) {
        const uint32_t kb16 = sb16 + ((h ? KVB : KVA) >> 4), kX = (kb16 + tX * 512) | 0x10000u, kY = (kb16 + tY * 512) | 0x10000u;
        const uint32_t qx = qX + h * 1024, qy = qY + h * 1024;
        const uint32_t onesP = bi ? ones : (kb16 + 1984) << 16;
        const uint32_t vX = VOFF(kb16 + tX * 512 + 256), vY = VOFF(kb16 + tY * 512 + 256);
        uint32_t ob[8];
        wg_fence(); QK2(qx, kX); wg_commit();
        exp_pack<0, 16>(s0, p0);
        wg_wait<0>(); keep(s1); keep(sx); keep(p0);
        wg_fence(); qk_issue(s0, qy, kY + 1536); PV(o, p0, vX + (wg ? onesP : ones), 1, true); wg_commit();
        merge_tri(s1, sx, tdiag); exp_pack<0, 16>(s1, p1); split_tri(p1, px, msk);
        wg_wait<0>(); keep(s0); keep(o); keep(p0); keep(p1); keep(px);
        wg_fence(); qk_issue(s1, qy, kY + 1024); PV2(vX + onesP, vX + ones); wg_commit();
        exp_pack<0, 16>(s0, p0);
        mbar_wait(BAR(B_KVFULL + h * 2 + 1), L);
        wg_wait<0>(); keep(s1); keep(o); keep(p0); keep(p1); keep(px);
        wg_fence(); qk_issue(s0, qy, kY + 512); wg_commit();
        bool ok = attn_pack(o, ob); keep(ob);
        wg_fence(); PV(o, p0, vY + (wg ? ones : onesP), 3, false); wg_commit();
        exp_pack<0, 16>(s1, p1);
        if (ok) attn_store(ob, ost + (h * 4 + tX) * 4096, BAR(B_ORDY + wg * 4 + h * 2)); else redo |= 1u << (h * 2);
        wg_wait<0>(); keep(s0); keep(o); keep(p0); keep(p1);
        wg_fence(); QK2(qy, kY); PV(o, p1, vY + onesP, 2, true); wg_commit();
        exp_pack<0, 16>(s0, p0);
        wg_wait<0>(); keep(s1); keep(sx); keep(o); keep(p0); keep(p1);
        wg_fence(); PV(o, p0, vY + onesP, 1, true); wg_commit();
        merge_tri(s1, sx, tdiag); exp_pack<0, 16>(s1, p1); split_tri(p1, px, msk); keep(p1); keep(px);
        mbar_wait(BAR(B_KVFULL + 2), L);
        wg_fence(); PV2(vY + onesP, vY + ones); wg_commit();
        qk_issue(s0, h ? qy : qX + 1024, kXB + 512); wg_commit();
        wg_wait<1>(); keep(o); keep(p0); keep(p1); keep(px);
        ok = attn_pack(o, ob);
        wg_wait<0>(); keep(s0);
        if (ok) attn_store(ob, ost + (h * 4 + tY) * 4096, BAR(B_ORDY + wg * 4 + h * 2 + 1)); else redo |= 2u << (h * 2);
        #pragma unroll
        for (int e = 0; e < 20; e++) o[e] = op[e];
      }
      #undef QK2
      #undef PV
      #undef PV2
      if (redo) {
        #pragma unroll 1
        for (int u = 0; u < 4; u++) if ((redo >> u) & 1) {
          const int h = u >> 1, t = (u & 1) ? tY : tX;
          attn_exact(sb + QO + (h * 4 + t) * 4096, sb + (h ? KVB : KVA), t, bi > 0, BAR(B_ORDY + wg * 4 + u));
        }
      }
    }
    PROFW(threadIdx.x == 0, L * 8 + 4);
    {
      IDS;
      const int t256 = wg * 128 + tid;
      float acc[64];
      const int tt = wg ^ rh;
      const int grow = bi * 256 + rh * 128 + tt * 64 + w * 16 + (lane >> 2);
      float al0 = 1.f, be0 = 0.f, al1 = 1.f, be1 = 0.f;
      const int idx0 = (int)uni(lds32(sb + INFO));
      const uint32_t tag = lds32(sb + INFO + 8) + L;
      uint4* const sp = &P.g->statP[bc][grow + (lane & 1) * 8];
      uint4* const yp = &P.g->yP[t256 >> 1][min(fid, 111)][t256 & 1];
      mbar_wait(BAR(B_FULLW), L);
      PROFW(t256 == 0, L * 8 + 5);
      wo_block<true>(acc, sb16, 0, tt);
      if (!(lane & 2)) st_ll(sp, 0u, 0u, 0u, 0u);
      uint4 fa = make_uint4(0u, 0u, 0u, 0u), fb = fa;
      uint2 wd[32];
      if (L) {
        if (fid < 112) st_ll(yp, 0u, 0u, 0u, 0u);
        fa = ld_ll(&P.g->statF[grow]); fb = ld_ll(&P.g->statF[grow + 8]);
      }
      #pragma unroll
      for (int n = 0; n < 32; n++) wd[n] = make_uint2(0u, 0u);
      #pragma unroll 1
      for (int n = 1, q = 1, pq = 0; n < 16; n++) {
        mbar_wait(BAR(B_FULLW + q), w_par(n, q, L));
        PROFD(t256 == 0 && !L && (n == 4 || n == 7 || n == 8 || n == 12), (n == 7 ? 63 : 41 + (n >> 2)));
        wo_block<false>(acc, sb16, q, tt);
        if (L && n == WD_N) {
          const uint2* src = (const uint2*)(WDSRC) + t256;
          #pragma unroll
          for (int e = 0; e < 32; e++) wd[e] = ldg_stream(src + e * 256);
        }
        wg_wait<1>(); if (tid == 0) mbar_arrive(BAR(B_EMPTYW + pq));
        pq = q; q = q == 5 ? 0 : q + 1;
      }
      if (L) {
        float r0 = rsqrtf(__uint_as_float(fa.y) + LN_EPS), r1 = rsqrtf(__uint_as_float(fb.y) + LN_EPS);
        if (grow != idx0) { al0 = 1.f + r0; be0 = -__uint_as_float(fa.x) * r0; }
        if (grow + 8 != idx0) { al1 = 1.f + r1; be1 = -__uint_as_float(fb.x) * r1; }
      }
      mbar_wait(BAR(B_RES), L);
      const int srow = tt * 64 + w * 16 + (lane & 15);
      const uint32_t ra = sb + rh * 16384 + srow * 128, sw = ((lane >> 4) ^ (srow & 7)) << 4;
      if ((idx0 >> 4) == bi * 16 + rh * 8 + tt * 4 + w) {
        int r = idx0 & 127;
        if (lane < 16) sts128(sb + (lane >> 3) * 32768 + rh * 16384 + r * 128 + (((lane & 7) ^ (r & 7)) << 4), lds128(sb + X2SEG + lane * 16));
        __syncwarp();
      }
      uint32_t rs[32];
      #pragma unroll
      for (int jj = 0; jj < 8; jj++) ldsm_x4((ra + (jj >> 2) * 32768) + (sw ^ ((jj & 3) << 5)), rs[4 * jj], rs[4 * jj + 1], rs[4 * jj + 2], rs[4 * jj + 3]);
      float rf[64];
      #pragma unroll
      for (int e = 0; e < 32; e++) { rf[2 * e] = fmaf(bf_lo(rs[e]), (e & 1) ? al1 : al0, (e & 1) ? be1 : be0); rf[2 * e + 1] = fmaf(bf_hi(rs[e]), (e & 1) ? al1 : al0, (e & 1) ? be1 : be0); }
      keep(rf);
      mbar_wait(BAR(B_RES), L);
      wg_wait<0>(); keep(acc);
      if (tid == 0) mbar_arrive(BAR(B_EMPTYW + 3));
      PROFW(t256 == 0, L * 8 + 6);
      #pragma unroll
      for (int jj = 0; jj < 8; jj++) {
        float* a = acc + 8 * jj;
        #pragma unroll
        for (int e = 0; e < 8; e++) a[e] += rf[8 * jj + e];
        stsm_x4((ra + (jj >> 2) * 32768) + (sw ^ ((jj & 3) << 5)), pack_bf16(a[0], a[1]), pack_bf16(a[2], a[3]), pack_bf16(a[4], a[5]), pack_bf16(a[6], a[7]));
        if (jj == 7) fence_async_smem();
        if ((jj & 3) == 3) warp_signal(BAR(B_XRDY + wg * 2 + (jj >> 2)));
      }
      {
        float s1a = 0.f, s2a = 0.f, da = 0.f, s1b = 0.f, s2b = 0.f, db = 0.f;
        #pragma unroll
        for (int j = 0; j < 16; j++) {
          const float* a = acc + 4 * j; float2 wv = lds64f(sb + WR + j * 32 + (lane & 3) * 8);
          s1a += a[0] + a[1]; s1b += a[2] + a[3];
          s2a = fmaf(a[0], a[0], s2a); s2b = fmaf(a[2], a[2], s2b); s2a = fmaf(a[1], a[1], s2a); s2b = fmaf(a[3], a[3], s2b);
          da = fmaf(a[0], wv.x, da); db = fmaf(a[2], wv.x, db); da = fmaf(a[1], wv.y, da); db = fmaf(a[3], wv.y, db);
        }
        bool odd = lane & 1;
        float u1 = (odd ? s1b : s1a) + __shfl_xor_sync(0xffffffffu, odd ? s1a : s1b, 1);
        float u2 = (odd ? s2b : s2a) + __shfl_xor_sync(0xffffffffu, odd ? s2a : s2b, 1);
        float u3 = (odd ? db : da) + __shfl_xor_sync(0xffffffffu, odd ? da : db, 1);
        u1 += __shfl_xor_sync(0xffffffffu, u1, 2); u2 += __shfl_xor_sync(0xffffffffu, u2, 2); u3 += __shfl_xor_sync(0xffffffffu, u3, 2);
        if (!(lane & 2)) st_ll(sp, __float_as_uint(u1), __float_as_uint(u2), __float_as_uint(u3), tag);
      }
      PROFW(t256 == 0, L * 8 + 7);
      if (L) {
        mbar_wait(BAR(B_PAR), 0);
        { float2 pa = lds64f(sb + PAR + (grow & 127) * 8), pb = lds64f(sb + PAR + (grow & 127) * 8 + 64); al0 = pa.x; be0 = pa.y; al1 = pb.x; be1 = pb.y; }
        #pragma unroll
        for (int j = 0; j < 16; j++) {
          rs[2 * j] = pack_bf16(fmaf(acc[4 * j], al0, be0), fmaf(acc[4 * j + 1], al0, be0));
          rs[2 * j + 1] = pack_bf16(fmaf(acc[4 * j + 2], al1, be1), fmaf(acc[4 * j + 3], al1, be1));
        }
        const int idx1 = (int)lds32(sb + INFO + 4);
        #pragma unroll
        for (int jj = 0; jj < 8; jj++) stsm_x4((ra + (jj >> 2) * 32768) + (sw ^ ((jj & 3) << 5)), rs[4 * jj], rs[4 * jj + 1], rs[4 * jj + 2], rs[4 * jj + 3]);
        __syncwarp();
        {
          const int r0 = (grow & ~15) + (lane >> 4), skip = idx1 - r0;
          const uint32_t a0 = sb + ((lane >> 3) & 1) * 32768 + (r0 & 255) * 128 + (((lane & 7) ^ (lane >> 4)) << 4);
          uint4* dst = (uint4*)(P.out + (size_t)r0 * 1024 + bc * 128) + (lane & 15);
          #pragma unroll
          for (int it = 0; it < 8; it++) { uint4 v = lds128((a0 + it * 256) ^ ((it & 3) << 5)); if (skip != 2 * it) dst[it * 256] = v; }
        }
        PROFW(t256 == 0, 16);
        if (fid < 112) {
          const int q = wg * 2 + (w >> 1);
          float g[8] = {0.f, 0.f, 0.f, 0.f, 0.f, 0.f, 0.f, 0.f};
          mbar_wait(BAR(B_FULLW + q), 0);
          bar_sync(3, 384);
          PROFW(t256 == 0, 29);
          #pragma unroll 1
          for (int n = 0; n < 4; n++) gemv8(g, sb + w_off(q) + (w & 1) * 16384 + n * 4096 + lane * 16, sb + HV + (q * 256 + n * 64 + (lane >> 2)) * 4, 32);
          sts32f(sb + PAR + 1024 + (q * 2 + (w & 1)) * 128 + ((lane & 3) * 8 + (lane >> 2)) * 4, fold8(g));
          bar_sync(1, 256);
          const uint32_t d = sb + PAR + 1024 + lane * 4;
          const float act = swiglu((lds32f(d) + lds32f(d + 256)) + (lds32f(d + 512) + lds32f(d + 768)),
                                   (lds32f(d + 128) + lds32f(d + 384)) + (lds32f(d + 640) + lds32f(d + 896)));
          PROFW(t256 == 0, 26);
          float y0 = 0.f, y1 = 0.f, y2 = 0.f, y3 = 0.f;
          sts32f(sb + HV + t256 * 4, act);
          __syncwarp();
          uint4 a4;
          #pragma unroll
          for (int n = 0; n < 32; n++) {
            if (!(n & 3)) a4 = lds128(sb + HV + (t256 >> 5) * 128 + n * 4);
            float av = __uint_as_float((n & 3) == 0 ? a4.x : ((n & 3) == 1 ? a4.y : ((n & 3) == 2 ? a4.z : a4.w)));
            y0 = fmaf(bf_lo(wd[n].x), av, y0); y1 = fmaf(bf_hi(wd[n].x), av, y1); y2 = fmaf(bf_lo(wd[n].y), av, y2); y3 = fmaf(bf_hi(wd[n].y), av, y3);
          }
          st_ll(yp, __float_as_uint(y0), __float_as_uint(y1), __float_as_uint(y2), (__float_as_uint(y3) & ~255u) | (lds32(sb + INFO + 12) + 1));
          PROFW(t256 == 0, 27);
        }
        return;
      }
    }
  }
  #undef IDS
  #undef LAYER
}

DEVI void loader(const Params& P, uint32_t sb) {
  const int lane = threadIdx.x & 31;
  const int bid = uni(BID), bi = bid >> 4, bp = bid & 15, rh = bp & 1, bc = bp >> 1;
  uint32_t phq = 0, tag = 0;
  #pragma unroll 1
  for (int L = 0; L < 2; L++) {
    int s = 0;
    uint32_t rdy = 0;
    #pragma unroll 1
    for (int n = L ? 0 : 3; n < 16; n++) {
      int kb = L ? kb_order(bc, n) : n;
      mbar_wait(BAR(B_EMPTYQ + s), (phq >> s) & 1);
      phq ^= 1u << s;
      if (L && n == 1) { mbar_wait(BAR(B_XRDY + 1), 0); mbar_wait(BAR(B_XRDY + 3), 0); }
      if (lane == 0) {
        mbar_expect_tx(BAR(B_FULLQ + s), L && n < 2 ? 40960 : 57344);
        tma_3d_h(sb + qb_off(s), &P.mWq, bp * 64, kb * 64, 0, BAR(B_FULLQ + s), L ? POL_Q1 : POL_Q0);
        if (!L) tma_2d(sb + qa_off(s), &P.mX, kb * 64, bi * 256, BAR(B_FULLQ + s));
      }
      if (L && n >= 2) {
        if (((rdy >> (2 * kb)) & 3) != 3) {
          do { rdy = __ballot_sync(0xffffffffu, ld_rlx(&P.g->flagX[bi][lane]) == tag); } while (((rdy >> (2 * kb)) & 3) != 3);
          fence_async_glob();
        }
        if (n == 3 || n == 4) mbar_wait(BAR(B_XFREE + n - 3), 0);
        if (lane == 0) bulk_g2s_h(sb + qa_off(s), P.g->x[bi][kb], 32768, BAR(B_FULLQ + s), POL_X);
      }
      PROFY(L && lane == 0 && (n == 2 || n == 3 || n == 9), n == 9 ? 60 : 56 + n);
      if (L && n == 2) { mbar_wait(BAR(B_FULLQ), 0); mbar_wait(BAR(B_FULLQ + 1), 1); if (lane < 2) mbar_arrive_peer(BAR(B_XFREE + lane)); }
      s = (s == 2) ? 0 : s + 1;
    }
    for (int q = 0; q < 3; q++) mbar_wait(BAR(B_EMPTYQ + q), (phq >> q) & 1);
    mbar_wait(BAR(B_PAR), L);
    tag = lds32(sb + INFO + 8) + L;
    #pragma unroll 1
    for (int q = 0; q < 4; q++) {
            if (bi) {
        const unsigned* f = &P.g->flagKV[bid - 16][q];
        uint32_t v0 = ld_rlx(f), v1;
        __nanosleep(100);
        while (true) { v1 = ld_rlx(f); if (v0 == tag) break; v0 = ld_rlx(f); if (v1 == tag) break; }
        fence_async_glob();
      }
      if (lane == 0) {
        mbar_expect_tx(BAR(B_KVFULL + q), 16384);
        bulk_g2s_h(sb + ((q >> 1) ? KVB : KVA) + ((q & 1) ? 0 : 16384), bi ? P.g->kv[bid - 16][q] : P.g->zero, 16384, BAR(B_KVFULL + q));
      }
      PROFY(!L && lane == 0 && bi && q != 2, 34 + (q + 1) / 2);
    }
    mbar_wait(BAR(B_ORDY), L); mbar_wait(BAR(B_ORDY + 4), L);
    {
      const uint4* src = P.g->o[bi][0][0][rh];
      rdy = 0;
      #pragma unroll 1
      for (int n = 0, q = 0; n < 16; n++, q = q == 5 ? 0 : q + 1) {
        const int j = wo_order(bc, n);
        if (((rdy >> (2 * j)) & 3) != 3) {
          do { rdy = __ballot_sync(0xffffffffu, ld_rlx(&P.g->flagO[bi][lane]) == tag); } while (((rdy >> (2 * j)) & 3) != 3);
          fence_async_glob();
        }
        if (n >= 2) mbar_wait(n < 6 ? BAR(B_HAFREE + (n >> 2)) : BAR(B_EMPTYW + q), n < 6 ? L : w_par(n - 6, q, L));
        if (n == THR_N) mbar_wait(BAR(B_OFREE), L);
        if (lane == 0) { mbar_expect_tx(BAR(B_FULLW + q), 16384); bulk_g2s_h(sb + w_off(q), src + j * 2048, 16384, BAR(B_FULLW + q)); }
      }
    }
    mbar_wait(BAR(B_OFREE), L);
  }
}

DEVI void ffn_prefetch(const Params& P, int q) {
  bulk_prefetch(q < 16 ? ((q & 1) ? P.wu : P.wg) + ((q >> 1) * 128 + blockIdx.x) * 3584 : P.wd + (min(FID, 111) * 8 + q - 16) * 4096, q < 16 ? 7168 : 8192);
}
DEVI void storer(const Params& P, uint32_t sb, int wg) {
  const int bid = uni(BID), bi = bid >> 4, rh = bid & 1, bc = (bid & 15) >> 1;
  const bool one = (threadIdx.x & 31) == 0;
  char* const g = (char*)P.g;
  #pragma unroll 1
  for (int L = 0; L < 2; L++) {
    mbar_wait(BAR(B_PAR), L);
    const uint32_t tag = lds32(sb + INFO + 8) + L;
    #pragma unroll 1
    for (int u = 0; u < 4; u++) {
      const int h = u >> 1, hi = (u & 1) ^ 1;
      uint32_t src, dst, fl, b0, b1;
      if (!wg) {
        src = (h ? KVB : KVA) + (2 + hi) * 16384; dst = offsetof(Scratch, kv) + (bid * 4 + u) * 16384; fl = offsetof(Scratch, flagKV) + (bid * 32 + u) * 4;
        b0 = BAR(B_KVRDY + (u ? 1 : 0)); b1 = b0 + 16;
      } else {
        src = QO + (h * 2 + hi) * 8192; dst = offsetof(Scratch, o) + ((((bi * 2 + h) * 8 + bc) * 2 + hi) * 2 + rh) * 8192;
        fl = offsetof(Scratch, flagO) + (bi * 32 + h * 16 + (bid & 15)) * 4;
        b0 = BAR(B_ORDY + u); b1 = b0 + 32;
      }
      mbar_wait(b0, L); mbar_wait(b1, L);
      fence_async_smem();
      PROFY(one && !L && u == wg, u ? 46 : 8);
      if (one && (wg || bi < 7)) bulk_s2g(g + dst, sb + src, 16384 >> wg);
      if (one && wg && u == 3) mbar_arrive(BAR(B_HAFREE + 1));
      if (wg && hi) continue;
      bulk_wait<0>();
      PROFY(one && !L && u == wg, u ? 61 : 62);
      fence_rel();
      if (one) { st_rlx((unsigned*)(g + fl), tag); if (!hi) mbar_arrive(BAR(B_HAFREE + h + (wg & h))); }
      PROFY(one && !L && (wg || u == 0 || u == 3), wg ? (u == 1 ? 38 : 54) : 32 + (u & 1));
    }
    if (L == 0) {
      char* dst = g + (offsetof(Scratch, x) + (bi * 16 + 2 * bc) * 32768 + rh * 16384);
      unsigned* f = (unsigned*)(g + (offsetof(Scratch, flagX) + (bi * 32 + bc * 4 + rh) * 4));
      const uint32_t a = sb + rh * 16384;
      if (wg == 0) {
        mbar_wait(BAR(B_XRDY), 0); mbar_wait(BAR(B_XRDY + 2), 0);
        fence_async_smem();
        PROFY(one, 41);
        if (one) bulk_s2g(dst, a, 16384);
        bulk_wait<0>();
        PROFY(one, 45);
        if (one) { mbar_arrive(BAR(B_XFREE)); mbar_arrive(BAR(B_PFREE)); }
        fence_rel();
        mbar_wait(BAR(B_XRDY + 1), 0); mbar_wait(BAR(B_XRDY + 3), 0);
        if (one) { st_rlx(f, tag); bulk_s2g(dst + 32768, a + 32768, 16384); }
        PROFY(one, 56);
        bulk_wait<0>();
        if (one) mbar_arrive(BAR(B_XFREE + 1));
        fence_rel();
        if (one) st_rlx(f + 2, tag);
        PROFY(one, 57);
      } else {
        mbar_wait(BAR(B_XRDY + 1), 0); mbar_wait(BAR(B_XRDY + 3), 0);
        mbar_wait(BAR(B_PFREE), 0);
        if (one) bulk_s2peer(a, 16384, BAR(B_FULLQ));
        { const uint32_t t0 = clk(); while (clk() - t0 < XD_D); }
        if (one) bulk_s2peer(a + 32768, 16384, BAR(B_FULLQ + 1));
      }
      if (wg == 0) {
        uint32_t t0 = clk() + PF1_D;
        #pragma unroll 1
        for (int q = PF1_S; q < PF1_E; q++) { while ((int)(clk() - t0) < 0) __nanosleep(50); if (one) ffn_prefetch(P, q); t0 += PF1_T; }
      }
    }
  }
}

DEVI void stg_issue(const Params& P, int c, uint32_t d, uint32_t du, uint32_t b) {
  mbar_expect_tx(b, 16384);
  if (c < 8) { tma_2d_h(d, &P.mWg, FID * 32, c * 128, b, POL_G); tma_2d_h(d + du, &P.mWu, FID * 32, c * 128, b, POL_U); }
  else if (c < 12) tma_3d_h(d, &P.mWd, 0, FID * 32 + (c - 8) * 8, 0, b, POL_D);
  else tma_2d_h(d, &P.mWp, FID * 32, (c - 12) * 256, b, POL_EF);
}
DEVI void stager(const Params& P, uint32_t sb) {
  {
    const int b = blockIdx.x;
    uint32_t t0 = clk();
    #pragma unroll 1
    for (int q = 0; q < PQ_N; q++) { bulk_prefetch(P.wqkv + (q * 128 + b) * 3072, 6144); while (clk() - t0 < PQ_T); t0 += PQ_T; }
    bulk_prefetch(P.wo + b * 8192, 16384);
    #pragma unroll 1
    for (int q = 0; q < PF0_N; q++) {
      while (clk() - t0 < PF0_T);
      t0 += PF0_T;
      ffn_prefetch(P, q);
    }
  }
  const int bid = BID, bi = bid >> 4, rh = bid & 1, bc = (bid & 15) >> 1;
  #pragma unroll 1
  for (int L = 0; L < 2; L++) {
    const int nch = FID >= 112 ? 0 : (L ? 8 : (FID < 96 ? 16 : 12));
    mbar_wait(BAR(B_KVFULL + W0_BAR), L);
    #pragma unroll 1
    for (int n = 0, q = 0; n < 16; n++, q = q == 5 ? 0 : q + 1) {
      if (n >= 2) mbar_wait(n < 6 ? BAR(B_HAFREE + (n >> 2)) : BAR(B_EMPTYW + q), n < 6 ? L : w_par(n - 6, q, L));
      if (n == THR_N) mbar_wait(BAR(B_OFREE), L);
      mbar_expect_tx(BAR(B_FULLW + q), 16384);
      tma_5d(sb + w_off(q) + 16384, &P.mWo, 0, 0, n >> 3, 2 * (wo_order(bc, n) & 7), 2 * bc, BAR(B_FULLW + q), L ? POL_EF : POL_NORMAL);
    }
    mbar_expect_tx(BAR(B_RES), 32768);
    #pragma unroll 1
    for (int e = 0; e < 2; e++) {
      mbar_wait(BAR(B_EMPTYW + 4 + e), 1);
      if (L) bulk_g2s_h(sb + e * 32768 + rh * 16384, P.g->x[bi][2 * bc + e] + rh * 1024, 16384, BAR(B_RES));
      else tma_2d_h(sb + e * 32768 + rh * 16384, &P.mXh, bc * 128 + e * 64, bi * 256 + rh * 128, BAR(B_RES), POL_EF);
    }
    if (L == 0) { mbar_arrive_peer(BAR(B_PFREE)); mbar_wait(BAR(B_EMPTYW), 0); mbar_wait(BAR(B_EMPTYW + 1), 0); }
    #pragma unroll 1
    for (int c = 0, slot = 0; c < nch; c++, slot = slot == 2 ? 0 : slot + 1) {
      mbar_wait(L ? BAR(B_EMPTYW + (c >> 1)) : BAR(B_STGE + slot), L | ((0x71c7 >> c) & 1));
      stg_issue(P, c, L ? sb + w_off(c >> 1) + (c & 1) * 8192 : sb + STG + slot * 16384, 8192 << L, L ? BAR(B_FULLW + (c >> 1)) : BAR(B_STG + slot));
    }
  }
}
DEVI void sum8(uint4 v, float& s1, float& s2) {
  float e[8] = {bf_lo(v.x), bf_hi(v.x), bf_lo(v.y), bf_hi(v.y), bf_lo(v.z), bf_hi(v.z), bf_lo(v.w), bf_hi(v.w)};
  #pragma unroll
  for (int q = 0; q < 8; q++) { s1 += e[q]; s2 = fmaf(e[q], e[q], s2); }
}
DEVI uint4 norm8(uint4 x, float m, float rs, uint32_t d, uint32_t d2) {
  #define HN(v) pack_bf16((bf_lo(v) - m) * rs, (bf_hi(v) - m) * rs)
  uint4 b = make_uint4(HN(x.x), HN(x.y), HN(x.z), HN(x.w));
  #undef HN
  sts128(d, make_uint4(b.x << 16, b.x & 0xffff0000u, b.y << 16, b.y & 0xffff0000u));
  sts128(d + d2, make_uint4(b.z << 16, b.z & 0xffff0000u, b.w << 16, b.w & 0xffff0000u));
  return b;
}
DEVI uint4 best4(uint32_t p) {
  uint4 a = lds128(p), b = lds128(p + 16), c = lds128(p + 32), d = lds128(p + 48);
  if (b.x > a.x) a = b;
  if (d.x > c.x) c = d;
  return c.x > a.x ? c : a;
}
#define FL(x) __uint_as_float(x)
#define UI(x) __float_as_uint(x)
DEVI void qkv_params(const Params& P, uint32_t sb, int row, uint32_t tag, bool second) {
  uint4 v0, v1; poll_ll2(&P.g->statF[row], &P.g->statF[row + 128], 0xffffffffu, tag, v0, v1);
  #pragma unroll 1
  for (int q = 0; q < 2; q++) {
    float var = FL(v0.y), c = rsqrtf(var + LN_EPS);
    if (second) { c += 1.f; c *= rsqrtf(fmaf(var * c, c, LN_EPS)); }
    const float mh = bf_round(FL(v0.x));
    sts64f(sb + PAR + q * 1024 + (row & 127) * 8, c, FL(pack_bf16(mh, FL(v0.x) - mh)));
    v0 = v1;
  }
  warp_signal(BAR(B_ROW));
}
DEVI void aux(const Params& P, uint32_t sb) {
  int tid = fresh_tid();
  #define lane (tid & 31)
  #define wq (tid >> 5)
  uint32_t ids = P.map[blockIdx.x], tag;
  #define bid ((int)(ids & 255))
  #define fid ((int)(ids >> 8))
  #define bi (bid >> 4)
  #define bp (bid & 15)
  #define bc (bp >> 1)
  #define FRESH() do { tid = fresh_tid(); uint4 z_ = ldsv128(sb + INFO2 + 16); ids = z_.y; tag = z_.z + L; idx = z_.w; } while (0)
  {
    const uint32_t epoch = ld_rlx(&P.g->epoch);
    if (tid == 0) {
      mbar_expect_tx(BAR(B_STG), 49152);
      tma_3d(sb + STG, &P.mWq, bp * 64, bi * 128, 0, BAR(B_STG));
      tma_3d(sb + STG + 24576, &P.mWq, bp * 64, bi * 128 + 64, 0, BAR(B_STG));
    }
    __syncwarp();
    sts64f(sb + ONES + tid * 8, FL(0x3F803F80u), FL(0x3F803F80u));
    float s1 = 0.f, s2 = 0.f;
    { uint4 v = __ldg((const uint4*)P.wr + tid);
      if ((tid >> 4) == bc) norm8(v, 0.f, 1.f, sb + WR + (tid & 15) * 32, 16);
      sum8(v, s1, s2);
      #pragma unroll 1
      for (int o = 16; o; o >>= 1) s1 += __shfl_xor_sync(0xffffffffu, s1, o);
      sts32f(sb + INFO2 + wq * 4, s1); }
    const uint4* src = (const uint4*)(P.x0 + (size_t)bid * 16384) + (tid >> 3) * 128 + (tid & 7);
    s1 = 0.f; s2 = 0.f;
    #pragma unroll 1
    for (int it = 0; it < 16; it += 4) {
      uint4 v0 = __ldg(src + it * 8), v1 = __ldg(src + it * 8 + 8), v2 = __ldg(src + it * 8 + 16), v3 = __ldg(src + it * 8 + 24);
      #pragma unroll 1
      for (int q = 0; q < 4; q++) { sum8(v0, s1, s2); v0 = v1; v1 = v2; v2 = v3; }
    }
    #pragma unroll 1
    for (int o = 1; o < 8; o <<= 1) { s1 += __shfl_xor_sync(0xffffffffu, s1, o); s2 += __shfl_xor_sync(0xffffffffu, s2, o); }
    tag = ((epoch % 16383u) + 1u) << 2;
    if (tid == 0) { sts128(sb + INFO, make_uint4(0x40000000u, 0u, tag, ((epoch % 127u) + 1u) << 1)); sts128(sb + INFO2 + 16, make_uint4(epoch, ids, tag, 0x40000000u)); }
    float m = s1 * (1.f / 1024.f);
    if ((tid & 7) == 0) st_ll(&P.g->statF[bid * 16 + (tid >> 3)], UI(m), UI(fmaxf(fmaf(-m, m, s2 * (1.f / 1024.f)), 0.f)), 0u, tag);
    bar_sync(2, 128);
    mbar_wait_b(BAR(B_STG), 0);
    if (tid < 96) {
      s1 = 0.f; s2 = 0.f;
      #pragma unroll 4
      for (int r = 0; r < 128; r++) {
        uint32_t v = lds32(sb + STG + (r >> 6) * 24576 + wq * 8192 + (r & 63) * 128 + ((lane * 4) ^ ((r & 7) << 4)));
        s1 += bf_lo(v); s2 += bf_hi(v);
      }
      st_ll(&P.g->csP[bp][bi][tid], UI(s1), UI(s2), 0u, tag);
      s1 = 0.f; s2 = 0.f;
      #pragma unroll 1
      for (int q = 0; q < 8; q += 2) {
        uint4 a, b; poll_ll2(&P.g->csP[bp][q][tid], &P.g->csP[bp][q + 1][tid], 0xffffffffu, tag, a, b);
        s1 += FL(a.x) + FL(b.x); s2 += FL(a.y) + FL(b.y);
      }
      const uint32_t hi = pack_bf16(-s1, -s2);
      sts32(sb + CS + (tid >> 2) * 32 + (tid & 3) * 4, hi);
      sts32(sb + CS + (tid >> 2) * 32 + (tid & 3) * 4 + 16, pack_bf16(-s1 - bf_lo(hi), -s2 - bf_hi(hi)));
    }
    fence_async_smem();
    qkv_params(P, sb, bi * 256 + tid, tag, false);
  }
  int idx;
  #pragma unroll 1
  for (int L = 0; L < 2; L++) {
    FRESH();
    {
      if ((idx >> 8) == bi && wq < 3) {
        uint4 v = poll_ll(&P.g->patch[wq * 256 + bp * 16 + (lane & 15)], 0xffffffffu, tag);
        sts64f(sb + PATCH + (wq * 16 + (lane & 15)) * 8, FL(v.x), FL(v.y));
      }
      sts32(sb + INFO, idx);
      bar_sync(2, 128);
      if (tid == 0) mbar_arrive(BAR(B_PAR));
      PROFX(tid == 0, L ? 23 : 17);
    }
    FRESH();
    mbar_wait_b(BAR(B_OFREE), L);
    #define blk (bi * 2 + (bid & 1))
    if (tid < 33) st_ll(tid < 32 ? &P.g->row[blk][bc * 32 + tid] : &P.g->best[bc][blk], 0u, 0u, 0u, 0u);
    mbar_wait_b(BAR(B_XRDY + 1), L); mbar_wait_b(BAR(B_XRDY + 3), L);
    PROFX(tid == 0, 37 + L * 16);
    FRESH();
    {
      float s1 = 0.f, s2 = 0.f, d = 0.f;
      #pragma unroll 1
      for (int q = 0; q < 8; q += 4) {
        const uint4* src = &P.g->statP[q][blk * 128 + tid];
        uint4 v0, v1, v2, v3; int it = 0;
        do { v0 = ld_ll(src); v1 = ld_ll(src + 2048); v2 = ld_ll(src + 4096); v3 = ld_ll(src + 6144); if (++it > SPIN_MAX) __trap(); }
        while (!__all_sync(0xffffffffu, v0.w == tag && v1.w == tag && v2.w == tag && v3.w == tag));
        s1 += (FL(v0.x) + FL(v1.x)) + (FL(v2.x) + FL(v3.x)); s2 += (FL(v0.y) + FL(v1.y)) + (FL(v2.y) + FL(v3.y)); d += (FL(v0.z) + FL(v1.z)) + (FL(v2.z) + FL(v3.z));
      }
      PROFX(tid == 0, 39 + L * 16);
      uint4 a = lds128(sb + INFO2), b, c;
      float m = s1 * (1.f / 1024.f), var = fmaxf(fmaf(-m, m, s2 * (1.f / 1024.f)), 0.f), rs = rsqrtf(var + LN_EPS);
      uint32_t key = UI(fmaf(-m, (FL(a.x) + FL(a.y)) + (FL(a.z) + FL(a.w)), d) * rs);
      key ^= (uint32_t)((int)key >> 31) | 0x80000000u;
      uint32_t win = __ballot_sync(0xffffffffu, key == __reduce_max_sync(0xffffffffu, key));
      if (lane == __ffs(win) - 1) sts128(sb + RED + wq * 16, make_uint4(key, UI(m), UI(rs), (tag << 11) | (uint32_t)(blk * 128 + tid)));
      if (L) sts64f(sb + PAR + tid * 8, 1.f + rs, -m * rs);
      else if ((tid >> 4) == bc) st_ll(&P.g->statF[blk * 128 + tid], UI(m), UI(var), 0u, tag + 1);
      bar_sync(2, 128);
      if (wq == 0) {
        a = best4(sb + RED);
        float2 v = lds64f(sb + (lane >> 4) * 32768 + (a.w & 255) * 128 + (((lane & 15) * 8) ^ ((a.w & 7) << 4)));
        st_ll(&P.g->row[blk][bc * 32 + lane], UI(v.x), UI(v.y), 0u, tag);
        if (lane == 0) { st_ll(&P.g->best[bc][blk], a.x, a.y, a.z, a.w); sts32(sb + INFO + 4, a.w & 2047); }
        __syncwarp();
        if (L) {
          const float al = 1.f + FL(a.z), be = -FL(a.y) * FL(a.z);
          sts64f(sb + RED + 1792 + lane * 8, FL(pack_bf16(fmaf(bf_lo(UI(v.x)), al, be), fmaf(bf_hi(UI(v.x)), al, be))),
                                             FL(pack_bf16(fmaf(bf_lo(UI(v.y)), al, be), fmaf(bf_hi(UI(v.y)), al, be))));
        }
        if (lane < 2 - L) mbar_arrive(L ? BAR(B_PAR) : BAR(B_XFREE + lane));
      }
      PROFX(tid == 0, 18 + L * 6);
      FRESH();
      a = poll_ll(&P.g->best[bc][lane & 15], 0xfffff800u, tag << 11);
      win = __ffs(__ballot_sync(0xffffffffu, a.x == __reduce_max_sync(0xffffffffu, a.x))) - 1;
      idx = __shfl_sync(0xffffffffu, a.w, win) & 2047;
      PROFX(tid == 0, 19 + L * 6);
      poll_ll2(&P.g->row[win][tid], &P.g->row[win][tid + 128], 0xffffffffu, tag, c, b);
      c.z = b.x; c.w = b.y;
      a.x = __shfl_sync(0xffffffffu, a.x, win); a.y = __shfl_sync(0xffffffffu, a.y, win); a.z = __shfl_sync(0xffffffffu, a.z, win);
      sts32(sb + INFO2 + 28, idx);
      PROFX(tid == 0, 61 + L);
      b = norm8(c, FL(a.y), FL(a.z), sb + HV + tid * 16, 2048);
      if (L && fid < 112) bar_arrive(3, 384);
      if ((tid >> 1) == (bid & 63)) {
        sts128(sb + RED + 64 + (tid & 1) * 16, bid < 64 ? make_uint4(c.x, c.y, b.x, b.y) : make_uint4(c.z, c.w, b.z, b.w));
        sts32(sb + RED + 96, a.x);
      }
      if (L && wq == 0 && win != blk) *(float2*)(P.out + (size_t)lds32(sb + INFO + 4) * 1024 + bc * 128 + lane * 4) = lds64f(sb + RED + 1792 + lane * 8);
      bar_sync(2, 128);
    }
    #pragma unroll 1
    for (int st = L; st < 3; st++) {
      FRESH();
      float a[8] = {0.f, 0.f, 0.f, 0.f, 0.f, 0.f, 0.f, 0.f};
      if (L == 0 && fid < (st == 2 ? 96 : 112)) {
        uint32_t ha = st == 1 ? sb + RED + 768 : sb + HV + ((st ? wq : wq & 1) * 64 + (lane >> 2)) * 4;
        uint32_t ph = (st ? (st == 1 ? 0x1cu : 0x11u) : 0x171u), bar = st == 1 ? BAR(B_STG + 2) : BAR(B_STG);
        uint32_t wa = sb + STG + tid * 16 + wq * 3584 + (st == 1 ? 32768 : 0);
        const uint32_t hx = st == 1 ? 256 : (st ? 1024 : 512);
        const bool lead = lane == 0;
        #pragma unroll 1
        do {
          mbar_wait(bar, ph & 1);
          PROFX(lead && threadIdx.x == 256 && st == 0 && (ph > 255 || ph < 4), 40 - 23 + __clz(ph));
          gemv8(a, wa, ha, 32);
          __syncwarp();
          if (lead) mbar_arrive(bar - 8 * (B_STG - B_STGE));
          const bool wrap = bar == BAR(B_STG + 2);
          bar += wrap ? -16 : 8; wa += wrap ? -32768 : 16384; ha += hx;
          ph >>= 1;
        } while (ph != 1);
      }
      FRESH();
      if (st == 1) {
        const uint32_t t8 = lds32(sb + INFO + 12) + L;
        if (L == 0 && fid < 112) {
          const bool odd = lane & 1;
          #pragma unroll
          for (int e = 0; e < 4; e++) { float z = __shfl_xor_sync(0xffffffffu, odd ? a[e] : a[4 + e], 1); if (odd) a[e] = z; else a[4 + e] = z; }
          uint4* dst = &P.g->yP[tid & ~1][fid][tid & 1];
          st_ll(dst, UI(a[0]), UI(a[1]), UI(a[2]), (UI(a[3]) & ~255u) | t8);
          st_ll(dst + 224, UI(a[4]), UI(a[5]), UI(a[6]), (UI(a[7]) & ~255u) | t8);
          PROFX(tid == 0, 21);
        }
        if (!L) qkv_params(P, sb, bi * 256 + tid, tag + 1, true);
        if (tid == 0) { uint32_t k = lds32(sb + RED + 96); sts32f(sb + RED + 100, bf_round(__fdividef(1.f, 1.f + __expf(-bf_round(FL(k ^ (~(uint32_t)((int)k >> 31) | 0x80000000u))))))); }
        uint4 v0, v1;
        poll_ll2(&P.g->yP[bid][0][min(tid, 111)], &P.g->yP[bid][0][min(tid, 111) + 112], 255u, t8, v0, v1);
        const float lo = (tid < 112 && !(tid & 1)) ? 1.f : 0.f, hi = (tid < 112 && (tid & 1)) ? 1.f : 0.f;
        const float y0 = FL(v0.x) + FL(v1.x), y1 = FL(v0.y) + FL(v1.y), y2 = FL(v0.z) + FL(v1.z), y3 = FL((v0.w & ~255u) | 128u) + FL((v1.w & ~255u) | 128u);
        a[0] = y0 * lo; a[1] = y1 * lo; a[2] = y2 * lo; a[3] = y3 * lo; a[4] = y0 * hi; a[5] = y1 * hi; a[6] = y2 * hi; a[7] = y3 * hi;
      }
      sts32f(sb + RED + 256 + wq * 128 + ((lane & 3) * 8 + (lane >> 2)) * 4, fold8(a));
      bar_sync(2, 128);
      const uint32_t d = sb + RED + 256 + lane * 4;
      float z0 = lds32f(d) + lds32f(d + 128), z1 = lds32f(d + 256) + lds32f(d + 384);
      if (st == 0) {
        sts32f(sb + RED + 768 + lane * 32 + wq * 4, swiglu(z0, z1));
        if (fid < 112) { st_ll(&P.g->yP[tid & ~1][fid][tid & 1], 0u, 0u, 0u, 0u); st_ll(&P.g->yP[tid | 1][fid][tid & 1], 0u, 0u, 0u, 0u); }
        if (tid < 24) st_ll(tid < 16 ? &P.g->x2[tid >> 1][2 * bid + (tid & 1)] : &P.g->patch[fid * 8 + tid - 16], 0u, 0u, 0u, 0u);
        bar_sync(2, 128); PROFX(tid == 0, 20); continue; }
      z0 += z1;
      if (st == 1) {
        z0 += __shfl_xor_sync(0xffffffffu, z0, 8); z0 += __shfl_xor_sync(0xffffffffu, z0, 16);
        uint32_t xw = lds32(sb + RED + 64 + (lane & 4) * 4 + (lane & 2) * 2), hw = lds32(sb + RED + 72 + (lane & 4) * 4 + (lane & 2) * 2);
        z0 = bf_round(((lane & 1) ? bf_hi(hw) : bf_lo(hw)) + bf_round(bf_round(z0) * lds32f(sb + RED + 100))) + ((lane & 1) ? bf_hi(xw) : bf_lo(xw));
      } else if (fid < 32) z0 *= QSCALE;
      uint32_t v = pack_bf16(z0, __shfl_down_sync(0xffffffffu, z0, 1)), v2 = __shfl_down_sync(0xffffffffu, v, 2);
      if (L) { if (tid == 0 || tid == 4) *(uint2*)(P.out + (size_t)idx * 1024 + bid * 8 + tid) = make_uint2(v, v2); PROFW(tid == 0, 28); break; }
      if ((tid & 3) == 0 && tid < (st == 1 ? 64 : 32)) st_ll(st == 1 ? &P.g->x2[tid >> 3][2 * bid + ((tid >> 2) & 1)] : &P.g->patch[fid * 8 + (tid >> 2)], v, v2, 0u, tag + 1);
      PROFX(tid == 0, st == 1 ? 22 : 31);
      if (st == 1) {
        uint4 x, y; poll_ll2(&P.g->x2[bi][tid], &P.g->x2[bi][tid + 128], 0xffffffffu, tag + 1, x, y);
        x.z = y.x; x.w = y.y;
        if (wq == (bc & 3)) sts64f(sb + X2SEG + lane * 8, FL(bc < 4 ? x.x : x.z), FL(bc < 4 ? x.y : x.w));
        float s1 = 0.f, s2 = 0.f;
        sum8(x, s1, s2);
        #pragma unroll
        for (int o = 16; o; o >>= 1) { s1 += __shfl_xor_sync(0xffffffffu, s1, o); s2 += __shfl_xor_sync(0xffffffffu, s2, o); }
        sts64f(sb + RED + wq * 8, s1, s2);
        bar_sync(2, 128);
        y = lds128(sb + RED); uint4 y2 = lds128(sb + RED + 16);
        float m = ((FL(y.x) + FL(y.z)) + (FL(y2.x) + FL(y2.z))) * (1.f / 1024.f);
        norm8(x, m, rsqrtf(fmaxf(fmaf(-m, m, ((FL(y.y) + FL(y.w)) + (FL(y2.y) + FL(y2.w))) * (1.f / 1024.f)), 0.f) + LN_EPS), sb + HV + tid * 16, 2048);
        bar_sync(2, 128);
        PROFX(tid == 0, 30);
      }
    }
  }
  if (bid == 0 && tid == 0) P.g->epoch = lds32(sb + INFO2 + 16) + 1;
  #undef blk
  #undef bid
  #undef fid
  #undef bi
  #undef bp
  #undef bc
  #undef FRESH
  #undef lane
  #undef wq
}

__global__ void __cluster_dims__(2, 1, 1) __launch_bounds__(512, 1) fused_kernel(const __grid_constant__ Params P) {
  extern __shared__ __align__(1024) uint8_t smem_raw[];
  const uint32_t sb = smem_u32(smem_raw);
  PROFT(threadIdx.x == 0, 0);
  if (threadIdx.x == 0) {
    for (int s = 0; s < 3; s++) mbar_init(BAR(B_FULLQ + s), 1);
    asm volatile("fence.mbarrier_init.release.cluster;" ::: "memory");
    #pragma unroll 1
    for (int s = 0; s < 3; s++) {
      mbar_expect_tx(BAR(B_FULLQ + s), 57344);
      tma_2d(sb + qa_off(s), &P.mX, s * 64, (BID >> 4) * 256, BAR(B_FULLQ + s));
      tma_3d(sb + qb_off(s), &P.mWq, (BID & 15) * 64, s * 64, 0, BAR(B_FULLQ + s));
    }
    if ((sb & 0x3FFFFu) != 1024) __trap();
  } else if (threadIdx.x >= 32 + B_EMPTYQ && threadIdx.x <= 32 + B_COUNT) {
    const int b = threadIdx.x == 32 + B_COUNT ? B_ROW : threadIdx.x - 32;
    const uint32_t cnt = b < B_XFREE ? (b == B_OFREE ? 1 : 2) : (b < B_KVRDY ? 3 : (b < B_KVFULL || b == B_ROW ? 4 : (b == B_PFREE ? 2 : 1)));
    mbar_init(BAR(b), cnt);
    asm volatile("fence.mbarrier_init.release.cluster;" ::: "memory");
  }
  __syncthreads();
  asm volatile("barrier.cluster.arrive.relaxed.aligned;" ::: "memory");
  const int wg = __shfl_sync(0xffffffffu, threadIdx.x >> 7, 0);
  if (wg < 2) { reg_inc<224>(); consumer(P, sb, wg); }
  else if (wg == 2) { reg_dec<40>(); aux(P, sb); }
  else {
    reg_dec<24>();
    asm volatile("barrier.cluster.wait.aligned;" ::: "memory");
    const int w = __shfl_sync(0xffffffffu, (threadIdx.x >> 5) & 3, 0);
    if (w == 0) loader(P, sb);
    else if (w < 3) storer(P, sb, w - 1);
    else if ((threadIdx.x & 31) == 0) stager(P, sb);
  }
}

typedef CUresult (*EncFn)(CUtensorMap*, CUtensorMapDataType, cuuint32_t, void*, const cuuint64_t*, const cuuint64_t*, const cuuint32_t*, const cuuint32_t*,
                          CUtensorMapInterleave, CUtensorMapSwizzle, CUtensorMapL2promotion, CUtensorMapFloatOOBfill);
static void mk_map(EncFn enc, CUtensorMap* m, const void* ptr, int rank, const cuuint64_t* dims, const cuuint64_t* strides, const cuuint32_t* box,
                   CUtensorMapSwizzle sw, CUtensorMapL2promotion pr) {
  cuuint32_t es[5] = {1, 1, 1, 1, 1};
  enc(m, CU_TENSOR_MAP_DATA_TYPE_BFLOAT16, rank, (void*)ptr, dims, strides, box, es, CU_TENSOR_MAP_INTERLEAVE_NONE, sw, pr, CU_TENSOR_MAP_FLOAT_OOB_FILL_NONE);
}
extern "C" void kernel_launch(void* const* d_in, const int* in_sizes, int n_in, void* d_out, int out_size) {
  (void)in_sizes; (void)n_in; (void)out_size;
  void* fn = nullptr; cudaDriverEntryPointQueryResult q;
  cudaGetDriverEntryPoint("cuTensorMapEncodeTiled", &fn, cudaEnableDefault, &q);
  EncFn enc = (EncFn)fn;
  cudaFuncSetAttribute(fused_kernel, cudaFuncAttributeMaxDynamicSharedMemorySize, SMEM_BYTES);
  Params P;
  const CUtensorMapSwizzle S128 = CU_TENSOR_MAP_SWIZZLE_128B, S0 = CU_TENSOR_MAP_SWIZZLE_NONE;
  const CUtensorMapL2promotion L256 = CU_TENSOR_MAP_L2_PROMOTION_L2_256B, L128 = CU_TENSOR_MAP_L2_PROMOTION_L2_128B;
  { cuuint64_t d[2] = {1024, 2048}, s[1] = {2048}; cuuint32_t b[2] = {64, 256}, bh[2] = {64, 128};
    mk_map(enc, &P.mX, d_in[0], 2, d, s, b, S128, L256); mk_map(enc, &P.mXh, d_in[0], 2, d, s, bh, S128, L256); }
  { cuuint64_t d[3] = {1024, 1024, 3}, s[2] = {6144, 2048}; cuuint32_t b[3] = {64, 64, 3}; mk_map(enc, &P.mWq, d_in[1], 3, d, s, b, S128, L256); }
  { cuuint64_t d[5] = {64, 32, 2, 16, 16}, s[4] = {2048, 65536, 131072, 128}; cuuint32_t b[5] = {64, 32, 1, 2, 2}; mk_map(enc, &P.mWo, d_in[2], 5, d, s, b, S128, L256); }
  { cuuint64_t d[2] = {3584, 1024}, s[1] = {7168}; cuuint32_t b[2] = {32, 128};
    mk_map(enc, &P.mWg, d_in[5], 2, d, s, b, S0, L128); mk_map(enc, &P.mWu, d_in[6], 2, d, s, b, S0, L128); }
  { cuuint64_t d[2] = {3072, 1024}, s[1] = {6144}; cuuint32_t b[2] = {32, 256}; mk_map(enc, &P.mWp, d_in[1], 2, d, s, b, S0, L128); }
  { cuuint64_t d[3] = {256, 3584, 4}, s[2] = {2048, 512}; cuuint32_t b[3] = {256, 8, 4}; mk_map(enc, &P.mWd, d_in[7], 3, d, s, b, S0, L128); }
  P.x0 = (const bf16*)d_in[0]; P.wqkv = (const bf16*)d_in[1]; P.wo = (const bf16*)d_in[2]; P.wr = (const bf16*)d_in[4]; P.wg = (const bf16*)d_in[5]; P.wu = (const bf16*)d_in[6]; P.wd = (const bf16*)d_in[7];
  P.out = (bf16*)d_out;
  cudaGetSymbolAddress((void**)&P.g, g_scr);
  for (int b = 0; b < 128; b++) {
    int j = b >> 1, quad = j < 4 ? 0 : (j < 36 ? 1 + (j - 4) % 8 : 9 + (j - 36) % 7), pos = j < 4 ? j : (j < 36 ? (j - 4) / 8 : (j - 36) / 7);
    int bid = ((quad >> 2) * 2 + (pos >> 1)) * 16 + ((quad & 3) * 2 + (pos & 1)) * 2 + (b & 1);
    int e = pos * 2 + (b & 1), fid = e < 6 ? quad * 6 + e : e * 16 + quad;
    P.map[b] = bid | fid << 8;
  }
  fused_kernel<<<128, 512, SMEM_BYTES>>>(P);
}
```

```cpp
#include <cuda_runtime.h>
#include <cuda_bf16.h>
#include <cuda.h>
#include <stdint.h>
#include <stddef.h>
typedef __nv_bfloat16 bf16;

template<int TB, int TA = 0> __device__ __forceinline__ void wgmma_ss_n192(float (&d)[96], uint64_t da, uint64_t db, int scale_d) {
  asm volatile("{\n.reg .pred p;\nsetp.ne.b32 p, %98, 0;\n"
    "wgmma.mma_async.sync.aligned.m64n192k16.f32.bf16.bf16 {%0, %1, %2, %3, %4, %5, %6, %7, %8, %9, %10, %11, %12, %13, %14, %15, %16, %17, %18, %19, %20, %21, %22, %23, %24, %25, %26, %27, %28, %29, %30, %31, %32, %33, %34, %35, %36, %37, %38, %39, %40, %41, %42, %43, %44, %45, %46, %47, %48, %49, %50, %51, %52, %53, %54, %55, %56, %57, %58, %59, %60, %61, %62, %63, %64, %65, %66, %67, %68, %69, %70, %71, %72, %73, %74, %75, %76, %77, %78, %79, %80, %81, %82, %83, %84, %85, %86, %87, %88, %89, %90, %91, %92, %93, %94, %95}, %96, %97, p, 1, 1, %100, %99;\n}\n"
    : "+f"(d[0]), "+f"(d[1]), "+f"(d[2]), "+f"(d[3]), "+f"(d[4]), "+f"(d[5]), "+f"(d[6]), "+f"(d[7]), "+f"(d[8]), "+f"(d[9]), "+f"(d[10]), "+f"(d[11]), "+f"(d[12]), "+f"(d[13]), "+f"(d[14]), "+f"(d[15]), "+f"(d[16]), "+f"(d[17]), "+f"(d[18]), "+f"(d[19]), "+f"(d[20]), "+f"(d[21]), "+f"(d[22]), "+f"(d[23]), "+f"(d[24]), "+f"(d[25]), "+f"(d[26]), "+f"(d[27]), "+f"(d[28]), "+f"(d[29]), "+f"(d[30]), "+f"(d[31]), "+f"(d[32]), "+f"(d[33]), "+f"(d[34]), "+f"(d[35]), "+f"(d[36]), "+f"(d[37]), "+f"(d[38]), "+f"(d[39]), "+f"(d[40]), "+f"(d[41]), "+f"(d[42]), "+f"(d[43]), "+f"(d[44]), "+f"(d[45]), "+f"(d[46]), "+f"(d[47]), "+f"(d[48]), "+f"(d[49]), "+f"(d[50]), "+f"(d[51]), "+f"(d[52]), "+f"(d[53]), "+f"(d[54]), "+f"(d[55]), "+f"(d[56]), "+f"(d[57]), "+f"(d[58]), "+f"(d[59]), "+f"(d[60]), "+f"(d[61]), "+f"(d[62]), "+f"(d[63]), "+f"(d[64]), "+f"(d[65]), "+f"(d[66]), "+f"(d[67]), "+f"(d[68]), "+f"(d[69]), "+f"(d[70]), "+f"(d[71]), "+f"(d[72]), "+f"(d[73]), "+f"(d[74]), "+f"(d[75]), "+f"(d[76]), "+f"(d[77]), "+f"(d[78]), "+f"(d[79]), "+f"(d[80]), "+f"(d[81]), "+f"(d[82]), "+f"(d[83]), "+f"(d[84]), "+f"(d[85]), "+f"(d[86]), "+f"(d[87]), "+f"(d[88]), "+f"(d[89]), "+f"(d[90]), "+f"(d[91]), "+f"(d[92]), "+f"(d[93]), "+f"(d[94]), "+f"(d[95])
    : "l"(da), "l"(db), "r"(scale_d), "n"(TB), "n"(TA));
}

template<int TB> __device__ __forceinline__ void wgmma_rs_n192(float (&d)[96], uint32_t a0, uint32_t a1, uint32_t a2, uint32_t a3, uint64_t db, int scale_d) {
  asm volatile("{\n.reg .pred p;\nsetp.ne.b32 p, %101, 0;\n"
    "wgmma.mma_async.sync.aligned.m64n192k16.f32.bf16.bf16 {%0, %1, %2, %3, %4, %5, %6, %7, %8, %9, %10, %11, %12, %13, %14, %15, %16, %17, %18, %19, %20, %21, %22, %23, %24, %25, %26, %27, %28, %29, %30, %31, %32, %33, %34, %35, %36, %37, %38, %39, %40, %41, %42, %43, %44, %45, %46, %47, %48, %49, %50, %51, %52, %53, %54, %55, %56, %57, %58, %59, %60, %61, %62, %63, %64, %65, %66, %67, %68, %69, %70, %71, %72, %73, %74, %75, %76, %77, %78, %79, %80, %81, %82, %83, %84, %85, %86, %87, %88, %89, %90, %91, %92, %93, %94, %95}, {%96, %97, %98, %99}, %100, p, 1, 1, %102;\n}\n"
    : "+f"(d[0]), "+f"(d[1]), "+f"(d[2]), "+f"(d[3]), "+f"(d[4]), "+f"(d[5]), "+f"(d[6]), "+f"(d[7]), "+f"(d[8]), "+f"(d[9]), "+f"(d[10]), "+f"(d[11]), "+f"(d[12]), "+f"(d[13]), "+f"(d[14]), "+f"(d[15]), "+f"(d[16]), "+f"(d[17]), "+f"(d[18]), "+f"(d[19]), "+f"(d[20]), "+f"(d[21]), "+f"(d[22]), "+f"(d[23]), "+f"(d[24]), "+f"(d[25]), "+f"(d[26]), "+f"(d[27]), "+f"(d[28]), "+f"(d[29]), "+f"(d[30]), "+f"(d[31]), "+f"(d[32]), "+f"(d[33]), "+f"(d[34]), "+f"(d[35]), "+f"(d[36]), "+f"(d[37]), "+f"(d[38]), "+f"(d[39]), "+f"(d[40]), "+f"(d[41]), "+f"(d[42]), "+f"(d[43]), "+f"(d[44]), "+f"(d[45]), "+f"(d[46]), "+f"(d[47]), "+f"(d[48]), "+f"(d[49]), "+f"(d[50]), "+f"(d[51]), "+f"(d[52]), "+f"(d[53]), "+f"(d[54]), "+f"(d[55]), "+f"(d[56]), "+f"(d[57]), "+f"(d[58]), "+f"(d[59]), "+f"(d[60]), "+f"(d[61]), "+f"(d[62]), "+f"(d[63]), "+f"(d[64]), "+f"(d[65]), "+f"(d[66]), "+f"(d[67]), "+f"(d[68]), "+f"(d[69]), "+f"(d[70]), "+f"(d[71]), "+f"(d[72]), "+f"(d[73]), "+f"(d[74]), "+f"(d[75]), "+f"(d[76]), "+f"(d[77]), "+f"(d[78]), "+f"(d[79]), "+f"(d[80]), "+f"(d[81]), "+f"(d[82]), "+f"(d[83]), "+f"(d[84]), "+f"(d[85]), "+f"(d[86]), "+f"(d[87]), "+f"(d[88]), "+f"(d[89]), "+f"(d[90]), "+f"(d[91]), "+f"(d[92]), "+f"(d[93]), "+f"(d[94]), "+f"(d[95])
    : "r"(a0), "r"(a1), "r"(a2), "r"(a3), "l"(db), "r"(scale_d), "n"(TB));
}

template<int TB, int TA = 0> __device__ __forceinline__ void wgmma_ss_n128(float (&d)[64], uint64_t da, uint64_t db, int scale_d) {
  asm volatile("{\n.reg .pred p;\nsetp.ne.b32 p, %66, 0;\n"
    "wgmma.mma_async.sync.aligned.m64n128k16.f32.bf16.bf16 {%0, %1, %2, %3, %4, %5, %6, %7, %8, %9, %10, %11, %12, %13, %14, %15, %16, %17, %18, %19, %20, %21, %22, %23, %24, %25, %26, %27, %28, %29, %30, %31, %32, %33, %34, %35, %36, %37, %38, %39, %40, %41, %42, %43, %44, %45, %46, %47, %48, %49, %50, %51, %52, %53, %54, %55, %56, %57, %58, %59, %60, %61, %62, %63}, %64, %65, p, 1, 1, %68, %67;\n}\n"
    : "+f"(d[0]), "+f"(d[1]), "+f"(d[2]), "+f"(d[3]), "+f"(d[4]), "+f"(d[5]), "+f"(d[6]), "+f"(d[7]), "+f"(d[8]), "+f"(d[9]), "+f"(d[10]), "+f"(d[11]), "+f"(d[12]), "+f"(d[13]), "+f"(d[14]), "+f"(d[15]), "+f"(d[16]), "+f"(d[17]), "+f"(d[18]), "+f"(d[19]), "+f"(d[20]), "+f"(d[21]), "+f"(d[22]), "+f"(d[23]), "+f"(d[24]), "+f"(d[25]), "+f"(d[26]), "+f"(d[27]), "+f"(d[28]), "+f"(d[29]), "+f"(d[30]), "+f"(d[31]), "+f"(d[32]), "+f"(d[33]), "+f"(d[34]), "+f"(d[35]), "+f"(d[36]), "+f"(d[37]), "+f"(d[38]), "+f"(d[39]), "+f"(d[40]), "+f"(d[41]), "+f"(d[42]), "+f"(d[43]), "+f"(d[44]), "+f"(d[45]), "+f"(d[46]), "+f"(d[47]), "+f"(d[48]), "+f"(d[49]), "+f"(d[50]), "+f"(d[51]), "+f"(d[52]), "+f"(d[53]), "+f"(d[54]), "+f"(d[55]), "+f"(d[56]), "+f"(d[57]), "+f"(d[58]), "+f"(d[59]), "+f"(d[60]), "+f"(d[61]), "+f"(d[62]), "+f"(d[63])
    : "l"(da), "l"(db), "r"(scale_d), "n"(TB), "n"(TA));
}

template<int TB, int TA = 0> __device__ __forceinline__ void wgmma_ss_n64(float (&d)[32], uint64_t da, uint64_t db, int scale_d) {
  asm volatile("{\n.reg .pred p;\nsetp.ne.b32 p, %34, 0;\n"
    "wgmma.mma_async.sync.aligned.m64n64k16.f32.bf16.bf16 {%0, %1, %2, %3, %4, %5, %6, %7, %8, %9, %10, %11, %12, %13, %14, %15, %16, %17, %18, %19, %20, %21, %22, %23, %24, %25, %26, %27, %28, %29, %30, %31}, %32, %33, p, 1, 1, %36, %35;\n}\n"
    : "+f"(d[0]), "+f"(d[1]), "+f"(d[2]), "+f"(d[3]), "+f"(d[4]), "+f"(d[5]), "+f"(d[6]), "+f"(d[7]), "+f"(d[8]), "+f"(d[9]), "+f"(d[10]), "+f"(d[11]), "+f"(d[12]), "+f"(d[13]), "+f"(d[14]), "+f"(d[15]), "+f"(d[16]), "+f"(d[17]), "+f"(d[18]), "+f"(d[19]), "+f"(d[20]), "+f"(d[21]), "+f"(d[22]), "+f"(d[23]), "+f"(d[24]), "+f"(d[25]), "+f"(d[26]), "+f"(d[27]), "+f"(d[28]), "+f"(d[29]), "+f"(d[30]), "+f"(d[31])
    : "l"(da), "l"(db), "r"(scale_d), "n"(TB), "n"(TA));
}

template<int TB> __device__ __forceinline__ void wgmma_rs_n40(float (&d)[20], uint32_t a0, uint32_t a1, uint32_t a2, uint32_t a3, uint64_t db, int scale_d) {
  asm volatile("{\n.reg .pred p;\nsetp.ne.b32 p, %25, 0;\n"
    "wgmma.mma_async.sync.aligned.m64n40k16.f32.bf16.bf16 {%0, %1, %2, %3, %4, %5, %6, %7, %8, %9, %10, %11, %12, %13, %14, %15, %16, %17, %18, %19}, {%20, %21, %22, %23}, %24, p, 1, 1, %26;\n}\n"
    : "+f"(d[0]), "+f"(d[1]), "+f"(d[2]), "+f"(d[3]), "+f"(d[4]), "+f"(d[5]), "+f"(d[6]), "+f"(d[7]), "+f"(d[8]), "+f"(d[9]), "+f"(d[10]), "+f"(d[11]), "+f"(d[12]), "+f"(d[13]), "+f"(d[14]), "+f"(d[15]), "+f"(d[16]), "+f"(d[17]), "+f"(d[18]), "+f"(d[19])
    : "r"(a0), "r"(a1), "r"(a2), "r"(a3), "l"(db), "r"(scale_d), "n"(TB));
}

#define DEVI __device__ __forceinline__
DEVI uint32_t smem_u32(const void* p) { return (uint32_t)__cvta_generic_to_shared(p); }
DEVI void mbar_init(uint32_t bar, uint32_t cnt) { asm volatile("mbarrier.init.shared::cta.b64 [%0], %1;" :: "r"(bar), "r"(cnt)); }
DEVI void mbar_expect_tx(uint32_t bar, uint32_t bytes) { asm volatile("mbarrier.arrive.expect_tx.shared::cta.b64 _, [%0], %1;" :: "r"(bar), "r"(bytes) : "memory"); }
DEVI void mbar_arrive(uint32_t bar) { asm volatile("mbarrier.arrive.shared::cta.b64 _, [%0];" :: "r"(bar) : "memory"); }
DEVI void mbar_arrive_peer(uint32_t bar) {
  asm volatile("{\n.reg .b32 ra;\nmapa.shared::cluster.u32 ra, %0, %1;\nmbarrier.arrive.shared::cluster.b64 _, [ra];\n}" :: "r"(bar), "r"((blockIdx.x & 1) ^ 1) : "memory");
}
DEVI void bulk_s2peer(uint32_t a, uint32_t bytes, uint32_t bar) {
  asm volatile("{\n.reg .b32 ra, rb;\nmapa.shared::cluster.u32 ra, %0, %3;\nmapa.shared::cluster.u32 rb, %2, %3;\n"
               "cp.async.bulk.shared::cluster.shared::cta.mbarrier::complete_tx::bytes [ra], [%0], %1, [rb];\n}"
               :: "r"(a), "r"(bytes), "r"(bar), "r"((blockIdx.x & 1) ^ 1) : "memory");
}
DEVI void mbar_wait(uint32_t bar, uint32_t parity) {
  asm volatile("{\n.reg .pred p;\nLW:\nmbarrier.try_wait.parity.shared::cta.b64 p, [%0], %1;\n@!p bra LW;\n}" :: "r"(bar), "r"(parity) : "memory");
}
DEVI uint32_t mbar_test(uint32_t bar, uint32_t parity) {
  uint32_t r; asm volatile("{\n.reg .pred p;\nmbarrier.test_wait.parity.shared::cta.b64 p, [%1], %2;\nselp.u32 %0, 1, 0, p;\n}" : "=r"(r) : "r"(bar), "r"(parity) : "memory"); return r;
}
DEVI void mbar_wait_b(uint32_t bar, uint32_t parity) {
  asm volatile("{\n.reg .pred p;\n.reg .u32 it;\nmov.u32 it, 0;\nLW:\nmbarrier.try_wait.parity.shared::cta.b64 p, [%0], %1;\n@p bra LD;\n"
               "add.u32 it, it, 1;\nsetp.lt.u32 p, it, 0x1000000;\n@p bra LW;\ntrap;\nLD:\n}" :: "r"(bar), "r"(parity) : "memory");
}
DEVI void tma_2d(uint32_t dst, const CUtensorMap* m, int c0, int c1, uint32_t bar) {
  asm volatile("cp.async.bulk.tensor.2d.shared::cluster.global.mbarrier::complete_tx::bytes [%0], [%1, {%3, %4}], [%2];"
    :: "r"(dst), "l"(m), "r"(bar), "r"(c0), "r"(c1) : "memory");
}
DEVI void tma_3d(uint32_t dst, const CUtensorMap* m, int c0, int c1, int c2, uint32_t bar) {
  asm volatile("cp.async.bulk.tensor.3d.shared::cluster.global.mbarrier::complete_tx::bytes [%0], [%1, {%3, %4, %5}], [%2];"
    :: "r"(dst), "l"(m), "r"(bar), "r"(c0), "r"(c1), "r"(c2) : "memory");
}
#define POL_EF POL_FIRST
constexpr uint64_t POL_FIRST = 0x12F0000000000000ull, POL_NORMAL = 0x1000000000000000ull;
DEVI void tma_2d_h(uint32_t dst, const CUtensorMap* m, int c0, int c1, uint32_t bar, uint64_t pol) {
  asm volatile("cp.async.bulk.tensor.2d.shared::cluster.global.mbarrier::complete_tx::bytes.L2::cache_hint [%0], [%1, {%3, %4}], [%2], %5;"
    :: "r"(dst), "l"(m), "r"(bar), "r"(c0), "r"(c1), "l"(pol) : "memory");
}
DEVI void tma_3d_h(uint32_t dst, const CUtensorMap* m, int c0, int c1, int c2, uint32_t bar, uint64_t pol) {
  asm volatile("cp.async.bulk.tensor.3d.shared::cluster.global.mbarrier::complete_tx::bytes.L2::cache_hint [%0], [%1, {%3, %4, %5}], [%2], %6;"
    :: "r"(dst), "l"(m), "r"(bar), "r"(c0), "r"(c1), "r"(c2), "l"(pol) : "memory");
}
DEVI void bulk_g2s_h(uint32_t s, const void* g, uint32_t bytes, uint32_t bar, uint64_t pol = POL_EF) {
  asm volatile("cp.async.bulk.shared::cluster.global.mbarrier::complete_tx::bytes.L2::cache_hint [%0], [%1], %2, [%3], %4;"
    :: "r"(s), "l"(g), "r"(bytes), "r"(bar), "l"(pol) : "memory");
}
DEVI void tma_5d(uint32_t dst, const CUtensorMap* m, int c0, int c1, int c2, int c3, int c4, uint32_t bar, uint64_t pol) {
  asm volatile("cp.async.bulk.tensor.5d.shared::cluster.global.mbarrier::complete_tx::bytes.L2::cache_hint [%0], [%1, {%3, %4, %5, %6, %7}], [%2], %8;"
    :: "r"(dst), "l"(m), "r"(bar), "r"(c0), "r"(c1), "r"(c2), "r"(c3), "r"(c4), "l"(pol) : "memory");
}
DEVI void tma_prefetch_2d(const CUtensorMap* m, int c0, int c1) {
  asm volatile("cp.async.bulk.prefetch.tensor.2d.L2.global.tile [%0, {%1, %2}];" :: "l"(m), "r"(c0), "r"(c1) : "memory");
}
DEVI void tma_prefetch_3d(const CUtensorMap* m, int c0, int c1, int c2) {
  asm volatile("cp.async.bulk.prefetch.tensor.3d.L2.global.tile [%0, {%1, %2, %3}];" :: "l"(m), "r"(c0), "r"(c1), "r"(c2) : "memory");
}
DEVI void bulk_prefetch(const void* g, uint32_t bytes) { asm volatile("cp.async.bulk.prefetch.L2.global [%0], %1;" :: "l"(g), "r"(bytes) : "memory"); }
DEVI void bulk_g2s(uint32_t s, const void* g, uint32_t bytes, uint32_t bar) {
  asm volatile("cp.async.bulk.shared::cluster.global.mbarrier::complete_tx::bytes [%0], [%1], %2, [%3];" :: "r"(s), "l"(g), "r"(bytes), "r"(bar) : "memory");
}
DEVI void bulk_s2g(void* g, uint32_t s, uint32_t bytes) {
  asm volatile("cp.async.bulk.global.shared::cta.bulk_group [%0], [%1], %2;\ncp.async.bulk.commit_group;" :: "l"(g), "r"(s), "r"(bytes) : "memory");
}
template<int N> DEVI void bulk_wait() { asm volatile("cp.async.bulk.wait_group %0;" :: "n"(N) : "memory"); }
DEVI void fence_async_smem() { asm volatile("fence.proxy.async.shared::cta;" ::: "memory"); }
DEVI void fence_async_glob() { asm volatile("fence.proxy.async.global;" ::: "memory"); }
DEVI unsigned ld_rlx(const unsigned* p) { unsigned v; asm volatile("ld.relaxed.gpu.global.u32 %0, [%1];" : "=r"(v) : "l"(p) : "memory"); return v; }
DEVI void st_rlx(unsigned* p, unsigned v) { asm volatile("st.relaxed.gpu.global.u32 [%0], %1;" :: "l"(p), "r"(v) : "memory"); }
DEVI uint2 ldg_stream(const uint2* p) { uint2 v; asm volatile("ld.global.nc.L1::no_allocate.v2.u32 {%0, %1}, [%2];" : "=r"(v.x), "=r"(v.y) : "l"(p)); return v; }
DEVI void fence_rel() { asm volatile("fence.release.gpu;" ::: "memory"); }
DEVI uint4 ld_ll(const uint4* p) {
  uint4 v;
  asm volatile("{\n.reg .b128 t;\n.reg .b64 a, b;\nld.relaxed.gpu.global.b128 t, [%4];\nmov.b128 {a, b}, t;\nmov.b64 {%0, %1}, a;\nmov.b64 {%2, %3}, b;\n}"
               : "=r"(v.x), "=r"(v.y), "=r"(v.z), "=r"(v.w) : "l"(p) : "memory");
  return v;
}
DEVI void st_ll(uint4* p, uint32_t x, uint32_t y, uint32_t z, uint32_t w) {
  asm volatile("{\n.reg .b128 t;\n.reg .b64 a, b;\nmov.b64 a, {%1, %2};\nmov.b64 b, {%3, %4};\nmov.b128 t, {a, b};\nst.relaxed.gpu.global.b128 [%0], t;\n}"
               :: "l"(p), "r"(x), "r"(y), "r"(z), "r"(w) : "memory");
}
#define SPIN_MAX 0x1000000
DEVI uint4 poll_ll(const uint4* p, uint32_t mask, uint32_t tag) {
  uint4 v; int it = 0;
  do { v = ld_ll(p); if (++it > SPIN_MAX) __trap(); } while (!__all_sync(0xffffffffu, (v.w & mask) == tag));
  return v;
}
DEVI void poll_ll2(const uint4* p, const uint4* q, uint32_t mask, uint32_t tag, uint4& a, uint4& b) {
  int it = 0;
  do { a = ld_ll(p); b = ld_ll(q); if (++it > SPIN_MAX) __trap(); } while (!__all_sync(0xffffffffu, (a.w & mask) == tag && (b.w & mask) == tag));
}
DEVI void bar_sync(int id, int n) { asm volatile("bar.sync %0, %1;" :: "r"(id), "r"(n) : "memory"); }
DEVI void bar_arrive(int id, int n) { asm volatile("bar.arrive %0, %1;" :: "r"(id), "r"(n) : "memory"); }
DEVI void wg_fence() { asm volatile("wgmma.fence.sync.aligned;" ::: "memory"); }
DEVI void wg_commit() { asm volatile("wgmma.commit_group.sync.aligned;" ::: "memory"); }
template<int N> DEVI void wg_wait() { asm volatile("wgmma.wait_group.sync.aligned %0;" :: "n"(N) : "memory"); }
template<int N> DEVI void reg_inc() { asm volatile("setmaxnreg.inc.sync.aligned.u32 %0;" :: "n"(N)); }
template<int N> DEVI void reg_dec() { asm volatile("setmaxnreg.dec.sync.aligned.u32 %0;" :: "n"(N)); }
DEVI float ex2f(float x) { float y; asm("ex2.approx.ftz.f32 %0, %1;" : "=f"(y) : "f"(x)); return y; }
DEVI uint32_t pack_bf16(float lo, float hi) { uint32_t r; asm("cvt.rn.bf16x2.f32 %0, %1, %2;" : "=r"(r) : "f"(hi), "f"(lo)); return r; }
DEVI float bf_lo(uint32_t v) { return __uint_as_float(v << 16); }
DEVI float bf_hi(uint32_t v) { return __uint_as_float(v & 0xffff0000u); }
DEVI float bf_round(float x) { return bf_lo(pack_bf16(x, 0.f)); }
DEVI void stsm_x4(uint32_t addr, uint32_t a, uint32_t b, uint32_t c, uint32_t d) {
  asm volatile("stmatrix.sync.aligned.m8n8.x4.shared.b16 [%0], {%1,%2,%3,%4};" :: "r"(addr), "r"(a), "r"(b), "r"(c), "r"(d) : "memory");
}
DEVI void ldsm_x4(uint32_t addr, uint32_t& a, uint32_t& b, uint32_t& c, uint32_t& d) {
  asm volatile("ldmatrix.sync.aligned.m8n8.x4.shared.b16 {%0,%1,%2,%3}, [%4];" : "=r"(a), "=r"(b), "=r"(c), "=r"(d) : "r"(addr) : "memory");
}
DEVI uint4 lds128(uint32_t a) { uint4 v; asm volatile("ld.shared.v4.u32 {%0,%1,%2,%3}, [%4];" : "=r"(v.x), "=r"(v.y), "=r"(v.z), "=r"(v.w) : "r"(a) : "memory"); return v; }
DEVI void sts128(uint32_t a, uint4 v) { asm volatile("st.shared.v4.u32 [%0], {%1,%2,%3,%4};" :: "r"(a), "r"(v.x), "r"(v.y), "r"(v.z), "r"(v.w) : "memory"); }
DEVI float2 lds64f(uint32_t a) { float2 v; asm volatile("ld.shared.v2.f32 {%0,%1}, [%2];" : "=f"(v.x), "=f"(v.y) : "r"(a) : "memory"); return v; }
DEVI void sts64f(uint32_t a, float x, float y) { asm volatile("st.shared.v2.f32 [%0], {%1,%2};" :: "r"(a), "f"(x), "f"(y) : "memory"); }
DEVI uint32_t lds32(uint32_t a) { uint32_t v; asm volatile("ld.shared.u32 %0, [%1];" : "=r"(v) : "r"(a) : "memory"); return v; }
DEVI float lds32f(uint32_t a) { return __uint_as_float(lds32(a)); }
DEVI void sts32(uint32_t a, uint32_t v) { asm volatile("st.shared.u32 [%0], %1;" :: "r"(a), "r"(v) : "memory"); }
DEVI void sts32f(uint32_t a, float v) { sts32(a, __float_as_uint(v)); }
DEVI void sts16(uint32_t a, uint32_t v) { asm volatile("st.shared.u16 [%0], %1;" :: "r"(a), "h"((unsigned short)v) : "memory"); }
template<int N> DEVI void keep(float (&d)[N]) {
  #pragma unroll
  for (int i = 0; i < N; i++) asm volatile("" : "+f"(d[i]) :: "memory");
}
template<int N> DEVI void keep(uint32_t (&d)[N]) {
  #pragma unroll
  for (int i = 0; i < N; i++) asm volatile("" : "+r"(d[i]) :: "memory");
}
template<uint32_t HI> DEVI uint64_t mkd(uint32_t lo) { uint64_t r; asm("mov.b64 %0, {%1, %2};" : "=l"(r) : "r"(lo), "n"(HI)); return r; }
constexpr uint32_t HI128 = (1u << 30) | (1024 >> 4), HI64 = (2u << 30) | (512 >> 4);
#define VOFF(x) ((uint32_t)(x) * (uint32_t)(1 - 65536))
DEVI bool elect() { uint32_t p; asm volatile("{\n.reg .pred q;\nelect.sync _|q, 0xffffffff;\nselp.u32 %0, 1, 0, q;\n}" : "=r"(p)); return p; }
DEVI void warp_signal(uint32_t bar) { __syncwarp(); if (elect()) mbar_arrive(bar); }

struct Scratch {
  uint4 kv[128][4][1024];
  uint4 o[8][2][8][2][1024];
  uint4 x[8][16][2048];
  uint4 zero[1024];
  uint4 statP[8][2048];
  uint4 statF[2048];
  uint4 csP[16][8][96];
  uint4 best[8][16];
  uint4 row[16][256];
  uint4 yP[128][112][2];
  uint4 x2[8][256];
  uint4 patch[1024];
  unsigned flagKV[128][32];
  unsigned flagO[8][32];
  unsigned flagX[8][32];
  unsigned epoch;
};
__device__ __align__(1024) Scratch g_scr;
#define PROFT(cond, slot)
#define PROFW(cond, slot)
#define PROFD(cond, slot)
#define PROFX(cond, slot)
#define PROFY(cond, slot)

constexpr uint32_t SB0 = 65536, HOLE = 90112, SA2 = 98304, SB1 = 131072, SB2 = 155648, STG = 180224;
constexpr uint32_t KVA = 0, KVB = 98304, QO = 65536;
constexpr uint32_t MISC = 229376, CS = MISC, ONES = MISC + 768, BARS = MISC + 1792, INFO = MISC + 2208, WR = MISC + 2224, X2SEG = MISC + 2736, INFO2 = MISC + 2992, DUMP = MISC + 3040;
constexpr uint32_t PAR = HOLE, HV = HOLE + 2048, RED = HOLE + 6144, PATCH = 196608;
constexpr uint32_t SMEM_BYTES = 232448;
enum { B_FULLQ = 0, B_EMPTYQ = 3, B_FULLW = 6, B_EMPTYW = 12, B_HAFREE = 18, B_OFREE = 20,
       B_XFREE = 21,
       B_KVRDY = 23, B_ORDY = 27, B_XRDY = 35, B_STGE = 39,
       B_KVFULL = 42, B_RES = 46, B_PAR = 47, B_STG = 48, B_PFREE = 51, B_COUNT = 52,
       B_ROW = 154 };
#define BAR(x) (sb + BARS + 8 * (x))
DEVI uint32_t qa_off(int s) { return s == 2 ? SA2 : (uint32_t)s * 32768u; }
DEVI uint32_t qb_off(int s) { return s == 0 ? SB0 : (s == 1 ? SB1 : SB2); }
DEVI int kb_order(int bc, int n) {
  const int e = n < 9 ? n - 2 : n - 9;
  return n < 2 ? 2 * bc + n : 2 * (((e < 4 ? e + 4 : e - 4 + (e - 4 >= (bc & 3))) + (bc & 4)) & 7) + (n >= 9);
}
DEVI int wo_order(int bc, int n) { return (n & 8) | ((n + (bc & 6)) & 7); }
DEVI uint32_t w_off(int s) { return (uint32_t)((0x431065 >> (4 * s)) & 7) * 32768u; }
DEVI uint32_t w_par(int n, int s, int L) { return ((n >= 6 && n < 12) ^ (!(s & 2) && L)); }
DEVI int w_next(int n, int s) { return s == 5 ? 0 : (n == 13 ? 4 : s + 1); }

struct Params {
  CUtensorMap mX, mXh, mWq, mWo, mWg, mWu, mWp, mWd;
  const bf16 *x0, *wqkv, *wo, *wr, *wg, *wu, *wd;
  bf16* out;
  Scratch* g;
  unsigned map[128];
};
#define BID ((int)(P.map[blockIdx.x] & 255))
#define FID ((int)(P.map[blockIdx.x] >> 8))
DEVI uint32_t uni(uint32_t v) { return __shfl_sync(0xffffffffu, v, 0); }
#define PQ_N 8
#define PQ_T 700
#define PF0_N 10
#define PF0_T 1600
#define PF1_E 24
#define PF1_T 1100
#define POL_Q1 POL_NORMAL
#define POL_X POL_NORMAL
#define PFA0_BAR 3
#define PFA1_BAR 0
#define PFA0_M 0
#define PFA1_M 0
#define PFA0_T 900
#define PFA1_T 700
#define PF1_S PF0_N
#define PF1_D 0
#define POL_G POL_NORMAL
#define POL_U POL_FIRST
#define POL_D POL_FIRST
#define JQ_N 6
#define WDSRC (P.wd + (size_t)min(fid, 111) * 32768)
#define WD_N 4
#define THR_N 6
#define KV_D 1300
#define XD_D 600
#define W0_BAR 3
#define POL_Q0 POL_NORMAL
constexpr float LN_EPS = 1e-5f;
constexpr float QSCALE = 0.17677669529663687f * 1.4426950408889634f;

DEVI void fma8(float (&a)[8], uint4 v, float h) {
  a[0] = fmaf(bf_lo(v.x), h, a[0]); a[1] = fmaf(bf_hi(v.x), h, a[1]); a[2] = fmaf(bf_lo(v.y), h, a[2]); a[3] = fmaf(bf_hi(v.y), h, a[3]);
  a[4] = fmaf(bf_lo(v.z), h, a[4]); a[5] = fmaf(bf_hi(v.z), h, a[5]); a[6] = fmaf(bf_lo(v.w), h, a[6]); a[7] = fmaf(bf_hi(v.w), h, a[7]);
}
DEVI void gemv8(float (&a)[8], uint32_t wa, uint32_t ha, uint32_t hs) {
  #pragma unroll
  for (int n = 0; n < 8; n += 2) {
    uint4 v0 = lds128(wa + n * 512), v1 = lds128(wa + n * 512 + 512);
    float h0 = lds32f(ha), h1 = lds32f(ha + hs);
    ha += 2 * hs;
    fma8(a, v0, h0); fma8(a, v1, h1);
  }
}
DEVI uint4 ldsv128(uint32_t a) { uint4 v; asm volatile("ld.volatile.shared.v4.u32 {%0,%1,%2,%3}, [%4];" : "=r"(v.x), "=r"(v.y), "=r"(v.z), "=r"(v.w) : "r"(a) : "memory"); return v; }
DEVI float ldsv32f(uint32_t a) { float v; asm volatile("ld.volatile.shared.f32 %0, [%1];" : "=f"(v) : "r"(a) : "memory"); return v; }
DEVI uint32_t clk() { uint32_t t; asm volatile("mov.u32 %0, %%clock;" : "=r"(t)); return t; }
DEVI int fresh_tid() { int t; asm volatile("mov.u32 %0, %%tid.x;" : "=r"(t)); return t & 127; }
DEVI float fold8(const float (&a)[8]) {
  const int lane = threadIdx.x & 31;
  const bool u = lane & 16, v = lane & 8, x = lane & 4;
  float b0 = (u ? a[4] : a[0]) + __shfl_xor_sync(0xffffffffu, u ? a[0] : a[4], 16), b1 = (u ? a[5] : a[1]) + __shfl_xor_sync(0xffffffffu, u ? a[1] : a[5], 16);
  float b2 = (u ? a[6] : a[2]) + __shfl_xor_sync(0xffffffffu, u ? a[2] : a[6], 16), b3 = (u ? a[7] : a[3]) + __shfl_xor_sync(0xffffffffu, u ? a[3] : a[7], 16);
  float c0 = (v ? b2 : b0) + __shfl_xor_sync(0xffffffffu, v ? b0 : b2, 8), c1 = (v ? b3 : b1) + __shfl_xor_sync(0xffffffffu, v ? b1 : b3, 8);
  return (x ? c1 : c0) + __shfl_xor_sync(0xffffffffu, x ? c0 : c1, 4);
}
DEVI float swiglu(float g, float u) { g = bf_round(g); return bf_round(bf_round(__fdividef(g, 1.f + __expf(-g))) * bf_round(u)); }

DEVI void qk_issue(float (&s)[32], uint32_t qd, uint32_t kd) {
  wgmma_ss_n64<0>(s, mkd<HI64>(qd), mkd<HI64>(kd), 0);
  wgmma_ss_n64<0>(s, mkd<HI64>(qd + 2), mkd<HI64>(kd + 2), 1);
}
template<int J0, int J1> DEVI void exp_pack(const float (&s)[32], uint32_t (&p)[16]) {
  #pragma unroll
  for (int j = J0; j < J1; j++) p[j] = pack_bf16(ex2f(s[2 * j]), ex2f(s[2 * j + 1]));
}
DEVI bool attn_pack(const float (&o)[20], uint32_t (&ob)[8]) {
  const float lo = 5.421010862427522e-20f, hi = 1.8446744073709552e19f;
  float i0, i1; asm("rcp.approx.ftz.f32 %0, %1;" : "=f"(i0) : "f"(o[16])); asm("rcp.approx.ftz.f32 %0, %1;" : "=f"(i1) : "f"(o[18]));
  #pragma unroll
  for (int e = 0; e < 8; e++) ob[e] = pack_bf16(o[2 * e] * ((e & 1) ? i1 : i0), o[2 * e + 1] * ((e & 1) ? i1 : i0));
  return __all_sync(0xffffffffu, o[16] >= lo && o[16] <= hi && o[18] >= lo && o[18] <= hi);
}
DEVI void attn_store(const uint32_t (&ob)[8], bool ok, uint32_t st, uint32_t sb, uint32_t bar) {
  stsm_x4(ok ? st : sb + DUMP, ob[0], ob[1], ob[2], ob[3]); stsm_x4(ok ? st ^ 32 : sb + DUMP, ob[4], ob[5], ob[6], ob[7]);
  __syncwarp();
  asm volatile("{\n.reg .pred p, q;\nelect.sync _|q, 0xffffffff;\nsetp.ne.and.u32 p, %1, 0, q;\n@p mbarrier.arrive.shared::cta.b64 _, [%0];\n}" :: "r"(bar), "r"((uint32_t)ok) : "memory");
}
DEVI void attn_exact(uint32_t st, uint32_t kv, int t, bool hasprev, uint32_t bar) {
  const int lane = threadIdx.x & 31;
  #pragma unroll 1
  for (int row = ((threadIdx.x >> 5) & 3) * 16, n = 0; n < 16; n++, row++) {
    const int k1 = 256 + t * 64 + row;
    float m = -INFINITY, l = 0.f, o = 0.f;
    #pragma unroll 1
    for (int k0 = hasprev ? k1 - 255 : 256; k0 <= k1; k0 += 32) {
      const int k = min(k0 + lane, k1), r = k & 63;
      float sc = 0.f;
      #pragma unroll 1
      for (int c = 0; c < 16; c++) {
        uint32_t a = lds32(st + row * 64 + ((c * 4) ^ ((row & 6) << 3))), b = lds32(kv + (k >> 6) * 8192 + r * 64 + ((c * 4) ^ ((r & 6) << 3)));
        sc = fmaf(bf_lo(a), bf_lo(b), fmaf(bf_hi(a), bf_hi(b), sc));
      }
      float mn = fmaxf(m, sc);
      #pragma unroll 1
      for (int x = 16; x; x >>= 1) mn = fmaxf(mn, __shfl_xor_sync(0xffffffffu, mn, x));
      const float al = ex2f(m - mn), pr = ex2f(sc - mn);
      m = mn; l *= al; o *= al;
      #pragma unroll 1
      for (int q = k0; q <= min(k0 + 31, k1); q++) {
        const float z = __shfl_sync(0xffffffffu, pr, q - k0);
        uint32_t b = lds32(kv + (q >> 6) * 8192 + 4096 + (q & 63) * 64 + (((lane >> 1) * 4) ^ ((q & 6) << 3)));
        l += z; o = fmaf(z, (lane & 1) ? bf_hi(b) : bf_lo(b), o);
      }
    }
    __syncwarp();
    sts16(st + row * 64 + ((lane * 2) ^ ((row & 6) << 3)), pack_bf16(__fdividef(o, l), 0.f));
  }
  warp_signal(bar);
}

template<int K0, int K1, int DONE = 0> DEVI void exp_pv(const float (&s)[32], uint32_t (&p)[16], float (&o)[20], uint32_t vd, bool accum) {
  #pragma unroll
  for (int ks = K0; ks < K1; ks++) {
    if (ks >= DONE) {
      #pragma unroll
      for (int j = 4 * ks; j < 4 * ks + 4; j++) p[j] = pack_bf16(ex2f(s[2 * j]), ex2f(s[2 * j + 1]));
    }
    asm volatile("" : "+r"(p[4 * ks]), "+r"(p[4 * ks + 1]), "+r"(p[4 * ks + 2]), "+r"(p[4 * ks + 3]));
    wg_fence();
    wgmma_rs_n40<1>(o, p[ks * 4], p[ks * 4 + 1], p[ks * 4 + 2], p[ks * 4 + 3], mkd<HI64>(vd + VOFF(ks * 64)), ks ? 1 : accum);
  }
}
DEVI void exp_pv2(const float (&s)[32], const float (&sx)[32], uint32_t (&p)[16], uint32_t (&px)[16], float (&o)[20], uint32_t v0, uint32_t v4,
                  const uint32_t (&msk)[9], int tdiag) {
  #pragma unroll
  for (int ks = 0; ks < 4; ks++) {
    #pragma unroll
    for (int j = 4 * ks; j < 4 * ks + 4; j++) {
      const int c = 8 * (j >> 1) - 8 * (j & 1);
      const uint32_t e = pack_bf16(ex2f(c > tdiag ? s[2 * j] : sx[2 * j]), ex2f(c + 1 > tdiag ? s[2 * j + 1] : sx[2 * j + 1])), m = msk[(j >> 1) - (j & 1) + 1];
      p[j] = e & m; px[j] = e & ~m;
      asm volatile("" : "+r"(p[j]), "+r"(px[j]));
    }
    wg_fence();
    wgmma_rs_n40<1>(o, p[ks * 4], p[ks * 4 + 1], p[ks * 4 + 2], p[ks * 4 + 3], mkd<HI64>(v0 + VOFF(ks * 64)), 1);
    wgmma_rs_n40<1>(o, px[ks * 4], px[ks * 4 + 1], px[ks * 4 + 2], px[ks * 4 + 3], mkd<HI64>(v4 + VOFF(ks * 64)), 1);
  }
}

template<int J0> DEVI void qkv_store(const float (&a)[96], float p0, float p1, uint32_t d) {
  #pragma unroll
  for (int hh = 0; hh < 2; hh++) {
    const int j = 4 * (J0 + 2 * hh);
    stsm_x4(d ^ (hh << 5), pack_bf16(a[j] * p0, a[j + 1] * p0), pack_bf16(a[j + 2] * p1, a[j + 3] * p1),
                           pack_bf16(a[j + 4] * p0, a[j + 5] * p0), pack_bf16(a[j + 6] * p1, a[j + 7] * p1));
  }
}
DEVI void mean_step(float (&a)[96], float m0, float m1, uint32_t cd, bool z) {
  const uint32_t u0 = z ? 0u : __float_as_uint(m0), u1 = z ? 0u : __float_as_uint(m1);
  uint32_t ma[4] = {__byte_perm(u0, 0u, 0x1010), __byte_perm(u1, 0u, 0x1010), __byte_perm(u0, 0u, 0x3232), __byte_perm(u1, 0u, 0x3232)};
  keep(ma);
  wg_fence();
  wgmma_rs_n192<1>(a, ma[0], ma[1], ma[2], ma[3], mkd<2>(cd), 1);
  wg_commit();
}

template<bool FIRST> DEVI void qkv_block(float (&aX)[96], float (&aY)[96], uint32_t sb16, int s, int tX, int tY) {
  uint32_t a16 = sb16 + (qa_off(s) >> 4), b16 = (sb16 + (qb_off(s) >> 4)) | ((8192u >> 4) << 16);
  uint32_t ax = (a16 + tX * 512) | 0x10000u, ay = (a16 + tY * 512) | 0x10000u;
  wg_fence();
  #pragma unroll
  for (int ks = 0; ks < 4; ks++) {
    wgmma_ss_n192<1>(aX, mkd<HI128>(ax + ks * 2), mkd<HI128>(b16 + ks * 128), !(FIRST && ks == 0));
    wgmma_ss_n192<1>(aY, mkd<HI128>(ay + ks * 2), mkd<HI128>(b16 + ks * 128), !(FIRST && ks == 0));
  }
  wg_commit();
}
DEVI void qkv_half(float (&a)[96], uint32_t sb16, int t, uint32_t sa, uint32_t sbb) {
  wg_fence();
  #pragma unroll
  for (int ks = 0; ks < 4; ks++)
    wgmma_ss_n192<1>(a, mkd<HI128>(((sb16 + (sa >> 4) + t * 512) | 0x10000u) + ks * 2), mkd<HI128>(((sb16 + (sbb >> 4)) | ((8192u >> 4) << 16)) + ks * 128), 1);
  wg_commit();
}
template<bool FIRST> DEVI void wo_block(float (&acc)[64], uint32_t sb16, int s, int wg) {
  uint32_t a16 = (sb16 + (w_off(s) >> 4) + wg * 256) | 0x10000u, b16 = (sb16 + (w_off(s) >> 4) + 1024) | ((8192u >> 4) << 16);
  wg_fence();
  #pragma unroll
  for (int ks = 0; ks < 4; ks++)
    wgmma_ss_n128<1>(acc, mkd<HI64>(a16 + (ks >> 1) * 512 + (ks & 1) * 2), mkd<HI128>(b16 + ks * 128), !(FIRST && ks == 0));
  wg_commit();
}
DEVI void consumer(const Params& P, uint32_t sb, int wg) {
  const int w = uni((threadIdx.x >> 5) & 3);
  #define LAYER uni(mbar_test(BAR(B_RES), 0))
  #define IDS L = LAYER; const int tid = fresh_tid(), lane = tid & 31
  const uint32_t ids = uni(P.map[blockIdx.x]);
  const int bi = (ids >> 4) & 7, rh = ids & 1, bc = (ids & 15) >> 1, fid = ids >> 8;
  const int tX = 3 - wg, tY = wg;
  constexpr uint32_t sb16 = 1024 >> 4;
  #pragma unroll 1
  while (true) {
    int L = LAYER;
    {
      float aX[96], aY[96];
      const bool lead = fresh_tid() == 0;
      if (L) mbar_wait(BAR(B_XRDY + wg * 2 + 1), 0);
      mbar_wait(BAR(B_FULLQ), 0);
      PROFW(threadIdx.x == 0, L * 8 + 1);
      qkv_block<true>(aX, aY, sb16, 0, tX, tY);
      #pragma unroll 1
      for (int n = 1, s = 1, ps = 0, ph = 0; n < 14; n++) {
        mbar_wait(BAR(B_FULLQ + s), ph ^ (s ? L : 0));
        PROFD(threadIdx.x == 0 && L && (n == 2 || n == 3 || n == 7 || n == 11 || n == 13), n == 2 ? 48 : 49 + (n >> 2));
        qkv_block<false>(aX, aY, sb16, s, tX, tY);
        wg_wait<1>(); if (lead) mbar_arrive(BAR(B_EMPTYQ + ps));
        ps = s; if (s == 2) { s = 0; ph ^= 1; } else s++;
      }
      mbar_wait(BAR(B_ROW), L);
      IDS;
      const uint32_t pa = sb + PAR + (w * 16 + (lane >> 2)) * 8;
      float2 p0 = lds64f(pa + tX * 512), p1 = lds64f(pa + tX * 512 + 64), p2 = lds64f(pa + tY * 512), p3 = lds64f(pa + tY * 512 + 64);
      mean_step(aX, p0.y, p1.y, sb16 + (CS >> 4), lane & 3);
      mbar_wait(BAR(B_FULLQ + 2), L);
      qkv_half(aX, sb16, tX, SA2, SB2);
      mbar_wait(BAR(B_FULLQ), 1);
      qkv_half(aX, sb16, tX, 0, SB0);
      wg_wait<3>(); if (lead) mbar_arrive(BAR(B_EMPTYQ + 1));
      bar_sync(1, 256);
      qkv_half(aY, sb16, tY, SA2, SB2);
      wg_wait<1>(); keep(aX);
      const int srow = w * 16 + (lane & 15);
      const uint32_t x0 = sb + srow * 64 + (((lane >> 4) ^ ((srow >> 1) & 3)) << 4), xX = x0 + (4 + tX) * 8192, xY = x0 + (4 + tY) * 8192;
      qkv_store<8>(aX, p0.x, p1.x, xX + KVA); qkv_store<16>(aX, p0.x, p1.x, xX + KVA + 4096);
      if (!L) warp_signal(BAR(B_KVRDY + wg * 2));
      qkv_half(aY, sb16, tY, 0, SB0);
      mean_step(aY, p2.y, p3.y, sb16 + (CS >> 4), fresh_tid() & 3);
      mbar_wait(BAR(B_PAR), L);
      const int l3 = fresh_tid() & 3, prow = (int)uni(lds32(sb + INFO)) - bi * 256;
      const bool pmine = (prow >> 4) == tX * 4 + w || (prow >> 4) == tY * 4 + w;
      const uint32_t poff = sb + (prow & 63) * 64 + ((l3 ^ ((prow >> 1) & 3)) << 4);
      if (pmine) { __syncwarp(); if (lane < 8) sts128(poff + KVA + (4 + (prow >> 6)) * 8192 + (lane >> 2) * 4096, lds128(sb + PATCH + 128 + (lane >> 2) * 128 + l3 * 16)); }
      if (L) warp_signal(BAR(B_KVRDY + wg * 2));
      wg_wait<2>(); if (lead) mbar_arrive(BAR(B_EMPTYQ + 2));
      mbar_wait(BAR(B_EMPTYQ + 2), L);
      qkv_store<12>(aX, p0.x, p1.x, xX + KVB); qkv_store<20>(aX, p0.x, p1.x, xX + KVB + 4096);
      wg_wait<0>(); keep(aY);
      if (lead) mbar_arrive(BAR(B_EMPTYQ));
      PROFW(threadIdx.x == 0, L * 8 + 2);
      qkv_store<8>(aY, p2.x, p3.x, xY + KVA); qkv_store<16>(aY, p2.x, p3.x, xY + KVA + 4096);
      qkv_store<12>(aY, p2.x, p3.x, xY + KVB); qkv_store<20>(aY, p2.x, p3.x, xY + KVB + 4096);
      p0.x *= QSCALE; p1.x *= QSCALE; p2.x *= QSCALE; p3.x *= QSCALE;
      mbar_wait(BAR(B_EMPTYQ), 1);
      qkv_store<0>(aX, p0.x, p1.x, x0 + QO + tX * 4096); qkv_store<4>(aX, p0.x, p1.x, x0 + QO + 16384 + tX * 4096);
      qkv_store<0>(aY, p2.x, p3.x, x0 + QO + tY * 4096); qkv_store<4>(aY, p2.x, p3.x, x0 + QO + 16384 + tY * 4096);
      if (pmine) {
        __syncwarp();
        if (lane < 24) sts128(poff + (lane < 8 ? QO + (lane >> 2) * 16384 + (prow >> 6) * 4096 : ((lane & 4) ? KVB : KVA) + (4 + (prow >> 6)) * 8192 + (lane >> 4) * 4096),
                              lds128(sb + PATCH + lane * 16));
      }
      fence_async_smem();
      warp_signal(BAR(B_KVRDY + wg * 2 + 1));
      bar_sync(1, 256);
    }
    PROFW(threadIdx.x == 0, L * 8 + 3);
    {
      IDS;
      float s0[32], s1[32], sx[32], o[20], op[20];
      uint32_t p0[16], p1[16], px[16], msk[9];
      const int tdiag = w * 16 + (lane >> 2) - 2 * (lane & 3);
      #pragma unroll
      for (int e = 0; e < 9; e++) msk[e] = ((8 * e - 8 > tdiag) ? 0xFFFFu : 0u) | ((8 * e - 7 > tdiag) ? 0xFFFF0000u : 0u);
      keep(msk);
      const uint32_t ones = (sb16 + (ONES >> 4)) << 16;
      const uint32_t qX = (sb16 + (QO >> 4) + tX * 256) | 0x10000u, qY = (sb16 + (QO >> 4) + tY * 256) | 0x10000u;
      const uint32_t kXB = (sb16 + (KVB >> 4) + tX * 512) | 0x10000u;
      uint32_t redo = 0;
      const uint32_t ost = sb + QO + (w * 16 + (lane & 15)) * 64 + (((lane >> 4) ^ ((lane >> 1) & 3)) << 4);
      #define QK(s, q, k) do { wg_fence(); qk_issue(s, q, k); wg_commit(); } while (0)
      #define QK2(q, k) do { wg_fence(); qk_issue(s1, q, k); qk_issue(sx, q, (k) + 2048); wg_commit(); } while (0)
      #define VB(v, b) ((v) + VOFF((b) * 512))
      {
        const uint32_t kXA = kXB - ((KVB - KVA) >> 4), vB = VOFF((kXB & 0xffffu) + 256), vA = vB - VOFF((KVB - KVA) >> 4);
        QK(s0, qX, kXA + 1536); qk_issue(s1, qX, kXA + 1024); wg_commit();
        wg_wait<1>(); keep(s0);
        exp_pv<0, 4>(s0, p0, o, VB(vA + ones, 3), false); wg_commit();
        wg_wait<1>(); keep(s1);
        QK(s0, qX + 1024, kXB + 1536);
        exp_pv<0, 4>(s1, p1, o, VB(vA + ones, 2), true); wg_commit();
        wg_wait<1>(); keep(s0); keep(p0);
        QK(s1, qX + 1024, kXB + 1024);
        exp_pv<0, 4>(s0, p0, op, VB(vB + ones, 3), false); wg_commit();
        wg_wait<1>(); keep(s1); keep(p1); keep(o);
        exp_pv<0, 2>(s1, p1, op, VB(vB + ones, 2), true);
        bar_sync(4 + wg * 4, 160);
        QK(s0, qX, kXA + 512);
        exp_pv<2, 4>(s1, p1, op, VB(vB + ones, 2), true); wg_commit();
        wg_wait<0>(); keep(s0); keep(p0); keep(p1); keep(op);
      }
      #pragma unroll 1
      for (int h = 0; h < 2; h++) {
        const uint32_t kb16 = sb16 + ((h ? KVB : KVA) >> 4), kY = (kb16 + tY * 512) | 0x10000u, qy = qY + h * 1024;
        const uint32_t onesP = bi ? ones : (kb16 + 1984) << 16;
        const uint32_t vX = VOFF(kb16 + tX * 512 + 256), vY = VOFF(kb16 + tY * 512 + 256);
        uint32_t ob[8];
        QK2(qX + h * 1024, (kb16 + tX * 512) | 0x10000u);
        exp_pv<0, 4>(s0, p0, o, VB(vX + (wg ? onesP : ones), 1), true); wg_commit();
        wg_wait<1>(); keep(s1); keep(sx);
        QK(s0, qy, kY + 1536);
        exp_pv2(s1, sx, p1, px, o, vX + onesP, VB(vX + ones, 4), msk, tdiag); wg_commit();
        wg_wait<1>(); keep(s0); keep(p0);
        QK(s1, qy, kY + 1024);
        exp_pack<0, 4>(s0, p0);
        wg_wait<1>(); keep(o); keep(p1); keep(px);
        bool ok = attn_pack(o, ob); keep(ob);
        exp_pv<0, 4, 1>(s0, p0, o, VB(vY + (wg ? ones : onesP), 3), false); wg_commit();
        attn_store(ob, ok, ost + (h * 4 + tX) * 4096, sb, BAR(B_ORDY + wg * 4 + h * 2)); redo |= ok ? 0u : 1u << (h * 2);
        wg_wait<1>(); keep(s1);
        exp_pv<0, 2>(s1, p1, o, VB(vY + onesP, 2), true);
        bar_sync(5 + wg * 4 + h * 2, 160);
        QK(s0, qy, kY + 512);
        exp_pv<2, 4>(s1, p1, o, VB(vY + onesP, 2), true); wg_commit();
        wg_wait<1>(); keep(s0); keep(p0);
        QK2(qy, kY);
        exp_pv<0, 4>(s0, p0, o, VB(vY + onesP, 1), true); wg_commit();
        wg_wait<1>(); keep(s1); keep(sx); keep(p1);
        bar_sync(6 + wg * 4, h ? 128 : 160);
        QK(s0, h ? qy : qX + 1024, kXB + 512);
        exp_pv2(s1, sx, p1, px, o, vY + onesP, VB(vY + ones, 4), msk, tdiag); wg_commit();
        wg_wait<0>(); keep(o); keep(s0); keep(p0); keep(p1); keep(px);
        ok = attn_pack(o, ob); attn_store(ob, ok, ost + (h * 4 + tY) * 4096, sb, BAR(B_ORDY + wg * 4 + h * 2 + 1)); redo |= ok ? 0u : 2u << (h * 2);
        #pragma unroll
        for (int e = 0; e < 20; e++) o[e] = op[e];
      }
      #undef QK
      #undef QK2
      #undef VB
      if (redo) {
        #pragma unroll 1
        for (int u = 0; u < 4; u++) if ((redo >> u) & 1) {
          const int h = u >> 1, t = (u & 1) ? tY : tX;
          attn_exact(sb + QO + (h * 4 + t) * 4096, sb + (h ? KVB : KVA), t, bi > 0, BAR(B_ORDY + wg * 4 + u));
        }
      }
    }
    PROFW(threadIdx.x == 0, L * 8 + 4);
    {
      IDS;
      const int t256 = wg * 128 + tid;
      float acc[64];
      const int tt = wg ^ rh;
      const int grow = bi * 256 + rh * 128 + tt * 64 + w * 16 + (lane >> 2);
      float al0 = 1.f, be0 = 0.f, al1 = 1.f, be1 = 0.f;
      const int idx0 = (int)uni(lds32(sb + INFO));
      const uint32_t tag = lds32(sb + INFO + 8) + L;
      uint4* const sp = &P.g->statP[bc][grow + (lane & 1) * 8];
      uint4* const yp = &P.g->yP[t256 >> 1][min(fid, 111)][t256 & 1];
      mbar_wait(BAR(B_FULLW), L);
      PROFW(t256 == 0, L * 8 + 5);
      wo_block<true>(acc, sb16, 0, tt);
      if (!(lane & 2)) st_ll(sp, 0u, 0u, 0u, 0u);
      uint4 fa = make_uint4(0u, 0u, 0u, 0u), fb = fa;
      uint2 wd[32];
      if (L) {
        if (fid < 112) st_ll(yp, 0u, 0u, 0u, 0u);
        fa = ld_ll(&P.g->statF[grow]); fb = ld_ll(&P.g->statF[grow + 8]);
      }
      #pragma unroll
      for (int n = 0; n < 32; n++) wd[n] = make_uint2(0u, 0u);
      #pragma unroll 1
      for (int n = 1, q = 1, pq = 0; n < 16; n++) {
        mbar_wait(BAR(B_FULLW + q), w_par(n, q, L));
        PROFD(t256 == 0 && !L && (n == 4 || n == 7 || n == 8 || n == 12), (n == 7 ? 63 : 41 + (n >> 2)));
        wo_block<false>(acc, sb16, q, tt);
        if (L && n == WD_N) {
          const uint2* src = (const uint2*)(WDSRC) + t256;
          #pragma unroll
          for (int e = 0; e < 32; e++) wd[e] = ldg_stream(src + e * 256);
        }
        wg_wait<1>(); if (tid == 0) mbar_arrive(BAR(B_EMPTYW + pq));
        pq = q; q = w_next(n, q);
      }
      if (L) {
        float r0 = rsqrtf(__uint_as_float(fa.y) + LN_EPS), r1 = rsqrtf(__uint_as_float(fb.y) + LN_EPS);
        if (grow != idx0) { al0 = 1.f + r0; be0 = -__uint_as_float(fa.x) * r0; }
        if (grow + 8 != idx0) { al1 = 1.f + r1; be1 = -__uint_as_float(fb.x) * r1; }
      }
      mbar_wait(BAR(B_RES), L);
      const int srow = tt * 64 + w * 16 + (lane & 15);
      const uint32_t ra = sb + rh * 16384 + srow * 128, sw = ((lane >> 4) ^ (srow & 7)) << 4;
      if ((idx0 >> 4) == bi * 16 + rh * 8 + tt * 4 + w) {
        int r = idx0 & 127;
        if (lane < 16) sts128(sb + (lane >> 3) * 32768 + rh * 16384 + r * 128 + (((lane & 7) ^ (r & 7)) << 4), lds128(sb + X2SEG + lane * 16));
        __syncwarp();
      }
      uint32_t rs[32];
      #pragma unroll
      for (int jj = 0; jj < 8; jj++) ldsm_x4((ra + (jj >> 2) * 32768) + (sw ^ ((jj & 3) << 5)), rs[4 * jj], rs[4 * jj + 1], rs[4 * jj + 2], rs[4 * jj + 3]);
      float rf[64];
      #pragma unroll
      for (int e = 0; e < 32; e++) { rf[2 * e] = fmaf(bf_lo(rs[e]), (e & 1) ? al1 : al0, (e & 1) ? be1 : be0); rf[2 * e + 1] = fmaf(bf_hi(rs[e]), (e & 1) ? al1 : al0, (e & 1) ? be1 : be0); }
      keep(rf);
      mbar_wait(BAR(B_RES), L);
      wg_wait<0>(); keep(acc);
      if (tid == 0) mbar_arrive(BAR(B_EMPTYW + 5));
      PROFW(t256 == 0, L * 8 + 6);
      #pragma unroll
      for (int jj = 0; jj < 8; jj++) {
        float* a = acc + 8 * jj;
        #pragma unroll
        for (int e = 0; e < 8; e++) a[e] += rf[8 * jj + e];
        stsm_x4((ra + (jj >> 2) * 32768) + (sw ^ ((jj & 3) << 5)), pack_bf16(a[0], a[1]), pack_bf16(a[2], a[3]), pack_bf16(a[4], a[5]), pack_bf16(a[6], a[7]));
        if (jj == 7) fence_async_smem();
        if ((jj & 3) == 3) warp_signal(BAR(B_XRDY + wg * 2 + (jj >> 2)));
      }
      {
        float s1a = 0.f, s2a = 0.f, da = 0.f, s1b = 0.f, s2b = 0.f, db = 0.f;
        #pragma unroll
        for (int j = 0; j < 16; j++) {
          const float* a = acc + 4 * j; float2 wv = lds64f(sb + WR + j * 32 + (lane & 3) * 8);
          s1a += a[0] + a[1]; s1b += a[2] + a[3];
          s2a = fmaf(a[0], a[0], s2a); s2b = fmaf(a[2], a[2], s2b); s2a = fmaf(a[1], a[1], s2a); s2b = fmaf(a[3], a[3], s2b);
          da = fmaf(a[0], wv.x, da); db = fmaf(a[2], wv.x, db); da = fmaf(a[1], wv.y, da); db = fmaf(a[3], wv.y, db);
        }
        bool odd = lane & 1;
        float u1 = (odd ? s1b : s1a) + __shfl_xor_sync(0xffffffffu, odd ? s1a : s1b, 1);
        float u2 = (odd ? s2b : s2a) + __shfl_xor_sync(0xffffffffu, odd ? s2a : s2b, 1);
        float u3 = (odd ? db : da) + __shfl_xor_sync(0xffffffffu, odd ? da : db, 1);
        u1 += __shfl_xor_sync(0xffffffffu, u1, 2); u2 += __shfl_xor_sync(0xffffffffu, u2, 2); u3 += __shfl_xor_sync(0xffffffffu, u3, 2);
        if (!(lane & 2)) st_ll(sp, __float_as_uint(u1), __float_as_uint(u2), __float_as_uint(u3), tag);
      }
      PROFW(t256 == 0, L * 8 + 7);
      if (L) {
        mbar_wait(BAR(B_PAR), 0);
        { float2 pa = lds64f(sb + PAR + (grow & 127) * 8), pb = lds64f(sb + PAR + (grow & 127) * 8 + 64); al0 = pa.x; be0 = pa.y; al1 = pb.x; be1 = pb.y; }
        #pragma unroll
        for (int j = 0; j < 16; j++) {
          rs[2 * j] = pack_bf16(fmaf(acc[4 * j], al0, be0), fmaf(acc[4 * j + 1], al0, be0));
          rs[2 * j + 1] = pack_bf16(fmaf(acc[4 * j + 2], al1, be1), fmaf(acc[4 * j + 3], al1, be1));
        }
        const int idx1 = (int)lds32(sb + INFO + 4);
        #pragma unroll
        for (int jj = 0; jj < 8; jj++) stsm_x4((ra + (jj >> 2) * 32768) + (sw ^ ((jj & 3) << 5)), rs[4 * jj], rs[4 * jj + 1], rs[4 * jj + 2], rs[4 * jj + 3]);
        __syncwarp();
        {
          const int r0 = (grow & ~15) + (lane >> 4), skip = idx1 - r0;
          const uint32_t a0 = sb + ((lane >> 3) & 1) * 32768 + (r0 & 255) * 128 + (((lane & 7) ^ (lane >> 4)) << 4);
          uint4* dst = (uint4*)(P.out + (size_t)r0 * 1024 + bc * 128) + (lane & 15);
          #pragma unroll
          for (int it = 0; it < 8; it++) { uint4 v = lds128((a0 + it * 256) ^ ((it & 3) << 5)); if (skip != 2 * it) dst[it * 256] = v; }
        }
        PROFW(t256 == 0, 16);
        if (fid < 112) {
          const int q = wg * 2 + (w >> 1);
          float g[8] = {0.f, 0.f, 0.f, 0.f, 0.f, 0.f, 0.f, 0.f};
          mbar_wait(BAR(B_FULLW + q + 2 * wg), 0);
          bar_sync(3, 384);
          PROFW(t256 == 0, 29);
          #pragma unroll 1
          for (int n = 0; n < 4; n++) gemv8(g, sb + w_off(q + 2 * wg) + (w & 1) * 16384 + n * 4096 + lane * 16, sb + HV + (q * 256 + n * 64 + (lane >> 2)) * 4, 32);
          sts32f(sb + PAR + 1024 + (q * 2 + (w & 1)) * 128 + ((lane & 3) * 8 + (lane >> 2)) * 4, fold8(g));
          bar_sync(1, 256);
          const uint32_t d = sb + PAR + 1024 + lane * 4;
          const float act = swiglu((lds32f(d) + lds32f(d + 256)) + (lds32f(d + 512) + lds32f(d + 768)),
                                   (lds32f(d + 128) + lds32f(d + 384)) + (lds32f(d + 640) + lds32f(d + 896)));
          PROFW(t256 == 0, 26);
          float y0 = 0.f, y1 = 0.f, y2 = 0.f, y3 = 0.f;
          sts32f(sb + HV + t256 * 4, act);
          __syncwarp();
          uint4 a4;
          #pragma unroll
          for (int n = 0; n < 32; n++) {
            if (!(n & 3)) a4 = lds128(sb + HV + (t256 >> 5) * 128 + n * 4);
            float av = __uint_as_float((n & 3) == 0 ? a4.x : ((n & 3) == 1 ? a4.y : ((n & 3) == 2 ? a4.z : a4.w)));
            y0 = fmaf(bf_lo(wd[n].x), av, y0); y1 = fmaf(bf_hi(wd[n].x), av, y1); y2 = fmaf(bf_lo(wd[n].y), av, y2); y3 = fmaf(bf_hi(wd[n].y), av, y3);
          }
          st_ll(yp, __float_as_uint(y0), __float_as_uint(y1), __float_as_uint(y2), (__float_as_uint(y3) & ~255u) | (lds32(sb + INFO + 12) + 1));
          PROFW(t256 == 0, 27);
        }
        return;
      }
    }
  }
  #undef IDS
  #undef LAYER
}

DEVI void loader(const Params& P, uint32_t sb) {
  const int lane = threadIdx.x & 31;
  const int bid = uni(BID), bi = bid >> 4, bp = bid & 15, rh = bp & 1, bc = bp >> 1;
  uint32_t phq = 0, tag = 0;
  #pragma unroll 1
  for (int L = 0; L < 2; L++) {
    int s = 0;
    uint32_t rdy = 0;
    #pragma unroll 1
    for (int n = L ? 0 : 3; n < 16; n++) {
      int kb = L ? kb_order(bc, n) : n;
      mbar_wait(BAR(B_EMPTYQ + s), (phq >> s) & 1);
      phq ^= 1u << s;
      if (L && n == 1) { mbar_wait(BAR(B_XRDY + 1), 0); mbar_wait(BAR(B_XRDY + 3), 0); }
      if (lane == 0) {
        mbar_expect_tx(BAR(B_FULLQ + s), L && n < 2 ? 40960 : 57344);
        tma_3d_h(sb + qb_off(s), &P.mWq, bp * 64, kb * 64, 0, BAR(B_FULLQ + s), L ? POL_Q1 : POL_Q0);
        if (!L) tma_2d(sb + qa_off(s), &P.mX, kb * 64, bi * 256, BAR(B_FULLQ + s));
      }
      if (L && n >= 2) {
        if (((rdy >> (2 * kb)) & 3) != 3) {
          do { rdy = __ballot_sync(0xffffffffu, ld_rlx(&P.g->flagX[bi][lane]) == tag); } while (((rdy >> (2 * kb)) & 3) != 3);
          fence_async_glob();
        }
        if (n == 3 || n == 4) mbar_wait(BAR(B_XFREE + n - 3), 0);
        if (lane == 0) bulk_g2s_h(sb + qa_off(s), P.g->x[bi][kb], 32768, BAR(B_FULLQ + s), POL_X);
      }
      PROFY(L && lane == 0 && (n == 2 || n == 3 || n == 9), n == 9 ? 60 : 56 + n);
      if (L && n == 2) { mbar_wait(BAR(B_FULLQ), 0); mbar_wait(BAR(B_FULLQ + 1), 1); if (lane < 2) mbar_arrive_peer(BAR(B_XFREE + lane)); }
      s = (s == 2) ? 0 : s + 1;
    }
    for (int q = 0; q < 3; q++) mbar_wait(BAR(B_EMPTYQ + q), (phq >> q) & 1);
    mbar_wait(BAR(B_PAR), L);
    tag = lds32(sb + INFO + 8) + L;
    #pragma unroll 1
    for (int q = 0; q < 4; q++) {
            if (bi) {
        const unsigned* f = &P.g->flagKV[bid - 16][q];
        while (ld_rlx(f) != tag);
        fence_async_glob();
      }
      if (lane == 0) {
        mbar_expect_tx(BAR(B_KVFULL + q), 16384);
        bulk_g2s_h(sb + ((q >> 1) ? KVB : KVA) + ((q & 1) ? 0 : 16384), bi ? P.g->kv[bid - 16][q] : P.g->zero, 16384, BAR(B_KVFULL + q));
      }
      PROFY(!L && lane == 0 && bi && q != 2, 34 + (q + 1) / 2);
    }
    mbar_wait(BAR(B_ORDY), L); mbar_wait(BAR(B_ORDY + 4), L);
    {
      const uint4* src = P.g->o[bi][0][0][rh];
      rdy = 0;
      #pragma unroll 1
      for (int n = 0, q = 0; n < 16; q = w_next(n, q), n++) {
        const int j = wo_order(bc, n);
        if (((rdy >> (2 * j)) & 3) != 3) {
          do { rdy = __ballot_sync(0xffffffffu, ld_rlx(&P.g->flagO[bi][lane]) == tag); } while (((rdy >> (2 * j)) & 3) != 3);
          fence_async_glob();
        }
        if (n >= 2) mbar_wait(n < 6 ? BAR(B_HAFREE + (n >> 2)) : BAR(B_EMPTYW + q), n < 6 ? L : w_par(n - 6, q, L));
        if (n == THR_N) mbar_wait(BAR(B_OFREE), L);
        if (lane == 0) { mbar_expect_tx(BAR(B_FULLW + q), 16384); bulk_g2s_h(sb + w_off(q), src + j * 2048, 16384, BAR(B_FULLW + q)); }
      }
    }
    mbar_wait(BAR(B_OFREE), L);
  }
}

DEVI void ffn_prefetch(const Params& P, int q) {
  bulk_prefetch(q < 16 ? ((q & 1) ? P.wu : P.wg) + ((q >> 1) * 128 + blockIdx.x) * 3584 : P.wd + (min(FID, 111) * 8 + q - 16) * 4096, q < 16 ? 7168 : 8192);
}
DEVI void storer(const Params& P, uint32_t sb, int wg) {
  const int bid = uni(BID), bi = bid >> 4, rh = bid & 1, bc = (bid & 15) >> 1;
  const bool one = (threadIdx.x & 31) == 0;
  char* const g = (char*)P.g;
  #pragma unroll 1
  for (int L = 0; L < 2; L++) {
    mbar_wait(BAR(B_PAR), L);
    const uint32_t tag = lds32(sb + INFO + 8) + L;
    if (wg) { mbar_wait(BAR(B_KVRDY), L); mbar_wait(BAR(B_KVRDY + 2), L); const uint32_t t0 = clk(); while (clk() - t0 < KV_D) __nanosleep(40); }
    #pragma unroll 1
    for (int u = 0; u < 2 + 4 * wg; u++) {
      const int h = u < 2 ? u : u >> 2, hi = (u & 1) ^ 1;
      uint32_t src, dst, fl, b0, b1;
      if (u < 2) {
        src = (h ? KVB : KVA) + (3 - wg) * 16384; dst = offsetof(Scratch, kv) + (bid * 4 + h * 2 + wg) * 16384; fl = offsetof(Scratch, flagKV) + (bid * 32 + h * 2 + wg) * 4;
        b0 = BAR(B_KVRDY + ((u | wg) ? 1 : 0)); b1 = b0 + 16;
      } else {
        src = QO + (h * 2 + hi) * 8192; dst = offsetof(Scratch, o) + ((((bi * 2 + h) * 8 + bc) * 2 + hi) * 2 + rh) * 8192;
        fl = offsetof(Scratch, flagO) + (bi * 32 + h * 16 + (bid & 15)) * 4;
        b0 = BAR(B_ORDY + u - 2); b1 = b0 + 32;
      }
      mbar_wait(b0, L); mbar_wait(b1, L);
      fence_async_smem();
      PROFY(one && !L && u == 3 * wg, u ? 46 : 8);
      if (one && (u >= 2 || bi < 7)) bulk_s2g(g + dst, sb + src, u < 2 ? 16384 : 8192);
      if (one && u == 5) mbar_arrive(BAR(B_HAFREE + 1));
      if (u == 2 || u == 4) continue;
      bulk_wait<0>();
      PROFY(one && !L && u == 3 * wg, u ? 61 : 62);
      fence_rel();
      if (one) { st_rlx((unsigned*)(g + fl), tag); if (!wg || u > 2) mbar_arrive(BAR(B_HAFREE + h + (wg & h))); }
      PROFY(one && !L && (u > 2 || u == wg), u > 2 ? (u == 3 ? 38 : 54) : 32 + u);
    }
    if (L == 0) {
      char* dst = g + (offsetof(Scratch, x) + (bi * 16 + 2 * bc) * 32768 + rh * 16384);
      unsigned* f = (unsigned*)(g + (offsetof(Scratch, flagX) + (bi * 32 + bc * 4 + rh) * 4));
      const uint32_t a = sb + rh * 16384;
      if (wg == 0) {
        mbar_wait(BAR(B_XRDY), 0); mbar_wait(BAR(B_XRDY + 2), 0);
        fence_async_smem();
        PROFY(one, 41);
        if (one) bulk_s2g(dst, a, 16384);
        bulk_wait<0>();
        PROFY(one, 45);
        if (one) { mbar_arrive(BAR(B_XFREE)); mbar_arrive(BAR(B_PFREE)); }
        fence_rel();
        mbar_wait(BAR(B_XRDY + 1), 0); mbar_wait(BAR(B_XRDY + 3), 0);
        if (one) { st_rlx(f, tag); bulk_s2g(dst + 32768, a + 32768, 16384); }
        PROFY(one, 56);
        bulk_wait<0>();
        if (one) mbar_arrive(BAR(B_XFREE + 1));
        fence_rel();
        if (one) st_rlx(f + 2, tag);
        PROFY(one, 57);
      } else {
        mbar_wait(BAR(B_XRDY + 1), 0); mbar_wait(BAR(B_XRDY + 3), 0);
        mbar_wait(BAR(B_PFREE), 0);
        if (one) bulk_s2peer(a, 16384, BAR(B_FULLQ));
        { const uint32_t t0 = clk(); while (clk() - t0 < XD_D); }
        if (one) bulk_s2peer(a + 32768, 16384, BAR(B_FULLQ + 1));
      }
      if (wg == 0) {
        uint32_t t0 = clk() + PF1_D;
        #pragma unroll 1
        for (int q = PF1_S; q < PF1_E; q++) { while ((int)(clk() - t0) < 0) __nanosleep(50); if (one) ffn_prefetch(P, q); t0 += PF1_T; }
      }
    }
  }
}

DEVI void stg_issue(const Params& P, int c, uint32_t d, uint32_t du, uint32_t b) {
  mbar_expect_tx(b, 16384);
  if (c < 8) { tma_2d_h(d, &P.mWg, FID * 32, c * 128, b, POL_G); tma_2d_h(d + du, &P.mWu, FID * 32, c * 128, b, POL_U); }
  else if (c < 12) tma_3d_h(d, &P.mWd, 0, FID * 32 + (c - 8) * 8, 0, b, POL_D);
  else tma_2d_h(d, &P.mWp, FID * 32, (c - 12) * 256, b, POL_EF);
}
DEVI void stager(const Params& P, uint32_t sb) {
  {
    const int b = blockIdx.x;
    uint32_t t0 = clk();
    #pragma unroll 1
    for (int q = 0; q < PQ_N; q++) { bulk_prefetch(P.wqkv + (q * 128 + b) * 3072, 6144); while (clk() - t0 < PQ_T); t0 += PQ_T; }
    bulk_prefetch(P.wo + b * 8192, 16384);
    #pragma unroll 1
    for (int q = 0; q < PF0_N; q++) {
      while (clk() - t0 < PF0_T);
      t0 += PF0_T;
      ffn_prefetch(P, q);
    }
  }
  const int bid = BID, bi = bid >> 4, rh = bid & 1, bc = (bid & 15) >> 1;
  #pragma unroll 1
  for (int L = 0; L < 2; L++) {
    const int nch = FID >= 112 ? 0 : (L ? 8 : (FID < 96 ? 16 : 12));
    mbar_wait(BAR(B_KVFULL + W0_BAR), L);
    #pragma unroll 1
    for (int n = 0, q = 0; n < 16; q = w_next(n, q), n++) {
      if (n >= 2) mbar_wait(n < 6 ? BAR(B_HAFREE + (n >> 2)) : BAR(B_EMPTYW + q), n < 6 ? L : w_par(n - 6, q, L));
      if (n == THR_N) mbar_wait(BAR(B_OFREE), L);
      mbar_expect_tx(BAR(B_FULLW + q), 16384);
      tma_5d(sb + w_off(q) + 16384, &P.mWo, 0, 0, n >> 3, 2 * (wo_order(bc, n) & 7), 2 * bc, BAR(B_FULLW + q), L ? POL_EF : POL_NORMAL);
      if (n == 13) {
        mbar_expect_tx(BAR(B_RES), 32768);
        #pragma unroll 1
        for (int e = 0; e < 2; e++) {
          mbar_wait(BAR(B_EMPTYW + 2 + e), 1);
          if (L) bulk_g2s_h(sb + e * 32768 + rh * 16384, P.g->x[bi][2 * bc + e] + rh * 1024, 16384, BAR(B_RES));
          else tma_2d_h(sb + e * 32768 + rh * 16384, &P.mXh, bc * 128 + e * 64, bi * 256 + rh * 128, BAR(B_RES), POL_EF);
        }
      }
    }
    if (L == 0) { mbar_arrive_peer(BAR(B_PFREE)); mbar_wait(BAR(B_EMPTYW), 0); mbar_wait(BAR(B_EMPTYW + 1), 0); }
    #pragma unroll 1
    for (int c = 0, slot = 0; c < nch; c++, slot = slot == 2 ? 0 : slot + 1) {
      const int q = (c >> 1) + (c & 4) / 2;
      mbar_wait(L ? BAR(B_EMPTYW + q) : BAR(B_STGE + slot), L | ((0x71c7 >> c) & 1));
      stg_issue(P, c, L ? sb + w_off(q) + (c & 1) * 8192 : sb + STG + slot * 16384, 8192 << L, L ? BAR(B_FULLW + q) : BAR(B_STG + slot));
    }
  }
}
DEVI void sum8(uint4 v, float& s1, float& s2) {
  float e[8] = {bf_lo(v.x), bf_hi(v.x), bf_lo(v.y), bf_hi(v.y), bf_lo(v.z), bf_hi(v.z), bf_lo(v.w), bf_hi(v.w)};
  #pragma unroll
  for (int q = 0; q < 8; q++) { s1 += e[q]; s2 = fmaf(e[q], e[q], s2); }
}
DEVI uint4 norm8(uint4 x, float m, float rs, uint32_t d, uint32_t d2) {
  #define HN(v) pack_bf16((bf_lo(v) - m) * rs, (bf_hi(v) - m) * rs)
  uint4 b = make_uint4(HN(x.x), HN(x.y), HN(x.z), HN(x.w));
  #undef HN
  sts128(d, make_uint4(b.x << 16, b.x & 0xffff0000u, b.y << 16, b.y & 0xffff0000u));
  sts128(d + d2, make_uint4(b.z << 16, b.z & 0xffff0000u, b.w << 16, b.w & 0xffff0000u));
  return b;
}
DEVI uint4 best4(uint32_t p) {
  uint4 a = lds128(p), b = lds128(p + 16), c = lds128(p + 32), d = lds128(p + 48);
  if (b.x > a.x) a = b;
  if (d.x > c.x) c = d;
  return c.x > a.x ? c : a;
}
#define FL(x) __uint_as_float(x)
#define UI(x) __float_as_uint(x)
DEVI void qkv_params(const Params& P, uint32_t sb, int row, uint32_t tag, bool second) {
  uint4 v0, v1; poll_ll2(&P.g->statF[row], &P.g->statF[row + 128], 0xffffffffu, tag, v0, v1);
  #pragma unroll 1
  for (int q = 0; q < 2; q++) {
    float var = FL(v0.y), c = rsqrtf(var + LN_EPS);
    if (second) { c += 1.f; c *= rsqrtf(fmaf(var * c, c, LN_EPS)); }
    const float mh = bf_round(FL(v0.x));
    sts64f(sb + PAR + q * 1024 + (row & 127) * 8, c, FL(pack_bf16(mh, FL(v0.x) - mh)));
    v0 = v1;
  }
  warp_signal(BAR(B_ROW));
}
DEVI void aux(const Params& P, uint32_t sb) {
  int tid = fresh_tid();
  #define lane (tid & 31)
  #define wq (tid >> 5)
  uint32_t ids = P.map[blockIdx.x], tag;
  #define bid ((int)(ids & 255))
  #define fid ((int)(ids >> 8))
  #define bi (bid >> 4)
  #define bp (bid & 15)
  #define bc (bp >> 1)
  #define FRESH() do { tid = fresh_tid(); uint4 z_ = ldsv128(sb + INFO2 + 16); ids = z_.y; tag = z_.z + L; idx = z_.w; } while (0)
  {
    const uint32_t epoch = ld_rlx(&P.g->epoch);
    if (tid == 0) {
      mbar_expect_tx(BAR(B_STG), 49152);
      tma_3d(sb + STG, &P.mWq, bp * 64, bi * 128, 0, BAR(B_STG));
      tma_3d(sb + STG + 24576, &P.mWq, bp * 64, bi * 128 + 64, 0, BAR(B_STG));
    }
    __syncwarp();
    sts64f(sb + ONES + tid * 8, FL(0x3F803F80u), FL(0x3F803F80u));
    float s1 = 0.f, s2 = 0.f;
    { uint4 v = __ldg((const uint4*)P.wr + tid);
      if ((tid >> 4) == bc) norm8(v, 0.f, 1.f, sb + WR + (tid & 15) * 32, 16);
      sum8(v, s1, s2);
      #pragma unroll 1
      for (int o = 16; o; o >>= 1) s1 += __shfl_xor_sync(0xffffffffu, s1, o);
      sts32f(sb + INFO2 + wq * 4, s1); }
    const uint4* src = (const uint4*)(P.x0 + (size_t)bid * 16384) + (tid >> 3) * 128 + (tid & 7);
    s1 = 0.f; s2 = 0.f;
    #pragma unroll 1
    for (int it = 0; it < 16; it += 4) {
      uint4 v0 = __ldg(src + it * 8), v1 = __ldg(src + it * 8 + 8), v2 = __ldg(src + it * 8 + 16), v3 = __ldg(src + it * 8 + 24);
      #pragma unroll 1
      for (int q = 0; q < 4; q++) { sum8(v0, s1, s2); v0 = v1; v1 = v2; v2 = v3; }
    }
    #pragma unroll 1
    for (int o = 1; o < 8; o <<= 1) { s1 += __shfl_xor_sync(0xffffffffu, s1, o); s2 += __shfl_xor_sync(0xffffffffu, s2, o); }
    tag = ((epoch % 16383u) + 1u) << 2;
    if (tid == 0) { sts128(sb + INFO, make_uint4(0x40000000u, 0u, tag, ((epoch % 127u) + 1u) << 1)); sts128(sb + INFO2 + 16, make_uint4(epoch, ids, tag, 0x40000000u)); }
    float m = s1 * (1.f / 1024.f);
    if ((tid & 7) == 0) st_ll(&P.g->statF[bid * 16 + (tid >> 3)], UI(m), UI(fmaxf(fmaf(-m, m, s2 * (1.f / 1024.f)), 0.f)), 0u, tag);
    bar_sync(2, 128);
    mbar_wait_b(BAR(B_STG), 0);
    if (tid < 96) {
      s1 = 0.f; s2 = 0.f;
      #pragma unroll 4
      for (int r = 0; r < 128; r++) {
        uint32_t v = lds32(sb + STG + (r >> 6) * 24576 + wq * 8192 + (r & 63) * 128 + ((lane * 4) ^ ((r & 7) << 4)));
        s1 += bf_lo(v); s2 += bf_hi(v);
      }
      st_ll(&P.g->csP[bp][bi][tid], UI(s1), UI(s2), 0u, tag);
      s1 = 0.f; s2 = 0.f;
      #pragma unroll 1
      for (int q = 0; q < 8; q += 2) {
        uint4 a, b; poll_ll2(&P.g->csP[bp][q][tid], &P.g->csP[bp][q + 1][tid], 0xffffffffu, tag, a, b);
        s1 += FL(a.x) + FL(b.x); s2 += FL(a.y) + FL(b.y);
      }
      const uint32_t hi = pack_bf16(-s1, -s2);
      sts32(sb + CS + (tid >> 2) * 32 + (tid & 3) * 4, hi);
      sts32(sb + CS + (tid >> 2) * 32 + (tid & 3) * 4 + 16, pack_bf16(-s1 - bf_lo(hi), -s2 - bf_hi(hi)));
    }
    fence_async_smem();
    qkv_params(P, sb, bi * 256 + tid, tag, false);
  }
  int idx;
  #pragma unroll 1
  for (int L = 0; L < 2; L++) {
    FRESH();
    {
      if ((idx >> 8) == bi && wq < 3) {
        uint4 v = poll_ll(&P.g->patch[wq * 256 + bp * 16 + (lane & 15)], 0xffffffffu, tag);
        sts64f(sb + PATCH + (wq * 16 + (lane & 15)) * 8, FL(v.x), FL(v.y));
      }
      sts32(sb + INFO, idx);
      bar_sync(2, 128);
      if (tid == 0) mbar_arrive(BAR(B_PAR));
      PROFX(tid == 0, L ? 23 : 17);
    }
    mbar_wait_b(BAR(B_KVFULL + wq), L);
    bar_arrive(4 + wq, 160); bar_arrive(8 + wq, 160);
    FRESH();
    mbar_wait_b(BAR(B_OFREE), L);
    #define blk (bi * 2 + (bid & 1))
    if (tid < 33) st_ll(tid < 32 ? &P.g->row[blk][bc * 32 + tid] : &P.g->best[bc][blk], 0u, 0u, 0u, 0u);
    mbar_wait_b(BAR(B_XRDY + 1), L); mbar_wait_b(BAR(B_XRDY + 3), L);
    PROFX(tid == 0, 37 + L * 16);
    FRESH();
    {
      float s1 = 0.f, s2 = 0.f, d = 0.f;
      #pragma unroll 1
      for (int q = 0; q < 8; q += 4) {
        const uint4* src = &P.g->statP[q][blk * 128 + tid];
        uint4 v0, v1, v2, v3; int it = 0;
        do { v0 = ld_ll(src); v1 = ld_ll(src + 2048); v2 = ld_ll(src + 4096); v3 = ld_ll(src + 6144); if (++it > SPIN_MAX) __trap(); }
        while (!__all_sync(0xffffffffu, v0.w == tag && v1.w == tag && v2.w == tag && v3.w == tag));
        s1 += (FL(v0.x) + FL(v1.x)) + (FL(v2.x) + FL(v3.x)); s2 += (FL(v0.y) + FL(v1.y)) + (FL(v2.y) + FL(v3.y)); d += (FL(v0.z) + FL(v1.z)) + (FL(v2.z) + FL(v3.z));
      }
      PROFX(tid == 0, 39 + L * 16);
      uint4 a = lds128(sb + INFO2), b, c;
      float m = s1 * (1.f / 1024.f), var = fmaxf(fmaf(-m, m, s2 * (1.f / 1024.f)), 0.f), rs = rsqrtf(var + LN_EPS);
      uint32_t key = UI(fmaf(-m, (FL(a.x) + FL(a.y)) + (FL(a.z) + FL(a.w)), d) * rs);
      key ^= (uint32_t)((int)key >> 31) | 0x80000000u;
      uint32_t win = __ballot_sync(0xffffffffu, key == __reduce_max_sync(0xffffffffu, key));
      if (lane == __ffs(win) - 1) sts128(sb + RED + wq * 16, make_uint4(key, UI(m), UI(rs), (tag << 11) | (uint32_t)(blk * 128 + tid)));
      if (L) sts64f(sb + PAR + tid * 8, 1.f + rs, -m * rs);
      else if ((tid >> 4) == bc) st_ll(&P.g->statF[blk * 128 + tid], UI(m), UI(var), 0u, tag + 1);
      bar_sync(2, 128);
      if (wq == 0) {
        a = best4(sb + RED);
        float2 v = lds64f(sb + (lane >> 4) * 32768 + (a.w & 255) * 128 + (((lane & 15) * 8) ^ ((a.w & 7) << 4)));
        st_ll(&P.g->row[blk][bc * 32 + lane], UI(v.x), UI(v.y), 0u, tag);
        if (lane == 0) { st_ll(&P.g->best[bc][blk], a.x, a.y, a.z, a.w); sts32(sb + INFO + 4, a.w & 2047); }
        __syncwarp();
        if (L) {
          const float al = 1.f + FL(a.z), be = -FL(a.y) * FL(a.z);
          sts64f(sb + RED + 1792 + lane * 8, FL(pack_bf16(fmaf(bf_lo(UI(v.x)), al, be), fmaf(bf_hi(UI(v.x)), al, be))),
                                             FL(pack_bf16(fmaf(bf_lo(UI(v.y)), al, be), fmaf(bf_hi(UI(v.y)), al, be))));
        }
        if (lane < 2 - L) mbar_arrive(L ? BAR(B_PAR) : BAR(B_XFREE + lane));
      }
      PROFX(tid == 0, 18 + L * 6);
      FRESH();
      a = poll_ll(&P.g->best[bc][lane & 15], 0xfffff800u, tag << 11);
      win = __ffs(__ballot_sync(0xffffffffu, a.x == __reduce_max_sync(0xffffffffu, a.x))) - 1;
      idx = __shfl_sync(0xffffffffu, a.w, win) & 2047;
      PROFX(tid == 0, 19 + L * 6);
      poll_ll2(&P.g->row[win][tid], &P.g->row[win][tid + 128], 0xffffffffu, tag, c, b);
      c.z = b.x; c.w = b.y;
      a.x = __shfl_sync(0xffffffffu, a.x, win); a.y = __shfl_sync(0xffffffffu, a.y, win); a.z = __shfl_sync(0xffffffffu, a.z, win);
      sts32(sb + INFO2 + 28, idx);
      PROFX(tid == 0, 61 + L);
      b = norm8(c, FL(a.y), FL(a.z), sb + HV + tid * 16, 2048);
      if (L && fid < 112) bar_arrive(3, 384);
      if ((tid >> 1) == (bid & 63)) {
        sts128(sb + RED + 64 + (tid & 1) * 16, bid < 64 ? make_uint4(c.x, c.y, b.x, b.y) : make_uint4(c.z, c.w, b.z, b.w));
        sts32(sb + RED + 96, a.x);
      }
      if (L && wq == 0 && win != blk) *(float2*)(P.out + (size_t)lds32(sb + INFO + 4) * 1024 + bc * 128 + lane * 4) = lds64f(sb + RED + 1792 + lane * 8);
      bar_sync(2, 128);
    }
    #pragma unroll 1
    for (int st = L; st < 3; st++) {
      FRESH();
      float a[8] = {0.f, 0.f, 0.f, 0.f, 0.f, 0.f, 0.f, 0.f};
      if (L == 0 && fid < (st == 2 ? 96 : 112)) {
        uint32_t ha = st == 1 ? sb + RED + 768 : sb + HV + ((st ? wq : wq & 1) * 64 + (lane >> 2)) * 4;
        uint32_t ph = (st ? (st == 1 ? 0x1cu : 0x11u) : 0x171u), bar = st == 1 ? BAR(B_STG + 2) : BAR(B_STG);
        uint32_t wa = sb + STG + tid * 16 + wq * 3584 + (st == 1 ? 32768 : 0);
        const uint32_t hx = st == 1 ? 256 : (st ? 1024 : 512);
        const bool lead = lane == 0;
        #pragma unroll 1
        do {
          mbar_wait(bar, ph & 1);
          PROFX(lead && threadIdx.x == 256 && st == 0 && (ph > 255 || ph < 4), 40 - 23 + __clz(ph));
          gemv8(a, wa, ha, 32);
          __syncwarp();
          if (lead) mbar_arrive(bar - 8 * (B_STG - B_STGE));
          const bool wrap = bar == BAR(B_STG + 2);
          bar += wrap ? -16 : 8; wa += wrap ? -32768 : 16384; ha += hx;
          ph >>= 1;
        } while (ph != 1);
      }
      FRESH();
      if (st == 1) {
        const uint32_t t8 = lds32(sb + INFO + 12) + L;
        if (L == 0 && fid < 112) {
          const bool odd = lane & 1;
          #pragma unroll
          for (int e = 0; e < 4; e++) { float z = __shfl_xor_sync(0xffffffffu, odd ? a[e] : a[4 + e], 1); if (odd) a[e] = z; else a[4 + e] = z; }
          uint4* dst = &P.g->yP[tid & ~1][fid][tid & 1];
          st_ll(dst, UI(a[0]), UI(a[1]), UI(a[2]), (UI(a[3]) & ~255u) | t8);
          st_ll(dst + 224, UI(a[4]), UI(a[5]), UI(a[6]), (UI(a[7]) & ~255u) | t8);
          PROFX(tid == 0, 21);
        }
        if (!L) qkv_params(P, sb, bi * 256 + tid, tag + 1, true);
        if (tid == 0) { uint32_t k = lds32(sb + RED + 96); sts32f(sb + RED + 100, bf_round(__fdividef(1.f, 1.f + __expf(-bf_round(FL(k ^ (~(uint32_t)((int)k >> 31) | 0x80000000u))))))); }
        uint4 v0, v1;
        poll_ll2(&P.g->yP[bid][0][min(tid, 111)], &P.g->yP[bid][0][min(tid, 111) + 112], 255u, t8, v0, v1);
        const float lo = (tid < 112 && !(tid & 1)) ? 1.f : 0.f, hi = (tid < 112 && (tid & 1)) ? 1.f : 0.f;
        const float y0 = FL(v0.x) + FL(v1.x), y1 = FL(v0.y) + FL(v1.y), y2 = FL(v0.z) + FL(v1.z), y3 = FL((v0.w & ~255u) | 128u) + FL((v1.w & ~255u) | 128u);
        a[0] = y0 * lo; a[1] = y1 * lo; a[2] = y2 * lo; a[3] = y3 * lo; a[4] = y0 * hi; a[5] = y1 * hi; a[6] = y2 * hi; a[7] = y3 * hi;
      }
      sts32f(sb + RED + 256 + wq * 128 + ((lane & 3) * 8 + (lane >> 2)) * 4, fold8(a));
      bar_sync(2, 128);
      const uint32_t d = sb + RED + 256 + lane * 4;
      float z0 = lds32f(d) + lds32f(d + 128), z1 = lds32f(d + 256) + lds32f(d + 384);
      if (st == 0) {
        sts32f(sb + RED + 768 + lane * 32 + wq * 4, swiglu(z0, z1));
        if (fid < 112) { st_ll(&P.g->yP[tid & ~1][fid][tid & 1], 0u, 0u, 0u, 0u); st_ll(&P.g->yP[tid | 1][fid][tid & 1], 0u, 0u, 0u, 0u); }
        if (tid < 24) st_ll(tid < 16 ? &P.g->x2[tid >> 1][2 * bid + (tid & 1)] : &P.g->patch[fid * 8 + tid - 16], 0u, 0u, 0u, 0u);
        bar_sync(2, 128); PROFX(tid == 0, 20); continue; }
      z0 += z1;
      if (st == 1) {
        z0 += __shfl_xor_sync(0xffffffffu, z0, 8); z0 += __shfl_xor_sync(0xffffffffu, z0, 16);
        uint32_t xw = lds32(sb + RED + 64 + (lane & 4) * 4 + (lane & 2) * 2), hw = lds32(sb + RED + 72 + (lane & 4) * 4 + (lane & 2) * 2);
        z0 = bf_round(((lane & 1) ? bf_hi(hw) : bf_lo(hw)) + bf_round(bf_round(z0) * lds32f(sb + RED + 100))) + ((lane & 1) ? bf_hi(xw) : bf_lo(xw));
      } else if (fid < 32) z0 *= QSCALE;
      uint32_t v = pack_bf16(z0, __shfl_down_sync(0xffffffffu, z0, 1)), v2 = __shfl_down_sync(0xffffffffu, v, 2);
      if (L) { if (tid == 0 || tid == 4) *(uint2*)(P.out + (size_t)idx * 1024 + bid * 8 + tid) = make_uint2(v, v2); PROFW(tid == 0, 28); break; }
      if ((tid & 3) == 0 && tid < (st == 1 ? 64 : 32)) st_ll(st == 1 ? &P.g->x2[tid >> 3][2 * bid + ((tid >> 2) & 1)] : &P.g->patch[fid * 8 + (tid >> 2)], v, v2, 0u, tag + 1);
      PROFX(tid == 0, st == 1 ? 22 : 31);
      if (st == 1) {
        uint4 x, y; poll_ll2(&P.g->x2[bi][tid], &P.g->x2[bi][tid + 128], 0xffffffffu, tag + 1, x, y);
        x.z = y.x; x.w = y.y;
        if (wq == (bc & 3)) sts64f(sb + X2SEG + lane * 8, FL(bc < 4 ? x.x : x.z), FL(bc < 4 ? x.y : x.w));
        float s1 = 0.f, s2 = 0.f;
        sum8(x, s1, s2);
        #pragma unroll
        for (int o = 16; o; o >>= 1) { s1 += __shfl_xor_sync(0xffffffffu, s1, o); s2 += __shfl_xor_sync(0xffffffffu, s2, o); }
        sts64f(sb + RED + wq * 8, s1, s2);
        bar_sync(2, 128);
        y = lds128(sb + RED); uint4 y2 = lds128(sb + RED + 16);
        float m = ((FL(y.x) + FL(y.z)) + (FL(y2.x) + FL(y2.z))) * (1.f / 1024.f);
        norm8(x, m, rsqrtf(fmaxf(fmaf(-m, m, ((FL(y.y) + FL(y.w)) + (FL(y2.y) + FL(y2.w))) * (1.f / 1024.f)), 0.f) + LN_EPS), sb + HV + tid * 16, 2048);
        bar_sync(2, 128);
        PROFX(tid == 0, 30);
      }
    }
  }
  if (bid == 0 && tid == 0) P.g->epoch = lds32(sb + INFO2 + 16) + 1;
  #undef blk
  #undef bid
  #undef fid
  #undef bi
  #undef bp
  #undef bc
  #undef FRESH
  #undef lane
  #undef wq
}

__global__ void __cluster_dims__(2, 1, 1) __launch_bounds__(512, 1) fused_kernel(const __grid_constant__ Params P) {
  extern __shared__ __align__(1024) uint8_t smem_raw[];
  const uint32_t sb = smem_u32(smem_raw);
  PROFT(threadIdx.x == 0, 0);
  if (threadIdx.x == 0) {
    for (int s = 0; s < 3; s++) mbar_init(BAR(B_FULLQ + s), 1);
    asm volatile("fence.mbarrier_init.release.cluster;" ::: "memory");
    #pragma unroll 1
    for (int s = 0; s < 3; s++) {
      mbar_expect_tx(BAR(B_FULLQ + s), 57344);
      tma_2d(sb + qa_off(s), &P.mX, s * 64, (BID >> 4) * 256, BAR(B_FULLQ + s));
      tma_3d(sb + qb_off(s), &P.mWq, (BID & 15) * 64, s * 64, 0, BAR(B_FULLQ + s));
    }
    if ((sb & 0x3FFFFu) != 1024) __trap();
  } else if (threadIdx.x >= 32 + B_EMPTYQ && threadIdx.x <= 32 + B_COUNT) {
    const int b = threadIdx.x == 32 + B_COUNT ? B_ROW : threadIdx.x - 32;
    const uint32_t cnt = b < B_XFREE ? (b == B_OFREE ? 1 : 2) : (b < B_KVRDY ? 3 : (b < B_KVFULL || b == B_ROW ? 4 : (b == B_PFREE ? 2 : 1)));
    mbar_init(BAR(b), cnt);
    asm volatile("fence.mbarrier_init.release.cluster;" ::: "memory");
  }
  __syncthreads();
  asm volatile("barrier.cluster.arrive.relaxed.aligned;" ::: "memory");
  const int wg = __shfl_sync(0xffffffffu, threadIdx.x >> 7, 0);
  if (wg < 2) { reg_inc<224>(); consumer(P, sb, wg); }
  else if (wg == 2) { reg_dec<40>(); aux(P, sb); }
  else {
    reg_dec<24>();
    asm volatile("barrier.cluster.wait.aligned;" ::: "memory");
    const int w = __shfl_sync(0xffffffffu, (threadIdx.x >> 5) & 3, 0);
    if (w == 0) loader(P, sb);
    else if (w < 3) storer(P, sb, w - 1);
    else if ((threadIdx.x & 31) == 0) stager(P, sb);
  }
}

typedef CUresult (*EncFn)(CUtensorMap*, CUtensorMapDataType, cuuint32_t, void*, const cuuint64_t*, const cuuint64_t*, const cuuint32_t*, const cuuint32_t*,
                          CUtensorMapInterleave, CUtensorMapSwizzle, CUtensorMapL2promotion, CUtensorMapFloatOOBfill);
static void mk_map(EncFn enc, CUtensorMap* m, const void* ptr, int rank, const cuuint64_t* dims, const cuuint64_t* strides, const cuuint32_t* box,
                   CUtensorMapSwizzle sw, CUtensorMapL2promotion pr) {
  cuuint32_t es[5] = {1, 1, 1, 1, 1};
  enc(m, CU_TENSOR_MAP_DATA_TYPE_BFLOAT16, rank, (void*)ptr, dims, strides, box, es, CU_TENSOR_MAP_INTERLEAVE_NONE, sw, pr, CU_TENSOR_MAP_FLOAT_OOB_FILL_NONE);
}
extern "C" void kernel_launch(void* const* d_in, const int* in_sizes, int n_in, void* d_out, int out_size) {
  (void)in_sizes; (void)n_in; (void)out_size;
  void* fn = nullptr; cudaDriverEntryPointQueryResult q;
  cudaGetDriverEntryPoint("cuTensorMapEncodeTiled", &fn, cudaEnableDefault, &q);
  EncFn enc = (EncFn)fn;
  cudaFuncSetAttribute(fused_kernel, cudaFuncAttributeMaxDynamicSharedMemorySize, SMEM_BYTES);
  Params P;
  const CUtensorMapSwizzle S128 = CU_TENSOR_MAP_SWIZZLE_128B, S0 = CU_TENSOR_MAP_SWIZZLE_NONE;
  const CUtensorMapL2promotion L256 = CU_TENSOR_MAP_L2_PROMOTION_L2_256B, L128 = CU_TENSOR_MAP_L2_PROMOTION_L2_128B;
  { cuuint64_t d[2] = {1024, 2048}, s[1] = {2048}; cuuint32_t b[2] = {64, 256}, bh[2] = {64, 128};
    mk_map(enc, &P.mX, d_in[0], 2, d, s, b, S128, L256); mk_map(enc, &P.mXh, d_in[0], 2, d, s, bh, S128, L256); }
  { cuuint64_t d[3] = {1024, 1024, 3}, s[2] = {6144, 2048}; cuuint32_t b[3] = {64, 64, 3}; mk_map(enc, &P.mWq, d_in[1], 3, d, s, b, S128, L256); }
  { cuuint64_t d[5] = {64, 32, 2, 16, 16}, s[4] = {2048, 65536, 131072, 128}; cuuint32_t b[5] = {64, 32, 1, 2, 2}; mk_map(enc, &P.mWo, d_in[2], 5, d, s, b, S128, L256); }
  { cuuint64_t d[2] = {3584, 1024}, s[1] = {7168}; cuuint32_t b[2] = {32, 128};
    mk_map(enc, &P.mWg, d_in[5], 2, d, s, b, S0, L128); mk_map(enc, &P.mWu, d_in[6], 2, d, s, b, S0, L128); }
  { cuuint64_t d[2] = {3072, 1024}, s[1] = {6144}; cuuint32_t b[2] = {32, 256}; mk_map(enc, &P.mWp, d_in[1], 2, d, s, b, S0, L128); }
  { cuuint64_t d[3] = {256, 3584, 4}, s[2] = {2048, 512}; cuuint32_t b[3] = {256, 8, 4}; mk_map(enc, &P.mWd, d_in[7], 3, d, s, b, S0, L128); }
  P.x0 = (const bf16*)d_in[0]; P.wqkv = (const bf16*)d_in[1]; P.wo = (const bf16*)d_in[2]; P.wr = (const bf16*)d_in[4]; P.wg = (const bf16*)d_in[5]; P.wu = (const bf16*)d_in[6]; P.wd = (const bf16*)d_in[7];
  P.out = (bf16*)d_out;
  cudaGetSymbolAddress((void**)&P.g, g_scr);
  for (int b = 0; b < 128; b++) {
    int j = b >> 1, quad = j < 4 ? 0 : (j < 36 ? 1 + (j - 4) % 8 : 9 + (j - 36) % 7), pos = j < 4 ? j : (j < 36 ? (j - 4) / 8 : (j - 36) / 7);
    int bid = ((quad >> 2) * 2 + (pos >> 1)) * 16 + ((quad & 3) * 2 + (pos & 1)) * 2 + (b & 1);
    int e = pos * 2 + (b & 1), fid = e < 6 ? quad * 6 + e : e * 16 + quad;
    P.map[b] = bid | fid << 8;
  }
  fused_kernel<<<128, 512, SMEM_BYTES>>>(P);
}
```

```cpp
#include <cuda_runtime.h>
#include <cuda_bf16.h>
#include <cuda.h>
#include <stdint.h>
#include <stddef.h>
typedef __nv_bfloat16 bf16;

template<int TB, int TA = 0> __device__ __forceinline__ void wgmma_ss_n192(float (&d)[96], uint64_t da, uint64_t db, int scale_d) {
  asm volatile("{\n.reg .pred p;\nsetp.ne.b32 p, %98, 0;\n"
    "wgmma.mma_async.sync.aligned.m64n192k16.f32.bf16.bf16 {%0, %1, %2, %3, %4, %5, %6, %7, %8, %9, %10, %11, %12, %13, %14, %15, %16, %17, %18, %19, %20, %21, %22, %23, %24, %25, %26, %27, %28, %29, %30, %31, %32, %33, %34, %35, %36, %37, %38, %39, %40, %41, %42, %43, %44, %45, %46, %47, %48, %49, %50, %51, %52, %53, %54, %55, %56, %57, %58, %59, %60, %61, %62, %63, %64, %65, %66, %67, %68, %69, %70, %71, %72, %73, %74, %75, %76, %77, %78, %79, %80, %81, %82, %83, %84, %85, %86, %87, %88, %89, %90, %91, %92, %93, %94, %95}, %96, %97, p, 1, 1, %100, %99;\n}\n"
    : "+f"(d[0]), "+f"(d[1]), "+f"(d[2]), "+f"(d[3]), "+f"(d[4]), "+f"(d[5]), "+f"(d[6]), "+f"(d[7]), "+f"(d[8]), "+f"(d[9]), "+f"(d[10]), "+f"(d[11]), "+f"(d[12]), "+f"(d[13]), "+f"(d[14]), "+f"(d[15]), "+f"(d[16]), "+f"(d[17]), "+f"(d[18]), "+f"(d[19]), "+f"(d[20]), "+f"(d[21]), "+f"(d[22]), "+f"(d[23]), "+f"(d[24]), "+f"(d[25]), "+f"(d[26]), "+f"(d[27]), "+f"(d[28]), "+f"(d[29]), "+f"(d[30]), "+f"(d[31]), "+f"(d[32]), "+f"(d[33]), "+f"(d[34]), "+f"(d[35]), "+f"(d[36]), "+f"(d[37]), "+f"(d[38]), "+f"(d[39]), "+f"(d[40]), "+f"(d[41]), "+f"(d[42]), "+f"(d[43]), "+f"(d[44]), "+f"(d[45]), "+f"(d[46]), "+f"(d[47]), "+f"(d[48]), "+f"(d[49]), "+f"(d[50]), "+f"(d[51]), "+f"(d[52]), "+f"(d[53]), "+f"(d[54]), "+f"(d[55]), "+f"(d[56]), "+f"(d[57]), "+f"(d[58]), "+f"(d[59]), "+f"(d[60]), "+f"(d[61]), "+f"(d[62]), "+f"(d[63]), "+f"(d[64]), "+f"(d[65]), "+f"(d[66]), "+f"(d[67]), "+f"(d[68]), "+f"(d[69]), "+f"(d[70]), "+f"(d[71]), "+f"(d[72]), "+f"(d[73]), "+f"(d[74]), "+f"(d[75]), "+f"(d[76]), "+f"(d[77]), "+f"(d[78]), "+f"(d[79]), "+f"(d[80]), "+f"(d[81]), "+f"(d[82]), "+f"(d[83]), "+f"(d[84]), "+f"(d[85]), "+f"(d[86]), "+f"(d[87]), "+f"(d[88]), "+f"(d[89]), "+f"(d[90]), "+f"(d[91]), "+f"(d[92]), "+f"(d[93]), "+f"(d[94]), "+f"(d[95])
    : "l"(da), "l"(db), "r"(scale_d), "n"(TB), "n"(TA));
}

template<int TB> __device__ __forceinline__ void wgmma_rs_n192(float (&d)[96], uint32_t a0, uint32_t a1, uint32_t a2, uint32_t a3, uint64_t db, int scale_d) {
  asm volatile("{\n.reg .pred p;\nsetp.ne.b32 p, %101, 0;\n"
    "wgmma.mma_async.sync.aligned.m64n192k16.f32.bf16.bf16 {%0, %1, %2, %3, %4, %5, %6, %7, %8, %9, %10, %11, %12, %13, %14, %15, %16, %17, %18, %19, %20, %21, %22, %23, %24, %25, %26, %27, %28, %29, %30, %31, %32, %33, %34, %35, %36, %37, %38, %39, %40, %41, %42, %43, %44, %45, %46, %47, %48, %49, %50, %51, %52, %53, %54, %55, %56, %57, %58, %59, %60, %61, %62, %63, %64, %65, %66, %67, %68, %69, %70, %71, %72, %73, %74, %75, %76, %77, %78, %79, %80, %81, %82, %83, %84, %85, %86, %87, %88, %89, %90, %91, %92, %93, %94, %95}, {%96, %97, %98, %99}, %100, p, 1, 1, %102;\n}\n"
    : "+f"(d[0]), "+f"(d[1]), "+f"(d[2]), "+f"(d[3]), "+f"(d[4]), "+f"(d[5]), "+f"(d[6]), "+f"(d[7]), "+f"(d[8]), "+f"(d[9]), "+f"(d[10]), "+f"(d[11]), "+f"(d[12]), "+f"(d[13]), "+f"(d[14]), "+f"(d[15]), "+f"(d[16]), "+f"(d[17]), "+f"(d[18]), "+f"(d[19]), "+f"(d[20]), "+f"(d[21]), "+f"(d[22]), "+f"(d[23]), "+f"(d[24]), "+f"(d[25]), "+f"(d[26]), "+f"(d[27]), "+f"(d[28]), "+f"(d[29]), "+f"(d[30]), "+f"(d[31]), "+f"(d[32]), "+f"(d[33]), "+f"(d[34]), "+f"(d[35]), "+f"(d[36]), "+f"(d[37]), "+f"(d[38]), "+f"(d[39]), "+f"(d[40]), "+f"(d[41]), "+f"(d[42]), "+f"(d[43]), "+f"(d[44]), "+f"(d[45]), "+f"(d[46]), "+f"(d[47]), "+f"(d[48]), "+f"(d[49]), "+f"(d[50]), "+f"(d[51]), "+f"(d[52]), "+f"(d[53]), "+f"(d[54]), "+f"(d[55]), "+f"(d[56]), "+f"(d[57]), "+f"(d[58]), "+f"(d[59]), "+f"(d[60]), "+f"(d[61]), "+f"(d[62]), "+f"(d[63]), "+f"(d[64]), "+f"(d[65]), "+f"(d[66]), "+f"(d[67]), "+f"(d[68]), "+f"(d[69]), "+f"(d[70]), "+f"(d[71]), "+f"(d[72]), "+f"(d[73]), "+f"(d[74]), "+f"(d[75]), "+f"(d[76]), "+f"(d[77]), "+f"(d[78]), "+f"(d[79]), "+f"(d[80]), "+f"(d[81]), "+f"(d[82]), "+f"(d[83]), "+f"(d[84]), "+f"(d[85]), "+f"(d[86]), "+f"(d[87]), "+f"(d[88]), "+f"(d[89]), "+f"(d[90]), "+f"(d[91]), "+f"(d[92]), "+f"(d[93]), "+f"(d[94]), "+f"(d[95])
    : "r"(a0), "r"(a1), "r"(a2), "r"(a3), "l"(db), "r"(scale_d), "n"(TB));
}

template<int TB, int TA = 0> __device__ __forceinline__ void wgmma_ss_n128(float (&d)[64], uint64_t da, uint64_t db, int scale_d) {
  asm volatile("{\n.reg .pred p;\nsetp.ne.b32 p, %66, 0;\n"
    "wgmma.mma_async.sync.aligned.m64n128k16.f32.bf16.bf16 {%0, %1, %2, %3, %4, %5, %6, %7, %8, %9, %10, %11, %12, %13, %14, %15, %16, %17, %18, %19, %20, %21, %22, %23, %24, %25, %26, %27, %28, %29, %30, %31, %32, %33, %34, %35, %36, %37, %38, %39, %40, %41, %42, %43, %44, %45, %46, %47, %48, %49, %50, %51, %52, %53, %54, %55, %56, %57, %58, %59, %60, %61, %62, %63}, %64, %65, p, 1, 1, %68, %67;\n}\n"
    : "+f"(d[0]), "+f"(d[1]), "+f"(d[2]), "+f"(d[3]), "+f"(d[4]), "+f"(d[5]), "+f"(d[6]), "+f"(d[7]), "+f"(d[8]), "+f"(d[9]), "+f"(d[10]), "+f"(d[11]), "+f"(d[12]), "+f"(d[13]), "+f"(d[14]), "+f"(d[15]), "+f"(d[16]), "+f"(d[17]), "+f"(d[18]), "+f"(d[19]), "+f"(d[20]), "+f"(d[21]), "+f"(d[22]), "+f"(d[23]), "+f"(d[24]), "+f"(d[25]), "+f"(d[26]), "+f"(d[27]), "+f"(d[28]), "+f"(d[29]), "+f"(d[30]), "+f"(d[31]), "+f"(d[32]), "+f"(d[33]), "+f"(d[34]), "+f"(d[35]), "+f"(d[36]), "+f"(d[37]), "+f"(d[38]), "+f"(d[39]), "+f"(d[40]), "+f"(d[41]), "+f"(d[42]), "+f"(d[43]), "+f"(d[44]), "+f"(d[45]), "+f"(d[46]), "+f"(d[47]), "+f"(d[48]), "+f"(d[49]), "+f"(d[50]), "+f"(d[51]), "+f"(d[52]), "+f"(d[53]), "+f"(d[54]), "+f"(d[55]), "+f"(d[56]), "+f"(d[57]), "+f"(d[58]), "+f"(d[59]), "+f"(d[60]), "+f"(d[61]), "+f"(d[62]), "+f"(d[63])
    : "l"(da), "l"(db), "r"(scale_d), "n"(TB), "n"(TA));
}

template<int TB, int TA = 0> __device__ __forceinline__ void wgmma_ss_n64(float (&d)[32], uint64_t da, uint64_t db, int scale_d) {
  asm volatile("{\n.reg .pred p;\nsetp.ne.b32 p, %34, 0;\n"
    "wgmma.mma_async.sync.aligned.m64n64k16.f32.bf16.bf16 {%0, %1, %2, %3, %4, %5, %6, %7, %8, %9, %10, %11, %12, %13, %14, %15, %16, %17, %18, %19, %20, %21, %22, %23, %24, %25, %26, %27, %28, %29, %30, %31}, %32, %33, p, 1, 1, %36, %35;\n}\n"
    : "+f"(d[0]), "+f"(d[1]), "+f"(d[2]), "+f"(d[3]), "+f"(d[4]), "+f"(d[5]), "+f"(d[6]), "+f"(d[7]), "+f"(d[8]), "+f"(d[9]), "+f"(d[10]), "+f"(d[11]), "+f"(d[12]), "+f"(d[13]), "+f"(d[14]), "+f"(d[15]), "+f"(d[16]), "+f"(d[17]), "+f"(d[18]), "+f"(d[19]), "+f"(d[20]), "+f"(d[21]), "+f"(d[22]), "+f"(d[23]), "+f"(d[24]), "+f"(d[25]), "+f"(d[26]), "+f"(d[27]), "+f"(d[28]), "+f"(d[29]), "+f"(d[30]), "+f"(d[31])
    : "l"(da), "l"(db), "r"(scale_d), "n"(TB), "n"(TA));
}

template<int TB, int TA = 0> __device__ __forceinline__ void wgmma_ss_n8(float (&d)[4], uint64_t da, uint64_t db, int scale_d) {
  asm volatile("{\n.reg .pred p;\nsetp.ne.b32 p, %6, 0;\n"
    "wgmma.mma_async.sync.aligned.m64n8k16.f32.bf16.bf16 {%0, %1, %2, %3}, %4, %5, p, 1, 1, %8, %7;\n}\n"
    : "+f"(d[0]), "+f"(d[1]), "+f"(d[2]), "+f"(d[3])
    : "l"(da), "l"(db), "r"(scale_d), "n"(TB), "n"(TA));
}

template<int TB> __device__ __forceinline__ void wgmma_rs_n40(float (&d)[20], uint32_t a0, uint32_t a1, uint32_t a2, uint32_t a3, uint64_t db, int scale_d) {
  asm volatile("{\n.reg .pred p;\nsetp.ne.b32 p, %25, 0;\n"
    "wgmma.mma_async.sync.aligned.m64n40k16.f32.bf16.bf16 {%0, %1, %2, %3, %4, %5, %6, %7, %8, %9, %10, %11, %12, %13, %14, %15, %16, %17, %18, %19}, {%20, %21, %22, %23}, %24, p, 1, 1, %26;\n}\n"
    : "+f"(d[0]), "+f"(d[1]), "+f"(d[2]), "+f"(d[3]), "+f"(d[4]), "+f"(d[5]), "+f"(d[6]), "+f"(d[7]), "+f"(d[8]), "+f"(d[9]), "+f"(d[10]), "+f"(d[11]), "+f"(d[12]), "+f"(d[13]), "+f"(d[14]), "+f"(d[15]), "+f"(d[16]), "+f"(d[17]), "+f"(d[18]), "+f"(d[19])
    : "r"(a0), "r"(a1), "r"(a2), "r"(a3), "l"(db), "r"(scale_d), "n"(TB));
}

#define DEVI __device__ __forceinline__
DEVI uint32_t smem_u32(const void* p) { return (uint32_t)__cvta_generic_to_shared(p); }
DEVI void mbar_init(uint32_t bar, uint32_t cnt) { asm volatile("mbarrier.init.shared::cta.b64 [%0], %1;" :: "r"(bar), "r"(cnt)); }
DEVI void mbar_expect_tx(uint32_t bar, uint32_t bytes) { asm volatile("mbarrier.arrive.expect_tx.shared::cta.b64 _, [%0], %1;" :: "r"(bar), "r"(bytes) : "memory"); }
DEVI void mbar_arrive(uint32_t bar) { asm volatile("mbarrier.arrive.shared::cta.b64 _, [%0];" :: "r"(bar) : "memory"); }
DEVI void mbar_arrive_peer(uint32_t bar) {
  asm volatile("{\n.reg .b32 ra;\nmapa.shared::cluster.u32 ra, %0, %1;\nmbarrier.arrive.shared::cluster.b64 _, [ra];\n}" :: "r"(bar), "r"((blockIdx.x & 1) ^ 1) : "memory");
}
DEVI void bulk_s2peer(uint32_t a, uint32_t bytes, uint32_t bar) {
  asm volatile("{\n.reg .b32 ra, rb;\nmapa.shared::cluster.u32 ra, %0, %3;\nmapa.shared::cluster.u32 rb, %2, %3;\n"
               "cp.async.bulk.shared::cluster.shared::cta.mbarrier::complete_tx::bytes [ra], [%0], %1, [rb];\n}"
               :: "r"(a), "r"(bytes), "r"(bar), "r"((blockIdx.x & 1) ^ 1) : "memory");
}
DEVI void mbar_wait(uint32_t bar, uint32_t parity) {
  asm volatile("{\n.reg .pred p;\nLW:\nmbarrier.try_wait.parity.shared::cta.b64 p, [%0], %1;\n@!p bra LW;\n}" :: "r"(bar), "r"(parity) : "memory");
}
DEVI uint32_t mbar_test(uint32_t bar, uint32_t parity) {
  uint32_t r; asm volatile("{\n.reg .pred p;\nmbarrier.test_wait.parity.shared::cta.b64 p, [%1], %2;\nselp.u32 %0, 1, 0, p;\n}" : "=r"(r) : "r"(bar), "r"(parity) : "memory"); return r;
}
DEVI void mbar_wait_b(uint32_t bar, uint32_t parity) {
  asm volatile("{\n.reg .pred p;\n.reg .u32 it;\nmov.u32 it, 0;\nLW:\nmbarrier.try_wait.parity.shared::cta.b64 p, [%0], %1;\n@p bra LD;\n"
               "add.u32 it, it, 1;\nsetp.lt.u32 p, it, 0x1000000;\n@p bra LW;\ntrap;\nLD:\n}" :: "r"(bar), "r"(parity) : "memory");
}
DEVI void tma_2d(uint32_t dst, const CUtensorMap* m, int c0, int c1, uint32_t bar) {
  asm volatile("cp.async.bulk.tensor.2d.shared::cluster.global.mbarrier::complete_tx::bytes [%0], [%1, {%3, %4}], [%2];"
    :: "r"(dst), "l"(m), "r"(bar), "r"(c0), "r"(c1) : "memory");
}
DEVI void tma_3d(uint32_t dst, const CUtensorMap* m, int c0, int c1, int c2, uint32_t bar) {
  asm volatile("cp.async.bulk.tensor.3d.shared::cluster.global.mbarrier::complete_tx::bytes [%0], [%1, {%3, %4, %5}], [%2];"
    :: "r"(dst), "l"(m), "r"(bar), "r"(c0), "r"(c1), "r"(c2) : "memory");
}
#define POL_EF POL_FIRST
constexpr uint64_t POL_FIRST = 0x12F0000000000000ull, POL_NORMAL = 0x1000000000000000ull;
DEVI void tma_2d_h(uint32_t dst, const CUtensorMap* m, int c0, int c1, uint32_t bar, uint64_t pol) {
  asm volatile("cp.async.bulk.tensor.2d.shared::cluster.global.mbarrier::complete_tx::bytes.L2::cache_hint [%0], [%1, {%3, %4}], [%2], %5;"
    :: "r"(dst), "l"(m), "r"(bar), "r"(c0), "r"(c1), "l"(pol) : "memory");
}
DEVI void tma_3d_h(uint32_t dst, const CUtensorMap* m, int c0, int c1, int c2, uint32_t bar, uint64_t pol) {
  asm volatile("cp.async.bulk.tensor.3d.shared::cluster.global.mbarrier::complete_tx::bytes.L2::cache_hint [%0], [%1, {%3, %4, %5}], [%2], %6;"
    :: "r"(dst), "l"(m), "r"(bar), "r"(c0), "r"(c1), "r"(c2), "l"(pol) : "memory");
}
DEVI void bulk_g2s_h(uint32_t s, const void* g, uint32_t bytes, uint32_t bar, uint64_t pol = POL_EF) {
  asm volatile("cp.async.bulk.shared::cluster.global.mbarrier::complete_tx::bytes.L2::cache_hint [%0], [%1], %2, [%3], %4;"
    :: "r"(s), "l"(g), "r"(bytes), "r"(bar), "l"(pol) : "memory");
}
DEVI void tma_5d(uint32_t dst, const CUtensorMap* m, int c0, int c1, int c2, int c3, int c4, uint32_t bar, uint64_t pol) {
  asm volatile("cp.async.bulk.tensor.5d.shared::cluster.global.mbarrier::complete_tx::bytes.L2::cache_hint [%0], [%1, {%3, %4, %5, %6, %7}], [%2], %8;"
    :: "r"(dst), "l"(m), "r"(bar), "r"(c0), "r"(c1), "r"(c2), "r"(c3), "r"(c4), "l"(pol) : "memory");
}
DEVI void tma_prefetch_2d(const CUtensorMap* m, int c0, int c1) {
  asm volatile("cp.async.bulk.prefetch.tensor.2d.L2.global.tile [%0, {%1, %2}];" :: "l"(m), "r"(c0), "r"(c1) : "memory");
}
DEVI void tma_prefetch_3d(const CUtensorMap* m, int c0, int c1, int c2) {
  asm volatile("cp.async.bulk.prefetch.tensor.3d.L2.global.tile [%0, {%1, %2, %3}];" :: "l"(m), "r"(c0), "r"(c1), "r"(c2) : "memory");
}
DEVI void bulk_prefetch(const void* g, uint32_t bytes) { asm volatile("cp.async.bulk.prefetch.L2.global [%0], %1;" :: "l"(g), "r"(bytes) : "memory"); }
DEVI void bulk_g2s(uint32_t s, const void* g, uint32_t bytes, uint32_t bar) {
  asm volatile("cp.async.bulk.shared::cluster.global.mbarrier::complete_tx::bytes [%0], [%1], %2, [%3];" :: "r"(s), "l"(g), "r"(bytes), "r"(bar) : "memory");
}
DEVI void bulk_s2g(void* g, uint32_t s, uint32_t bytes) {
  asm volatile("cp.async.bulk.global.shared::cta.bulk_group [%0], [%1], %2;\ncp.async.bulk.commit_group;" :: "l"(g), "r"(s), "r"(bytes) : "memory");
}
template<int N> DEVI void bulk_wait() { asm volatile("cp.async.bulk.wait_group %0;" :: "n"(N) : "memory"); }
DEVI void fence_async_smem() { asm volatile("fence.proxy.async.shared::cta;" ::: "memory"); }
DEVI void fence_async_glob() { asm volatile("fence.proxy.async.global;" ::: "memory"); }
DEVI unsigned ld_rlx(const unsigned* p) { unsigned v; asm volatile("ld.relaxed.gpu.global.u32 %0, [%1];" : "=r"(v) : "l"(p) : "memory"); return v; }
DEVI void st_rlx(unsigned* p, unsigned v) { asm volatile("st.relaxed.gpu.global.u32 [%0], %1;" :: "l"(p), "r"(v) : "memory"); }
DEVI uint2 ldg_stream(const uint2* p) { uint2 v; asm volatile("ld.global.nc.L1::no_allocate.v2.u32 {%0, %1}, [%2];" : "=r"(v.x), "=r"(v.y) : "l"(p)); return v; }
DEVI void fence_rel() { asm volatile("fence.release.gpu;" ::: "memory"); }
DEVI uint4 ld_ll(const uint4* p) {
  uint4 v;
  asm volatile("{\n.reg .b128 t;\n.reg .b64 a, b;\nld.relaxed.gpu.global.b128 t, [%4];\nmov.b128 {a, b}, t;\nmov.b64 {%0, %1}, a;\nmov.b64 {%2, %3}, b;\n}"
               : "=r"(v.x), "=r"(v.y), "=r"(v.z), "=r"(v.w) : "l"(p) : "memory");
  return v;
}
DEVI void st_ll(uint4* p, uint32_t x, uint32_t y, uint32_t z, uint32_t w) {
  asm volatile("{\n.reg .b128 t;\n.reg .b64 a, b;\nmov.b64 a, {%1, %2};\nmov.b64 b, {%3, %4};\nmov.b128 t, {a, b};\nst.relaxed.gpu.global.b128 [%0], t;\n}"
               :: "l"(p), "r"(x), "r"(y), "r"(z), "r"(w) : "memory");
}
#define SPIN_MAX 0x1000000
DEVI uint4 poll_ll(const uint4* p, uint32_t mask, uint32_t tag) {
  uint4 v; int it = 0;
  do { v = ld_ll(p); if (++it > SPIN_MAX) __trap(); } while (!__all_sync(0xffffffffu, (v.w & mask) == tag));
  return v;
}
DEVI void poll_ll2(const uint4* p, const uint4* q, uint32_t mask, uint32_t tag, uint4& a, uint4& b) {
  int it = 0;
  do { a = ld_ll(p); b = ld_ll(q); if (++it > SPIN_MAX) __trap(); } while (!__all_sync(0xffffffffu, (a.w & mask) == tag && (b.w & mask) == tag));
}
DEVI void bar_sync(int id, int n) { asm volatile("bar.sync %0, %1;" :: "r"(id), "r"(n) : "memory"); }
DEVI void bar_arrive(int id, int n) { asm volatile("bar.arrive %0, %1;" :: "r"(id), "r"(n) : "memory"); }
DEVI void wg_fence() { asm volatile("wgmma.fence.sync.aligned;" ::: "memory"); }
DEVI void wg_commit() { asm volatile("wgmma.commit_group.sync.aligned;" ::: "memory"); }
template<int N> DEVI void wg_wait() { asm volatile("wgmma.wait_group.sync.aligned %0;" :: "n"(N) : "memory"); }
template<int N> DEVI void reg_inc() { asm volatile("setmaxnreg.inc.sync.aligned.u32 %0;" :: "n"(N)); }
template<int N> DEVI void reg_dec() { asm volatile("setmaxnreg.dec.sync.aligned.u32 %0;" :: "n"(N)); }
DEVI float ex2f(float x) { float y; asm("ex2.approx.ftz.f32 %0, %1;" : "=f"(y) : "f"(x)); return y; }
DEVI uint32_t pack_bf16(float lo, float hi) { uint32_t r; asm("cvt.rn.bf16x2.f32 %0, %1, %2;" : "=r"(r) : "f"(hi), "f"(lo)); return r; }
DEVI float bf_lo(uint32_t v) { return __uint_as_float(v << 16); }
DEVI float bf_hi(uint32_t v) { return __uint_as_float(v & 0xffff0000u); }
DEVI float bf_round(float x) { return bf_lo(pack_bf16(x, 0.f)); }
DEVI void stsm_x4(uint32_t addr, uint32_t a, uint32_t b, uint32_t c, uint32_t d) {
  asm volatile("stmatrix.sync.aligned.m8n8.x4.shared.b16 [%0], {%1,%2,%3,%4};" :: "r"(addr), "r"(a), "r"(b), "r"(c), "r"(d) : "memory");
}
DEVI void ldsm_x4(uint32_t addr, uint32_t& a, uint32_t& b, uint32_t& c, uint32_t& d) {
  asm volatile("ldmatrix.sync.aligned.m8n8.x4.shared.b16 {%0,%1,%2,%3}, [%4];" : "=r"(a), "=r"(b), "=r"(c), "=r"(d) : "r"(addr) : "memory");
}
DEVI uint4 lds128(uint32_t a) { uint4 v; asm volatile("ld.shared.v4.u32 {%0,%1,%2,%3}, [%4];" : "=r"(v.x), "=r"(v.y), "=r"(v.z), "=r"(v.w) : "r"(a) : "memory"); return v; }
DEVI void sts128(uint32_t a, uint4 v) { asm volatile("st.shared.v4.u32 [%0], {%1,%2,%3,%4};" :: "r"(a), "r"(v.x), "r"(v.y), "r"(v.z), "r"(v.w) : "memory"); }
DEVI float2 lds64f(uint32_t a) { float2 v; asm volatile("ld.shared.v2.f32 {%0,%1}, [%2];" : "=f"(v.x), "=f"(v.y) : "r"(a) : "memory"); return v; }
DEVI void sts64f(uint32_t a, float x, float y) { asm volatile("st.shared.v2.f32 [%0], {%1,%2};" :: "r"(a), "f"(x), "f"(y) : "memory"); }
DEVI uint32_t lds32(uint32_t a) { uint32_t v; asm volatile("ld.shared.u32 %0, [%1];" : "=r"(v) : "r"(a) : "memory"); return v; }
DEVI float lds32f(uint32_t a) { return __uint_as_float(lds32(a)); }
DEVI void sts32(uint32_t a, uint32_t v) { asm volatile("st.shared.u32 [%0], %1;" :: "r"(a), "r"(v) : "memory"); }
DEVI void sts32f(uint32_t a, float v) { sts32(a, __float_as_uint(v)); }
DEVI void sts16(uint32_t a, uint32_t v) { asm volatile("st.shared.u16 [%0], %1;" :: "r"(a), "h"((unsigned short)v) : "memory"); }
template<int N> DEVI void keep(float (&d)[N]) {
  #pragma unroll
  for (int i = 0; i < N; i++) asm volatile("" : "+f"(d[i]) :: "memory");
}
template<int N> DEVI void keep(uint32_t (&d)[N]) {
  #pragma unroll
  for (int i = 0; i < N; i++) asm volatile("" : "+r"(d[i]) :: "memory");
}
template<uint32_t HI> DEVI uint64_t mkd(uint32_t lo) { uint64_t r; asm("mov.b64 %0, {%1, %2};" : "=l"(r) : "r"(lo), "n"(HI)); return r; }
constexpr uint32_t HI128 = (1u << 30) | (1024 >> 4), HI64 = (2u << 30) | (512 >> 4);
#define VOFF(x) ((uint32_t)(x) * (uint32_t)(1 - 65536))
DEVI bool elect() { uint32_t p; asm volatile("{\n.reg .pred q;\nelect.sync _|q, 0xffffffff;\nselp.u32 %0, 1, 0, q;\n}" : "=r"(p)); return p; }
DEVI void warp_signal(uint32_t bar) { __syncwarp(); if (elect()) mbar_arrive(bar); }

struct Scratch {
  uint4 kv[128][4][1024];
  uint4 o[8][2][8][2][1024];
  uint4 x[8][16][2048];
  uint4 zero[1024];
  uint4 statP[8][2048];
  uint4 statF[2048];
  uint4 csP[16][8][96];
  uint4 best[8][16];
  uint4 row[16][256];
  uint4 yP[128][112][2];
  uint4 x2[8][256];
  uint4 patch[128][64];
  unsigned flagKV[128][32];
  unsigned flagO[8][32];
  unsigned flagX[8][32];
  unsigned epoch;
};
__device__ __align__(1024) Scratch g_scr;
#define PROFT(cond, slot)
#define PROFW(cond, slot)
#define PROFD(cond, slot)
#define PROFX(cond, slot)
#define PROFY(cond, slot)

constexpr uint32_t SB0 = 65536, HOLE = 90112, SA2 = 98304, SB1 = 131072, SB2 = 155648, STG = 180224;
constexpr uint32_t KVA = 0, KVB = 98304, QO = 65536;
constexpr uint32_t MISC = 229376, CS = MISC, ONES = MISC + 768, BARS = MISC + 1792, INFO = MISC + 2208, WR = MISC + 2224, X2SEG = MISC + 2736, INFO2 = MISC + 2992, DUMP = MISC + 3040;
constexpr uint32_t PAR = HOLE, HV = HOLE + 2048, RED = HOLE + 6144, PATCH = 196608;
constexpr uint32_t SMEM_BYTES = 232448;
enum { B_FULLQ = 0, B_EMPTYQ = 3, B_FULLW = 6, B_EMPTYW = 12, B_HAFREE = 18, B_OFREE = 20,
       B_XFREE = 21,
       B_KVRDY = 23, B_ORDY = 27, B_XRDY = 35, B_STGE = 39,
       B_KVFULL = 42, B_RES = 46, B_PAR = 47, B_STG = 48, B_PFREE = 51, B_COUNT = 52,
       B_ROW = 154 };
#define BAR(x) (sb + BARS + 8 * (x))
DEVI uint32_t qa_off(int s) { return s == 2 ? SA2 : (uint32_t)s * 32768u; }
DEVI uint32_t qb_off(int s) { return s == 0 ? SB0 : (s == 1 ? SB1 : SB2); }
DEVI int kb_order(int bc, int n) {
  const int e = n < 9 ? n - 2 : n - 9;
  return n < 2 ? 2 * bc + n : 2 * (((e < 4 ? e + 4 : e - 4 + (e - 4 >= (bc & 3))) + (bc & 4)) & 7) + (n >= 9);
}
DEVI int wo_order(int bc, int n) { return (n & 8) | ((n + (bc & 6)) & 7); }
DEVI uint32_t w_off(int s) { return (uint32_t)((0x431065 >> (4 * s)) & 7) * 32768u; }
DEVI uint32_t w_par(int n, int s, int L) { return ((n >= 6 && n < 12) ^ (!(s & 2) && L)); }
DEVI int w_next(int n, int s) { return s == 5 ? 0 : (n == 13 ? 4 : s + 1); }

struct Params {
  CUtensorMap mX, mXh, mWq, mWo, mWg, mWu, mWp, mWd;
  const bf16 *x0, *wqkv, *wo, *wr, *wg, *wu, *wd;
  bf16* out;
  Scratch* g;
  unsigned map[128];
};
#define BID ((int)(P.map[blockIdx.x] & 255))
#define FID ((int)(P.map[blockIdx.x] >> 8))
DEVI uint32_t uni(uint32_t v) { return __shfl_sync(0xffffffffu, v, 0); }
#define PQ_N 8
#define PQ_T 700
#define PF0_N 10
#define PF0_T 1600
#define PF1_E 24
#define PF1_T 1100
#define POL_Q1 POL_NORMAL
#define POL_X POL_NORMAL
#define PFA0_BAR 3
#define PFA1_BAR 0
#define PFA0_M 0
#define PFA1_M 0
#define PFA0_T 900
#define PFA1_T 700
#define PF1_S PF0_N
#define PF1_D 0
#define POL_G POL_NORMAL
#define POL_U POL_FIRST
#define POL_D POL_FIRST
#define JQ_N 6
#define WDSRC (P.wd + (size_t)min(fid, 111) * 32768)
#define WDSRC2 (P.wd + FID * 32768)
#define WD_N 4
#define THR_N 6
#define KV_D 1300
#define XD_D 600
#define W0_BAR 3
#define QEF_N 11
#define POL_Q0 POL_NORMAL
constexpr float LN_EPS = 1e-5f;
constexpr float QSCALE = 0.17677669529663687f * 1.4426950408889634f;

DEVI void fma8(float (&a)[8], uint4 v, float h) {
  a[0] = fmaf(bf_lo(v.x), h, a[0]); a[1] = fmaf(bf_hi(v.x), h, a[1]); a[2] = fmaf(bf_lo(v.y), h, a[2]); a[3] = fmaf(bf_hi(v.y), h, a[3]);
  a[4] = fmaf(bf_lo(v.z), h, a[4]); a[5] = fmaf(bf_hi(v.z), h, a[5]); a[6] = fmaf(bf_lo(v.w), h, a[6]); a[7] = fmaf(bf_hi(v.w), h, a[7]);
}
DEVI uint4 ldsv128(uint32_t a) { uint4 v; asm volatile("ld.volatile.shared.v4.u32 {%0,%1,%2,%3}, [%4];" : "=r"(v.x), "=r"(v.y), "=r"(v.z), "=r"(v.w) : "r"(a) : "memory"); return v; }
DEVI float ldsv32f(uint32_t a) { float v; asm volatile("ld.volatile.shared.f32 %0, [%1];" : "=f"(v) : "r"(a) : "memory"); return v; }
DEVI uint32_t clk() { uint32_t t; asm volatile("mov.u32 %0, %%clock;" : "=r"(t)); return t; }
DEVI int fresh_tid() { int t; asm volatile("mov.u32 %0, %%tid.x;" : "=r"(t)); return t & 127; }
DEVI float fold8(const float (&a)[8]) {
  const int lane = threadIdx.x & 31;
  const bool u = lane & 16, v = lane & 8, x = lane & 4;
  float b0 = (u ? a[4] : a[0]) + __shfl_xor_sync(0xffffffffu, u ? a[0] : a[4], 16), b1 = (u ? a[5] : a[1]) + __shfl_xor_sync(0xffffffffu, u ? a[1] : a[5], 16);
  float b2 = (u ? a[6] : a[2]) + __shfl_xor_sync(0xffffffffu, u ? a[2] : a[6], 16), b3 = (u ? a[7] : a[3]) + __shfl_xor_sync(0xffffffffu, u ? a[3] : a[7], 16);
  float c0 = (v ? b2 : b0) + __shfl_xor_sync(0xffffffffu, v ? b0 : b2, 8), c1 = (v ? b3 : b1) + __shfl_xor_sync(0xffffffffu, v ? b1 : b3, 8);
  return (x ? c1 : c0) + __shfl_xor_sync(0xffffffffu, x ? c0 : c1, 4);
}
DEVI float swiglu(float g, float u) { g = bf_round(g); return bf_round(bf_round(__fdividef(g, 1.f + __expf(-g))) * bf_round(u)); }

DEVI void qk_issue(float (&s)[32], uint32_t qd, uint32_t kd) {
  wgmma_ss_n64<0>(s, mkd<HI64>(qd), mkd<HI64>(kd), 0);
  wgmma_ss_n64<0>(s, mkd<HI64>(qd + 2), mkd<HI64>(kd + 2), 1);
}
template<int J0, int J1> DEVI void exp_pack(const float (&s)[32], uint32_t (&p)[16]) {
  #pragma unroll
  for (int j = J0; j < J1; j++) p[j] = pack_bf16(ex2f(s[2 * j]), ex2f(s[2 * j + 1]));
}
DEVI bool attn_pack(const float (&o)[20], uint32_t (&ob)[8]) {
  const float lo = 5.421010862427522e-20f, hi = 1.8446744073709552e19f;
  float i0, i1; asm("rcp.approx.ftz.f32 %0, %1;" : "=f"(i0) : "f"(o[16])); asm("rcp.approx.ftz.f32 %0, %1;" : "=f"(i1) : "f"(o[18]));
  #pragma unroll
  for (int e = 0; e < 8; e++) ob[e] = pack_bf16(o[2 * e] * ((e & 1) ? i1 : i0), o[2 * e + 1] * ((e & 1) ? i1 : i0));
  return __all_sync(0xffffffffu, o[16] >= lo && o[16] <= hi && o[18] >= lo && o[18] <= hi);
}
DEVI void attn_store(const uint32_t (&ob)[8], bool ok, uint32_t st, uint32_t sb, uint32_t bar) {
  stsm_x4(ok ? st : sb + DUMP, ob[0], ob[1], ob[2], ob[3]); stsm_x4(ok ? st ^ 32 : sb + DUMP, ob[4], ob[5], ob[6], ob[7]);
  __syncwarp();
  asm volatile("{\n.reg .pred p, q;\nelect.sync _|q, 0xffffffff;\nsetp.ne.and.u32 p, %1, 0, q;\n@p mbarrier.arrive.shared::cta.b64 _, [%0];\n}" :: "r"(bar), "r"((uint32_t)ok) : "memory");
}
DEVI void attn_exact(uint32_t st, uint32_t kv, int t, bool hasprev, uint32_t bar) {
  const int lane = threadIdx.x & 31;
  #pragma unroll 1
  for (int row = ((threadIdx.x >> 5) & 3) * 16, n = 0; n < 16; n++, row++) {
    const int k1 = 256 + t * 64 + row;
    float m = -INFINITY, l = 0.f, o = 0.f;
    #pragma unroll 1
    for (int k0 = hasprev ? k1 - 255 : 256; k0 <= k1; k0 += 32) {
      const int k = min(k0 + lane, k1), r = k & 63;
      float sc = 0.f;
      #pragma unroll 1
      for (int c = 0; c < 16; c++) {
        uint32_t a = lds32(st + row * 64 + ((c * 4) ^ ((row & 6) << 3))), b = lds32(kv + (k >> 6) * 8192 + r * 64 + ((c * 4) ^ ((r & 6) << 3)));
        sc = fmaf(bf_lo(a), bf_lo(b), fmaf(bf_hi(a), bf_hi(b), sc));
      }
      float mn = fmaxf(m, sc);
      #pragma unroll 1
      for (int x = 16; x; x >>= 1) mn = fmaxf(mn, __shfl_xor_sync(0xffffffffu, mn, x));
      const float al = ex2f(m - mn), pr = ex2f(sc - mn);
      m = mn; l *= al; o *= al;
      #pragma unroll 1
      for (int q = k0; q <= min(k0 + 31, k1); q++) {
        const float z = __shfl_sync(0xffffffffu, pr, q - k0);
        uint32_t b = lds32(kv + (q >> 6) * 8192 + 4096 + (q & 63) * 64 + (((lane >> 1) * 4) ^ ((q & 6) << 3)));
        l += z; o = fmaf(z, (lane & 1) ? bf_hi(b) : bf_lo(b), o);
      }
    }
    __syncwarp();
    sts16(st + row * 64 + ((lane * 2) ^ ((row & 6) << 3)), pack_bf16(__fdividef(o, l), 0.f));
  }
  warp_signal(bar);
}

template<int K0, int K1, int DONE = 0> DEVI void exp_pv(const float (&s)[32], uint32_t (&p)[16], float (&o)[20], uint32_t vd, bool accum) {
  #pragma unroll
  for (int ks = K0; ks < K1; ks++) {
    if (ks >= DONE) {
      #pragma unroll
      for (int j = 4 * ks; j < 4 * ks + 4; j++) p[j] = pack_bf16(ex2f(s[2 * j]), ex2f(s[2 * j + 1]));
    }
    asm volatile("" : "+r"(p[4 * ks]), "+r"(p[4 * ks + 1]), "+r"(p[4 * ks + 2]), "+r"(p[4 * ks + 3]));
    wg_fence();
    wgmma_rs_n40<1>(o, p[ks * 4], p[ks * 4 + 1], p[ks * 4 + 2], p[ks * 4 + 3], mkd<HI64>(vd + VOFF(ks * 64)), ks ? 1 : accum);
  }
}
DEVI void exp_pv2(const float (&s)[32], const float (&sx)[32], uint32_t (&p)[16], uint32_t (&px)[16], float (&o)[20], uint32_t v0, uint32_t v4,
                  const uint32_t (&msk)[9], int tdiag) {
  #pragma unroll
  for (int ks = 0; ks < 4; ks++) {
    #pragma unroll
    for (int j = 4 * ks; j < 4 * ks + 4; j++) {
      const int c = 8 * (j >> 1) - 8 * (j & 1);
      const uint32_t e = pack_bf16(ex2f(c > tdiag ? s[2 * j] : sx[2 * j]), ex2f(c + 1 > tdiag ? s[2 * j + 1] : sx[2 * j + 1])), m = msk[(j >> 1) - (j & 1) + 1];
      p[j] = e & m; px[j] = e & ~m;
      asm volatile("" : "+r"(p[j]), "+r"(px[j]));
    }
    wg_fence();
    wgmma_rs_n40<1>(o, p[ks * 4], p[ks * 4 + 1], p[ks * 4 + 2], p[ks * 4 + 3], mkd<HI64>(v0 + VOFF(ks * 64)), 1);
    wgmma_rs_n40<1>(o, px[ks * 4], px[ks * 4 + 1], px[ks * 4 + 2], px[ks * 4 + 3], mkd<HI64>(v4 + VOFF(ks * 64)), 1);
  }
}

template<int J0> DEVI void qkv_store(const float (&a)[96], float p0, float p1, uint32_t d) {
  #pragma unroll
  for (int hh = 0; hh < 2; hh++) {
    const int j = 4 * (J0 + 2 * hh);
    stsm_x4(d ^ (hh << 5), pack_bf16(a[j] * p0, a[j + 1] * p0), pack_bf16(a[j + 2] * p1, a[j + 3] * p1),
                           pack_bf16(a[j + 4] * p0, a[j + 5] * p0), pack_bf16(a[j + 6] * p1, a[j + 7] * p1));
  }
}
DEVI void mean_step(float (&a)[96], float m0, float m1, uint32_t cd, bool z) {
  const uint32_t u0 = z ? 0u : __float_as_uint(m0), u1 = z ? 0u : __float_as_uint(m1);
  uint32_t ma[4] = {__byte_perm(u0, 0u, 0x1010), __byte_perm(u1, 0u, 0x1010), __byte_perm(u0, 0u, 0x3232), __byte_perm(u1, 0u, 0x3232)};
  keep(ma);
  wg_fence();
  wgmma_rs_n192<1>(a, ma[0], ma[1], ma[2], ma[3], mkd<2>(cd), 1);
  wg_commit();
}

template<bool FIRST> DEVI void qkv_block(float (&aX)[96], float (&aY)[96], uint32_t sb16, int s, int tX, int tY) {
  uint32_t a16 = sb16 + (qa_off(s) >> 4), b16 = (sb16 + (qb_off(s) >> 4)) | ((8192u >> 4) << 16);
  uint32_t ax = (a16 + tX * 512) | 0x10000u, ay = (a16 + tY * 512) | 0x10000u;
  wg_fence();
  #pragma unroll
  for (int ks = 0; ks < 4; ks++) {
    wgmma_ss_n192<1>(aX, mkd<HI128>(ax + ks * 2), mkd<HI128>(b16 + ks * 128), !(FIRST && ks == 0));
    wgmma_ss_n192<1>(aY, mkd<HI128>(ay + ks * 2), mkd<HI128>(b16 + ks * 128), !(FIRST && ks == 0));
  }
  wg_commit();
}
DEVI void qkv_half(float (&a)[96], uint32_t sb16, int t, uint32_t sa, uint32_t sbb) {
  wg_fence();
  #pragma unroll
  for (int ks = 0; ks < 4; ks++)
    wgmma_ss_n192<1>(a, mkd<HI128>(((sb16 + (sa >> 4) + t * 512) | 0x10000u) + ks * 2), mkd<HI128>(((sb16 + (sbb >> 4)) | ((8192u >> 4) << 16)) + ks * 128), 1);
  wg_commit();
}
template<bool FIRST> DEVI void wo_block(float (&acc)[64], uint32_t sb16, int s, int wg) {
  uint32_t a16 = (sb16 + (w_off(s) >> 4) + wg * 256) | 0x10000u, b16 = (sb16 + (w_off(s) >> 4) + 1024) | ((8192u >> 4) << 16);
  wg_fence();
  #pragma unroll
  for (int ks = 0; ks < 4; ks++)
    wgmma_ss_n128<1>(acc, mkd<HI64>(a16 + (ks >> 1) * 512 + (ks & 1) * 2), mkd<HI128>(b16 + ks * 128), !(FIRST && ks == 0));
  wg_commit();
}
DEVI void consumer(const Params& P, uint32_t sb, int wg) {
  const int w = uni((threadIdx.x >> 5) & 3);
  #define LAYER uni(mbar_test(BAR(B_RES), 0))
  #define IDS L = LAYER; const int tid = fresh_tid(), lane = tid & 31
  const uint32_t ids = uni(P.map[blockIdx.x]);
  const int bi = (ids >> 4) & 7, rh = ids & 1, bc = (ids & 15) >> 1, fid = ids >> 8;
  const int tX = 3 - wg, tY = wg;
  constexpr uint32_t sb16 = 1024 >> 4;
  #pragma unroll 1
  while (true) {
    int L = LAYER;
    {
      float aX[96], aY[96];
      const bool lead = fresh_tid() == 0;
      if (L) mbar_wait(BAR(B_XRDY + wg * 2 + 1), 0);
      mbar_wait(BAR(B_FULLQ), 0);
      PROFW(threadIdx.x == 0, L * 8 + 1);
      qkv_block<true>(aX, aY, sb16, 0, tX, tY);
      #pragma unroll 1
      for (int n = 1, s = 1, ps = 0, ph = 0; n < 14; n++) {
        mbar_wait(BAR(B_FULLQ + s), ph ^ (s ? L : 0));
        PROFD(threadIdx.x == 0 && L && (n == 2 || n == 3 || n == 7 || n == 11 || n == 13), n == 2 ? 48 : 49 + (n >> 2));
        qkv_block<false>(aX, aY, sb16, s, tX, tY);
        wg_wait<1>(); if (lead) mbar_arrive(BAR(B_EMPTYQ + ps));
        ps = s; if (s == 2) { s = 0; ph ^= 1; } else s++;
      }
      mbar_wait(BAR(B_ROW), L);
      IDS;
      const uint32_t pa = sb + PAR + (w * 16 + (lane >> 2)) * 8;
      float2 p0 = lds64f(pa + tX * 512), p1 = lds64f(pa + tX * 512 + 64), p2 = lds64f(pa + tY * 512), p3 = lds64f(pa + tY * 512 + 64);
      mean_step(aX, p0.y, p1.y, sb16 + (CS >> 4), lane & 3);
      mbar_wait(BAR(B_FULLQ + 2), L);
      qkv_half(aX, sb16, tX, SA2, SB2);
      mbar_wait(BAR(B_FULLQ), 1);
      qkv_half(aX, sb16, tX, 0, SB0);
      wg_wait<3>(); if (lead) mbar_arrive(BAR(B_EMPTYQ + 1));
      bar_sync(1, 256);
      qkv_half(aY, sb16, tY, SA2, SB2);
      wg_wait<1>(); keep(aX);
      const int srow = w * 16 + (lane & 15);
      const uint32_t x0 = sb + srow * 64 + (((lane >> 4) ^ ((srow >> 1) & 3)) << 4), xX = x0 + (4 + tX) * 8192, xY = x0 + (4 + tY) * 8192;
      qkv_store<8>(aX, p0.x, p1.x, xX + KVA); qkv_store<16>(aX, p0.x, p1.x, xX + KVA + 4096);
      if (!L) warp_signal(BAR(B_KVRDY + wg * 2));
      qkv_half(aY, sb16, tY, 0, SB0);
      mean_step(aY, p2.y, p3.y, sb16 + (CS >> 4), fresh_tid() & 3);
      mbar_wait(BAR(B_PAR), L);
      const int l3 = fresh_tid() & 3, prow = (int)uni(lds32(sb + INFO)) - bi * 256;
      const bool pmine = (prow >> 4) == tX * 4 + w || (prow >> 4) == tY * 4 + w;
      const uint32_t poff = sb + (prow & 63) * 64 + ((l3 ^ ((prow >> 1) & 3)) << 4);
      if (pmine) { __syncwarp(); if (lane < 8) sts128(poff + KVA + (4 + (prow >> 6)) * 8192 + (lane >> 2) * 4096, lds128(sb + PATCH + 128 + (lane >> 2) * 128 + l3 * 16)); }
      if (L) warp_signal(BAR(B_KVRDY + wg * 2));
      wg_wait<2>(); if (lead) mbar_arrive(BAR(B_EMPTYQ + 2));
      mbar_wait(BAR(B_EMPTYQ + 2), L);
      qkv_store<12>(aX, p0.x, p1.x, xX + KVB); qkv_store<20>(aX, p0.x, p1.x, xX + KVB + 4096);
      wg_wait<0>(); keep(aY);
      if (lead) mbar_arrive(BAR(B_EMPTYQ));
      PROFW(threadIdx.x == 0, L * 8 + 2);
      qkv_store<8>(aY, p2.x, p3.x, xY + KVA); qkv_store<16>(aY, p2.x, p3.x, xY + KVA + 4096);
      qkv_store<12>(aY, p2.x, p3.x, xY + KVB); qkv_store<20>(aY, p2.x, p3.x, xY + KVB + 4096);
      p0.x *= QSCALE; p1.x *= QSCALE; p2.x *= QSCALE; p3.x *= QSCALE;
      mbar_wait(BAR(B_EMPTYQ), 1);
      qkv_store<0>(aX, p0.x, p1.x, x0 + QO + tX * 4096); qkv_store<4>(aX, p0.x, p1.x, x0 + QO + 16384 + tX * 4096);
      qkv_store<0>(aY, p2.x, p3.x, x0 + QO + tY * 4096); qkv_store<4>(aY, p2.x, p3.x, x0 + QO + 16384 + tY * 4096);
      if (pmine) {
        __syncwarp();
        if (lane < 24) sts128(poff + (lane < 8 ? QO + (lane >> 2) * 16384 + (prow >> 6) * 4096 : ((lane & 4) ? KVB : KVA) + (4 + (prow >> 6)) * 8192 + (lane >> 4) * 4096),
                              lds128(sb + PATCH + lane * 16));
      }
      fence_async_smem();
      warp_signal(BAR(B_KVRDY + wg * 2 + 1));
      bar_sync(1, 256);
    }
    PROFW(threadIdx.x == 0, L * 8 + 3);
    {
      IDS;
      float s0[32], s1[32], sx[32], o[20], op[20];
      uint32_t p0[16], p1[16], px[16], msk[9];
      const int tdiag = w * 16 + (lane >> 2) - 2 * (lane & 3);
      #pragma unroll
      for (int e = 0; e < 9; e++) msk[e] = ((8 * e - 8 > tdiag) ? 0xFFFFu : 0u) | ((8 * e - 7 > tdiag) ? 0xFFFF0000u : 0u);
      keep(msk);
      const uint32_t ones = (sb16 + (ONES >> 4)) << 16;
      const uint32_t qX = (sb16 + (QO >> 4) + tX * 256) | 0x10000u, qY = (sb16 + (QO >> 4) + tY * 256) | 0x10000u;
      const uint32_t kXB = (sb16 + (KVB >> 4) + tX * 512) | 0x10000u;
      uint32_t redo = 0;
      const uint32_t ost = sb + QO + (w * 16 + (lane & 15)) * 64 + (((lane >> 4) ^ ((lane >> 1) & 3)) << 4);
      #define QK(s, q, k) do { wg_fence(); qk_issue(s, q, k); wg_commit(); } while (0)
      #define QK2(q, k) do { wg_fence(); qk_issue(s1, q, k); qk_issue(sx, q, (k) + 2048); wg_commit(); } while (0)
      #define VB(v, b) ((v) + VOFF((b) * 512))
      QK(s0, qX + 1024, kXB + 1536);
      #pragma unroll
      for (int e = 0; e < 20; e++) o[e] = 0.f;
      wg_wait<0>(); keep(s0);
      #pragma unroll 1
      for (int h = 1; h >= 0; h--) {
        const uint32_t kXA = kXB - ((KVB - KVA) >> 4), kX = h ? kXB : kXA, vX = VOFF((kX & 0xffffu) + 256) + ones;
        QK(s1, qX + h * 1024, kX + 1024);
        #pragma unroll
        for (int e = 0; e < 20; e++) op[e] = o[e];
        keep(op);
        exp_pv<0, 4>(s0, p0, o, VB(vX, 3), false); wg_commit();
        wg_wait<1>(); keep(s1);
        exp_pv<0, 2>(s1, p1, o, VB(vX, 2), true);
        bar_sync(h ? 12 + wg : 4 + wg * 4, h ? 128 : 160);
        QK(s0, qX, kXA + 512 + h * 1024);
        exp_pv<2, 4>(s1, p1, o, VB(vX, 2), true); wg_commit();
        wg_wait<0>(); keep(s0); keep(p0); keep(p1); keep(o);
      }
      #pragma unroll 1
      for (int h = 0; h < 2; h++) {
        const uint32_t kb16 = sb16 + ((h ? KVB : KVA) >> 4), kY = (kb16 + tY * 512) | 0x10000u, qy = qY + h * 1024;
        const uint32_t onesP = bi ? ones : (kb16 + 1984) << 16;
        const uint32_t vX = VOFF(kb16 + tX * 512 + 256), vY = VOFF(kb16 + tY * 512 + 256);
        uint32_t ob[8];
        QK2(qX + h * 1024, (kb16 + tX * 512) | 0x10000u);
        exp_pv<0, 4>(s0, p0, o, VB(vX + (wg ? onesP : ones), 1), true); wg_commit();
        wg_wait<1>(); keep(s1); keep(sx);
        QK(s0, qy, kY + 1536);
        exp_pv2(s1, sx, p1, px, o, vX + onesP, VB(vX + ones, 4), msk, tdiag); wg_commit();
        wg_wait<1>(); keep(s0); keep(p0);
        QK(s1, qy, kY + 1024);
        exp_pack<0, 4>(s0, p0);
        wg_wait<1>(); keep(o); keep(p1); keep(px);
        bool ok = attn_pack(o, ob); keep(ob);
        exp_pv<0, 4, 1>(s0, p0, o, VB(vY + (wg ? ones : onesP), 3), false); wg_commit();
        attn_store(ob, ok, ost + (h * 4 + tX) * 4096, sb, BAR(B_ORDY + wg * 4 + h * 2)); redo |= ok ? 0u : 1u << (h * 2);
        wg_wait<1>(); keep(s1);
        exp_pv<0, 2>(s1, p1, o, VB(vY + onesP, 2), true);
        bar_sync(5 + wg * 4 + h * 2, 160);
        QK(s0, qy, kY + 512);
        exp_pv<2, 4>(s1, p1, o, VB(vY + onesP, 2), true); wg_commit();
        wg_wait<1>(); keep(s0); keep(p0);
        QK2(qy, kY);
        exp_pv<0, 4>(s0, p0, o, VB(vY + onesP, 1), true); wg_commit();
        wg_wait<1>(); keep(s1); keep(sx); keep(p1);
        bar_sync(6 + wg * 4, h ? 128 : 160);
        QK(s0, h ? qy : qX + 1024, kXB + 512);
        exp_pv2(s1, sx, p1, px, o, vY + onesP, VB(vY + ones, 4), msk, tdiag); wg_commit();
        wg_wait<0>(); keep(o); keep(s0); keep(p0); keep(p1); keep(px);
        ok = attn_pack(o, ob); attn_store(ob, ok, ost + (h * 4 + tY) * 4096, sb, BAR(B_ORDY + wg * 4 + h * 2 + 1)); redo |= ok ? 0u : 2u << (h * 2);
        #pragma unroll
        for (int e = 0; e < 20; e++) o[e] = op[e];
      }
      #undef QK
      #undef QK2
      #undef VB
      if (redo) {
        #pragma unroll 1
        for (int u = 0; u < 4; u++) if ((redo >> u) & 1) {
          const int h = u >> 1, t = (u & 1) ? tY : tX;
          attn_exact(sb + QO + (h * 4 + t) * 4096, sb + (h ? KVB : KVA), t, bi > 0, BAR(B_ORDY + wg * 4 + u));
        }
      }
    }
    PROFW(threadIdx.x == 0, L * 8 + 4);
    {
      IDS;
      const int t256 = wg * 128 + tid;
      float acc[64];
      const int tt = wg ^ rh;
      const int grow = bi * 256 + rh * 128 + tt * 64 + w * 16 + (lane >> 2);
      float al0 = 1.f, be0 = 0.f, al1 = 1.f, be1 = 0.f;
      const int idx0 = (int)uni(lds32(sb + INFO));
      const uint32_t tag = lds32(sb + INFO + 8) + L;
      uint4* const sp = &P.g->statP[bc][grow + (lane & 1) * 8];
      uint4* const yp = &P.g->yP[t256 >> 1][min(fid, 111)][t256 & 1];
      mbar_wait(BAR(B_FULLW), L);
      PROFW(t256 == 0, L * 8 + 5);
      wo_block<true>(acc, sb16, 0, tt);
      if (!(lane & 2)) st_ll(sp, 0u, 0u, 0u, 0u);
      uint4 fa = make_uint4(0u, 0u, 0u, 0u), fb = fa;
      uint2 wd[4];
      if (L) {
        if (fid < 112) st_ll(yp, 0u, 0u, 0u, 0u);
        fa = ld_ll(&P.g->statF[grow]); fb = ld_ll(&P.g->statF[grow + 8]);
      }
      #pragma unroll
      for (int e = 0; e < 4; e++) { wd[e] = make_uint2(0u, 0u); if (L) wd[e] = ldg_stream((const uint2*)(WDSRC) + t256 + (28 + e) * 256); }
      #pragma unroll 1
      for (int n = 1, q = 1, pq = 0; n < 16; n++) {
        mbar_wait(BAR(B_FULLW + q), w_par(n, q, L));
        PROFD(t256 == 0 && !L && (n == 4 || n == 7 || n == 8 || n == 12), (n == 7 ? 63 : 41 + (n >> 2)));
        wo_block<false>(acc, sb16, q, tt);
        wg_wait<1>(); if (tid == 0) mbar_arrive(BAR(B_EMPTYW + pq));
        pq = q; q = w_next(n, q);
      }
      if (L) {
        float r0 = rsqrtf(__uint_as_float(fa.y) + LN_EPS), r1 = rsqrtf(__uint_as_float(fb.y) + LN_EPS);
        if (grow != idx0) { al0 = 1.f + r0; be0 = -__uint_as_float(fa.x) * r0; }
        if (grow + 8 != idx0) { al1 = 1.f + r1; be1 = -__uint_as_float(fb.x) * r1; }
      }
      mbar_wait(BAR(B_RES), L);
      const int srow = tt * 64 + w * 16 + (lane & 15);
      const uint32_t ra = sb + rh * 16384 + srow * 128, sw = ((lane >> 4) ^ (srow & 7)) << 4;
      if ((idx0 >> 4) == bi * 16 + rh * 8 + tt * 4 + w) {
        int r = idx0 & 127;
        if (lane < 16) sts128(sb + (lane >> 3) * 32768 + rh * 16384 + r * 128 + (((lane & 7) ^ (r & 7)) << 4), lds128(sb + X2SEG + lane * 16));
        __syncwarp();
      }
      uint32_t rs[32];
      #pragma unroll
      for (int jj = 0; jj < 8; jj++) ldsm_x4((ra + (jj >> 2) * 32768) + (sw ^ ((jj & 3) << 5)), rs[4 * jj], rs[4 * jj + 1], rs[4 * jj + 2], rs[4 * jj + 3]);
      float rf[64];
      #pragma unroll
      for (int e = 0; e < 32; e++) { rf[2 * e] = fmaf(bf_lo(rs[e]), (e & 1) ? al1 : al0, (e & 1) ? be1 : be0); rf[2 * e + 1] = fmaf(bf_hi(rs[e]), (e & 1) ? al1 : al0, (e & 1) ? be1 : be0); }
      keep(rf);
      mbar_wait(BAR(B_RES), L);
      wg_wait<0>(); keep(acc);
      if (tid == 0) mbar_arrive(BAR(B_EMPTYW + 5));
      PROFW(t256 == 0, L * 8 + 6);
      #pragma unroll
      for (int jj = 0; jj < 8; jj++) {
        float* a = acc + 8 * jj;
        #pragma unroll
        for (int e = 0; e < 8; e++) a[e] += rf[8 * jj + e];
        stsm_x4((ra + (jj >> 2) * 32768) + (sw ^ ((jj & 3) << 5)), pack_bf16(a[0], a[1]), pack_bf16(a[2], a[3]), pack_bf16(a[4], a[5]), pack_bf16(a[6], a[7]));
        if (jj == 7) fence_async_smem();
        if ((jj & 3) == 3) warp_signal(BAR(B_XRDY + wg * 2 + (jj >> 2)));
      }
      {
        float s1a = 0.f, s2a = 0.f, da = 0.f, s1b = 0.f, s2b = 0.f, db = 0.f;
        #pragma unroll
        for (int j = 0; j < 16; j++) {
          const float* a = acc + 4 * j; float2 wv = lds64f(sb + WR + j * 32 + (lane & 3) * 8);
          s1a += a[0] + a[1]; s1b += a[2] + a[3];
          s2a = fmaf(a[0], a[0], s2a); s2b = fmaf(a[2], a[2], s2b); s2a = fmaf(a[1], a[1], s2a); s2b = fmaf(a[3], a[3], s2b);
          da = fmaf(a[0], wv.x, da); db = fmaf(a[2], wv.x, db); da = fmaf(a[1], wv.y, da); db = fmaf(a[3], wv.y, db);
        }
        bool odd = lane & 1;
        float u1 = (odd ? s1b : s1a) + __shfl_xor_sync(0xffffffffu, odd ? s1a : s1b, 1);
        float u2 = (odd ? s2b : s2a) + __shfl_xor_sync(0xffffffffu, odd ? s2a : s2b, 1);
        float u3 = (odd ? db : da) + __shfl_xor_sync(0xffffffffu, odd ? da : db, 1);
        u1 += __shfl_xor_sync(0xffffffffu, u1, 2); u2 += __shfl_xor_sync(0xffffffffu, u2, 2); u3 += __shfl_xor_sync(0xffffffffu, u3, 2);
        if (!(lane & 2)) st_ll(sp, __float_as_uint(u1), __float_as_uint(u2), __float_as_uint(u3), tag);
      }
      PROFW(t256 == 0, L * 8 + 7);
      if (L) {
        mbar_wait(BAR(B_PAR), 0);
        { float2 pa = lds64f(sb + PAR + (grow & 127) * 8), pb = lds64f(sb + PAR + (grow & 127) * 8 + 64); al0 = pa.x; be0 = pa.y; al1 = pb.x; be1 = pb.y; }
        #pragma unroll
        for (int j = 0; j < 16; j++) {
          rs[2 * j] = pack_bf16(fmaf(acc[4 * j], al0, be0), fmaf(acc[4 * j + 1], al0, be0));
          rs[2 * j + 1] = pack_bf16(fmaf(acc[4 * j + 2], al1, be1), fmaf(acc[4 * j + 3], al1, be1));
        }
        const int idx1 = (int)lds32(sb + INFO + 4);
        #pragma unroll
        for (int jj = 0; jj < 8; jj++) stsm_x4((ra + (jj >> 2) * 32768) + (sw ^ ((jj & 3) << 5)), rs[4 * jj], rs[4 * jj + 1], rs[4 * jj + 2], rs[4 * jj + 3]);
        __syncwarp();
        {
          const int r0 = (grow & ~15) + (lane >> 4), skip = idx1 - r0;
          const uint32_t a0 = sb + ((lane >> 3) & 1) * 32768 + (r0 & 255) * 128 + (((lane & 7) ^ (lane >> 4)) << 4);
          uint4* dst = (uint4*)(P.out + (size_t)r0 * 1024 + bc * 128) + (lane & 15);
          #pragma unroll
          for (int it = 0; it < 8; it++) { uint4 v = lds128((a0 + it * 256) ^ ((it & 3) << 5)); if (skip != 2 * it) dst[it * 256] = v; }
        }
        PROFW(t256 == 0, 16);
        if (fid < 112) {
          bar_sync(3, 384);
          const float act = swiglu(lds32f(sb + PAR + 1024 + lane * 4), lds32f(sb + PAR + 1152 + lane * 4));
          PROFW(t256 == 0, 26);
          float y0 = 0.f, y1 = 0.f, y2 = 0.f, y3 = 0.f;
          sts32f(sb + HV + t256 * 4, act);
          __syncwarp();
          mbar_wait(BAR(B_FULLW + 2), 0);
          #pragma unroll 1
          for (int n = 7; n >= 0; n--) {
            const uint4 a4 = lds128(sb + HV + (t256 >> 5) * 128 + n * 16);
            const uint32_t src = sb + t256 * 8 + (n > 4 ? QO + (n - 5) * 8192 : ((n - 1) & 2) * 16384 + ((n - 1) & 1) * 8192 + (rh ^ 1) * 16384);
            #pragma unroll
            for (int e = 0; e < 4; e++) {
              const float av = __uint_as_float(e == 0 ? a4.x : (e == 1 ? a4.y : (e == 2 ? a4.z : a4.w)));
              y0 = fmaf(bf_lo(wd[e].x), av, y0); y1 = fmaf(bf_hi(wd[e].x), av, y1); y2 = fmaf(bf_lo(wd[e].y), av, y2); y3 = fmaf(bf_hi(wd[e].y), av, y3);
              const float2 v = lds64f(src + e * 2048); wd[e] = make_uint2(__float_as_uint(v.x), __float_as_uint(v.y));
            }
          }
          st_ll(yp, __float_as_uint(y0), __float_as_uint(y1), __float_as_uint(y2), (__float_as_uint(y3) & ~255u) | (lds32(sb + INFO + 12) + 1));
          PROFW(t256 == 0, 27);
        }
        return;
      }
    }
  }
  #undef IDS
  #undef LAYER
}

DEVI void loader(const Params& P, uint32_t sb) {
  const int lane = threadIdx.x & 31;
  const int bid = uni(BID), bi = bid >> 4, bp = bid & 15, rh = bp & 1, bc = bp >> 1;
  uint32_t phq = 0, tag = 0;
  #pragma unroll 1
  for (int L = 0; L < 2; L++) {
    int s = 0;
    uint32_t rdy = 0;
    #pragma unroll 1
    for (int n = L ? 0 : 3; n < 16; n++) {
      int kb = L ? kb_order(bc, n) : n;
      mbar_wait(BAR(B_EMPTYQ + s), (phq >> s) & 1);
      phq ^= 1u << s;
      if (L && n == 1) { mbar_wait(BAR(B_XRDY + 1), 0); mbar_wait(BAR(B_XRDY + 3), 0); }
      if (lane == 0) {
        mbar_expect_tx(BAR(B_FULLQ + s), L && n < 2 ? 40960 : 57344);
        tma_3d_h(sb + qb_off(s), &P.mWq, bp * 64, kb * 64, 0, BAR(B_FULLQ + s), L && n >= QEF_N ? POL_FIRST : POL_NORMAL);
        if (!L) tma_2d(sb + qa_off(s), &P.mX, kb * 64, bi * 256, BAR(B_FULLQ + s));
      }
      if (L && n >= 2) {
        if (((rdy >> (2 * kb)) & 3) != 3) {
          do { rdy = __ballot_sync(0xffffffffu, ld_rlx(&P.g->flagX[bi][lane]) == tag); } while (((rdy >> (2 * kb)) & 3) != 3);
          fence_async_glob();
        }
        if (n == 3 || n == 4) mbar_wait(BAR(B_XFREE + n - 3), 0);
        if (lane == 0) bulk_g2s_h(sb + qa_off(s), P.g->x[bi][kb], 32768, BAR(B_FULLQ + s), POL_X);
      }
      PROFY(L && lane == 0 && (n == 2 || n == 3 || n == 9), n == 9 ? 60 : 56 + n);
      if (L && n == 2) { mbar_wait(BAR(B_FULLQ), 0); mbar_wait(BAR(B_FULLQ + 1), 1); if (lane < 2) mbar_arrive_peer(BAR(B_XFREE + lane)); }
      s = (s == 2) ? 0 : s + 1;
    }
    for (int q = 0; q < 3; q++) mbar_wait(BAR(B_EMPTYQ + q), (phq >> q) & 1);
    mbar_wait(BAR(B_PAR), L);
    tag = lds32(sb + INFO + 8) + L;
    #pragma unroll 1
    for (int q = 0; q < 4; q++) {
            if (bi) {
        const unsigned* f = &P.g->flagKV[bid - 16][q];
        while (ld_rlx(f) != tag);
        fence_async_glob();
      }
      if (lane == 0) {
        mbar_expect_tx(BAR(B_KVFULL + q), 16384);
        bulk_g2s_h(sb + ((q >> 1) ? KVB : KVA) + ((q & 1) ? 0 : 16384), bi ? P.g->kv[bid - 16][q] : P.g->zero, 16384, BAR(B_KVFULL + q));
      }
      PROFY(!L && lane == 0 && bi && q != 2, 34 + (q + 1) / 2);
    }
    mbar_wait(BAR(B_ORDY), L); mbar_wait(BAR(B_ORDY + 4), L);
    {
      const uint4* src = P.g->o[bi][0][0][rh];
      rdy = 0;
      #pragma unroll 1
      for (int n = 0, q = 0; n < 16; q = w_next(n, q), n++) {
        const int j = wo_order(bc, n);
        if (((rdy >> (2 * j)) & 3) != 3) {
          do { rdy = __ballot_sync(0xffffffffu, ld_rlx(&P.g->flagO[bi][lane]) == tag); } while (((rdy >> (2 * j)) & 3) != 3);
          fence_async_glob();
        }
        if (n >= 2) mbar_wait(n < 6 ? BAR(B_HAFREE + (n >> 2)) : BAR(B_EMPTYW + q), n < 6 ? L : w_par(n - 6, q, L));
        if (n == THR_N) mbar_wait(BAR(B_OFREE), L);
        if (lane == 0) { mbar_expect_tx(BAR(B_FULLW + q), 16384); bulk_g2s_h(sb + w_off(q), src + j * 2048, 16384, BAR(B_FULLW + q)); }
      }
    }
    mbar_wait(BAR(B_OFREE), L);
  }
}

DEVI void ffn_prefetch(const Params& P, int q) {
  bulk_prefetch(q < 16 ? ((q & 1) ? P.wu : P.wg) + ((q >> 1) * 128 + blockIdx.x) * 3584 : P.wd + (min(FID, 111) * 8 + q - 16) * 4096, q < 16 ? 7168 : 8192);
}
DEVI void storer(const Params& P, uint32_t sb, int wg) {
  const int bid = uni(BID), bi = bid >> 4, rh = bid & 1, bc = (bid & 15) >> 1;
  const bool one = (threadIdx.x & 31) == 0;
  char* const g = (char*)P.g;
  #pragma unroll 1
  for (int L = 0; L < 2; L++) {
    mbar_wait(BAR(B_PAR), L);
    const uint32_t tag = lds32(sb + INFO + 8) + L;
    if (wg) { mbar_wait(BAR(B_KVRDY), L); mbar_wait(BAR(B_KVRDY + 2), L); const uint32_t t0 = clk(); while (clk() - t0 < KV_D) __nanosleep(40); }
    #pragma unroll 1
    for (int u = 0; u < 2 + 4 * wg; u++) {
      const int h = u < 2 ? u : u >> 2, hi = (u & 1) ^ 1;
      uint32_t src, dst, fl, b0, b1;
      if (u < 2) {
        src = (h ? KVB : KVA) + (3 - wg) * 16384; dst = offsetof(Scratch, kv) + (bid * 4 + h * 2 + wg) * 16384; fl = offsetof(Scratch, flagKV) + (bid * 32 + h * 2 + wg) * 4;
        b0 = BAR(B_KVRDY + ((u | wg) ? 1 : 0)); b1 = b0 + 16;
      } else {
        src = QO + (h * 2 + hi) * 8192; dst = offsetof(Scratch, o) + ((((bi * 2 + h) * 8 + bc) * 2 + hi) * 2 + rh) * 8192;
        fl = offsetof(Scratch, flagO) + (bi * 32 + h * 16 + (bid & 15)) * 4;
        b0 = BAR(B_ORDY + u - 2); b1 = b0 + 32;
      }
      mbar_wait(b0, L); mbar_wait(b1, L);
      fence_async_smem();
      PROFY(one && !L && u == 3 * wg, u ? 46 : 8);
      if (one && (u >= 2 || bi < 7)) bulk_s2g(g + dst, sb + src, u < 2 ? 16384 : 8192);
      if (one && u == 5) mbar_arrive(BAR(B_HAFREE + 1));
      if (u == 2 || u == 4) continue;
      bulk_wait<0>();
      PROFY(one && !L && u == 3 * wg, u ? 61 : 62);
      fence_rel();
      if (one) { st_rlx((unsigned*)(g + fl), tag); if (!wg || u > 2) mbar_arrive(BAR(B_HAFREE + h + (wg & h))); }
      PROFY(one && !L && (u > 2 || u == wg), u > 2 ? (u == 3 ? 38 : 54) : 32 + u);
    }
    if (L == 0) {
      char* dst = g + (offsetof(Scratch, x) + (bi * 16 + 2 * bc) * 32768 + rh * 16384);
      unsigned* f = (unsigned*)(g + (offsetof(Scratch, flagX) + (bi * 32 + bc * 4 + rh) * 4));
      const uint32_t a = sb + rh * 16384;
      if (wg == 0) {
        mbar_wait(BAR(B_XRDY), 0); mbar_wait(BAR(B_XRDY + 2), 0);
        fence_async_smem();
        PROFY(one, 41);
        if (one) bulk_s2g(dst, a, 16384);
        bulk_wait<0>();
        PROFY(one, 45);
        if (one) { mbar_arrive(BAR(B_XFREE)); mbar_arrive(BAR(B_PFREE)); }
        fence_rel();
        mbar_wait(BAR(B_XRDY + 1), 0); mbar_wait(BAR(B_XRDY + 3), 0);
        if (one) { st_rlx(f, tag); bulk_s2g(dst + 32768, a + 32768, 16384); }
        PROFY(one, 56);
        bulk_wait<0>();
        if (one) mbar_arrive(BAR(B_XFREE + 1));
        fence_rel();
        if (one) st_rlx(f + 2, tag);
        PROFY(one, 57);
      } else {
        mbar_wait(BAR(B_XRDY + 1), 0); mbar_wait(BAR(B_XRDY + 3), 0);
        mbar_wait(BAR(B_PFREE), 0);
        if (one) bulk_s2peer(a, 16384, BAR(B_FULLQ));
        { const uint32_t t0 = clk(); while (clk() - t0 < XD_D); }
        if (one) bulk_s2peer(a + 32768, 16384, BAR(B_FULLQ + 1));
      }
      if (wg == 0) {
        uint32_t t0 = clk() + PF1_D;
        #pragma unroll 1
        for (int q = PF1_S; q < PF1_E; q++) { while ((int)(clk() - t0) < 0) __nanosleep(50); if (one) ffn_prefetch(P, q); t0 += PF1_T; }
      }
    }
  }
}

DEVI void stg_issue(const Params& P, int c, uint32_t d, uint32_t du, uint32_t b) {
  mbar_expect_tx(b, 16384);
  if (c < 8) { tma_2d_h(d, &P.mWg, FID * 32, c * 128, b, POL_G); tma_2d_h(d + du, &P.mWu, FID * 32, c * 128, b, POL_U); }
  else if (c < 12) tma_3d_h(d, &P.mWd, 0, FID * 32 + (c - 8) * 8, 0, b, POL_D);
  else tma_2d_h(d, &P.mWp, (c - 12) * 1024 + (BID >> 2) * 32, (BID & 3) * 256, b, POL_EF);
}
DEVI void stager(const Params& P, uint32_t sb) {
  {
    const int b = blockIdx.x;
    uint32_t t0 = clk();
    #pragma unroll 1
    for (int q = 0; q < PQ_N; q++) { bulk_prefetch(P.wqkv + (q * 128 + b) * 3072, 6144); while (clk() - t0 < PQ_T); t0 += PQ_T; }
    bulk_prefetch(P.wo + b * 8192, 16384);
    #pragma unroll 1
    for (int q = 0; q < PF0_N; q++) {
      while (clk() - t0 < PF0_T);
      t0 += PF0_T;
      ffn_prefetch(P, q);
    }
  }
  const int bid = BID, bi = bid >> 4, rh = bid & 1, bc = (bid & 15) >> 1;
  #pragma unroll 1
  for (int L = 0; L < 2; L++) {
    const int nch = L ? (FID < 112 ? 8 : 0) : 15;
    mbar_wait(BAR(B_KVFULL + W0_BAR), L);
    #pragma unroll 1
    for (int n = 0, q = 0; n < 16; q = w_next(n, q), n++) {
      if (n >= 2) mbar_wait(n < 6 ? BAR(B_HAFREE + (n >> 2)) : BAR(B_EMPTYW + q), n < 6 ? L : w_par(n - 6, q, L));
      if (n == THR_N) mbar_wait(BAR(B_OFREE), L);
      mbar_expect_tx(BAR(B_FULLW + q), 16384);
      tma_5d(sb + w_off(q) + 16384, &P.mWo, 0, 0, n >> 3, 2 * (wo_order(bc, n) & 7), 2 * bc, BAR(B_FULLW + q), L ? POL_EF : POL_NORMAL);
      if (n == 13) {
        mbar_expect_tx(BAR(B_RES), 32768);
        #pragma unroll 1
        for (int e = 0; e < 2; e++) {
          mbar_wait(BAR(B_EMPTYW + 2 + e), 1);
          if (L) bulk_g2s_h(sb + e * 32768 + rh * 16384, P.g->x[bi][2 * bc + e] + rh * 1024, 16384, BAR(B_RES));
          else tma_2d_h(sb + e * 32768 + rh * 16384, &P.mXh, bc * 128 + e * 64, bi * 256 + rh * 128, BAR(B_RES), POL_EF);
        }
      }
    }
    if (L && nch) {
      const bf16* src = WDSRC2;
      mbar_expect_tx(BAR(B_FULLW + 2), 32768); mbar_expect_tx(BAR(B_FULLW + 2), 24576);
      #pragma unroll 1
      for (int e = 0; e < 3; e++) bulk_g2s_h(sb + e * 32768 + (e < 2 ? (rh ^ 1) * 16384 : 0), src + e * 8192, e < 2 ? 16384 : 24576, BAR(B_FULLW + 2));
    }
    if (L == 0) { mbar_arrive_peer(BAR(B_PFREE)); mbar_wait(BAR(B_EMPTYW), 0); mbar_wait(BAR(B_EMPTYW + 1), 0); }
    #pragma unroll 1
    for (int c = FID < 112 ? 0 : 12, slot = 0; c < nch; c++, slot = slot == 2 ? 0 : slot + 1) {
      const int q = (c >> 1) + (c & 4) / 2;
      mbar_wait(L ? BAR(B_EMPTYW + q) : BAR(B_STGE + slot), L | ((0x71c7 >> c) & 1));
      #define CC c
      stg_issue(P, CC, L ? sb + w_off(q) + (c & 1) * 8192 : sb + STG + slot * 16384, 8192 << L, L ? BAR(B_FULLW + q) : BAR(B_STG + slot));
    }
  }
}
DEVI void sum8(uint4 v, float& s1, float& s2) {
  float e[8] = {bf_lo(v.x), bf_hi(v.x), bf_lo(v.y), bf_hi(v.y), bf_lo(v.z), bf_hi(v.z), bf_lo(v.w), bf_hi(v.w)};
  #pragma unroll
  for (int q = 0; q < 8; q++) { s1 += e[q]; s2 = fmaf(e[q], e[q], s2); }
}
DEVI uint4 norm8(uint4 x, float m, float rs) {
  #define HN(v) pack_bf16((bf_lo(v) - m) * rs, (bf_hi(v) - m) * rs)
  return make_uint4(HN(x.x), HN(x.y), HN(x.z), HN(x.w));
  #undef HN
}
DEVI void put_f32(uint4 b, uint32_t d, uint32_t d2) {
  sts128(d, make_uint4(b.x << 16, b.x & 0xffff0000u, b.y << 16, b.y & 0xffff0000u));
  sts128(d + d2, make_uint4(b.z << 16, b.z & 0xffff0000u, b.w << 16, b.w & 0xffff0000u));
}
DEVI void put_bf16(uint4 b, uint32_t d) {
  sts64f(d, __uint_as_float(b.x), __uint_as_float(b.y)); sts64f(d + 1024, __uint_as_float(b.z), __uint_as_float(b.w));
  fence_async_smem();
}
DEVI uint4 best4(uint32_t p) {
  uint4 a = lds128(p), b = lds128(p + 16), c = lds128(p + 32), d = lds128(p + 48);
  if (b.x > a.x) a = b;
  if (d.x > c.x) c = d;
  return c.x > a.x ? c : a;
}
#define FL(x) __uint_as_float(x)
#define UI(x) __float_as_uint(x)
DEVI void qkv_params(const Params& P, uint32_t sb, int row, uint32_t tag, bool second) {
  uint4 v0, v1; poll_ll2(&P.g->statF[row], &P.g->statF[row + 128], 0xffffffffu, tag, v0, v1);
  #pragma unroll 1
  for (int q = 0; q < 2; q++) {
    float var = FL(v0.y), c = rsqrtf(var + LN_EPS);
    if (second) { c += 1.f; c *= rsqrtf(fmaf(var * c, c, LN_EPS)); }
    const float mh = bf_round(FL(v0.x));
    sts64f(sb + PAR + q * 1024 + (row & 127) * 8, c, FL(pack_bf16(mh, FL(v0.x) - mh)));
    v0 = v1;
  }
  warp_signal(BAR(B_ROW));
}
DEVI void aux(const Params& P, uint32_t sb) {
  int tid = fresh_tid();
  #define lane (tid & 31)
  #define wq (tid >> 5)
  uint32_t ids = P.map[blockIdx.x], tag;
  #define bid ((int)(ids & 255))
  #define fid ((int)(ids >> 8))
  #define bi (bid >> 4)
  #define bp (bid & 15)
  #define bc (bp >> 1)
  #define FRESH() do { tid = fresh_tid(); uint4 z_ = ldsv128(sb + INFO2 + 16); ids = z_.y; tag = z_.z + L; idx = z_.w; } while (0)
  {
    const uint32_t epoch = ld_rlx(&P.g->epoch);
    if (tid == 0) {
      mbar_expect_tx(BAR(B_STG), 49152);
      tma_3d(sb + STG, &P.mWq, bp * 64, bi * 128, 0, BAR(B_STG));
      tma_3d(sb + STG + 24576, &P.mWq, bp * 64, bi * 128 + 64, 0, BAR(B_STG));
    }
    __syncwarp();
    sts64f(sb + ONES + tid * 8, FL(0x3F803F80u), FL(0x3F803F80u));
    float s1 = 0.f, s2 = 0.f;
    { uint4 v = __ldg((const uint4*)P.wr + tid);
      if ((tid >> 4) == bc) put_f32(v, sb + WR + (tid & 15) * 32, 16);
      sum8(v, s1, s2);
      #pragma unroll 1
      for (int o = 16; o; o >>= 1) s1 += __shfl_xor_sync(0xffffffffu, s1, o);
      sts32f(sb + INFO2 + wq * 4, s1); }
    const uint4* src = (const uint4*)(P.x0 + (size_t)bid * 16384) + (tid >> 3) * 128 + (tid & 7);
    s1 = 0.f; s2 = 0.f;
    #pragma unroll 1
    for (int it = 0; it < 16; it += 4) {
      uint4 v0 = __ldg(src + it * 8), v1 = __ldg(src + it * 8 + 8), v2 = __ldg(src + it * 8 + 16), v3 = __ldg(src + it * 8 + 24);
      #pragma unroll 1
      for (int q = 0; q < 4; q++) { sum8(v0, s1, s2); v0 = v1; v1 = v2; v2 = v3; }
    }
    #pragma unroll 1
    for (int o = 1; o < 8; o <<= 1) { s1 += __shfl_xor_sync(0xffffffffu, s1, o); s2 += __shfl_xor_sync(0xffffffffu, s2, o); }
    tag = ((epoch % 16383u) + 1u) << 2;
    if (tid == 0) { sts128(sb + INFO, make_uint4(0x40000000u, 0u, tag, ((epoch % 127u) + 1u) << 1)); sts128(sb + INFO2 + 16, make_uint4(epoch, ids, tag, 0x40000000u)); }
    float m = s1 * (1.f / 1024.f);
    if ((tid & 7) == 0) st_ll(&P.g->statF[bid * 16 + (tid >> 3)], UI(m), UI(fmaxf(fmaf(-m, m, s2 * (1.f / 1024.f)), 0.f)), 0u, tag);
    bar_sync(2, 128);
    mbar_wait_b(BAR(B_STG), 0);
    if (tid < 96) {
      s1 = 0.f; s2 = 0.f;
      #pragma unroll 4
      for (int r = 0; r < 128; r++) {
        uint32_t v = lds32(sb + STG + (r >> 6) * 24576 + wq * 8192 + (r & 63) * 128 + ((lane * 4) ^ ((r & 7) << 4)));
        s1 += bf_lo(v); s2 += bf_hi(v);
      }
      st_ll(&P.g->csP[bp][bi][tid], UI(s1), UI(s2), 0u, tag);
      s1 = 0.f; s2 = 0.f;
      #pragma unroll 1
      for (int q = 0; q < 8; q += 2) {
        uint4 a, b; poll_ll2(&P.g->csP[bp][q][tid], &P.g->csP[bp][q + 1][tid], 0xffffffffu, tag, a, b);
        s1 += FL(a.x) + FL(b.x); s2 += FL(a.y) + FL(b.y);
      }
      const uint32_t hi = pack_bf16(-s1, -s2);
      sts32(sb + CS + (tid >> 2) * 32 + (tid & 3) * 4, hi);
      sts32(sb + CS + (tid >> 2) * 32 + (tid & 3) * 4 + 16, pack_bf16(-s1 - bf_lo(hi), -s2 - bf_hi(hi)));
    }
    fence_async_smem();
    qkv_params(P, sb, bi * 256 + tid, tag, false);
  }
  int idx;
  #pragma unroll 1
  for (int L = 0; L < 2; L++) {
    FRESH();
    {
      if ((idx >> 8) == bi) {
        const uint4* src = &P.g->patch[bp * 8 + (tid >> 6) * 4][tid & 63];
        uint4 v0, v1, v2, v3; int it = 0;
        do { v0 = ld_ll(src); v1 = ld_ll(src + 64); v2 = ld_ll(src + 128); v3 = ld_ll(src + 192); if (++it > SPIN_MAX) __trap(); }
        while (!__all_sync(0xffffffffu, v0.w == tag && v1.w == tag && v2.w == tag && v3.w == tag));
        float q = (FL(v0.x) + FL(v1.x)) + (FL(v2.x) + FL(v3.x)), k = (FL(v0.y) + FL(v1.y)) + (FL(v2.y) + FL(v3.y)), v = (FL(v0.z) + FL(v1.z)) + (FL(v2.z) + FL(v3.z));
        q += __shfl_xor_sync(0xffffffffu, q, 1); k += __shfl_xor_sync(0xffffffffu, k, 1); v += __shfl_xor_sync(0xffffffffu, v, 1);
        bar_sync(2, 128);
        const uint32_t d = sb + PATCH + (tid & ~1), kv = pack_bf16(k, v);
        sts16(d, pack_bf16(q * QSCALE, 0.f)); sts16(d + 128, kv); sts16(d + 256, kv >> 16);
      }
      sts32(sb + INFO, idx);
      bar_sync(2, 128);
      if (tid == 0) mbar_arrive(BAR(B_PAR));
      PROFX(tid == 0, L ? 23 : 17);
    }
    mbar_wait_b(BAR(B_KVFULL + wq), L);
    bar_arrive(4 + wq, 160); bar_arrive(8 + wq, 160);
    FRESH();
    mbar_wait_b(BAR(B_OFREE), L);
    #define blk (bi * 2 + (bid & 1))
    if (tid < 33) st_ll(tid < 32 ? &P.g->row[blk][bc * 32 + tid] : &P.g->best[bc][blk], 0u, 0u, 0u, 0u);
    if (!L) {
        if (fid < 112) { st_ll(&P.g->yP[tid & ~1][fid][tid & 1], 0u, 0u, 0u, 0u); st_ll(&P.g->yP[tid | 1][fid][tid & 1], 0u, 0u, 0u, 0u); }
        if (tid < 80) st_ll(tid < 64 ? &P.g->patch[bid][tid] : &P.g->x2[(tid >> 1) & 7][2 * bid + (tid & 1)], 0u, 0u, 0u, 0u);
    }
    mbar_wait_b(BAR(B_XRDY + 1), L); mbar_wait_b(BAR(B_XRDY + 3), L);
    PROFX(tid == 0, 37 + L * 16);
    FRESH();
    {
      float s1 = 0.f, s2 = 0.f, d = 0.f;
      #pragma unroll 1
      for (int q = 0; q < 8; q += 4) {
        const uint4* src = &P.g->statP[q][blk * 128 + tid];
        uint4 v0, v1, v2, v3; int it = 0;
        do { v0 = ld_ll(src); v1 = ld_ll(src + 2048); v2 = ld_ll(src + 4096); v3 = ld_ll(src + 6144); if (++it > SPIN_MAX) __trap(); }
        while (!__all_sync(0xffffffffu, v0.w == tag && v1.w == tag && v2.w == tag && v3.w == tag));
        s1 += (FL(v0.x) + FL(v1.x)) + (FL(v2.x) + FL(v3.x)); s2 += (FL(v0.y) + FL(v1.y)) + (FL(v2.y) + FL(v3.y)); d += (FL(v0.z) + FL(v1.z)) + (FL(v2.z) + FL(v3.z));
      }
      PROFX(tid == 0, 39 + L * 16);
      uint4 a = lds128(sb + INFO2), b, c;
      float m = s1 * (1.f / 1024.f), var = fmaxf(fmaf(-m, m, s2 * (1.f / 1024.f)), 0.f), rs = rsqrtf(var + LN_EPS);
      uint32_t key = UI(fmaf(-m, (FL(a.x) + FL(a.y)) + (FL(a.z) + FL(a.w)), d) * rs);
      key ^= (uint32_t)((int)key >> 31) | 0x80000000u;
      uint32_t win = __ballot_sync(0xffffffffu, key == __reduce_max_sync(0xffffffffu, key));
      if (lane == __ffs(win) - 1) sts128(sb + RED + wq * 16, make_uint4(key, UI(m), UI(rs), (tag << 11) | (uint32_t)(blk * 128 + tid)));
      if (L) sts64f(sb + PAR + tid * 8, 1.f + rs, -m * rs);
      else if ((tid >> 4) == bc) st_ll(&P.g->statF[blk * 128 + tid], UI(m), UI(var), 0u, tag + 1);
      bar_sync(2, 128);
      if (wq == 0) {
        a = best4(sb + RED);
        float2 v = lds64f(sb + (lane >> 4) * 32768 + (a.w & 255) * 128 + (((lane & 15) * 8) ^ ((a.w & 7) << 4)));
        st_ll(&P.g->row[blk][bc * 32 + lane], UI(v.x), UI(v.y), 0u, tag);
        if (lane == 0) { st_ll(&P.g->best[bc][blk], a.x, a.y, a.z, a.w); sts32(sb + INFO + 4, a.w & 2047); }
        __syncwarp();
        if (L) {
          const float al = 1.f + FL(a.z), be = -FL(a.y) * FL(a.z);
          sts64f(sb + RED + 1792 + lane * 8, FL(pack_bf16(fmaf(bf_lo(UI(v.x)), al, be), fmaf(bf_hi(UI(v.x)), al, be))),
                                             FL(pack_bf16(fmaf(bf_lo(UI(v.y)), al, be), fmaf(bf_hi(UI(v.y)), al, be))));
        }
        if (lane < 2 - L) mbar_arrive(L ? BAR(B_PAR) : BAR(B_XFREE + lane));
      }
      PROFX(tid == 0, 18 + L * 6);
      FRESH();
      a = poll_ll(&P.g->best[bc][lane & 15], 0xfffff800u, tag << 11);
      win = __ffs(__ballot_sync(0xffffffffu, a.x == __reduce_max_sync(0xffffffffu, a.x))) - 1;
      idx = __shfl_sync(0xffffffffu, a.w, win) & 2047;
      PROFX(tid == 0, 19 + L * 6);
      poll_ll2(&P.g->row[win][tid], &P.g->row[win][tid + 128], 0xffffffffu, tag, c, b);
      c.z = b.x; c.w = b.y;
      a.x = __shfl_sync(0xffffffffu, a.x, win); a.y = __shfl_sync(0xffffffffu, a.y, win); a.z = __shfl_sync(0xffffffffu, a.z, win);
      sts32(sb + INFO2 + 28, idx);
      PROFX(tid == 0, 61 + L);
      b = norm8(c, FL(a.y), FL(a.z));
      if (L) put_bf16(b, sb + HV + tid * 8); else put_f32(b, sb + HV + tid * 16, 2048);
      if ((tid >> 1) == (bid & 63)) {
        sts128(sb + RED + 64 + (tid & 1) * 16, bid < 64 ? make_uint4(c.x, c.y, b.x, b.y) : make_uint4(c.z, c.w, b.z, b.w));
        sts32(sb + RED + 96, a.x);
      }
      bar_sync(2, 128);
      if (L) {
        PROFW(tid == 0, 29);
        if (uni(fid) < 112) {
          float d[4] = {0.f, 0.f, 0.f, 0.f};
          #pragma unroll 1
          for (int g = 0; g < 8; g++) {
            const int q = (g >> 1) + (g & 4) / 2;
            mbar_wait(BAR(B_FULLW + q), 0);
            const uint32_t ad = (64 + (w_off(q) >> 4) + (g & 1) * 512) | (1024u << 16), bd = (64 + (HV >> 4) + g * 16) | 0x10000u;
            wg_fence();
            #pragma unroll
            for (int ks = 0; ks < 8; ks++) wgmma_ss_n8<0, 1>(d, mkd<HI64>(ad + ks * 64), mkd<8>(bd + ks * 2), 1);
            wg_commit();
          }
          wg_wait<0>(); keep(d);
          if (!(lane & 3)) { sts32f(sb + PAR + 1024 + wq * 64 + lane, d[0]); sts32f(sb + PAR + 1056 + wq * 64 + lane, d[2]); }
          bar_arrive(3, 384);
        }
        if (wq == 0 && win != blk) *(float2*)(P.out + (size_t)lds32(sb + INFO + 4) * 1024 + bc * 128 + lane * 4) = lds64f(sb + RED + 1792 + lane * 8);
      }
    }
    #pragma unroll 1
    for (int st = L; st < 2; st++) {
      FRESH();
      float a[8] = {0.f, 0.f, 0.f, 0.f, 0.f, 0.f, 0.f, 0.f};
      if (L == 0 && fid < 112) {
        uint32_t ha = st ? sb + RED + 768 : sb + HV + ((wq & 1) * 64 + (lane >> 2)) * 4;
        uint32_t ph = st ? 0x1cu : 0x171u, bar = st ? BAR(B_STG + 2) : BAR(B_STG);
        uint32_t wa = sb + STG + wq * 4096 + (st ? 32768 + lane * 16 : (lane ^ (lane >> 3)) * 16);
        const uint32_t hx = st ? 256 : 512;
        const bool lead = lane == 0;
        uint4 vc = make_uint4(0u, 0u, 0u, 0u); float hc = 0.f;
        #pragma unroll 1
        do {
          mbar_wait(bar, ph & 1);
          PROFX(lead && threadIdx.x == 256 && st == 0 && (ph > 255 || ph < 4), 40 - 23 + __clz(ph));
          #pragma unroll
          for (int n = 0; n < 8; n++) { const uint4 v = lds128(wa + n * 512); const float h = lds32f(ha + n * 32); fma8(a, vc, hc); vc = v; hc = h; }
          __syncwarp();
          if (lead) mbar_arrive(bar - 8 * (B_STG - B_STGE));
          const bool wrap = bar == BAR(B_STG + 2);
          bar += wrap ? -16 : 8; wa += wrap ? -32768 : 16384; ha += hx;
          ph >>= 1;
        } while (ph != 1);
        fma8(a, vc, hc);
      }
      FRESH();
      if (st == 1) {
        const uint32_t t8 = lds32(sb + INFO + 12) + L;
        if (L == 0 && fid < 112) {
          const bool odd = lane & 1;
          #pragma unroll
          for (int e = 0; e < 4; e++) { float z = __shfl_xor_sync(0xffffffffu, odd ? a[e] : a[4 + e], 1); if (odd) a[e] = z; else a[4 + e] = z; }
          uint4* dst = &P.g->yP[tid & ~1][fid][tid & 1];
          st_ll(dst, UI(a[0]), UI(a[1]), UI(a[2]), (UI(a[3]) & ~255u) | t8);
          st_ll(dst + 224, UI(a[4]), UI(a[5]), UI(a[6]), (UI(a[7]) & ~255u) | t8);
          PROFX(tid == 0, 21);
        }
        if (!L) qkv_params(P, sb, bi * 256 + tid, tag + 1, true);
        if (tid == 0) { uint32_t k = lds32(sb + RED + 96); sts32f(sb + RED + 100, bf_round(__fdividef(1.f, 1.f + __expf(-bf_round(FL(k ^ (~(uint32_t)((int)k >> 31) | 0x80000000u))))))); }
        uint4 v0, v1;
        poll_ll2(&P.g->yP[bid][0][min(tid, 111)], &P.g->yP[bid][0][min(tid, 111) + 112], 255u, t8, v0, v1);
        const float lo = (tid < 112 && !(tid & 1)) ? 1.f : 0.f, hi = (tid < 112 && (tid & 1)) ? 1.f : 0.f;
        const float y0 = FL(v0.x) + FL(v1.x), y1 = FL(v0.y) + FL(v1.y), y2 = FL(v0.z) + FL(v1.z), y3 = FL((v0.w & ~255u) | 128u) + FL((v1.w & ~255u) | 128u);
        a[0] = y0 * lo; a[1] = y1 * lo; a[2] = y2 * lo; a[3] = y3 * lo; a[4] = y0 * hi; a[5] = y1 * hi; a[6] = y2 * hi; a[7] = y3 * hi;
      }
      sts32f(sb + RED + 256 + wq * 128 + ((lane & 3) * 8 + (lane >> 2)) * 4, fold8(a));
      bar_sync(2, 128);
      const uint32_t d = sb + RED + 256 + lane * 4;
      float z0 = lds32f(d) + lds32f(d + 128), z1 = lds32f(d + 256) + lds32f(d + 384);
      if (st == 0) {
        sts32f(sb + RED + 768 + lane * 32 + wq * 4, swiglu(z0, z1));
        bar_sync(2, 128); PROFX(tid == 0, 20); continue; }
      z0 += z1;
      z0 += __shfl_xor_sync(0xffffffffu, z0, 8); z0 += __shfl_xor_sync(0xffffffffu, z0, 16);
      uint32_t xw = lds32(sb + RED + 64 + (lane & 4) * 4 + (lane & 2) * 2), hw = lds32(sb + RED + 72 + (lane & 4) * 4 + (lane & 2) * 2);
      z0 = bf_round(((lane & 1) ? bf_hi(hw) : bf_lo(hw)) + bf_round(bf_round(z0) * lds32f(sb + RED + 100))) + ((lane & 1) ? bf_hi(xw) : bf_lo(xw));
      uint32_t v = pack_bf16(z0, __shfl_down_sync(0xffffffffu, z0, 1)), v2 = __shfl_down_sync(0xffffffffu, v, 2);
      if (L) { if (tid == 0 || tid == 4) *(uint2*)(P.out + (size_t)idx * 1024 + bid * 8 + tid) = make_uint2(v, v2); PROFW(tid == 0, 28); }
      else if ((tid & 3) == 0 && tid < 64) st_ll(&P.g->x2[tid >> 3][2 * bid + ((tid >> 2) & 1)], v, v2, 0u, tag + 1);
    }
    if (L == 0) {
      PROFX(tid == 0, 22);
      FRESH();
      uint4 x, y; poll_ll2(&P.g->x2[bi][tid], &P.g->x2[bi][tid + 128], 0xffffffffu, tag + 1, x, y);
      x.z = y.x; x.w = y.y;
      if (wq == (bc & 3)) sts64f(sb + X2SEG + lane * 8, FL(bc < 4 ? x.x : x.z), FL(bc < 4 ? x.y : x.w));
      float s1 = 0.f, s2 = 0.f;
      sum8(x, s1, s2);
      #pragma unroll
      for (int o = 16; o; o >>= 1) { s1 += __shfl_xor_sync(0xffffffffu, s1, o); s2 += __shfl_xor_sync(0xffffffffu, s2, o); }
      sts64f(sb + RED + wq * 8, s1, s2);
      bar_sync(2, 128);
      y = lds128(sb + RED); uint4 y2 = lds128(sb + RED + 16);
      float m = ((FL(y.x) + FL(y.z)) + (FL(y2.x) + FL(y2.z))) * (1.f / 1024.f);
      put_bf16(norm8(x, m, rsqrtf(fmaxf(fmaf(-m, m, ((FL(y.y) + FL(y.w)) + (FL(y2.y) + FL(y2.w))) * (1.f / 1024.f)), 0.f) + LN_EPS)), sb + HV + tid * 8);
      mbar_wait(BAR(B_STG), 1); mbar_wait(BAR(B_STG + 1), 0); mbar_wait(BAR(B_STG + 2), 0);
      bar_sync(2, 128);
      PROFX(tid == 0, 30);
      float d0[4] = {0.f, 0.f, 0.f, 0.f}, d1[4] = {0.f, 0.f, 0.f, 0.f}, d2[4] = {0.f, 0.f, 0.f, 0.f};
      const uint32_t bd = (64 + (HV >> 4) + uni(bid & 3) * 32) | 0x10000u;
      #pragma unroll 1
      for (int ks = 0; ks < 8; ks++) {
        const uint32_t ad = (64 + (STG >> 4) + ks * 128) | (64u << 16);
        wg_fence();
        wgmma_ss_n8<0, 1>(d0, mkd<HI64>(ad), mkd<8>(bd + ks * 4), 1);
        wgmma_ss_n8<0, 1>(d1, mkd<HI64>(ad + 1024), mkd<8>(bd + ks * 4), 1);
        wgmma_ss_n8<0, 1>(d2, mkd<HI64>(ad + 2048), mkd<8>(bd + ks * 4), 1);
        wg_commit();
      }
      wg_wait<0>(); keep(d0); keep(d1); keep(d2);
      FRESH();
      if ((lane & 3) == (wq >> 1)) {
        uint4* dst = &P.g->patch[bid][(wq & 1) * 32 + (lane >> 2) * 2 + (wq >> 1)];
        st_ll(dst, UI(d0[0]), UI(d1[0]), UI(d2[0]), tag + 1); st_ll(dst + 16, UI(d0[2]), UI(d1[2]), UI(d2[2]), tag + 1);
      }
      PROFX(tid == 0, 31);
    }
  }
  if (bid == 0 && tid == 0) P.g->epoch = lds32(sb + INFO2 + 16) + 1;
  #undef blk
  #undef bid
  #undef fid
  #undef bi
  #undef bp
  #undef bc
  #undef FRESH
  #undef lane
  #undef wq
}

__global__ void __cluster_dims__(2, 1, 1) __launch_bounds__(512, 1) fused_kernel(const __grid_constant__ Params P) {
  extern __shared__ __align__(1024) uint8_t smem_raw[];
  const uint32_t sb = smem_u32(smem_raw);
  PROFT(threadIdx.x == 0, 0);
  if (threadIdx.x == 0) {
    for (int s = 0; s < 3; s++) mbar_init(BAR(B_FULLQ + s), 1);
    asm volatile("fence.mbarrier_init.release.cluster;" ::: "memory");
    #pragma unroll 1
    for (int s = 0; s < 3; s++) {
      mbar_expect_tx(BAR(B_FULLQ + s), 57344);
      tma_2d(sb + qa_off(s), &P.mX, s * 64, (BID >> 4) * 256, BAR(B_FULLQ + s));
      tma_3d(sb + qb_off(s), &P.mWq, (BID & 15) * 64, s * 64, 0, BAR(B_FULLQ + s));
    }
    if ((sb & 0x3FFFFu) != 1024) __trap();
  } else if (threadIdx.x >= 32 + B_EMPTYQ && threadIdx.x <= 32 + B_COUNT) {
    const int b = threadIdx.x == 32 + B_COUNT ? B_ROW : threadIdx.x - 32;
    const uint32_t cnt = b < B_XFREE ? (b == B_OFREE ? 1 : 2) : (b < B_KVRDY ? 3 : (b < B_KVFULL || b == B_ROW ? 4 : (b == B_PFREE ? 2 : 1)));
    mbar_init(BAR(b), cnt);
    asm volatile("fence.mbarrier_init.release.cluster;" ::: "memory");
  }
  __syncthreads();
  asm volatile("barrier.cluster.arrive.relaxed.aligned;" ::: "memory");
  const int wg = __shfl_sync(0xffffffffu, threadIdx.x >> 7, 0);
  if (wg < 2) { reg_inc<224>(); consumer(P, sb, wg); }
  else if (wg == 2) { reg_dec<40>(); aux(P, sb); }
  else {
    reg_dec<24>();
    asm volatile("barrier.cluster.wait.aligned;" ::: "memory");
    const int w = __shfl_sync(0xffffffffu, (threadIdx.x >> 5) & 3, 0);
    if (w == 0) loader(P, sb);
    else if (w < 3) storer(P, sb, w - 1);
    else if ((threadIdx.x & 31) == 0) stager(P, sb);
  }
}

typedef CUresult (*EncFn)(CUtensorMap*, CUtensorMapDataType, cuuint32_t, void*, const cuuint64_t*, const cuuint64_t*, const cuuint32_t*, const cuuint32_t*,
                          CUtensorMapInterleave, CUtensorMapSwizzle, CUtensorMapL2promotion, CUtensorMapFloatOOBfill);
static void mk_map(EncFn enc, CUtensorMap* m, const void* ptr, int rank, const cuuint64_t* dims, const cuuint64_t* strides, const cuuint32_t* box,
                   CUtensorMapSwizzle sw, CUtensorMapL2promotion pr) {
  cuuint32_t es[5] = {1, 1, 1, 1, 1};
  enc(m, CU_TENSOR_MAP_DATA_TYPE_BFLOAT16, rank, (void*)ptr, dims, strides, box, es, CU_TENSOR_MAP_INTERLEAVE_NONE, sw, pr, CU_TENSOR_MAP_FLOAT_OOB_FILL_NONE);
}
extern "C" void kernel_launch(void* const* d_in, const int* in_sizes, int n_in, void* d_out, int out_size) {
  (void)in_sizes; (void)n_in; (void)out_size;
  void* fn = nullptr; cudaDriverEntryPointQueryResult q;
  cudaGetDriverEntryPoint("cuTensorMapEncodeTiled", &fn, cudaEnableDefault, &q);
  EncFn enc = (EncFn)fn;
  cudaFuncSetAttribute(fused_kernel, cudaFuncAttributeMaxDynamicSharedMemorySize, SMEM_BYTES);
  Params P;
  const CUtensorMapSwizzle S128 = CU_TENSOR_MAP_SWIZZLE_128B, S64 = CU_TENSOR_MAP_SWIZZLE_64B, S0 = CU_TENSOR_MAP_SWIZZLE_NONE;
  const CUtensorMapL2promotion L256 = CU_TENSOR_MAP_L2_PROMOTION_L2_256B, L128 = CU_TENSOR_MAP_L2_PROMOTION_L2_128B;
  { cuuint64_t d[2] = {1024, 2048}, s[1] = {2048}; cuuint32_t b[2] = {64, 256}, bh[2] = {64, 128};
    mk_map(enc, &P.mX, d_in[0], 2, d, s, b, S128, L256); mk_map(enc, &P.mXh, d_in[0], 2, d, s, bh, S128, L256); }
  { cuuint64_t d[3] = {1024, 1024, 3}, s[2] = {6144, 2048}; cuuint32_t b[3] = {64, 64, 3}; mk_map(enc, &P.mWq, d_in[1], 3, d, s, b, S128, L256); }
  { cuuint64_t d[5] = {64, 32, 2, 16, 16}, s[4] = {2048, 65536, 131072, 128}; cuuint32_t b[5] = {64, 32, 1, 2, 2}; mk_map(enc, &P.mWo, d_in[2], 5, d, s, b, S128, L256); }
  { cuuint64_t d[2] = {3584, 1024}, s[1] = {7168}; cuuint32_t b[2] = {32, 128};
    mk_map(enc, &P.mWg, d_in[5], 2, d, s, b, S64, L128); mk_map(enc, &P.mWu, d_in[6], 2, d, s, b, S64, L128); }
  { cuuint64_t d[2] = {3072, 1024}, s[1] = {6144}; cuuint32_t b[2] = {32, 256}; mk_map(enc, &P.mWp, d_in[1], 2, d, s, b, S64, L128); }
  { cuuint64_t d[3] = {256, 3584, 4}, s[2] = {2048, 512}; cuuint32_t b[3] = {256, 8, 4}; mk_map(enc, &P.mWd, d_in[7], 3, d, s, b, S0, L128); }
  P.x0 = (const bf16*)d_in[0]; P.wqkv = (const bf16*)d_in[1]; P.wo = (const bf16*)d_in[2]; P.wr = (const bf16*)d_in[4]; P.wg = (const bf16*)d_in[5]; P.wu = (const bf16*)d_in[6]; P.wd = (const bf16*)d_in[7];
  P.out = (bf16*)d_out;
  cudaGetSymbolAddress((void**)&P.g, g_scr);
  for (int b = 0; b < 128; b++) {
    int j = b >> 1, quad = j < 4 ? 0 : (j < 36 ? 1 + (j - 4) % 8 : 9 + (j - 36) % 7), pos = j < 4 ? j : (j < 36 ? (j - 4) / 8 : (j - 36) / 7);
    int bid = ((quad >> 2) * 2 + (pos >> 1)) * 16 + ((quad & 3) * 2 + (pos & 1)) * 2 + (b & 1);
    int e = pos * 2 + (b & 1), fid = e < 7 ? quad * 7 + e : 112 + quad;
    P.map[b] = bid | fid << 8;
  }
  fused_kernel<<<128, 512, SMEM_BYTES>>>(P);
}
```

```cpp
#include <cuda_runtime.h>
#include <cuda_bf16.h>
#include <cuda.h>
#include <stdint.h>
#include <stddef.h>
typedef __nv_bfloat16 bf16;

template<int TB, int TA = 0> __device__ __forceinline__ void wgmma_ss_n192(float (&d)[96], uint64_t da, uint64_t db, int scale_d) {
  asm volatile("{\n.reg .pred p;\nsetp.ne.b32 p, %98, 0;\n"
    "wgmma.mma_async.sync.aligned.m64n192k16.f32.bf16.bf16 {%0, %1, %2, %3, %4, %5, %6, %7, %8, %9, %10, %11, %12, %13, %14, %15, %16, %17, %18, %19, %20, %21, %22, %23, %24, %25, %26, %27, %28, %29, %30, %31, %32, %33, %34, %35, %36, %37, %38, %39, %40, %41, %42, %43, %44, %45, %46, %47, %48, %49, %50, %51, %52, %53, %54, %55, %56, %57, %58, %59, %60, %61, %62, %63, %64, %65, %66, %67, %68, %69, %70, %71, %72, %73, %74, %75, %76, %77, %78, %79, %80, %81, %82, %83, %84, %85, %86, %87, %88, %89, %90, %91, %92, %93, %94, %95}, %96, %97, p, 1, 1, %100, %99;\n}\n"
    : "+f"(d[0]), "+f"(d[1]), "+f"(d[2]), "+f"(d[3]), "+f"(d[4]), "+f"(d[5]), "+f"(d[6]), "+f"(d[7]), "+f"(d[8]), "+f"(d[9]), "+f"(d[10]), "+f"(d[11]), "+f"(d[12]), "+f"(d[13]), "+f"(d[14]), "+f"(d[15]), "+f"(d[16]), "+f"(d[17]), "+f"(d[18]), "+f"(d[19]), "+f"(d[20]), "+f"(d[21]), "+f"(d[22]), "+f"(d[23]), "+f"(d[24]), "+f"(d[25]), "+f"(d[26]), "+f"(d[27]), "+f"(d[28]), "+f"(d[29]), "+f"(d[30]), "+f"(d[31]), "+f"(d[32]), "+f"(d[33]), "+f"(d[34]), "+f"(d[35]), "+f"(d[36]), "+f"(d[37]), "+f"(d[38]), "+f"(d[39]), "+f"(d[40]), "+f"(d[41]), "+f"(d[42]), "+f"(d[43]), "+f"(d[44]), "+f"(d[45]), "+f"(d[46]), "+f"(d[47]), "+f"(d[48]), "+f"(d[49]), "+f"(d[50]), "+f"(d[51]), "+f"(d[52]), "+f"(d[53]), "+f"(d[54]), "+f"(d[55]), "+f"(d[56]), "+f"(d[57]), "+f"(d[58]), "+f"(d[59]), "+f"(d[60]), "+f"(d[61]), "+f"(d[62]), "+f"(d[63]), "+f"(d[64]), "+f"(d[65]), "+f"(d[66]), "+f"(d[67]), "+f"(d[68]), "+f"(d[69]), "+f"(d[70]), "+f"(d[71]), "+f"(d[72]), "+f"(d[73]), "+f"(d[74]), "+f"(d[75]), "+f"(d[76]), "+f"(d[77]), "+f"(d[78]), "+f"(d[79]), "+f"(d[80]), "+f"(d[81]), "+f"(d[82]), "+f"(d[83]), "+f"(d[84]), "+f"(d[85]), "+f"(d[86]), "+f"(d[87]), "+f"(d[88]), "+f"(d[89]), "+f"(d[90]), "+f"(d[91]), "+f"(d[92]), "+f"(d[93]), "+f"(d[94]), "+f"(d[95])
    : "l"(da), "l"(db), "r"(scale_d), "n"(TB), "n"(TA));
}

template<int TB> __device__ __forceinline__ void wgmma_rs_n192(float (&d)[96], uint32_t a0, uint32_t a1, uint32_t a2, uint32_t a3, uint64_t db, int scale_d) {
  asm volatile("{\n.reg .pred p;\nsetp.ne.b32 p, %101, 0;\n"
    "wgmma.mma_async.sync.aligned.m64n192k16.f32.bf16.bf16 {%0, %1, %2, %3, %4, %5, %6, %7, %8, %9, %10, %11, %12, %13, %14, %15, %16, %17, %18, %19, %20, %21, %22, %23, %24, %25, %26, %27, %28, %29, %30, %31, %32, %33, %34, %35, %36, %37, %38, %39, %40, %41, %42, %43, %44, %45, %46, %47, %48, %49, %50, %51, %52, %53, %54, %55, %56, %57, %58, %59, %60, %61, %62, %63, %64, %65, %66, %67, %68, %69, %70, %71, %72, %73, %74, %75, %76, %77, %78, %79, %80, %81, %82, %83, %84, %85, %86, %87, %88, %89, %90, %91, %92, %93, %94, %95}, {%96, %97, %98, %99}, %100, p, 1, 1, %102;\n}\n"
    : "+f"(d[0]), "+f"(d[1]), "+f"(d[2]), "+f"(d[3]), "+f"(d[4]), "+f"(d[5]), "+f"(d[6]), "+f"(d[7]), "+f"(d[8]), "+f"(d[9]), "+f"(d[10]), "+f"(d[11]), "+f"(d[12]), "+f"(d[13]), "+f"(d[14]), "+f"(d[15]), "+f"(d[16]), "+f"(d[17]), "+f"(d[18]), "+f"(d[19]), "+f"(d[20]), "+f"(d[21]), "+f"(d[22]), "+f"(d[23]), "+f"(d[24]), "+f"(d[25]), "+f"(d[26]), "+f"(d[27]), "+f"(d[28]), "+f"(d[29]), "+f"(d[30]), "+f"(d[31]), "+f"(d[32]), "+f"(d[33]), "+f"(d[34]), "+f"(d[35]), "+f"(d[36]), "+f"(d[37]), "+f"(d[38]), "+f"(d[39]), "+f"(d[40]), "+f"(d[41]), "+f"(d[42]), "+f"(d[43]), "+f"(d[44]), "+f"(d[45]), "+f"(d[46]), "+f"(d[47]), "+f"(d[48]), "+f"(d[49]), "+f"(d[50]), "+f"(d[51]), "+f"(d[52]), "+f"(d[53]), "+f"(d[54]), "+f"(d[55]), "+f"(d[56]), "+f"(d[57]), "+f"(d[58]), "+f"(d[59]), "+f"(d[60]), "+f"(d[61]), "+f"(d[62]), "+f"(d[63]), "+f"(d[64]), "+f"(d[65]), "+f"(d[66]), "+f"(d[67]), "+f"(d[68]), "+f"(d[69]), "+f"(d[70]), "+f"(d[71]), "+f"(d[72]), "+f"(d[73]), "+f"(d[74]), "+f"(d[75]), "+f"(d[76]), "+f"(d[77]), "+f"(d[78]), "+f"(d[79]), "+f"(d[80]), "+f"(d[81]), "+f"(d[82]), "+f"(d[83]), "+f"(d[84]), "+f"(d[85]), "+f"(d[86]), "+f"(d[87]), "+f"(d[88]), "+f"(d[89]), "+f"(d[90]), "+f"(d[91]), "+f"(d[92]), "+f"(d[93]), "+f"(d[94]), "+f"(d[95])
    : "r"(a0), "r"(a1), "r"(a2), "r"(a3), "l"(db), "r"(scale_d), "n"(TB));
}

template<int TB, int TA = 0> __device__ __forceinline__ void wgmma_ss_n128(float (&d)[64], uint64_t da, uint64_t db, int scale_d) {
  asm volatile("{\n.reg .pred p;\nsetp.ne.b32 p, %66, 0;\n"
    "wgmma.mma_async.sync.aligned.m64n128k16.f32.bf16.bf16 {%0, %1, %2, %3, %4, %5, %6, %7, %8, %9, %10, %11, %12, %13, %14, %15, %16, %17, %18, %19, %20, %21, %22, %23, %24, %25, %26, %27, %28, %29, %30, %31, %32, %33, %34, %35, %36, %37, %38, %39, %40, %41, %42, %43, %44, %45, %46, %47, %48, %49, %50, %51, %52, %53, %54, %55, %56, %57, %58, %59, %60, %61, %62, %63}, %64, %65, p, 1, 1, %68, %67;\n}\n"
    : "+f"(d[0]), "+f"(d[1]), "+f"(d[2]), "+f"(d[3]), "+f"(d[4]), "+f"(d[5]), "+f"(d[6]), "+f"(d[7]), "+f"(d[8]), "+f"(d[9]), "+f"(d[10]), "+f"(d[11]), "+f"(d[12]), "+f"(d[13]), "+f"(d[14]), "+f"(d[15]), "+f"(d[16]), "+f"(d[17]), "+f"(d[18]), "+f"(d[19]), "+f"(d[20]), "+f"(d[21]), "+f"(d[22]), "+f"(d[23]), "+f"(d[24]), "+f"(d[25]), "+f"(d[26]), "+f"(d[27]), "+f"(d[28]), "+f"(d[29]), "+f"(d[30]), "+f"(d[31]), "+f"(d[32]), "+f"(d[33]), "+f"(d[34]), "+f"(d[35]), "+f"(d[36]), "+f"(d[37]), "+f"(d[38]), "+f"(d[39]), "+f"(d[40]), "+f"(d[41]), "+f"(d[42]), "+f"(d[43]), "+f"(d[44]), "+f"(d[45]), "+f"(d[46]), "+f"(d[47]), "+f"(d[48]), "+f"(d[49]), "+f"(d[50]), "+f"(d[51]), "+f"(d[52]), "+f"(d[53]), "+f"(d[54]), "+f"(d[55]), "+f"(d[56]), "+f"(d[57]), "+f"(d[58]), "+f"(d[59]), "+f"(d[60]), "+f"(d[61]), "+f"(d[62]), "+f"(d[63])
    : "l"(da), "l"(db), "r"(scale_d), "n"(TB), "n"(TA));
}

template<int TB, int TA = 0> __device__ __forceinline__ void wgmma_ss_n64(float (&d)[32], uint64_t da, uint64_t db, int scale_d) {
  asm volatile("{\n.reg .pred p;\nsetp.ne.b32 p, %34, 0;\n"
    "wgmma.mma_async.sync.aligned.m64n64k16.f32.bf16.bf16 {%0, %1, %2, %3, %4, %5, %6, %7, %8, %9, %10, %11, %12, %13, %14, %15, %16, %17, %18, %19, %20, %21, %22, %23, %24, %25, %26, %27, %28, %29, %30, %31}, %32, %33, p, 1, 1, %36, %35;\n}\n"
    : "+f"(d[0]), "+f"(d[1]), "+f"(d[2]), "+f"(d[3]), "+f"(d[4]), "+f"(d[5]), "+f"(d[6]), "+f"(d[7]), "+f"(d[8]), "+f"(d[9]), "+f"(d[10]), "+f"(d[11]), "+f"(d[12]), "+f"(d[13]), "+f"(d[14]), "+f"(d[15]), "+f"(d[16]), "+f"(d[17]), "+f"(d[18]), "+f"(d[19]), "+f"(d[20]), "+f"(d[21]), "+f"(d[22]), "+f"(d[23]), "+f"(d[24]), "+f"(d[25]), "+f"(d[26]), "+f"(d[27]), "+f"(d[28]), "+f"(d[29]), "+f"(d[30]), "+f"(d[31])
    : "l"(da), "l"(db), "r"(scale_d), "n"(TB), "n"(TA));
}

template<int TB, int TA = 0> __device__ __forceinline__ void wgmma_ss_n8(float (&d)[4], uint64_t da, uint64_t db, int scale_d) {
  asm volatile("{\n.reg .pred p;\nsetp.ne.b32 p, %6, 0;\n"
    "wgmma.mma_async.sync.aligned.m64n8k16.f32.bf16.bf16 {%0, %1, %2, %3}, %4, %5, p, 1, 1, %8, %7;\n}\n"
    : "+f"(d[0]), "+f"(d[1]), "+f"(d[2]), "+f"(d[3])
    : "l"(da), "l"(db), "r"(scale_d), "n"(TB), "n"(TA));
}

template<int TB> __device__ __forceinline__ void wgmma_rs_n40(float (&d)[20], uint32_t a0, uint32_t a1, uint32_t a2, uint32_t a3, uint64_t db, int scale_d) {
  asm volatile("{\n.reg .pred p;\nsetp.ne.b32 p, %25, 0;\n"
    "wgmma.mma_async.sync.aligned.m64n40k16.f32.bf16.bf16 {%0, %1, %2, %3, %4, %5, %6, %7, %8, %9, %10, %11, %12, %13, %14, %15, %16, %17, %18, %19}, {%20, %21, %22, %23}, %24, p, 1, 1, %26;\n}\n"
    : "+f"(d[0]), "+f"(d[1]), "+f"(d[2]), "+f"(d[3]), "+f"(d[4]), "+f"(d[5]), "+f"(d[6]), "+f"(d[7]), "+f"(d[8]), "+f"(d[9]), "+f"(d[10]), "+f"(d[11]), "+f"(d[12]), "+f"(d[13]), "+f"(d[14]), "+f"(d[15]), "+f"(d[16]), "+f"(d[17]), "+f"(d[18]), "+f"(d[19])
    : "r"(a0), "r"(a1), "r"(a2), "r"(a3), "l"(db), "r"(scale_d), "n"(TB));
}

#define DEVI __device__ __forceinline__
DEVI uint32_t smem_u32(const void* p) { return (uint32_t)__cvta_generic_to_shared(p); }
DEVI void mbar_init(uint32_t bar, uint32_t cnt) { asm volatile("mbarrier.init.shared::cta.b64 [%0], %1;" :: "r"(bar), "r"(cnt)); }
DEVI void mbar_expect_tx(uint32_t bar, uint32_t bytes) { asm volatile("mbarrier.arrive.expect_tx.shared::cta.b64 _, [%0], %1;" :: "r"(bar), "r"(bytes) : "memory"); }
DEVI void mbar_arrive(uint32_t bar) { asm volatile("mbarrier.arrive.shared::cta.b64 _, [%0];" :: "r"(bar) : "memory"); }
DEVI void mbar_arrive_peer(uint32_t bar) {
  asm volatile("{\n.reg .b32 ra;\nmapa.shared::cluster.u32 ra, %0, %1;\nmbarrier.arrive.shared::cluster.b64 _, [ra];\n}" :: "r"(bar), "r"((blockIdx.x & 1) ^ 1) : "memory");
}
DEVI void bulk_s2peer(uint32_t a, uint32_t bytes, uint32_t bar) {
  asm volatile("{\n.reg .b32 ra, rb;\nmapa.shared::cluster.u32 ra, %0, %3;\nmapa.shared::cluster.u32 rb, %2, %3;\n"
               "cp.async.bulk.shared::cluster.shared::cta.mbarrier::complete_tx::bytes [ra], [%0], %1, [rb];\n}"
               :: "r"(a), "r"(bytes), "r"(bar), "r"((blockIdx.x & 1) ^ 1) : "memory");
}
DEVI void mbar_wait(uint32_t bar, uint32_t parity) {
  asm volatile("{\n.reg .pred p;\nLW:\nmbarrier.try_wait.parity.shared::cta.b64 p, [%0], %1;\n@!p bra LW;\n}" :: "r"(bar), "r"(parity) : "memory");
}
DEVI uint32_t mbar_test(uint32_t bar, uint32_t parity) {
  uint32_t r; asm volatile("{\n.reg .pred p;\nmbarrier.test_wait.parity.shared::cta.b64 p, [%1], %2;\nselp.u32 %0, 1, 0, p;\n}" : "=r"(r) : "r"(bar), "r"(parity) : "memory"); return r;
}
DEVI void mbar_wait_b(uint32_t bar, uint32_t parity) {
  asm volatile("{\n.reg .pred p;\n.reg .u32 it;\nmov.u32 it, 0;\nLW:\nmbarrier.try_wait.parity.shared::cta.b64 p, [%0], %1;\n@p bra LD;\n"
               "add.u32 it, it, 1;\nsetp.lt.u32 p, it, 0x1000000;\n@p bra LW;\ntrap;\nLD:\n}" :: "r"(bar), "r"(parity) : "memory");
}
DEVI void tma_2d(uint32_t dst, const CUtensorMap* m, int c0, int c1, uint32_t bar) {
  asm volatile("cp.async.bulk.tensor.2d.shared::cluster.global.mbarrier::complete_tx::bytes [%0], [%1, {%3, %4}], [%2];"
    :: "r"(dst), "l"(m), "r"(bar), "r"(c0), "r"(c1) : "memory");
}
DEVI void tma_3d(uint32_t dst, const CUtensorMap* m, int c0, int c1, int c2, uint32_t bar) {
  asm volatile("cp.async.bulk.tensor.3d.shared::cluster.global.mbarrier::complete_tx::bytes [%0], [%1, {%3, %4, %5}], [%2];"
    :: "r"(dst), "l"(m), "r"(bar), "r"(c0), "r"(c1), "r"(c2) : "memory");
}
#define POL_EF POL_FIRST
constexpr uint64_t POL_FIRST = 0x12F0000000000000ull, POL_NORMAL = 0x1000000000000000ull;
DEVI void tma_2d_h(uint32_t dst, const CUtensorMap* m, int c0, int c1, uint32_t bar, uint64_t pol) {
  asm volatile("cp.async.bulk.tensor.2d.shared::cluster.global.mbarrier::complete_tx::bytes.L2::cache_hint [%0], [%1, {%3, %4}], [%2], %5;"
    :: "r"(dst), "l"(m), "r"(bar), "r"(c0), "r"(c1), "l"(pol) : "memory");
}
DEVI void tma_3d_h(uint32_t dst, const CUtensorMap* m, int c0, int c1, int c2, uint32_t bar, uint64_t pol) {
  asm volatile("cp.async.bulk.tensor.3d.shared::cluster.global.mbarrier::complete_tx::bytes.L2::cache_hint [%0], [%1, {%3, %4, %5}], [%2], %6;"
    :: "r"(dst), "l"(m), "r"(bar), "r"(c0), "r"(c1), "r"(c2), "l"(pol) : "memory");
}
DEVI void bulk_g2s_h(uint32_t s, const void* g, uint32_t bytes, uint32_t bar, uint64_t pol = POL_EF) {
  asm volatile("cp.async.bulk.shared::cluster.global.mbarrier::complete_tx::bytes.L2::cache_hint [%0], [%1], %2, [%3], %4;"
    :: "r"(s), "l"(g), "r"(bytes), "r"(bar), "l"(pol) : "memory");
}
DEVI void tma_5d(uint32_t dst, const CUtensorMap* m, int c0, int c1, int c2, int c3, int c4, uint32_t bar, uint64_t pol) {
  asm volatile("cp.async.bulk.tensor.5d.shared::cluster.global.mbarrier::complete_tx::bytes.L2::cache_hint [%0], [%1, {%3, %4, %5, %6, %7}], [%2], %8;"
    :: "r"(dst), "l"(m), "r"(bar), "r"(c0), "r"(c1), "r"(c2), "r"(c3), "r"(c4), "l"(pol) : "memory");
}
DEVI void tma_prefetch_2d(const CUtensorMap* m, int c0, int c1) {
  asm volatile("cp.async.bulk.prefetch.tensor.2d.L2.global.tile [%0, {%1, %2}];" :: "l"(m), "r"(c0), "r"(c1) : "memory");
}
DEVI void tma_prefetch_3d(const CUtensorMap* m, int c0, int c1, int c2) {
  asm volatile("cp.async.bulk.prefetch.tensor.3d.L2.global.tile [%0, {%1, %2, %3}];" :: "l"(m), "r"(c0), "r"(c1), "r"(c2) : "memory");
}
DEVI void bulk_prefetch(const void* g, uint32_t bytes) { asm volatile("cp.async.bulk.prefetch.L2.global [%0], %1;" :: "l"(g), "r"(bytes) : "memory"); }
DEVI void bulk_g2s(uint32_t s, const void* g, uint32_t bytes, uint32_t bar) {
  asm volatile("cp.async.bulk.shared::cluster.global.mbarrier::complete_tx::bytes [%0], [%1], %2, [%3];" :: "r"(s), "l"(g), "r"(bytes), "r"(bar) : "memory");
}
DEVI void bulk_s2g(void* g, uint32_t s, uint32_t bytes) {
  asm volatile("cp.async.bulk.global.shared::cta.bulk_group [%0], [%1], %2;\ncp.async.bulk.commit_group;" :: "l"(g), "r"(s), "r"(bytes) : "memory");
}
template<int N> DEVI void bulk_wait() { asm volatile("cp.async.bulk.wait_group %0;" :: "n"(N) : "memory"); }
DEVI void fence_async_smem() { asm volatile("fence.proxy.async.shared::cta;" ::: "memory"); }
DEVI void fence_async_glob() { asm volatile("fence.proxy.async.global;" ::: "memory"); }
DEVI unsigned ld_rlx(const unsigned* p) { unsigned v; asm volatile("ld.relaxed.gpu.global.u32 %0, [%1];" : "=r"(v) : "l"(p) : "memory"); return v; }
DEVI void st_rlx(unsigned* p, unsigned v) { asm volatile("st.relaxed.gpu.global.u32 [%0], %1;" :: "l"(p), "r"(v) : "memory"); }
DEVI uint2 ldg_stream(const uint2* p) { uint2 v; asm volatile("ld.global.nc.L1::no_allocate.v2.u32 {%0, %1}, [%2];" : "=r"(v.x), "=r"(v.y) : "l"(p)); return v; }
DEVI void fence_rel() { asm volatile("fence.release.gpu;" ::: "memory"); }
DEVI uint4 ld_ll(const uint4* p) {
  uint4 v;
  asm volatile("{\n.reg .b128 t;\n.reg .b64 a, b;\nld.relaxed.gpu.global.b128 t, [%4];\nmov.b128 {a, b}, t;\nmov.b64 {%0, %1}, a;\nmov.b64 {%2, %3}, b;\n}"
               : "=r"(v.x), "=r"(v.y), "=r"(v.z), "=r"(v.w) : "l"(p) : "memory");
  return v;
}
DEVI void st_ll(uint4* p, uint32_t x, uint32_t y, uint32_t z, uint32_t w) {
  asm volatile("{\n.reg .b128 t;\n.reg .b64 a, b;\nmov.b64 a, {%1, %2};\nmov.b64 b, {%3, %4};\nmov.b128 t, {a, b};\nst.relaxed.gpu.global.b128 [%0], t;\n}"
               :: "l"(p), "r"(x), "r"(y), "r"(z), "r"(w) : "memory");
}
#define SPIN_MAX 0x1000000
DEVI uint4 poll_ll(const uint4* p, uint32_t mask, uint32_t tag) {
  uint4 v; int it = 0;
  do { v = ld_ll(p); if (++it > SPIN_MAX) __trap(); } while (!__all_sync(0xffffffffu, (v.w & mask) == tag));
  return v;
}
DEVI void poll_ll2(const uint4* p, const uint4* q, uint32_t mask, uint32_t tag, uint4& a, uint4& b) {
  int it = 0;
  do { a = ld_ll(p); b = ld_ll(q); if (++it > SPIN_MAX) __trap(); } while (!__all_sync(0xffffffffu, (a.w & mask) == tag && (b.w & mask) == tag));
}
DEVI void bar_sync(int id, int n) { asm volatile("bar.sync %0, %1;" :: "r"(id), "r"(n) : "memory"); }
DEVI void bar_arrive(int id, int n) { asm volatile("bar.arrive %0, %1;" :: "r"(id), "r"(n) : "memory"); }
DEVI void wg_fence() { asm volatile("wgmma.fence.sync.aligned;" ::: "memory"); }
DEVI void wg_commit() { asm volatile("wgmma.commit_group.sync.aligned;" ::: "memory"); }
template<int N> DEVI void wg_wait() { asm volatile("wgmma.wait_group.sync.aligned %0;" :: "n"(N) : "memory"); }
template<int N> DEVI void reg_inc() { asm volatile("setmaxnreg.inc.sync.aligned.u32 %0;" :: "n"(N)); }
template<int N> DEVI void reg_dec() { asm volatile("setmaxnreg.dec.sync.aligned.u32 %0;" :: "n"(N)); }
DEVI float ex2f(float x) { float y; asm("ex2.approx.ftz.f32 %0, %1;" : "=f"(y) : "f"(x)); return y; }
DEVI uint32_t pack_bf16(float lo, float hi) { uint32_t r; asm("cvt.rn.bf16x2.f32 %0, %1, %2;" : "=r"(r) : "f"(hi), "f"(lo)); return r; }
DEVI float bf_lo(uint32_t v) { return __uint_as_float(v << 16); }
DEVI float bf_hi(uint32_t v) { return __uint_as_float(v & 0xffff0000u); }
DEVI float bf_round(float x) { return bf_lo(pack_bf16(x, 0.f)); }
DEVI void stsm_x4(uint32_t addr, uint32_t a, uint32_t b, uint32_t c, uint32_t d) {
  asm volatile("stmatrix.sync.aligned.m8n8.x4.shared.b16 [%0], {%1,%2,%3,%4};" :: "r"(addr), "r"(a), "r"(b), "r"(c), "r"(d) : "memory");
}
DEVI void ldsm_x4(uint32_t addr, uint32_t& a, uint32_t& b, uint32_t& c, uint32_t& d) {
  asm volatile("ldmatrix.sync.aligned.m8n8.x4.shared.b16 {%0,%1,%2,%3}, [%4];" : "=r"(a), "=r"(b), "=r"(c), "=r"(d) : "r"(addr) : "memory");
}
DEVI uint4 lds128(uint32_t a) { uint4 v; asm volatile("ld.shared.v4.u32 {%0,%1,%2,%3}, [%4];" : "=r"(v.x), "=r"(v.y), "=r"(v.z), "=r"(v.w) : "r"(a) : "memory"); return v; }
DEVI void sts128(uint32_t a, uint4 v) { asm volatile("st.shared.v4.u32 [%0], {%1,%2,%3,%4};" :: "r"(a), "r"(v.x), "r"(v.y), "r"(v.z), "r"(v.w) : "memory"); }
DEVI float2 lds64f(uint32_t a) { float2 v; asm volatile("ld.shared.v2.f32 {%0,%1}, [%2];" : "=f"(v.x), "=f"(v.y) : "r"(a) : "memory"); return v; }
DEVI void sts64f(uint32_t a, float x, float y) { asm volatile("st.shared.v2.f32 [%0], {%1,%2};" :: "r"(a), "f"(x), "f"(y) : "memory"); }
DEVI uint32_t lds32(uint32_t a) { uint32_t v; asm volatile("ld.shared.u32 %0, [%1];" : "=r"(v) : "r"(a) : "memory"); return v; }
DEVI float lds32f(uint32_t a) { return __uint_as_float(lds32(a)); }
DEVI void sts32(uint32_t a, uint32_t v) { asm volatile("st.shared.u32 [%0], %1;" :: "r"(a), "r"(v) : "memory"); }
DEVI void sts32f(uint32_t a, float v) { sts32(a, __float_as_uint(v)); }
DEVI void sts16(uint32_t a, uint32_t v) { asm volatile("st.shared.u16 [%0], %1;" :: "r"(a), "h"((unsigned short)v) : "memory"); }
template<int N> DEVI void keep(float (&d)[N]) {
  #pragma unroll
  for (int i = 0; i < N; i++) asm volatile("" : "+f"(d[i]) :: "memory");
}
template<int N> DEVI void keep(uint32_t (&d)[N]) {
  #pragma unroll
  for (int i = 0; i < N; i++) asm volatile("" : "+r"(d[i]) :: "memory");
}
template<uint32_t HI> DEVI uint64_t mkd(uint32_t lo) { uint64_t r; asm("mov.b64 %0, {%1, %2};" : "=l"(r) : "r"(lo), "n"(HI)); return r; }
constexpr uint32_t HI128 = (1u << 30) | (1024 >> 4), HI64 = (2u << 30) | (512 >> 4);
#define VOFF(x) ((uint32_t)(x) * (uint32_t)(1 - 65536))
DEVI bool elect() { uint32_t p; asm volatile("{\n.reg .pred q;\nelect.sync _|q, 0xffffffff;\nselp.u32 %0, 1, 0, q;\n}" : "=r"(p)); return p; }
DEVI void warp_signal(uint32_t bar) { __syncwarp(); if (elect()) mbar_arrive(bar); }

struct Scratch {
  uint4 kv[128][4][1024];
  uint4 o[8][2][8][2][1024];
  uint4 x[8][16][2048];
  uint4 zero[1024];
  uint4 statP[8][2048];
  uint4 statF[2048];
  uint4 csP[16][8][96];
  uint4 best[8][16];
  uint4 row[16][256];
  uint4 yP[128][112][2];
  uint4 x2[8][256];
  uint4 patch[128][64];
  unsigned flagKV[128][32];
  unsigned flagO[8][32];
  unsigned flagX[8][32];
  unsigned epoch;
};
__device__ __align__(1024) Scratch g_scr;
#define PROFT(cond, slot)
#define PROFW(cond, slot)
#define PROFD(cond, slot)
#define PROFX(cond, slot)
#define PROFY(cond, slot)

constexpr uint32_t SB0 = 65536, HOLE = 90112, SA2 = 98304, SB1 = 131072, SB2 = 155648, STG = 180224;
constexpr uint32_t KVA = 0, KVB = 98304, QO = 65536;
constexpr uint32_t MISC = 229376, CS = MISC, ONES = MISC + 768, BARS = MISC + 1792, INFO = MISC + 2208, WR = MISC + 2224, X2SEG = MISC + 2736, INFO2 = MISC + 2992, DUMP = MISC + 3040;
constexpr uint32_t PAR = HOLE, HV = HOLE + 2048, RED = HOLE + 6144, PATCH = 196608;
constexpr uint32_t SMEM_BYTES = 232448;
enum { B_FULLQ = 0, B_EMPTYQ = 3, B_FULLW = 6, B_EMPTYW = 12, B_HAFREE = 18, B_OFREE = 20,
       B_XFREE = 21,
       B_KVRDY = 23, B_ORDY = 27, B_XRDY = 35, B_STGE = 39,
       B_KVFULL = 42, B_RES = 46, B_PAR = 47, B_STG = 48, B_PFREE = 51, B_COUNT = 52,
       B_ROW = 154 };
#define BAR(x) (sb + BARS + 8 * (x))
DEVI uint32_t qa_off(int s) { return s == 2 ? SA2 : (uint32_t)s * 32768u; }
DEVI uint32_t qb_off(int s) { return s == 0 ? SB0 : (s == 1 ? SB1 : SB2); }
DEVI int kb_order(int bc, int n) {
  const int e = n < 9 ? n - 2 : n - 9;
  return n < 2 ? 2 * bc + n : 2 * (((e < 4 ? e + 4 : e - 4 + (e - 4 >= (bc & 3))) + (bc & 4)) & 7) + (n >= 9);
}
DEVI int wo_order(int bc, int n) { return (n & 8) | ((n + (bc & 6)) & 7); }
DEVI uint32_t w_off(int s) { return (uint32_t)((0x431065 >> (4 * s)) & 7) * 32768u; }
DEVI uint32_t w_par(int n, int s, int L) { return ((n >= 6 && n < 12) ^ (!(s & 2) && L)); }
DEVI int w_next(int n, int s) { return s == 5 ? 0 : (n == 13 ? 4 : s + 1); }

struct Params {
  CUtensorMap mX, mXh, mWq, mWo, mWg, mWu, mWp, mWd;
  const bf16 *x0, *wqkv, *wo, *wr, *wg, *wu, *wd;
  bf16* out;
  Scratch* g;
  unsigned map[128];
};
#define BID ((int)(P.map[blockIdx.x] & 255))
#define FID ((int)(P.map[blockIdx.x] >> 8))
DEVI uint32_t uni(uint32_t v) { return __shfl_sync(0xffffffffu, v, 0); }
#define PQ_N 8
#define PQ_T 700
#define PF0_N 10
#define PF0_T 1600
#define PF1_E 24
#define PF1_T 1100
#define POL_Q1 POL_NORMAL
#define POL_X POL_NORMAL
#define PFA0_BAR 3
#define PFA1_BAR 0
#define PFA0_M 0
#define PFA1_M 0
#define PFA0_T 900
#define PFA1_T 700
#define PF1_S PF0_N
#define PF1_D 0
#define POL_G POL_NORMAL
#define POL_U POL_FIRST
#define POL_D POL_FIRST
#define JQ_N 6
#define WDSRC (P.wd + (size_t)min(fid, 111) * 32768)
#define WDSRC2 (P.wd + FID * 32768)
#define WD_N 4
#define THR_N 6
#define KV_D 1300
#define XD_D 600
#define W0_BAR 3
#define QEF_N 11
#define PACE_T 300
#define POL_Q0 POL_NORMAL
constexpr float LN_EPS = 1e-5f;
constexpr float QSCALE = 0.17677669529663687f * 1.4426950408889634f;

DEVI void fma8(float (&a)[8], uint4 v, float h) {
  a[0] = fmaf(bf_lo(v.x), h, a[0]); a[1] = fmaf(bf_hi(v.x), h, a[1]); a[2] = fmaf(bf_lo(v.y), h, a[2]); a[3] = fmaf(bf_hi(v.y), h, a[3]);
  a[4] = fmaf(bf_lo(v.z), h, a[4]); a[5] = fmaf(bf_hi(v.z), h, a[5]); a[6] = fmaf(bf_lo(v.w), h, a[6]); a[7] = fmaf(bf_hi(v.w), h, a[7]);
}
DEVI uint4 ldsv128(uint32_t a) { uint4 v; asm volatile("ld.volatile.shared.v4.u32 {%0,%1,%2,%3}, [%4];" : "=r"(v.x), "=r"(v.y), "=r"(v.z), "=r"(v.w) : "r"(a) : "memory"); return v; }
DEVI float ldsv32f(uint32_t a) { float v; asm volatile("ld.volatile.shared.f32 %0, [%1];" : "=f"(v) : "r"(a) : "memory"); return v; }
DEVI uint32_t clk() { uint32_t t; asm volatile("mov.u32 %0, %%clock;" : "=r"(t)); return t; }
DEVI int fresh_tid() { int t; asm volatile("mov.u32 %0, %%tid.x;" : "=r"(t)); return t & 127; }
DEVI float fold8(const float (&a)[8]) {
  const int lane = threadIdx.x & 31;
  const bool u = lane & 16, v = lane & 8, x = lane & 4;
  float b0 = (u ? a[4] : a[0]) + __shfl_xor_sync(0xffffffffu, u ? a[0] : a[4], 16), b1 = (u ? a[5] : a[1]) + __shfl_xor_sync(0xffffffffu, u ? a[1] : a[5], 16);
  float b2 = (u ? a[6] : a[2]) + __shfl_xor_sync(0xffffffffu, u ? a[2] : a[6], 16), b3 = (u ? a[7] : a[3]) + __shfl_xor_sync(0xffffffffu, u ? a[3] : a[7], 16);
  float c0 = (v ? b2 : b0) + __shfl_xor_sync(0xffffffffu, v ? b0 : b2, 8), c1 = (v ? b3 : b1) + __shfl_xor_sync(0xffffffffu, v ? b1 : b3, 8);
  return (x ? c1 : c0) + __shfl_xor_sync(0xffffffffu, x ? c0 : c1, 4);
}
DEVI float swiglu(float g, float u) { g = bf_round(g); return bf_round(bf_round(__fdividef(g, 1.f + __expf(-g))) * bf_round(u)); }

DEVI void qk_issue(float (&s)[32], uint32_t qd, uint32_t kd) {
  wgmma_ss_n64<0>(s, mkd<HI64>(qd), mkd<HI64>(kd), 0);
  wgmma_ss_n64<0>(s, mkd<HI64>(qd + 2), mkd<HI64>(kd + 2), 1);
}
template<int J0, int J1> DEVI void exp_pack(const float (&s)[32], uint32_t (&p)[16]) {
  #pragma unroll
  for (int j = J0; j < J1; j++) p[j] = pack_bf16(ex2f(s[2 * j]), ex2f(s[2 * j + 1]));
}
DEVI bool attn_pack(const float (&o)[20], uint32_t (&ob)[8]) {
  const float lo = 5.421010862427522e-20f, hi = 1.8446744073709552e19f;
  float i0, i1; asm("rcp.approx.ftz.f32 %0, %1;" : "=f"(i0) : "f"(o[16])); asm("rcp.approx.ftz.f32 %0, %1;" : "=f"(i1) : "f"(o[18]));
  #pragma unroll
  for (int e = 0; e < 8; e++) ob[e] = pack_bf16(o[2 * e] * ((e & 1) ? i1 : i0), o[2 * e + 1] * ((e & 1) ? i1 : i0));
  return __all_sync(0xffffffffu, o[16] >= lo && o[16] <= hi && o[18] >= lo && o[18] <= hi);
}
DEVI void attn_store(const uint32_t (&ob)[8], bool ok, uint32_t st, uint32_t sb, uint32_t bar) {
  stsm_x4(ok ? st : sb + DUMP, ob[0], ob[1], ob[2], ob[3]); stsm_x4(ok ? st ^ 32 : sb + DUMP, ob[4], ob[5], ob[6], ob[7]);
  __syncwarp();
  asm volatile("{\n.reg .pred p, q;\nelect.sync _|q, 0xffffffff;\nsetp.ne.and.u32 p, %1, 0, q;\n@p mbarrier.arrive.shared::cta.b64 _, [%0];\n}" :: "r"(bar), "r"((uint32_t)ok) : "memory");
}
DEVI void attn_exact(uint32_t st, uint32_t kv, int t, bool hasprev, uint32_t bar) {
  const int lane = threadIdx.x & 31;
  #pragma unroll 1
  for (int row = ((threadIdx.x >> 5) & 3) * 16, n = 0; n < 16; n++, row++) {
    const int k1 = 256 + t * 64 + row;
    float m = -INFINITY, l = 0.f, o = 0.f;
    #pragma unroll 1
    for (int k0 = hasprev ? k1 - 255 : 256; k0 <= k1; k0 += 32) {
      const int k = min(k0 + lane, k1), r = k & 63;
      float sc = 0.f;
      #pragma unroll 1
      for (int c = 0; c < 16; c++) {
        uint32_t a = lds32(st + row * 64 + ((c * 4) ^ ((row & 6) << 3))), b = lds32(kv + (k >> 6) * 8192 + r * 64 + ((c * 4) ^ ((r & 6) << 3)));
        sc = fmaf(bf_lo(a), bf_lo(b), fmaf(bf_hi(a), bf_hi(b), sc));
      }
      float mn = fmaxf(m, sc);
      #pragma unroll 1
      for (int x = 16; x; x >>= 1) mn = fmaxf(mn, __shfl_xor_sync(0xffffffffu, mn, x));
      const float al = ex2f(m - mn), pr = ex2f(sc - mn);
      m = mn; l *= al; o *= al;
      #pragma unroll 1
      for (int q = k0; q <= min(k0 + 31, k1); q++) {
        const float z = __shfl_sync(0xffffffffu, pr, q - k0);
        uint32_t b = lds32(kv + (q >> 6) * 8192 + 4096 + (q & 63) * 64 + (((lane >> 1) * 4) ^ ((q & 6) << 3)));
        l += z; o = fmaf(z, (lane & 1) ? bf_hi(b) : bf_lo(b), o);
      }
    }
    __syncwarp();
    sts16(st + row * 64 + ((lane * 2) ^ ((row & 6) << 3)), pack_bf16(__fdividef(o, l), 0.f));
  }
  warp_signal(bar);
}

template<int K0, int K1, int DONE = 0> DEVI void exp_pv(const float (&s)[32], uint32_t (&p)[16], float (&o)[20], uint32_t vd, bool accum) {
  #pragma unroll
  for (int ks = K0; ks < K1; ks++) {
    if (ks >= DONE) {
      #pragma unroll
      for (int j = 4 * ks; j < 4 * ks + 4; j++) p[j] = pack_bf16(ex2f(s[2 * j]), ex2f(s[2 * j + 1]));
    }
    asm volatile("" : "+r"(p[4 * ks]), "+r"(p[4 * ks + 1]), "+r"(p[4 * ks + 2]), "+r"(p[4 * ks + 3]));
    wg_fence();
    wgmma_rs_n40<1>(o, p[ks * 4], p[ks * 4 + 1], p[ks * 4 + 2], p[ks * 4 + 3], mkd<HI64>(vd + VOFF(ks * 64)), ks ? 1 : accum);
  }
}
DEVI void exp_pv2(const float (&s)[32], const float (&sx)[32], uint32_t (&p)[16], uint32_t (&px)[16], float (&o)[20], uint32_t v0, uint32_t v4,
                  const uint32_t (&msk)[9], int tdiag) {
  #pragma unroll
  for (int ks = 0; ks < 4; ks++) {
    #pragma unroll
    for (int j = 4 * ks; j < 4 * ks + 4; j++) {
      const int c = 8 * (j >> 1) - 8 * (j & 1);
      const uint32_t e = pack_bf16(ex2f(c > tdiag ? s[2 * j] : sx[2 * j]), ex2f(c + 1 > tdiag ? s[2 * j + 1] : sx[2 * j + 1])), m = msk[(j >> 1) - (j & 1) + 1];
      p[j] = e & m; px[j] = e & ~m;
      asm volatile("" : "+r"(p[j]), "+r"(px[j]));
    }
    wg_fence();
    wgmma_rs_n40<1>(o, p[ks * 4], p[ks * 4 + 1], p[ks * 4 + 2], p[ks * 4 + 3], mkd<HI64>(v0 + VOFF(ks * 64)), 1);
    wgmma_rs_n40<1>(o, px[ks * 4], px[ks * 4 + 1], px[ks * 4 + 2], px[ks * 4 + 3], mkd<HI64>(v4 + VOFF(ks * 64)), 1);
  }
}

template<int J0> DEVI void qkv_store(const float (&a)[96], float p0, float p1, uint32_t d) {
  #pragma unroll
  for (int hh = 0; hh < 2; hh++) {
    const int j = 4 * (J0 + 2 * hh);
    stsm_x4(d ^ (hh << 5), pack_bf16(a[j] * p0, a[j + 1] * p0), pack_bf16(a[j + 2] * p1, a[j + 3] * p1),
                           pack_bf16(a[j + 4] * p0, a[j + 5] * p0), pack_bf16(a[j + 6] * p1, a[j + 7] * p1));
  }
}
DEVI void mean_step(float (&a)[96], float m0, float m1, uint32_t cd, bool z) {
  const uint32_t u0 = z ? 0u : __float_as_uint(m0), u1 = z ? 0u : __float_as_uint(m1);
  uint32_t ma[4] = {__byte_perm(u0, 0u, 0x1010), __byte_perm(u1, 0u, 0x1010), __byte_perm(u0, 0u, 0x3232), __byte_perm(u1, 0u, 0x3232)};
  keep(ma);
  wg_fence();
  wgmma_rs_n192<1>(a, ma[0], ma[1], ma[2], ma[3], mkd<2>(cd), 1);
  wg_commit();
}

template<bool FIRST> DEVI void qkv_block(float (&aX)[96], float (&aY)[96], uint32_t sb16, int s, int tX, int tY) {
  uint32_t a16 = sb16 + (qa_off(s) >> 4), b16 = (sb16 + (qb_off(s) >> 4)) | ((8192u >> 4) << 16);
  uint32_t ax = (a16 + tX * 512) | 0x10000u, ay = (a16 + tY * 512) | 0x10000u;
  wg_fence();
  #pragma unroll
  for (int ks = 0; ks < 4; ks++) {
    wgmma_ss_n192<1>(aX, mkd<HI128>(ax + ks * 2), mkd<HI128>(b16 + ks * 128), !(FIRST && ks == 0));
    wgmma_ss_n192<1>(aY, mkd<HI128>(ay + ks * 2), mkd<HI128>(b16 + ks * 128), !(FIRST && ks == 0));
  }
  wg_commit();
}
DEVI void qkv_half(float (&a)[96], uint32_t sb16, int t, uint32_t sa, uint32_t sbb) {
  wg_fence();
  #pragma unroll
  for (int ks = 0; ks < 4; ks++)
    wgmma_ss_n192<1>(a, mkd<HI128>(((sb16 + (sa >> 4) + t * 512) | 0x10000u) + ks * 2), mkd<HI128>(((sb16 + (sbb >> 4)) | ((8192u >> 4) << 16)) + ks * 128), 1);
  wg_commit();
}
template<bool FIRST> DEVI void wo_block(float (&acc)[64], uint32_t sb16, int s, int wg) {
  uint32_t a16 = (sb16 + (w_off(s) >> 4) + wg * 256) | 0x10000u, b16 = (sb16 + (w_off(s) >> 4) + 1024) | ((8192u >> 4) << 16);
  wg_fence();
  #pragma unroll
  for (int ks = 0; ks < 4; ks++)
    wgmma_ss_n128<1>(acc, mkd<HI64>(a16 + (ks >> 1) * 512 + (ks & 1) * 2), mkd<HI128>(b16 + ks * 128), !(FIRST && ks == 0));
  wg_commit();
}
DEVI void consumer(const Params& P, uint32_t sb, int wg) {
  const int w = uni((threadIdx.x >> 5) & 3);
  #define LAYER uni(mbar_test(BAR(B_RES), 0))
  #define IDS L = LAYER; const int tid = fresh_tid(), lane = tid & 31
  const uint32_t ids = uni(P.map[blockIdx.x]);
  const int bi = (ids >> 4) & 7, rh = ids & 1, bc = (ids & 15) >> 1, fid = ids >> 8;
  const int tX = 3 - wg, tY = wg;
  constexpr uint32_t sb16 = 1024 >> 4;
  #pragma unroll 1
  while (true) {
    int L = LAYER;
    {
      float aX[96], aY[96];
      const bool lead = fresh_tid() == 0;
      if (L) mbar_wait(BAR(B_XRDY + wg * 2 + 1), 0);
      mbar_wait(BAR(B_FULLQ), 0);
      PROFW(threadIdx.x == 0, L * 8 + 1);
      qkv_block<true>(aX, aY, sb16, 0, tX, tY);
      #pragma unroll 1
      for (int n = 1, s = 1, ps = 0, ph = 0; n < 14; n++) {
        mbar_wait(BAR(B_FULLQ + s), ph ^ (s ? L : 0));
        PROFD(threadIdx.x == 0 && L && (n == 2 || n == 3 || n == 7 || n == 11 || n == 13), n == 2 ? 48 : 49 + (n >> 2));
        qkv_block<false>(aX, aY, sb16, s, tX, tY);
        wg_wait<1>(); if (lead) mbar_arrive(BAR(B_EMPTYQ + ps));
        ps = s; if (s == 2) { s = 0; ph ^= 1; } else s++;
      }
      mbar_wait(BAR(B_ROW), L);
      IDS;
      const uint32_t pa = sb + PAR + (w * 16 + (lane >> 2)) * 8;
      float2 p0 = lds64f(pa + tX * 512), p1 = lds64f(pa + tX * 512 + 64), p2 = lds64f(pa + tY * 512), p3 = lds64f(pa + tY * 512 + 64);
      mean_step(aX, p0.y, p1.y, sb16 + (CS >> 4), lane & 3);
      mbar_wait(BAR(B_FULLQ + 2), L);
      qkv_half(aX, sb16, tX, SA2, SB2);
      mbar_wait(BAR(B_FULLQ), 1);
      qkv_half(aX, sb16, tX, 0, SB0);
      wg_wait<3>(); if (lead) mbar_arrive(BAR(B_EMPTYQ + 1));
      bar_sync(1, 256);
      qkv_half(aY, sb16, tY, SA2, SB2);
      wg_wait<1>(); keep(aX);
      const int srow = w * 16 + (lane & 15);
      const uint32_t x0 = sb + srow * 64 + (((lane >> 4) ^ ((srow >> 1) & 3)) << 4), xX = x0 + (4 + tX) * 8192, xY = x0 + (4 + tY) * 8192;
      qkv_store<8>(aX, p0.x, p1.x, xX + KVA); qkv_store<16>(aX, p0.x, p1.x, xX + KVA + 4096);
      if (!L) warp_signal(BAR(B_KVRDY + wg * 2));
      qkv_half(aY, sb16, tY, 0, SB0);
      mean_step(aY, p2.y, p3.y, sb16 + (CS >> 4), fresh_tid() & 3);
      mbar_wait(BAR(B_PAR), L);
      const int l3 = fresh_tid() & 3, prow = (int)uni(lds32(sb + INFO)) - bi * 256;
      const bool pmine = (prow >> 4) == tX * 4 + w || (prow >> 4) == tY * 4 + w;
      const uint32_t poff = sb + (prow & 63) * 64 + ((l3 ^ ((prow >> 1) & 3)) << 4);
      if (pmine) { __syncwarp(); if (lane < 8) sts128(poff + KVA + (4 + (prow >> 6)) * 8192 + (lane >> 2) * 4096, lds128(sb + PATCH + 128 + (lane >> 2) * 128 + l3 * 16)); }
      if (L) warp_signal(BAR(B_KVRDY + wg * 2));
      wg_wait<2>(); if (lead) mbar_arrive(BAR(B_EMPTYQ + 2));
      mbar_wait(BAR(B_EMPTYQ + 2), L);
      qkv_store<12>(aX, p0.x, p1.x, xX + KVB); qkv_store<20>(aX, p0.x, p1.x, xX + KVB + 4096);
      wg_wait<0>(); keep(aY);
      if (lead) mbar_arrive(BAR(B_EMPTYQ));
      PROFW(threadIdx.x == 0, L * 8 + 2);
      qkv_store<8>(aY, p2.x, p3.x, xY + KVA); qkv_store<16>(aY, p2.x, p3.x, xY + KVA + 4096);
      qkv_store<12>(aY, p2.x, p3.x, xY + KVB); qkv_store<20>(aY, p2.x, p3.x, xY + KVB + 4096);
      p0.x *= QSCALE; p1.x *= QSCALE; p2.x *= QSCALE; p3.x *= QSCALE;
      mbar_wait(BAR(B_EMPTYQ), 1);
      qkv_store<0>(aX, p0.x, p1.x, x0 + QO + tX * 4096); qkv_store<4>(aX, p0.x, p1.x, x0 + QO + 16384 + tX * 4096);
      qkv_store<0>(aY, p2.x, p3.x, x0 + QO + tY * 4096); qkv_store<4>(aY, p2.x, p3.x, x0 + QO + 16384 + tY * 4096);
      if (pmine) {
        __syncwarp();
        if (lane < 24) sts128(poff + (lane < 8 ? QO + (lane >> 2) * 16384 + (prow >> 6) * 4096 : ((lane & 4) ? KVB : KVA) + (4 + (prow >> 6)) * 8192 + (lane >> 4) * 4096),
                              lds128(sb + PATCH + lane * 16));
      }
      fence_async_smem();
      warp_signal(BAR(B_KVRDY + wg * 2 + 1));
      bar_sync(1, 256);
    }
    PROFW(threadIdx.x == 0, L * 8 + 3);
    {
      IDS;
      float s0[32], s1[32], sx[32], o[20], op[20];
      uint32_t p0[16], p1[16], px[16], msk[9];
      const int tdiag = w * 16 + (lane >> 2) - 2 * (lane & 3);
      #pragma unroll
      for (int e = 0; e < 9; e++) msk[e] = ((8 * e - 8 > tdiag) ? 0xFFFFu : 0u) | ((8 * e - 7 > tdiag) ? 0xFFFF0000u : 0u);
      keep(msk);
      const uint32_t ones = (sb16 + (ONES >> 4)) << 16;
      const uint32_t qX = (sb16 + (QO >> 4) + tX * 256) | 0x10000u, qY = (sb16 + (QO >> 4) + tY * 256) | 0x10000u;
      const uint32_t kXB = (sb16 + (KVB >> 4) + tX * 512) | 0x10000u;
      uint32_t redo = 0;
      const uint32_t ost = sb + QO + (w * 16 + (lane & 15)) * 64 + (((lane >> 4) ^ ((lane >> 1) & 3)) << 4);
      #define QK(s, q, k) do { wg_fence(); qk_issue(s, q, k); wg_commit(); } while (0)
      #define QK2(q, k) do { wg_fence(); qk_issue(s1, q, k); qk_issue(sx, q, (k) + 2048); wg_commit(); } while (0)
      #define VB(v, b) ((v) + VOFF((b) * 512))
      QK(s0, qX + 1024, kXB + 1536);
      #pragma unroll
      for (int e = 0; e < 20; e++) o[e] = 0.f;
      wg_wait<0>(); keep(s0);
      #pragma unroll 1
      for (int h = 1; h >= 0; h--) {
        const uint32_t kXA = kXB - ((KVB - KVA) >> 4), kX = h ? kXB : kXA, vX = VOFF((kX & 0xffffu) + 256) + ones;
        QK(s1, qX + h * 1024, kX + 1024);
        #pragma unroll
        for (int e = 0; e < 20; e++) op[e] = o[e];
        keep(op);
        exp_pv<0, 4>(s0, p0, o, VB(vX, 3), false); wg_commit();
        wg_wait<1>(); keep(s1);
        exp_pv<0, 2>(s1, p1, o, VB(vX, 2), true);
        bar_sync(h ? 12 + wg : 4 + wg * 4, h ? 128 : 160);
        QK(s0, qX, kXA + 512 + h * 1024);
        exp_pv<2, 4>(s1, p1, o, VB(vX, 2), true); wg_commit();
        wg_wait<0>(); keep(s0); keep(p0); keep(p1); keep(o);
      }
      #pragma unroll 1
      for (int h = 0; h < 2; h++) {
        const uint32_t kb16 = sb16 + ((h ? KVB : KVA) >> 4), kY = (kb16 + tY * 512) | 0x10000u, qy = qY + h * 1024;
        const uint32_t onesP = bi ? ones : (kb16 + 1984) << 16;
        const uint32_t vX = VOFF(kb16 + tX * 512 + 256), vY = VOFF(kb16 + tY * 512 + 256);
        uint32_t ob[8];
        QK2(qX + h * 1024, (kb16 + tX * 512) | 0x10000u);
        exp_pv<0, 4>(s0, p0, o, VB(vX + (wg ? onesP : ones), 1), true); wg_commit();
        wg_wait<1>(); keep(s1); keep(sx);
        QK(s0, qy, kY + 1536);
        exp_pv2(s1, sx, p1, px, o, vX + onesP, VB(vX + ones, 4), msk, tdiag); wg_commit();
        wg_wait<1>(); keep(s0); keep(p0);
        QK(s1, qy, kY + 1024);
        exp_pack<0, 4>(s0, p0);
        wg_wait<1>(); keep(o); keep(p1); keep(px);
        bool ok = attn_pack(o, ob); keep(ob);
        exp_pv<0, 4, 1>(s0, p0, o, VB(vY + (wg ? ones : onesP), 3), false); wg_commit();
        attn_store(ob, ok, ost + (h * 4 + tX) * 4096, sb, BAR(B_ORDY + wg * 4 + h * 2)); redo |= ok ? 0u : 1u << (h * 2);
        wg_wait<1>(); keep(s1);
        exp_pv<0, 2>(s1, p1, o, VB(vY + onesP, 2), true);
        bar_sync(5 + wg * 4 + h * 2, 160);
        QK(s0, qy, kY + 512);
        exp_pv<2, 4>(s1, p1, o, VB(vY + onesP, 2), true); wg_commit();
        wg_wait<1>(); keep(s0); keep(p0);
        QK2(qy, kY);
        exp_pv<0, 4>(s0, p0, o, VB(vY + onesP, 1), true); wg_commit();
        wg_wait<1>(); keep(s1); keep(sx); keep(p1);
        bar_sync(6 + wg * 4, h ? 128 : 160);
        QK(s0, h ? qy : qX + 1024, kXB + 512);
        exp_pv2(s1, sx, p1, px, o, vY + onesP, VB(vY + ones, 4), msk, tdiag); wg_commit();
        wg_wait<0>(); keep(o); keep(s0); keep(p0); keep(p1); keep(px);
        ok = attn_pack(o, ob); attn_store(ob, ok, ost + (h * 4 + tY) * 4096, sb, BAR(B_ORDY + wg * 4 + h * 2 + 1)); redo |= ok ? 0u : 2u << (h * 2);
        #pragma unroll
        for (int e = 0; e < 20; e++) o[e] = op[e];
      }
      #undef QK
      #undef QK2
      #undef VB
      if (redo) {
        #pragma unroll 1
        for (int u = 0; u < 4; u++) if ((redo >> u) & 1) {
          const int h = u >> 1, t = (u & 1) ? tY : tX;
          attn_exact(sb + QO + (h * 4 + t) * 4096, sb + (h ? KVB : KVA), t, bi > 0, BAR(B_ORDY + wg * 4 + u));
        }
      }
    }
    PROFW(threadIdx.x == 0, L * 8 + 4);
    {
      IDS;
      const int t256 = wg * 128 + tid;
      float acc[64];
      const int tt = wg ^ rh;
      const int grow = bi * 256 + rh * 128 + tt * 64 + w * 16 + (lane >> 2);
      float al0 = 1.f, be0 = 0.f, al1 = 1.f, be1 = 0.f;
      const int idx0 = (int)uni(lds32(sb + INFO));
      const uint32_t tag = lds32(sb + INFO + 8) + L;
      uint4* const sp = &P.g->statP[bc][grow + (lane & 1) * 8];
      uint4* const yp = &P.g->yP[t256 >> 1][min(fid, 111)][t256 & 1];
      mbar_wait(BAR(B_FULLW), L);
      PROFW(t256 == 0, L * 8 + 5);
      wo_block<true>(acc, sb16, 0, tt);
      if (!(lane & 2)) st_ll(sp, 0u, 0u, 0u, 0u);
      uint4 fa = make_uint4(0u, 0u, 0u, 0u), fb = fa;
      uint2 wd[4];
      if (L) {
        if (fid < 112) st_ll(yp, 0u, 0u, 0u, 0u);
        fa = ld_ll(&P.g->statF[grow]); fb = ld_ll(&P.g->statF[grow + 8]);
      }
      #pragma unroll
      for (int e = 0; e < 4; e++) { wd[e] = make_uint2(0u, 0u); if (L) wd[e] = ldg_stream((const uint2*)(WDSRC) + t256 + (28 + e) * 256); }
      #pragma unroll 1
      for (int n = 1, q = 1, pq = 0; n < 16; n++) {
        mbar_wait(BAR(B_FULLW + q), w_par(n, q, L));
        PROFD(t256 == 0 && !L && (n == 4 || n == 7 || n == 8 || n == 12), (n == 7 ? 63 : 41 + (n >> 2)));
        wo_block<false>(acc, sb16, q, tt);
        wg_wait<1>(); if (tid == 0) mbar_arrive(BAR(B_EMPTYW + pq));
        pq = q; q = w_next(n, q);
      }
      if (L) {
        float r0 = rsqrtf(__uint_as_float(fa.y) + LN_EPS), r1 = rsqrtf(__uint_as_float(fb.y) + LN_EPS);
        if (grow != idx0) { al0 = 1.f + r0; be0 = -__uint_as_float(fa.x) * r0; }
        if (grow + 8 != idx0) { al1 = 1.f + r1; be1 = -__uint_as_float(fb.x) * r1; }
      }
      mbar_wait(BAR(B_RES), L);
      const int srow = tt * 64 + w * 16 + (lane & 15);
      const uint32_t ra = sb + rh * 16384 + srow * 128, sw = ((lane >> 4) ^ (srow & 7)) << 4;
      if ((idx0 >> 4) == bi * 16 + rh * 8 + tt * 4 + w) {
        int r = idx0 & 127;
        if (lane < 16) sts128(sb + (lane >> 3) * 32768 + rh * 16384 + r * 128 + (((lane & 7) ^ (r & 7)) << 4), lds128(sb + X2SEG + lane * 16));
        __syncwarp();
      }
      uint32_t rs[32];
      #pragma unroll
      for (int jj = 0; jj < 8; jj++) ldsm_x4((ra + (jj >> 2) * 32768) + (sw ^ ((jj & 3) << 5)), rs[4 * jj], rs[4 * jj + 1], rs[4 * jj + 2], rs[4 * jj + 3]);
      float rf[64];
      #pragma unroll
      for (int e = 0; e < 32; e++) { rf[2 * e] = fmaf(bf_lo(rs[e]), (e & 1) ? al1 : al0, (e & 1) ? be1 : be0); rf[2 * e + 1] = fmaf(bf_hi(rs[e]), (e & 1) ? al1 : al0, (e & 1) ? be1 : be0); }
      keep(rf);
      mbar_wait(BAR(B_RES), L);
      wg_wait<0>(); keep(acc);
      if (tid == 0) mbar_arrive(BAR(B_EMPTYW + 5));
      PROFW(t256 == 0, L * 8 + 6);
      #pragma unroll
      for (int jj = 0; jj < 8; jj++) {
        float* a = acc + 8 * jj;
        #pragma unroll
        for (int e = 0; e < 8; e++) a[e] += rf[8 * jj + e];
        stsm_x4((ra + (jj >> 2) * 32768) + (sw ^ ((jj & 3) << 5)), pack_bf16(a[0], a[1]), pack_bf16(a[2], a[3]), pack_bf16(a[4], a[5]), pack_bf16(a[6], a[7]));
        if (jj == 7) fence_async_smem();
        if ((jj & 3) == 3) warp_signal(BAR(B_XRDY + wg * 2 + (jj >> 2)));
      }
      {
        float s1a = 0.f, s2a = 0.f, da = 0.f, s1b = 0.f, s2b = 0.f, db = 0.f;
        #pragma unroll
        for (int j = 0; j < 16; j++) {
          const float* a = acc + 4 * j; float2 wv = lds64f(sb + WR + j * 32 + (lane & 3) * 8);
          s1a += a[0] + a[1]; s1b += a[2] + a[3];
          s2a = fmaf(a[0], a[0], s2a); s2b = fmaf(a[2], a[2], s2b); s2a = fmaf(a[1], a[1], s2a); s2b = fmaf(a[3], a[3], s2b);
          da = fmaf(a[0], wv.x, da); db = fmaf(a[2], wv.x, db); da = fmaf(a[1], wv.y, da); db = fmaf(a[3], wv.y, db);
        }
        bool odd = lane & 1;
        float u1 = (odd ? s1b : s1a) + __shfl_xor_sync(0xffffffffu, odd ? s1a : s1b, 1);
        float u2 = (odd ? s2b : s2a) + __shfl_xor_sync(0xffffffffu, odd ? s2a : s2b, 1);
        float u3 = (odd ? db : da) + __shfl_xor_sync(0xffffffffu, odd ? da : db, 1);
        u1 += __shfl_xor_sync(0xffffffffu, u1, 2); u2 += __shfl_xor_sync(0xffffffffu, u2, 2); u3 += __shfl_xor_sync(0xffffffffu, u3, 2);
        if (!(lane & 2)) st_ll(sp, __float_as_uint(u1), __float_as_uint(u2), __float_as_uint(u3), tag);
      }
      PROFW(t256 == 0, L * 8 + 7);
      if (L) {
        mbar_wait(BAR(B_PAR), 0);
        { float2 pa = lds64f(sb + PAR + (grow & 127) * 8), pb = lds64f(sb + PAR + (grow & 127) * 8 + 64); al0 = pa.x; be0 = pa.y; al1 = pb.x; be1 = pb.y; }
        #pragma unroll
        for (int j = 0; j < 16; j++) {
          rs[2 * j] = pack_bf16(fmaf(acc[4 * j], al0, be0), fmaf(acc[4 * j + 1], al0, be0));
          rs[2 * j + 1] = pack_bf16(fmaf(acc[4 * j + 2], al1, be1), fmaf(acc[4 * j + 3], al1, be1));
        }
        #pragma unroll
        for (int jj = 0; jj < 8; jj++) stsm_x4((ra + (jj >> 2) * 32768) + (sw ^ ((jj & 3) << 5)), rs[4 * jj], rs[4 * jj + 1], rs[4 * jj + 2], rs[4 * jj + 3]);
        PROFW(t256 == 0, 16);
        if (fid >= 112) bar_arrive(3, 384);
        else {
          float d[4] = {0.f, 0.f, 0.f, 0.f};
          mbar_wait(BAR(B_FULLW + wg * 4), 0); mbar_wait(BAR(B_FULLW + wg * 4 + 1), 0);
          bar_sync(3, 384);
          PROFW(t256 == 0, 29);
          #pragma unroll 1
          for (int g = 0; g < 4; g++) {
            const uint32_t ad = (sb16 + (wg ? 6144 : 10240) + (g >> 1) * 2048 + (g & 1) * 512) | (1024u << 16), bd = (sb16 + (HV >> 4) + wg * 64 + g * 16) | 0x10000u;
            wg_fence();
            #pragma unroll
            for (int ks = 0; ks < 8; ks++) wgmma_ss_n8<0, 1>(d, mkd<HI64>(ad + ks * 64), mkd<8>(bd + ks * 2), 1);
            wg_commit();
          }
          mbar_wait(BAR(B_FULLW + 2), 0);
          wg_wait<0>(); keep(d);
          if (!(lane & 3)) { sts32f(sb + PAR + 1024 + wg * 256 + w * 64 + lane, d[0]); sts32f(sb + PAR + 1056 + wg * 256 + w * 64 + lane, d[2]); }
          bar_sync(1, 256);
          const uint32_t ga = sb + PAR + 1024 + lane * 4, aa = sb + HV + (t256 >> 5) * 128;
          sts32f(aa + lane * 4, swiglu(lds32f(ga) + lds32f(ga + 256), lds32f(ga + 128) + lds32f(ga + 384)));
          __syncwarp();
          PROFW(t256 == 0, 26);
          float y0 = 0.f, y1 = 0.f, y2 = 0.f, y3 = 0.f;
          uint32_t tbl = rh ? 0x001459a8u : 0x023679a8u;
          uint4 a4 = lds128(aa + 112);
          #pragma unroll 2
          for (int n = 0; n < 8; n++, tbl >>= 4) {
            const uint32_t src = sb + t256 * 8 + (tbl & 15) * 8192;
            const uint4 an = lds128(aa + ((0x00123564u >> (4 * n)) & 15) * 16);
            #pragma unroll
            for (int e = 0; e < 4; e++) {
              const float av = __uint_as_float(e == 0 ? a4.x : (e == 1 ? a4.y : (e == 2 ? a4.z : a4.w)));
              y0 = fmaf(bf_lo(wd[e].x), av, y0); y1 = fmaf(bf_hi(wd[e].x), av, y1); y2 = fmaf(bf_lo(wd[e].y), av, y2); y3 = fmaf(bf_hi(wd[e].y), av, y3);
              const float2 v = lds64f(src + e * 2048); wd[e] = make_uint2(__float_as_uint(v.x), __float_as_uint(v.y));
            }
            a4 = an;
          }
          st_ll(yp, __float_as_uint(y0), __float_as_uint(y1), __float_as_uint(y2), (__float_as_uint(y3) & ~255u) | (lds32(sb + INFO + 12) + 1));
          PROFW(t256 == 0, 27);
        }
        return;
      }
    }
  }
  #undef IDS
  #undef LAYER
}

DEVI void loader(const Params& P, uint32_t sb) {
  const int lane = threadIdx.x & 31;
  const int bid = uni(BID), bi = bid >> 4, bp = bid & 15, rh = bp & 1, bc = bp >> 1;
  uint32_t phq = 0, tag = 0;
  #pragma unroll 1
  for (int L = 0; L < 2; L++) {
    int s = 0;
    uint32_t rdy = 0;
    #pragma unroll 1
    for (int n = L ? 0 : 3; n < 16; n++) {
      int kb = L ? kb_order(bc, n) : n;
      mbar_wait(BAR(B_EMPTYQ + s), (phq >> s) & 1);
      phq ^= 1u << s;
      if (L && n == 1) { mbar_wait(BAR(B_XRDY + 1), 0); mbar_wait(BAR(B_XRDY + 3), 0); }
      if (lane == 0) {
        mbar_expect_tx(BAR(B_FULLQ + s), L && n < 2 ? 40960 : 57344);
        tma_3d_h(sb + qb_off(s), &P.mWq, bp * 64, kb * 64, 0, BAR(B_FULLQ + s), L && n >= QEF_N ? POL_FIRST : POL_NORMAL);
        if (!L) tma_2d(sb + qa_off(s), &P.mX, kb * 64, bi * 256, BAR(B_FULLQ + s));
      }
      if (L && n >= 2) {
        if (((rdy >> (2 * kb)) & 3) != 3) {
          do { rdy = __ballot_sync(0xffffffffu, ld_rlx(&P.g->flagX[bi][lane]) == tag); } while (((rdy >> (2 * kb)) & 3) != 3);
          fence_async_glob();
        }
        if (n == 3 || n == 4) mbar_wait(BAR(B_XFREE + n - 3), 0);
        if (lane == 0) bulk_g2s_h(sb + qa_off(s), P.g->x[bi][kb], 32768, BAR(B_FULLQ + s), POL_X);
      }
      PROFY(L && lane == 0 && (n == 2 || n == 3 || n == 9), n == 9 ? 60 : 56 + n);
      if (L && n == 2) { mbar_wait(BAR(B_FULLQ), 0); mbar_wait(BAR(B_FULLQ + 1), 1); if (lane < 2) mbar_arrive_peer(BAR(B_XFREE + lane)); }
      s = (s == 2) ? 0 : s + 1;
    }
    for (int q = 0; q < 3; q++) mbar_wait(BAR(B_EMPTYQ + q), (phq >> q) & 1);
    mbar_wait(BAR(B_PAR), L);
    tag = lds32(sb + INFO + 8) + L;
    #pragma unroll 1
    for (int q = 0; q < 4; q++) {
            if (bi) {
        const unsigned* f = &P.g->flagKV[bid - 16][q];
        while (ld_rlx(f) != tag);
        fence_async_glob();
      }
      if (lane == 0) {
        mbar_expect_tx(BAR(B_KVFULL + q), 16384);
        bulk_g2s_h(sb + ((q >> 1) ? KVB : KVA) + ((q & 1) ? 0 : 16384), bi ? P.g->kv[bid - 16][q] : P.g->zero, 16384, BAR(B_KVFULL + q));
      }
      PROFY(!L && lane == 0 && bi && q != 2, 34 + (q + 1) / 2);
    }
    mbar_wait(BAR(B_ORDY), L); mbar_wait(BAR(B_ORDY + 4), L);
    {
      const uint4* src = P.g->o[bi][0][0][rh];
      rdy = 0;
      #pragma unroll 1
      for (int n = 0, q = 0; n < 16; q = w_next(n, q), n++) {
        const int j = wo_order(bc, n);
        if (((rdy >> (2 * j)) & 3) != 3) {
          do { rdy = __ballot_sync(0xffffffffu, ld_rlx(&P.g->flagO[bi][lane]) == tag); } while (((rdy >> (2 * j)) & 3) != 3);
          fence_async_glob();
        }
        if (n >= 2) mbar_wait(n < 6 ? BAR(B_HAFREE + (n >> 2)) : BAR(B_EMPTYW + q), n < 6 ? L : w_par(n - 6, q, L));
        if (n == THR_N) mbar_wait(BAR(B_OFREE), L);
        if (lane == 0) { mbar_expect_tx(BAR(B_FULLW + q), 16384); bulk_g2s_h(sb + w_off(q), src + j * 2048, 16384, BAR(B_FULLW + q)); }
      }
    }
    mbar_wait(BAR(B_OFREE), L);
  }
}

DEVI void ffn_prefetch(const Params& P, int q) {
  bulk_prefetch(q < 16 ? ((q & 1) ? P.wu : P.wg) + ((q >> 1) * 128 + blockIdx.x) * 3584 : P.wd + (min(FID, 111) * 8 + q - 16) * 4096, q < 16 ? 7168 : 8192);
}
DEVI void storer(const Params& P, uint32_t sb, int wg) {
  const int bid = uni(BID), bi = bid >> 4, rh = bid & 1, bc = (bid & 15) >> 1;
  const bool one = (threadIdx.x & 31) == 0;
  char* const g = (char*)P.g;
  #pragma unroll 1
  for (int L = 0; L < 2; L++) {
    mbar_wait(BAR(B_PAR), L);
    const uint32_t tag = lds32(sb + INFO + 8) + L;
    if (wg) { mbar_wait(BAR(B_KVRDY), L); mbar_wait(BAR(B_KVRDY + 2), L); const uint32_t t0 = clk(); while (clk() - t0 < KV_D) __nanosleep(40); }
    #pragma unroll 1
    for (int u = 0; u < 2 + 4 * wg; u++) {
      const int h = u < 2 ? u : u >> 2, hi = (u & 1) ^ 1;
      uint32_t src, dst, fl, b0, b1;
      if (u < 2) {
        src = (h ? KVB : KVA) + (3 - wg) * 16384; dst = offsetof(Scratch, kv) + (bid * 4 + h * 2 + wg) * 16384; fl = offsetof(Scratch, flagKV) + (bid * 32 + h * 2 + wg) * 4;
        b0 = BAR(B_KVRDY + ((u | wg) ? 1 : 0)); b1 = b0 + 16;
      } else {
        src = QO + (h * 2 + hi) * 8192; dst = offsetof(Scratch, o) + ((((bi * 2 + h) * 8 + bc) * 2 + hi) * 2 + rh) * 8192;
        fl = offsetof(Scratch, flagO) + (bi * 32 + h * 16 + (bid & 15)) * 4;
        b0 = BAR(B_ORDY + u - 2); b1 = b0 + 32;
      }
      mbar_wait(b0, L); mbar_wait(b1, L);
      fence_async_smem();
      PROFY(one && !L && u == 3 * wg, u ? 46 : 8);
      if (one && (u >= 2 || bi < 7)) bulk_s2g(g + dst, sb + src, u < 2 ? 16384 : 8192);
      if (one && u == 5) mbar_arrive(BAR(B_HAFREE + 1));
      if (u == 2 || u == 4) continue;
      bulk_wait<0>();
      PROFY(one && !L && u == 3 * wg, u ? 61 : 62);
      fence_rel();
      if (one) { st_rlx((unsigned*)(g + fl), tag); if (!wg || u > 2) mbar_arrive(BAR(B_HAFREE + h + (wg & h))); }
      PROFY(one && !L && (u > 2 || u == wg), u > 2 ? (u == 3 ? 38 : 54) : 32 + u);
    }
    if (L == 0) {
      char* dst = g + (offsetof(Scratch, x) + (bi * 16 + 2 * bc) * 32768 + rh * 16384);
      unsigned* f = (unsigned*)(g + (offsetof(Scratch, flagX) + (bi * 32 + bc * 4 + rh) * 4));
      const uint32_t a = sb + rh * 16384;
      if (wg == 0) {
        mbar_wait(BAR(B_XRDY), 0); mbar_wait(BAR(B_XRDY + 2), 0);
        fence_async_smem();
        PROFY(one, 41);
        if (one) bulk_s2g(dst, a, 16384);
        bulk_wait<0>();
        PROFY(one, 45);
        if (one) { mbar_arrive(BAR(B_XFREE)); mbar_arrive(BAR(B_PFREE)); }
        fence_rel();
        mbar_wait(BAR(B_XRDY + 1), 0); mbar_wait(BAR(B_XRDY + 3), 0);
        if (one) { st_rlx(f, tag); bulk_s2g(dst + 32768, a + 32768, 16384); }
        PROFY(one, 56);
        bulk_wait<0>();
        if (one) mbar_arrive(BAR(B_XFREE + 1));
        fence_rel();
        if (one) st_rlx(f + 2, tag);
        PROFY(one, 57);
      } else {
        mbar_wait(BAR(B_XRDY + 1), 0); mbar_wait(BAR(B_XRDY + 3), 0);
        mbar_wait(BAR(B_PFREE), 0);
        if (one) bulk_s2peer(a, 16384, BAR(B_FULLQ));
        { const uint32_t t0 = clk(); while (clk() - t0 < XD_D); }
        if (one) bulk_s2peer(a + 32768, 16384, BAR(B_FULLQ + 1));
      }
      if (wg == 0) {
        uint32_t t0 = clk() + PF1_D;
        #pragma unroll 1
        for (int q = PF1_S; q < PF1_E; q++) { while ((int)(clk() - t0) < 0) __nanosleep(50); if (one) ffn_prefetch(P, q); t0 += PF1_T; }
      }
    }
  }
}

DEVI void stg_issue(const Params& P, int c, uint32_t d, uint32_t du, uint32_t b) {
  mbar_expect_tx(b, 16384);
  if (c < 8) { tma_2d_h(d, &P.mWg, FID * 32, c * 128, b, POL_G); tma_2d_h(d + du, &P.mWu, FID * 32, c * 128, b, POL_U); }
  else if (c < 12) tma_3d_h(d, &P.mWd, 0, FID * 32 + (c - 8) * 8, 0, b, POL_D);
  else tma_2d_h(d, &P.mWp, (c - 12) * 1024 + (BID >> 2) * 32, (BID & 3) * 256, b, POL_EF);
}
DEVI void pace() { const uint32_t t0 = clk(); while (clk() - t0 < PACE_T); }
DEVI void stager(const Params& P, uint32_t sb) {
  {
    const int b = blockIdx.x;
    uint32_t t0 = clk();
    #pragma unroll 1
    for (int q = 0; q < PQ_N; q++) { bulk_prefetch(P.wqkv + (q * 128 + b) * 3072, 6144); while (clk() - t0 < PQ_T) __nanosleep(50); t0 += PQ_T; }
    bulk_prefetch(P.wo + b * 8192, 16384);
    #pragma unroll 1
    for (int q = 0; q < PF0_N; q++) {
      while (clk() - t0 < PF0_T) __nanosleep(50);
      t0 += PF0_T;
      ffn_prefetch(P, q);
    }
  }
  const int bid = BID, bi = bid >> 4, rh = bid & 1, bc = (bid & 15) >> 1;
  #pragma unroll 1
  for (int L = 0; L < 2; L++) {
    const int nch = L ? (FID < 112 ? 8 : 0) : 15;
    mbar_wait(BAR(B_KVFULL + W0_BAR), L);
    #pragma unroll 1
    for (int n = 0, q = 0; n < 16; q = w_next(n, q), n++) {
      if (n >= 2) mbar_wait(n < 6 ? BAR(B_HAFREE + (n >> 2)) : BAR(B_EMPTYW + q), n < 6 ? L : w_par(n - 6, q, L));
      if (n == THR_N) mbar_wait(BAR(B_OFREE), L);
      mbar_expect_tx(BAR(B_FULLW + q), 16384);
      tma_5d(sb + w_off(q) + 16384, &P.mWo, 0, 0, n >> 3, 2 * (wo_order(bc, n) & 7), 2 * bc, BAR(B_FULLW + q), L ? POL_EF : POL_NORMAL);
      if (n == 13) {
        mbar_expect_tx(BAR(B_RES), 32768);
        #pragma unroll 1
        for (int e = 0; e < 2; e++) {
          mbar_wait(BAR(B_EMPTYW + 2 + e), 1);
          if (L) bulk_g2s_h(sb + e * 32768 + rh * 16384, P.g->x[bi][2 * bc + e] + rh * 1024, 16384, BAR(B_RES));
          else tma_2d_h(sb + e * 32768 + rh * 16384, &P.mXh, bc * 128 + e * 64, bi * 256 + rh * 128, BAR(B_RES), POL_EF);
        }
      }
    }
    if (L && nch) {
      const bf16* src = WDSRC2;
      mbar_expect_tx(BAR(B_FULLW + 2), 32768); mbar_expect_tx(BAR(B_FULLW + 2), 24576);
      #pragma unroll 1
      for (int e = 0; e < 3; e++) { bulk_g2s_h(sb + e * 32768 + (e < 2 ? (rh ^ 1) * 16384 : 0), src + e * 8192, e < 2 ? 16384 : 24576, BAR(B_FULLW + 2)); pace(); }
    }
    if (L == 0) { mbar_arrive_peer(BAR(B_PFREE)); mbar_wait(BAR(B_EMPTYW), 0); mbar_wait(BAR(B_EMPTYW + 1), 0); }
    #pragma unroll 1
    for (int c = FID < 112 ? 0 : 12, slot = 0; c < nch; c++, slot = slot == 2 ? 0 : slot + 1) {
      const int q = (c >> 1) + (c & 4) / 2;
      mbar_wait(L ? BAR(B_EMPTYW + q) : BAR(B_STGE + slot), L | ((0x71c7 >> c) & 1));
      #define CC c
      stg_issue(P, CC, L ? sb + w_off(q) + (c & 1) * 8192 : sb + STG + slot * 16384, 8192 << L, L ? BAR(B_FULLW + q) : BAR(B_STG + slot));
      if (L) pace();
    }
  }
}
DEVI void sum8(uint4 v, float& s1, float& s2) {
  float e[8] = {bf_lo(v.x), bf_hi(v.x), bf_lo(v.y), bf_hi(v.y), bf_lo(v.z), bf_hi(v.z), bf_lo(v.w), bf_hi(v.w)};
  #pragma unroll
  for (int q = 0; q < 8; q++) { s1 += e[q]; s2 = fmaf(e[q], e[q], s2); }
}
DEVI uint4 norm8(uint4 x, float m, float rs) {
  #define HN(v) pack_bf16((bf_lo(v) - m) * rs, (bf_hi(v) - m) * rs)
  return make_uint4(HN(x.x), HN(x.y), HN(x.z), HN(x.w));
  #undef HN
}
DEVI void put_f32(uint4 b, uint32_t d, uint32_t d2) {
  sts128(d, make_uint4(b.x << 16, b.x & 0xffff0000u, b.y << 16, b.y & 0xffff0000u));
  sts128(d + d2, make_uint4(b.z << 16, b.z & 0xffff0000u, b.w << 16, b.w & 0xffff0000u));
}
DEVI void put_bf16(uint4 b, uint32_t d) {
  sts64f(d, __uint_as_float(b.x), __uint_as_float(b.y)); sts64f(d + 1024, __uint_as_float(b.z), __uint_as_float(b.w));
  fence_async_smem();
}
DEVI uint4 best4(uint32_t p) {
  uint4 a = lds128(p), b = lds128(p + 16), c = lds128(p + 32), d = lds128(p + 48);
  if (b.x > a.x) a = b;
  if (d.x > c.x) c = d;
  return c.x > a.x ? c : a;
}
#define FL(x) __uint_as_float(x)
#define UI(x) __float_as_uint(x)
DEVI void qkv_params(const Params& P, uint32_t sb, int row, uint32_t tag, bool second) {
  uint4 v0, v1; poll_ll2(&P.g->statF[row], &P.g->statF[row + 128], 0xffffffffu, tag, v0, v1);
  #pragma unroll 1
  for (int q = 0; q < 2; q++) {
    float var = FL(v0.y), c = rsqrtf(var + LN_EPS);
    if (second) { c += 1.f; c *= rsqrtf(fmaf(var * c, c, LN_EPS)); }
    const float mh = bf_round(FL(v0.x));
    sts64f(sb + PAR + q * 1024 + (row & 127) * 8, c, FL(pack_bf16(mh, FL(v0.x) - mh)));
    v0 = v1;
  }
  warp_signal(BAR(B_ROW));
}
DEVI void aux(const Params& P, uint32_t sb) {
  int tid = fresh_tid();
  #define lane (tid & 31)
  #define wq (tid >> 5)
  uint32_t ids = P.map[blockIdx.x], tag;
  #define bid ((int)(ids & 255))
  #define fid ((int)(ids >> 8))
  #define bi (bid >> 4)
  #define bp (bid & 15)
  #define bc (bp >> 1)
  #define FRESH() do { tid = fresh_tid(); uint4 z_ = ldsv128(sb + INFO2 + 16); ids = z_.y; tag = z_.z + L; idx = z_.w; } while (0)
  {
    const uint32_t epoch = ld_rlx(&P.g->epoch);
    if (tid == 0) {
      mbar_expect_tx(BAR(B_STG), 49152);
      tma_3d(sb + STG, &P.mWq, bp * 64, bi * 128, 0, BAR(B_STG));
      tma_3d(sb + STG + 24576, &P.mWq, bp * 64, bi * 128 + 64, 0, BAR(B_STG));
    }
    __syncwarp();
    sts64f(sb + ONES + tid * 8, FL(0x3F803F80u), FL(0x3F803F80u));
    float s1 = 0.f, s2 = 0.f;
    { uint4 v = __ldg((const uint4*)P.wr + tid);
      if ((tid >> 4) == bc) put_f32(v, sb + WR + (tid & 15) * 32, 16);
      sum8(v, s1, s2);
      #pragma unroll 1
      for (int o = 16; o; o >>= 1) s1 += __shfl_xor_sync(0xffffffffu, s1, o);
      sts32f(sb + INFO2 + wq * 4, s1); }
    const uint4* src = (const uint4*)(P.x0 + (size_t)bid * 16384) + (tid >> 3) * 128 + (tid & 7);
    s1 = 0.f; s2 = 0.f;
    #pragma unroll 1
    for (int it = 0; it < 16; it += 4) {
      uint4 v0 = __ldg(src + it * 8), v1 = __ldg(src + it * 8 + 8), v2 = __ldg(src + it * 8 + 16), v3 = __ldg(src + it * 8 + 24);
      #pragma unroll 1
      for (int q = 0; q < 4; q++) { sum8(v0, s1, s2); v0 = v1; v1 = v2; v2 = v3; }
    }
    #pragma unroll 1
    for (int o = 1; o < 8; o <<= 1) { s1 += __shfl_xor_sync(0xffffffffu, s1, o); s2 += __shfl_xor_sync(0xffffffffu, s2, o); }
    tag = ((epoch % 16383u) + 1u) << 2;
    if (tid == 0) { sts128(sb + INFO, make_uint4(0x40000000u, 0u, tag, ((epoch % 127u) + 1u) << 1)); sts128(sb + INFO2 + 16, make_uint4(epoch, ids, tag, 0x40000000u)); }
    float m = s1 * (1.f / 1024.f);
    if ((tid & 7) == 0) st_ll(&P.g->statF[bid * 16 + (tid >> 3)], UI(m), UI(fmaxf(fmaf(-m, m, s2 * (1.f / 1024.f)), 0.f)), 0u, tag);
    bar_sync(2, 128);
    mbar_wait_b(BAR(B_STG), 0);
    if (tid < 96) {
      s1 = 0.f; s2 = 0.f;
      #pragma unroll 4
      for (int r = 0; r < 128; r++) {
        uint32_t v = lds32(sb + STG + (r >> 6) * 24576 + wq * 8192 + (r & 63) * 128 + ((lane * 4) ^ ((r & 7) << 4)));
        s1 += bf_lo(v); s2 += bf_hi(v);
      }
      st_ll(&P.g->csP[bp][bi][tid], UI(s1), UI(s2), 0u, tag);
      s1 = 0.f; s2 = 0.f;
      #pragma unroll 1
      for (int q = 0; q < 8; q += 2) {
        uint4 a, b; poll_ll2(&P.g->csP[bp][q][tid], &P.g->csP[bp][q + 1][tid], 0xffffffffu, tag, a, b);
        s1 += FL(a.x) + FL(b.x); s2 += FL(a.y) + FL(b.y);
      }
      const uint32_t hi = pack_bf16(-s1, -s2);
      sts32(sb + CS + (tid >> 2) * 32 + (tid & 3) * 4, hi);
      sts32(sb + CS + (tid >> 2) * 32 + (tid & 3) * 4 + 16, pack_bf16(-s1 - bf_lo(hi), -s2 - bf_hi(hi)));
    }
    fence_async_smem();
    qkv_params(P, sb, bi * 256 + tid, tag, false);
  }
  int idx;
  #pragma unroll 1
  for (int L = 0; L < 2; L++) {
    FRESH();
    {
      if ((idx >> 8) == bi) {
        const uint4* src = &P.g->patch[bp * 8 + (tid >> 6) * 4][tid & 63];
        uint4 v0, v1, v2, v3; int it = 0;
        do { v0 = ld_ll(src); v1 = ld_ll(src + 64); v2 = ld_ll(src + 128); v3 = ld_ll(src + 192); if (++it > SPIN_MAX) __trap(); }
        while (!__all_sync(0xffffffffu, v0.w == tag && v1.w == tag && v2.w == tag && v3.w == tag));
        float q = (FL(v0.x) + FL(v1.x)) + (FL(v2.x) + FL(v3.x)), k = (FL(v0.y) + FL(v1.y)) + (FL(v2.y) + FL(v3.y)), v = (FL(v0.z) + FL(v1.z)) + (FL(v2.z) + FL(v3.z));
        q += __shfl_xor_sync(0xffffffffu, q, 1); k += __shfl_xor_sync(0xffffffffu, k, 1); v += __shfl_xor_sync(0xffffffffu, v, 1);
        bar_sync(2, 128);
        const uint32_t d = sb + PATCH + (tid & ~1), kv = pack_bf16(k, v);
        sts16(d, pack_bf16(q * QSCALE, 0.f)); sts16(d + 128, kv); sts16(d + 256, kv >> 16);
      }
      sts32(sb + INFO, idx);
      bar_sync(2, 128);
      if (tid == 0) mbar_arrive(BAR(B_PAR));
      PROFX(tid == 0, L ? 23 : 17);
    }
    mbar_wait_b(BAR(B_KVFULL + wq), L);
    bar_arrive(4 + wq, 160); bar_arrive(8 + wq, 160);
    FRESH();
    mbar_wait_b(BAR(B_OFREE), L);
    #define blk (bi * 2 + (bid & 1))
    if (tid < 33) st_ll(tid < 32 ? &P.g->row[blk][bc * 32 + tid] : &P.g->best[bc][blk], 0u, 0u, 0u, 0u);
    if (!L) {
        if (fid < 112) { st_ll(&P.g->yP[tid & ~1][fid][tid & 1], 0u, 0u, 0u, 0u); st_ll(&P.g->yP[tid | 1][fid][tid & 1], 0u, 0u, 0u, 0u); }
        if (tid < 80) st_ll(tid < 64 ? &P.g->patch[bid][tid] : &P.g->x2[(tid >> 1) & 7][2 * bid + (tid & 1)], 0u, 0u, 0u, 0u);
    }
    mbar_wait_b(BAR(B_XRDY + 1), L); mbar_wait_b(BAR(B_XRDY + 3), L);
    PROFX(tid == 0, 37 + L * 16);
    FRESH();
    {
      float s1 = 0.f, s2 = 0.f, d = 0.f;
      #pragma unroll 1
      for (int q = 0; q < 8; q += 4) {
        const uint4* src = &P.g->statP[q][blk * 128 + tid];
        uint4 v0, v1, v2, v3; int it = 0;
        do { v0 = ld_ll(src); v1 = ld_ll(src + 2048); v2 = ld_ll(src + 4096); v3 = ld_ll(src + 6144); if (++it > SPIN_MAX) __trap(); }
        while (!__all_sync(0xffffffffu, v0.w == tag && v1.w == tag && v2.w == tag && v3.w == tag));
        s1 += (FL(v0.x) + FL(v1.x)) + (FL(v2.x) + FL(v3.x)); s2 += (FL(v0.y) + FL(v1.y)) + (FL(v2.y) + FL(v3.y)); d += (FL(v0.z) + FL(v1.z)) + (FL(v2.z) + FL(v3.z));
      }
      PROFX(tid == 0, 39 + L * 16);
      uint4 a = lds128(sb + INFO2), b, c;
      float m = s1 * (1.f / 1024.f), var = fmaxf(fmaf(-m, m, s2 * (1.f / 1024.f)), 0.f), rs = rsqrtf(var + LN_EPS);
      uint32_t key = UI(fmaf(-m, (FL(a.x) + FL(a.y)) + (FL(a.z) + FL(a.w)), d) * rs);
      key ^= (uint32_t)((int)key >> 31) | 0x80000000u;
      uint32_t win = __ballot_sync(0xffffffffu, key == __reduce_max_sync(0xffffffffu, key));
      if (lane == __ffs(win) - 1) sts128(sb + RED + wq * 16, make_uint4(key, UI(m), UI(rs), (tag << 11) | (uint32_t)(blk * 128 + tid)));
      if (L) sts64f(sb + PAR + tid * 8, 1.f + rs, -m * rs);
      else if ((tid >> 4) == bc) st_ll(&P.g->statF[blk * 128 + tid], UI(m), UI(var), 0u, tag + 1);
      bar_sync(2, 128);
      if (wq == 0) {
        a = best4(sb + RED);
        float2 v = lds64f(sb + (lane >> 4) * 32768 + (a.w & 255) * 128 + (((lane & 15) * 8) ^ ((a.w & 7) << 4)));
        st_ll(&P.g->row[blk][bc * 32 + lane], UI(v.x), UI(v.y), 0u, tag);
        if (lane == 0) st_ll(&P.g->best[bc][blk], a.x, a.y, a.z, a.w);
        __syncwarp();
        if (lane < 2 - L) mbar_arrive(L ? BAR(B_PAR) : BAR(B_XFREE + lane));
      }
      PROFX(tid == 0, 18 + L * 6);
      FRESH();
      a = poll_ll(&P.g->best[bc][lane & 15], 0xfffff800u, tag << 11);
      win = __ffs(__ballot_sync(0xffffffffu, a.x == __reduce_max_sync(0xffffffffu, a.x))) - 1;
      idx = __shfl_sync(0xffffffffu, a.w, win) & 2047;
      PROFX(tid == 0, 19 + L * 6);
      poll_ll2(&P.g->row[win][tid], &P.g->row[win][tid + 128], 0xffffffffu, tag, c, b);
      c.z = b.x; c.w = b.y;
      a.x = __shfl_sync(0xffffffffu, a.x, win); a.y = __shfl_sync(0xffffffffu, a.y, win); a.z = __shfl_sync(0xffffffffu, a.z, win);
      sts32(sb + INFO2 + 28, idx);
      PROFX(tid == 0, 61 + L);
      b = norm8(c, FL(a.y), FL(a.z));
      if (L) put_bf16(b, sb + HV + tid * 8); else put_f32(b, sb + HV + tid * 16, 2048);
      if ((tid >> 1) == (bid & 63)) {
        sts128(sb + RED + 64 + (tid & 1) * 16, bid < 64 ? make_uint4(c.x, c.y, b.x, b.y) : make_uint4(c.z, c.w, b.z, b.w));
        sts32(sb + RED + 96, a.x);
      }
      bar_sync(2 + L, 128 + L * 256);
      if (L) {
        const int r0 = blk * 128 + (tid >> 4);
        uint32_t src = sb + ((tid >> 3) & 1) * 32768 + (r0 & 255) * 128 + (((tid ^ r0) & 7) << 4);
        uint4* dst = (uint4*)(P.out + (size_t)r0 * 1024 + bc * 128) + (tid & 15);
        #pragma unroll 4
        for (int it = 0; it < 16; it++) { uint4 v = lds128(src + it * 1024); if (idx - r0 != it * 8) dst[it * 1024] = v; }
      }
    }
    #pragma unroll 1
    for (int st = L; st < 2; st++) {
      FRESH();
      float a[8] = {0.f, 0.f, 0.f, 0.f, 0.f, 0.f, 0.f, 0.f};
      if (L == 0 && fid < 112) {
        uint32_t ha = st ? sb + RED + 768 : sb + HV + ((wq & 1) * 64 + (lane >> 2)) * 4;
        uint32_t ph = st ? 0x1cu : 0x171u, bar = st ? BAR(B_STG + 2) : BAR(B_STG);
        uint32_t wa = sb + STG + wq * 4096 + (st ? 32768 + lane * 16 : (lane ^ (lane >> 3)) * 16);
        const uint32_t hx = st ? 256 : 512;
        const bool lead = lane == 0;
        uint4 vc = make_uint4(0u, 0u, 0u, 0u); float hc = 0.f;
        #pragma unroll 1
        do {
          mbar_wait(bar, ph & 1);
          PROFX(lead && threadIdx.x == 256 && st == 0 && (ph > 255 || ph < 4), 40 - 23 + __clz(ph));
          #pragma unroll
          for (int n = 0; n < 8; n++) { const uint4 v = lds128(wa + n * 512); const float h = lds32f(ha + n * 32); fma8(a, vc, hc); vc = v; hc = h; }
          __syncwarp();
          if (lead) mbar_arrive(bar - 8 * (B_STG - B_STGE));
          const bool wrap = bar == BAR(B_STG + 2);
          bar += wrap ? -16 : 8; wa += wrap ? -32768 : 16384; ha += hx;
          ph >>= 1;
        } while (ph != 1);
        fma8(a, vc, hc);
      }
      FRESH();
      if (st == 1) {
        const uint32_t t8 = lds32(sb + INFO + 12) + L;
        if (L == 0 && fid < 112) {
          const bool odd = lane & 1;
          #pragma unroll
          for (int e = 0; e < 4; e++) { float z = __shfl_xor_sync(0xffffffffu, odd ? a[e] : a[4 + e], 1); if (odd) a[e] = z; else a[4 + e] = z; }
          uint4* dst = &P.g->yP[tid & ~1][fid][tid & 1];
          st_ll(dst, UI(a[0]), UI(a[1]), UI(a[2]), (UI(a[3]) & ~255u) | t8);
          st_ll(dst + 224, UI(a[4]), UI(a[5]), UI(a[6]), (UI(a[7]) & ~255u) | t8);
          PROFX(tid == 0, 21);
        }
        if (!L) qkv_params(P, sb, bi * 256 + tid, tag + 1, true);
        if (tid == 0) { uint32_t k = lds32(sb + RED + 96); sts32f(sb + RED + 100, bf_round(__fdividef(1.f, 1.f + __expf(-bf_round(FL(k ^ (~(uint32_t)((int)k >> 31) | 0x80000000u))))))); }
        uint4 v0, v1;
        poll_ll2(&P.g->yP[bid][0][min(tid, 111)], &P.g->yP[bid][0][min(tid, 111) + 112], 255u, t8, v0, v1);
        const float lo = (tid < 112 && !(tid & 1)) ? 1.f : 0.f, hi = (tid < 112 && (tid & 1)) ? 1.f : 0.f;
        const float y0 = FL(v0.x) + FL(v1.x), y1 = FL(v0.y) + FL(v1.y), y2 = FL(v0.z) + FL(v1.z), y3 = FL((v0.w & ~255u) | 128u) + FL((v1.w & ~255u) | 128u);
        a[0] = y0 * lo; a[1] = y1 * lo; a[2] = y2 * lo; a[3] = y3 * lo; a[4] = y0 * hi; a[5] = y1 * hi; a[6] = y2 * hi; a[7] = y3 * hi;
      }
      sts32f(sb + RED + 256 + wq * 128 + ((lane & 3) * 8 + (lane >> 2)) * 4, fold8(a));
      bar_sync(2, 128);
      const uint32_t d = sb + RED + 256 + lane * 4;
      float z0 = lds32f(d) + lds32f(d + 128), z1 = lds32f(d + 256) + lds32f(d + 384);
      if (st == 0) {
        sts32f(sb + RED + 768 + lane * 32 + wq * 4, swiglu(z0, z1));
        bar_sync(2, 128); PROFX(tid == 0, 20); continue; }
      z0 += z1;
      z0 += __shfl_xor_sync(0xffffffffu, z0, 8); z0 += __shfl_xor_sync(0xffffffffu, z0, 16);
      uint32_t xw = lds32(sb + RED + 64 + (lane & 4) * 4 + (lane & 2) * 2), hw = lds32(sb + RED + 72 + (lane & 4) * 4 + (lane & 2) * 2);
      z0 = bf_round(((lane & 1) ? bf_hi(hw) : bf_lo(hw)) + bf_round(bf_round(z0) * lds32f(sb + RED + 100))) + ((lane & 1) ? bf_hi(xw) : bf_lo(xw));
      uint32_t v = pack_bf16(z0, __shfl_down_sync(0xffffffffu, z0, 1)), v2 = __shfl_down_sync(0xffffffffu, v, 2);
      if (L) { if (tid == 0 || tid == 4) *(uint2*)(P.out + (size_t)idx * 1024 + bid * 8 + tid) = make_uint2(v, v2); PROFW(tid == 0, 28); }
      else if ((tid & 3) == 0 && tid < 64) st_ll(&P.g->x2[tid >> 3][2 * bid + ((tid >> 2) & 1)], v, v2, 0u, tag + 1);
    }
    if (L == 0) {
      PROFX(tid == 0, 22);
      FRESH();
      uint4 x, y; poll_ll2(&P.g->x2[bi][tid], &P.g->x2[bi][tid + 128], 0xffffffffu, tag + 1, x, y);
      x.z = y.x; x.w = y.y;
      if (wq == (bc & 3)) sts64f(sb + X2SEG + lane * 8, FL(bc < 4 ? x.x : x.z), FL(bc < 4 ? x.y : x.w));
      float s1 = 0.f, s2 = 0.f;
      sum8(x, s1, s2);
      #pragma unroll
      for (int o = 16; o; o >>= 1) { s1 += __shfl_xor_sync(0xffffffffu, s1, o); s2 += __shfl_xor_sync(0xffffffffu, s2, o); }
      sts64f(sb + RED + wq * 8, s1, s2);
      bar_sync(2, 128);
      y = lds128(sb + RED); uint4 y2 = lds128(sb + RED + 16);
      float m = ((FL(y.x) + FL(y.z)) + (FL(y2.x) + FL(y2.z))) * (1.f / 1024.f);
      put_bf16(norm8(x, m, rsqrtf(fmaxf(fmaf(-m, m, ((FL(y.y) + FL(y.w)) + (FL(y2.y) + FL(y2.w))) * (1.f / 1024.f)), 0.f) + LN_EPS)), sb + HV + tid * 8);
      mbar_wait(BAR(B_STG), 1); mbar_wait(BAR(B_STG + 1), 0); mbar_wait(BAR(B_STG + 2), 0);
      bar_sync(2, 128);
      PROFX(tid == 0, 30);
      float d0[4] = {0.f, 0.f, 0.f, 0.f}, d1[4] = {0.f, 0.f, 0.f, 0.f}, d2[4] = {0.f, 0.f, 0.f, 0.f};
      const uint32_t bd = (64 + (HV >> 4) + uni(bid & 3) * 32) | 0x10000u;
      #pragma unroll 1
      for (int ks = 0; ks < 8; ks++) {
        const uint32_t ad = (64 + (STG >> 4) + ks * 128) | (64u << 16);
        wg_fence();
        wgmma_ss_n8<0, 1>(d0, mkd<HI64>(ad), mkd<8>(bd + ks * 4), 1);
        wgmma_ss_n8<0, 1>(d1, mkd<HI64>(ad + 1024), mkd<8>(bd + ks * 4), 1);
        wgmma_ss_n8<0, 1>(d2, mkd<HI64>(ad + 2048), mkd<8>(bd + ks * 4), 1);
        wg_commit();
      }
      wg_wait<0>(); keep(d0); keep(d1); keep(d2);
      FRESH();
      if ((lane & 3) == (wq >> 1)) {
        uint4* dst = &P.g->patch[bid][(wq & 1) * 32 + (lane >> 2) * 2 + (wq >> 1)];
        st_ll(dst, UI(d0[0]), UI(d1[0]), UI(d2[0]), tag + 1); st_ll(dst + 16, UI(d0[2]), UI(d1[2]), UI(d2[2]), tag + 1);
      }
      PROFX(tid == 0, 31);
    }
  }
  if (bid == 0 && tid == 0) P.g->epoch = lds32(sb + INFO2 + 16) + 1;
  #undef blk
  #undef bid
  #undef fid
  #undef bi
  #undef bp
  #undef bc
  #undef FRESH
  #undef lane
  #undef wq
}

__global__ void __cluster_dims__(2, 1, 1) __launch_bounds__(512, 1) fused_kernel(const __grid_constant__ Params P) {
  extern __shared__ __align__(1024) uint8_t smem_raw[];
  const uint32_t sb = smem_u32(smem_raw);
  PROFT(threadIdx.x == 0, 0);
  if (threadIdx.x == 0) {
    for (int s = 0; s < 3; s++) mbar_init(BAR(B_FULLQ + s), 1);
    asm volatile("fence.mbarrier_init.release.cluster;" ::: "memory");
    #pragma unroll 1
    for (int s = 0; s < 3; s++) {
      mbar_expect_tx(BAR(B_FULLQ + s), 57344);
      tma_2d(sb + qa_off(s), &P.mX, s * 64, (BID >> 4) * 256, BAR(B_FULLQ + s));
      tma_3d(sb + qb_off(s), &P.mWq, (BID & 15) * 64, s * 64, 0, BAR(B_FULLQ + s));
    }
    if ((sb & 0x3FFFFu) != 1024) __trap();
  } else if (threadIdx.x >= 32 + B_EMPTYQ && threadIdx.x <= 32 + B_COUNT) {
    const int b = threadIdx.x == 32 + B_COUNT ? B_ROW : threadIdx.x - 32;
    const uint32_t cnt = b < B_XFREE ? (b == B_OFREE ? 1 : 2) : (b < B_KVRDY ? 3 : (b < B_KVFULL || b == B_ROW ? 4 : (b == B_PFREE ? 2 : 1)));
    mbar_init(BAR(b), cnt);
    asm volatile("fence.mbarrier_init.release.cluster;" ::: "memory");
  }
  __syncthreads();
  asm volatile("barrier.cluster.arrive.relaxed.aligned;" ::: "memory");
  const int wg = __shfl_sync(0xffffffffu, threadIdx.x >> 7, 0);
  if (wg < 2) { reg_inc<224>(); consumer(P, sb, wg); }
  else if (wg == 2) { reg_dec<40>(); aux(P, sb); }
  else {
    reg_dec<24>();
    asm volatile("barrier.cluster.wait.aligned;" ::: "memory");
    const int w = __shfl_sync(0xffffffffu, (threadIdx.x >> 5) & 3, 0);
    if (w == 0) loader(P, sb);
    else if (w < 3) storer(P, sb, w - 1);
    else if ((threadIdx.x & 31) == 0) stager(P, sb);
  }
}

typedef CUresult (*EncFn)(CUtensorMap*, CUtensorMapDataType, cuuint32_t, void*, const cuuint64_t*, const cuuint64_t*, const cuuint32_t*, const cuuint32_t*,
                          CUtensorMapInterleave, CUtensorMapSwizzle, CUtensorMapL2promotion, CUtensorMapFloatOOBfill);
static void mk_map(EncFn enc, CUtensorMap* m, const void* ptr, int rank, const cuuint64_t* dims, const cuuint64_t* strides, const cuuint32_t* box,
                   CUtensorMapSwizzle sw, CUtensorMapL2promotion pr) {
  cuuint32_t es[5] = {1, 1, 1, 1, 1};
  enc(m, CU_TENSOR_MAP_DATA_TYPE_BFLOAT16, rank, (void*)ptr, dims, strides, box, es, CU_TENSOR_MAP_INTERLEAVE_NONE, sw, pr, CU_TENSOR_MAP_FLOAT_OOB_FILL_NONE);
}
extern "C" void kernel_launch(void* const* d_in, const int* in_sizes, int n_in, void* d_out, int out_size) {
  (void)in_sizes; (void)n_in; (void)out_size;
  void* fn = nullptr; cudaDriverEntryPointQueryResult q;
  cudaGetDriverEntryPoint("cuTensorMapEncodeTiled", &fn, cudaEnableDefault, &q);
  EncFn enc = (EncFn)fn;
  cudaFuncSetAttribute(fused_kernel, cudaFuncAttributeMaxDynamicSharedMemorySize, SMEM_BYTES);
  Params P;
  const CUtensorMapSwizzle S128 = CU_TENSOR_MAP_SWIZZLE_128B, S64 = CU_TENSOR_MAP_SWIZZLE_64B, S0 = CU_TENSOR_MAP_SWIZZLE_NONE;
  const CUtensorMapL2promotion L256 = CU_TENSOR_MAP_L2_PROMOTION_L2_256B, L128 = CU_TENSOR_MAP_L2_PROMOTION_L2_128B;
  { cuuint64_t d[2] = {1024, 2048}, s[1] = {2048}; cuuint32_t b[2] = {64, 256}, bh[2] = {64, 128};
    mk_map(enc, &P.mX, d_in[0], 2, d, s, b, S128, L256); mk_map(enc, &P.mXh, d_in[0], 2, d, s, bh, S128, L256); }
  { cuuint64_t d[3] = {1024, 1024, 3}, s[2] = {6144, 2048}; cuuint32_t b[3] = {64, 64, 3}; mk_map(enc, &P.mWq, d_in[1], 3, d, s, b, S128, L256); }
  { cuuint64_t d[5] = {64, 32, 2, 16, 16}, s[4] = {2048, 65536, 131072, 128}; cuuint32_t b[5] = {64, 32, 1, 2, 2}; mk_map(enc, &P.mWo, d_in[2], 5, d, s, b, S128, L256); }
  { cuuint64_t d[2] = {3584, 1024}, s[1] = {7168}; cuuint32_t b[2] = {32, 128};
    mk_map(enc, &P.mWg, d_in[5], 2, d, s, b, S64, L128); mk_map(enc, &P.mWu, d_in[6], 2, d, s, b, S64, L128); }
  { cuuint64_t d[2] = {3072, 1024}, s[1] = {6144}; cuuint32_t b[2] = {32, 256}; mk_map(enc, &P.mWp, d_in[1], 2, d, s, b, S64, L128); }
  { cuuint64_t d[3] = {256, 3584, 4}, s[2] = {2048, 512}; cuuint32_t b[3] = {256, 8, 4}; mk_map(enc, &P.mWd, d_in[7], 3, d, s, b, S0, L128); }
  P.x0 = (const bf16*)d_in[0]; P.wqkv = (const bf16*)d_in[1]; P.wo = (const bf16*)d_in[2]; P.wr = (const bf16*)d_in[4]; P.wg = (const bf16*)d_in[5]; P.wu = (const bf16*)d_in[6]; P.wd = (const bf16*)d_in[7];
  P.out = (bf16*)d_out;
  cudaGetSymbolAddress((void**)&P.g, g_scr);
  for (int b = 0; b < 128; b++) {
    int j = b >> 1, quad = j < 4 ? 0 : (j < 36 ? 1 + (j - 4) % 8 : 9 + (j - 36) % 7), pos = j < 4 ? j : (j < 36 ? (j - 4) / 8 : (j - 36) / 7);
    int bid = ((quad >> 2) * 2 + (pos >> 1)) * 16 + ((quad & 3) * 2 + (pos & 1)) * 2 + (b & 1);
    int e = pos * 2 + (b & 1), fid = e < 7 ? quad * 7 + e : 112 + quad;
    P.map[b] = bid | fid << 8;
  }
  fused_kernel<<<128, 512, SMEM_BYTES>>>(P);
}
```

```cpp
#include <cuda_runtime.h>
#include <cuda_bf16.h>
#include <cuda.h>
#include <stdint.h>
#include <stddef.h>
typedef __nv_bfloat16 bf16;

template<int TB, int TA = 0> __device__ __forceinline__ void wgmma_ss_n192(float (&d)[96], uint64_t da, uint64_t db, int scale_d) {
  asm volatile("{\n.reg .pred p;\nsetp.ne.b32 p, %98, 0;\n"
    "wgmma.mma_async.sync.aligned.m64n192k16.f32.bf16.bf16 {%0, %1, %2, %3, %4, %5, %6, %7, %8, %9, %10, %11, %12, %13, %14, %15, %16, %17, %18, %19, %20, %21, %22, %23, %24, %25, %26, %27, %28, %29, %30, %31, %32, %33, %34, %35, %36, %37, %38, %39, %40, %41, %42, %43, %44, %45, %46, %47, %48, %49, %50, %51, %52, %53, %54, %55, %56, %57, %58, %59, %60, %61, %62, %63, %64, %65, %66, %67, %68, %69, %70, %71, %72, %73, %74, %75, %76, %77, %78, %79, %80, %81, %82, %83, %84, %85, %86, %87, %88, %89, %90, %91, %92, %93, %94, %95}, %96, %97, p, 1, 1, %100, %99;\n}\n"
    : "+f"(d[0]), "+f"(d[1]), "+f"(d[2]), "+f"(d[3]), "+f"(d[4]), "+f"(d[5]), "+f"(d[6]), "+f"(d[7]), "+f"(d[8]), "+f"(d[9]), "+f"(d[10]), "+f"(d[11]), "+f"(d[12]), "+f"(d[13]), "+f"(d[14]), "+f"(d[15]), "+f"(d[16]), "+f"(d[17]), "+f"(d[18]), "+f"(d[19]), "+f"(d[20]), "+f"(d[21]), "+f"(d[22]), "+f"(d[23]), "+f"(d[24]), "+f"(d[25]), "+f"(d[26]), "+f"(d[27]), "+f"(d[28]), "+f"(d[29]), "+f"(d[30]), "+f"(d[31]), "+f"(d[32]), "+f"(d[33]), "+f"(d[34]), "+f"(d[35]), "+f"(d[36]), "+f"(d[37]), "+f"(d[38]), "+f"(d[39]), "+f"(d[40]), "+f"(d[41]), "+f"(d[42]), "+f"(d[43]), "+f"(d[44]), "+f"(d[45]), "+f"(d[46]), "+f"(d[47]), "+f"(d[48]), "+f"(d[49]), "+f"(d[50]), "+f"(d[51]), "+f"(d[52]), "+f"(d[53]), "+f"(d[54]), "+f"(d[55]), "+f"(d[56]), "+f"(d[57]), "+f"(d[58]), "+f"(d[59]), "+f"(d[60]), "+f"(d[61]), "+f"(d[62]), "+f"(d[63]), "+f"(d[64]), "+f"(d[65]), "+f"(d[66]), "+f"(d[67]), "+f"(d[68]), "+f"(d[69]), "+f"(d[70]), "+f"(d[71]), "+f"(d[72]), "+f"(d[73]), "+f"(d[74]), "+f"(d[75]), "+f"(d[76]), "+f"(d[77]), "+f"(d[78]), "+f"(d[79]), "+f"(d[80]), "+f"(d[81]), "+f"(d[82]), "+f"(d[83]), "+f"(d[84]), "+f"(d[85]), "+f"(d[86]), "+f"(d[87]), "+f"(d[88]), "+f"(d[89]), "+f"(d[90]), "+f"(d[91]), "+f"(d[92]), "+f"(d[93]), "+f"(d[94]), "+f"(d[95])
    : "l"(da), "l"(db), "r"(scale_d), "n"(TB), "n"(TA));
}

template<int TB> __device__ __forceinline__ void wgmma_rs_n192(float (&d)[96], uint32_t a0, uint32_t a1, uint32_t a2, uint32_t a3, uint64_t db, int scale_d) {
  asm volatile("{\n.reg .pred p;\nsetp.ne.b32 p, %101, 0;\n"
    "wgmma.mma_async.sync.aligned.m64n192k16.f32.bf16.bf16 {%0, %1, %2, %3, %4, %5, %6, %7, %8, %9, %10, %11, %12, %13, %14, %15, %16, %17, %18, %19, %20, %21, %22, %23, %24, %25, %26, %27, %28, %29, %30, %31, %32, %33, %34, %35, %36, %37, %38, %39, %40, %41, %42, %43, %44, %45, %46, %47, %48, %49, %50, %51, %52, %53, %54, %55, %56, %57, %58, %59, %60, %61, %62, %63, %64, %65, %66, %67, %68, %69, %70, %71, %72, %73, %74, %75, %76, %77, %78, %79, %80, %81, %82, %83, %84, %85, %86, %87, %88, %89, %90, %91, %92, %93, %94, %95}, {%96, %97, %98, %99}, %100, p, 1, 1, %102;\n}\n"
    : "+f"(d[0]), "+f"(d[1]), "+f"(d[2]), "+f"(d[3]), "+f"(d[4]), "+f"(d[5]), "+f"(d[6]), "+f"(d[7]), "+f"(d[8]), "+f"(d[9]), "+f"(d[10]), "+f"(d[11]), "+f"(d[12]), "+f"(d[13]), "+f"(d[14]), "+f"(d[15]), "+f"(d[16]), "+f"(d[17]), "+f"(d[18]), "+f"(d[19]), "+f"(d[20]), "+f"(d[21]), "+f"(d[22]), "+f"(d[23]), "+f"(d[24]), "+f"(d[25]), "+f"(d[26]), "+f"(d[27]), "+f"(d[28]), "+f"(d[29]), "+f"(d[30]), "+f"(d[31]), "+f"(d[32]), "+f"(d[33]), "+f"(d[34]), "+f"(d[35]), "+f"(d[36]), "+f"(d[37]), "+f"(d[38]), "+f"(d[39]), "+f"(d[40]), "+f"(d[41]), "+f"(d[42]), "+f"(d[43]), "+f"(d[44]), "+f"(d[45]), "+f"(d[46]), "+f"(d[47]), "+f"(d[48]), "+f"(d[49]), "+f"(d[50]), "+f"(d[51]), "+f"(d[52]), "+f"(d[53]), "+f"(d[54]), "+f"(d[55]), "+f"(d[56]), "+f"(d[57]), "+f"(d[58]), "+f"(d[59]), "+f"(d[60]), "+f"(d[61]), "+f"(d[62]), "+f"(d[63]), "+f"(d[64]), "+f"(d[65]), "+f"(d[66]), "+f"(d[67]), "+f"(d[68]), "+f"(d[69]), "+f"(d[70]), "+f"(d[71]), "+f"(d[72]), "+f"(d[73]), "+f"(d[74]), "+f"(d[75]), "+f"(d[76]), "+f"(d[77]), "+f"(d[78]), "+f"(d[79]), "+f"(d[80]), "+f"(d[81]), "+f"(d[82]), "+f"(d[83]), "+f"(d[84]), "+f"(d[85]), "+f"(d[86]), "+f"(d[87]), "+f"(d[88]), "+f"(d[89]), "+f"(d[90]), "+f"(d[91]), "+f"(d[92]), "+f"(d[93]), "+f"(d[94]), "+f"(d[95])
    : "r"(a0), "r"(a1), "r"(a2), "r"(a3), "l"(db), "r"(scale_d), "n"(TB));
}

template<int TB, int TA = 0> __device__ __forceinline__ void wgmma_ss_n128(float (&d)[64], uint64_t da, uint64_t db, int scale_d) {
  asm volatile("{\n.reg .pred p;\nsetp.ne.b32 p, %66, 0;\n"
    "wgmma.mma_async.sync.aligned.m64n128k16.f32.bf16.bf16 {%0, %1, %2, %3, %4, %5, %6, %7, %8, %9, %10, %11, %12, %13, %14, %15, %16, %17, %18, %19, %20, %21, %22, %23, %24, %25, %26, %27, %28, %29, %30, %31, %32, %33, %34, %35, %36, %37, %38, %39, %40, %41, %42, %43, %44, %45, %46, %47, %48, %49, %50, %51, %52, %53, %54, %55, %56, %57, %58, %59, %60, %61, %62, %63}, %64, %65, p, 1, 1, %68, %67;\n}\n"
    : "+f"(d[0]), "+f"(d[1]), "+f"(d[2]), "+f"(d[3]), "+f"(d[4]), "+f"(d[5]), "+f"(d[6]), "+f"(d[7]), "+f"(d[8]), "+f"(d[9]), "+f"(d[10]), "+f"(d[11]), "+f"(d[12]), "+f"(d[13]), "+f"(d[14]), "+f"(d[15]), "+f"(d[16]), "+f"(d[17]), "+f"(d[18]), "+f"(d[19]), "+f"(d[20]), "+f"(d[21]), "+f"(d[22]), "+f"(d[23]), "+f"(d[24]), "+f"(d[25]), "+f"(d[26]), "+f"(d[27]), "+f"(d[28]), "+f"(d[29]), "+f"(d[30]), "+f"(d[31]), "+f"(d[32]), "+f"(d[33]), "+f"(d[34]), "+f"(d[35]), "+f"(d[36]), "+f"(d[37]), "+f"(d[38]), "+f"(d[39]), "+f"(d[40]), "+f"(d[41]), "+f"(d[42]), "+f"(d[43]), "+f"(d[44]), "+f"(d[45]), "+f"(d[46]), "+f"(d[47]), "+f"(d[48]), "+f"(d[49]), "+f"(d[50]), "+f"(d[51]), "+f"(d[52]), "+f"(d[53]), "+f"(d[54]), "+f"(d[55]), "+f"(d[56]), "+f"(d[57]), "+f"(d[58]), "+f"(d[59]), "+f"(d[60]), "+f"(d[61]), "+f"(d[62]), "+f"(d[63])
    : "l"(da), "l"(db), "r"(scale_d), "n"(TB), "n"(TA));
}

template<int TB, int TA = 0> __device__ __forceinline__ void wgmma_ss_n64(float (&d)[32], uint64_t da, uint64_t db, int scale_d) {
  asm volatile("{\n.reg .pred p;\nsetp.ne.b32 p, %34, 0;\n"
    "wgmma.mma_async.sync.aligned.m64n64k16.f32.bf16.bf16 {%0, %1, %2, %3, %4, %5, %6, %7, %8, %9, %10, %11, %12, %13, %14, %15, %16, %17, %18, %19, %20, %21, %22, %23, %24, %25, %26, %27, %28, %29, %30, %31}, %32, %33, p, 1, 1, %36, %35;\n}\n"
    : "+f"(d[0]), "+f"(d[1]), "+f"(d[2]), "+f"(d[3]), "+f"(d[4]), "+f"(d[5]), "+f"(d[6]), "+f"(d[7]), "+f"(d[8]), "+f"(d[9]), "+f"(d[10]), "+f"(d[11]), "+f"(d[12]), "+f"(d[13]), "+f"(d[14]), "+f"(d[15]), "+f"(d[16]), "+f"(d[17]), "+f"(d[18]), "+f"(d[19]), "+f"(d[20]), "+f"(d[21]), "+f"(d[22]), "+f"(d[23]), "+f"(d[24]), "+f"(d[25]), "+f"(d[26]), "+f"(d[27]), "+f"(d[28]), "+f"(d[29]), "+f"(d[30]), "+f"(d[31])
    : "l"(da), "l"(db), "r"(scale_d), "n"(TB), "n"(TA));
}

template<int TB, int TA = 0> __device__ __forceinline__ void wgmma_ss_n8(float (&d)[4], uint64_t da, uint64_t db, int scale_d) {
  asm volatile("{\n.reg .pred p;\nsetp.ne.b32 p, %6, 0;\n"
    "wgmma.mma_async.sync.aligned.m64n8k16.f32.bf16.bf16 {%0, %1, %2, %3}, %4, %5, p, 1, 1, %8, %7;\n}\n"
    : "+f"(d[0]), "+f"(d[1]), "+f"(d[2]), "+f"(d[3])
    : "l"(da), "l"(db), "r"(scale_d), "n"(TB), "n"(TA));
}

template<int TB> __device__ __forceinline__ void wgmma_rs_n40(float (&d)[20], uint32_t a0, uint32_t a1, uint32_t a2, uint32_t a3, uint64_t db, int scale_d) {
  asm volatile("{\n.reg .pred p;\nsetp.ne.b32 p, %25, 0;\n"
    "wgmma.mma_async.sync.aligned.m64n40k16.f32.bf16.bf16 {%0, %1, %2, %3, %4, %5, %6, %7, %8, %9, %10, %11, %12, %13, %14, %15, %16, %17, %18, %19}, {%20, %21, %22, %23}, %24, p, 1, 1, %26;\n}\n"
    : "+f"(d[0]), "+f"(d[1]), "+f"(d[2]), "+f"(d[3]), "+f"(d[4]), "+f"(d[5]), "+f"(d[6]), "+f"(d[7]), "+f"(d[8]), "+f"(d[9]), "+f"(d[10]), "+f"(d[11]), "+f"(d[12]), "+f"(d[13]), "+f"(d[14]), "+f"(d[15]), "+f"(d[16]), "+f"(d[17]), "+f"(d[18]), "+f"(d[19])
    : "r"(a0), "r"(a1), "r"(a2), "r"(a3), "l"(db), "r"(scale_d), "n"(TB));
}

#define DEVI __device__ __forceinline__
DEVI uint32_t smem_u32(const void* p) { return (uint32_t)__cvta_generic_to_shared(p); }
DEVI void mbar_init(uint32_t bar, uint32_t cnt) { asm volatile("mbarrier.init.shared::cta.b64 [%0], %1;" :: "r"(bar), "r"(cnt)); }
DEVI void mbar_expect_tx(uint32_t bar, uint32_t bytes) { asm volatile("mbarrier.arrive.expect_tx.shared::cta.b64 _, [%0], %1;" :: "r"(bar), "r"(bytes) : "memory"); }
DEVI void mbar_arrive(uint32_t bar) { asm volatile("mbarrier.arrive.shared::cta.b64 _, [%0];" :: "r"(bar) : "memory"); }
DEVI void mbar_arrive_peer(uint32_t bar) {
  asm volatile("{\n.reg .b32 ra;\nmapa.shared::cluster.u32 ra, %0, %1;\nmbarrier.arrive.shared::cluster.b64 _, [ra];\n}" :: "r"(bar), "r"((blockIdx.x & 1) ^ 1) : "memory");
}
DEVI void bulk_s2peer(uint32_t a, uint32_t bytes, uint32_t bar) {
  asm volatile("{\n.reg .b32 ra, rb;\nmapa.shared::cluster.u32 ra, %0, %3;\nmapa.shared::cluster.u32 rb, %2, %3;\n"
               "cp.async.bulk.shared::cluster.shared::cta.mbarrier::complete_tx::bytes [ra], [%0], %1, [rb];\n}"
               :: "r"(a), "r"(bytes), "r"(bar), "r"((blockIdx.x & 1) ^ 1) : "memory");
}
DEVI void mbar_wait(uint32_t bar, uint32_t parity) {
  asm volatile("{\n.reg .pred p;\nLW:\nmbarrier.try_wait.parity.shared::cta.b64 p, [%0], %1;\n@!p bra LW;\n}" :: "r"(bar), "r"(parity) : "memory");
}
DEVI uint32_t mbar_test(uint32_t bar, uint32_t parity) {
  uint32_t r; asm volatile("{\n.reg .pred p;\nmbarrier.test_wait.parity.shared::cta.b64 p, [%1], %2;\nselp.u32 %0, 1, 0, p;\n}" : "=r"(r) : "r"(bar), "r"(parity) : "memory"); return r;
}
DEVI void mbar_wait_b(uint32_t bar, uint32_t parity) {
  asm volatile("{\n.reg .pred p;\n.reg .u32 it;\nmov.u32 it, 0;\nLW:\nmbarrier.try_wait.parity.shared::cta.b64 p, [%0], %1;\n@p bra LD;\n"
               "add.u32 it, it, 1;\nsetp.lt.u32 p, it, 0x1000000;\n@p bra LW;\ntrap;\nLD:\n}" :: "r"(bar), "r"(parity) : "memory");
}
DEVI void tma_2d(uint32_t dst, const CUtensorMap* m, int c0, int c1, uint32_t bar) {
  asm volatile("cp.async.bulk.tensor.2d.shared::cluster.global.mbarrier::complete_tx::bytes [%0], [%1, {%3, %4}], [%2];"
    :: "r"(dst), "l"(m), "r"(bar), "r"(c0), "r"(c1) : "memory");
}
DEVI void tma_3d(uint32_t dst, const CUtensorMap* m, int c0, int c1, int c2, uint32_t bar) {
  asm volatile("cp.async.bulk.tensor.3d.shared::cluster.global.mbarrier::complete_tx::bytes [%0], [%1, {%3, %4, %5}], [%2];"
    :: "r"(dst), "l"(m), "r"(bar), "r"(c0), "r"(c1), "r"(c2) : "memory");
}
#define POL_EF POL_FIRST
constexpr uint64_t POL_FIRST = 0x12F0000000000000ull, POL_NORMAL = 0x1000000000000000ull;
DEVI void tma_2d_h(uint32_t dst, const CUtensorMap* m, int c0, int c1, uint32_t bar, uint64_t pol) {
  asm volatile("cp.async.bulk.tensor.2d.shared::cluster.global.mbarrier::complete_tx::bytes.L2::cache_hint [%0], [%1, {%3, %4}], [%2], %5;"
    :: "r"(dst), "l"(m), "r"(bar), "r"(c0), "r"(c1), "l"(pol) : "memory");
}
DEVI void tma_3d_h(uint32_t dst, const CUtensorMap* m, int c0, int c1, int c2, uint32_t bar, uint64_t pol) {
  asm volatile("cp.async.bulk.tensor.3d.shared::cluster.global.mbarrier::complete_tx::bytes.L2::cache_hint [%0], [%1, {%3, %4, %5}], [%2], %6;"
    :: "r"(dst), "l"(m), "r"(bar), "r"(c0), "r"(c1), "r"(c2), "l"(pol) : "memory");
}
DEVI void bulk_g2s_h(uint32_t s, const void* g, uint32_t bytes, uint32_t bar, uint64_t pol = POL_EF) {
  asm volatile("cp.async.bulk.shared::cluster.global.mbarrier::complete_tx::bytes.L2::cache_hint [%0], [%1], %2, [%3], %4;"
    :: "r"(s), "l"(g), "r"(bytes), "r"(bar), "l"(pol) : "memory");
}
DEVI void tma_5d(uint32_t dst, const CUtensorMap* m, int c0, int c1, int c2, int c3, int c4, uint32_t bar, uint64_t pol) {
  asm volatile("cp.async.bulk.tensor.5d.shared::cluster.global.mbarrier::complete_tx::bytes.L2::cache_hint [%0], [%1, {%3, %4, %5, %6, %7}], [%2], %8;"
    :: "r"(dst), "l"(m), "r"(bar), "r"(c0), "r"(c1), "r"(c2), "r"(c3), "r"(c4), "l"(pol) : "memory");
}
DEVI void tma_prefetch_2d(const CUtensorMap* m, int c0, int c1) {
  asm volatile("cp.async.bulk.prefetch.tensor.2d.L2.global.tile [%0, {%1, %2}];" :: "l"(m), "r"(c0), "r"(c1) : "memory");
}
DEVI void tma_prefetch_3d(const CUtensorMap* m, int c0, int c1, int c2) {
  asm volatile("cp.async.bulk.prefetch.tensor.3d.L2.global.tile [%0, {%1, %2, %3}];" :: "l"(m), "r"(c0), "r"(c1), "r"(c2) : "memory");
}
DEVI void bulk_prefetch(const void* g, uint32_t bytes) { asm volatile("cp.async.bulk.prefetch.L2.global [%0], %1;" :: "l"(g), "r"(bytes) : "memory"); }
DEVI void bulk_g2s(uint32_t s, const void* g, uint32_t bytes, uint32_t bar) {
  asm volatile("cp.async.bulk.shared::cluster.global.mbarrier::complete_tx::bytes [%0], [%1], %2, [%3];" :: "r"(s), "l"(g), "r"(bytes), "r"(bar) : "memory");
}
DEVI void bulk_s2g(void* g, uint32_t s, uint32_t bytes) {
  asm volatile("cp.async.bulk.global.shared::cta.bulk_group [%0], [%1], %2;\ncp.async.bulk.commit_group;" :: "l"(g), "r"(s), "r"(bytes) : "memory");
}
template<int N> DEVI void bulk_wait() { asm volatile("cp.async.bulk.wait_group %0;" :: "n"(N) : "memory"); }
DEVI void fence_async_smem() { asm volatile("fence.proxy.async.shared::cta;" ::: "memory"); }
DEVI void fence_async_glob() { asm volatile("fence.proxy.async.global;" ::: "memory"); }
DEVI unsigned ld_rlx(const unsigned* p) { unsigned v; asm volatile("ld.relaxed.gpu.global.u32 %0, [%1];" : "=r"(v) : "l"(p) : "memory"); return v; }
DEVI void st_rlx(unsigned* p, unsigned v) { asm volatile("st.relaxed.gpu.global.u32 [%0], %1;" :: "l"(p), "r"(v) : "memory"); }
DEVI uint2 ldg_stream(const uint2* p) { uint2 v; asm volatile("ld.global.nc.L1::no_allocate.v2.u32 {%0, %1}, [%2];" : "=r"(v.x), "=r"(v.y) : "l"(p)); return v; }
DEVI void fence_rel() { asm volatile("fence.release.gpu;" ::: "memory"); }
DEVI uint4 ld_ll(const uint4* p) {
  uint4 v;
  asm volatile("{\n.reg .b128 t;\n.reg .b64 a, b;\nld.relaxed.gpu.global.b128 t, [%4];\nmov.b128 {a, b}, t;\nmov.b64 {%0, %1}, a;\nmov.b64 {%2, %3}, b;\n}"
               : "=r"(v.x), "=r"(v.y), "=r"(v.z), "=r"(v.w) : "l"(p) : "memory");
  return v;
}
DEVI void st_ll(uint4* p, uint32_t x, uint32_t y, uint32_t z, uint32_t w) {
  asm volatile("{\n.reg .b128 t;\n.reg .b64 a, b;\nmov.b64 a, {%1, %2};\nmov.b64 b, {%3, %4};\nmov.b128 t, {a, b};\nst.relaxed.gpu.global.b128 [%0], t;\n}"
               :: "l"(p), "r"(x), "r"(y), "r"(z), "r"(w) : "memory");
}
#define SPIN_MAX 0x1000000
DEVI uint4 poll_ll(const uint4* p, uint32_t mask, uint32_t tag) {
  uint4 v; int it = 0;
  do { v = ld_ll(p); if (++it > SPIN_MAX) __trap(); } while (!__all_sync(0xffffffffu, (v.w & mask) == tag));
  return v;
}
DEVI void poll_ll2(const uint4* p, const uint4* q, uint32_t mask, uint32_t tag, uint4& a, uint4& b) {
  int it = 0;
  do { a = ld_ll(p); b = ld_ll(q); if (++it > SPIN_MAX) __trap(); } while (!__all_sync(0xffffffffu, (a.w & mask) == tag && (b.w & mask) == tag));
}
DEVI void bar_sync(int id, int n) { asm volatile("bar.sync %0, %1;" :: "r"(id), "r"(n) : "memory"); }
DEVI void bar_arrive(int id, int n) { asm volatile("bar.arrive %0, %1;" :: "r"(id), "r"(n) : "memory"); }
DEVI void wg_fence() { asm volatile("wgmma.fence.sync.aligned;" ::: "memory"); }
DEVI void wg_commit() { asm volatile("wgmma.commit_group.sync.aligned;" ::: "memory"); }
template<int N> DEVI void wg_wait() { asm volatile("wgmma.wait_group.sync.aligned %0;" :: "n"(N) : "memory"); }
template<int N> DEVI void reg_inc() { asm volatile("setmaxnreg.inc.sync.aligned.u32 %0;" :: "n"(N)); }
template<int N> DEVI void reg_dec() { asm volatile("setmaxnreg.dec.sync.aligned.u32 %0;" :: "n"(N)); }
DEVI float ex2f(float x) { float y; asm("ex2.approx.ftz.f32 %0, %1;" : "=f"(y) : "f"(x)); return y; }
DEVI uint32_t pack_bf16(float lo, float hi) { uint32_t r; asm("cvt.rn.bf16x2.f32 %0, %1, %2;" : "=r"(r) : "f"(hi), "f"(lo)); return r; }
DEVI float bf_lo(uint32_t v) { return __uint_as_float(v << 16); }
DEVI float bf_hi(uint32_t v) { return __uint_as_float(v & 0xffff0000u); }
DEVI float bf_round(float x) { return bf_lo(pack_bf16(x, 0.f)); }
DEVI void stsm_x4(uint32_t addr, uint32_t a, uint32_t b, uint32_t c, uint32_t d) {
  asm volatile("stmatrix.sync.aligned.m8n8.x4.shared.b16 [%0], {%1,%2,%3,%4};" :: "r"(addr), "r"(a), "r"(b), "r"(c), "r"(d) : "memory");
}
DEVI void ldsm_x4(uint32_t addr, uint32_t& a, uint32_t& b, uint32_t& c, uint32_t& d) {
  asm volatile("ldmatrix.sync.aligned.m8n8.x4.shared.b16 {%0,%1,%2,%3}, [%4];" : "=r"(a), "=r"(b), "=r"(c), "=r"(d) : "r"(addr) : "memory");
}
DEVI uint4 lds128(uint32_t a) { uint4 v; asm volatile("ld.shared.v4.u32 {%0,%1,%2,%3}, [%4];" : "=r"(v.x), "=r"(v.y), "=r"(v.z), "=r"(v.w) : "r"(a) : "memory"); return v; }
DEVI void sts128(uint32_t a, uint4 v) { asm volatile("st.shared.v4.u32 [%0], {%1,%2,%3,%4};" :: "r"(a), "r"(v.x), "r"(v.y), "r"(v.z), "r"(v.w) : "memory"); }
DEVI float2 lds64f(uint32_t a) { float2 v; asm volatile("ld.shared.v2.f32 {%0,%1}, [%2];" : "=f"(v.x), "=f"(v.y) : "r"(a) : "memory"); return v; }
DEVI void sts64f(uint32_t a, float x, float y) { asm volatile("st.shared.v2.f32 [%0], {%1,%2};" :: "r"(a), "f"(x), "f"(y) : "memory"); }
DEVI uint32_t lds32(uint32_t a) { uint32_t v; asm volatile("ld.shared.u32 %0, [%1];" : "=r"(v) : "r"(a) : "memory"); return v; }
DEVI float lds32f(uint32_t a) { return __uint_as_float(lds32(a)); }
DEVI void sts32(uint32_t a, uint32_t v) { asm volatile("st.shared.u32 [%0], %1;" :: "r"(a), "r"(v) : "memory"); }
DEVI void sts32f(uint32_t a, float v) { sts32(a, __float_as_uint(v)); }
DEVI void sts16(uint32_t a, uint32_t v) { asm volatile("st.shared.u16 [%0], %1;" :: "r"(a), "h"((unsigned short)v) : "memory"); }
template<int N> DEVI void keep(float (&d)[N]) {
  #pragma unroll
  for (int i = 0; i < N; i++) asm volatile("" : "+f"(d[i]) :: "memory");
}
template<int N> DEVI void keep(uint32_t (&d)[N]) {
  #pragma unroll
  for (int i = 0; i < N; i++) asm volatile("" : "+r"(d[i]) :: "memory");
}
template<uint32_t HI> DEVI uint64_t mkd(uint32_t lo) { uint64_t r; asm("mov.b64 %0, {%1, %2};" : "=l"(r) : "r"(lo), "n"(HI)); return r; }
constexpr uint32_t HI128 = (1u << 30) | (1024 >> 4), HI64 = (2u << 30) | (512 >> 4);
#define VOFF(x) ((uint32_t)(x) * (uint32_t)(1 - 65536))
DEVI bool elect() { uint32_t p; asm volatile("{\n.reg .pred q;\nelect.sync _|q, 0xffffffff;\nselp.u32 %0, 1, 0, q;\n}" : "=r"(p)); return p; }
DEVI void warp_signal(uint32_t bar) { __syncwarp(); if (elect()) mbar_arrive(bar); }

struct Scratch {
  uint4 kv[128][4][1024];
  uint4 o[8][2][8][2][1024];
  uint4 x[8][16][2048];
  uint4 zero[1024];
  uint4 statP[8][2048];
  uint4 statF[2048];
  uint4 csP[16][8][96];
  uint4 best[8][16];
  uint4 row[16][256];
  uint4 yP[128][112][2];
  uint4 x2[8][256];
  uint4 patch[128][64];
  unsigned flagKV[128][32];
  unsigned flagO[8][32];
  unsigned flagX[8][32];
  unsigned epoch;
};
__device__ __align__(1024) Scratch g_scr;
#define PROFT(cond, slot)
#define PROFW(cond, slot)
#define PROFD(cond, slot)
#define PROFX(cond, slot)
#define PROFY(cond, slot)

constexpr uint32_t SB0 = 65536, HOLE = 90112, SA2 = 98304, SB1 = 131072, SB2 = 155648, STG = 180224;
constexpr uint32_t KVA = 0, KVB = 98304, QO = 65536;
constexpr uint32_t MISC = 229376, CS = MISC, ONES = MISC + 768, BARS = MISC + 1792, INFO = MISC + 2208, WR = MISC + 2224, X2SEG = MISC + 2736, INFO2 = MISC + 2992, DUMP = MISC + 3040;
constexpr uint32_t PAR = HOLE, HV = HOLE + 2048, RED = HOLE + 6144, PATCH = 196608;
constexpr uint32_t SMEM_BYTES = 232448;
enum { B_FULLQ = 0, B_EMPTYQ = 3, B_FULLW = 6, B_EMPTYW = 12, B_HAFREE = 18, B_OFREE = 20,
       B_XFREE = 21,
       B_KVRDY = 23, B_ORDY = 27, B_XRDY = 35, B_STGE = 39,
       B_KVFULL = 42, B_RES = 46, B_PAR = 47, B_STG = 48, B_PFREE = 51, B_COUNT = 52,
       B_ROW = 154 };
#define BAR(x) (sb + BARS + 8 * (x))
DEVI uint32_t qa_off(int s) { return s == 2 ? SA2 : (uint32_t)s * 32768u; }
DEVI uint32_t qb_off(int s) { return s == 0 ? SB0 : (s == 1 ? SB1 : SB2); }
DEVI int kb_order(int bc, int n) {
  const int e = n < 9 ? n - 2 : n - 9;
  return n < 2 ? 2 * bc + n : 2 * (((e < 4 ? e + 4 : e - 4 + (e - 4 >= (bc & 3))) + (bc & 4)) & 7) + (n >= 9);
}
DEVI int wo_order(int bc, int n) { return (n & 8) | ((n + (bc & 6)) & 7); }
DEVI uint32_t w_off(int s) { return (uint32_t)((0x431065 >> (4 * s)) & 7) * 32768u; }
DEVI uint32_t w_par(int n, int s, int L) { return ((n >= 6 && n < 12) ^ (!(s & 2) && L)); }
DEVI int w_next(int n, int s) { return s == 5 ? 0 : (n == 13 ? 4 : s + 1); }

struct Params {
  CUtensorMap mX, mXh, mWq, mWo, mWg, mWu, mWp, mWd;
  const bf16 *x0, *wqkv, *wo, *wr, *wg, *wu, *wd;
  bf16* out;
  Scratch* g;
  unsigned map[128];
};
#define BID ((int)(P.map[blockIdx.x] & 255))
#define FID ((int)(P.map[blockIdx.x] >> 8))
DEVI uint32_t uni(uint32_t v) { return __shfl_sync(0xffffffffu, v, 0); }
#define PQ_N 8
#define PQ_T 700
#define PF0_N 10
#define PF0_T 1600
#define PF1_E 24
#define PF1_T 1100
#define POL_Q1 POL_NORMAL
#define POL_X POL_NORMAL
#define PFA0_BAR 3
#define PFA1_BAR 0
#define PFA0_M 0
#define PFA1_M 0
#define PFA0_T 900
#define PFA1_T 700
#define PF1_S PF0_N
#define PF1_D 0
#define POL_G POL_NORMAL
#define POL_U POL_FIRST
#define POL_D POL_FIRST
#define JQ_N 6
#define WDSRC (P.wd + (size_t)min(fid, 111) * 32768)
#define WDSRC2 (P.wd + FID * 32768)
#define WD_N 4
#define THR_N 6
#define KV_D 1300
#define XD_D 600
#define W0_BAR 3
#define QEF_N 11
#define PACE_T 300
#define POL_Q0 POL_NORMAL
constexpr float LN_EPS = 1e-5f;
constexpr float QSCALE = 0.17677669529663687f * 1.4426950408889634f;

DEVI void fma8(float (&a)[8], uint4 v, float h) {
  a[0] = fmaf(bf_lo(v.x), h, a[0]); a[1] = fmaf(bf_hi(v.x), h, a[1]); a[2] = fmaf(bf_lo(v.y), h, a[2]); a[3] = fmaf(bf_hi(v.y), h, a[3]);
  a[4] = fmaf(bf_lo(v.z), h, a[4]); a[5] = fmaf(bf_hi(v.z), h, a[5]); a[6] = fmaf(bf_lo(v.w), h, a[6]); a[7] = fmaf(bf_hi(v.w), h, a[7]);
}
DEVI uint4 ldsv128(uint32_t a) { uint4 v; asm volatile("ld.volatile.shared.v4.u32 {%0,%1,%2,%3}, [%4];" : "=r"(v.x), "=r"(v.y), "=r"(v.z), "=r"(v.w) : "r"(a) : "memory"); return v; }
DEVI float ldsv32f(uint32_t a) { float v; asm volatile("ld.volatile.shared.f32 %0, [%1];" : "=f"(v) : "r"(a) : "memory"); return v; }
DEVI uint32_t clk() { uint32_t t; asm volatile("mov.u32 %0, %%clock;" : "=r"(t)); return t; }
DEVI int fresh_tid() { int t; asm volatile("mov.u32 %0, %%tid.x;" : "=r"(t)); return t & 127; }
DEVI float fold8(const float (&a)[8]) {
  const int lane = threadIdx.x & 31;
  const bool u = lane & 16, v = lane & 8, x = lane & 4;
  float b0 = (u ? a[4] : a[0]) + __shfl_xor_sync(0xffffffffu, u ? a[0] : a[4], 16), b1 = (u ? a[5] : a[1]) + __shfl_xor_sync(0xffffffffu, u ? a[1] : a[5], 16);
  float b2 = (u ? a[6] : a[2]) + __shfl_xor_sync(0xffffffffu, u ? a[2] : a[6], 16), b3 = (u ? a[7] : a[3]) + __shfl_xor_sync(0xffffffffu, u ? a[3] : a[7], 16);
  float c0 = (v ? b2 : b0) + __shfl_xor_sync(0xffffffffu, v ? b0 : b2, 8), c1 = (v ? b3 : b1) + __shfl_xor_sync(0xffffffffu, v ? b1 : b3, 8);
  return (x ? c1 : c0) + __shfl_xor_sync(0xffffffffu, x ? c0 : c1, 4);
}
DEVI float swiglu(float g, float u) { g = bf_round(g); return bf_round(bf_round(__fdividef(g, 1.f + __expf(-g))) * bf_round(u)); }

DEVI void qk_issue(float (&s)[32], uint32_t qd, uint32_t kd) {
  wgmma_ss_n64<0>(s, mkd<HI64>(qd), mkd<HI64>(kd), 0);
  wgmma_ss_n64<0>(s, mkd<HI64>(qd + 2), mkd<HI64>(kd + 2), 1);
}
template<int J0, int J1> DEVI void exp_pack(const float (&s)[32], uint32_t (&p)[16]) {
  #pragma unroll
  for (int j = J0; j < J1; j++) p[j] = pack_bf16(ex2f(s[2 * j]), ex2f(s[2 * j + 1]));
}
DEVI bool attn_pack(const float (&o)[20], uint32_t (&ob)[8]) {
  const float lo = 5.421010862427522e-20f, hi = 1.8446744073709552e19f;
  float i0, i1; asm("rcp.approx.ftz.f32 %0, %1;" : "=f"(i0) : "f"(o[16])); asm("rcp.approx.ftz.f32 %0, %1;" : "=f"(i1) : "f"(o[18]));
  #pragma unroll
  for (int e = 0; e < 8; e++) ob[e] = pack_bf16(o[2 * e] * ((e & 1) ? i1 : i0), o[2 * e + 1] * ((e & 1) ? i1 : i0));
  return __all_sync(0xffffffffu, o[16] >= lo && o[16] <= hi && o[18] >= lo && o[18] <= hi);
}
DEVI void attn_store(const uint32_t (&ob)[8], bool ok, uint32_t st, uint32_t sb, uint32_t bar) {
  stsm_x4(ok ? st : sb + DUMP, ob[0], ob[1], ob[2], ob[3]); stsm_x4(ok ? st ^ 32 : sb + DUMP, ob[4], ob[5], ob[6], ob[7]);
  __syncwarp();
  asm volatile("{\n.reg .pred p, q;\nelect.sync _|q, 0xffffffff;\nsetp.ne.and.u32 p, %1, 0, q;\n@p mbarrier.arrive.shared::cta.b64 _, [%0];\n}" :: "r"(bar), "r"((uint32_t)ok) : "memory");
}
DEVI void attn_exact(uint32_t st, uint32_t kv, int t, bool hasprev, uint32_t bar) {
  const int lane = threadIdx.x & 31;
  #pragma unroll 1
  for (int row = ((threadIdx.x >> 5) & 3) * 16, n = 0; n < 16; n++, row++) {
    const int k1 = 256 + t * 64 + row;
    float m = -INFINITY, l = 0.f, o = 0.f;
    #pragma unroll 1
    for (int k0 = hasprev ? k1 - 255 : 256; k0 <= k1; k0 += 32) {
      const int k = min(k0 + lane, k1), r = k & 63;
      float sc = 0.f;
      #pragma unroll 1
      for (int c = 0; c < 16; c++) {
        uint32_t a = lds32(st + row * 64 + ((c * 4) ^ ((row & 6) << 3))), b = lds32(kv + (k >> 6) * 8192 + r * 64 + ((c * 4) ^ ((r & 6) << 3)));
        sc = fmaf(bf_lo(a), bf_lo(b), fmaf(bf_hi(a), bf_hi(b), sc));
      }
      float mn = fmaxf(m, sc);
      #pragma unroll 1
      for (int x = 16; x; x >>= 1) mn = fmaxf(mn, __shfl_xor_sync(0xffffffffu, mn, x));
      const float al = ex2f(m - mn), pr = ex2f(sc - mn);
      m = mn; l *= al; o *= al;
      #pragma unroll 1
      for (int q = k0; q <= min(k0 + 31, k1); q++) {
        const float z = __shfl_sync(0xffffffffu, pr, q - k0);
        uint32_t b = lds32(kv + (q >> 6) * 8192 + 4096 + (q & 63) * 64 + (((lane >> 1) * 4) ^ ((q & 6) << 3)));
        l += z; o = fmaf(z, (lane & 1) ? bf_hi(b) : bf_lo(b), o);
      }
    }
    __syncwarp();
    sts16(st + row * 64 + ((lane * 2) ^ ((row & 6) << 3)), pack_bf16(__fdividef(o, l), 0.f));
  }
  warp_signal(bar);
}

template<int K0, int K1, int DONE = 0> DEVI void exp_pv(const float (&s)[32], uint32_t (&p)[16], float (&o)[20], uint32_t vd, bool accum) {
  #pragma unroll
  for (int ks = K0; ks < K1; ks++) {
    if (ks >= DONE) {
      #pragma unroll
      for (int j = 4 * ks; j < 4 * ks + 4; j++) p[j] = pack_bf16(ex2f(s[2 * j]), ex2f(s[2 * j + 1]));
    }
    asm volatile("" : "+r"(p[4 * ks]), "+r"(p[4 * ks + 1]), "+r"(p[4 * ks + 2]), "+r"(p[4 * ks + 3]));
    wg_fence();
    wgmma_rs_n40<1>(o, p[ks * 4], p[ks * 4 + 1], p[ks * 4 + 2], p[ks * 4 + 3], mkd<HI64>(vd + VOFF(ks * 64)), ks ? 1 : accum);
  }
}
DEVI void exp_pv2(const float (&s)[32], const float (&sx)[32], uint32_t (&p)[16], uint32_t (&px)[16], float (&o)[20], uint32_t v0, uint32_t v4,
                  const uint32_t (&msk)[9], int tdiag) {
  #pragma unroll
  for (int ks = 0; ks < 4; ks++) {
    #pragma unroll
    for (int j = 4 * ks; j < 4 * ks + 4; j++) {
      const int c = 8 * (j >> 1) - 8 * (j & 1);
      const uint32_t e = pack_bf16(ex2f(c > tdiag ? s[2 * j] : sx[2 * j]), ex2f(c + 1 > tdiag ? s[2 * j + 1] : sx[2 * j + 1])), m = msk[(j >> 1) - (j & 1) + 1];
      p[j] = e & m; px[j] = e & ~m;
      asm volatile("" : "+r"(p[j]), "+r"(px[j]));
    }
    wg_fence();
    wgmma_rs_n40<1>(o, p[ks * 4], p[ks * 4 + 1], p[ks * 4 + 2], p[ks * 4 + 3], mkd<HI64>(v0 + VOFF(ks * 64)), 1);
    wgmma_rs_n40<1>(o, px[ks * 4], px[ks * 4 + 1], px[ks * 4 + 2], px[ks * 4 + 3], mkd<HI64>(v4 + VOFF(ks * 64)), 1);
  }
}

template<int J0> DEVI void qkv_store(const float (&a)[96], float p0, float p1, uint32_t d) {
  #pragma unroll
  for (int hh = 0; hh < 2; hh++) {
    const int j = 4 * (J0 + 2 * hh);
    stsm_x4(d ^ (hh << 5), pack_bf16(a[j] * p0, a[j + 1] * p0), pack_bf16(a[j + 2] * p1, a[j + 3] * p1),
                           pack_bf16(a[j + 4] * p0, a[j + 5] * p0), pack_bf16(a[j + 6] * p1, a[j + 7] * p1));
  }
}
DEVI void mean_step(float (&a)[96], float m0, float m1, uint32_t cd, bool z) {
  const uint32_t u0 = z ? 0u : __float_as_uint(m0), u1 = z ? 0u : __float_as_uint(m1);
  uint32_t ma[4] = {__byte_perm(u0, 0u, 0x1010), __byte_perm(u1, 0u, 0x1010), __byte_perm(u0, 0u, 0x3232), __byte_perm(u1, 0u, 0x3232)};
  keep(ma);
  wg_fence();
  wgmma_rs_n192<1>(a, ma[0], ma[1], ma[2], ma[3], mkd<2>(cd), 1);
  wg_commit();
}

template<bool FIRST> DEVI void qkv_block(float (&aX)[96], float (&aY)[96], uint32_t sb16, int s, int tX, int tY) {
  uint32_t a16 = sb16 + (qa_off(s) >> 4), b16 = (sb16 + (qb_off(s) >> 4)) | ((8192u >> 4) << 16);
  uint32_t ax = (a16 + tX * 512) | 0x10000u, ay = (a16 + tY * 512) | 0x10000u;
  wg_fence();
  #pragma unroll
  for (int ks = 0; ks < 4; ks++) {
    wgmma_ss_n192<1>(aX, mkd<HI128>(ax + ks * 2), mkd<HI128>(b16 + ks * 128), !(FIRST && ks == 0));
    wgmma_ss_n192<1>(aY, mkd<HI128>(ay + ks * 2), mkd<HI128>(b16 + ks * 128), !(FIRST && ks == 0));
  }
  wg_commit();
}
DEVI void qkv_half(float (&a)[96], uint32_t sb16, int t, uint32_t sa, uint32_t sbb) {
  wg_fence();
  #pragma unroll
  for (int ks = 0; ks < 4; ks++)
    wgmma_ss_n192<1>(a, mkd<HI128>(((sb16 + (sa >> 4) + t * 512) | 0x10000u) + ks * 2), mkd<HI128>(((sb16 + (sbb >> 4)) | ((8192u >> 4) << 16)) + ks * 128), 1);
  wg_commit();
}
template<bool FIRST> DEVI void wo_block(float (&acc)[64], uint32_t sb16, int s, int wg) {
  uint32_t a16 = (sb16 + (w_off(s) >> 4) + wg * 256) | 0x10000u, b16 = (sb16 + (w_off(s) >> 4) + 1024) | ((8192u >> 4) << 16);
  wg_fence();
  #pragma unroll
  for (int ks = 0; ks < 4; ks++)
    wgmma_ss_n128<1>(acc, mkd<HI64>(a16 + (ks >> 1) * 512 + (ks & 1) * 2), mkd<HI128>(b16 + ks * 128), !(FIRST && ks == 0));
  wg_commit();
}
DEVI void consumer(const Params& P, uint32_t sb, int wg) {
  const int w = uni((threadIdx.x >> 5) & 3);
  #define LAYER uni(mbar_test(BAR(B_RES), 0))
  #define IDS L = LAYER; const int tid = fresh_tid(), lane = tid & 31
  const uint32_t ids = uni(P.map[blockIdx.x]);
  const int bi = (ids >> 4) & 7, rh = ids & 1, bc = (ids & 15) >> 1, fid = ids >> 8;
  const int tX = 3 - wg, tY = wg;
  constexpr uint32_t sb16 = 1024 >> 4;
  #pragma unroll 1
  while (true) {
    int L = LAYER;
    {
      float aX[96], aY[96];
      const bool lead = fresh_tid() == 0;
      if (L) mbar_wait(BAR(B_XRDY + wg * 2 + 1), 0);
      mbar_wait(BAR(B_FULLQ), 0);
      PROFW(threadIdx.x == 0, L * 8 + 1);
      qkv_block<true>(aX, aY, sb16, 0, tX, tY);
      #pragma unroll 1
      for (int n = 1, s = 1, ps = 0, ph = 0; n < 14; n++) {
        mbar_wait(BAR(B_FULLQ + s), ph ^ (s ? L : 0));
        PROFD(threadIdx.x == 0 && L && (n == 2 || n == 3 || n == 7 || n == 11 || n == 13), n == 2 ? 48 : 49 + (n >> 2));
        qkv_block<false>(aX, aY, sb16, s, tX, tY);
        wg_wait<1>(); if (lead) mbar_arrive(BAR(B_EMPTYQ + ps));
        ps = s; if (s == 2) { s = 0; ph ^= 1; } else s++;
      }
      mbar_wait(BAR(B_ROW), L);
      IDS;
      const uint32_t pa = sb + PAR + (w * 16 + (lane >> 2)) * 8;
      float2 p0 = lds64f(pa + tX * 512), p1 = lds64f(pa + tX * 512 + 64), p2 = lds64f(pa + tY * 512), p3 = lds64f(pa + tY * 512 + 64);
      mean_step(aX, p0.y, p1.y, sb16 + (CS >> 4), lane & 3);
      mbar_wait(BAR(B_FULLQ + 2), L);
      qkv_half(aX, sb16, tX, SA2, SB2);
      mbar_wait(BAR(B_FULLQ), 1);
      qkv_half(aX, sb16, tX, 0, SB0);
      wg_wait<3>(); if (lead) mbar_arrive(BAR(B_EMPTYQ + 1));
      bar_sync(1, 256);
      qkv_half(aY, sb16, tY, SA2, SB2);
      wg_wait<1>(); keep(aX);
      const int srow = w * 16 + (lane & 15);
      const uint32_t x0 = sb + srow * 64 + (((lane >> 4) ^ ((srow >> 1) & 3)) << 4), xX = x0 + (4 + tX) * 8192, xY = x0 + (4 + tY) * 8192;
      qkv_store<8>(aX, p0.x, p1.x, xX + KVA); qkv_store<16>(aX, p0.x, p1.x, xX + KVA + 4096);
      warp_signal(BAR(B_KVRDY + wg * 2));
      qkv_half(aY, sb16, tY, 0, SB0);
      mean_step(aY, p2.y, p3.y, sb16 + (CS >> 4), fresh_tid() & 3);
      wg_wait<2>(); if (lead) mbar_arrive(BAR(B_EMPTYQ + 2));
      mbar_wait(BAR(B_EMPTYQ + 2), L);
      qkv_store<12>(aX, p0.x, p1.x, xX + KVB); qkv_store<20>(aX, p0.x, p1.x, xX + KVB + 4096);
      wg_wait<0>(); keep(aY);
      if (lead) mbar_arrive(BAR(B_EMPTYQ));
      PROFW(threadIdx.x == 0, L * 8 + 2);
      qkv_store<8>(aY, p2.x, p3.x, xY + KVA); qkv_store<16>(aY, p2.x, p3.x, xY + KVA + 4096);
      qkv_store<12>(aY, p2.x, p3.x, xY + KVB); qkv_store<20>(aY, p2.x, p3.x, xY + KVB + 4096);
      warp_signal(BAR(B_KVRDY + wg * 2 + 1));
      p0.x *= QSCALE; p1.x *= QSCALE; p2.x *= QSCALE; p3.x *= QSCALE;
      mbar_wait(BAR(B_EMPTYQ), 1);
      qkv_store<0>(aX, p0.x, p1.x, x0 + QO + tX * 4096);
      qkv_store<0>(aY, p2.x, p3.x, x0 + QO + tY * 4096); qkv_store<4>(aY, p2.x, p3.x, x0 + QO + 16384 + tY * 4096);
      mbar_wait(BAR(B_PAR), L);
      qkv_store<4>(aX, p0.x, p1.x, x0 + QO + 16384 + tX * 4096);
      const int prow = (int)uni(lds32(sb + INFO)) - bi * 256;
      if ((prow >> 4) == tX * 4 + w || (prow >> 4) == tY * 4 + w) {
        __syncwarp();
        if (lane < 24) sts128(sb + (prow & 63) * 64 + (((lane ^ (prow >> 1)) & 3) << 4) +
                              (lane < 8 ? QO + (lane >> 2) * 16384 + (prow >> 6) * 4096 : ((lane & 4) ? KVB : KVA) + (4 + (prow >> 6)) * 8192 + (lane >> 4) * 4096),
                              lds128(sb + PATCH + lane * 16));
      }
      fence_async_smem();
      bar_sync(1, 256);
    }
    PROFW(threadIdx.x == 0, L * 8 + 3);
    {
      IDS;
      float s0[32], s1[32], sx[32], o[20], op[20];
      uint32_t p0[16], p1[16], px[16], msk[9];
      const int tdiag = w * 16 + (lane >> 2) - 2 * (lane & 3);
      #pragma unroll
      for (int e = 0; e < 9; e++) msk[e] = ((8 * e - 8 > tdiag) ? 0xFFFFu : 0u) | ((8 * e - 7 > tdiag) ? 0xFFFF0000u : 0u);
      keep(msk);
      const uint32_t ones = (sb16 + (ONES >> 4)) << 16;
      const uint32_t qX = (sb16 + (QO >> 4) + tX * 256) | 0x10000u, qY = (sb16 + (QO >> 4) + tY * 256) | 0x10000u;
      const uint32_t kXB = (sb16 + (KVB >> 4) + tX * 512) | 0x10000u;
      uint32_t redo = 0;
      const uint32_t ost = sb + QO + (w * 16 + (lane & 15)) * 64 + (((lane >> 4) ^ ((lane >> 1) & 3)) << 4);
      #define QK(s, q, k) do { wg_fence(); qk_issue(s, q, k); wg_commit(); } while (0)
      #define QK2(q, k) do { wg_fence(); qk_issue(s1, q, k); qk_issue(sx, q, (k) + 2048); wg_commit(); } while (0)
      #define VB(v, b) ((v) + VOFF((b) * 512))
      QK(s0, qX + 1024, kXB + 1536);
      #pragma unroll
      for (int e = 0; e < 20; e++) o[e] = 0.f;
      wg_wait<0>(); keep(s0);
      #pragma unroll 1
      for (int h = 1; h >= 0; h--) {
        const uint32_t kXA = kXB - ((KVB - KVA) >> 4), kX = h ? kXB : kXA, vX = VOFF((kX & 0xffffu) + 256) + ones;
        QK(s1, qX + h * 1024, kX + 1024);
        #pragma unroll
        for (int e = 0; e < 20; e++) op[e] = o[e];
        keep(op);
        exp_pv<0, 4>(s0, p0, o, VB(vX, 3), false); wg_commit();
        wg_wait<1>(); keep(s1);
        exp_pv<0, 2>(s1, p1, o, VB(vX, 2), true);
        bar_sync(h ? 12 + wg : 4 + wg * 4, h ? 128 : 160);
        QK(s0, qX, kXA + 512 + h * 1024);
        exp_pv<2, 4>(s1, p1, o, VB(vX, 2), true); wg_commit();
        wg_wait<0>(); keep(s0); keep(p0); keep(p1); keep(o);
      }
      #pragma unroll 1
      for (int h = 0; h < 2; h++) {
        const uint32_t kb16 = sb16 + ((h ? KVB : KVA) >> 4), kY = (kb16 + tY * 512) | 0x10000u, qy = qY + h * 1024;
        const uint32_t onesP = bi ? ones : (kb16 + 1984) << 16;
        const uint32_t vX = VOFF(kb16 + tX * 512 + 256), vY = VOFF(kb16 + tY * 512 + 256);
        uint32_t ob[8];
        QK2(qX + h * 1024, (kb16 + tX * 512) | 0x10000u);
        exp_pv<0, 4>(s0, p0, o, VB(vX + (wg ? onesP : ones), 1), true); wg_commit();
        wg_wait<1>(); keep(s1); keep(sx);
        QK(s0, qy, kY + 1536);
        exp_pv2(s1, sx, p1, px, o, vX + onesP, VB(vX + ones, 4), msk, tdiag); wg_commit();
        wg_wait<1>(); keep(s0); keep(p0);
        QK(s1, qy, kY + 1024);
        exp_pack<0, 4>(s0, p0);
        wg_wait<1>(); keep(o); keep(p1); keep(px);
        bool ok = attn_pack(o, ob); keep(ob);
        exp_pv<0, 4, 1>(s0, p0, o, VB(vY + (wg ? ones : onesP), 3), false); wg_commit();
        attn_store(ob, ok, ost + (h * 4 + tX) * 4096, sb, BAR(B_ORDY + wg * 4 + h * 2)); redo |= ok ? 0u : 1u << (h * 2);
        wg_wait<1>(); keep(s1);
        exp_pv<0, 2>(s1, p1, o, VB(vY + onesP, 2), true);
        bar_sync(5 + wg * 4 + h * 2, 160);
        QK(s0, qy, kY + 512);
        exp_pv<2, 4>(s1, p1, o, VB(vY + onesP, 2), true); wg_commit();
        wg_wait<1>(); keep(s0); keep(p0);
        QK2(qy, kY);
        exp_pv<0, 4>(s0, p0, o, VB(vY + onesP, 1), true); wg_commit();
        wg_wait<1>(); keep(s1); keep(sx); keep(p1);
        bar_sync(6 + wg * 4, h ? 128 : 160);
        QK(s0, h ? qy : qX + 1024, kXB + 512);
        exp_pv2(s1, sx, p1, px, o, vY + onesP, VB(vY + ones, 4), msk, tdiag); wg_commit();
        wg_wait<0>(); keep(o); keep(s0); keep(p0); keep(p1); keep(px);
        ok = attn_pack(o, ob); attn_store(ob, ok, ost + (h * 4 + tY) * 4096, sb, BAR(B_ORDY + wg * 4 + h * 2 + 1)); redo |= ok ? 0u : 2u << (h * 2);
        #pragma unroll
        for (int e = 0; e < 20; e++) o[e] = op[e];
      }
      #undef QK
      #undef QK2
      #undef VB
      if (redo) {
        #pragma unroll 1
        for (int u = 0; u < 4; u++) if ((redo >> u) & 1) {
          const int h = u >> 1, t = (u & 1) ? tY : tX;
          attn_exact(sb + QO + (h * 4 + t) * 4096, sb + (h ? KVB : KVA), t, bi > 0, BAR(B_ORDY + wg * 4 + u));
        }
      }
    }
    PROFW(threadIdx.x == 0, L * 8 + 4);
    {
      IDS;
      const int t256 = wg * 128 + tid;
      float acc[64];
      const int tt = wg ^ rh;
      const int grow = bi * 256 + rh * 128 + tt * 64 + w * 16 + (lane >> 2);
      float al0 = 1.f, be0 = 0.f, al1 = 1.f, be1 = 0.f;
      const int idx0 = (int)uni(lds32(sb + INFO));
      const uint32_t tag = lds32(sb + INFO + 8) + L;
      uint4* const sp = &P.g->statP[bc][grow + (lane & 1) * 8];
      uint4* const yp = &P.g->yP[t256 >> 1][min(fid, 111)][t256 & 1];
      mbar_wait(BAR(B_FULLW), L);
      PROFW(t256 == 0, L * 8 + 5);
      wo_block<true>(acc, sb16, 0, tt);
      if (!(lane & 2)) st_ll(sp, 0u, 0u, 0u, 0u);
      uint4 fa = make_uint4(0u, 0u, 0u, 0u), fb = fa;
      uint2 wd[4];
      if (L) {
        if (fid < 112) st_ll(yp, 0u, 0u, 0u, 0u);
        fa = ld_ll(&P.g->statF[grow]); fb = ld_ll(&P.g->statF[grow + 8]);
      }
      #pragma unroll
      for (int e = 0; e < 4; e++) { wd[e] = make_uint2(0u, 0u); if (L) wd[e] = ldg_stream((const uint2*)(WDSRC) + t256 + (28 + e) * 256); }
      #pragma unroll 1
      for (int n = 1, q = 1, pq = 0; n < 16; n++) {
        mbar_wait(BAR(B_FULLW + q), w_par(n, q, L));
        PROFD(t256 == 0 && !L && (n == 4 || n == 7 || n == 8 || n == 12), (n == 7 ? 63 : 41 + (n >> 2)));
        wo_block<false>(acc, sb16, q, tt);
        wg_wait<1>(); if (tid == 0) mbar_arrive(BAR(B_EMPTYW + pq));
        pq = q; q = w_next(n, q);
      }
      if (L) {
        float r0 = rsqrtf(__uint_as_float(fa.y) + LN_EPS), r1 = rsqrtf(__uint_as_float(fb.y) + LN_EPS);
        if (grow != idx0) { al0 = 1.f + r0; be0 = -__uint_as_float(fa.x) * r0; }
        if (grow + 8 != idx0) { al1 = 1.f + r1; be1 = -__uint_as_float(fb.x) * r1; }
      }
      mbar_wait(BAR(B_RES), L);
      const int srow = tt * 64 + w * 16 + (lane & 15);
      const uint32_t ra = sb + rh * 16384 + srow * 128, sw = ((lane >> 4) ^ (srow & 7)) << 4;
      if ((idx0 >> 4) == bi * 16 + rh * 8 + tt * 4 + w) {
        int r = idx0 & 127;
        if (lane < 16) sts128(sb + (lane >> 3) * 32768 + rh * 16384 + r * 128 + (((lane & 7) ^ (r & 7)) << 4), lds128(sb + X2SEG + lane * 16));
        __syncwarp();
      }
      uint32_t rs[32];
      #pragma unroll
      for (int jj = 0; jj < 8; jj++) ldsm_x4((ra + (jj >> 2) * 32768) + (sw ^ ((jj & 3) << 5)), rs[4 * jj], rs[4 * jj + 1], rs[4 * jj + 2], rs[4 * jj + 3]);
      float rf[64];
      #pragma unroll
      for (int e = 0; e < 32; e++) { rf[2 * e] = fmaf(bf_lo(rs[e]), (e & 1) ? al1 : al0, (e & 1) ? be1 : be0); rf[2 * e + 1] = fmaf(bf_hi(rs[e]), (e & 1) ? al1 : al0, (e & 1) ? be1 : be0); }
      keep(rf);
      mbar_wait(BAR(B_RES), L);
      wg_wait<0>(); keep(acc);
      if (tid == 0) mbar_arrive(BAR(B_EMPTYW + 5));
      PROFW(t256 == 0, L * 8 + 6);
      #pragma unroll
      for (int jj = 0; jj < 8; jj++) {
        float* a = acc + 8 * jj;
        #pragma unroll
        for (int e = 0; e < 8; e++) a[e] += rf[8 * jj + e];
        stsm_x4((ra + (jj >> 2) * 32768) + (sw ^ ((jj & 3) << 5)), pack_bf16(a[0], a[1]), pack_bf16(a[2], a[3]), pack_bf16(a[4], a[5]), pack_bf16(a[6], a[7]));
        if (jj == 7) fence_async_smem();
        if ((jj & 3) == 3) warp_signal(BAR(B_XRDY + wg * 2 + (jj >> 2)));
      }
      {
        float s1a = 0.f, s2a = 0.f, da = 0.f, s1b = 0.f, s2b = 0.f, db = 0.f;
        #pragma unroll
        for (int j = 0; j < 16; j++) {
          const float* a = acc + 4 * j; float2 wv = lds64f(sb + WR + j * 32 + (lane & 3) * 8);
          s1a += a[0] + a[1]; s1b += a[2] + a[3];
          s2a = fmaf(a[0], a[0], s2a); s2b = fmaf(a[2], a[2], s2b); s2a = fmaf(a[1], a[1], s2a); s2b = fmaf(a[3], a[3], s2b);
          da = fmaf(a[0], wv.x, da); db = fmaf(a[2], wv.x, db); da = fmaf(a[1], wv.y, da); db = fmaf(a[3], wv.y, db);
        }
        bool odd = lane & 1;
        float u1 = (odd ? s1b : s1a) + __shfl_xor_sync(0xffffffffu, odd ? s1a : s1b, 1);
        float u2 = (odd ? s2b : s2a) + __shfl_xor_sync(0xffffffffu, odd ? s2a : s2b, 1);
        float u3 = (odd ? db : da) + __shfl_xor_sync(0xffffffffu, odd ? da : db, 1);
        u1 += __shfl_xor_sync(0xffffffffu, u1, 2); u2 += __shfl_xor_sync(0xffffffffu, u2, 2); u3 += __shfl_xor_sync(0xffffffffu, u3, 2);
        if (!(lane & 2)) st_ll(sp, __float_as_uint(u1), __float_as_uint(u2), __float_as_uint(u3), tag);
      }
      PROFW(t256 == 0, L * 8 + 7);
      if (L) {
        mbar_wait(BAR(B_PAR), 0);
        { float2 pa = lds64f(sb + PAR + (grow & 127) * 8), pb = lds64f(sb + PAR + (grow & 127) * 8 + 64); al0 = pa.x; be0 = pa.y; al1 = pb.x; be1 = pb.y; }
        #pragma unroll
        for (int j = 0; j < 16; j++) {
          rs[2 * j] = pack_bf16(fmaf(acc[4 * j], al0, be0), fmaf(acc[4 * j + 1], al0, be0));
          rs[2 * j + 1] = pack_bf16(fmaf(acc[4 * j + 2], al1, be1), fmaf(acc[4 * j + 3], al1, be1));
        }
        #pragma unroll
        for (int jj = 0; jj < 8; jj++) stsm_x4((ra + (jj >> 2) * 32768) + (sw ^ ((jj & 3) << 5)), rs[4 * jj], rs[4 * jj + 1], rs[4 * jj + 2], rs[4 * jj + 3]);
        PROFW(t256 == 0, 16);
        if (fid >= 112) bar_arrive(3, 384);
        else {
          float d[4] = {0.f, 0.f, 0.f, 0.f};
          mbar_wait(BAR(B_FULLW + wg * 4), 0); mbar_wait(BAR(B_FULLW + wg * 4 + 1), 0);
          bar_sync(3, 384);
          PROFW(t256 == 0, 29);
          #pragma unroll 1
          for (int g = 0; g < 4; g++) {
            const uint32_t ad = (sb16 + (wg ? 6144 : 10240) + (g >> 1) * 2048 + (g & 1) * 512) | (1024u << 16), bd = (sb16 + (HV >> 4) + wg * 64 + g * 16) | 0x10000u;
            wg_fence();
            #pragma unroll
            for (int ks = 0; ks < 8; ks++) wgmma_ss_n8<0, 1>(d, mkd<HI64>(ad + ks * 64), mkd<8>(bd + ks * 2), 1);
            wg_commit();
          }
          mbar_wait(BAR(B_FULLW + 2), 0);
          wg_wait<0>(); keep(d);
          if (!(lane & 3)) { sts32f(sb + PAR + 1024 + wg * 256 + w * 64 + lane, d[0]); sts32f(sb + PAR + 1056 + wg * 256 + w * 64 + lane, d[2]); }
          bar_sync(1, 256);
          const uint32_t ga = sb + PAR + 1024 + lane * 4, aa = sb + HV + (t256 >> 5) * 128;
          sts32f(aa + lane * 4, swiglu(lds32f(ga) + lds32f(ga + 256), lds32f(ga + 128) + lds32f(ga + 384)));
          __syncwarp();
          PROFW(t256 == 0, 26);
          float y0 = 0.f, y1 = 0.f, y2 = 0.f, y3 = 0.f;
          uint32_t tbl = rh ? 0x001459a8u : 0x023679a8u;
          uint4 a4 = lds128(aa + 112);
          #pragma unroll 2
          for (int n = 0; n < 8; n++, tbl >>= 4) {
            const uint32_t src = sb + t256 * 8 + (tbl & 15) * 8192;
            const uint4 an = lds128(aa + ((0x00123564u >> (4 * n)) & 15) * 16);
            #pragma unroll
            for (int e = 0; e < 4; e++) {
              const float av = __uint_as_float(e == 0 ? a4.x : (e == 1 ? a4.y : (e == 2 ? a4.z : a4.w)));
              y0 = fmaf(bf_lo(wd[e].x), av, y0); y1 = fmaf(bf_hi(wd[e].x), av, y1); y2 = fmaf(bf_lo(wd[e].y), av, y2); y3 = fmaf(bf_hi(wd[e].y), av, y3);
              const float2 v = lds64f(src + e * 2048); wd[e] = make_uint2(__float_as_uint(v.x), __float_as_uint(v.y));
            }
            a4 = an;
          }
          st_ll(yp, __float_as_uint(y0), __float_as_uint(y1), __float_as_uint(y2), (__float_as_uint(y3) & ~255u) | (lds32(sb + INFO + 12) + 1));
          PROFW(t256 == 0, 27);
        }
        return;
      }
    }
  }
  #undef IDS
  #undef LAYER
}

DEVI void loader(const Params& P, uint32_t sb) {
  const int lane = threadIdx.x & 31;
  const int bid = uni(BID), bi = bid >> 4, bp = bid & 15, rh = bp & 1, bc = bp >> 1;
  uint32_t phq = 0, tag = 0;
  #pragma unroll 1
  for (int L = 0; L < 2; L++) {
    int s = 0;
    uint32_t rdy = 0;
    #pragma unroll 1
    for (int n = L ? 0 : 3; n < 16; n++) {
      int kb = L ? kb_order(bc, n) : n;
      mbar_wait(BAR(B_EMPTYQ + s), (phq >> s) & 1);
      phq ^= 1u << s;
      if (L && n == 1) { mbar_wait(BAR(B_XRDY + 1), 0); mbar_wait(BAR(B_XRDY + 3), 0); }
      if (lane == 0) {
        mbar_expect_tx(BAR(B_FULLQ + s), L && n < 2 ? 40960 : 57344);
        tma_3d_h(sb + qb_off(s), &P.mWq, bp * 64, kb * 64, 0, BAR(B_FULLQ + s), L && n >= QEF_N ? POL_FIRST : POL_NORMAL);
        if (!L) tma_2d(sb + qa_off(s), &P.mX, kb * 64, bi * 256, BAR(B_FULLQ + s));
      }
      if (L && n >= 2) {
        if (((rdy >> (2 * kb)) & 3) != 3) {
          do { rdy = __ballot_sync(0xffffffffu, ld_rlx(&P.g->flagX[bi][lane]) == tag); } while (((rdy >> (2 * kb)) & 3) != 3);
          fence_async_glob();
        }
        if (n == 3 || n == 4) mbar_wait(BAR(B_XFREE + n - 3), 0);
        if (lane == 0) bulk_g2s_h(sb + qa_off(s), P.g->x[bi][kb], 32768, BAR(B_FULLQ + s), POL_X);
      }
      PROFY(L && lane == 0 && (n == 2 || n == 3 || n == 9), n == 9 ? 60 : 56 + n);
      if (L && n == 2) { mbar_wait(BAR(B_FULLQ), 0); mbar_wait(BAR(B_FULLQ + 1), 1); if (lane < 2) mbar_arrive_peer(BAR(B_XFREE + lane)); }
      s = (s == 2) ? 0 : s + 1;
    }
    for (int q = 0; q < 3; q++) mbar_wait(BAR(B_EMPTYQ + q), (phq >> q) & 1);
    tag = lds32(sb + INFO + 8) + L;
    #pragma unroll 1
    for (int q = 0; q < 4; q++) {
            if (bi) {
        const unsigned* f = &P.g->flagKV[bid - 16][q];
        while (ld_rlx(f) != tag);
        fence_async_glob();
      }
      if (lane == 0) {
        mbar_expect_tx(BAR(B_KVFULL + q), 16384);
        bulk_g2s_h(sb + ((q >> 1) ? KVB : KVA) + ((q & 1) ? 0 : 16384), bi ? P.g->kv[bid - 16][q] : P.g->zero, 16384, BAR(B_KVFULL + q));
      }
      PROFY(!L && lane == 0 && bi && q != 2, 34 + (q + 1) / 2);
    }
    mbar_wait(BAR(B_ORDY), L);
    {
      const uint4* src = P.g->o[bi][0][0][rh];
      rdy = 0;
      #pragma unroll 1
      for (int n = 0, q = 0; n < 16; q = w_next(n, q), n++) {
        const int j = wo_order(bc, n);
        if (((rdy >> (2 * j)) & 3) != 3) {
          do { rdy = __ballot_sync(0xffffffffu, ld_rlx(&P.g->flagO[bi][lane]) == tag); } while (((rdy >> (2 * j)) & 3) != 3);
          fence_async_glob();
        }
        if (n >= 2) mbar_wait(n < 6 ? BAR(B_HAFREE + (n >> 2)) : BAR(B_EMPTYW + q), n < 6 ? L : w_par(n - 6, q, L));
        if (n == THR_N) mbar_wait(BAR(B_OFREE), L);
        if (lane == 0) { mbar_expect_tx(BAR(B_FULLW + q), 16384); bulk_g2s_h(sb + w_off(q), src + j * 2048, 16384, BAR(B_FULLW + q)); }
      }
    }
    mbar_wait(BAR(B_OFREE), L);
  }
}

DEVI void ffn_prefetch(const Params& P, int q) {
  bulk_prefetch(q < 16 ? ((q & 1) ? P.wu : P.wg) + ((q >> 1) * 128 + blockIdx.x) * 3584 : P.wd + (min(FID, 111) * 8 + q - 16) * 4096, q < 16 ? 7168 : 8192);
}
DEVI void storer(const Params& P, uint32_t sb, int wg) {
  const int bid = uni(BID), bi = bid >> 4, rh = bid & 1, bc = (bid & 15) >> 1;
  const bool one = (threadIdx.x & 31) == 0;
  char* const g = (char*)P.g;
  #pragma unroll 1
  for (int L = 0; L < 2; L++) {
    mbar_wait(BAR(B_ROW), L);
    const uint32_t tag = lds32(sb + INFO + 8) + L;
    if (wg) { mbar_wait(BAR(B_KVRDY), L); mbar_wait(BAR(B_KVRDY + 2), L); const uint32_t t0 = clk(); while (clk() - t0 < KV_D) __nanosleep(40); }
    #pragma unroll 1
    for (int u = 0; u < 2 + 4 * wg; u++) {
      const int h = u < 2 ? u : u >> 2, hi = (u & 1) ^ 1;
      uint32_t src, dst, fl, b0, b1;
      if (u < 2) {
        src = (h ? KVB : KVA) + (3 - wg) * 16384; dst = offsetof(Scratch, kv) + (bid * 4 + h * 2 + wg) * 16384; fl = offsetof(Scratch, flagKV) + (bid * 32 + h * 2 + wg) * 4;
        b0 = BAR(B_KVRDY + ((u | wg) ? 1 : 0)); b1 = b0 + 16;
      } else {
        src = QO + (h * 2 + hi) * 8192; dst = offsetof(Scratch, o) + ((((bi * 2 + h) * 8 + bc) * 2 + hi) * 2 + rh) * 8192;
        fl = offsetof(Scratch, flagO) + (bi * 32 + h * 16 + (bid & 15)) * 4;
        b0 = BAR(B_ORDY + u - 2); b1 = b0 + 32;
      }
      mbar_wait(b0, L); mbar_wait(b1, L);
      fence_async_smem();
      PROFY(one && !L && u == 3 * wg, u ? 46 : 8);
      if (one && (u >= 2 || bi < 7)) bulk_s2g(g + dst, sb + src, u < 2 ? 16384 : 8192);
      if (one && u == 5) mbar_arrive(BAR(B_HAFREE + 1));
      if (u == 2 || u == 4) continue;
      bulk_wait<0>();
      PROFY(one && !L && u == 3 * wg, u ? 61 : 62);
      fence_rel();
      if (one) { st_rlx((unsigned*)(g + fl), tag); if (!wg || u > 2) mbar_arrive(BAR(B_HAFREE + h + (wg & h))); }
      PROFY(one && !L && (u > 2 || u == wg), u > 2 ? (u == 3 ? 38 : 54) : 32 + u);
    }
    if (L == 0) {
      char* dst = g + (offsetof(Scratch, x) + (bi * 16 + 2 * bc) * 32768 + rh * 16384);
      unsigned* f = (unsigned*)(g + (offsetof(Scratch, flagX) + (bi * 32 + bc * 4 + rh) * 4));
      const uint32_t a = sb + rh * 16384;
      if (wg == 0) {
        mbar_wait(BAR(B_XRDY), 0); mbar_wait(BAR(B_XRDY + 2), 0);
        fence_async_smem();
        PROFY(one, 41);
        if (one) bulk_s2g(dst, a, 16384);
        bulk_wait<0>();
        PROFY(one, 45);
        if (one) { mbar_arrive(BAR(B_XFREE)); mbar_arrive(BAR(B_PFREE)); }
        fence_rel();
        mbar_wait(BAR(B_XRDY + 1), 0); mbar_wait(BAR(B_XRDY + 3), 0);
        if (one) { st_rlx(f, tag); bulk_s2g(dst + 32768, a + 32768, 16384); }
        PROFY(one, 56);
        bulk_wait<0>();
        if (one) mbar_arrive(BAR(B_XFREE + 1));
        fence_rel();
        if (one) st_rlx(f + 2, tag);
        PROFY(one, 57);
      } else {
        mbar_wait(BAR(B_XRDY + 1), 0); mbar_wait(BAR(B_XRDY + 3), 0);
        mbar_wait(BAR(B_PFREE), 0);
        if (one) bulk_s2peer(a, 16384, BAR(B_FULLQ));
        { const uint32_t t0 = clk(); while (clk() - t0 < XD_D); }
        if (one) bulk_s2peer(a + 32768, 16384, BAR(B_FULLQ + 1));
      }
      if (wg == 0) {
        uint32_t t0 = clk() + PF1_D;
        #pragma unroll 1
        for (int q = PF1_S; q < PF1_E; q++) { while ((int)(clk() - t0) < 0) __nanosleep(50); if (one) ffn_prefetch(P, q); t0 += PF1_T; }
      }
    }
  }
}

DEVI void stg_issue(const Params& P, int c, uint32_t d, uint32_t du, uint32_t b) {
  mbar_expect_tx(b, 16384);
  if (c < 8) { tma_2d_h(d, &P.mWg, FID * 32, c * 128, b, POL_G); tma_2d_h(d + du, &P.mWu, FID * 32, c * 128, b, POL_U); }
  else if (c < 12) tma_3d_h(d, &P.mWd, 0, FID * 32 + (c - 8) * 8, 0, b, POL_D);
  else tma_2d_h(d, &P.mWp, (c - 12) * 1024 + (BID >> 2) * 32, (BID & 3) * 256, b, POL_EF);
}
DEVI void pace() { const uint32_t t0 = clk(); while (clk() - t0 < PACE_T); }
DEVI void stager(const Params& P, uint32_t sb) {
  {
    const int b = blockIdx.x;
    uint32_t t0 = clk();
    #pragma unroll 1
    for (int q = 0; q < PQ_N; q++) { bulk_prefetch(P.wqkv + (q * 128 + b) * 3072, 6144); while (clk() - t0 < PQ_T) __nanosleep(50); t0 += PQ_T; }
    bulk_prefetch(P.wo + b * 8192, 16384);
    #pragma unroll 1
    for (int q = 0; q < PF0_N; q++) {
      while (clk() - t0 < PF0_T) __nanosleep(50);
      t0 += PF0_T;
      ffn_prefetch(P, q);
    }
  }
  const int bid = BID, bi = bid >> 4, rh = bid & 1, bc = (bid & 15) >> 1;
  #pragma unroll 1
  for (int L = 0; L < 2; L++) {
    const int nch = L ? (FID < 112 ? 8 : 0) : 15;
    mbar_wait(BAR(B_PAR), L); mbar_wait(BAR(B_KVFULL + W0_BAR), L);
    #pragma unroll 1
    for (int n = 0, q = 0; n < 16; q = w_next(n, q), n++) {
      if (n >= 2) mbar_wait(n < 6 ? BAR(B_HAFREE + (n >> 2)) : BAR(B_EMPTYW + q), n < 6 ? L : w_par(n - 6, q, L));
      if (n == THR_N) mbar_wait(BAR(B_OFREE), L);
      mbar_expect_tx(BAR(B_FULLW + q), 16384);
      tma_5d(sb + w_off(q) + 16384, &P.mWo, 0, 0, n >> 3, 2 * (wo_order(bc, n) & 7), 2 * bc, BAR(B_FULLW + q), L ? POL_EF : POL_NORMAL);
      if (n == 13) {
        mbar_expect_tx(BAR(B_RES), 32768);
        #pragma unroll 1
        for (int e = 0; e < 2; e++) {
          mbar_wait(BAR(B_EMPTYW + 2 + e), 1);
          if (L) bulk_g2s_h(sb + e * 32768 + rh * 16384, P.g->x[bi][2 * bc + e] + rh * 1024, 16384, BAR(B_RES));
          else tma_2d_h(sb + e * 32768 + rh * 16384, &P.mXh, bc * 128 + e * 64, bi * 256 + rh * 128, BAR(B_RES), POL_EF);
        }
      }
    }
    if (L && nch) {
      const bf16* src = WDSRC2;
      mbar_expect_tx(BAR(B_FULLW + 2), 32768); mbar_expect_tx(BAR(B_FULLW + 2), 24576);
      #pragma unroll 1
      for (int e = 0; e < 3; e++) { bulk_g2s_h(sb + e * 32768 + (e < 2 ? (rh ^ 1) * 16384 : 0), src + e * 8192, e < 2 ? 16384 : 24576, BAR(B_FULLW + 2)); pace(); }
    }
    if (L == 0) { mbar_arrive_peer(BAR(B_PFREE)); mbar_wait(BAR(B_EMPTYW), 0); mbar_wait(BAR(B_EMPTYW + 1), 0); }
    #pragma unroll 1
    for (int c = FID < 112 ? 0 : 12, slot = 0; c < nch; c++, slot = slot == 2 ? 0 : slot + 1) {
      const int q = (c >> 1) + (c & 4) / 2;
      mbar_wait(L ? BAR(B_EMPTYW + q) : BAR(B_STGE + slot), L | ((0x71c7 >> c) & 1));
      #define CC c
      stg_issue(P, CC, L ? sb + w_off(q) + (c & 1) * 8192 : sb + STG + slot * 16384, 8192 << L, L ? BAR(B_FULLW + q) : BAR(B_STG + slot));
      if (L) pace();
    }
  }
}
DEVI void sum8(uint4 v, float& s1, float& s2) {
  float e[8] = {bf_lo(v.x), bf_hi(v.x), bf_lo(v.y), bf_hi(v.y), bf_lo(v.z), bf_hi(v.z), bf_lo(v.w), bf_hi(v.w)};
  #pragma unroll
  for (int q = 0; q < 8; q++) { s1 += e[q]; s2 = fmaf(e[q], e[q], s2); }
}
DEVI uint4 norm8(uint4 x, float m, float rs) {
  #define HN(v) pack_bf16((bf_lo(v) - m) * rs, (bf_hi(v) - m) * rs)
  return make_uint4(HN(x.x), HN(x.y), HN(x.z), HN(x.w));
  #undef HN
}
DEVI void put_f32(uint4 b, uint32_t d, uint32_t d2) {
  sts128(d, make_uint4(b.x << 16, b.x & 0xffff0000u, b.y << 16, b.y & 0xffff0000u));
  sts128(d + d2, make_uint4(b.z << 16, b.z & 0xffff0000u, b.w << 16, b.w & 0xffff0000u));
}
DEVI void put_bf16(uint4 b, uint32_t d) {
  sts64f(d, __uint_as_float(b.x), __uint_as_float(b.y)); sts64f(d + 1024, __uint_as_float(b.z), __uint_as_float(b.w));
  fence_async_smem();
}
DEVI uint4 best4(uint32_t p) {
  uint4 a = lds128(p), b = lds128(p + 16), c = lds128(p + 32), d = lds128(p + 48);
  if (b.x > a.x) a = b;
  if (d.x > c.x) c = d;
  return c.x > a.x ? c : a;
}
#define FL(x) __uint_as_float(x)
#define UI(x) __float_as_uint(x)
DEVI void qkv_params(const Params& P, uint32_t sb, int row, uint32_t tag, bool second) {
  uint4 v0, v1; poll_ll2(&P.g->statF[row], &P.g->statF[row + 128], 0xffffffffu, tag, v0, v1);
  #pragma unroll 1
  for (int q = 0; q < 2; q++) {
    float var = FL(v0.y), c = rsqrtf(var + LN_EPS);
    if (second) { c += 1.f; c *= rsqrtf(fmaf(var * c, c, LN_EPS)); }
    const float mh = bf_round(FL(v0.x));
    sts64f(sb + PAR + q * 1024 + (row & 127) * 8, c, FL(pack_bf16(mh, FL(v0.x) - mh)));
    v0 = v1;
  }
  warp_signal(BAR(B_ROW));
}
DEVI void aux(const Params& P, uint32_t sb) {
  int tid = fresh_tid();
  #define lane (tid & 31)
  #define wq (tid >> 5)
  uint32_t ids = P.map[blockIdx.x], tag;
  #define bid ((int)(ids & 255))
  #define fid ((int)(ids >> 8))
  #define bi (bid >> 4)
  #define bp (bid & 15)
  #define bc (bp >> 1)
  #define FRESH() do { tid = fresh_tid(); uint4 z_ = ldsv128(sb + INFO2 + 16); ids = z_.y; tag = z_.z + L; idx = z_.w; } while (0)
  {
    const uint32_t epoch = ld_rlx(&P.g->epoch);
    if (tid == 0) {
      mbar_expect_tx(BAR(B_STG), 49152);
      tma_3d(sb + STG, &P.mWq, bp * 64, bi * 128, 0, BAR(B_STG));
      tma_3d(sb + STG + 24576, &P.mWq, bp * 64, bi * 128 + 64, 0, BAR(B_STG));
    }
    __syncwarp();
    sts64f(sb + ONES + tid * 8, FL(0x3F803F80u), FL(0x3F803F80u));
    float s1 = 0.f, s2 = 0.f;
    { uint4 v = __ldg((const uint4*)P.wr + tid);
      if ((tid >> 4) == bc) put_f32(v, sb + WR + (tid & 15) * 32, 16);
      sum8(v, s1, s2);
      #pragma unroll 1
      for (int o = 16; o; o >>= 1) s1 += __shfl_xor_sync(0xffffffffu, s1, o);
      sts32f(sb + INFO2 + wq * 4, s1); }
    const uint4* src = (const uint4*)(P.x0 + (size_t)bid * 16384) + (tid >> 3) * 128 + (tid & 7);
    s1 = 0.f; s2 = 0.f;
    #pragma unroll 1
    for (int it = 0; it < 16; it += 4) {
      uint4 v0 = __ldg(src + it * 8), v1 = __ldg(src + it * 8 + 8), v2 = __ldg(src + it * 8 + 16), v3 = __ldg(src + it * 8 + 24);
      #pragma unroll 1
      for (int q = 0; q < 4; q++) { sum8(v0, s1, s2); v0 = v1; v1 = v2; v2 = v3; }
    }
    #pragma unroll 1
    for (int o = 1; o < 8; o <<= 1) { s1 += __shfl_xor_sync(0xffffffffu, s1, o); s2 += __shfl_xor_sync(0xffffffffu, s2, o); }
    tag = ((epoch % 16383u) + 1u) << 2;
    if (tid == 0) { sts128(sb + INFO, make_uint4(0x40000000u, 0u, tag, ((epoch % 127u) + 1u) << 1)); sts128(sb + INFO2 + 16, make_uint4(epoch, ids, tag, 0x40000000u)); }
    float m = s1 * (1.f / 1024.f);
    if ((tid & 7) == 0) st_ll(&P.g->statF[bid * 16 + (tid >> 3)], UI(m), UI(fmaxf(fmaf(-m, m, s2 * (1.f / 1024.f)), 0.f)), 0u, tag);
    bar_sync(2, 128);
    mbar_wait_b(BAR(B_STG), 0);
    if (tid < 96) {
      s1 = 0.f; s2 = 0.f;
      #pragma unroll 4
      for (int r = 0; r < 128; r++) {
        uint32_t v = lds32(sb + STG + (r >> 6) * 24576 + wq * 8192 + (r & 63) * 128 + ((lane * 4) ^ ((r & 7) << 4)));
        s1 += bf_lo(v); s2 += bf_hi(v);
      }
      st_ll(&P.g->csP[bp][bi][tid], UI(s1), UI(s2), 0u, tag);
      s1 = 0.f; s2 = 0.f;
      #pragma unroll 1
      for (int q = 0; q < 8; q += 2) {
        uint4 a, b; poll_ll2(&P.g->csP[bp][q][tid], &P.g->csP[bp][q + 1][tid], 0xffffffffu, tag, a, b);
        s1 += FL(a.x) + FL(b.x); s2 += FL(a.y) + FL(b.y);
      }
      const uint32_t hi = pack_bf16(-s1, -s2);
      sts32(sb + CS + (tid >> 2) * 32 + (tid & 3) * 4, hi);
      sts32(sb + CS + (tid >> 2) * 32 + (tid & 3) * 4 + 16, pack_bf16(-s1 - bf_lo(hi), -s2 - bf_hi(hi)));
    }
    fence_async_smem();
    qkv_params(P, sb, bi * 256 + tid, tag, false);
  }
  int idx;
  #pragma unroll 1
  for (int L = 0; L < 2; L++) {
    FRESH();
    {
      if ((unsigned)(bi - (idx >> 8)) < 2u) {
        const uint4* src = &P.g->patch[bp * 8 + (tid >> 6) * 4][tid & 63];
        uint4 v0, v1, v2, v3; int it = 0;
        do { v0 = ld_ll(src); v1 = ld_ll(src + 64); v2 = ld_ll(src + 128); v3 = ld_ll(src + 192); if (++it > SPIN_MAX) __trap(); }
        while (!__all_sync(0xffffffffu, v0.w == tag && v1.w == tag && v2.w == tag && v3.w == tag));
        float q = (FL(v0.x) + FL(v1.x)) + (FL(v2.x) + FL(v3.x)), k = (FL(v0.y) + FL(v1.y)) + (FL(v2.y) + FL(v3.y)), v = (FL(v0.z) + FL(v1.z)) + (FL(v2.z) + FL(v3.z));
        q += __shfl_xor_sync(0xffffffffu, q, 1); k += __shfl_xor_sync(0xffffffffu, k, 1); v += __shfl_xor_sync(0xffffffffu, v, 1);
        bar_sync(2, 128);
        const uint32_t d = sb + PATCH + (tid & ~1), kv = pack_bf16(k, v);
        sts16(d, pack_bf16(q * QSCALE, 0.f)); sts16(d + 128, kv); sts16(d + 256, kv >> 16);
      }
      sts32(sb + INFO, idx);
      bar_sync(2, 128);
    }
    const uint4 fix = lds128(sb + PATCH + 128 + (lane & 4) * 32 + (wq >> 1) * 64 + (lane & 3) * 16);
    warp_signal(BAR(B_PAR));
    PROFX(tid == 0, L ? 23 : 17);
    mbar_wait_b(BAR(B_KVFULL + wq), L);
    if ((idx >> 7) == bi * 2 - 1 - (wq & 1)) {
      if (lane < 8) sts128(sb + ((wq >> 1) ? KVB : KVA) + ((idx >> 6) & 3) * 8192 + (lane >> 2) * 4096 + (idx & 63) * 64 + (((lane ^ (idx >> 1)) & 3) << 4), fix);
      fence_async_smem();
    }
    bar_arrive(4 + wq, 160); bar_arrive(8 + wq, 160);
    FRESH();
    mbar_wait_b(BAR(B_OFREE), L);
    #define blk (bi * 2 + (bid & 1))
    if (tid < 33) st_ll(tid < 32 ? &P.g->row[blk][bc * 32 + tid] : &P.g->best[bc][blk], 0u, 0u, 0u, 0u);
    if (!L) {
        if (fid < 112) { st_ll(&P.g->yP[tid & ~1][fid][tid & 1], 0u, 0u, 0u, 0u); st_ll(&P.g->yP[tid | 1][fid][tid & 1], 0u, 0u, 0u, 0u); }
        if (tid < 80) st_ll(tid < 64 ? &P.g->patch[bid][tid] : &P.g->x2[(tid >> 1) & 7][2 * bid + (tid & 1)], 0u, 0u, 0u, 0u);
    }
    mbar_wait_b(BAR(B_XRDY + 1), L); mbar_wait_b(BAR(B_XRDY + 3), L);
    PROFX(tid == 0, 37 + L * 16);
    FRESH();
    {
      float s1 = 0.f, s2 = 0.f, d = 0.f;
      #pragma unroll 1
      for (int q = 0; q < 8; q += 4) {
        const uint4* src = &P.g->statP[q][blk * 128 + tid];
        uint4 v0, v1, v2, v3; int it = 0;
        do { v0 = ld_ll(src); v1 = ld_ll(src + 2048); v2 = ld_ll(src + 4096); v3 = ld_ll(src + 6144); if (++it > SPIN_MAX) __trap(); }
        while (!__all_sync(0xffffffffu, v0.w == tag && v1.w == tag && v2.w == tag && v3.w == tag));
        s1 += (FL(v0.x) + FL(v1.x)) + (FL(v2.x) + FL(v3.x)); s2 += (FL(v0.y) + FL(v1.y)) + (FL(v2.y) + FL(v3.y)); d += (FL(v0.z) + FL(v1.z)) + (FL(v2.z) + FL(v3.z));
      }
      PROFX(tid == 0, 39 + L * 16);
      uint4 a = lds128(sb + INFO2), b, c;
      float m = s1 * (1.f / 1024.f), var = fmaxf(fmaf(-m, m, s2 * (1.f / 1024.f)), 0.f), rs = rsqrtf(var + LN_EPS);
      uint32_t key = UI(fmaf(-m, (FL(a.x) + FL(a.y)) + (FL(a.z) + FL(a.w)), d) * rs);
      key ^= (uint32_t)((int)key >> 31) | 0x80000000u;
      uint32_t win = __ballot_sync(0xffffffffu, key == __reduce_max_sync(0xffffffffu, key));
      if (lane == __ffs(win) - 1) sts128(sb + RED + wq * 16, make_uint4(key, UI(m), UI(rs), (tag << 11) | (uint32_t)(blk * 128 + tid)));
      if (L) sts64f(sb + PAR + tid * 8, 1.f + rs, -m * rs);
      else if ((tid >> 4) == bc) st_ll(&P.g->statF[blk * 128 + tid], UI(m), UI(var), 0u, tag + 1);
      bar_sync(2, 128);
      if (wq == 0) {
        a = best4(sb + RED);
        float2 v = lds64f(sb + (lane >> 4) * 32768 + (a.w & 255) * 128 + (((lane & 15) * 8) ^ ((a.w & 7) << 4)));
        st_ll(&P.g->row[blk][bc * 32 + lane], UI(v.x), UI(v.y), 0u, tag);
        if (lane == 0) st_ll(&P.g->best[bc][blk], a.x, a.y, a.z, a.w);
        __syncwarp();
        if (lane < 2 + 2 * L) mbar_arrive(L ? BAR(B_PAR) : BAR(B_XFREE + lane));
      }
      PROFX(tid == 0, 18 + L * 6);
      FRESH();
      a = poll_ll(&P.g->best[bc][lane & 15], 0xfffff800u, tag << 11);
      win = __ffs(__ballot_sync(0xffffffffu, a.x == __reduce_max_sync(0xffffffffu, a.x))) - 1;
      idx = __shfl_sync(0xffffffffu, a.w, win) & 2047;
      PROFX(tid == 0, 19 + L * 6);
      poll_ll2(&P.g->row[win][tid], &P.g->row[win][tid + 128], 0xffffffffu, tag, c, b);
      c.z = b.x; c.w = b.y;
      a.x = __shfl_sync(0xffffffffu, a.x, win); a.y = __shfl_sync(0xffffffffu, a.y, win); a.z = __shfl_sync(0xffffffffu, a.z, win);
      sts32(sb + INFO2 + 28, idx);
      PROFX(tid == 0, 61 + L);
      b = norm8(c, FL(a.y), FL(a.z));
      if (L) put_bf16(b, sb + HV + tid * 8); else put_f32(b, sb + HV + tid * 16, 2048);
      if ((tid >> 1) == (bid & 63)) {
        sts128(sb + RED + 64 + (tid & 1) * 16, bid < 64 ? make_uint4(c.x, c.y, b.x, b.y) : make_uint4(c.z, c.w, b.z, b.w));
        sts32(sb + RED + 96, a.x);
      }
      bar_sync(2 + L, 128 + L * 256);
      if (L) {
        const int r0 = blk * 128 + (tid >> 4);
        uint32_t src = sb + ((tid >> 3) & 1) * 32768 + (r0 & 255) * 128 + (((tid ^ r0) & 7) << 4);
        uint4* dst = (uint4*)(P.out + (size_t)r0 * 1024 + bc * 128) + (tid & 15);
        #pragma unroll 4
        for (int it = 0; it < 16; it++) { uint4 v = lds128(src + it * 1024); if (idx - r0 != it * 8) dst[it * 1024] = v; }
      }
    }
    #pragma unroll 1
    for (int st = L; st < 2; st++) {
      FRESH();
      float a[8] = {0.f, 0.f, 0.f, 0.f, 0.f, 0.f, 0.f, 0.f};
      if (L == 0 && fid < 112) {
        uint32_t ha = st ? sb + RED + 768 : sb + HV + ((wq & 1) * 64 + (lane >> 2)) * 4;
        uint32_t ph = st ? 0x1cu : 0x171u, bar = st ? BAR(B_STG + 2) : BAR(B_STG);
        uint32_t wa = sb + STG + wq * 4096 + (st ? 32768 + lane * 16 : (lane ^ (lane >> 3)) * 16);
        const uint32_t hx = st ? 256 : 512;
        const bool lead = lane == 0;
        uint4 vc = make_uint4(0u, 0u, 0u, 0u); float hc = 0.f;
        #pragma unroll 1
        do {
          mbar_wait(bar, ph & 1);
          PROFX(lead && threadIdx.x == 256 && st == 0 && (ph > 255 || ph < 4), 40 - 23 + __clz(ph));
          #pragma unroll
          for (int n = 0; n < 8; n++) { const uint4 v = lds128(wa + n * 512); const float h = lds32f(ha + n * 32); fma8(a, vc, hc); vc = v; hc = h; }
          __syncwarp();
          if (lead) mbar_arrive(bar - 8 * (B_STG - B_STGE));
          const bool wrap = bar == BAR(B_STG + 2);
          bar += wrap ? -16 : 8; wa += wrap ? -32768 : 16384; ha += hx;
          ph >>= 1;
        } while (ph != 1);
        fma8(a, vc, hc);
      }
      FRESH();
      if (st == 1) {
        const uint32_t t8 = lds32(sb + INFO + 12) + L;
        if (L == 0 && fid < 112) {
          const bool odd = lane & 1;
          #pragma unroll
          for (int e = 0; e < 4; e++) { float z = __shfl_xor_sync(0xffffffffu, odd ? a[e] : a[4 + e], 1); if (odd) a[e] = z; else a[4 + e] = z; }
          uint4* dst = &P.g->yP[tid & ~1][fid][tid & 1];
          st_ll(dst, UI(a[0]), UI(a[1]), UI(a[2]), (UI(a[3]) & ~255u) | t8);
          st_ll(dst + 224, UI(a[4]), UI(a[5]), UI(a[6]), (UI(a[7]) & ~255u) | t8);
          PROFX(tid == 0, 21);
        }
        if (!L) qkv_params(P, sb, bi * 256 + tid, tag + 1, true);
        if (tid == 0) { uint32_t k = lds32(sb + RED + 96); sts32f(sb + RED + 100, bf_round(__fdividef(1.f, 1.f + __expf(-bf_round(FL(k ^ (~(uint32_t)((int)k >> 31) | 0x80000000u))))))); }
        uint4 v0, v1;
        poll_ll2(&P.g->yP[bid][0][min(tid, 111)], &P.g->yP[bid][0][min(tid, 111) + 112], 255u, t8, v0, v1);
        const float lo = (tid < 112 && !(tid & 1)) ? 1.f : 0.f, hi = (tid < 112 && (tid & 1)) ? 1.f : 0.f;
        const float y0 = FL(v0.x) + FL(v1.x), y1 = FL(v0.y) + FL(v1.y), y2 = FL(v0.z) + FL(v1.z), y3 = FL((v0.w & ~255u) | 128u) + FL((v1.w & ~255u) | 128u);
        a[0] = y0 * lo; a[1] = y1 * lo; a[2] = y2 * lo; a[3] = y3 * lo; a[4] = y0 * hi; a[5] = y1 * hi; a[6] = y2 * hi; a[7] = y3 * hi;
      }
      sts32f(sb + RED + 256 + wq * 128 + ((lane & 3) * 8 + (lane >> 2)) * 4, fold8(a));
      bar_sync(2, 128);
      const uint32_t d = sb + RED + 256 + lane * 4;
      float z0 = lds32f(d) + lds32f(d + 128), z1 = lds32f(d + 256) + lds32f(d + 384);
      if (st == 0) {
        sts32f(sb + RED + 768 + lane * 32 + wq * 4, swiglu(z0, z1));
        bar_sync(2, 128); PROFX(tid == 0, 20); continue; }
      z0 += z1;
      z0 += __shfl_xor_sync(0xffffffffu, z0, 8); z0 += __shfl_xor_sync(0xffffffffu, z0, 16);
      uint32_t xw = lds32(sb + RED + 64 + (lane & 4) * 4 + (lane & 2) * 2), hw = lds32(sb + RED + 72 + (lane & 4) * 4 + (lane & 2) * 2);
      z0 = bf_round(((lane & 1) ? bf_hi(hw) : bf_lo(hw)) + bf_round(bf_round(z0) * lds32f(sb + RED + 100))) + ((lane & 1) ? bf_hi(xw) : bf_lo(xw));
      uint32_t v = pack_bf16(z0, __shfl_down_sync(0xffffffffu, z0, 1)), v2 = __shfl_down_sync(0xffffffffu, v, 2);
      if (L) { if (tid == 0 || tid == 4) *(uint2*)(P.out + (size_t)idx * 1024 + bid * 8 + tid) = make_uint2(v, v2); PROFW(tid == 0, 28); }
      else if ((tid & 3) == 0 && tid < 64) st_ll(&P.g->x2[tid >> 3][2 * bid + ((tid >> 2) & 1)], v, v2, 0u, tag + 1);
    }
    if (L == 0) {
      PROFX(tid == 0, 22);
      FRESH();
      uint4 x, y; poll_ll2(&P.g->x2[bi][tid], &P.g->x2[bi][tid + 128], 0xffffffffu, tag + 1, x, y);
      x.z = y.x; x.w = y.y;
      if (wq == (bc & 3)) sts64f(sb + X2SEG + lane * 8, FL(bc < 4 ? x.x : x.z), FL(bc < 4 ? x.y : x.w));
      float s1 = 0.f, s2 = 0.f;
      sum8(x, s1, s2);
      #pragma unroll
      for (int o = 16; o; o >>= 1) { s1 += __shfl_xor_sync(0xffffffffu, s1, o); s2 += __shfl_xor_sync(0xffffffffu, s2, o); }
      sts64f(sb + RED + wq * 8, s1, s2);
      bar_sync(2, 128);
      y = lds128(sb + RED); uint4 y2 = lds128(sb + RED + 16);
      float m = ((FL(y.x) + FL(y.z)) + (FL(y2.x) + FL(y2.z))) * (1.f / 1024.f);
      put_bf16(norm8(x, m, rsqrtf(fmaxf(fmaf(-m, m, ((FL(y.y) + FL(y.w)) + (FL(y2.y) + FL(y2.w))) * (1.f / 1024.f)), 0.f) + LN_EPS)), sb + HV + tid * 8);
      mbar_wait(BAR(B_STG), 1); mbar_wait(BAR(B_STG + 1), 0); mbar_wait(BAR(B_STG + 2), 0);
      bar_sync(2, 128);
      PROFX(tid == 0, 30);
      float d0[4] = {0.f, 0.f, 0.f, 0.f}, d1[4] = {0.f, 0.f, 0.f, 0.f}, d2[4] = {0.f, 0.f, 0.f, 0.f};
      const uint32_t bd = (64 + (HV >> 4) + uni(bid & 3) * 32) | 0x10000u;
      #pragma unroll 1
      for (int ks = 0; ks < 8; ks++) {
        const uint32_t ad = (64 + (STG >> 4) + ks * 128) | (64u << 16);
        wg_fence();
        wgmma_ss_n8<0, 1>(d0, mkd<HI64>(ad), mkd<8>(bd + ks * 4), 1);
        wgmma_ss_n8<0, 1>(d1, mkd<HI64>(ad + 1024), mkd<8>(bd + ks * 4), 1);
        wgmma_ss_n8<0, 1>(d2, mkd<HI64>(ad + 2048), mkd<8>(bd + ks * 4), 1);
        wg_commit();
      }
      wg_wait<0>(); keep(d0); keep(d1); keep(d2);
      FRESH();
      if ((lane & 3) == (wq >> 1)) {
        uint4* dst = &P.g->patch[bid][(wq & 1) * 32 + (lane >> 2) * 2 + (wq >> 1)];
        st_ll(dst, UI(d0[0]), UI(d1[0]), UI(d2[0]), tag + 1); st_ll(dst + 16, UI(d0[2]), UI(d1[2]), UI(d2[2]), tag + 1);
      }
      PROFX(tid == 0, 31);
    }
  }
  if (bid == 0 && tid == 0) P.g->epoch = lds32(sb + INFO2 + 16) + 1;
  #undef blk
  #undef bid
  #undef fid
  #undef bi
  #undef bp
  #undef bc
  #undef FRESH
  #undef lane
  #undef wq
}

__global__ void __cluster_dims__(2, 1, 1) __launch_bounds__(512, 1) fused_kernel(const __grid_constant__ Params P) {
  extern __shared__ __align__(1024) uint8_t smem_raw[];
  const uint32_t sb = smem_u32(smem_raw);
  PROFT(threadIdx.x == 0, 0);
  if (threadIdx.x == 0) {
    for (int s = 0; s < 3; s++) mbar_init(BAR(B_FULLQ + s), 1);
    asm volatile("fence.mbarrier_init.release.cluster;" ::: "memory");
    #pragma unroll 1
    for (int s = 0; s < 3; s++) {
      mbar_expect_tx(BAR(B_FULLQ + s), 57344);
      tma_2d(sb + qa_off(s), &P.mX, s * 64, (BID >> 4) * 256, BAR(B_FULLQ + s));
      tma_3d(sb + qb_off(s), &P.mWq, (BID & 15) * 64, s * 64, 0, BAR(B_FULLQ + s));
    }
    if ((sb & 0x3FFFFu) != 1024) __trap();
  } else if (threadIdx.x >= 32 + B_EMPTYQ && threadIdx.x <= 32 + B_COUNT) {
    const int b = threadIdx.x == 32 + B_COUNT ? B_ROW : threadIdx.x - 32;
    const uint32_t cnt = b < B_XFREE ? (b == B_OFREE ? 1 : 2) : (b < B_KVRDY ? 3 : (b < B_KVFULL || b == B_ROW || b == B_PAR ? 4 : (b == B_PFREE ? 2 : 1)));
    mbar_init(BAR(b), cnt);
    asm volatile("fence.mbarrier_init.release.cluster;" ::: "memory");
  }
  __syncthreads();
  asm volatile("barrier.cluster.arrive.relaxed.aligned;" ::: "memory");
  const int wg = __shfl_sync(0xffffffffu, threadIdx.x >> 7, 0);
  if (wg < 2) { reg_inc<224>(); consumer(P, sb, wg); }
  else if (wg == 2) { reg_dec<40>(); aux(P, sb); }
  else {
    reg_dec<24>();
    asm volatile("barrier.cluster.wait.aligned;" ::: "memory");
    const int w = __shfl_sync(0xffffffffu, (threadIdx.x >> 5) & 3, 0);
    if (w == 0) loader(P, sb);
    else if (w < 3) storer(P, sb, w - 1);
    else if ((threadIdx.x & 31) == 0) stager(P, sb);
  }
}

typedef CUresult (*EncFn)(CUtensorMap*, CUtensorMapDataType, cuuint32_t, void*, const cuuint64_t*, const cuuint64_t*, const cuuint32_t*, const cuuint32_t*,
                          CUtensorMapInterleave, CUtensorMapSwizzle, CUtensorMapL2promotion, CUtensorMapFloatOOBfill);
static void mk_map(EncFn enc, CUtensorMap* m, const void* ptr, int rank, const cuuint64_t* dims, const cuuint64_t* strides, const cuuint32_t* box,
                   CUtensorMapSwizzle sw, CUtensorMapL2promotion pr) {
  cuuint32_t es[5] = {1, 1, 1, 1, 1};
  enc(m, CU_TENSOR_MAP_DATA_TYPE_BFLOAT16, rank, (void*)ptr, dims, strides, box, es, CU_TENSOR_MAP_INTERLEAVE_NONE, sw, pr, CU_TENSOR_MAP_FLOAT_OOB_FILL_NONE);
}
extern "C" void kernel_launch(void* const* d_in, const int* in_sizes, int n_in, void* d_out, int out_size) {
  (void)in_sizes; (void)n_in; (void)out_size;
  void* fn = nullptr; cudaDriverEntryPointQueryResult q;
  cudaGetDriverEntryPoint("cuTensorMapEncodeTiled", &fn, cudaEnableDefault, &q);
  EncFn enc = (EncFn)fn;
  cudaFuncSetAttribute(fused_kernel, cudaFuncAttributeMaxDynamicSharedMemorySize, SMEM_BYTES);
  Params P;
  const CUtensorMapSwizzle S128 = CU_TENSOR_MAP_SWIZZLE_128B, S64 = CU_TENSOR_MAP_SWIZZLE_64B, S0 = CU_TENSOR_MAP_SWIZZLE_NONE;
  const CUtensorMapL2promotion L256 = CU_TENSOR_MAP_L2_PROMOTION_L2_256B, L128 = CU_TENSOR_MAP_L2_PROMOTION_L2_128B;
  { cuuint64_t d[2] = {1024, 2048}, s[1] = {2048}; cuuint32_t b[2] = {64, 256}, bh[2] = {64, 128};
    mk_map(enc, &P.mX, d_in[0], 2, d, s, b, S128, L256); mk_map(enc, &P.mXh, d_in[0], 2, d, s, bh, S128, L256); }
  { cuuint64_t d[3] = {1024, 1024, 3}, s[2] = {6144, 2048}; cuuint32_t b[3] = {64, 64, 3}; mk_map(enc, &P.mWq, d_in[1], 3, d, s, b, S128, L256); }
  { cuuint64_t d[5] = {64, 32, 2, 16, 16}, s[4] = {2048, 65536, 131072, 128}; cuuint32_t b[5] = {64, 32, 1, 2, 2}; mk_map(enc, &P.mWo, d_in[2], 5, d, s, b, S128, L256); }
  { cuuint64_t d[2] = {3584, 1024}, s[1] = {7168}; cuuint32_t b[2] = {32, 128};
    mk_map(enc, &P.mWg, d_in[5], 2, d, s, b, S64, L128); mk_map(enc, &P.mWu, d_in[6], 2, d, s, b, S64, L128); }
  { cuuint64_t d[2] = {3072, 1024}, s[1] = {6144}; cuuint32_t b[2] = {32, 256}; mk_map(enc, &P.mWp, d_in[1], 2, d, s, b, S64, L128); }
  { cuuint64_t d[3] = {256, 3584, 4}, s[2] = {2048, 512}; cuuint32_t b[3] = {256, 8, 4}; mk_map(enc, &P.mWd, d_in[7], 3, d, s, b, S0, L128); }
  P.x0 = (const bf16*)d_in[0]; P.wqkv = (const bf16*)d_in[1]; P.wo = (const bf16*)d_in[2]; P.wr = (const bf16*)d_in[4]; P.wg = (const bf16*)d_in[5]; P.wu = (const bf16*)d_in[6]; P.wd = (const bf16*)d_in[7];
  P.out = (bf16*)d_out;
  cudaGetSymbolAddress((void**)&P.g, g_scr);
  for (int b = 0; b < 128; b++) {
    int j = b >> 1, quad = j < 4 ? 0 : (j < 36 ? 1 + (j - 4) % 8 : 9 + (j - 36) % 7), pos = j < 4 ? j : (j < 36 ? (j - 4) / 8 : (j - 36) / 7);
    int bid = ((quad >> 2) * 2 + (pos >> 1)) * 16 + ((quad & 3) * 2 + (pos & 1)) * 2 + (b & 1);
    int e = pos * 2 + (b & 1), fid = e < 7 ? quad * 7 + e : 112 + quad;
    P.map[b] = bid | fid << 8;
  }
  fused_kernel<<<128, 512, SMEM_BYTES>>>(P);
}
```

```cpp
#include <cuda_runtime.h>
#include <cuda_bf16.h>
#include <cuda.h>
#include <stdint.h>
#include <stddef.h>
typedef __nv_bfloat16 bf16;

template<int TB, int TA = 0> __device__ __forceinline__ void wgmma_ss_n192(float (&d)[96], uint64_t da, uint64_t db, int scale_d) {
  asm volatile("{\n.reg .pred p;\nsetp.ne.b32 p, %98, 0;\n"
    "wgmma.mma_async.sync.aligned.m64n192k16.f32.bf16.bf16 {%0, %1, %2, %3, %4, %5, %6, %7, %8, %9, %10, %11, %12, %13, %14, %15, %16, %17, %18, %19, %20, %21, %22, %23, %24, %25, %26, %27, %28, %29, %30, %31, %32, %33, %34, %35, %36, %37, %38, %39, %40, %41, %42, %43, %44, %45, %46, %47, %48, %49, %50, %51, %52, %53, %54, %55, %56, %57, %58, %59, %60, %61, %62, %63, %64, %65, %66, %67, %68, %69, %70, %71, %72, %73, %74, %75, %76, %77, %78, %79, %80, %81, %82, %83, %84, %85, %86, %87, %88, %89, %90, %91, %92, %93, %94, %95}, %96, %97, p, 1, 1, %100, %99;\n}\n"
    : "+f"(d[0]), "+f"(d[1]), "+f"(d[2]), "+f"(d[3]), "+f"(d[4]), "+f"(d[5]), "+f"(d[6]), "+f"(d[7]), "+f"(d[8]), "+f"(d[9]), "+f"(d[10]), "+f"(d[11]), "+f"(d[12]), "+f"(d[13]), "+f"(d[14]), "+f"(d[15]), "+f"(d[16]), "+f"(d[17]), "+f"(d[18]), "+f"(d[19]), "+f"(d[20]), "+f"(d[21]), "+f"(d[22]), "+f"(d[23]), "+f"(d[24]), "+f"(d[25]), "+f"(d[26]), "+f"(d[27]), "+f"(d[28]), "+f"(d[29]), "+f"(d[30]), "+f"(d[31]), "+f"(d[32]), "+f"(d[33]), "+f"(d[34]), "+f"(d[35]), "+f"(d[36]), "+f"(d[37]), "+f"(d[38]), "+f"(d[39]), "+f"(d[40]), "+f"(d[41]), "+f"(d[42]), "+f"(d[43]), "+f"(d[44]), "+f"(d[45]), "+f"(d[46]), "+f"(d[47]), "+f"(d[48]), "+f"(d[49]), "+f"(d[50]), "+f"(d[51]), "+f"(d[52]), "+f"(d[53]), "+f"(d[54]), "+f"(d[55]), "+f"(d[56]), "+f"(d[57]), "+f"(d[58]), "+f"(d[59]), "+f"(d[60]), "+f"(d[61]), "+f"(d[62]), "+f"(d[63]), "+f"(d[64]), "+f"(d[65]), "+f"(d[66]), "+f"(d[67]), "+f"(d[68]), "+f"(d[69]), "+f"(d[70]), "+f"(d[71]), "+f"(d[72]), "+f"(d[73]), "+f"(d[74]), "+f"(d[75]), "+f"(d[76]), "+f"(d[77]), "+f"(d[78]), "+f"(d[79]), "+f"(d[80]), "+f"(d[81]), "+f"(d[82]), "+f"(d[83]), "+f"(d[84]), "+f"(d[85]), "+f"(d[86]), "+f"(d[87]), "+f"(d[88]), "+f"(d[89]), "+f"(d[90]), "+f"(d[91]), "+f"(d[92]), "+f"(d[93]), "+f"(d[94]), "+f"(d[95])
    : "l"(da), "l"(db), "r"(scale_d), "n"(TB), "n"(TA));
}

template<int TB> __device__ __forceinline__ void wgmma_rs_n192(float (&d)[96], uint32_t a0, uint32_t a1, uint32_t a2, uint32_t a3, uint64_t db, int scale_d) {
  asm volatile("{\n.reg .pred p;\nsetp.ne.b32 p, %101, 0;\n"
    "wgmma.mma_async.sync.aligned.m64n192k16.f32.bf16.bf16 {%0, %1, %2, %3, %4, %5, %6, %7, %8, %9, %10, %11, %12, %13, %14, %15, %16, %17, %18, %19, %20, %21, %22, %23, %24, %25, %26, %27, %28, %29, %30, %31, %32, %33, %34, %35, %36, %37, %38, %39, %40, %41, %42, %43, %44, %45, %46, %47, %48, %49, %50, %51, %52, %53, %54, %55, %56, %57, %58, %59, %60, %61, %62, %63, %64, %65, %66, %67, %68, %69, %70, %71, %72, %73, %74, %75, %76, %77, %78, %79, %80, %81, %82, %83, %84, %85, %86, %87, %88, %89, %90, %91, %92, %93, %94, %95}, {%96, %97, %98, %99}, %100, p, 1, 1, %102;\n}\n"
    : "+f"(d[0]), "+f"(d[1]), "+f"(d[2]), "+f"(d[3]), "+f"(d[4]), "+f"(d[5]), "+f"(d[6]), "+f"(d[7]), "+f"(d[8]), "+f"(d[9]), "+f"(d[10]), "+f"(d[11]), "+f"(d[12]), "+f"(d[13]), "+f"(d[14]), "+f"(d[15]), "+f"(d[16]), "+f"(d[17]), "+f"(d[18]), "+f"(d[19]), "+f"(d[20]), "+f"(d[21]), "+f"(d[22]), "+f"(d[23]), "+f"(d[24]), "+f"(d[25]), "+f"(d[26]), "+f"(d[27]), "+f"(d[28]), "+f"(d[29]), "+f"(d[30]), "+f"(d[31]), "+f"(d[32]), "+f"(d[33]), "+f"(d[34]), "+f"(d[35]), "+f"(d[36]), "+f"(d[37]), "+f"(d[38]), "+f"(d[39]), "+f"(d[40]), "+f"(d[41]), "+f"(d[42]), "+f"(d[43]), "+f"(d[44]), "+f"(d[45]), "+f"(d[46]), "+f"(d[47]), "+f"(d[48]), "+f"(d[49]), "+f"(d[50]), "+f"(d[51]), "+f"(d[52]), "+f"(d[53]), "+f"(d[54]), "+f"(d[55]), "+f"(d[56]), "+f"(d[57]), "+f"(d[58]), "+f"(d[59]), "+f"(d[60]), "+f"(d[61]), "+f"(d[62]), "+f"(d[63]), "+f"(d[64]), "+f"(d[65]), "+f"(d[66]), "+f"(d[67]), "+f"(d[68]), "+f"(d[69]), "+f"(d[70]), "+f"(d[71]), "+f"(d[72]), "+f"(d[73]), "+f"(d[74]), "+f"(d[75]), "+f"(d[76]), "+f"(d[77]), "+f"(d[78]), "+f"(d[79]), "+f"(d[80]), "+f"(d[81]), "+f"(d[82]), "+f"(d[83]), "+f"(d[84]), "+f"(d[85]), "+f"(d[86]), "+f"(d[87]), "+f"(d[88]), "+f"(d[89]), "+f"(d[90]), "+f"(d[91]), "+f"(d[92]), "+f"(d[93]), "+f"(d[94]), "+f"(d[95])
    : "r"(a0), "r"(a1), "r"(a2), "r"(a3), "l"(db), "r"(scale_d), "n"(TB));
}

template<int TB, int TA = 0> __device__ __forceinline__ void wgmma_ss_n128(float (&d)[64], uint64_t da, uint64_t db, int scale_d) {
  asm volatile("{\n.reg .pred p;\nsetp.ne.b32 p, %66, 0;\n"
    "wgmma.mma_async.sync.aligned.m64n128k16.f32.bf16.bf16 {%0, %1, %2, %3, %4, %5, %6, %7, %8, %9, %10, %11, %12, %13, %14, %15, %16, %17, %18, %19, %20, %21, %22, %23, %24, %25, %26, %27, %28, %29, %30, %31, %32, %33, %34, %35, %36, %37, %38, %39, %40, %41, %42, %43, %44, %45, %46, %47, %48, %49, %50, %51, %52, %53, %54, %55, %56, %57, %58, %59, %60, %61, %62, %63}, %64, %65, p, 1, 1, %68, %67;\n}\n"
    : "+f"(d[0]), "+f"(d[1]), "+f"(d[2]), "+f"(d[3]), "+f"(d[4]), "+f"(d[5]), "+f"(d[6]), "+f"(d[7]), "+f"(d[8]), "+f"(d[9]), "+f"(d[10]), "+f"(d[11]), "+f"(d[12]), "+f"(d[13]), "+f"(d[14]), "+f"(d[15]), "+f"(d[16]), "+f"(d[17]), "+f"(d[18]), "+f"(d[19]), "+f"(d[20]), "+f"(d[21]), "+f"(d[22]), "+f"(d[23]), "+f"(d[24]), "+f"(d[25]), "+f"(d[26]), "+f"(d[27]), "+f"(d[28]), "+f"(d[29]), "+f"(d[30]), "+f"(d[31]), "+f"(d[32]), "+f"(d[33]), "+f"(d[34]), "+f"(d[35]), "+f"(d[36]), "+f"(d[37]), "+f"(d[38]), "+f"(d[39]), "+f"(d[40]), "+f"(d[41]), "+f"(d[42]), "+f"(d[43]), "+f"(d[44]), "+f"(d[45]), "+f"(d[46]), "+f"(d[47]), "+f"(d[48]), "+f"(d[49]), "+f"(d[50]), "+f"(d[51]), "+f"(d[52]), "+f"(d[53]), "+f"(d[54]), "+f"(d[55]), "+f"(d[56]), "+f"(d[57]), "+f"(d[58]), "+f"(d[59]), "+f"(d[60]), "+f"(d[61]), "+f"(d[62]), "+f"(d[63])
    : "l"(da), "l"(db), "r"(scale_d), "n"(TB), "n"(TA));
}

template<int TB, int TA = 0> __device__ __forceinline__ void wgmma_ss_n64(float (&d)[32], uint64_t da, uint64_t db, int scale_d) {
  asm volatile("{\n.reg .pred p;\nsetp.ne.b32 p, %34, 0;\n"
    "wgmma.mma_async.sync.aligned.m64n64k16.f32.bf16.bf16 {%0, %1, %2, %3, %4, %5, %6, %7, %8, %9, %10, %11, %12, %13, %14, %15, %16, %17, %18, %19, %20, %21, %22, %23, %24, %25, %26, %27, %28, %29, %30, %31}, %32, %33, p, 1, 1, %36, %35;\n}\n"
    : "+f"(d[0]), "+f"(d[1]), "+f"(d[2]), "+f"(d[3]), "+f"(d[4]), "+f"(d[5]), "+f"(d[6]), "+f"(d[7]), "+f"(d[8]), "+f"(d[9]), "+f"(d[10]), "+f"(d[11]), "+f"(d[12]), "+f"(d[13]), "+f"(d[14]), "+f"(d[15]), "+f"(d[16]), "+f"(d[17]), "+f"(d[18]), "+f"(d[19]), "+f"(d[20]), "+f"(d[21]), "+f"(d[22]), "+f"(d[23]), "+f"(d[24]), "+f"(d[25]), "+f"(d[26]), "+f"(d[27]), "+f"(d[28]), "+f"(d[29]), "+f"(d[30]), "+f"(d[31])
    : "l"(da), "l"(db), "r"(scale_d), "n"(TB), "n"(TA));
}

template<int TB, int TA = 0> __device__ __forceinline__ void wgmma_ss_n8(float (&d)[4], uint64_t da, uint64_t db, int scale_d) {
  asm volatile("{\n.reg .pred p;\nsetp.ne.b32 p, %6, 0;\n"
    "wgmma.mma_async.sync.aligned.m64n8k16.f32.bf16.bf16 {%0, %1, %2, %3}, %4, %5, p, 1, 1, %8, %7;\n}\n"
    : "+f"(d[0]), "+f"(d[1]), "+f"(d[2]), "+f"(d[3])
    : "l"(da), "l"(db), "r"(scale_d), "n"(TB), "n"(TA));
}

template<int TB> __device__ __forceinline__ void wgmma_rs_n40(float (&d)[20], uint32_t a0, uint32_t a1, uint32_t a2, uint32_t a3, uint64_t db, int scale_d) {
  asm volatile("{\n.reg .pred p;\nsetp.ne.b32 p, %25, 0;\n"
    "wgmma.mma_async.sync.aligned.m64n40k16.f32.bf16.bf16 {%0, %1, %2, %3, %4, %5, %6, %7, %8, %9, %10, %11, %12, %13, %14, %15, %16, %17, %18, %19}, {%20, %21, %22, %23}, %24, p, 1, 1, %26;\n}\n"
    : "+f"(d[0]), "+f"(d[1]), "+f"(d[2]), "+f"(d[3]), "+f"(d[4]), "+f"(d[5]), "+f"(d[6]), "+f"(d[7]), "+f"(d[8]), "+f"(d[9]), "+f"(d[10]), "+f"(d[11]), "+f"(d[12]), "+f"(d[13]), "+f"(d[14]), "+f"(d[15]), "+f"(d[16]), "+f"(d[17]), "+f"(d[18]), "+f"(d[19])
    : "r"(a0), "r"(a1), "r"(a2), "r"(a3), "l"(db), "r"(scale_d), "n"(TB));
}

#define DEVI __device__ __forceinline__
DEVI uint32_t smem_u32(const void* p) { return (uint32_t)__cvta_generic_to_shared(p); }
DEVI void mbar_init(uint32_t bar, uint32_t cnt) { asm volatile("mbarrier.init.shared::cta.b64 [%0], %1;" :: "r"(bar), "r"(cnt)); }
DEVI void mbar_expect_tx(uint32_t bar, uint32_t bytes) { asm volatile("mbarrier.arrive.expect_tx.shared::cta.b64 _, [%0], %1;" :: "r"(bar), "r"(bytes) : "memory"); }
DEVI void mbar_arrive(uint32_t bar) { asm volatile("mbarrier.arrive.shared::cta.b64 _, [%0];" :: "r"(bar) : "memory"); }
DEVI void mbar_arrive_peer(uint32_t bar) {
  asm volatile("{\n.reg .b32 ra;\nmapa.shared::cluster.u32 ra, %0, %1;\nmbarrier.arrive.shared::cluster.b64 _, [ra];\n}" :: "r"(bar), "r"((blockIdx.x & 1) ^ 1) : "memory");
}
DEVI void bulk_s2peer(uint32_t a, uint32_t bytes, uint32_t bar) {
  asm volatile("{\n.reg .b32 ra, rb;\nmapa.shared::cluster.u32 ra, %0, %3;\nmapa.shared::cluster.u32 rb, %2, %3;\n"
               "cp.async.bulk.shared::cluster.shared::cta.mbarrier::complete_tx::bytes [ra], [%0], %1, [rb];\n}"
               :: "r"(a), "r"(bytes), "r"(bar), "r"((blockIdx.x & 1) ^ 1) : "memory");
}
DEVI void mbar_wait(uint32_t bar, uint32_t parity) {
  asm volatile("{\n.reg .pred p;\nLW:\nmbarrier.try_wait.parity.shared::cta.b64 p, [%0], %1;\n@!p bra LW;\n}" :: "r"(bar), "r"(parity) : "memory");
}
DEVI uint32_t mbar_test(uint32_t bar, uint32_t parity) {
  uint32_t r; asm volatile("{\n.reg .pred p;\nmbarrier.test_wait.parity.shared::cta.b64 p, [%1], %2;\nselp.u32 %0, 1, 0, p;\n}" : "=r"(r) : "r"(bar), "r"(parity) : "memory"); return r;
}
DEVI void mbar_wait_b(uint32_t bar, uint32_t parity) {
  asm volatile("{\n.reg .pred p;\n.reg .u32 it;\nmov.u32 it, 0;\nLW:\nmbarrier.try_wait.parity.shared::cta.b64 p, [%0], %1;\n@p bra LD;\n"
               "add.u32 it, it, 1;\nsetp.lt.u32 p, it, 0x1000000;\n@p bra LW;\ntrap;\nLD:\n}" :: "r"(bar), "r"(parity) : "memory");
}
DEVI void tma_2d(uint32_t dst, const CUtensorMap* m, int c0, int c1, uint32_t bar) {
  asm volatile("cp.async.bulk.tensor.2d.shared::cluster.global.mbarrier::complete_tx::bytes [%0], [%1, {%3, %4}], [%2];"
    :: "r"(dst), "l"(m), "r"(bar), "r"(c0), "r"(c1) : "memory");
}
DEVI void tma_3d(uint32_t dst, const CUtensorMap* m, int c0, int c1, int c2, uint32_t bar) {
  asm volatile("cp.async.bulk.tensor.3d.shared::cluster.global.mbarrier::complete_tx::bytes [%0], [%1, {%3, %4, %5}], [%2];"
    :: "r"(dst), "l"(m), "r"(bar), "r"(c0), "r"(c1), "r"(c2) : "memory");
}
#define POL_EF POL_FIRST
constexpr uint64_t POL_FIRST = 0x12F0000000000000ull, POL_NORMAL = 0x1000000000000000ull;
DEVI void tma_2d_h(uint32_t dst, const CUtensorMap* m, int c0, int c1, uint32_t bar, uint64_t pol) {
  asm volatile("cp.async.bulk.tensor.2d.shared::cluster.global.mbarrier::complete_tx::bytes.L2::cache_hint [%0], [%1, {%3, %4}], [%2], %5;"
    :: "r"(dst), "l"(m), "r"(bar), "r"(c0), "r"(c1), "l"(pol) : "memory");
}
DEVI void tma_3d_h(uint32_t dst, const CUtensorMap* m, int c0, int c1, int c2, uint32_t bar, uint64_t pol) {
  asm volatile("cp.async.bulk.tensor.3d.shared::cluster.global.mbarrier::complete_tx::bytes.L2::cache_hint [%0], [%1, {%3, %4, %5}], [%2], %6;"
    :: "r"(dst), "l"(m), "r"(bar), "r"(c0), "r"(c1), "r"(c2), "l"(pol) : "memory");
}
DEVI void bulk_g2s_h(uint32_t s, const void* g, uint32_t bytes, uint32_t bar, uint64_t pol = POL_EF) {
  asm volatile("cp.async.bulk.shared::cluster.global.mbarrier::complete_tx::bytes.L2::cache_hint [%0], [%1], %2, [%3], %4;"
    :: "r"(s), "l"(g), "r"(bytes), "r"(bar), "l"(pol) : "memory");
}
DEVI void tma_5d(uint32_t dst, const CUtensorMap* m, int c0, int c1, int c2, int c3, int c4, uint32_t bar, uint64_t pol) {
  asm volatile("cp.async.bulk.tensor.5d.shared::cluster.global.mbarrier::complete_tx::bytes.L2::cache_hint [%0], [%1, {%3, %4, %5, %6, %7}], [%2], %8;"
    :: "r"(dst), "l"(m), "r"(bar), "r"(c0), "r"(c1), "r"(c2), "r"(c3), "r"(c4), "l"(pol) : "memory");
}
DEVI void tma_prefetch_2d(const CUtensorMap* m, int c0, int c1) {
  asm volatile("cp.async.bulk.prefetch.tensor.2d.L2.global.tile [%0, {%1, %2}];" :: "l"(m), "r"(c0), "r"(c1) : "memory");
}
DEVI void tma_prefetch_3d(const CUtensorMap* m, int c0, int c1, int c2) {
  asm volatile("cp.async.bulk.prefetch.tensor.3d.L2.global.tile [%0, {%1, %2, %3}];" :: "l"(m), "r"(c0), "r"(c1), "r"(c2) : "memory");
}
DEVI void bulk_prefetch(const void* g, uint32_t bytes) { asm volatile("cp.async.bulk.prefetch.L2.global [%0], %1;" :: "l"(g), "r"(bytes) : "memory"); }
DEVI void bulk_g2s(uint32_t s, const void* g, uint32_t bytes, uint32_t bar) {
  asm volatile("cp.async.bulk.shared::cluster.global.mbarrier::complete_tx::bytes [%0], [%1], %2, [%3];" :: "r"(s), "l"(g), "r"(bytes), "r"(bar) : "memory");
}
DEVI void bulk_s2g(void* g, uint32_t s, uint32_t bytes) {
  asm volatile("cp.async.bulk.global.shared::cta.bulk_group [%0], [%1], %2;\ncp.async.bulk.commit_group;" :: "l"(g), "r"(s), "r"(bytes) : "memory");
}
template<int N> DEVI void bulk_wait() { asm volatile("cp.async.bulk.wait_group %0;" :: "n"(N) : "memory"); }
DEVI void fence_async_smem() { asm volatile("fence.proxy.async.shared::cta;" ::: "memory"); }
DEVI void fence_async_glob() { asm volatile("fence.proxy.async.global;" ::: "memory"); }
DEVI unsigned ld_rlx(const unsigned* p) { unsigned v; asm volatile("ld.relaxed.gpu.global.u32 %0, [%1];" : "=r"(v) : "l"(p) : "memory"); return v; }
DEVI void st_rlx(unsigned* p, unsigned v) { asm volatile("st.relaxed.gpu.global.u32 [%0], %1;" :: "l"(p), "r"(v) : "memory"); }
DEVI uint2 ldg_stream(const uint2* p) { uint2 v; asm volatile("ld.global.nc.L1::no_allocate.v2.u32 {%0, %1}, [%2];" : "=r"(v.x), "=r"(v.y) : "l"(p)); return v; }
DEVI void fence_rel() { asm volatile("fence.release.gpu;" ::: "memory"); }
DEVI uint4 ld_ll(const uint4* p) {
  uint4 v;
  asm volatile("{\n.reg .b128 t;\n.reg .b64 a, b;\nld.relaxed.gpu.global.b128 t, [%4];\nmov.b128 {a, b}, t;\nmov.b64 {%0, %1}, a;\nmov.b64 {%2, %3}, b;\n}"
               : "=r"(v.x), "=r"(v.y), "=r"(v.z), "=r"(v.w) : "l"(p) : "memory");
  return v;
}
DEVI void st_ll(uint4* p, uint32_t x, uint32_t y, uint32_t z, uint32_t w) {
  asm volatile("{\n.reg .b128 t;\n.reg .b64 a, b;\nmov.b64 a, {%1, %2};\nmov.b64 b, {%3, %4};\nmov.b128 t, {a, b};\nst.relaxed.gpu.global.b128 [%0], t;\n}"
               :: "l"(p), "r"(x), "r"(y), "r"(z), "r"(w) : "memory");
}
#define SPIN_MAX 0x1000000
DEVI uint4 poll_ll(const uint4* p, uint32_t mask, uint32_t tag) {
  uint4 v; int it = 0;
  do { v = ld_ll(p); if (++it > SPIN_MAX) __trap(); } while (!__all_sync(0xffffffffu, (v.w & mask) == tag));
  return v;
}
DEVI void poll_ll2(const uint4* p, const uint4* q, uint32_t mask, uint32_t tag, uint4& a, uint4& b) {
  int it = 0;
  do { a = ld_ll(p); b = ld_ll(q); if (++it > SPIN_MAX) __trap(); } while (!__all_sync(0xffffffffu, (a.w & mask) == tag && (b.w & mask) == tag));
}
DEVI void bar_sync(int id, int n) { asm volatile("bar.sync %0, %1;" :: "r"(id), "r"(n) : "memory"); }
DEVI void bar_arrive(int id, int n) { asm volatile("bar.arrive %0, %1;" :: "r"(id), "r"(n) : "memory"); }
DEVI void wg_fence() { asm volatile("wgmma.fence.sync.aligned;" ::: "memory"); }
DEVI void wg_commit() { asm volatile("wgmma.commit_group.sync.aligned;" ::: "memory"); }
template<int N> DEVI void wg_wait() { asm volatile("wgmma.wait_group.sync.aligned %0;" :: "n"(N) : "memory"); }
template<int N> DEVI void reg_inc() { asm volatile("setmaxnreg.inc.sync.aligned.u32 %0;" :: "n"(N)); }
template<int N> DEVI void reg_dec() { asm volatile("setmaxnreg.dec.sync.aligned.u32 %0;" :: "n"(N)); }
DEVI float ex2f(float x) { float y; asm("ex2.approx.ftz.f32 %0, %1;" : "=f"(y) : "f"(x)); return y; }
DEVI uint32_t pack_bf16(float lo, float hi) { uint32_t r; asm("cvt.rn.bf16x2.f32 %0, %1, %2;" : "=r"(r) : "f"(hi), "f"(lo)); return r; }
DEVI float bf_lo(uint32_t v) { return __uint_as_float(v << 16); }
DEVI float bf_hi(uint32_t v) { return __uint_as_float(v & 0xffff0000u); }
DEVI float bf_round(float x) { return bf_lo(pack_bf16(x, 0.f)); }
DEVI void stsm_x4(uint32_t addr, uint32_t a, uint32_t b, uint32_t c, uint32_t d) {
  asm volatile("stmatrix.sync.aligned.m8n8.x4.shared.b16 [%0], {%1,%2,%3,%4};" :: "r"(addr), "r"(a), "r"(b), "r"(c), "r"(d) : "memory");
}
DEVI void ldsm_x4(uint32_t addr, uint32_t& a, uint32_t& b, uint32_t& c, uint32_t& d) {
  asm volatile("ldmatrix.sync.aligned.m8n8.x4.shared.b16 {%0,%1,%2,%3}, [%4];" : "=r"(a), "=r"(b), "=r"(c), "=r"(d) : "r"(addr) : "memory");
}
DEVI uint4 lds128(uint32_t a) { uint4 v; asm volatile("ld.shared.v4.u32 {%0,%1,%2,%3}, [%4];" : "=r"(v.x), "=r"(v.y), "=r"(v.z), "=r"(v.w) : "r"(a) : "memory"); return v; }
DEVI void sts128(uint32_t a, uint4 v) { asm volatile("st.shared.v4.u32 [%0], {%1,%2,%3,%4};" :: "r"(a), "r"(v.x), "r"(v.y), "r"(v.z), "r"(v.w) : "memory"); }
DEVI float2 lds64f(uint32_t a) { float2 v; asm volatile("ld.shared.v2.f32 {%0,%1}, [%2];" : "=f"(v.x), "=f"(v.y) : "r"(a) : "memory"); return v; }
DEVI void sts64f(uint32_t a, float x, float y) { asm volatile("st.shared.v2.f32 [%0], {%1,%2};" :: "r"(a), "f"(x), "f"(y) : "memory"); }
DEVI uint32_t lds32(uint32_t a) { uint32_t v; asm volatile("ld.shared.u32 %0, [%1];" : "=r"(v) : "r"(a) : "memory"); return v; }
DEVI float lds32f(uint32_t a) { return __uint_as_float(lds32(a)); }
DEVI void sts32(uint32_t a, uint32_t v) { asm volatile("st.shared.u32 [%0], %1;" :: "r"(a), "r"(v) : "memory"); }
DEVI void sts32f(uint32_t a, float v) { sts32(a, __float_as_uint(v)); }
DEVI void sts16(uint32_t a, uint32_t v) { asm volatile("st.shared.u16 [%0], %1;" :: "r"(a), "h"((unsigned short)v) : "memory"); }
template<int N> DEVI void keep(float (&d)[N]) {
  #pragma unroll
  for (int i = 0; i < N; i++) asm volatile("" : "+f"(d[i]) :: "memory");
}
template<int N> DEVI void keep(uint32_t (&d)[N]) {
  #pragma unroll
  for (int i = 0; i < N; i++) asm volatile("" : "+r"(d[i]) :: "memory");
}
template<uint32_t HI> DEVI uint64_t mkd(uint32_t lo) { uint64_t r; asm("mov.b64 %0, {%1, %2};" : "=l"(r) : "r"(lo), "n"(HI)); return r; }
constexpr uint32_t HI128 = (1u << 30) | (1024 >> 4), HI64 = (2u << 30) | (512 >> 4);
#define VOFF(x) ((uint32_t)(x) * (uint32_t)(1 - 65536))
DEVI bool elect() { uint32_t p; asm volatile("{\n.reg .pred q;\nelect.sync _|q, 0xffffffff;\nselp.u32 %0, 1, 0, q;\n}" : "=r"(p)); return p; }
DEVI void warp_signal(uint32_t bar) { __syncwarp(); if (elect()) mbar_arrive(bar); }

struct Scratch {
  uint4 kv[128][4][1024];
  uint4 o[8][2][8][2][1024];
  uint4 x[8][16][2048];
  uint4 zero[1024];
  uint4 statP[8][2048];
  uint4 statF[2048];
  uint4 csP[16][8][96];
  uint4 best[8][16];
  uint4 row[16][256];
  uint4 yP[128][112][2];
  uint4 x2[8][256];
  uint4 patch[128][64];
  unsigned flagKV[128][32];
  unsigned flagO[8][32];
  unsigned flagX[8][32];
  unsigned epoch;
};
__device__ __align__(1024) Scratch g_scr;
#define PROFT(cond, slot)
#define PROFW(cond, slot)
#define PROFD(cond, slot)
#define PROFX(cond, slot)
#define PROFY(cond, slot)

constexpr uint32_t SB0 = 65536, HOLE = 90112, SA2 = 98304, SB1 = 131072, SB2 = 155648, STG = 180224;
constexpr uint32_t KVA = 0, KVB = 98304, QO = 65536;
constexpr uint32_t MISC = 229376, CS = MISC, ONES = MISC + 768, BARS = MISC + 1792, INFO = MISC + 2208, WR = MISC + 2224, X2SEG = MISC + 2736, INFO2 = MISC + 2992, DUMP = MISC + 3040;
constexpr uint32_t PAR = HOLE, HV = HOLE + 2048, RED = HOLE + 6144, PATCH = 196608;
constexpr uint32_t SMEM_BYTES = 232448;
enum { B_FULLQ = 0, B_EMPTYQ = 3, B_FULLW = 6, B_EMPTYW = 12, B_HAFREE = 18, B_OFREE = 20,
       B_XFREE = 21,
       B_KVRDY = 23, B_ORDY = 27, B_XRDY = 35, B_STGE = 39,
       B_KVFULL = 42, B_RES = 46, B_PAR = 47, B_STG = 48, B_PFREE = 51, B_COUNT = 52,
       B_ROW = 154 };
#define BAR(x) (sb + BARS + 8 * (x))
DEVI uint32_t qa_off(int s) { return s == 2 ? SA2 : (uint32_t)s * 32768u; }
DEVI uint32_t qb_off(int s) { return s == 0 ? SB0 : (s == 1 ? SB1 : SB2); }
DEVI int kb_order(int bc, int n) {
  const int e = n < 9 ? n - 2 : n - 9;
  return n < 2 ? 2 * bc + n : 2 * (((e < 4 ? e + 4 : e - 4 + (e - 4 >= (bc & 3))) + (bc & 4)) & 7) + (n >= 9);
}
DEVI int wo_order(int bc, int n) { return (n & 8) | ((n + (bc & 6)) & 7); }
DEVI uint32_t w_off(int s) { return (uint32_t)((0x431065 >> (4 * s)) & 7) * 32768u; }
DEVI uint32_t w_par(int n, int s, int L) { return ((n >= 6 && n < 12) ^ (!(s & 2) && L)); }
DEVI int w_next(int n, int s) { return s == 5 ? 0 : (n == 13 ? 4 : s + 1); }

struct Params {
  CUtensorMap mX, mXh, mWq, mWo, mWg, mWu, mWp, mWd;
  const bf16 *x0, *wqkv, *wo, *wr, *wg, *wu, *wd;
  bf16* out;
  Scratch* g;
  unsigned map[128];
};
#define BID ((int)(P.map[blockIdx.x] & 255))
#define FID ((int)(P.map[blockIdx.x] >> 8))
DEVI uint32_t uni(uint32_t v) { return __shfl_sync(0xffffffffu, v, 0); }
#define PQ_N 8
#define PQ_T 700
#define PF0_N 10
#define PF0_T 1600
#define PF1_E 24
#define PF1_T 1100
#define POL_Q1 POL_NORMAL
#define POL_X POL_NORMAL
#define PFA0_BAR 3
#define PFA1_BAR 0
#define PFA0_M 0
#define PFA1_M 0
#define PFA0_T 900
#define PFA1_T 700
#define PF1_S PF0_N
#define PF1_D 0
#define POL_G POL_NORMAL
#define POL_U POL_FIRST
#define POL_D POL_FIRST
#define JQ_N 6
#define WDSRC (P.wd + (size_t)min(fid, 111) * 32768)
#define WDSRC2 (P.wd + FID * 32768)
#define WD_N 4
#define THR_N 6
#define KV_D 1300
#define XD_D 600
#define W0_BAR 3
#define QEF_N 11
#define PACE_T 300
#define POL_Q0 POL_NORMAL
constexpr float LN_EPS = 1e-5f;
constexpr float QSCALE = 0.17677669529663687f * 1.4426950408889634f;

DEVI void fma8(float (&a)[8], uint4 v, float h) {
  a[0] = fmaf(bf_lo(v.x), h, a[0]); a[1] = fmaf(bf_hi(v.x), h, a[1]); a[2] = fmaf(bf_lo(v.y), h, a[2]); a[3] = fmaf(bf_hi(v.y), h, a[3]);
  a[4] = fmaf(bf_lo(v.z), h, a[4]); a[5] = fmaf(bf_hi(v.z), h, a[5]); a[6] = fmaf(bf_lo(v.w), h, a[6]); a[7] = fmaf(bf_hi(v.w), h, a[7]);
}
DEVI uint4 ldsv128(uint32_t a) { uint4 v; asm volatile("ld.volatile.shared.v4.u32 {%0,%1,%2,%3}, [%4];" : "=r"(v.x), "=r"(v.y), "=r"(v.z), "=r"(v.w) : "r"(a) : "memory"); return v; }
DEVI float ldsv32f(uint32_t a) { float v; asm volatile("ld.volatile.shared.f32 %0, [%1];" : "=f"(v) : "r"(a) : "memory"); return v; }
DEVI uint32_t clk() { uint32_t t; asm volatile("mov.u32 %0, %%clock;" : "=r"(t)); return t; }
DEVI int fresh_tid() { int t; asm volatile("mov.u32 %0, %%tid.x;" : "=r"(t)); return t & 127; }
DEVI float fold8(const float (&a)[8]) {
  const int lane = threadIdx.x & 31;
  const bool u = lane & 16, v = lane & 8, x = lane & 4;
  float b0 = (u ? a[4] : a[0]) + __shfl_xor_sync(0xffffffffu, u ? a[0] : a[4], 16), b1 = (u ? a[5] : a[1]) + __shfl_xor_sync(0xffffffffu, u ? a[1] : a[5], 16);
  float b2 = (u ? a[6] : a[2]) + __shfl_xor_sync(0xffffffffu, u ? a[2] : a[6], 16), b3 = (u ? a[7] : a[3]) + __shfl_xor_sync(0xffffffffu, u ? a[3] : a[7], 16);
  float c0 = (v ? b2 : b0) + __shfl_xor_sync(0xffffffffu, v ? b0 : b2, 8), c1 = (v ? b3 : b1) + __shfl_xor_sync(0xffffffffu, v ? b1 : b3, 8);
  return (x ? c1 : c0) + __shfl_xor_sync(0xffffffffu, x ? c0 : c1, 4);
}
DEVI float swiglu(float g, float u) { g = bf_round(g); return bf_round(bf_round(__fdividef(g, 1.f + __expf(-g))) * bf_round(u)); }

DEVI void qk_issue(float (&s)[32], uint32_t qd, uint32_t kd) {
  wgmma_ss_n64<0>(s, mkd<HI64>(qd), mkd<HI64>(kd), 0);
  wgmma_ss_n64<0>(s, mkd<HI64>(qd + 2), mkd<HI64>(kd + 2), 1);
}
template<int J0, int J1> DEVI void exp_pack(const float (&s)[32], uint32_t (&p)[16]) {
  #pragma unroll
  for (int j = J0; j < J1; j++) p[j] = pack_bf16(ex2f(s[2 * j]), ex2f(s[2 * j + 1]));
}
DEVI bool attn_pack(const float (&o)[20], uint32_t (&ob)[8]) {
  const float lo = 5.421010862427522e-20f, hi = 1.8446744073709552e19f;
  float i0, i1; asm("rcp.approx.ftz.f32 %0, %1;" : "=f"(i0) : "f"(o[16])); asm("rcp.approx.ftz.f32 %0, %1;" : "=f"(i1) : "f"(o[18]));
  #pragma unroll
  for (int e = 0; e < 8; e++) ob[e] = pack_bf16(o[2 * e] * ((e & 1) ? i1 : i0), o[2 * e + 1] * ((e & 1) ? i1 : i0));
  return __all_sync(0xffffffffu, o[16] >= lo && o[16] <= hi && o[18] >= lo && o[18] <= hi);
}
DEVI void attn_store(const uint32_t (&ob)[8], bool ok, uint32_t st, uint32_t sb, uint32_t bar) {
  stsm_x4(ok ? st : sb + DUMP, ob[0], ob[1], ob[2], ob[3]); stsm_x4(ok ? st ^ 32 : sb + DUMP, ob[4], ob[5], ob[6], ob[7]);
  __syncwarp();
  asm volatile("{\n.reg .pred p, q;\nelect.sync _|q, 0xffffffff;\nsetp.ne.and.u32 p, %1, 0, q;\n@p mbarrier.arrive.shared::cta.b64 _, [%0];\n}" :: "r"(bar), "r"((uint32_t)ok) : "memory");
}
DEVI void attn_exact(uint32_t st, uint32_t kv, int t, bool hasprev, uint32_t bar) {
  const int lane = threadIdx.x & 31;
  #pragma unroll 1
  for (int row = ((threadIdx.x >> 5) & 3) * 16, n = 0; n < 16; n++, row++) {
    const int k1 = 256 + t * 64 + row;
    float m = -INFINITY, l = 0.f, o = 0.f;
    #pragma unroll 1
    for (int k0 = hasprev ? k1 - 255 : 256; k0 <= k1; k0 += 32) {
      const int k = min(k0 + lane, k1), r = k & 63;
      float sc = 0.f;
      #pragma unroll 1
      for (int c = 0; c < 16; c++) {
        uint32_t a = lds32(st + row * 64 + ((c * 4) ^ ((row & 6) << 3))), b = lds32(kv + (k >> 6) * 8192 + r * 64 + ((c * 4) ^ ((r & 6) << 3)));
        sc = fmaf(bf_lo(a), bf_lo(b), fmaf(bf_hi(a), bf_hi(b), sc));
      }
      float mn = fmaxf(m, sc);
      #pragma unroll 1
      for (int x = 16; x; x >>= 1) mn = fmaxf(mn, __shfl_xor_sync(0xffffffffu, mn, x));
      const float al = ex2f(m - mn), pr = ex2f(sc - mn);
      m = mn; l *= al; o *= al;
      #pragma unroll 1
      for (int q = k0; q <= min(k0 + 31, k1); q++) {
        const float z = __shfl_sync(0xffffffffu, pr, q - k0);
        uint32_t b = lds32(kv + (q >> 6) * 8192 + 4096 + (q & 63) * 64 + (((lane >> 1) * 4) ^ ((q & 6) << 3)));
        l += z; o = fmaf(z, (lane & 1) ? bf_hi(b) : bf_lo(b), o);
      }
    }
    __syncwarp();
    sts16(st + row * 64 + ((lane * 2) ^ ((row & 6) << 3)), pack_bf16(__fdividef(o, l), 0.f));
  }
  warp_signal(bar);
}

template<int K0, int K1, int DONE = 0> DEVI void exp_pv(const float (&s)[32], uint32_t (&p)[16], float (&o)[20], uint32_t vd, bool accum) {
  #pragma unroll
  for (int ks = K0; ks < K1; ks++) {
    if (ks >= DONE) {
      #pragma unroll
      for (int j = 4 * ks; j < 4 * ks + 4; j++) p[j] = pack_bf16(ex2f(s[2 * j]), ex2f(s[2 * j + 1]));
    }
    asm volatile("" : "+r"(p[4 * ks]), "+r"(p[4 * ks + 1]), "+r"(p[4 * ks + 2]), "+r"(p[4 * ks + 3]));
    wg_fence();
    wgmma_rs_n40<1>(o, p[ks * 4], p[ks * 4 + 1], p[ks * 4 + 2], p[ks * 4 + 3], mkd<HI64>(vd + VOFF(ks * 64)), ks ? 1 : accum);
  }
}
DEVI void exp_pv2(const float (&s)[32], const float (&sx)[32], uint32_t (&p)[16], uint32_t (&px)[16], float (&o)[20], uint32_t v0, uint32_t v4,
                  const uint32_t (&msk)[9], int tdiag) {
  #pragma unroll
  for (int ks = 0; ks < 4; ks++) {
    #pragma unroll
    for (int j = 4 * ks; j < 4 * ks + 4; j++) {
      const int c = 8 * (j >> 1) - 8 * (j & 1);
      const uint32_t e = pack_bf16(ex2f(c > tdiag ? s[2 * j] : sx[2 * j]), ex2f(c + 1 > tdiag ? s[2 * j + 1] : sx[2 * j + 1])), m = msk[(j >> 1) - (j & 1) + 1];
      p[j] = e & m; px[j] = e & ~m;
      asm volatile("" : "+r"(p[j]), "+r"(px[j]));
    }
    wg_fence();
    wgmma_rs_n40<1>(o, p[ks * 4], p[ks * 4 + 1], p[ks * 4 + 2], p[ks * 4 + 3], mkd<HI64>(v0 + VOFF(ks * 64)), 1);
    wgmma_rs_n40<1>(o, px[ks * 4], px[ks * 4 + 1], px[ks * 4 + 2], px[ks * 4 + 3], mkd<HI64>(v4 + VOFF(ks * 64)), 1);
  }
}

template<int J0> DEVI void qkv_store(const float (&a)[96], float p0, float p1, uint32_t d) {
  #pragma unroll
  for (int hh = 0; hh < 2; hh++) {
    const int j = 4 * (J0 + 2 * hh);
    stsm_x4(d ^ (hh << 5), pack_bf16(a[j] * p0, a[j + 1] * p0), pack_bf16(a[j + 2] * p1, a[j + 3] * p1),
                           pack_bf16(a[j + 4] * p0, a[j + 5] * p0), pack_bf16(a[j + 6] * p1, a[j + 7] * p1));
  }
}
DEVI void mean_step(float (&a)[96], float m0, float m1, uint32_t cd, bool z) {
  const uint32_t u0 = z ? 0u : __float_as_uint(m0), u1 = z ? 0u : __float_as_uint(m1);
  uint32_t ma[4] = {__byte_perm(u0, 0u, 0x1010), __byte_perm(u1, 0u, 0x1010), __byte_perm(u0, 0u, 0x3232), __byte_perm(u1, 0u, 0x3232)};
  keep(ma);
  wg_fence();
  wgmma_rs_n192<1>(a, ma[0], ma[1], ma[2], ma[3], mkd<2>(cd), 1);
  wg_commit();
}

template<bool FIRST> DEVI void qkv_block(float (&aX)[96], float (&aY)[96], uint32_t sb16, int s, int tX, int tY) {
  uint32_t a16 = sb16 + (qa_off(s) >> 4), b16 = (sb16 + (qb_off(s) >> 4)) | ((8192u >> 4) << 16);
  uint32_t ax = (a16 + tX * 512) | 0x10000u, ay = (a16 + tY * 512) | 0x10000u;
  wg_fence();
  #pragma unroll
  for (int ks = 0; ks < 4; ks++) {
    wgmma_ss_n192<1>(aX, mkd<HI128>(ax + ks * 2), mkd<HI128>(b16 + ks * 128), !(FIRST && ks == 0));
    wgmma_ss_n192<1>(aY, mkd<HI128>(ay + ks * 2), mkd<HI128>(b16 + ks * 128), !(FIRST && ks == 0));
  }
  wg_commit();
}
DEVI void qkv_half(float (&a)[96], uint32_t sb16, int t, uint32_t sa, uint32_t sbb) {
  wg_fence();
  #pragma unroll
  for (int ks = 0; ks < 4; ks++)
    wgmma_ss_n192<1>(a, mkd<HI128>(((sb16 + (sa >> 4) + t * 512) | 0x10000u) + ks * 2), mkd<HI128>(((sb16 + (sbb >> 4)) | ((8192u >> 4) << 16)) + ks * 128), 1);
  wg_commit();
}
template<bool FIRST> DEVI void wo_block(float (&acc)[64], uint32_t sb16, int s, int wg) {
  uint32_t a16 = (sb16 + (w_off(s) >> 4) + wg * 256) | 0x10000u, b16 = (sb16 + (w_off(s) >> 4) + 1024) | ((8192u >> 4) << 16);
  wg_fence();
  #pragma unroll
  for (int ks = 0; ks < 4; ks++)
    wgmma_ss_n128<1>(acc, mkd<HI64>(a16 + (ks >> 1) * 512 + (ks & 1) * 2), mkd<HI128>(b16 + ks * 128), !(FIRST && ks == 0));
  wg_commit();
}
DEVI void consumer(const Params& P, uint32_t sb, int wg) {
  const int w = uni((threadIdx.x >> 5) & 3);
  #define LAYER uni(mbar_test(BAR(B_RES), 0))
  #define IDS L = LAYER; const int tid = fresh_tid(), lane = tid & 31
  const uint32_t ids = uni(P.map[blockIdx.x]);
  const int bi = (ids >> 4) & 7, rh = ids & 1, bc = (ids & 15) >> 1, fid = ids >> 8;
  const int tX = 3 - wg, tY = wg;
  constexpr uint32_t sb16 = 1024 >> 4;
  #pragma unroll 1
  while (true) {
    int L = LAYER;
    {
      float aX[96], aY[96];
      const bool lead = fresh_tid() == 0;
      if (L) mbar_wait(BAR(B_XRDY + wg * 2 + 1), 0);
      mbar_wait(BAR(B_FULLQ), 0);
      PROFW(threadIdx.x == 0, L * 8 + 1);
      qkv_block<true>(aX, aY, sb16, 0, tX, tY);
      #pragma unroll 1
      for (int n = 1, s = 1, ps = 0, ph = 0; n < 14; n++) {
        mbar_wait(BAR(B_FULLQ + s), ph ^ (s ? L : 0));
        PROFD(threadIdx.x == 0 && L && (n == 2 || n == 3 || n == 7 || n == 11 || n == 13), n == 2 ? 48 : 49 + (n >> 2));
        qkv_block<false>(aX, aY, sb16, s, tX, tY);
        wg_wait<1>(); if (lead) mbar_arrive(BAR(B_EMPTYQ + ps));
        ps = s; if (s == 2) { s = 0; ph ^= 1; } else s++;
      }
      mbar_wait(BAR(B_FULLQ + 2), L);
      qkv_half(aX, sb16, tX, SA2, SB2);
      mbar_wait(BAR(B_ROW), L);
      IDS;
      const uint32_t pa = sb + PAR + (w * 16 + (lane >> 2)) * 8;
      float2 p0 = lds64f(pa + tX * 512), p1 = lds64f(pa + tX * 512 + 64), p2 = lds64f(pa + tY * 512), p3 = lds64f(pa + tY * 512 + 64);
      mean_step(aX, p0.y, p1.y, sb16 + (CS >> 4), lane & 3);
      mbar_wait(BAR(B_FULLQ), 1);
      qkv_half(aX, sb16, tX, 0, SB0);
      wg_wait<3>(); if (lead) mbar_arrive(BAR(B_EMPTYQ + 1));
      bar_sync(1, 256);
      qkv_half(aY, sb16, tY, SA2, SB2);
      wg_wait<1>(); keep(aX);
      const int srow = w * 16 + (lane & 15);
      const uint32_t x0 = sb + srow * 64 + (((lane >> 4) ^ ((srow >> 1) & 3)) << 4), xX = x0 + (4 + tX) * 8192, xY = x0 + (4 + tY) * 8192;
      qkv_store<8>(aX, p0.x, p1.x, xX + KVA); qkv_store<16>(aX, p0.x, p1.x, xX + KVA + 4096);
      warp_signal(BAR(B_KVRDY + wg * 2));
      qkv_half(aY, sb16, tY, 0, SB0);
      mean_step(aY, p2.y, p3.y, sb16 + (CS >> 4), fresh_tid() & 3);
      wg_wait<2>(); if (lead) mbar_arrive(BAR(B_EMPTYQ + 2));
      mbar_wait(BAR(B_EMPTYQ + 2), L);
      qkv_store<12>(aX, p0.x, p1.x, xX + KVB); qkv_store<20>(aX, p0.x, p1.x, xX + KVB + 4096);
      wg_wait<0>(); keep(aY);
      if (lead) mbar_arrive(BAR(B_EMPTYQ));
      PROFW(threadIdx.x == 0, L * 8 + 2);
      qkv_store<8>(aY, p2.x, p3.x, xY + KVA); qkv_store<16>(aY, p2.x, p3.x, xY + KVA + 4096);
      qkv_store<12>(aY, p2.x, p3.x, xY + KVB); qkv_store<20>(aY, p2.x, p3.x, xY + KVB + 4096);
      warp_signal(BAR(B_KVRDY + wg * 2 + 1));
      p0.x *= QSCALE; p1.x *= QSCALE; p2.x *= QSCALE; p3.x *= QSCALE;
      mbar_wait(BAR(B_EMPTYQ), 1);
      qkv_store<0>(aX, p0.x, p1.x, x0 + QO + tX * 4096);
      qkv_store<0>(aY, p2.x, p3.x, x0 + QO + tY * 4096); qkv_store<4>(aY, p2.x, p3.x, x0 + QO + 16384 + tY * 4096);
      mbar_wait(BAR(B_PAR), L);
      qkv_store<4>(aX, p0.x, p1.x, x0 + QO + 16384 + tX * 4096);
      const int prow = (int)uni(lds32(sb + INFO)) - bi * 256;
      if ((prow >> 4) == tX * 4 + w || (prow >> 4) == tY * 4 + w) {
        __syncwarp();
        if (lane < 24) sts128(sb + (prow & 63) * 64 + (((lane ^ (prow >> 1)) & 3) << 4) +
                              (lane < 8 ? QO + (lane >> 2) * 16384 + (prow >> 6) * 4096 : ((lane & 4) ? KVB : KVA) + (4 + (prow >> 6)) * 8192 + (lane >> 4) * 4096),
                              lds128(sb + PATCH + lane * 16));
      }
      fence_async_smem();
      bar_sync(1, 256);
    }
    PROFW(threadIdx.x == 0, L * 8 + 3);
    {
      IDS;
      float s0[32], s1[32], sx[32], o[20], op[20];
      uint32_t p0[16], p1[16], px[16], msk[9];
      const int tdiag = w * 16 + (lane >> 2) - 2 * (lane & 3);
      #pragma unroll
      for (int e = 0; e < 9; e++) msk[e] = ((8 * e - 8 > tdiag) ? 0xFFFFu : 0u) | ((8 * e - 7 > tdiag) ? 0xFFFF0000u : 0u);
      keep(msk);
      const uint32_t ones = (sb16 + (ONES >> 4)) << 16;
      const uint32_t qX = (sb16 + (QO >> 4) + tX * 256) | 0x10000u, qY = (sb16 + (QO >> 4) + tY * 256) | 0x10000u;
      const uint32_t kXB = (sb16 + (KVB >> 4) + tX * 512) | 0x10000u;
      uint32_t redo = 0;
      const uint32_t ost = sb + QO + (w * 16 + (lane & 15)) * 64 + (((lane >> 4) ^ ((lane >> 1) & 3)) << 4);
      #define QK(s, q, k) do { wg_fence(); qk_issue(s, q, k); wg_commit(); } while (0)
      #define QK2(q, k) do { wg_fence(); qk_issue(s1, q, k); qk_issue(sx, q, (k) + 2048); wg_commit(); } while (0)
      #define VB(v, b) ((v) + VOFF((b) * 512))
      QK(s0, qX + 1024, kXB + 1536);
      #pragma unroll
      for (int e = 0; e < 20; e++) o[e] = 0.f;
      wg_wait<0>(); keep(s0);
      #pragma unroll 1
      for (int h = 1; h >= 0; h--) {
        const uint32_t kXA = kXB - ((KVB - KVA) >> 4), kX = h ? kXB : kXA, vX = VOFF((kX & 0xffffu) + 256) + ones;
        QK(s1, qX + h * 1024, kX + 1024);
        #pragma unroll
        for (int e = 0; e < 20; e++) op[e] = o[e];
        keep(op);
        exp_pv<0, 4>(s0, p0, o, VB(vX, 3), false); wg_commit();
        wg_wait<1>(); keep(s1);
        exp_pv<0, 2>(s1, p1, o, VB(vX, 2), true);
        bar_sync(h ? 12 + wg : 4 + wg * 4, h ? 128 : 160);
        QK(s0, qX, kXA + 512 + h * 1024);
        exp_pv<2, 4>(s1, p1, o, VB(vX, 2), true); wg_commit();
        wg_wait<0>(); keep(s0); keep(p0); keep(p1); keep(o);
      }
      #pragma unroll 1
      for (int h = 0; h < 2; h++) {
        const uint32_t kb16 = sb16 + ((h ? KVB : KVA) >> 4), kY = (kb16 + tY * 512) | 0x10000u, qy = qY + h * 1024;
        const uint32_t onesP = bi ? ones : (kb16 + 1984) << 16;
        const uint32_t vX = VOFF(kb16 + tX * 512 + 256), vY = VOFF(kb16 + tY * 512 + 256);
        uint32_t ob[8];
        QK2(qX + h * 1024, (kb16 + tX * 512) | 0x10000u);
        exp_pv<0, 4>(s0, p0, o, VB(vX + (wg ? onesP : ones), 1), true); wg_commit();
        wg_wait<1>(); keep(s1); keep(sx);
        QK(s0, qy, kY + 1536);
        exp_pv2(s1, sx, p1, px, o, vX + onesP, VB(vX + ones, 4), msk, tdiag); wg_commit();
        wg_wait<1>(); keep(s0); keep(p0);
        QK(s1, qy, kY + 1024);
        exp_pack<0, 4>(s0, p0);
        wg_wait<1>(); keep(o); keep(p1); keep(px);
        bool ok = attn_pack(o, ob); keep(ob);
        exp_pv<0, 4, 1>(s0, p0, o, VB(vY + (wg ? ones : onesP), 3), false); wg_commit();
        attn_store(ob, ok, ost + (h * 4 + tX) * 4096, sb, BAR(B_ORDY + wg * 4 + h * 2)); redo |= ok ? 0u : 1u << (h * 2);
        wg_wait<1>(); keep(s1);
        exp_pv<0, 2>(s1, p1, o, VB(vY + onesP, 2), true);
        bar_sync(5 + wg * 4 + h * 2, 160);
        QK(s0, qy, kY + 512);
        exp_pv<2, 4>(s1, p1, o, VB(vY + onesP, 2), true); wg_commit();
        wg_wait<1>(); keep(s0); keep(p0);
        QK2(qy, kY);
        exp_pv<0, 4>(s0, p0, o, VB(vY + onesP, 1), true); wg_commit();
        wg_wait<1>(); keep(s1); keep(sx); keep(p1);
        bar_sync(6 + wg * 4, h ? 128 : 160);
        QK(s0, h ? qy : qX + 1024, kXB + 512);
        exp_pv2(s1, sx, p1, px, o, vY + onesP, VB(vY + ones, 4), msk, tdiag); wg_commit();
        wg_wait<0>(); keep(o); keep(s0); keep(p0); keep(p1); keep(px);
        ok = attn_pack(o, ob); attn_store(ob, ok, ost + (h * 4 + tY) * 4096, sb, BAR(B_ORDY + wg * 4 + h * 2 + 1)); redo |= ok ? 0u : 2u << (h * 2);
        #pragma unroll
        for (int e = 0; e < 20; e++) o[e] = op[e];
      }
      #undef QK
      #undef QK2
      #undef VB
      if (redo) {
        #pragma unroll 1
        for (int u = 0; u < 4; u++) if ((redo >> u) & 1) {
          const int h = u >> 1, t = (u & 1) ? tY : tX;
          attn_exact(sb + QO + (h * 4 + t) * 4096, sb + (h ? KVB : KVA), t, bi > 0, BAR(B_ORDY + wg * 4 + u));
        }
      }
    }
    PROFW(threadIdx.x == 0, L * 8 + 4);
    {
      IDS;
      const int t256 = wg * 128 + tid;
      float acc[64];
      const int tt = wg ^ rh;
      const int grow = bi * 256 + rh * 128 + tt * 64 + w * 16 + (lane >> 2);
      float al0 = 1.f, be0 = 0.f, al1 = 1.f, be1 = 0.f;
      const int idx0 = (int)uni(lds32(sb + INFO));
      const uint32_t tag = lds32(sb + INFO + 8) + L;
      uint4* const sp = &P.g->statP[bc][grow + (lane & 1) * 8];
      uint4* const yp = &P.g->yP[t256 >> 1][min(fid, 111)][t256 & 1];
      mbar_wait(BAR(B_FULLW), L);
      PROFW(t256 == 0, L * 8 + 5);
      wo_block<true>(acc, sb16, 0, tt);
      if (!(lane & 2)) st_ll(sp, 0u, 0u, 0u, 0u);
      uint4 fa = make_uint4(0u, 0u, 0u, 0u), fb = fa;
      uint2 wd[4];
      if (L) {
        if (fid < 112) st_ll(yp, 0u, 0u, 0u, 0u);
        fa = ld_ll(&P.g->statF[grow]); fb = ld_ll(&P.g->statF[grow + 8]);
      }
      #pragma unroll
      for (int e = 0; e < 4; e++) { wd[e] = make_uint2(0u, 0u); if (L) wd[e] = ldg_stream((const uint2*)(WDSRC) + t256 + (28 + e) * 256); }
      #pragma unroll 1
      for (int n = 1, q = 1, pq = 0; n < 16; n++) {
        mbar_wait(BAR(B_FULLW + q), w_par(n, q, L));
        PROFD(t256 == 0 && !L && (n == 4 || n == 7 || n == 8 || n == 12), (n == 7 ? 63 : 41 + (n >> 2)));
        wo_block<false>(acc, sb16, q, tt);
        wg_wait<1>(); if (tid == 0) mbar_arrive(BAR(B_EMPTYW + pq));
        pq = q; q = w_next(n, q);
      }
      if (L) {
        float r0 = rsqrtf(__uint_as_float(fa.y) + LN_EPS), r1 = rsqrtf(__uint_as_float(fb.y) + LN_EPS);
        if (grow != idx0) { al0 = 1.f + r0; be0 = -__uint_as_float(fa.x) * r0; }
        if (grow + 8 != idx0) { al1 = 1.f + r1; be1 = -__uint_as_float(fb.x) * r1; }
      }
      mbar_wait(BAR(B_RES), L);
      const int srow = tt * 64 + w * 16 + (lane & 15);
      const uint32_t ra = sb + rh * 16384 + srow * 128, sw = ((lane >> 4) ^ (srow & 7)) << 4;
      if ((idx0 >> 4) == bi * 16 + rh * 8 + tt * 4 + w) {
        int r = idx0 & 127;
        if (lane < 16) sts128(sb + (lane >> 3) * 32768 + rh * 16384 + r * 128 + (((lane & 7) ^ (r & 7)) << 4), lds128(sb + X2SEG + lane * 16));
        __syncwarp();
      }
      uint32_t rs[32];
      #pragma unroll
      for (int jj = 0; jj < 8; jj++) ldsm_x4((ra + (jj >> 2) * 32768) + (sw ^ ((jj & 3) << 5)), rs[4 * jj], rs[4 * jj + 1], rs[4 * jj + 2], rs[4 * jj + 3]);
      float rf[64];
      #pragma unroll
      for (int e = 0; e < 32; e++) { rf[2 * e] = fmaf(bf_lo(rs[e]), (e & 1) ? al1 : al0, (e & 1) ? be1 : be0); rf[2 * e + 1] = fmaf(bf_hi(rs[e]), (e & 1) ? al1 : al0, (e & 1) ? be1 : be0); }
      keep(rf);
      mbar_wait(BAR(B_RES), L);
      wg_wait<0>(); keep(acc);
      if (tid == 0) mbar_arrive(BAR(B_EMPTYW + 5));
      PROFW(t256 == 0, L * 8 + 6);
      #pragma unroll
      for (int jj = 0; jj < 8; jj++) {
        float* a = acc + 8 * jj;
        #pragma unroll
        for (int e = 0; e < 8; e++) a[e] += rf[8 * jj + e];
        stsm_x4((ra + (jj >> 2) * 32768) + (sw ^ ((jj & 3) << 5)), pack_bf16(a[0], a[1]), pack_bf16(a[2], a[3]), pack_bf16(a[4], a[5]), pack_bf16(a[6], a[7]));
        if (jj == 7) fence_async_smem();
        if ((jj & 3) == 3) warp_signal(BAR(B_XRDY + wg * 2 + (jj >> 2)));
      }
      {
        float s1a = 0.f, s2a = 0.f, da = 0.f, s1b = 0.f, s2b = 0.f, db = 0.f;
        #pragma unroll
        for (int j = 0; j < 16; j++) {
          const float* a = acc + 4 * j; float2 wv = lds64f(sb + WR + j * 32 + (lane & 3) * 8);
          s1a += a[0] + a[1]; s1b += a[2] + a[3];
          s2a = fmaf(a[0], a[0], s2a); s2b = fmaf(a[2], a[2], s2b); s2a = fmaf(a[1], a[1], s2a); s2b = fmaf(a[3], a[3], s2b);
          da = fmaf(a[0], wv.x, da); db = fmaf(a[2], wv.x, db); da = fmaf(a[1], wv.y, da); db = fmaf(a[3], wv.y, db);
        }
        bool odd = lane & 1;
        float u1 = (odd ? s1b : s1a) + __shfl_xor_sync(0xffffffffu, odd ? s1a : s1b, 1);
        float u2 = (odd ? s2b : s2a) + __shfl_xor_sync(0xffffffffu, odd ? s2a : s2b, 1);
        float u3 = (odd ? db : da) + __shfl_xor_sync(0xffffffffu, odd ? da : db, 1);
        u1 += __shfl_xor_sync(0xffffffffu, u1, 2); u2 += __shfl_xor_sync(0xffffffffu, u2, 2); u3 += __shfl_xor_sync(0xffffffffu, u3, 2);
        if (!(lane & 2)) st_ll(sp, __float_as_uint(u1), __float_as_uint(u2), __float_as_uint(u3), tag);
      }
      PROFW(t256 == 0, L * 8 + 7);
      if (L) {
        mbar_wait(BAR(B_PAR), 0);
        { float2 pa = lds64f(sb + PAR + (grow & 127) * 8), pb = lds64f(sb + PAR + (grow & 127) * 8 + 64); al0 = pa.x; be0 = pa.y; al1 = pb.x; be1 = pb.y; }
        #pragma unroll
        for (int j = 0; j < 16; j++) {
          rs[2 * j] = pack_bf16(fmaf(acc[4 * j], al0, be0), fmaf(acc[4 * j + 1], al0, be0));
          rs[2 * j + 1] = pack_bf16(fmaf(acc[4 * j + 2], al1, be1), fmaf(acc[4 * j + 3], al1, be1));
        }
        #pragma unroll
        for (int jj = 0; jj < 8; jj++) stsm_x4((ra + (jj >> 2) * 32768) + (sw ^ ((jj & 3) << 5)), rs[4 * jj], rs[4 * jj + 1], rs[4 * jj + 2], rs[4 * jj + 3]);
        PROFW(t256 == 0, 16);
        if (fid >= 112) bar_arrive(3, 384);
        else {
          float d[4] = {0.f, 0.f, 0.f, 0.f};
          mbar_wait(BAR(B_FULLW + wg * 4), 0); mbar_wait(BAR(B_FULLW + wg * 4 + 1), 0);
          bar_sync(3, 384);
          PROFW(t256 == 0, 29);
          #pragma unroll 1
          for (int g = 0; g < 4; g++) {
            const uint32_t ad = (sb16 + (wg ? 6144 : 10240) + (g >> 1) * 2048 + (g & 1) * 512) | (1024u << 16), bd = (sb16 + (HV >> 4) + wg * 64 + g * 16) | 0x10000u;
            wg_fence();
            #pragma unroll
            for (int ks = 0; ks < 8; ks++) wgmma_ss_n8<0, 1>(d, mkd<HI64>(ad + ks * 64), mkd<8>(bd + ks * 2), 1);
            wg_commit();
          }
          mbar_wait(BAR(B_FULLW + 2), 0);
          wg_wait<0>(); keep(d);
          if (!(lane & 3)) { sts32f(sb + PAR + 1024 + wg * 256 + w * 64 + lane, d[0]); sts32f(sb + PAR + 1056 + wg * 256 + w * 64 + lane, d[2]); }
          bar_sync(1, 256);
          const uint32_t ga = sb + PAR + 1024 + lane * 4, aa = sb + HV + (t256 >> 5) * 128;
          sts32f(aa + lane * 4, swiglu(lds32f(ga) + lds32f(ga + 256), lds32f(ga + 128) + lds32f(ga + 384)));
          __syncwarp();
          PROFW(t256 == 0, 26);
          float y0 = 0.f, y1 = 0.f, y2 = 0.f, y3 = 0.f;
          uint32_t tbl = rh ? 0x001459a8u : 0x023679a8u;
          uint4 a4 = lds128(aa + 112);
          #pragma unroll 2
          for (int n = 0; n < 8; n++, tbl >>= 4) {
            const uint32_t src = sb + t256 * 8 + (tbl & 15) * 8192;
            const uint4 an = lds128(aa + ((0x00123564u >> (4 * n)) & 15) * 16);
            #pragma unroll
            for (int e = 0; e < 4; e++) {
              const float av = __uint_as_float(e == 0 ? a4.x : (e == 1 ? a4.y : (e == 2 ? a4.z : a4.w)));
              y0 = fmaf(bf_lo(wd[e].x), av, y0); y1 = fmaf(bf_hi(wd[e].x), av, y1); y2 = fmaf(bf_lo(wd[e].y), av, y2); y3 = fmaf(bf_hi(wd[e].y), av, y3);
              const float2 v = lds64f(src + e * 2048); wd[e] = make_uint2(__float_as_uint(v.x), __float_as_uint(v.y));
            }
            a4 = an;
          }
          st_ll(yp, __float_as_uint(y0), __float_as_uint(y1), __float_as_uint(y2), (__float_as_uint(y3) & ~255u) | (lds32(sb + INFO + 12) + 1));
          PROFW(t256 == 0, 27);
        }
        return;
      }
    }
  }
  #undef IDS
  #undef LAYER
}

DEVI void loader(const Params& P, uint32_t sb) {
  const int lane = threadIdx.x & 31;
  const int bid = uni(BID), bi = bid >> 4, bp = bid & 15, rh = bp & 1, bc = bp >> 1;
  uint32_t phq = 0, tag = 0;
  #pragma unroll 1
  for (int L = 0; L < 2; L++) {
    int s = 0;
    uint32_t rdy = 0;
    #pragma unroll 1
    for (int n = L ? 0 : 3; n < 16; n++) {
      int kb = L ? kb_order(bc, n) : n;
      mbar_wait(BAR(B_EMPTYQ + s), (phq >> s) & 1);
      phq ^= 1u << s;
      if (L && n == 1) { mbar_wait(BAR(B_XRDY + 1), 0); mbar_wait(BAR(B_XRDY + 3), 0); }
      if (lane == 0) {
        mbar_expect_tx(BAR(B_FULLQ + s), L && n < 2 ? 40960 : 57344);
        tma_3d_h(sb + qb_off(s), &P.mWq, bp * 64, kb * 64, 0, BAR(B_FULLQ + s), L && n >= QEF_N ? POL_FIRST : POL_NORMAL);
        if (!L) tma_2d(sb + qa_off(s), &P.mX, kb * 64, bi * 256, BAR(B_FULLQ + s));
      }
      if (L && n >= 2) {
        if (((rdy >> (2 * kb)) & 3) != 3) {
          do { rdy = __ballot_sync(0xffffffffu, ld_rlx(&P.g->flagX[bi][lane]) == tag); } while (((rdy >> (2 * kb)) & 3) != 3);
          fence_async_glob();
        }
        if (n == 3 || n == 4) mbar_wait(BAR(B_XFREE + n - 3), 0);
        if (lane == 0) bulk_g2s_h(sb + qa_off(s), P.g->x[bi][kb], 32768, BAR(B_FULLQ + s), POL_X);
      }
      PROFY(L && lane == 0 && (n == 2 || n == 3 || n == 9), n == 9 ? 60 : 56 + n);
      if (L && n == 2) { mbar_wait(BAR(B_FULLQ), 0); mbar_wait(BAR(B_FULLQ + 1), 1); if (lane < 2) mbar_arrive_peer(BAR(B_XFREE + lane)); }
      s = (s == 2) ? 0 : s + 1;
    }
    for (int q = 0; q < 3; q++) mbar_wait(BAR(B_EMPTYQ + q), (phq >> q) & 1);
    tag = lds32(sb + INFO + 8) + L;
    #pragma unroll 1
    for (int q = 0; q < 4; q++) {
            if (bi) {
        const unsigned* f = &P.g->flagKV[bid - 16][q];
        while (ld_rlx(f) != tag);
        fence_async_glob();
      }
      if (lane == 0) {
        mbar_expect_tx(BAR(B_KVFULL + q), 16384);
        bulk_g2s_h(sb + ((q >> 1) ? KVB : KVA) + ((q & 1) ? 0 : 16384), bi ? P.g->kv[bid - 16][q] : P.g->zero, 16384, BAR(B_KVFULL + q));
      }
      PROFY(!L && lane == 0 && bi && q != 2, 34 + (q + 1) / 2);
    }
    mbar_wait(BAR(B_ORDY), L);
    {
      const uint4* src = P.g->o[bi][0][0][rh];
      rdy = 0;
      #pragma unroll 1
      for (int n = 0, q = 0; n < 16; q = w_next(n, q), n++) {
        const int j = wo_order(bc, n);
        if (((rdy >> (2 * j)) & 3) != 3) {
          do { rdy = __ballot_sync(0xffffffffu, ld_rlx(&P.g->flagO[bi][lane]) == tag); } while (((rdy >> (2 * j)) & 3) != 3);
          fence_async_glob();
        }
        if (n >= 2) mbar_wait(n < 6 ? BAR(B_HAFREE + (n >> 2)) : BAR(B_EMPTYW + q), n < 6 ? L : w_par(n - 6, q, L));
        if (n == THR_N) mbar_wait(BAR(B_OFREE), L);
        if (lane == 0) { mbar_expect_tx(BAR(B_FULLW + q), 16384); bulk_g2s_h(sb + w_off(q), src + j * 2048, 16384, BAR(B_FULLW + q)); }
      }
    }
    mbar_wait(BAR(B_OFREE), L);
  }
}

DEVI void ffn_prefetch(const Params& P, int q) {
  bulk_prefetch(q < 16 ? ((q & 1) ? P.wu : P.wg) + ((q >> 1) * 128 + blockIdx.x) * 3584 : P.wd + (min(FID, 111) * 8 + q - 16) * 4096, q < 16 ? 7168 : 8192);
}
DEVI void storer(const Params& P, uint32_t sb, int wg) {
  const int bid = uni(BID), bi = bid >> 4, rh = bid & 1, bc = (bid & 15) >> 1;
  const bool one = (threadIdx.x & 31) == 0;
  char* const g = (char*)P.g;
  const uint32_t tag0 = uni(((ld_rlx(&P.g->epoch) % 16383u) + 1u) << 2);
  #pragma unroll 1
  for (int L = 0; L < 2; L++) {
    const uint32_t tag = tag0 + L;
    if (wg) {
      #pragma unroll 1
      for (int r = threadIdx.x & 31; r < 256; r += 32) {
        uint4 v;
        do v = ld_ll(&P.g->statF[bi * 256 + r]); while (!__all_sync(0xffffffffu, v.w == tag));
        float var = __uint_as_float(v.y), c = rsqrtf(var + LN_EPS);
        if (L) { c += 1.f; c *= rsqrtf(fmaf(var * c, c, LN_EPS)); }
        const float mh = bf_round(__uint_as_float(v.x));
        sts64f(sb + PAR + r * 8, c, __uint_as_float(pack_bf16(mh, __uint_as_float(v.x) - mh)));
      }
      if (!L) mbar_wait(BAR(B_PAR), 0);
      warp_signal(BAR(B_ROW));
    }
    if (wg) { mbar_wait(BAR(B_KVRDY), L); mbar_wait(BAR(B_KVRDY + 2), L); const uint32_t t0 = clk(); while (clk() - t0 < KV_D) __nanosleep(40); }
    #pragma unroll 1
    for (int u = 0; u < 2 + 4 * wg; u++) {
      const int h = u < 2 ? u : u >> 2, hi = (u & 1) ^ 1;
      uint32_t src, dst, fl, b0, b1;
      if (u < 2) {
        src = (h ? KVB : KVA) + (3 - wg) * 16384; dst = offsetof(Scratch, kv) + (bid * 4 + h * 2 + wg) * 16384; fl = offsetof(Scratch, flagKV) + (bid * 32 + h * 2 + wg) * 4;
        b0 = BAR(B_KVRDY + ((u | wg) ? 1 : 0)); b1 = b0 + 16;
      } else {
        src = QO + (h * 2 + hi) * 8192; dst = offsetof(Scratch, o) + ((((bi * 2 + h) * 8 + bc) * 2 + hi) * 2 + rh) * 8192;
        fl = offsetof(Scratch, flagO) + (bi * 32 + h * 16 + (bid & 15)) * 4;
        b0 = BAR(B_ORDY + u - 2); b1 = b0 + 32;
      }
      mbar_wait(b0, L); mbar_wait(b1, L);
      fence_async_smem();
      PROFY(one && !L && u == 3 * wg, u ? 46 : 8);
      if (one && (u >= 2 || bi < 7)) bulk_s2g(g + dst, sb + src, u < 2 ? 16384 : 8192);
      if (one && u == 5) mbar_arrive(BAR(B_HAFREE + 1));
      if (u == 2 || u == 4) continue;
      bulk_wait<0>();
      PROFY(one && !L && u == 3 * wg, u ? 61 : 62);
      fence_rel();
      if (one) { st_rlx((unsigned*)(g + fl), tag); if (!wg || u > 2) mbar_arrive(BAR(B_HAFREE + h + (wg & h))); }
      PROFY(one && !L && (u > 2 || u == wg), u > 2 ? (u == 3 ? 38 : 54) : 32 + u);
    }
    if (L == 0) {
      char* dst = g + (offsetof(Scratch, x) + (bi * 16 + 2 * bc) * 32768 + rh * 16384);
      unsigned* f = (unsigned*)(g + (offsetof(Scratch, flagX) + (bi * 32 + bc * 4 + rh) * 4));
      const uint32_t a = sb + rh * 16384;
      if (wg == 0) {
        mbar_wait(BAR(B_XRDY), 0); mbar_wait(BAR(B_XRDY + 2), 0);
        fence_async_smem();
        PROFY(one, 41);
        if (one) bulk_s2g(dst, a, 16384);
        bulk_wait<0>();
        PROFY(one, 45);
        if (one) { mbar_arrive(BAR(B_XFREE)); mbar_arrive(BAR(B_PFREE)); }
        fence_rel();
        mbar_wait(BAR(B_XRDY + 1), 0); mbar_wait(BAR(B_XRDY + 3), 0);
        if (one) { st_rlx(f, tag); bulk_s2g(dst + 32768, a + 32768, 16384); }
        PROFY(one, 56);
        bulk_wait<0>();
        if (one) mbar_arrive(BAR(B_XFREE + 1));
        fence_rel();
        if (one) st_rlx(f + 2, tag);
        PROFY(one, 57);
      } else {
        mbar_wait(BAR(B_XRDY + 1), 0); mbar_wait(BAR(B_XRDY + 3), 0);
        mbar_wait(BAR(B_PFREE), 0);
        if (one) bulk_s2peer(a, 16384, BAR(B_FULLQ));
        { const uint32_t t0 = clk(); while (clk() - t0 < XD_D); }
        if (one) bulk_s2peer(a + 32768, 16384, BAR(B_FULLQ + 1));
      }
      if (wg == 0) {
        uint32_t t0 = clk() + PF1_D;
        #pragma unroll 1
        for (int q = PF1_S; q < PF1_E; q++) { while ((int)(clk() - t0) < 0) __nanosleep(50); if (one) ffn_prefetch(P, q); t0 += PF1_T; }
      }
    }
  }
}

DEVI void stg_issue(const Params& P, int c, uint32_t d, uint32_t du, uint32_t b) {
  mbar_expect_tx(b, 16384);
  if (c < 8) { tma_2d_h(d, &P.mWg, FID * 32, c * 128, b, POL_G); tma_2d_h(d + du, &P.mWu, FID * 32, c * 128, b, POL_U); }
  else if (c < 12) tma_3d_h(d, &P.mWd, 0, FID * 32 + (c - 8) * 8, 0, b, POL_D);
  else tma_2d_h(d, &P.mWp, (c - 12) * 1024 + (BID >> 2) * 32, (BID & 3) * 256, b, POL_EF);
}
DEVI void pace() { const uint32_t t0 = clk(); while (clk() - t0 < PACE_T); }
DEVI void stager(const Params& P, uint32_t sb) {
  {
    const int b = blockIdx.x;
    uint32_t t0 = clk();
    #pragma unroll 1
    for (int q = 0; q < PQ_N; q++) { bulk_prefetch(P.wqkv + (q * 128 + b) * 3072, 6144); while (clk() - t0 < PQ_T) __nanosleep(50); t0 += PQ_T; }
    bulk_prefetch(P.wo + b * 8192, 16384);
    #pragma unroll 1
    for (int q = 0; q < PF0_N; q++) {
      while (clk() - t0 < PF0_T) __nanosleep(50);
      t0 += PF0_T;
      ffn_prefetch(P, q);
    }
  }
  const int bid = BID, bi = bid >> 4, rh = bid & 1, bc = (bid & 15) >> 1;
  #pragma unroll 1
  for (int L = 0; L < 2; L++) {
    const int nch = L ? (FID < 112 ? 8 : 0) : 15;
    mbar_wait(BAR(B_PAR), L); mbar_wait(BAR(B_KVFULL + W0_BAR), L);
    #pragma unroll 1
    for (int n = 0, q = 0; n < 16; q = w_next(n, q), n++) {
      if (n >= 2) mbar_wait(n < 6 ? BAR(B_HAFREE + (n >> 2)) : BAR(B_EMPTYW + q), n < 6 ? L : w_par(n - 6, q, L));
      if (n == THR_N) mbar_wait(BAR(B_OFREE), L);
      mbar_expect_tx(BAR(B_FULLW + q), 16384);
      tma_5d(sb + w_off(q) + 16384, &P.mWo, 0, 0, n >> 3, 2 * (wo_order(bc, n) & 7), 2 * bc, BAR(B_FULLW + q), L ? POL_EF : POL_NORMAL);
      if (n == 13) {
        mbar_expect_tx(BAR(B_RES), 32768);
        #pragma unroll 1
        for (int e = 0; e < 2; e++) {
          mbar_wait(BAR(B_EMPTYW + 2 + e), 1);
          if (L) bulk_g2s_h(sb + e * 32768 + rh * 16384, P.g->x[bi][2 * bc + e] + rh * 1024, 16384, BAR(B_RES));
          else tma_2d_h(sb + e * 32768 + rh * 16384, &P.mXh, bc * 128 + e * 64, bi * 256 + rh * 128, BAR(B_RES), POL_EF);
        }
      }
    }
    if (L && nch) {
      const bf16* src = WDSRC2;
      mbar_expect_tx(BAR(B_FULLW + 2), 32768); mbar_expect_tx(BAR(B_FULLW + 2), 24576);
      #pragma unroll 1
      for (int e = 0; e < 3; e++) { bulk_g2s_h(sb + e * 32768 + (e < 2 ? (rh ^ 1) * 16384 : 0), src + e * 8192, e < 2 ? 16384 : 24576, BAR(B_FULLW + 2)); pace(); }
    }
    if (L == 0) { mbar_arrive_peer(BAR(B_PFREE)); mbar_wait(BAR(B_EMPTYW), 0); mbar_wait(BAR(B_EMPTYW + 1), 0); }
    #pragma unroll 1
    for (int c = FID < 112 ? 0 : 12, slot = 0; c < nch; c++, slot = slot == 2 ? 0 : slot + 1) {
      const int q = (c >> 1) + (c & 4) / 2;
      mbar_wait(L ? BAR(B_EMPTYW + q) : BAR(B_STGE + slot), L | ((0x71c7 >> c) & 1));
      #define CC c
      stg_issue(P, CC, L ? sb + w_off(q) + (c & 1) * 8192 : sb + STG + slot * 16384, 8192 << L, L ? BAR(B_FULLW + q) : BAR(B_STG + slot));
      if (L) pace();
    }
  }
}
DEVI void sum8(uint4 v, float& s1, float& s2) {
  float e[8] = {bf_lo(v.x), bf_hi(v.x), bf_lo(v.y), bf_hi(v.y), bf_lo(v.z), bf_hi(v.z), bf_lo(v.w), bf_hi(v.w)};
  #pragma unroll
  for (int q = 0; q < 8; q++) { s1 += e[q]; s2 = fmaf(e[q], e[q], s2); }
}
DEVI uint4 norm8(uint4 x, float m, float rs) {
  #define HN(v) pack_bf16((bf_lo(v) - m) * rs, (bf_hi(v) - m) * rs)
  return make_uint4(HN(x.x), HN(x.y), HN(x.z), HN(x.w));
  #undef HN
}
DEVI void put_f32(uint4 b, uint32_t d, uint32_t d2) {
  sts128(d, make_uint4(b.x << 16, b.x & 0xffff0000u, b.y << 16, b.y & 0xffff0000u));
  sts128(d + d2, make_uint4(b.z << 16, b.z & 0xffff0000u, b.w << 16, b.w & 0xffff0000u));
}
DEVI void put_bf16(uint4 b, uint32_t d) {
  sts64f(d, __uint_as_float(b.x), __uint_as_float(b.y)); sts64f(d + 1024, __uint_as_float(b.z), __uint_as_float(b.w));
  fence_async_smem();
}
DEVI uint4 best4(uint32_t p) {
  uint4 a = lds128(p), b = lds128(p + 16), c = lds128(p + 32), d = lds128(p + 48);
  if (b.x > a.x) a = b;
  if (d.x > c.x) c = d;
  return c.x > a.x ? c : a;
}
#define FL(x) __uint_as_float(x)
#define UI(x) __float_as_uint(x)
DEVI void aux(const Params& P, uint32_t sb) {
  int tid = fresh_tid();
  #define lane (tid & 31)
  #define wq (tid >> 5)
  uint32_t ids = P.map[blockIdx.x], tag;
  #define bid ((int)(ids & 255))
  #define fid ((int)(ids >> 8))
  #define bi (bid >> 4)
  #define bp (bid & 15)
  #define bc (bp >> 1)
  #define FRESH() do { tid = fresh_tid(); uint4 z_ = ldsv128(sb + INFO2 + 16); ids = z_.y; tag = z_.z + L; idx = z_.w; } while (0)
  {
    const uint32_t epoch = ld_rlx(&P.g->epoch);
    if (tid == 0) {
      mbar_expect_tx(BAR(B_STG), 49152);
      tma_3d(sb + STG, &P.mWq, bp * 64, bi * 128, 0, BAR(B_STG));
      tma_3d(sb + STG + 24576, &P.mWq, bp * 64, bi * 128 + 64, 0, BAR(B_STG));
    }
    __syncwarp();
    sts64f(sb + ONES + tid * 8, FL(0x3F803F80u), FL(0x3F803F80u));
    float s1 = 0.f, s2 = 0.f;
    { uint4 v = __ldg((const uint4*)P.wr + tid);
      if ((tid >> 4) == bc) put_f32(v, sb + WR + (tid & 15) * 32, 16);
      sum8(v, s1, s2);
      #pragma unroll 1
      for (int o = 16; o; o >>= 1) s1 += __shfl_xor_sync(0xffffffffu, s1, o);
      sts32f(sb + INFO2 + wq * 4, s1); }
    const uint4* src = (const uint4*)(P.x0 + (size_t)bid * 16384) + (tid >> 3) * 128 + (tid & 7);
    s1 = 0.f; s2 = 0.f;
    #pragma unroll 1
    for (int it = 0; it < 16; it += 4) {
      uint4 v0 = __ldg(src + it * 8), v1 = __ldg(src + it * 8 + 8), v2 = __ldg(src + it * 8 + 16), v3 = __ldg(src + it * 8 + 24);
      #pragma unroll 1
      for (int q = 0; q < 4; q++) { sum8(v0, s1, s2); v0 = v1; v1 = v2; v2 = v3; }
    }
    #pragma unroll 1
    for (int o = 1; o < 8; o <<= 1) { s1 += __shfl_xor_sync(0xffffffffu, s1, o); s2 += __shfl_xor_sync(0xffffffffu, s2, o); }
    tag = ((epoch % 16383u) + 1u) << 2;
    if (tid == 0) { sts128(sb + INFO, make_uint4(0x40000000u, 0u, tag, ((epoch % 127u) + 1u) << 1)); sts128(sb + INFO2 + 16, make_uint4(epoch, ids, tag, 0x40000000u)); }
    float m = s1 * (1.f / 1024.f);
    if ((tid & 7) == 0) st_ll(&P.g->statF[bid * 16 + (tid >> 3)], UI(m), UI(fmaxf(fmaf(-m, m, s2 * (1.f / 1024.f)), 0.f)), 0u, tag);
    bar_sync(2, 128);
    mbar_wait_b(BAR(B_STG), 0);
    if (tid < 96) {
      s1 = 0.f; s2 = 0.f;
      #pragma unroll 1
      for (int r = 0; r < 16; r++) {
        const uint32_t a = sb + STG + (r >> 3) * 24576 + wq * 8192 + (r & 7) * 128 + ((lane * 4) ^ ((r & 7) << 4));
        #pragma unroll
        for (int e = 0; e < 8; e++) { uint32_t v = lds32(a + e * 1024); s1 += bf_lo(v); s2 += bf_hi(v); }
      }
      st_ll(&P.g->csP[bp][bi][tid], UI(s1), UI(s2), 0u, tag);
      s1 = 0.f; s2 = 0.f;
      #pragma unroll 1
      for (int q = 0; q < 8; q += 2) {
        uint4 a, b; poll_ll2(&P.g->csP[bp][q][tid], &P.g->csP[bp][q + 1][tid], 0xffffffffu, tag, a, b);
        s1 += FL(a.x) + FL(b.x); s2 += FL(a.y) + FL(b.y);
      }
      const uint32_t hi = pack_bf16(-s1, -s2);
      sts32(sb + CS + (tid >> 2) * 32 + (tid & 3) * 4, hi);
      sts32(sb + CS + (tid >> 2) * 32 + (tid & 3) * 4 + 16, pack_bf16(-s1 - bf_lo(hi), -s2 - bf_hi(hi)));
    }
    fence_async_smem();
  }
  int idx;
  #pragma unroll 1
  for (int L = 0; L < 2; L++) {
    FRESH();
    {
      if ((unsigned)(bi - (idx >> 8)) < 2u) {
        const uint4* src = &P.g->patch[bp * 8 + (tid >> 6) * 4][tid & 63];
        uint4 v0, v1, v2, v3; int it = 0;
        do { v0 = ld_ll(src); v1 = ld_ll(src + 64); v2 = ld_ll(src + 128); v3 = ld_ll(src + 192); if (++it > SPIN_MAX) __trap(); }
        while (!__all_sync(0xffffffffu, v0.w == tag && v1.w == tag && v2.w == tag && v3.w == tag));
        float q = (FL(v0.x) + FL(v1.x)) + (FL(v2.x) + FL(v3.x)), k = (FL(v0.y) + FL(v1.y)) + (FL(v2.y) + FL(v3.y)), v = (FL(v0.z) + FL(v1.z)) + (FL(v2.z) + FL(v3.z));
        q += __shfl_xor_sync(0xffffffffu, q, 1); k += __shfl_xor_sync(0xffffffffu, k, 1); v += __shfl_xor_sync(0xffffffffu, v, 1);
        bar_sync(2, 128);
        const uint32_t d = sb + PATCH + (tid & ~1), kv = pack_bf16(k, v);
        sts16(d, pack_bf16(q * QSCALE, 0.f)); sts16(d + 128, kv); sts16(d + 256, kv >> 16);
      }
      sts32(sb + INFO, idx);
      bar_sync(2, 128);
    }
    const uint4 fix = lds128(sb + PATCH + 128 + (lane & 4) * 32 + (wq >> 1) * 64 + (lane & 3) * 16);
    warp_signal(BAR(B_PAR));
    PROFX(tid == 0, L ? 23 : 17);
    mbar_wait_b(BAR(B_KVFULL + wq), L);
    if ((idx >> 7) == bi * 2 - 1 - (wq & 1)) {
      if (lane < 8) sts128(sb + ((wq >> 1) ? KVB : KVA) + ((idx >> 6) & 3) * 8192 + (lane >> 2) * 4096 + (idx & 63) * 64 + (((lane ^ (idx >> 1)) & 3) << 4), fix);
      fence_async_smem();
    }
    bar_arrive(4 + wq, 160); bar_arrive(8 + wq, 160);
    FRESH();
    mbar_wait_b(BAR(B_OFREE), L);
    #define blk (bi * 2 + (bid & 1))
    if (tid < 33) st_ll(tid < 32 ? &P.g->row[blk][bc * 32 + tid] : &P.g->best[bc][blk], 0u, 0u, 0u, 0u);
    if (!L) {
        if (fid < 112) { st_ll(&P.g->yP[tid & ~1][fid][tid & 1], 0u, 0u, 0u, 0u); st_ll(&P.g->yP[tid | 1][fid][tid & 1], 0u, 0u, 0u, 0u); }
        if (tid < 80) st_ll(tid < 64 ? &P.g->patch[bid][tid] : &P.g->x2[(tid >> 1) & 7][2 * bid + (tid & 1)], 0u, 0u, 0u, 0u);
    }
    mbar_wait_b(BAR(B_XRDY + 1), L); mbar_wait_b(BAR(B_XRDY + 3), L);
    PROFX(tid == 0, 37 + L * 16);
    FRESH();
    {
      float s1 = 0.f, s2 = 0.f, d = 0.f;
      #pragma unroll 1
      for (int q = 0; q < 8; q += 4) {
        const uint4* src = &P.g->statP[q][blk * 128 + tid];
        uint4 v0, v1, v2, v3; int it = 0;
        do { v0 = ld_ll(src); v1 = ld_ll(src + 2048); v2 = ld_ll(src + 4096); v3 = ld_ll(src + 6144); if (++it > SPIN_MAX) __trap(); }
        while (!__all_sync(0xffffffffu, v0.w == tag && v1.w == tag && v2.w == tag && v3.w == tag));
        s1 += (FL(v0.x) + FL(v1.x)) + (FL(v2.x) + FL(v3.x)); s2 += (FL(v0.y) + FL(v1.y)) + (FL(v2.y) + FL(v3.y)); d += (FL(v0.z) + FL(v1.z)) + (FL(v2.z) + FL(v3.z));
      }
      PROFX(tid == 0, 39 + L * 16);
      uint4 a = lds128(sb + INFO2), b, c;
      float m = s1 * (1.f / 1024.f), var = fmaxf(fmaf(-m, m, s2 * (1.f / 1024.f)), 0.f), rs = rsqrtf(var + LN_EPS);
      uint32_t key = UI(fmaf(-m, (FL(a.x) + FL(a.y)) + (FL(a.z) + FL(a.w)), d) * rs);
      key ^= (uint32_t)((int)key >> 31) | 0x80000000u;
      uint32_t win = __ballot_sync(0xffffffffu, key == __reduce_max_sync(0xffffffffu, key));
      if (lane == __ffs(win) - 1) sts128(sb + RED + wq * 16, make_uint4(key, UI(m), UI(rs), (tag << 11) | (uint32_t)(blk * 128 + tid)));
      if (L) sts64f(sb + PAR + tid * 8, 1.f + rs, -m * rs);
      else if ((tid >> 4) == bc) st_ll(&P.g->statF[blk * 128 + tid], UI(m), UI(var), 0u, tag + 1);
      bar_sync(2, 128);
      if (wq == 0) {
        a = best4(sb + RED);
        float2 v = lds64f(sb + (lane >> 4) * 32768 + (a.w & 255) * 128 + (((lane & 15) * 8) ^ ((a.w & 7) << 4)));
        st_ll(&P.g->row[blk][bc * 32 + lane], UI(v.x), UI(v.y), 0u, tag);
        if (lane == 0) st_ll(&P.g->best[bc][blk], a.x, a.y, a.z, a.w);
        __syncwarp();
        if (lane < 2 + 2 * L) mbar_arrive(L ? BAR(B_PAR) : BAR(B_XFREE + lane));
      }
      PROFX(tid == 0, 18 + L * 6);
      FRESH();
      a = poll_ll(&P.g->best[bc][lane & 15], 0xfffff800u, tag << 11);
      win = __ffs(__ballot_sync(0xffffffffu, a.x == __reduce_max_sync(0xffffffffu, a.x))) - 1;
      idx = __shfl_sync(0xffffffffu, a.w, win) & 2047;
      PROFX(tid == 0, 19 + L * 6);
      poll_ll2(&P.g->row[win][tid], &P.g->row[win][tid + 128], 0xffffffffu, tag, c, b);
      c.z = b.x; c.w = b.y;
      a.x = __shfl_sync(0xffffffffu, a.x, win); a.y = __shfl_sync(0xffffffffu, a.y, win); a.z = __shfl_sync(0xffffffffu, a.z, win);
      sts32(sb + INFO2 + 28, idx);
      PROFX(tid == 0, 61 + L);
      b = norm8(c, FL(a.y), FL(a.z));
      if (L) put_bf16(b, sb + HV + tid * 8); else put_f32(b, sb + HV + tid * 16, 2048);
      if ((tid >> 1) == (bid & 63)) {
        sts128(sb + RED + 64 + (tid & 1) * 16, bid < 64 ? make_uint4(c.x, c.y, b.x, b.y) : make_uint4(c.z, c.w, b.z, b.w));
        sts32(sb + RED + 96, a.x);
      }
      bar_sync(2 + L, 128 + L * 256);
      if (L) {
        const int r0 = blk * 128 + (tid >> 4);
        uint32_t src = sb + ((tid >> 3) & 1) * 32768 + (r0 & 255) * 128 + (((tid ^ r0) & 7) << 4);
        uint4* dst = (uint4*)(P.out + (size_t)r0 * 1024 + bc * 128) + (tid & 15);
        #pragma unroll 4
        for (int it = 0; it < 16; it++) { uint4 v = lds128(src + it * 1024); if (idx - r0 != it * 8) dst[it * 1024] = v; }
      }
    }
    #pragma unroll 1
    for (int st = L; st < 2; st++) {
      FRESH();
      float a[8] = {0.f, 0.f, 0.f, 0.f, 0.f, 0.f, 0.f, 0.f};
      if (L == 0 && fid < 112) {
        uint32_t ha = st ? sb + RED + 768 : sb + HV + ((wq & 1) * 64 + (lane >> 2)) * 4;
        uint32_t ph = st ? 0x1cu : 0x171u, bar = st ? BAR(B_STG + 2) : BAR(B_STG);
        uint32_t wa = sb + STG + wq * 4096 + (st ? 32768 + lane * 16 : (lane ^ (lane >> 3)) * 16);
        const uint32_t hx = st ? 256 : 512;
        const bool lead = lane == 0;
        uint4 vc = make_uint4(0u, 0u, 0u, 0u); float hc = 0.f;
        #pragma unroll 1
        do {
          mbar_wait(bar, ph & 1);
          PROFX(lead && threadIdx.x == 256 && st == 0 && (ph > 255 || ph < 4), 40 - 23 + __clz(ph));
          #pragma unroll
          for (int n = 0; n < 8; n++) { const uint4 v = lds128(wa + n * 512); const float h = lds32f(ha + n * 32); fma8(a, vc, hc); vc = v; hc = h; }
          __syncwarp();
          if (lead) mbar_arrive(bar - 8 * (B_STG - B_STGE));
          const bool wrap = bar == BAR(B_STG + 2);
          bar += wrap ? -16 : 8; wa += wrap ? -32768 : 16384; ha += hx;
          ph >>= 1;
        } while (ph != 1);
        fma8(a, vc, hc);
      }
      FRESH();
      if (st == 1) {
        const uint32_t t8 = lds32(sb + INFO + 12) + L;
        if (L == 0 && fid < 112) {
          const bool odd = lane & 1;
          #pragma unroll
          for (int e = 0; e < 4; e++) { float z = __shfl_xor_sync(0xffffffffu, odd ? a[e] : a[4 + e], 1); if (odd) a[e] = z; else a[4 + e] = z; }
          uint4* dst = &P.g->yP[tid & ~1][fid][tid & 1];
          st_ll(dst, UI(a[0]), UI(a[1]), UI(a[2]), (UI(a[3]) & ~255u) | t8);
          st_ll(dst + 224, UI(a[4]), UI(a[5]), UI(a[6]), (UI(a[7]) & ~255u) | t8);
          PROFX(tid == 0, 21);
        }
        if (tid == 0) { uint32_t k = lds32(sb + RED + 96); sts32f(sb + RED + 100, bf_round(__fdividef(1.f, 1.f + __expf(-bf_round(FL(k ^ (~(uint32_t)((int)k >> 31) | 0x80000000u))))))); }
        uint4 v0, v1;
        poll_ll2(&P.g->yP[bid][0][min(tid, 111)], &P.g->yP[bid][0][min(tid, 111) + 112], 255u, t8, v0, v1);
        const float lo = (tid < 112 && !(tid & 1)) ? 1.f : 0.f, hi = (tid < 112 && (tid & 1)) ? 1.f : 0.f;
        const float y0 = FL(v0.x) + FL(v1.x), y1 = FL(v0.y) + FL(v1.y), y2 = FL(v0.z) + FL(v1.z), y3 = FL((v0.w & ~255u) | 128u) + FL((v1.w & ~255u) | 128u);
        a[0] = y0 * lo; a[1] = y1 * lo; a[2] = y2 * lo; a[3] = y3 * lo; a[4] = y0 * hi; a[5] = y1 * hi; a[6] = y2 * hi; a[7] = y3 * hi;
      }
      sts32f(sb + RED + 256 + wq * 128 + ((lane & 3) * 8 + (lane >> 2)) * 4, fold8(a));
      bar_sync(2, 128);
      const uint32_t d = sb + RED + 256 + lane * 4;
      float z0 = lds32f(d) + lds32f(d + 128), z1 = lds32f(d + 256) + lds32f(d + 384);
      if (st == 0) {
        sts32f(sb + RED + 768 + lane * 32 + wq * 4, swiglu(z0, z1));
        bar_sync(2, 128); PROFX(tid == 0, 20); continue; }
      z0 += z1;
      z0 += __shfl_xor_sync(0xffffffffu, z0, 8); z0 += __shfl_xor_sync(0xffffffffu, z0, 16);
      uint32_t xw = lds32(sb + RED + 64 + (lane & 4) * 4 + (lane & 2) * 2), hw = lds32(sb + RED + 72 + (lane & 4) * 4 + (lane & 2) * 2);
      z0 = bf_round(((lane & 1) ? bf_hi(hw) : bf_lo(hw)) + bf_round(bf_round(z0) * lds32f(sb + RED + 100))) + ((lane & 1) ? bf_hi(xw) : bf_lo(xw));
      uint32_t v = pack_bf16(z0, __shfl_down_sync(0xffffffffu, z0, 1)), v2 = __shfl_down_sync(0xffffffffu, v, 2);
      if (L) { if (tid == 0 || tid == 4) *(uint2*)(P.out + (size_t)idx * 1024 + bid * 8 + tid) = make_uint2(v, v2); PROFW(tid == 0, 28); }
      else if ((tid & 3) == 0 && tid < 64) st_ll(&P.g->x2[tid >> 3][2 * bid + ((tid >> 2) & 1)], v, v2, 0u, tag + 1);
    }
    if (L == 0) {
      PROFX(tid == 0, 22);
      FRESH();
      uint4 x, y; poll_ll2(&P.g->x2[bi][tid], &P.g->x2[bi][tid + 128], 0xffffffffu, tag + 1, x, y);
      x.z = y.x; x.w = y.y;
      if (wq == (bc & 3)) sts64f(sb + X2SEG + lane * 8, FL(bc < 4 ? x.x : x.z), FL(bc < 4 ? x.y : x.w));
      float s1 = 0.f, s2 = 0.f;
      sum8(x, s1, s2);
      #pragma unroll
      for (int o = 16; o; o >>= 1) { s1 += __shfl_xor_sync(0xffffffffu, s1, o); s2 += __shfl_xor_sync(0xffffffffu, s2, o); }
      sts64f(sb + RED + wq * 8, s1, s2);
      bar_sync(2, 128);
      y = lds128(sb + RED); uint4 y2 = lds128(sb + RED + 16);
      float m = ((FL(y.x) + FL(y.z)) + (FL(y2.x) + FL(y2.z))) * (1.f / 1024.f);
      put_bf16(norm8(x, m, rsqrtf(fmaxf(fmaf(-m, m, ((FL(y.y) + FL(y.w)) + (FL(y2.y) + FL(y2.w))) * (1.f / 1024.f)), 0.f) + LN_EPS)), sb + HV + tid * 8);
      mbar_wait(BAR(B_STG), 1); mbar_wait(BAR(B_STG + 1), 0); mbar_wait(BAR(B_STG + 2), 0);
      bar_sync(2, 128);
      PROFX(tid == 0, 30);
      float d0[4] = {0.f, 0.f, 0.f, 0.f}, d1[4] = {0.f, 0.f, 0.f, 0.f}, d2[4] = {0.f, 0.f, 0.f, 0.f};
      const uint32_t bd = (64 + (HV >> 4) + uni(bid & 3) * 32) | 0x10000u;
      #pragma unroll 1
      for (int ks = 0; ks < 8; ks++) {
        const uint32_t ad = (64 + (STG >> 4) + ks * 128) | (64u << 16);
        wg_fence();
        wgmma_ss_n8<0, 1>(d0, mkd<HI64>(ad), mkd<8>(bd + ks * 4), 1);
        wgmma_ss_n8<0, 1>(d1, mkd<HI64>(ad + 1024), mkd<8>(bd + ks * 4), 1);
        wgmma_ss_n8<0, 1>(d2, mkd<HI64>(ad + 2048), mkd<8>(bd + ks * 4), 1);
        wg_commit();
      }
      wg_wait<0>(); keep(d0); keep(d1); keep(d2);
      FRESH();
      if ((lane & 3) == (wq >> 1)) {
        uint4* dst = &P.g->patch[bid][(wq & 1) * 32 + (lane >> 2) * 2 + (wq >> 1)];
        st_ll(dst, UI(d0[0]), UI(d1[0]), UI(d2[0]), tag + 1); st_ll(dst + 16, UI(d0[2]), UI(d1[2]), UI(d2[2]), tag + 1);
      }
      PROFX(tid == 0, 31);
    }
  }
  if (bid == 0 && tid == 0) P.g->epoch = lds32(sb + INFO2 + 16) + 1;
  #undef blk
  #undef bid
  #undef fid
  #undef bi
  #undef bp
  #undef bc
  #undef FRESH
  #undef lane
  #undef wq
}

__global__ void __cluster_dims__(2, 1, 1) __launch_bounds__(512, 1) fused_kernel(const __grid_constant__ Params P) {
  extern __shared__ __align__(1024) uint8_t smem_raw[];
  const uint32_t sb = smem_u32(smem_raw);
  PROFT(threadIdx.x == 0, 0);
  if (threadIdx.x == 0) {
    for (int s = 0; s < 3; s++) mbar_init(BAR(B_FULLQ + s), 1);
    asm volatile("fence.mbarrier_init.release.cluster;" ::: "memory");
    #pragma unroll 1
    for (int s = 0; s < 3; s++) {
      mbar_expect_tx(BAR(B_FULLQ + s), 57344);
      tma_2d(sb + qa_off(s), &P.mX, s * 64, (BID >> 4) * 256, BAR(B_FULLQ + s));
      tma_3d(sb + qb_off(s), &P.mWq, (BID & 15) * 64, s * 64, 0, BAR(B_FULLQ + s));
    }
    if ((sb & 0x3FFFFu) != 1024) __trap();
  } else if (threadIdx.x == 480) {
    asm volatile("prefetch.tensormap [%0];" :: "l"(&P.mWq) : "memory");
  } else if (threadIdx.x >= 32 && !(threadIdx.x & 28) && (threadIdx.x >> 3) + (threadIdx.x & 3) <= B_COUNT + 1) {
    int b = (threadIdx.x >> 3) + (threadIdx.x & 3) - 1;
    if (b == B_COUNT) b = B_ROW;
    const uint32_t cnt = b < B_XFREE ? (b == B_OFREE ? 1 : 2) : (b < B_KVRDY ? 3 : (b < B_KVFULL || b == B_PAR ? 4 : (b == B_PFREE ? 2 : 1)));
    mbar_init(BAR(b), cnt);
    asm volatile("fence.mbarrier_init.release.cluster;" ::: "memory");
  }
  __syncthreads();
  asm volatile("barrier.cluster.arrive.relaxed.aligned;" ::: "memory");
  const int wg = __shfl_sync(0xffffffffu, threadIdx.x >> 7, 0);
  if (wg < 2) { reg_inc<224>(); consumer(P, sb, wg); }
  else if (wg == 2) { reg_dec<40>(); aux(P, sb); }
  else {
    reg_dec<24>();
    asm volatile("barrier.cluster.wait.aligned;" ::: "memory");
    const int w = __shfl_sync(0xffffffffu, (threadIdx.x >> 5) & 3, 0);
    if (w == 0) loader(P, sb);
    else if (w < 3) storer(P, sb, w - 1);
    else if ((threadIdx.x & 31) == 0) stager(P, sb);
  }
}

typedef CUresult (*EncFn)(CUtensorMap*, CUtensorMapDataType, cuuint32_t, void*, const cuuint64_t*, const cuuint64_t*, const cuuint32_t*, const cuuint32_t*,
                          CUtensorMapInterleave, CUtensorMapSwizzle, CUtensorMapL2promotion, CUtensorMapFloatOOBfill);
static void mk_map(EncFn enc, CUtensorMap* m, const void* ptr, int rank, const cuuint64_t* dims, const cuuint64_t* strides, const cuuint32_t* box,
                   CUtensorMapSwizzle sw, CUtensorMapL2promotion pr) {
  cuuint32_t es[5] = {1, 1, 1, 1, 1};
  enc(m, CU_TENSOR_MAP_DATA_TYPE_BFLOAT16, rank, (void*)ptr, dims, strides, box, es, CU_TENSOR_MAP_INTERLEAVE_NONE, sw, pr, CU_TENSOR_MAP_FLOAT_OOB_FILL_NONE);
}
extern "C" void kernel_launch(void* const* d_in, const int* in_sizes, int n_in, void* d_out, int out_size) {
  (void)in_sizes; (void)n_in; (void)out_size;
  void* fn = nullptr; cudaDriverEntryPointQueryResult q;
  cudaGetDriverEntryPoint("cuTensorMapEncodeTiled", &fn, cudaEnableDefault, &q);
  EncFn enc = (EncFn)fn;
  cudaFuncSetAttribute(fused_kernel, cudaFuncAttributeMaxDynamicSharedMemorySize, SMEM_BYTES);
  Params P;
  const CUtensorMapSwizzle S128 = CU_TENSOR_MAP_SWIZZLE_128B, S64 = CU_TENSOR_MAP_SWIZZLE_64B, S0 = CU_TENSOR_MAP_SWIZZLE_NONE;
  const CUtensorMapL2promotion L256 = CU_TENSOR_MAP_L2_PROMOTION_L2_256B, L128 = CU_TENSOR_MAP_L2_PROMOTION_L2_128B;
  { cuuint64_t d[2] = {1024, 2048}, s[1] = {2048}; cuuint32_t b[2] = {64, 256}, bh[2] = {64, 128};
    mk_map(enc, &P.mX, d_in[0], 2, d, s, b, S128, L256); mk_map(enc, &P.mXh, d_in[0], 2, d, s, bh, S128, L256); }
  { cuuint64_t d[3] = {1024, 1024, 3}, s[2] = {6144, 2048}; cuuint32_t b[3] = {64, 64, 3}; mk_map(enc, &P.mWq, d_in[1], 3, d, s, b, S128, L256); }
  { cuuint64_t d[5] = {64, 32, 2, 16, 16}, s[4] = {2048, 65536, 131072, 128}; cuuint32_t b[5] = {64, 32, 1, 2, 2}; mk_map(enc, &P.mWo, d_in[2], 5, d, s, b, S128, L256); }
  { cuuint64_t d[2] = {3584, 1024}, s[1] = {7168}; cuuint32_t b[2] = {32, 128};
    mk_map(enc, &P.mWg, d_in[5], 2, d, s, b, S64, L128); mk_map(enc, &P.mWu, d_in[6], 2, d, s, b, S64, L128); }
  { cuuint64_t d[2] = {3072, 1024}, s[1] = {6144}; cuuint32_t b[2] = {32, 256}; mk_map(enc, &P.mWp, d_in[1], 2, d, s, b, S64, L128); }
  { cuuint64_t d[3] = {256, 3584, 4}, s[2] = {2048, 512}; cuuint32_t b[3] = {256, 8, 4}; mk_map(enc, &P.mWd, d_in[7], 3, d, s, b, S0, L128); }
  P.x0 = (const bf16*)d_in[0]; P.wqkv = (const bf16*)d_in[1]; P.wo = (const bf16*)d_in[2]; P.wr = (const bf16*)d_in[4]; P.wg = (const bf16*)d_in[5]; P.wu = (const bf16*)d_in[6]; P.wd = (const bf16*)d_in[7];
  P.out = (bf16*)d_out;
  cudaGetSymbolAddress((void**)&P.g, g_scr);
  for (int b = 0; b < 128; b++) {
    int j = b >> 1, quad = j < 4 ? 0 : (j < 36 ? 1 + (j - 4) % 8 : 9 + (j - 36) % 7), pos = j < 4 ? j : (j < 36 ? (j - 4) / 8 : (j - 36) / 7);
    int bid = ((quad >> 2) * 2 + (pos >> 1)) * 16 + ((quad & 3) * 2 + (pos & 1)) * 2 + (b & 1);
    int e = pos * 2 + (b & 1), fid = e < 7 ? quad * 7 + e : 112 + quad;
    P.map[b] = bid | fid << 8;
  }
  fused_kernel<<<128, 512, SMEM_BYTES>>>(P);
}
```

```cpp
#include <cuda_runtime.h>
#include <cuda_bf16.h>
#include <cuda.h>
#include <stdint.h>
#include <stddef.h>
typedef __nv_bfloat16 bf16;

template<int TB, int TA = 0> __device__ __forceinline__ void wgmma_ss_n192(float (&d)[96], uint64_t da, uint64_t db, int scale_d) {
  asm volatile("{\n.reg .pred p;\nsetp.ne.b32 p, %98, 0;\n"
    "wgmma.mma_async.sync.aligned.m64n192k16.f32.bf16.bf16 {%0, %1, %2, %3, %4, %5, %6, %7, %8, %9, %10, %11, %12, %13, %14, %15, %16, %17, %18, %19, %20, %21, %22, %23, %24, %25, %26, %27, %28, %29, %30, %31, %32, %33, %34, %35, %36, %37, %38, %39, %40, %41, %42, %43, %44, %45, %46, %47, %48, %49, %50, %51, %52, %53, %54, %55, %56, %57, %58, %59, %60, %61, %62, %63, %64, %65, %66, %67, %68, %69, %70, %71, %72, %73, %74, %75, %76, %77, %78, %79, %80, %81, %82, %83, %84, %85, %86, %87, %88, %89, %90, %91, %92, %93, %94, %95}, %96, %97, p, 1, 1, %100, %99;\n}\n"
    : "+f"(d[0]), "+f"(d[1]), "+f"(d[2]), "+f"(d[3]), "+f"(d[4]), "+f"(d[5]), "+f"(d[6]), "+f"(d[7]), "+f"(d[8]), "+f"(d[9]), "+f"(d[10]), "+f"(d[11]), "+f"(d[12]), "+f"(d[13]), "+f"(d[14]), "+f"(d[15]), "+f"(d[16]), "+f"(d[17]), "+f"(d[18]), "+f"(d[19]), "+f"(d[20]), "+f"(d[21]), "+f"(d[22]), "+f"(d[23]), "+f"(d[24]), "+f"(d[25]), "+f"(d[26]), "+f"(d[27]), "+f"(d[28]), "+f"(d[29]), "+f"(d[30]), "+f"(d[31]), "+f"(d[32]), "+f"(d[33]), "+f"(d[34]), "+f"(d[35]), "+f"(d[36]), "+f"(d[37]), "+f"(d[38]), "+f"(d[39]), "+f"(d[40]), "+f"(d[41]), "+f"(d[42]), "+f"(d[43]), "+f"(d[44]), "+f"(d[45]), "+f"(d[46]), "+f"(d[47]), "+f"(d[48]), "+f"(d[49]), "+f"(d[50]), "+f"(d[51]), "+f"(d[52]), "+f"(d[53]), "+f"(d[54]), "+f"(d[55]), "+f"(d[56]), "+f"(d[57]), "+f"(d[58]), "+f"(d[59]), "+f"(d[60]), "+f"(d[61]), "+f"(d[62]), "+f"(d[63]), "+f"(d[64]), "+f"(d[65]), "+f"(d[66]), "+f"(d[67]), "+f"(d[68]), "+f"(d[69]), "+f"(d[70]), "+f"(d[71]), "+f"(d[72]), "+f"(d[73]), "+f"(d[74]), "+f"(d[75]), "+f"(d[76]), "+f"(d[77]), "+f"(d[78]), "+f"(d[79]), "+f"(d[80]), "+f"(d[81]), "+f"(d[82]), "+f"(d[83]), "+f"(d[84]), "+f"(d[85]), "+f"(d[86]), "+f"(d[87]), "+f"(d[88]), "+f"(d[89]), "+f"(d[90]), "+f"(d[91]), "+f"(d[92]), "+f"(d[93]), "+f"(d[94]), "+f"(d[95])
    : "l"(da), "l"(db), "r"(scale_d), "n"(TB), "n"(TA));
}

template<int TB> __device__ __forceinline__ void wgmma_rs_n192(float (&d)[96], uint32_t a0, uint32_t a1, uint32_t a2, uint32_t a3, uint64_t db, int scale_d) {
  asm volatile("{\n.reg .pred p;\nsetp.ne.b32 p, %101, 0;\n"
    "wgmma.mma_async.sync.aligned.m64n192k16.f32.bf16.bf16 {%0, %1, %2, %3, %4, %5, %6, %7, %8, %9, %10, %11, %12, %13, %14, %15, %16, %17, %18, %19, %20, %21, %22, %23, %24, %25, %26, %27, %28, %29, %30, %31, %32, %33, %34, %35, %36, %37, %38, %39, %40, %41, %42, %43, %44, %45, %46, %47, %48, %49, %50, %51, %52, %53, %54, %55, %56, %57, %58, %59, %60, %61, %62, %63, %64, %65, %66, %67, %68, %69, %70, %71, %72, %73, %74, %75, %76, %77, %78, %79, %80, %81, %82, %83, %84, %85, %86, %87, %88, %89, %90, %91, %92, %93, %94, %95}, {%96, %97, %98, %99}, %100, p, 1, 1, %102;\n}\n"
    : "+f"(d[0]), "+f"(d[1]), "+f"(d[2]), "+f"(d[3]), "+f"(d[4]), "+f"(d[5]), "+f"(d[6]), "+f"(d[7]), "+f"(d[8]), "+f"(d[9]), "+f"(d[10]), "+f"(d[11]), "+f"(d[12]), "+f"(d[13]), "+f"(d[14]), "+f"(d[15]), "+f"(d[16]), "+f"(d[17]), "+f"(d[18]), "+f"(d[19]), "+f"(d[20]), "+f"(d[21]), "+f"(d[22]), "+f"(d[23]), "+f"(d[24]), "+f"(d[25]), "+f"(d[26]), "+f"(d[27]), "+f"(d[28]), "+f"(d[29]), "+f"(d[30]), "+f"(d[31]), "+f"(d[32]), "+f"(d[33]), "+f"(d[34]), "+f"(d[35]), "+f"(d[36]), "+f"(d[37]), "+f"(d[38]), "+f"(d[39]), "+f"(d[40]), "+f"(d[41]), "+f"(d[42]), "+f"(d[43]), "+f"(d[44]), "+f"(d[45]), "+f"(d[46]), "+f"(d[47]), "+f"(d[48]), "+f"(d[49]), "+f"(d[50]), "+f"(d[51]), "+f"(d[52]), "+f"(d[53]), "+f"(d[54]), "+f"(d[55]), "+f"(d[56]), "+f"(d[57]), "+f"(d[58]), "+f"(d[59]), "+f"(d[60]), "+f"(d[61]), "+f"(d[62]), "+f"(d[63]), "+f"(d[64]), "+f"(d[65]), "+f"(d[66]), "+f"(d[67]), "+f"(d[68]), "+f"(d[69]), "+f"(d[70]), "+f"(d[71]), "+f"(d[72]), "+f"(d[73]), "+f"(d[74]), "+f"(d[75]), "+f"(d[76]), "+f"(d[77]), "+f"(d[78]), "+f"(d[79]), "+f"(d[80]), "+f"(d[81]), "+f"(d[82]), "+f"(d[83]), "+f"(d[84]), "+f"(d[85]), "+f"(d[86]), "+f"(d[87]), "+f"(d[88]), "+f"(d[89]), "+f"(d[90]), "+f"(d[91]), "+f"(d[92]), "+f"(d[93]), "+f"(d[94]), "+f"(d[95])
    : "r"(a0), "r"(a1), "r"(a2), "r"(a3), "l"(db), "r"(scale_d), "n"(TB));
}

template<int TB, int TA = 0> __device__ __forceinline__ void wgmma_ss_n128(float (&d)[64], uint64_t da, uint64_t db, int scale_d) {
  asm volatile("{\n.reg .pred p;\nsetp.ne.b32 p, %66, 0;\n"
    "wgmma.mma_async.sync.aligned.m64n128k16.f32.bf16.bf16 {%0, %1, %2, %3, %4, %5, %6, %7, %8, %9, %10, %11, %12, %13, %14, %15, %16, %17, %18, %19, %20, %21, %22, %23, %24, %25, %26, %27, %28, %29, %30, %31, %32, %33, %34, %35, %36, %37, %38, %39, %40, %41, %42, %43, %44, %45, %46, %47, %48, %49, %50, %51, %52, %53, %54, %55, %56, %57, %58, %59, %60, %61, %62, %63}, %64, %65, p, 1, 1, %68, %67;\n}\n"
    : "+f"(d[0]), "+f"(d[1]), "+f"(d[2]), "+f"(d[3]), "+f"(d[4]), "+f"(d[5]), "+f"(d[6]), "+f"(d[7]), "+f"(d[8]), "+f"(d[9]), "+f"(d[10]), "+f"(d[11]), "+f"(d[12]), "+f"(d[13]), "+f"(d[14]), "+f"(d[15]), "+f"(d[16]), "+f"(d[17]), "+f"(d[18]), "+f"(d[19]), "+f"(d[20]), "+f"(d[21]), "+f"(d[22]), "+f"(d[23]), "+f"(d[24]), "+f"(d[25]), "+f"(d[26]), "+f"(d[27]), "+f"(d[28]), "+f"(d[29]), "+f"(d[30]), "+f"(d[31]), "+f"(d[32]), "+f"(d[33]), "+f"(d[34]), "+f"(d[35]), "+f"(d[36]), "+f"(d[37]), "+f"(d[38]), "+f"(d[39]), "+f"(d[40]), "+f"(d[41]), "+f"(d[42]), "+f"(d[43]), "+f"(d[44]), "+f"(d[45]), "+f"(d[46]), "+f"(d[47]), "+f"(d[48]), "+f"(d[49]), "+f"(d[50]), "+f"(d[51]), "+f"(d[52]), "+f"(d[53]), "+f"(d[54]), "+f"(d[55]), "+f"(d[56]), "+f"(d[57]), "+f"(d[58]), "+f"(d[59]), "+f"(d[60]), "+f"(d[61]), "+f"(d[62]), "+f"(d[63])
    : "l"(da), "l"(db), "r"(scale_d), "n"(TB), "n"(TA));
}

template<int TB, int TA = 0> __device__ __forceinline__ void wgmma_ss_n64(float (&d)[32], uint64_t da, uint64_t db, int scale_d) {
  asm volatile("{\n.reg .pred p;\nsetp.ne.b32 p, %34, 0;\n"
    "wgmma.mma_async.sync.aligned.m64n64k16.f32.bf16.bf16 {%0, %1, %2, %3, %4, %5, %6, %7, %8, %9, %10, %11, %12, %13, %14, %15, %16, %17, %18, %19, %20, %21, %22, %23, %24, %25, %26, %27, %28, %29, %30, %31}, %32, %33, p, 1, 1, %36, %35;\n}\n"
    : "+f"(d[0]), "+f"(d[1]), "+f"(d[2]), "+f"(d[3]), "+f"(d[4]), "+f"(d[5]), "+f"(d[6]), "+f"(d[7]), "+f"(d[8]), "+f"(d[9]), "+f"(d[10]), "+f"(d[11]), "+f"(d[12]), "+f"(d[13]), "+f"(d[14]), "+f"(d[15]), "+f"(d[16]), "+f"(d[17]), "+f"(d[18]), "+f"(d[19]), "+f"(d[20]), "+f"(d[21]), "+f"(d[22]), "+f"(d[23]), "+f"(d[24]), "+f"(d[25]), "+f"(d[26]), "+f"(d[27]), "+f"(d[28]), "+f"(d[29]), "+f"(d[30]), "+f"(d[31])
    : "l"(da), "l"(db), "r"(scale_d), "n"(TB), "n"(TA));
}

template<int TB, int TA = 0> __device__ __forceinline__ void wgmma_ss_n8(float (&d)[4], uint64_t da, uint64_t db, int scale_d) {
  asm volatile("{\n.reg .pred p;\nsetp.ne.b32 p, %6, 0;\n"
    "wgmma.mma_async.sync.aligned.m64n8k16.f32.bf16.bf16 {%0, %1, %2, %3}, %4, %5, p, 1, 1, %8, %7;\n}\n"
    : "+f"(d[0]), "+f"(d[1]), "+f"(d[2]), "+f"(d[3])
    : "l"(da), "l"(db), "r"(scale_d), "n"(TB), "n"(TA));
}

template<int TB> __device__ __forceinline__ void wgmma_rs_n40(float (&d)[20], uint32_t a0, uint32_t a1, uint32_t a2, uint32_t a3, uint64_t db, int scale_d) {
  asm volatile("{\n.reg .pred p;\nsetp.ne.b32 p, %25, 0;\n"
    "wgmma.mma_async.sync.aligned.m64n40k16.f32.bf16.bf16 {%0, %1, %2, %3, %4, %5, %6, %7, %8, %9, %10, %11, %12, %13, %14, %15, %16, %17, %18, %19}, {%20, %21, %22, %23}, %24, p, 1, 1, %26;\n}\n"
    : "+f"(d[0]), "+f"(d[1]), "+f"(d[2]), "+f"(d[3]), "+f"(d[4]), "+f"(d[5]), "+f"(d[6]), "+f"(d[7]), "+f"(d[8]), "+f"(d[9]), "+f"(d[10]), "+f"(d[11]), "+f"(d[12]), "+f"(d[13]), "+f"(d[14]), "+f"(d[15]), "+f"(d[16]), "+f"(d[17]), "+f"(d[18]), "+f"(d[19])
    : "r"(a0), "r"(a1), "r"(a2), "r"(a3), "l"(db), "r"(scale_d), "n"(TB));
}

#define DEVI __device__ __forceinline__
DEVI uint32_t smem_u32(const void* p) { return (uint32_t)__cvta_generic_to_shared(p); }
DEVI void mbar_init(uint32_t bar, uint32_t cnt) { asm volatile("mbarrier.init.shared::cta.b64 [%0], %1;" :: "r"(bar), "r"(cnt)); }
DEVI void mbar_expect_tx(uint32_t bar, uint32_t bytes) { asm volatile("mbarrier.arrive.expect_tx.shared::cta.b64 _, [%0], %1;" :: "r"(bar), "r"(bytes) : "memory"); }
DEVI void mbar_arrive(uint32_t bar) { asm volatile("mbarrier.arrive.shared::cta.b64 _, [%0];" :: "r"(bar) : "memory"); }
DEVI void mbar_arrive_peer(uint32_t bar) {
  asm volatile("{\n.reg .b32 ra;\nmapa.shared::cluster.u32 ra, %0, %1;\nmbarrier.arrive.shared::cluster.b64 _, [ra];\n}" :: "r"(bar), "r"((blockIdx.x & 1) ^ 1) : "memory");
}
DEVI void bulk_s2peer(uint32_t a, uint32_t bytes, uint32_t bar) {
  asm volatile("{\n.reg .b32 ra, rb;\nmapa.shared::cluster.u32 ra, %0, %3;\nmapa.shared::cluster.u32 rb, %2, %3;\n"
               "cp.async.bulk.shared::cluster.shared::cta.mbarrier::complete_tx::bytes [ra], [%0], %1, [rb];\n}"
               :: "r"(a), "r"(bytes), "r"(bar), "r"((blockIdx.x & 1) ^ 1) : "memory");
}
DEVI void mbar_wait(uint32_t bar, uint32_t parity) {
  asm volatile("{\n.reg .pred p;\nLW:\nmbarrier.try_wait.parity.shared::cta.b64 p, [%0], %1;\n@!p bra LW;\n}" :: "r"(bar), "r"(parity) : "memory");
}
DEVI uint32_t mbar_test(uint32_t bar, uint32_t parity) {
  uint32_t r; asm volatile("{\n.reg .pred p;\nmbarrier.test_wait.parity.shared::cta.b64 p, [%1], %2;\nselp.u32 %0, 1, 0, p;\n}" : "=r"(r) : "r"(bar), "r"(parity) : "memory"); return r;
}
DEVI void mbar_wait_b(uint32_t bar, uint32_t parity) {
  asm volatile("{\n.reg .pred p;\n.reg .u32 it;\nmov.u32 it, 0;\nLW:\nmbarrier.try_wait.parity.shared::cta.b64 p, [%0], %1;\n@p bra LD;\n"
               "add.u32 it, it, 1;\nsetp.lt.u32 p, it, 0x1000000;\n@p bra LW;\ntrap;\nLD:\n}" :: "r"(bar), "r"(parity) : "memory");
}
DEVI void tma_2d(uint32_t dst, const CUtensorMap* m, int c0, int c1, uint32_t bar) {
  asm volatile("cp.async.bulk.tensor.2d.shared::cluster.global.mbarrier::complete_tx::bytes [%0], [%1, {%3, %4}], [%2];"
    :: "r"(dst), "l"(m), "r"(bar), "r"(c0), "r"(c1) : "memory");
}
DEVI void tma_3d(uint32_t dst, const CUtensorMap* m, int c0, int c1, int c2, uint32_t bar) {
  asm volatile("cp.async.bulk.tensor.3d.shared::cluster.global.mbarrier::complete_tx::bytes [%0], [%1, {%3, %4, %5}], [%2];"
    :: "r"(dst), "l"(m), "r"(bar), "r"(c0), "r"(c1), "r"(c2) : "memory");
}
#define POL_EF POL_FIRST
constexpr uint64_t POL_FIRST = 0x12F0000000000000ull, POL_NORMAL = 0x1000000000000000ull;
DEVI void tma_2d_h(uint32_t dst, const CUtensorMap* m, int c0, int c1, uint32_t bar, uint64_t pol) {
  asm volatile("cp.async.bulk.tensor.2d.shared::cluster.global.mbarrier::complete_tx::bytes.L2::cache_hint [%0], [%1, {%3, %4}], [%2], %5;"
    :: "r"(dst), "l"(m), "r"(bar), "r"(c0), "r"(c1), "l"(pol) : "memory");
}
DEVI void tma_3d_h(uint32_t dst, const CUtensorMap* m, int c0, int c1, int c2, uint32_t bar, uint64_t pol) {
  asm volatile("cp.async.bulk.tensor.3d.shared::cluster.global.mbarrier::complete_tx::bytes.L2::cache_hint [%0], [%1, {%3, %4, %5}], [%2], %6;"
    :: "r"(dst), "l"(m), "r"(bar), "r"(c0), "r"(c1), "r"(c2), "l"(pol) : "memory");
}
DEVI void bulk_g2s_h(uint32_t s, const void* g, uint32_t bytes, uint32_t bar, uint64_t pol = POL_EF) {
  asm volatile("cp.async.bulk.shared::cluster.global.mbarrier::complete_tx::bytes.L2::cache_hint [%0], [%1], %2, [%3], %4;"
    :: "r"(s), "l"(g), "r"(bytes), "r"(bar), "l"(pol) : "memory");
}
DEVI void tma_5d(uint32_t dst, const CUtensorMap* m, int c0, int c1, int c2, int c3, int c4, uint32_t bar, uint64_t pol) {
  asm volatile("cp.async.bulk.tensor.5d.shared::cluster.global.mbarrier::complete_tx::bytes.L2::cache_hint [%0], [%1, {%3, %4, %5, %6, %7}], [%2], %8;"
    :: "r"(dst), "l"(m), "r"(bar), "r"(c0), "r"(c1), "r"(c2), "r"(c3), "r"(c4), "l"(pol) : "memory");
}
DEVI void tma_prefetch_2d(const CUtensorMap* m, int c0, int c1) {
  asm volatile("cp.async.bulk.prefetch.tensor.2d.L2.global.tile [%0, {%1, %2}];" :: "l"(m), "r"(c0), "r"(c1) : "memory");
}
DEVI void tma_prefetch_3d(const CUtensorMap* m, int c0, int c1, int c2) {
  asm volatile("cp.async.bulk.prefetch.tensor.3d.L2.global.tile [%0, {%1, %2, %3}];" :: "l"(m), "r"(c0), "r"(c1), "r"(c2) : "memory");
}
DEVI void bulk_prefetch(const void* g, uint32_t bytes) { asm volatile("cp.async.bulk.prefetch.L2.global [%0], %1;" :: "l"(g), "r"(bytes) : "memory"); }
DEVI void bulk_g2s(uint32_t s, const void* g, uint32_t bytes, uint32_t bar) {
  asm volatile("cp.async.bulk.shared::cluster.global.mbarrier::complete_tx::bytes [%0], [%1], %2, [%3];" :: "r"(s), "l"(g), "r"(bytes), "r"(bar) : "memory");
}
DEVI void bulk_s2g(void* g, uint32_t s, uint32_t bytes) {
  asm volatile("cp.async.bulk.global.shared::cta.bulk_group [%0], [%1], %2;\ncp.async.bulk.commit_group;" :: "l"(g), "r"(s), "r"(bytes) : "memory");
}
template<int N> DEVI void bulk_wait() { asm volatile("cp.async.bulk.wait_group %0;" :: "n"(N) : "memory"); }
DEVI void fence_async_smem() { asm volatile("fence.proxy.async.shared::cta;" ::: "memory"); }
DEVI void fence_async_glob() { asm volatile("fence.proxy.async.global;" ::: "memory"); }
DEVI unsigned ld_rlx(const unsigned* p) { unsigned v; asm volatile("ld.relaxed.gpu.global.u32 %0, [%1];" : "=r"(v) : "l"(p) : "memory"); return v; }
DEVI void st_rlx(unsigned* p, unsigned v) { asm volatile("st.relaxed.gpu.global.u32 [%0], %1;" :: "l"(p), "r"(v) : "memory"); }
DEVI uint2 ldg_stream(const uint2* p) { uint2 v; asm volatile("ld.global.nc.L1::no_allocate.v2.u32 {%0, %1}, [%2];" : "=r"(v.x), "=r"(v.y) : "l"(p)); return v; }
DEVI void fence_rel() { asm volatile("fence.release.gpu;" ::: "memory"); }
DEVI uint4 ld_ll(const uint4* p) {
  uint4 v;
  asm volatile("{\n.reg .b128 t;\n.reg .b64 a, b;\nld.relaxed.gpu.global.b128 t, [%4];\nmov.b128 {a, b}, t;\nmov.b64 {%0, %1}, a;\nmov.b64 {%2, %3}, b;\n}"
               : "=r"(v.x), "=r"(v.y), "=r"(v.z), "=r"(v.w) : "l"(p) : "memory");
  return v;
}
DEVI void st_ll(uint4* p, uint32_t x, uint32_t y, uint32_t z, uint32_t w) {
  asm volatile("{\n.reg .b128 t;\n.reg .b64 a, b;\nmov.b64 a, {%1, %2};\nmov.b64 b, {%3, %4};\nmov.b128 t, {a, b};\nst.relaxed.gpu.global.b128 [%0], t;\n}"
               :: "l"(p), "r"(x), "r"(y), "r"(z), "r"(w) : "memory");
}
#define SPIN_MAX 0x1000000
DEVI uint4 poll_ll(const uint4* p, uint32_t mask, uint32_t tag) {
  uint4 v; int it = 0;
  do { v = ld_ll(p); if (++it > SPIN_MAX) __trap(); } while (!__all_sync(0xffffffffu, (v.w & mask) == tag));
  return v;
}
DEVI void poll_ll2(const uint4* p, const uint4* q, uint32_t mask, uint32_t tag, uint4& a, uint4& b) {
  int it = 0;
  do { a = ld_ll(p); b = ld_ll(q); if (++it > SPIN_MAX) __trap(); } while (!__all_sync(0xffffffffu, (a.w & mask) == tag && (b.w & mask) == tag));
}
DEVI void bar_sync(int id, int n) { asm volatile("bar.sync %0, %1;" :: "r"(id), "r"(n) : "memory"); }
DEVI void bar_arrive(int id, int n) { asm volatile("bar.arrive %0, %1;" :: "r"(id), "r"(n) : "memory"); }
DEVI void wg_fence() { asm volatile("wgmma.fence.sync.aligned;" ::: "memory"); }
DEVI void wg_commit() { asm volatile("wgmma.commit_group.sync.aligned;" ::: "memory"); }
template<int N> DEVI void wg_wait() { asm volatile("wgmma.wait_group.sync.aligned %0;" :: "n"(N) : "memory"); }
template<int N> DEVI void reg_inc() { asm volatile("setmaxnreg.inc.sync.aligned.u32 %0;" :: "n"(N)); }
template<int N> DEVI void reg_dec() { asm volatile("setmaxnreg.dec.sync.aligned.u32 %0;" :: "n"(N)); }
DEVI float ex2f(float x) { float y; asm("ex2.approx.ftz.f32 %0, %1;" : "=f"(y) : "f"(x)); return y; }
DEVI uint32_t pack_bf16(float lo, float hi) { uint32_t r; asm("cvt.rn.bf16x2.f32 %0, %1, %2;" : "=r"(r) : "f"(hi), "f"(lo)); return r; }
DEVI float bf_lo(uint32_t v) { return __uint_as_float(v << 16); }
DEVI float bf_hi(uint32_t v) { return __uint_as_float(v & 0xffff0000u); }
DEVI float bf_round(float x) { return bf_lo(pack_bf16(x, 0.f)); }
DEVI void stsm_x4(uint32_t addr, uint32_t a, uint32_t b, uint32_t c, uint32_t d) {
  asm volatile("stmatrix.sync.aligned.m8n8.x4.shared.b16 [%0], {%1,%2,%3,%4};" :: "r"(addr), "r"(a), "r"(b), "r"(c), "r"(d) : "memory");
}
DEVI void ldsm_x4(uint32_t addr, uint32_t& a, uint32_t& b, uint32_t& c, uint32_t& d) {
  asm volatile("ldmatrix.sync.aligned.m8n8.x4.shared.b16 {%0,%1,%2,%3}, [%4];" : "=r"(a), "=r"(b), "=r"(c), "=r"(d) : "r"(addr) : "memory");
}
DEVI uint4 lds128(uint32_t a) { uint4 v; asm volatile("ld.shared.v4.u32 {%0,%1,%2,%3}, [%4];" : "=r"(v.x), "=r"(v.y), "=r"(v.z), "=r"(v.w) : "r"(a) : "memory"); return v; }
DEVI void sts128(uint32_t a, uint4 v) { asm volatile("st.shared.v4.u32 [%0], {%1,%2,%3,%4};" :: "r"(a), "r"(v.x), "r"(v.y), "r"(v.z), "r"(v.w) : "memory"); }
DEVI float2 lds64f(uint32_t a) { float2 v; asm volatile("ld.shared.v2.f32 {%0,%1}, [%2];" : "=f"(v.x), "=f"(v.y) : "r"(a) : "memory"); return v; }
DEVI void sts64f(uint32_t a, float x, float y) { asm volatile("st.shared.v2.f32 [%0], {%1,%2};" :: "r"(a), "f"(x), "f"(y) : "memory"); }
DEVI uint32_t lds32(uint32_t a) { uint32_t v; asm volatile("ld.shared.u32 %0, [%1];" : "=r"(v) : "r"(a) : "memory"); return v; }
DEVI float lds32f(uint32_t a) { return __uint_as_float(lds32(a)); }
DEVI void sts32(uint32_t a, uint32_t v) { asm volatile("st.shared.u32 [%0], %1;" :: "r"(a), "r"(v) : "memory"); }
DEVI void sts32f(uint32_t a, float v) { sts32(a, __float_as_uint(v)); }
DEVI void sts16(uint32_t a, uint32_t v) { asm volatile("st.shared.u16 [%0], %1;" :: "r"(a), "h"((unsigned short)v) : "memory"); }
template<int N> DEVI void keep(float (&d)[N]) {
  #pragma unroll
  for (int i = 0; i < N; i++) asm volatile("" : "+f"(d[i]) :: "memory");
}
template<int N> DEVI void keep(uint32_t (&d)[N]) {
  #pragma unroll
  for (int i = 0; i < N; i++) asm volatile("" : "+r"(d[i]) :: "memory");
}
template<uint32_t HI> DEVI uint64_t mkd(uint32_t lo) { uint64_t r; asm("mov.b64 %0, {%1, %2};" : "=l"(r) : "r"(lo), "n"(HI)); return r; }
constexpr uint32_t HI128 = (1u << 30) | (1024 >> 4), HI64 = (2u << 30) | (512 >> 4);
#define VOFF(x) ((uint32_t)(x) * (uint32_t)(1 - 65536))
DEVI bool elect() { uint32_t p; asm volatile("{\n.reg .pred q;\nelect.sync _|q, 0xffffffff;\nselp.u32 %0, 1, 0, q;\n}" : "=r"(p)); return p; }
DEVI void warp_signal(uint32_t bar) { __syncwarp(); if (elect()) mbar_arrive(bar); }

struct Scratch {
  uint4 kv[128][4][1024];
  uint4 o[8][2][8][2][1024];
  uint4 x[8][16][2048];
  uint4 zero[1024];
  uint4 statP[8][2048];
  uint4 statF[2048];
  uint4 csP[16][8][96];
  uint4 best[8][16];
  uint4 row[16][256];
  uint4 yP[128][112][2];
  uint4 x2[8][256];
  uint4 patch[128][64];
  unsigned flagKV[128][32];
  unsigned flagO[8][32];
  unsigned flagX[8][32];
  unsigned epoch;
};
__device__ __align__(1024) Scratch g_scr;
#define PROFT(cond, slot)
#define PROFW(cond, slot)
#define PROFD(cond, slot)
#define PROFX(cond, slot)
#define PROFY(cond, slot)

constexpr uint32_t SB0 = 65536, HOLE = 90112, SA2 = 98304, SB1 = 131072, SB2 = 155648, STG = 180224;
constexpr uint32_t KVA = 0, KVB = 98304, QO = 65536;
constexpr uint32_t MISC = 229376, CS = MISC, ONES = MISC + 768, BARS = MISC + 1792, INFO = MISC + 2208, WR = MISC + 2224, X2SEG = MISC + 2736, INFO2 = MISC + 2992, DUMP = MISC + 3040;
constexpr uint32_t PAR = HOLE, HV = HOLE + 2048, RED = HOLE + 6144, PATCH = 196608;
constexpr uint32_t SMEM_BYTES = 232448;
enum { B_FULLQ = 0, B_EMPTYQ = 3, B_FULLW = 6, B_EMPTYW = 12, B_HAFREE = 18, B_OFREE = 20,
       B_XFREE = 21,
       B_KVRDY = 23, B_ORDY = 27, B_XRDY = 35, B_STGE = 39,
       B_KVFULL = 42, B_RES = 46, B_PAR = 47, B_STG = 48, B_PFREE = 51, B_COUNT = 52,
       B_ROW = 154 };
#define BAR(x) (sb + BARS + 8 * (x))
DEVI uint32_t qa_off(int s) { return s == 2 ? SA2 : (uint32_t)s * 32768u; }
DEVI uint32_t qb_off(int s) { return s == 0 ? SB0 : (s == 1 ? SB1 : SB2); }
DEVI int kb_order(int bc, int n) {
  const int e = n < 9 ? n - 2 : n - 9;
  return n < 2 ? 2 * bc + n : 2 * (((e < 4 ? e + 4 : e - 4 + (e - 4 >= (bc & 3))) + (bc & 4)) & 7) + (n >= 9);
}
DEVI int wo_order(int bc, int n) { return (n & 8) | ((n + (bc & 6)) & 7); }
DEVI uint32_t w_off(int s) { return (uint32_t)((0x431065 >> (4 * s)) & 7) * 32768u; }
DEVI uint32_t w_par(int n, int s, int L) { return ((n >= 6 && n < 12) ^ (!(s & 2) && L)); }
DEVI int w_next(int n, int s) { return s == 5 ? 0 : (n == 13 ? 4 : s + 1); }

struct Params {
  CUtensorMap mX, mXh, mWq, mWo, mWg, mWu, mWp, mWd;
  const bf16 *x0, *wqkv, *wo, *wr, *wg, *wu, *wd;
  bf16* out;
  Scratch* g;
  unsigned map[128];
};
#define BID ((int)(P.map[blockIdx.x] & 255))
#define FID ((int)(P.map[blockIdx.x] >> 8))
DEVI uint32_t uni(uint32_t v) { return __shfl_sync(0xffffffffu, v, 0); }
#define PQ_N 8
#define PQ_T 700
#define PF0_N 10
#define PF0_T 1600
#define PF1_E 24
#define PF1_T 1100
#define POL_Q1 POL_NORMAL
#define POL_X POL_NORMAL
#define PFA0_BAR 3
#define PFA1_BAR 0
#define PFA0_M 0
#define PFA1_M 0
#define PFA0_T 900
#define PFA1_T 700
#define PF1_S PF0_N
#define PF1_D 0
#define POL_G POL_NORMAL
#define POL_U POL_FIRST
#define POL_D POL_FIRST
#define JQ_N 6
#define WDSRC (P.wd + (size_t)min(fid, 111) * 32768)
#define WDSRC2 (P.wd + FID * 32768)
#define WD_N 4
#define THR_N 6
#define KV_D 1800
#define XD_D 300
#define W0_BAR 3
#define QEF_N 99
#define PACE_T 300
#define IDLE_T 11000
#define POL_Q0 POL_NORMAL
constexpr float LN_EPS = 1e-5f;
constexpr float QSCALE = 0.17677669529663687f * 1.4426950408889634f;

DEVI void fma8(float (&a)[8], uint4 v, float h) {
  a[0] = fmaf(bf_lo(v.x), h, a[0]); a[1] = fmaf(bf_hi(v.x), h, a[1]); a[2] = fmaf(bf_lo(v.y), h, a[2]); a[3] = fmaf(bf_hi(v.y), h, a[3]);
  a[4] = fmaf(bf_lo(v.z), h, a[4]); a[5] = fmaf(bf_hi(v.z), h, a[5]); a[6] = fmaf(bf_lo(v.w), h, a[6]); a[7] = fmaf(bf_hi(v.w), h, a[7]);
}
DEVI uint4 ldsv128(uint32_t a) { uint4 v; asm volatile("ld.volatile.shared.v4.u32 {%0,%1,%2,%3}, [%4];" : "=r"(v.x), "=r"(v.y), "=r"(v.z), "=r"(v.w) : "r"(a) : "memory"); return v; }
DEVI float ldsv32f(uint32_t a) { float v; asm volatile("ld.volatile.shared.f32 %0, [%1];" : "=f"(v) : "r"(a) : "memory"); return v; }
DEVI uint32_t clk() { uint32_t t; asm volatile("mov.u32 %0, %%clock;" : "=r"(t)); return t; }
DEVI int fresh_tid() { int t; asm volatile("mov.u32 %0, %%tid.x;" : "=r"(t)); return t & 127; }
DEVI float fold8(const float (&a)[8]) {
  const int lane = threadIdx.x & 31;
  const bool u = lane & 16, v = lane & 8, x = lane & 4;
  float b0 = (u ? a[4] : a[0]) + __shfl_xor_sync(0xffffffffu, u ? a[0] : a[4], 16), b1 = (u ? a[5] : a[1]) + __shfl_xor_sync(0xffffffffu, u ? a[1] : a[5], 16);
  float b2 = (u ? a[6] : a[2]) + __shfl_xor_sync(0xffffffffu, u ? a[2] : a[6], 16), b3 = (u ? a[7] : a[3]) + __shfl_xor_sync(0xffffffffu, u ? a[3] : a[7], 16);
  float c0 = (v ? b2 : b0) + __shfl_xor_sync(0xffffffffu, v ? b0 : b2, 8), c1 = (v ? b3 : b1) + __shfl_xor_sync(0xffffffffu, v ? b1 : b3, 8);
  return (x ? c1 : c0) + __shfl_xor_sync(0xffffffffu, x ? c0 : c1, 4);
}
DEVI float swiglu(float g, float u) { g = bf_round(g); return bf_round(bf_round(__fdividef(g, 1.f + __expf(-g))) * bf_round(u)); }

DEVI void qk_issue(float (&s)[32], uint32_t qd, uint32_t kd) {
  wgmma_ss_n64<0>(s, mkd<HI64>(qd), mkd<HI64>(kd), 0);
  wgmma_ss_n64<0>(s, mkd<HI64>(qd + 2), mkd<HI64>(kd + 2), 1);
}
template<int J0, int J1> DEVI void exp_pack(const float (&s)[32], uint32_t (&p)[16]) {
  #pragma unroll
  for (int j = J0; j < J1; j++) p[j] = pack_bf16(ex2f(s[2 * j]), ex2f(s[2 * j + 1]));
}
DEVI bool attn_pack(const float (&o)[20], uint32_t (&ob)[8]) {
  const float lo = 5.421010862427522e-20f, hi = 1.8446744073709552e19f;
  float i0, i1; asm("rcp.approx.ftz.f32 %0, %1;" : "=f"(i0) : "f"(o[16])); asm("rcp.approx.ftz.f32 %0, %1;" : "=f"(i1) : "f"(o[18]));
  #pragma unroll
  for (int e = 0; e < 8; e++) ob[e] = pack_bf16(o[2 * e] * ((e & 1) ? i1 : i0), o[2 * e + 1] * ((e & 1) ? i1 : i0));
  return __all_sync(0xffffffffu, o[16] >= lo && o[16] <= hi && o[18] >= lo && o[18] <= hi);
}
DEVI void attn_store(const uint32_t (&ob)[8], bool ok, uint32_t st, uint32_t sb, uint32_t bar) {
  stsm_x4(ok ? st : sb + DUMP, ob[0], ob[1], ob[2], ob[3]); stsm_x4(ok ? st ^ 32 : sb + DUMP, ob[4], ob[5], ob[6], ob[7]);
  __syncwarp();
  asm volatile("{\n.reg .pred p, q;\nelect.sync _|q, 0xffffffff;\nsetp.ne.and.u32 p, %1, 0, q;\n@p mbarrier.arrive.shared::cta.b64 _, [%0];\n}" :: "r"(bar), "r"((uint32_t)ok) : "memory");
}
DEVI void attn_exact(uint32_t st, uint32_t kv, int t, bool hasprev, uint32_t bar) {
  const int lane = threadIdx.x & 31;
  #pragma unroll 1
  for (int row = ((threadIdx.x >> 5) & 3) * 16, n = 0; n < 16; n++, row++) {
    const int k1 = 256 + t * 64 + row;
    float m = -INFINITY, l = 0.f, o = 0.f;
    #pragma unroll 1
    for (int k0 = hasprev ? k1 - 255 : 256; k0 <= k1; k0 += 32) {
      const int k = min(k0 + lane, k1), r = k & 63;
      float sc = 0.f;
      #pragma unroll 1
      for (int c = 0; c < 16; c++) {
        uint32_t a = lds32(st + row * 64 + ((c * 4) ^ ((row & 6) << 3))), b = lds32(kv + (k >> 6) * 8192 + r * 64 + ((c * 4) ^ ((r & 6) << 3)));
        sc = fmaf(bf_lo(a), bf_lo(b), fmaf(bf_hi(a), bf_hi(b), sc));
      }
      float mn = fmaxf(m, sc);
      #pragma unroll 1
      for (int x = 16; x; x >>= 1) mn = fmaxf(mn, __shfl_xor_sync(0xffffffffu, mn, x));
      const float al = ex2f(m - mn), pr = ex2f(sc - mn);
      m = mn; l *= al; o *= al;
      #pragma unroll 1
      for (int q = k0; q <= min(k0 + 31, k1); q++) {
        const float z = __shfl_sync(0xffffffffu, pr, q - k0);
        uint32_t b = lds32(kv + (q >> 6) * 8192 + 4096 + (q & 63) * 64 + (((lane >> 1) * 4) ^ ((q & 6) << 3)));
        l += z; o = fmaf(z, (lane & 1) ? bf_hi(b) : bf_lo(b), o);
      }
    }
    __syncwarp();
    sts16(st + row * 64 + ((lane * 2) ^ ((row & 6) << 3)), pack_bf16(__fdividef(o, l), 0.f));
  }
  warp_signal(bar);
}

template<int K0, int K1, int DONE = 0> DEVI void exp_pv(const float (&s)[32], uint32_t (&p)[16], float (&o)[20], uint32_t vd, bool accum) {
  #pragma unroll
  for (int ks = K0; ks < K1; ks++) {
    if (ks >= DONE) {
      #pragma unroll
      for (int j = 4 * ks; j < 4 * ks + 4; j++) p[j] = pack_bf16(ex2f(s[2 * j]), ex2f(s[2 * j + 1]));
    }
    asm volatile("" : "+r"(p[4 * ks]), "+r"(p[4 * ks + 1]), "+r"(p[4 * ks + 2]), "+r"(p[4 * ks + 3]));
    wg_fence();
    wgmma_rs_n40<1>(o, p[ks * 4], p[ks * 4 + 1], p[ks * 4 + 2], p[ks * 4 + 3], mkd<HI64>(vd + VOFF(ks * 64)), ks ? 1 : accum);
  }
}
DEVI void exp_pv2(const float (&s)[32], const float (&sx)[32], uint32_t (&p)[16], uint32_t (&px)[16], float (&o)[20], uint32_t v0, uint32_t v4,
                  const uint32_t (&msk)[9], int tdiag) {
  #pragma unroll
  for (int ks = 0; ks < 4; ks++) {
    #pragma unroll
    for (int j = 4 * ks; j < 4 * ks + 4; j++) {
      const int c = 8 * (j >> 1) - 8 * (j & 1);
      const uint32_t e = pack_bf16(ex2f(c > tdiag ? s[2 * j] : sx[2 * j]), ex2f(c + 1 > tdiag ? s[2 * j + 1] : sx[2 * j + 1])), m = msk[(j >> 1) - (j & 1) + 1];
      p[j] = e & m; px[j] = e & ~m;
      asm volatile("" : "+r"(p[j]), "+r"(px[j]));
    }
    wg_fence();
    wgmma_rs_n40<1>(o, p[ks * 4], p[ks * 4 + 1], p[ks * 4 + 2], p[ks * 4 + 3], mkd<HI64>(v0 + VOFF(ks * 64)), 1);
    wgmma_rs_n40<1>(o, px[ks * 4], px[ks * 4 + 1], px[ks * 4 + 2], px[ks * 4 + 3], mkd<HI64>(v4 + VOFF(ks * 64)), 1);
  }
}

template<int J0> DEVI void qkv_store(const float (&a)[96], float p0, float p1, uint32_t d) {
  #pragma unroll
  for (int hh = 0; hh < 2; hh++) {
    const int j = 4 * (J0 + 2 * hh);
    stsm_x4(d ^ (hh << 5), pack_bf16(a[j] * p0, a[j + 1] * p0), pack_bf16(a[j + 2] * p1, a[j + 3] * p1),
                           pack_bf16(a[j + 4] * p0, a[j + 5] * p0), pack_bf16(a[j + 6] * p1, a[j + 7] * p1));
  }
}
DEVI void mean_step(float (&a)[96], float m0, float m1, uint32_t cd, bool z) {
  const uint32_t u0 = z ? 0u : __float_as_uint(m0), u1 = z ? 0u : __float_as_uint(m1);
  uint32_t ma[4] = {__byte_perm(u0, 0u, 0x1010), __byte_perm(u1, 0u, 0x1010), __byte_perm(u0, 0u, 0x3232), __byte_perm(u1, 0u, 0x3232)};
  keep(ma);
  wg_fence();
  wgmma_rs_n192<1>(a, ma[0], ma[1], ma[2], ma[3], mkd<2>(cd), 1);
  wg_commit();
}

template<bool FIRST> DEVI void qkv_block(float (&aX)[96], float (&aY)[96], uint32_t sb16, int s, int tX, int tY) {
  uint32_t a16 = sb16 + (qa_off(s) >> 4), b16 = (sb16 + (qb_off(s) >> 4)) | ((8192u >> 4) << 16);
  uint32_t ax = (a16 + tX * 512) | 0x10000u, ay = (a16 + tY * 512) | 0x10000u;
  wg_fence();
  #pragma unroll
  for (int ks = 0; ks < 4; ks++) {
    wgmma_ss_n192<1>(aX, mkd<HI128>(ax + ks * 2), mkd<HI128>(b16 + ks * 128), !(FIRST && ks == 0));
    wgmma_ss_n192<1>(aY, mkd<HI128>(ay + ks * 2), mkd<HI128>(b16 + ks * 128), !(FIRST && ks == 0));
  }
  wg_commit();
}
DEVI void qkv_half(float (&a)[96], uint32_t sb16, int t, uint32_t sa, uint32_t sbb) {
  wg_fence();
  #pragma unroll
  for (int ks = 0; ks < 4; ks++)
    wgmma_ss_n192<1>(a, mkd<HI128>(((sb16 + (sa >> 4) + t * 512) | 0x10000u) + ks * 2), mkd<HI128>(((sb16 + (sbb >> 4)) | ((8192u >> 4) << 16)) + ks * 128), 1);
  wg_commit();
}
template<bool FIRST> DEVI void wo_block(float (&acc)[64], uint32_t sb16, int s, int wg) {
  uint32_t a16 = (sb16 + (w_off(s) >> 4) + wg * 256) | 0x10000u, b16 = (sb16 + (w_off(s) >> 4) + 1024) | ((8192u >> 4) << 16);
  wg_fence();
  #pragma unroll
  for (int ks = 0; ks < 4; ks++)
    wgmma_ss_n128<1>(acc, mkd<HI64>(a16 + (ks >> 1) * 512 + (ks & 1) * 2), mkd<HI128>(b16 + ks * 128), !(FIRST && ks == 0));
  wg_commit();
}
DEVI void consumer(const Params& P, uint32_t sb, int wg) {
  const int w = uni((threadIdx.x >> 5) & 3);
  #define LAYER uni(mbar_test(BAR(B_RES), 0))
  #define IDS L = LAYER; const int tid = fresh_tid(), lane = tid & 31
  const uint32_t ids = uni(P.map[blockIdx.x]);
  const int bi = (ids >> 4) & 7, rh = ids & 1, bc = (ids & 15) >> 1, fid = ids >> 8;
  const int tX = 3 - wg, tY = wg;
  constexpr uint32_t sb16 = 1024 >> 4;
  #pragma unroll 1
  while (true) {
    int L = LAYER;
    {
      float aX[96], aY[96];
      const bool lead = fresh_tid() == 0;
      if (L) mbar_wait(BAR(B_XRDY + wg * 2 + 1), 0);
      mbar_wait(BAR(B_FULLQ), 0);
      PROFW(threadIdx.x == 0, L * 8 + 1);
      qkv_block<true>(aX, aY, sb16, 0, tX, tY);
      #pragma unroll 1
      for (int n = 1, s = 1, ps = 0, ph = 0; n < 14; n++) {
        mbar_wait(BAR(B_FULLQ + s), ph ^ (s ? L : 0));
        PROFD(threadIdx.x == 0 && L && (n == 2 || n == 3 || n == 7 || n == 11 || n == 13), n == 2 ? 48 : 49 + (n >> 2));
        qkv_block<false>(aX, aY, sb16, s, tX, tY);
        wg_wait<1>(); if (lead) mbar_arrive(BAR(B_EMPTYQ + ps));
        ps = s; if (s == 2) { s = 0; ph ^= 1; } else s++;
      }
      mbar_wait(BAR(B_FULLQ + 2), L);
      qkv_half(aX, sb16, tX, SA2, SB2);
      mbar_wait(BAR(B_ROW), L);
      IDS;
      const uint32_t pa = sb + PAR + (w * 16 + (lane >> 2)) * 8;
      float2 p0 = lds64f(pa + tX * 512), p1 = lds64f(pa + tX * 512 + 64), p2 = lds64f(pa + tY * 512), p3 = lds64f(pa + tY * 512 + 64);
      mean_step(aX, p0.y, p1.y, sb16 + (CS >> 4), lane & 3);
      mbar_wait(BAR(B_FULLQ), 1);
      qkv_half(aX, sb16, tX, 0, SB0);
      wg_wait<3>(); if (lead) mbar_arrive(BAR(B_EMPTYQ + 1));
      bar_sync(1, 256);
      qkv_half(aY, sb16, tY, SA2, SB2);
      wg_wait<1>(); keep(aX);
      const int srow = w * 16 + (lane & 15);
      const uint32_t x0 = sb + srow * 64 + (((lane >> 4) ^ ((srow >> 1) & 3)) << 4), xX = x0 + (4 + tX) * 8192, xY = x0 + (4 + tY) * 8192;
      qkv_store<8>(aX, p0.x, p1.x, xX + KVA); qkv_store<16>(aX, p0.x, p1.x, xX + KVA + 4096);
      warp_signal(BAR(B_KVRDY + wg * 2));
      qkv_half(aY, sb16, tY, 0, SB0);
      mean_step(aY, p2.y, p3.y, sb16 + (CS >> 4), fresh_tid() & 3);
      wg_wait<2>(); if (lead) mbar_arrive(BAR(B_EMPTYQ + 2));
      mbar_wait(BAR(B_EMPTYQ + 2), L);
      qkv_store<12>(aX, p0.x, p1.x, xX + KVB); qkv_store<20>(aX, p0.x, p1.x, xX + KVB + 4096);
      wg_wait<0>(); keep(aY);
      if (lead) mbar_arrive(BAR(B_EMPTYQ));
      PROFW(threadIdx.x == 0, L * 8 + 2);
      qkv_store<8>(aY, p2.x, p3.x, xY + KVA); qkv_store<16>(aY, p2.x, p3.x, xY + KVA + 4096);
      qkv_store<12>(aY, p2.x, p3.x, xY + KVB); qkv_store<20>(aY, p2.x, p3.x, xY + KVB + 4096);
      warp_signal(BAR(B_KVRDY + wg * 2 + 1));
      p0.x *= QSCALE; p1.x *= QSCALE; p2.x *= QSCALE; p3.x *= QSCALE;
      mbar_wait(BAR(B_EMPTYQ), 1);
      qkv_store<0>(aX, p0.x, p1.x, x0 + QO + tX * 4096);
      qkv_store<0>(aY, p2.x, p3.x, x0 + QO + tY * 4096); qkv_store<4>(aY, p2.x, p3.x, x0 + QO + 16384 + tY * 4096);
      mbar_wait(BAR(B_PAR), L);
      qkv_store<4>(aX, p0.x, p1.x, x0 + QO + 16384 + tX * 4096);
      const int prow = (int)uni(lds32(sb + INFO)) - bi * 256;
      if ((prow >> 4) == tX * 4 + w || (prow >> 4) == tY * 4 + w) {
        __syncwarp();
        if (lane < 24) sts128(sb + (prow & 63) * 64 + (((lane ^ (prow >> 1)) & 3) << 4) +
                              (lane < 8 ? QO + (lane >> 2) * 16384 + (prow >> 6) * 4096 : ((lane & 4) ? KVB : KVA) + (4 + (prow >> 6)) * 8192 + (lane >> 4) * 4096),
                              lds128(sb + PATCH + lane * 16));
      }
      fence_async_smem();
      bar_sync(1, 256);
    }
    PROFW(threadIdx.x == 0, L * 8 + 3);
    {
      IDS;
      float s0[32], s1[32], sx[32], o[20], op[20];
      uint32_t p0[16], p1[16], px[16], msk[9];
      const int tdiag = w * 16 + (lane >> 2) - 2 * (lane & 3);
      #pragma unroll
      for (int e = 0; e < 9; e++) msk[e] = ((8 * e - 8 > tdiag) ? 0xFFFFu : 0u) | ((8 * e - 7 > tdiag) ? 0xFFFF0000u : 0u);
      keep(msk);
      const uint32_t ones = (sb16 + (ONES >> 4)) << 16;
      const uint32_t qX = (sb16 + (QO >> 4) + tX * 256) | 0x10000u, qY = (sb16 + (QO >> 4) + tY * 256) | 0x10000u;
      const uint32_t kXB = (sb16 + (KVB >> 4) + tX * 512) | 0x10000u;
      uint32_t redo = 0;
      const uint32_t ost = sb + QO + (w * 16 + (lane & 15)) * 64 + (((lane >> 4) ^ ((lane >> 1) & 3)) << 4);
      #define QK(s, q, k) do { wg_fence(); qk_issue(s, q, k); wg_commit(); } while (0)
      #define QK2(q, k) do { wg_fence(); qk_issue(s1, q, k); qk_issue(sx, q, (k) + 2048); wg_commit(); } while (0)
      #define VB(v, b) ((v) + VOFF((b) * 512))
      QK(s0, qX + 1024, kXB + 1536);
      #pragma unroll
      for (int e = 0; e < 20; e++) o[e] = 0.f;
      wg_wait<0>(); keep(s0);
      #pragma unroll 1
      for (int h = 1; h >= 0; h--) {
        const uint32_t kXA = kXB - ((KVB - KVA) >> 4), kX = h ? kXB : kXA, vX = VOFF((kX & 0xffffu) + 256) + ones;
        QK(s1, qX + h * 1024, kX + 1024);
        #pragma unroll
        for (int e = 0; e < 20; e++) op[e] = o[e];
        keep(op);
        exp_pv<0, 4>(s0, p0, o, VB(vX, 3), false); wg_commit();
        wg_wait<1>(); keep(s1);
        exp_pv<0, 2>(s1, p1, o, VB(vX, 2), true);
        bar_sync(h ? 12 + wg : 4 + wg * 4, h ? 128 : 160);
        QK(s0, qX, kXA + 512 + h * 1024);
        exp_pv<2, 4>(s1, p1, o, VB(vX, 2), true); wg_commit();
        wg_wait<0>(); keep(s0); keep(p0); keep(p1); keep(o);
      }
      #pragma unroll 1
      for (int h = 0; h < 2; h++) {
        const uint32_t kb16 = sb16 + ((h ? KVB : KVA) >> 4), kY = (kb16 + tY * 512) | 0x10000u, qy = qY + h * 1024;
        const uint32_t onesP = bi ? ones : (kb16 + 1984) << 16;
        const uint32_t vX = VOFF(kb16 + tX * 512 + 256), vY = VOFF(kb16 + tY * 512 + 256);
        uint32_t ob[8];
        QK2(qX + h * 1024, (kb16 + tX * 512) | 0x10000u);
        exp_pv<0, 4>(s0, p0, o, VB(vX + (wg ? onesP : ones), 1), true); wg_commit();
        wg_wait<1>(); keep(s1); keep(sx);
        QK(s0, qy, kY + 1536);
        exp_pv2(s1, sx, p1, px, o, vX + onesP, VB(vX + ones, 4), msk, tdiag); wg_commit();
        wg_wait<1>(); keep(s0); keep(p0);
        QK(s1, qy, kY + 1024);
        exp_pack<0, 4>(s0, p0);
        wg_wait<1>(); keep(o); keep(p1); keep(px);
        bool ok = attn_pack(o, ob); keep(ob);
        exp_pv<0, 4, 1>(s0, p0, o, VB(vY + (wg ? ones : onesP), 3), false); wg_commit();
        attn_store(ob, ok, ost + (h * 4 + tX) * 4096, sb, BAR(B_ORDY + wg * 4 + h * 2)); redo |= ok ? 0u : 1u << (h * 2);
        wg_wait<1>(); keep(s1);
        exp_pv<0, 2>(s1, p1, o, VB(vY + onesP, 2), true);
        bar_sync(5 + wg * 4 + h * 2, 160);
        QK(s0, qy, kY + 512);
        exp_pv<2, 4>(s1, p1, o, VB(vY + onesP, 2), true); wg_commit();
        wg_wait<1>(); keep(s0); keep(p0);
        QK2(qy, kY);
        exp_pv<0, 4>(s0, p0, o, VB(vY + onesP, 1), true); wg_commit();
        wg_wait<1>(); keep(s1); keep(sx); keep(p1);
        bar_sync(6 + wg * 4, h ? 128 : 160);
        QK(s0, h ? qy : qX + 1024, kXB + 512);
        exp_pv2(s1, sx, p1, px, o, vY + onesP, VB(vY + ones, 4), msk, tdiag); wg_commit();
        wg_wait<0>(); keep(o); keep(s0); keep(p0); keep(p1); keep(px);
        ok = attn_pack(o, ob); attn_store(ob, ok, ost + (h * 4 + tY) * 4096, sb, BAR(B_ORDY + wg * 4 + h * 2 + 1)); redo |= ok ? 0u : 2u << (h * 2);
        #pragma unroll
        for (int e = 0; e < 20; e++) o[e] = op[e];
      }
      #undef QK
      #undef QK2
      #undef VB
      if (redo) {
        #pragma unroll 1
        for (int u = 0; u < 4; u++) if ((redo >> u) & 1) {
          const int h = u >> 1, t = (u & 1) ? tY : tX;
          attn_exact(sb + QO + (h * 4 + t) * 4096, sb + (h ? KVB : KVA), t, bi > 0, BAR(B_ORDY + wg * 4 + u));
        }
      }
    }
    PROFW(threadIdx.x == 0, L * 8 + 4);
    {
      IDS;
      const int t256 = wg * 128 + tid;
      float acc[64];
      const int tt = wg ^ rh;
      const int grow = bi * 256 + rh * 128 + tt * 64 + w * 16 + (lane >> 2);
      float al0 = 1.f, be0 = 0.f, al1 = 1.f, be1 = 0.f;
      const int idx0 = (int)uni(lds32(sb + INFO));
      const uint32_t tag = lds32(sb + INFO + 8) + L;
      uint4* const sp = &P.g->statP[bc][grow + (lane & 1) * 8];
      uint4* const yp = &P.g->yP[t256 >> 1][min(fid, 111)][t256 & 1];
      mbar_wait(BAR(B_FULLW), L);
      PROFW(t256 == 0, L * 8 + 5);
      wo_block<true>(acc, sb16, 0, tt);
      if (!(lane & 2)) st_ll(sp, 0u, 0u, 0u, 0u);
      uint4 fa = make_uint4(0u, 0u, 0u, 0u), fb = fa;
      uint2 wd[4];
      if (L) {
        fa = ld_ll(&P.g->statF[grow]); fb = ld_ll(&P.g->statF[grow + 8]);
      }
      #pragma unroll
      for (int e = 0; e < 4; e++) { wd[e] = make_uint2(0u, 0u); if (L) wd[e] = ldg_stream((const uint2*)(WDSRC) + t256 + (28 + e) * 256); }
      #pragma unroll 1
      for (int n = 1, q = 1, pq = 0; n < 16; n++) {
        mbar_wait(BAR(B_FULLW + q), w_par(n, q, L));
        PROFD(t256 == 0 && !L && (n == 4 || n == 7 || n == 8 || n == 12), (n == 7 ? 63 : 41 + (n >> 2)));
        wo_block<false>(acc, sb16, q, tt);
        wg_wait<1>(); if (tid == 0) mbar_arrive(BAR(B_EMPTYW + pq));
        pq = q; q = w_next(n, q);
      }
      if (L) {
        float r0 = rsqrtf(__uint_as_float(fa.y) + LN_EPS), r1 = rsqrtf(__uint_as_float(fb.y) + LN_EPS);
        if (grow != idx0) { al0 = 1.f + r0; be0 = -__uint_as_float(fa.x) * r0; }
        if (grow + 8 != idx0) { al1 = 1.f + r1; be1 = -__uint_as_float(fb.x) * r1; }
      }
      mbar_wait(BAR(B_RES), L);
      const int srow = tt * 64 + w * 16 + (lane & 15);
      const uint32_t ra = sb + rh * 16384 + srow * 128, sw = ((lane >> 4) ^ (srow & 7)) << 4;
      if ((idx0 >> 4) == bi * 16 + rh * 8 + tt * 4 + w) {
        int r = idx0 & 127;
        if (lane < 16) sts128(sb + (lane >> 3) * 32768 + rh * 16384 + r * 128 + (((lane & 7) ^ (r & 7)) << 4), lds128(sb + X2SEG + lane * 16));
        __syncwarp();
      }
      uint32_t rs[32];
      #pragma unroll
      for (int jj = 0; jj < 8; jj++) ldsm_x4((ra + (jj >> 2) * 32768) + (sw ^ ((jj & 3) << 5)), rs[4 * jj], rs[4 * jj + 1], rs[4 * jj + 2], rs[4 * jj + 3]);
      float rf[64];
      #pragma unroll
      for (int e = 0; e < 32; e++) { rf[2 * e] = fmaf(bf_lo(rs[e]), (e & 1) ? al1 : al0, (e & 1) ? be1 : be0); rf[2 * e + 1] = fmaf(bf_hi(rs[e]), (e & 1) ? al1 : al0, (e & 1) ? be1 : be0); }
      keep(rf);
      mbar_wait(BAR(B_RES), L);
      wg_wait<0>(); keep(acc);
      if (tid == 0) mbar_arrive(BAR(B_EMPTYW + 5));
      PROFW(t256 == 0, L * 8 + 6);
      #pragma unroll
      for (int jj = 0; jj < 8; jj++) {
        float* a = acc + 8 * jj;
        #pragma unroll
        for (int e = 0; e < 8; e++) a[e] += rf[8 * jj + e];
        stsm_x4((ra + (jj >> 2) * 32768) + (sw ^ ((jj & 3) << 5)), pack_bf16(a[0], a[1]), pack_bf16(a[2], a[3]), pack_bf16(a[4], a[5]), pack_bf16(a[6], a[7]));
        if (jj == 7) fence_async_smem();
        if ((jj & 3) == 3) warp_signal(BAR(B_XRDY + wg * 2 + (jj >> 2)));
      }
      {
        float s1a = 0.f, s2a = 0.f, da = 0.f, s1b = 0.f, s2b = 0.f, db = 0.f;
        #pragma unroll
        for (int j = 0; j < 16; j++) {
          const float* a = acc + 4 * j; float2 wv = lds64f(sb + WR + j * 32 + (lane & 3) * 8);
          s1a += a[0] + a[1]; s1b += a[2] + a[3];
          s2a = fmaf(a[0], a[0], s2a); s2b = fmaf(a[2], a[2], s2b); s2a = fmaf(a[1], a[1], s2a); s2b = fmaf(a[3], a[3], s2b);
          da = fmaf(a[0], wv.x, da); db = fmaf(a[2], wv.x, db); da = fmaf(a[1], wv.y, da); db = fmaf(a[3], wv.y, db);
        }
        bool odd = lane & 1;
        float u1 = (odd ? s1b : s1a) + __shfl_xor_sync(0xffffffffu, odd ? s1a : s1b, 1);
        float u2 = (odd ? s2b : s2a) + __shfl_xor_sync(0xffffffffu, odd ? s2a : s2b, 1);
        float u3 = (odd ? db : da) + __shfl_xor_sync(0xffffffffu, odd ? da : db, 1);
        u1 += __shfl_xor_sync(0xffffffffu, u1, 2); u2 += __shfl_xor_sync(0xffffffffu, u2, 2); u3 += __shfl_xor_sync(0xffffffffu, u3, 2);
        if (!(lane & 2)) st_ll(sp, __float_as_uint(u1), __float_as_uint(u2), __float_as_uint(u3), tag);
      }
      PROFW(t256 == 0, L * 8 + 7);
      if (L) {
        mbar_wait(BAR(B_PAR), 0);
        { float2 pa = lds64f(sb + PAR + (grow & 127) * 8), pb = lds64f(sb + PAR + (grow & 127) * 8 + 64); al0 = pa.x; be0 = pa.y; al1 = pb.x; be1 = pb.y; }
        #pragma unroll
        for (int j = 0; j < 16; j++) {
          rs[2 * j] = pack_bf16(fmaf(acc[4 * j], al0, be0), fmaf(acc[4 * j + 1], al0, be0));
          rs[2 * j + 1] = pack_bf16(fmaf(acc[4 * j + 2], al1, be1), fmaf(acc[4 * j + 3], al1, be1));
        }
        #pragma unroll
        for (int jj = 0; jj < 8; jj++) stsm_x4((ra + (jj >> 2) * 32768) + (sw ^ ((jj & 3) << 5)), rs[4 * jj], rs[4 * jj + 1], rs[4 * jj + 2], rs[4 * jj + 3]);
        PROFW(t256 == 0, 16);
        if (fid >= 112) bar_arrive(3, 384);
        else {
          float d[4] = {0.f, 0.f, 0.f, 0.f};
          mbar_wait(BAR(B_FULLW + wg * 4), 0); mbar_wait(BAR(B_FULLW + wg * 4 + 1), 0);
          bar_sync(3, 384);
          PROFW(t256 == 0, 29);
          #pragma unroll 1
          for (int g = 0; g < 4; g++) {
            const uint32_t ad = (sb16 + (wg ? 6144 : 10240) + (g >> 1) * 2048 + (g & 1) * 512) | (1024u << 16), bd = (sb16 + (HV >> 4) + wg * 64 + g * 16) | 0x10000u;
            wg_fence();
            #pragma unroll
            for (int ks = 0; ks < 8; ks++) wgmma_ss_n8<0, 1>(d, mkd<HI64>(ad + ks * 64), mkd<8>(bd + ks * 2), 1);
            wg_commit();
          }
          mbar_wait(BAR(B_FULLW + 2), 0);
          wg_wait<0>(); keep(d);
          if (!(lane & 3)) { sts32f(sb + PAR + 1024 + wg * 256 + w * 64 + lane, d[0]); sts32f(sb + PAR + 1056 + wg * 256 + w * 64 + lane, d[2]); }
          bar_sync(1, 256);
          const uint32_t ga = sb + PAR + 1024 + lane * 4, aa = sb + HV + (t256 >> 5) * 128;
          sts32f(aa + lane * 4, swiglu(lds32f(ga) + lds32f(ga + 256), lds32f(ga + 128) + lds32f(ga + 384)));
          __syncwarp();
          PROFW(t256 == 0, 26);
          float y0 = 0.f, y1 = 0.f, y2 = 0.f, y3 = 0.f;
          uint32_t tbl = rh ? 0x001459a8u : 0x023679a8u;
          uint4 a4 = lds128(aa + 112);
          #pragma unroll 2
          for (int n = 0; n < 8; n++, tbl >>= 4) {
            const uint32_t src = sb + t256 * 8 + (tbl & 15) * 8192;
            const uint4 an = lds128(aa + ((0x00123564u >> (4 * n)) & 15) * 16);
            #pragma unroll
            for (int e = 0; e < 4; e++) {
              const float av = __uint_as_float(e == 0 ? a4.x : (e == 1 ? a4.y : (e == 2 ? a4.z : a4.w)));
              y0 = fmaf(bf_lo(wd[e].x), av, y0); y1 = fmaf(bf_hi(wd[e].x), av, y1); y2 = fmaf(bf_lo(wd[e].y), av, y2); y3 = fmaf(bf_hi(wd[e].y), av, y3);
              const float2 v = lds64f(src + e * 2048); wd[e] = make_uint2(__float_as_uint(v.x), __float_as_uint(v.y));
            }
            a4 = an;
          }
          st_ll(yp, __float_as_uint(y0), __float_as_uint(y1), __float_as_uint(y2), (__float_as_uint(y3) & ~255u) | (lds32(sb + INFO + 12) + 1));
          PROFW(t256 == 0, 27);
        }
        return;
      }
    }
  }
  #undef IDS
  #undef LAYER
}

DEVI void loader(const Params& P, uint32_t sb) {
  const int lane = threadIdx.x & 31;
  const int bid = uni(BID), bi = bid >> 4, bp = bid & 15, rh = bp & 1, bc = bp >> 1;
  uint32_t phq = 0, tag = 0;
  #pragma unroll 1
  for (int L = 0; L < 2; L++) {
    int s = 0;
    uint32_t rdy = 0;
    #pragma unroll 1
    for (int n = L ? 0 : 3; n < 16; n++) {
      int kb = L ? kb_order(bc, n) : n;
      mbar_wait(BAR(B_EMPTYQ + s), (phq >> s) & 1);
      phq ^= 1u << s;
      if (L && n == 1) { mbar_wait(BAR(B_XRDY + 1), 0); mbar_wait(BAR(B_XRDY + 3), 0); }
      if (lane == 0) {
        mbar_expect_tx(BAR(B_FULLQ + s), L && n < 2 ? 40960 : 57344);
        tma_3d_h(sb + qb_off(s), &P.mWq, bp * 64, kb * 64, 0, BAR(B_FULLQ + s), L && n >= QEF_N ? POL_FIRST : POL_NORMAL);
        if (!L) tma_2d(sb + qa_off(s), &P.mX, kb * 64, bi * 256, BAR(B_FULLQ + s));
      }
      if (L && n >= 2) {
        if (((rdy >> (2 * kb)) & 3) != 3) {
          do { rdy = __ballot_sync(0xffffffffu, ld_rlx(&P.g->flagX[bi][lane]) == tag); } while (((rdy >> (2 * kb)) & 3) != 3);
          fence_async_glob();
        }
        if (n == 3 || n == 4) mbar_wait(BAR(B_XFREE + n - 3), 0);
        if (lane == 0) bulk_g2s_h(sb + qa_off(s), P.g->x[bi][kb], 32768, BAR(B_FULLQ + s), POL_X);
      }
      PROFY(L && lane == 0 && (n == 2 || n == 3 || n == 9), n == 9 ? 60 : 56 + n);
      if (L && n == 2) { mbar_wait(BAR(B_FULLQ), 0); mbar_wait(BAR(B_FULLQ + 1), 1); if (lane < 2) mbar_arrive_peer(BAR(B_XFREE + lane)); }
      s = (s == 2) ? 0 : s + 1;
    }
    for (int q = 0; q < 3; q++) mbar_wait(BAR(B_EMPTYQ + q), (phq >> q) & 1);
    tag = lds32(sb + INFO + 8) + L;
    #pragma unroll 1
    for (int q = 0; q < 4; q++) {
            if (bi) {
        const unsigned* f = &P.g->flagKV[bid - 16][q];
        while (ld_rlx(f) != tag);
        fence_async_glob();
      }
      if (lane == 0) {
        mbar_expect_tx(BAR(B_KVFULL + q), 16384);
        bulk_g2s_h(sb + ((q >> 1) ? KVB : KVA) + ((q & 1) ? 0 : 16384), bi ? P.g->kv[bid - 16][q] : P.g->zero, 16384, BAR(B_KVFULL + q));
      }
      PROFY(!L && lane == 0 && bi && q != 2, 34 + (q + 1) / 2);
    }
    mbar_wait(BAR(B_ORDY), L);
    {
      const uint4* src = P.g->o[bi][0][0][rh];
      rdy = 0;
      #pragma unroll 1
      for (int n = 0, q = 0; n < 16; q = w_next(n, q), n++) {
        const int j = wo_order(bc, n);
        if (((rdy >> (2 * j)) & 3) != 3) {
          do { rdy = __ballot_sync(0xffffffffu, ld_rlx(&P.g->flagO[bi][lane]) == tag); } while (((rdy >> (2 * j)) & 3) != 3);
          fence_async_glob();
        }
        if (n >= 2) mbar_wait(n < 6 ? BAR(B_HAFREE + (n >> 2)) : BAR(B_EMPTYW + q), n < 6 ? L : w_par(n - 6, q, L));
        if (n == THR_N) mbar_wait(BAR(B_OFREE), L);
        if (lane == 0) { mbar_expect_tx(BAR(B_FULLW + q), 16384); bulk_g2s_h(sb + w_off(q), src + j * 2048, 16384, BAR(B_FULLW + q)); }
      }
    }
    mbar_wait(BAR(B_OFREE), L);
  }
}

DEVI void ffn_prefetch(const Params& P, int q) {
  bulk_prefetch(q < 16 ? ((q & 1) ? P.wu : P.wg) + ((q >> 1) * 128 + blockIdx.x) * 3584 : P.wd + (min(FID, 111) * 8 + q - 16) * 4096, q < 16 ? 7168 : 8192);
}
DEVI void storer(const Params& P, uint32_t sb, int wg) {
  const int bid = uni(BID), bi = bid >> 4, rh = bid & 1, bc = (bid & 15) >> 1;
  const bool one = (threadIdx.x & 31) == 0;
  char* const g = (char*)P.g;
  const uint32_t tag0 = uni(((ld_rlx(&P.g->epoch) % 16383u) + 1u) << 2);
  #pragma unroll 1
  for (int L = 0; L < 2; L++) {
    const uint32_t tag = tag0 + L;
    if (wg) {
      #pragma unroll 1
      for (int r = threadIdx.x & 31; r < 256; r += 32) {
        uint4 v;
        do v = ld_ll(&P.g->statF[bi * 256 + r]); while (!__all_sync(0xffffffffu, v.w == tag));
        float var = __uint_as_float(v.y), c = rsqrtf(var + LN_EPS);
        if (L) { c += 1.f; c *= rsqrtf(fmaf(var * c, c, LN_EPS)); }
        const float mh = bf_round(__uint_as_float(v.x));
        sts64f(sb + PAR + r * 8, c, __uint_as_float(pack_bf16(mh, __uint_as_float(v.x) - mh)));
      }
      if (!L) mbar_wait(BAR(B_PAR), 0);
      warp_signal(BAR(B_ROW));
    }
    if (wg) { mbar_wait(BAR(B_KVRDY), L); mbar_wait(BAR(B_KVRDY + 2), L); const uint32_t t0 = clk(); while (clk() - t0 < KV_D) __nanosleep(40); }
    #pragma unroll 1
    for (int u = 0; u < 2 + 4 * wg; u++) {
      const int h = u < 2 ? u : u >> 2, hi = (u & 1) ^ 1;
      uint32_t src, dst, fl, b0, b1;
      if (u < 2) {
        src = (h ? KVB : KVA) + (3 - wg) * 16384; dst = offsetof(Scratch, kv) + (bid * 4 + h * 2 + wg) * 16384; fl = offsetof(Scratch, flagKV) + (bid * 32 + h * 2 + wg) * 4;
        b0 = BAR(B_KVRDY + ((u | wg) ? 1 : 0)); b1 = b0 + 16;
      } else {
        src = QO + (h * 2 + hi) * 8192; dst = offsetof(Scratch, o) + ((((bi * 2 + h) * 8 + bc) * 2 + hi) * 2 + rh) * 8192;
        fl = offsetof(Scratch, flagO) + (bi * 32 + h * 16 + (bid & 15)) * 4;
        b0 = BAR(B_ORDY + u - 2); b1 = b0 + 32;
      }
      mbar_wait(b0, L); mbar_wait(b1, L);
      fence_async_smem();
      PROFY(one && !L && u == 3 * wg, u ? 46 : 8);
      if (one && (u >= 2 || bi < 7)) bulk_s2g(g + dst, sb + src, u < 2 ? 16384 : 8192);
      if (one && u == 5) mbar_arrive(BAR(B_HAFREE + 1));
      if (u == 2 || u == 4) continue;
      bulk_wait<0>();
      PROFY(one && !L && u == 3 * wg, u ? 61 : 62);
      fence_rel();
      if (one) { st_rlx((unsigned*)(g + fl), tag); if (!wg || u > 2) mbar_arrive(BAR(B_HAFREE + h + (wg & h))); }
      PROFY(one && !L && (u > 2 || u == wg), u > 2 ? (u == 3 ? 38 : 54) : 32 + u);
    }
    if (L == 0) {
      char* dst = g + (offsetof(Scratch, x) + (bi * 16 + 2 * bc) * 32768 + rh * 16384);
      unsigned* f = (unsigned*)(g + (offsetof(Scratch, flagX) + (bi * 32 + bc * 4 + rh) * 4));
      const uint32_t a = sb + rh * 16384;
      if (wg == 0) {
        mbar_wait(BAR(B_XRDY), 0); mbar_wait(BAR(B_XRDY + 2), 0);
        fence_async_smem();
        PROFY(one, 41);
        if (one) bulk_s2g(dst, a, 16384);
        bulk_wait<0>();
        PROFY(one, 45);
        if (one) { mbar_arrive(BAR(B_XFREE)); mbar_arrive(BAR(B_PFREE)); }
        fence_rel();
        mbar_wait(BAR(B_XRDY + 1), 0); mbar_wait(BAR(B_XRDY + 3), 0);
        if (one) { st_rlx(f, tag); bulk_s2g(dst + 32768, a + 32768, 16384); }
        PROFY(one, 56);
        bulk_wait<0>();
        if (one) mbar_arrive(BAR(B_XFREE + 1));
        fence_rel();
        if (one) st_rlx(f + 2, tag);
        PROFY(one, 57);
      } else {
        mbar_wait(BAR(B_XRDY + 1), 0); mbar_wait(BAR(B_XRDY + 3), 0);
        mbar_wait(BAR(B_PFREE), 0);
        if (one) bulk_s2peer(a, 16384, BAR(B_FULLQ));
        { const uint32_t t0 = clk(); while (clk() - t0 < XD_D); }
        if (one) bulk_s2peer(a + 32768, 16384, BAR(B_FULLQ + 1));
      }
      if (wg == 0) {
        uint32_t t0 = clk() + PF1_D;
        #pragma unroll 1
        for (int q = PF1_S; q < PF1_E; q++) { while ((int)(clk() - t0) < 0) __nanosleep(50); if (one) ffn_prefetch(P, q); t0 += PF1_T; }
      }
    }
  }
}

DEVI void stg_issue(const Params& P, int c, uint32_t d, uint32_t du, uint32_t b) {
  mbar_expect_tx(b, 16384);
  if (c < 8) { tma_2d_h(d, &P.mWg, FID * 32, c * 128, b, POL_G); tma_2d_h(d + du, &P.mWu, FID * 32, c * 128, b, POL_U); }
  else if (c < 12) tma_3d_h(d, &P.mWd, 0, FID * 32 + (c - 8) * 8, 0, b, POL_D);
  else tma_2d_h(d, &P.mWp, (c - 12) * 1024 + (BID >> 2) * 32, (BID & 3) * 256, b, POL_EF);
}
DEVI void pace() { const uint32_t t0 = clk(); while (clk() - t0 < PACE_T); }
DEVI void stager(const Params& P, uint32_t sb) {
  {
    const int b = blockIdx.x;
    uint32_t t0 = clk();
    #pragma unroll 1
    for (int q = 0; q < PQ_N; q++) { bulk_prefetch(P.wqkv + (q * 128 + b) * 3072, 6144); while (clk() - t0 < PQ_T) __nanosleep(50); t0 += PQ_T; }
    bulk_prefetch(P.wo + b * 8192, 16384);
    #pragma unroll 1
    for (int q = 0; q < PF0_N; q++) {
      while (clk() - t0 < PF0_T) __nanosleep(50);
      t0 += PF0_T;
      ffn_prefetch(P, q);
    }
  }
  const int bid = BID, bi = bid >> 4, rh = bid & 1, bc = (bid & 15) >> 1;
  #pragma unroll 1
  for (int L = 0; L < 2; L++) {
    const int nch = L ? (FID < 112 ? 8 : 0) : 15;
    mbar_wait(BAR(B_PAR), L); mbar_wait(BAR(B_KVFULL + W0_BAR), L);
    #pragma unroll 1
    for (int n = 0, q = 0; n < 16; q = w_next(n, q), n++) {
      if (n >= 2) mbar_wait(n < 6 ? BAR(B_HAFREE + (n >> 2)) : BAR(B_EMPTYW + q), n < 6 ? L : w_par(n - 6, q, L));
      if (n == THR_N) mbar_wait(BAR(B_OFREE), L);
      mbar_expect_tx(BAR(B_FULLW + q), 16384);
      tma_5d(sb + w_off(q) + 16384, &P.mWo, 0, 0, n >> 3, 2 * (wo_order(bc, n) & 7), 2 * bc, BAR(B_FULLW + q), L ? POL_EF : POL_NORMAL);
      if (n == 13) {
        mbar_expect_tx(BAR(B_RES), 32768);
        #pragma unroll 1
        for (int e = 0; e < 2; e++) {
          mbar_wait(BAR(B_EMPTYW + 2 + e), 1);
          if (L) bulk_g2s_h(sb + e * 32768 + rh * 16384, P.g->x[bi][2 * bc + e] + rh * 1024, 16384, BAR(B_RES));
          else tma_2d_h(sb + e * 32768 + rh * 16384, &P.mXh, bc * 128 + e * 64, bi * 256 + rh * 128, BAR(B_RES), POL_EF);
        }
      }
    }
    if (L && nch) {
      const bf16* src = WDSRC2;
      mbar_expect_tx(BAR(B_FULLW + 2), 32768); mbar_expect_tx(BAR(B_FULLW + 2), 24576);
      #pragma unroll 1
      for (int e = 0; e < 3; e++) { bulk_g2s_h(sb + e * 32768 + (e < 2 ? (rh ^ 1) * 16384 : 0), src + e * 8192, e < 2 ? 16384 : 24576, BAR(B_FULLW + 2)); pace(); }
    }
    if (L == 0) { mbar_arrive_peer(BAR(B_PFREE)); mbar_wait(BAR(B_EMPTYW), 0); mbar_wait(BAR(B_EMPTYW + 1), 0); }
    #pragma unroll 1
    for (int c = FID < 112 ? 0 : 12, slot = 0; c < nch; c++, slot = slot == 2 ? 0 : slot + 1) {
      const int q = (c >> 1) + (c & 4) / 2;
      mbar_wait(L ? BAR(B_EMPTYW + q) : BAR(B_STGE + slot), L | ((0x71c7 >> c) & 1));
      #define CC c
      stg_issue(P, CC, L ? sb + w_off(q) + (c & 1) * 8192 : sb + STG + slot * 16384, 8192 << L, L ? BAR(B_FULLW + q) : BAR(B_STG + slot));
      if (L) pace();
    }
  }
}
DEVI void sum8(uint4 v, float& s1, float& s2) {
  float e[8] = {bf_lo(v.x), bf_hi(v.x), bf_lo(v.y), bf_hi(v.y), bf_lo(v.z), bf_hi(v.z), bf_lo(v.w), bf_hi(v.w)};
  #pragma unroll
  for (int q = 0; q < 8; q++) { s1 += e[q]; s2 = fmaf(e[q], e[q], s2); }
}
DEVI uint4 norm8(uint4 x, float m, float rs) {
  #define HN(v) pack_bf16((bf_lo(v) - m) * rs, (bf_hi(v) - m) * rs)
  return make_uint4(HN(x.x), HN(x.y), HN(x.z), HN(x.w));
  #undef HN
}
DEVI void put_f32(uint4 b, uint32_t d, uint32_t d2) {
  sts128(d, make_uint4(b.x << 16, b.x & 0xffff0000u, b.y << 16, b.y & 0xffff0000u));
  sts128(d + d2, make_uint4(b.z << 16, b.z & 0xffff0000u, b.w << 16, b.w & 0xffff0000u));
}
DEVI void put_bf16(uint4 b, uint32_t d) {
  sts64f(d, __uint_as_float(b.x), __uint_as_float(b.y)); sts64f(d + 1024, __uint_as_float(b.z), __uint_as_float(b.w));
  fence_async_smem();
}
DEVI uint4 best4(uint32_t p) {
  uint4 a = lds128(p), b = lds128(p + 16), c = lds128(p + 32), d = lds128(p + 48);
  if (b.x > a.x) a = b;
  if (d.x > c.x) c = d;
  return c.x > a.x ? c : a;
}
#define FL(x) __uint_as_float(x)
#define UI(x) __float_as_uint(x)
DEVI void aux(const Params& P, uint32_t sb) {
  int tid = fresh_tid();
  #define lane (tid & 31)
  #define wq (tid >> 5)
  uint32_t ids = P.map[blockIdx.x], tag;
  #define bid ((int)(ids & 255))
  #define fid ((int)(ids >> 8))
  #define bi (bid >> 4)
  #define bp (bid & 15)
  #define bc (bp >> 1)
  #define FRESH() do { tid = fresh_tid(); uint4 z_ = ldsv128(sb + INFO2 + 16); ids = z_.y; tag = z_.z + L; idx = z_.w; } while (0)
  {
    const uint32_t epoch = ld_rlx(&P.g->epoch);
    if (tid == 0) {
      mbar_expect_tx(BAR(B_STG), 49152);
      tma_3d(sb + STG, &P.mWq, bp * 64, bi * 128, 0, BAR(B_STG));
      tma_3d(sb + STG + 24576, &P.mWq, bp * 64, bi * 128 + 64, 0, BAR(B_STG));
    }
    __syncwarp();
    sts64f(sb + ONES + tid * 8, FL(0x3F803F80u), FL(0x3F803F80u));
    float s1 = 0.f, s2 = 0.f;
    { uint4 v = __ldg((const uint4*)P.wr + tid);
      if ((tid >> 4) == bc) put_f32(v, sb + WR + (tid & 15) * 32, 16);
      sum8(v, s1, s2);
      #pragma unroll 1
      for (int o = 16; o; o >>= 1) s1 += __shfl_xor_sync(0xffffffffu, s1, o);
      sts32f(sb + INFO2 + wq * 4, s1); }
    const uint4* src = (const uint4*)(P.x0 + (size_t)bid * 16384) + (tid >> 3) * 128 + (tid & 7);
    s1 = 0.f; s2 = 0.f;
    #pragma unroll 1
    for (int it = 0; it < 16; it += 4) {
      uint4 v0 = __ldg(src + it * 8), v1 = __ldg(src + it * 8 + 8), v2 = __ldg(src + it * 8 + 16), v3 = __ldg(src + it * 8 + 24);
      #pragma unroll 1
      for (int q = 0; q < 4; q++) { sum8(v0, s1, s2); v0 = v1; v1 = v2; v2 = v3; }
    }
    #pragma unroll 1
    for (int o = 1; o < 8; o <<= 1) { s1 += __shfl_xor_sync(0xffffffffu, s1, o); s2 += __shfl_xor_sync(0xffffffffu, s2, o); }
    tag = ((epoch % 16383u) + 1u) << 2;
    if (tid == 0) { sts128(sb + INFO, make_uint4(0x40000000u, 0u, tag, ((epoch % 127u) + 1u) << 1)); sts128(sb + INFO2 + 16, make_uint4(epoch, ids, tag, 0x40000000u)); }
    float m = s1 * (1.f / 1024.f);
    if ((tid & 7) == 0) st_ll(&P.g->statF[bid * 16 + (tid >> 3)], UI(m), UI(fmaxf(fmaf(-m, m, s2 * (1.f / 1024.f)), 0.f)), 0u, tag);
    bar_sync(2, 128);
    mbar_wait_b(BAR(B_STG), 0);
    if (tid < 96) {
      s1 = 0.f; s2 = 0.f;
      #pragma unroll 1
      for (int r = 0; r < 16; r++) {
        const uint32_t a = sb + STG + (r >> 3) * 24576 + wq * 8192 + (r & 7) * 128 + ((lane * 4) ^ ((r & 7) << 4));
        #pragma unroll
        for (int e = 0; e < 8; e++) { uint32_t v = lds32(a + e * 1024); s1 += bf_lo(v); s2 += bf_hi(v); }
      }
      st_ll(&P.g->csP[bp][bi][tid], UI(s1), UI(s2), 0u, tag);
      s1 = 0.f; s2 = 0.f;
      #pragma unroll 1
      for (int q = 0; q < 8; q += 2) {
        uint4 a, b; poll_ll2(&P.g->csP[bp][q][tid], &P.g->csP[bp][q + 1][tid], 0xffffffffu, tag, a, b);
        s1 += FL(a.x) + FL(b.x); s2 += FL(a.y) + FL(b.y);
      }
      const uint32_t hi = pack_bf16(-s1, -s2);
      sts32(sb + CS + (tid >> 2) * 32 + (tid & 3) * 4, hi);
      sts32(sb + CS + (tid >> 2) * 32 + (tid & 3) * 4 + 16, pack_bf16(-s1 - bf_lo(hi), -s2 - bf_hi(hi)));
    }
    fence_async_smem();
  }
  int idx;
  #pragma unroll 1
  for (int L = 0; L < 2; L++) {
    FRESH();
    {
      if ((unsigned)(bi - (idx >> 8)) < 2u) {
        const uint4* src = &P.g->patch[bp * 8 + (tid >> 6) * 4][tid & 63];
        uint4 v0, v1, v2, v3; int it = 0;
        do { v0 = ld_ll(src); v1 = ld_ll(src + 64); v2 = ld_ll(src + 128); v3 = ld_ll(src + 192); if (++it > SPIN_MAX) __trap(); }
        while (!__all_sync(0xffffffffu, v0.w == tag && v1.w == tag && v2.w == tag && v3.w == tag));
        float q = (FL(v0.x) + FL(v1.x)) + (FL(v2.x) + FL(v3.x)), k = (FL(v0.y) + FL(v1.y)) + (FL(v2.y) + FL(v3.y)), v = (FL(v0.z) + FL(v1.z)) + (FL(v2.z) + FL(v3.z));
        q += __shfl_xor_sync(0xffffffffu, q, 1); k += __shfl_xor_sync(0xffffffffu, k, 1); v += __shfl_xor_sync(0xffffffffu, v, 1);
        bar_sync(2, 128);
        const uint32_t d = sb + PATCH + (tid & ~1), kv = pack_bf16(k, v);
        sts16(d, pack_bf16(q * QSCALE, 0.f)); sts16(d + 128, kv); sts16(d + 256, kv >> 16);
      }
      sts32(sb + INFO, idx);
      bar_sync(2, 128);
    }
    const uint4 fix = lds128(sb + PATCH + 128 + (lane & 4) * 32 + (wq >> 1) * 64 + (lane & 3) * 16);
    warp_signal(BAR(B_PAR));
    PROFX(tid == 0, L ? 23 : 17);
    mbar_wait_b(BAR(B_KVFULL + wq), L);
    if ((idx >> 7) == bi * 2 - 1 - (wq & 1)) {
      if (lane < 8) sts128(sb + ((wq >> 1) ? KVB : KVA) + ((idx >> 6) & 3) * 8192 + (lane >> 2) * 4096 + (idx & 63) * 64 + (((lane ^ (idx >> 1)) & 3) << 4), fix);
      fence_async_smem();
    }
    bar_arrive(4 + wq, 160); bar_arrive(8 + wq, 160);
    FRESH();
    mbar_wait_b(BAR(B_OFREE), L);
    #define blk (bi * 2 + (bid & 1))
    if (tid < 33) st_ll(tid < 32 ? &P.g->row[blk][bc * 32 + tid] : &P.g->best[bc][blk], 0u, 0u, 0u, 0u);
    mbar_wait_b(BAR(B_XRDY + 1), L); mbar_wait_b(BAR(B_XRDY + 3), L);
    PROFX(tid == 0, 37 + L * 16);
    FRESH();
    {
      float s1 = 0.f, s2 = 0.f, d = 0.f;
      #pragma unroll 1
      for (int q = 0; q < 8; q += 4) {
        const uint4* src = &P.g->statP[q][blk * 128 + tid];
        uint4 v0, v1, v2, v3; int it = 0;
        do { v0 = ld_ll(src); v1 = ld_ll(src + 2048); v2 = ld_ll(src + 4096); v3 = ld_ll(src + 6144); if (++it > SPIN_MAX) __trap(); }
        while (!__all_sync(0xffffffffu, v0.w == tag && v1.w == tag && v2.w == tag && v3.w == tag));
        s1 += (FL(v0.x) + FL(v1.x)) + (FL(v2.x) + FL(v3.x)); s2 += (FL(v0.y) + FL(v1.y)) + (FL(v2.y) + FL(v3.y)); d += (FL(v0.z) + FL(v1.z)) + (FL(v2.z) + FL(v3.z));
      }
      PROFX(tid == 0, 39 + L * 16);
      uint4 a = lds128(sb + INFO2), b, c;
      float m = s1 * (1.f / 1024.f), var = fmaxf(fmaf(-m, m, s2 * (1.f / 1024.f)), 0.f), rs = rsqrtf(var + LN_EPS);
      uint32_t key = UI(fmaf(-m, (FL(a.x) + FL(a.y)) + (FL(a.z) + FL(a.w)), d) * rs);
      key ^= (uint32_t)((int)key >> 31) | 0x80000000u;
      uint32_t win = __ballot_sync(0xffffffffu, key == __reduce_max_sync(0xffffffffu, key));
      if (lane == __ffs(win) - 1) sts128(sb + RED + wq * 16, make_uint4(key, UI(m), UI(rs), (tag << 11) | (uint32_t)(blk * 128 + tid)));
      if (L) sts64f(sb + PAR + tid * 8, 1.f + rs, -m * rs);
      else if ((tid >> 4) == bc) st_ll(&P.g->statF[blk * 128 + tid], UI(m), UI(var), 0u, tag + 1);
      bar_sync(2, 128);
      if (wq == 0) {
        a = best4(sb + RED);
        float2 v = lds64f(sb + (lane >> 4) * 32768 + (a.w & 255) * 128 + (((lane & 15) * 8) ^ ((a.w & 7) << 4)));
        st_ll(&P.g->row[blk][bc * 32 + lane], UI(v.x), UI(v.y), 0u, tag);
        if (lane == 0) st_ll(&P.g->best[bc][blk], a.x, a.y, a.z, a.w);
        __syncwarp();
        if (lane < 2 + 2 * L) mbar_arrive(L ? BAR(B_PAR) : BAR(B_XFREE + lane));
      }
      PROFX(tid == 0, 18 + L * 6);
      FRESH();
      a = poll_ll(&P.g->best[bc][lane & 15], 0xfffff800u, tag << 11);
      win = __ffs(__ballot_sync(0xffffffffu, a.x == __reduce_max_sync(0xffffffffu, a.x))) - 1;
      idx = __shfl_sync(0xffffffffu, a.w, win) & 2047;
      PROFX(tid == 0, 19 + L * 6);
      poll_ll2(&P.g->row[win][tid], &P.g->row[win][tid + 128], 0xffffffffu, tag, c, b);
      c.z = b.x; c.w = b.y;
      a.x = __shfl_sync(0xffffffffu, a.x, win); a.y = __shfl_sync(0xffffffffu, a.y, win); a.z = __shfl_sync(0xffffffffu, a.z, win);
      sts32(sb + INFO2 + 28, idx);
      PROFX(tid == 0, 61 + L);
      b = norm8(c, FL(a.y), FL(a.z));
      if (L) put_bf16(b, sb + HV + tid * 8); else put_f32(b, sb + HV + tid * 16, 2048);
      if ((tid >> 1) == (bid & 63)) {
        sts128(sb + RED + 64 + (tid & 1) * 16, bid < 64 ? make_uint4(c.x, c.y, b.x, b.y) : make_uint4(c.z, c.w, b.z, b.w));
        sts32(sb + RED + 96, a.x);
      }
      bar_sync(2 + L, 128 + L * 256);
      if (L) {
        const int r0 = blk * 128 + (tid >> 4);
        uint32_t src = sb + ((tid >> 3) & 1) * 32768 + (r0 & 255) * 128 + (((tid ^ r0) & 7) << 4);
        uint4* dst = (uint4*)(P.out + (size_t)r0 * 1024 + bc * 128) + (tid & 15);
        #pragma unroll 4
        for (int it = 0; it < 16; it++) { uint4 v = lds128(src + it * 1024); if (idx - r0 != it * 8) dst[it * 1024] = v; }
      }
    }
    #pragma unroll 1
    for (int st = L; st < 2; st++) {
      FRESH();
      float a[8] = {0.f, 0.f, 0.f, 0.f, 0.f, 0.f, 0.f, 0.f};
      if (L == 0 && fid < 112) {
        uint32_t ha = st ? sb + RED + 768 : sb + HV + ((wq & 1) * 64 + (lane >> 2)) * 4;
        uint32_t ph = st ? 0x1cu : 0x171u, bar = st ? BAR(B_STG + 2) : BAR(B_STG);
        uint32_t wa = sb + STG + wq * 4096 + (st ? 32768 + lane * 16 : (lane ^ (lane >> 3)) * 16);
        const uint32_t hx = st ? 256 : 512;
        const bool lead = lane == 0;
        uint4 vc = make_uint4(0u, 0u, 0u, 0u); float hc = 0.f;
        #pragma unroll 1
        do {
          mbar_wait(bar, ph & 1);
          PROFX(lead && threadIdx.x == 256 && st == 0 && (ph > 255 || ph < 4), 40 - 23 + __clz(ph));
          #pragma unroll
          for (int n = 0; n < 8; n++) { const uint4 v = lds128(wa + n * 512); const float h = lds32f(ha + n * 32); fma8(a, vc, hc); vc = v; hc = h; }
          __syncwarp();
          if (lead) mbar_arrive(bar - 8 * (B_STG - B_STGE));
          const bool wrap = bar == BAR(B_STG + 2);
          bar += wrap ? -16 : 8; wa += wrap ? -32768 : 16384; ha += hx;
          ph >>= 1;
        } while (ph != 1);
        fma8(a, vc, hc);
      }
      FRESH();
      if (st == 1) {
        const uint32_t t8 = lds32(sb + INFO + 12) + L;
        if (L == 0 && fid < 112) {
          const bool odd = lane & 1;
          #pragma unroll
          for (int e = 0; e < 4; e++) { float z = __shfl_xor_sync(0xffffffffu, odd ? a[e] : a[4 + e], 1); if (odd) a[e] = z; else a[4 + e] = z; }
          uint4* dst = &P.g->yP[tid & ~1][fid][tid & 1];
          st_ll(dst, UI(a[0]), UI(a[1]), UI(a[2]), (UI(a[3]) & ~255u) | t8);
          st_ll(dst + 224, UI(a[4]), UI(a[5]), UI(a[6]), (UI(a[7]) & ~255u) | t8);
          PROFX(tid == 0, 21);
        }
        if (tid == 0) { uint32_t k = lds32(sb + RED + 96); sts32f(sb + RED + 100, bf_round(__fdividef(1.f, 1.f + __expf(-bf_round(FL(k ^ (~(uint32_t)((int)k >> 31) | 0x80000000u))))))); }
        uint4 v0, v1;
        poll_ll2(&P.g->yP[bid][0][min(tid, 111)], &P.g->yP[bid][0][min(tid, 111) + 112], 255u, t8, v0, v1);
        const float lo = (tid < 112 && !(tid & 1)) ? 1.f : 0.f, hi = (tid < 112 && (tid & 1)) ? 1.f : 0.f;
        const float y0 = FL(v0.x) + FL(v1.x), y1 = FL(v0.y) + FL(v1.y), y2 = FL(v0.z) + FL(v1.z), y3 = FL((v0.w & ~255u) | 128u) + FL((v1.w & ~255u) | 128u);
        a[0] = y0 * lo; a[1] = y1 * lo; a[2] = y2 * lo; a[3] = y3 * lo; a[4] = y0 * hi; a[5] = y1 * hi; a[6] = y2 * hi; a[7] = y3 * hi;
      }
      sts32f(sb + RED + 256 + wq * 128 + ((lane & 3) * 8 + (lane >> 2)) * 4, fold8(a));
      bar_sync(2, 128);
      const uint32_t d = sb + RED + 256 + lane * 4;
      float z0 = lds32f(d) + lds32f(d + 128), z1 = lds32f(d + 256) + lds32f(d + 384);
      if (st == 0) {
        sts32f(sb + RED + 768 + lane * 32 + wq * 4, swiglu(z0, z1));
        bar_sync(2, 128);
        if (fid < 112) { st_ll(&P.g->yP[tid & ~1][fid][tid & 1], 0u, 0u, 0u, 0u); st_ll(&P.g->yP[tid | 1][fid][tid & 1], 0u, 0u, 0u, 0u); }
        else { const uint32_t t0 = clk(); while (clk() - t0 < IDLE_T) __nanosleep(200); }
        if (tid < 80) st_ll(tid < 64 ? &P.g->patch[bid][tid] : &P.g->x2[(tid >> 1) & 7][2 * bid + (tid & 1)], 0u, 0u, 0u, 0u);
        PROFX(tid == 0, 20); continue; }
      z0 += z1;
      z0 += __shfl_xor_sync(0xffffffffu, z0, 8); z0 += __shfl_xor_sync(0xffffffffu, z0, 16);
      uint32_t xw = lds32(sb + RED + 64 + (lane & 4) * 4 + (lane & 2) * 2), hw = lds32(sb + RED + 72 + (lane & 4) * 4 + (lane & 2) * 2);
      z0 = bf_round(((lane & 1) ? bf_hi(hw) : bf_lo(hw)) + bf_round(bf_round(z0) * lds32f(sb + RED + 100))) + ((lane & 1) ? bf_hi(xw) : bf_lo(xw));
      uint32_t v = pack_bf16(z0, __shfl_down_sync(0xffffffffu, z0, 1)), v2 = __shfl_down_sync(0xffffffffu, v, 2);
      if (L) { if (tid == 0 || tid == 4) *(uint2*)(P.out + (size_t)idx * 1024 + bid * 8 + tid) = make_uint2(v, v2); PROFW(tid == 0, 28); }
      else if ((tid & 3) == 0 && tid < 64) st_ll(&P.g->x2[tid >> 3][2 * bid + ((tid >> 2) & 1)], v, v2, 0u, tag + 1);
    }
    if (L == 0) {
      PROFX(tid == 0, 22);
      FRESH();
      uint4 x, y; poll_ll2(&P.g->x2[bi][tid], &P.g->x2[bi][tid + 128], 0xffffffffu, tag + 1, x, y);
      x.z = y.x; x.w = y.y;
      if (wq == (bc & 3)) sts64f(sb + X2SEG + lane * 8, FL(bc < 4 ? x.x : x.z), FL(bc < 4 ? x.y : x.w));
      float s1 = 0.f, s2 = 0.f;
      sum8(x, s1, s2);
      #pragma unroll
      for (int o = 16; o; o >>= 1) { s1 += __shfl_xor_sync(0xffffffffu, s1, o); s2 += __shfl_xor_sync(0xffffffffu, s2, o); }
      sts64f(sb + RED + wq * 8, s1, s2);
      bar_sync(2, 128);
      y = lds128(sb + RED); uint4 y2 = lds128(sb + RED + 16);
      float m = ((FL(y.x) + FL(y.z)) + (FL(y2.x) + FL(y2.z))) * (1.f / 1024.f);
      put_bf16(norm8(x, m, rsqrtf(fmaxf(fmaf(-m, m, ((FL(y.y) + FL(y.w)) + (FL(y2.y) + FL(y2.w))) * (1.f / 1024.f)), 0.f) + LN_EPS)), sb + HV + tid * 8);
      mbar_wait(BAR(B_STG), 1); mbar_wait(BAR(B_STG + 1), 0); mbar_wait(BAR(B_STG + 2), 0);
      bar_sync(2, 128);
      PROFX(tid == 0, 30);
      float d0[4] = {0.f, 0.f, 0.f, 0.f}, d1[4] = {0.f, 0.f, 0.f, 0.f}, d2[4] = {0.f, 0.f, 0.f, 0.f};
      const uint32_t bd = (64 + (HV >> 4) + uni(bid & 3) * 32) | 0x10000u;
      #pragma unroll 1
      for (int ks = 0; ks < 8; ks++) {
        const uint32_t ad = (64 + (STG >> 4) + ks * 128) | (64u << 16);
        wg_fence();
        wgmma_ss_n8<0, 1>(d0, mkd<HI64>(ad), mkd<8>(bd + ks * 4), 1);
        wgmma_ss_n8<0, 1>(d1, mkd<HI64>(ad + 1024), mkd<8>(bd + ks * 4), 1);
        wgmma_ss_n8<0, 1>(d2, mkd<HI64>(ad + 2048), mkd<8>(bd + ks * 4), 1);
        wg_commit();
      }
      wg_wait<0>(); keep(d0); keep(d1); keep(d2);
      FRESH();
      if ((lane & 3) == (wq >> 1)) {
        uint4* dst = &P.g->patch[bid][(wq & 1) * 32 + (lane >> 2) * 2 + (wq >> 1)];
        st_ll(dst, UI(d0[0]), UI(d1[0]), UI(d2[0]), tag + 1); st_ll(dst + 16, UI(d0[2]), UI(d1[2]), UI(d2[2]), tag + 1);
      }
      PROFX(tid == 0, 31);
    }
  }
  if (bid == 0 && tid == 0) P.g->epoch = lds32(sb + INFO2 + 16) + 1;
  #undef blk
  #undef bid
  #undef fid
  #undef bi
  #undef bp
  #undef bc
  #undef FRESH
  #undef lane
  #undef wq
}

__global__ void __cluster_dims__(2, 1, 1) __launch_bounds__(512, 1) fused_kernel(const __grid_constant__ Params P) {
  extern __shared__ __align__(1024) uint8_t smem_raw[];
  const uint32_t sb = smem_u32(smem_raw);
  PROFT(threadIdx.x == 0, 0);
  if (threadIdx.x == 0) {
    for (int s = 0; s < 3; s++) mbar_init(BAR(B_FULLQ + s), 1);
    asm volatile("fence.mbarrier_init.release.cluster;" ::: "memory");
    #pragma unroll 1
    for (int s = 0; s < 3; s++) {
      mbar_expect_tx(BAR(B_FULLQ + s), 57344);
      tma_2d(sb + qa_off(s), &P.mX, s * 64, (BID >> 4) * 256, BAR(B_FULLQ + s));
      tma_3d(sb + qb_off(s), &P.mWq, (BID & 15) * 64, s * 64, 0, BAR(B_FULLQ + s));
    }
    if ((sb & 0x3FFFFu) != 1024) __trap();
  } else if (threadIdx.x == 480) {
    asm volatile("prefetch.tensormap [%0];" :: "l"(&P.mWq) : "memory");
  } else if (threadIdx.x >= 32 && !(threadIdx.x & 28) && (threadIdx.x >> 3) + (threadIdx.x & 3) <= B_COUNT + 1) {
    int b = (threadIdx.x >> 3) + (threadIdx.x & 3) - 1;
    if (b == B_COUNT) b = B_ROW;
    const uint32_t cnt = b < B_XFREE ? (b == B_OFREE ? 1 : 2) : (b < B_KVRDY ? 3 : (b < B_KVFULL || b == B_PAR ? 4 : (b == B_PFREE ? 2 : 1)));
    mbar_init(BAR(b), cnt);
    asm volatile("fence.mbarrier_init.release.cluster;" ::: "memory");
  }
  __syncthreads();
  asm volatile("barrier.cluster.arrive.relaxed.aligned;" ::: "memory");
  const int wg = __shfl_sync(0xffffffffu, threadIdx.x >> 7, 0);
  if (wg < 2) { reg_inc<224>(); consumer(P, sb, wg); }
  else if (wg == 2) { reg_dec<40>(); aux(P, sb); }
  else {
    reg_dec<24>();
    asm volatile("barrier.cluster.wait.aligned;" ::: "memory");
    const int w = __shfl_sync(0xffffffffu, (threadIdx.x >> 5) & 3, 0);
    if (w == 0) loader(P, sb);
    else if (w < 3) storer(P, sb, w - 1);
    else if ((threadIdx.x & 31) == 0) stager(P, sb);
  }
}

typedef CUresult (*EncFn)(CUtensorMap*, CUtensorMapDataType, cuuint32_t, void*, const cuuint64_t*, const cuuint64_t*, const cuuint32_t*, const cuuint32_t*,
                          CUtensorMapInterleave, CUtensorMapSwizzle, CUtensorMapL2promotion, CUtensorMapFloatOOBfill);
static void mk_map(EncFn enc, CUtensorMap* m, const void* ptr, int rank, const cuuint64_t* dims, const cuuint64_t* strides, const cuuint32_t* box,
                   CUtensorMapSwizzle sw, CUtensorMapL2promotion pr) {
  cuuint32_t es[5] = {1, 1, 1, 1, 1};
  enc(m, CU_TENSOR_MAP_DATA_TYPE_BFLOAT16, rank, (void*)ptr, dims, strides, box, es, CU_TENSOR_MAP_INTERLEAVE_NONE, sw, pr, CU_TENSOR_MAP_FLOAT_OOB_FILL_NONE);
}
extern "C" void kernel_launch(void* const* d_in, const int* in_sizes, int n_in, void* d_out, int out_size) {
  (void)in_sizes; (void)n_in; (void)out_size;
  void* fn = nullptr; cudaDriverEntryPointQueryResult q;
  cudaGetDriverEntryPoint("cuTensorMapEncodeTiled", &fn, cudaEnableDefault, &q);
  EncFn enc = (EncFn)fn;
  cudaFuncSetAttribute(fused_kernel, cudaFuncAttributeMaxDynamicSharedMemorySize, SMEM_BYTES);
  Params P;
  const CUtensorMapSwizzle S128 = CU_TENSOR_MAP_SWIZZLE_128B, S64 = CU_TENSOR_MAP_SWIZZLE_64B, S0 = CU_TENSOR_MAP_SWIZZLE_NONE;
  const CUtensorMapL2promotion L256 = CU_TENSOR_MAP_L2_PROMOTION_L2_256B, L128 = CU_TENSOR_MAP_L2_PROMOTION_L2_128B;
  { cuuint64_t d[2] = {1024, 2048}, s[1] = {2048}; cuuint32_t b[2] = {64, 256}, bh[2] = {64, 128};
    mk_map(enc, &P.mX, d_in[0], 2, d, s, b, S128, L256); mk_map(enc, &P.mXh, d_in[0], 2, d, s, bh, S128, L256); }
  { cuuint64_t d[3] = {1024, 1024, 3}, s[2] = {6144, 2048}; cuuint32_t b[3] = {64, 64, 3}; mk_map(enc, &P.mWq, d_in[1], 3, d, s, b, S128, L256); }
  { cuuint64_t d[5] = {64, 32, 2, 16, 16}, s[4] = {2048, 65536, 131072, 128}; cuuint32_t b[5] = {64, 32, 1, 2, 2}; mk_map(enc, &P.mWo, d_in[2], 5, d, s, b, S128, L256); }
  { cuuint64_t d[2] = {3584, 1024}, s[1] = {7168}; cuuint32_t b[2] = {32, 128};
    mk_map(enc, &P.mWg, d_in[5], 2, d, s, b, S64, L128); mk_map(enc, &P.mWu, d_in[6], 2, d, s, b, S64, L128); }
  { cuuint64_t d[2] = {3072, 1024}, s[1] = {6144}; cuuint32_t b[2] = {32, 256}; mk_map(enc, &P.mWp, d_in[1], 2, d, s, b, S64, L128); }
  { cuuint64_t d[3] = {256, 3584, 4}, s[2] = {2048, 512}; cuuint32_t b[3] = {256, 8, 4}; mk_map(enc, &P.mWd, d_in[7], 3, d, s, b, S0, L128); }
  P.x0 = (const bf16*)d_in[0]; P.wqkv = (const bf16*)d_in[1]; P.wo = (const bf16*)d_in[2]; P.wr = (const bf16*)d_in[4]; P.wg = (const bf16*)d_in[5]; P.wu = (const bf16*)d_in[6]; P.wd = (const bf16*)d_in[7];
  P.out = (bf16*)d_out;
  cudaGetSymbolAddress((void**)&P.g, g_scr);
  for (int b = 0; b < 128; b++) {
    int j = b >> 1, quad = j < 4 ? 0 : (j < 36 ? 1 + (j - 4) % 8 : 9 + (j - 36) % 7), pos = j < 4 ? j : (j < 36 ? (j - 4) / 8 : (j - 36) / 7);
    int bid = ((quad >> 2) * 2 + (pos >> 1)) * 16 + ((quad & 3) * 2 + (pos & 1)) * 2 + (b & 1);
    int e = pos * 2 + (b & 1), fid = e < 7 ? quad * 7 + e : 112 + quad;
    P.map[b] = bid | fid << 8;
  }
  fused_kernel<<<128, 512, SMEM_BYTES>>>(P);
}
```

```cpp
#include <cuda_runtime.h>
#include <cuda_bf16.h>
#include <cuda.h>
#include <stdint.h>
#include <stddef.h>
typedef __nv_bfloat16 bf16;

template<int TB, int TA = 0> __device__ __forceinline__ void wgmma_ss_n192(float (&d)[96], uint64_t da, uint64_t db, int scale_d) {
  asm volatile("{\n.reg .pred p;\nsetp.ne.b32 p, %98, 0;\n"
    "wgmma.mma_async.sync.aligned.m64n192k16.f32.bf16.bf16 {%0, %1, %2, %3, %4, %5, %6, %7, %8, %9, %10, %11, %12, %13, %14, %15, %16, %17, %18, %19, %20, %21, %22, %23, %24, %25, %26, %27, %28, %29, %30, %31, %32, %33, %34, %35, %36, %37, %38, %39, %40, %41, %42, %43, %44, %45, %46, %47, %48, %49, %50, %51, %52, %53, %54, %55, %56, %57, %58, %59, %60, %61, %62, %63, %64, %65, %66, %67, %68, %69, %70, %71, %72, %73, %74, %75, %76, %77, %78, %79, %80, %81, %82, %83, %84, %85, %86, %87, %88, %89, %90, %91, %92, %93, %94, %95}, %96, %97, p, 1, 1, %100, %99;\n}\n"
    : "+f"(d[0]), "+f"(d[1]), "+f"(d[2]), "+f"(d[3]), "+f"(d[4]), "+f"(d[5]), "+f"(d[6]), "+f"(d[7]), "+f"(d[8]), "+f"(d[9]), "+f"(d[10]), "+f"(d[11]), "+f"(d[12]), "+f"(d[13]), "+f"(d[14]), "+f"(d[15]), "+f"(d[16]), "+f"(d[17]), "+f"(d[18]), "+f"(d[19]), "+f"(d[20]), "+f"(d[21]), "+f"(d[22]), "+f"(d[23]), "+f"(d[24]), "+f"(d[25]), "+f"(d[26]), "+f"(d[27]), "+f"(d[28]), "+f"(d[29]), "+f"(d[30]), "+f"(d[31]), "+f"(d[32]), "+f"(d[33]), "+f"(d[34]), "+f"(d[35]), "+f"(d[36]), "+f"(d[37]), "+f"(d[38]), "+f"(d[39]), "+f"(d[40]), "+f"(d[41]), "+f"(d[42]), "+f"(d[43]), "+f"(d[44]), "+f"(d[45]), "+f"(d[46]), "+f"(d[47]), "+f"(d[48]), "+f"(d[49]), "+f"(d[50]), "+f"(d[51]), "+f"(d[52]), "+f"(d[53]), "+f"(d[54]), "+f"(d[55]), "+f"(d[56]), "+f"(d[57]), "+f"(d[58]), "+f"(d[59]), "+f"(d[60]), "+f"(d[61]), "+f"(d[62]), "+f"(d[63]), "+f"(d[64]), "+f"(d[65]), "+f"(d[66]), "+f"(d[67]), "+f"(d[68]), "+f"(d[69]), "+f"(d[70]), "+f"(d[71]), "+f"(d[72]), "+f"(d[73]), "+f"(d[74]), "+f"(d[75]), "+f"(d[76]), "+f"(d[77]), "+f"(d[78]), "+f"(d[79]), "+f"(d[80]), "+f"(d[81]), "+f"(d[82]), "+f"(d[83]), "+f"(d[84]), "+f"(d[85]), "+f"(d[86]), "+f"(d[87]), "+f"(d[88]), "+f"(d[89]), "+f"(d[90]), "+f"(d[91]), "+f"(d[92]), "+f"(d[93]), "+f"(d[94]), "+f"(d[95])
    : "l"(da), "l"(db), "r"(scale_d), "n"(TB), "n"(TA));
}

template<int TB> __device__ __forceinline__ void wgmma_rs_n192(float (&d)[96], uint32_t a0, uint32_t a1, uint32_t a2, uint32_t a3, uint64_t db, int scale_d) {
  asm volatile("{\n.reg .pred p;\nsetp.ne.b32 p, %101, 0;\n"
    "wgmma.mma_async.sync.aligned.m64n192k16.f32.bf16.bf16 {%0, %1, %2, %3, %4, %5, %6, %7, %8, %9, %10, %11, %12, %13, %14, %15, %16, %17, %18, %19, %20, %21, %22, %23, %24, %25, %26, %27, %28, %29, %30, %31, %32, %33, %34, %35, %36, %37, %38, %39, %40, %41, %42, %43, %44, %45, %46, %47, %48, %49, %50, %51, %52, %53, %54, %55, %56, %57, %58, %59, %60, %61, %62, %63, %64, %65, %66, %67, %68, %69, %70, %71, %72, %73, %74, %75, %76, %77, %78, %79, %80, %81, %82, %83, %84, %85, %86, %87, %88, %89, %90, %91, %92, %93, %94, %95}, {%96, %97, %98, %99}, %100, p, 1, 1, %102;\n}\n"
    : "+f"(d[0]), "+f"(d[1]), "+f"(d[2]), "+f"(d[3]), "+f"(d[4]), "+f"(d[5]), "+f"(d[6]), "+f"(d[7]), "+f"(d[8]), "+f"(d[9]), "+f"(d[10]), "+f"(d[11]), "+f"(d[12]), "+f"(d[13]), "+f"(d[14]), "+f"(d[15]), "+f"(d[16]), "+f"(d[17]), "+f"(d[18]), "+f"(d[19]), "+f"(d[20]), "+f"(d[21]), "+f"(d[22]), "+f"(d[23]), "+f"(d[24]), "+f"(d[25]), "+f"(d[26]), "+f"(d[27]), "+f"(d[28]), "+f"(d[29]), "+f"(d[30]), "+f"(d[31]), "+f"(d[32]), "+f"(d[33]), "+f"(d[34]), "+f"(d[35]), "+f"(d[36]), "+f"(d[37]), "+f"(d[38]), "+f"(d[39]), "+f"(d[40]), "+f"(d[41]), "+f"(d[42]), "+f"(d[43]), "+f"(d[44]), "+f"(d[45]), "+f"(d[46]), "+f"(d[47]), "+f"(d[48]), "+f"(d[49]), "+f"(d[50]), "+f"(d[51]), "+f"(d[52]), "+f"(d[53]), "+f"(d[54]), "+f"(d[55]), "+f"(d[56]), "+f"(d[57]), "+f"(d[58]), "+f"(d[59]), "+f"(d[60]), "+f"(d[61]), "+f"(d[62]), "+f"(d[63]), "+f"(d[64]), "+f"(d[65]), "+f"(d[66]), "+f"(d[67]), "+f"(d[68]), "+f"(d[69]), "+f"(d[70]), "+f"(d[71]), "+f"(d[72]), "+f"(d[73]), "+f"(d[74]), "+f"(d[75]), "+f"(d[76]), "+f"(d[77]), "+f"(d[78]), "+f"(d[79]), "+f"(d[80]), "+f"(d[81]), "+f"(d[82]), "+f"(d[83]), "+f"(d[84]), "+f"(d[85]), "+f"(d[86]), "+f"(d[87]), "+f"(d[88]), "+f"(d[89]), "+f"(d[90]), "+f"(d[91]), "+f"(d[92]), "+f"(d[93]), "+f"(d[94]), "+f"(d[95])
    : "r"(a0), "r"(a1), "r"(a2), "r"(a3), "l"(db), "r"(scale_d), "n"(TB));
}

template<int TB, int TA = 0> __device__ __forceinline__ void wgmma_ss_n128(float (&d)[64], uint64_t da, uint64_t db, int scale_d) {
  asm volatile("{\n.reg .pred p;\nsetp.ne.b32 p, %66, 0;\n"
    "wgmma.mma_async.sync.aligned.m64n128k16.f32.bf16.bf16 {%0, %1, %2, %3, %4, %5, %6, %7, %8, %9, %10, %11, %12, %13, %14, %15, %16, %17, %18, %19, %20, %21, %22, %23, %24, %25, %26, %27, %28, %29, %30, %31, %32, %33, %34, %35, %36, %37, %38, %39, %40, %41, %42, %43, %44, %45, %46, %47, %48, %49, %50, %51, %52, %53, %54, %55, %56, %57, %58, %59, %60, %61, %62, %63}, %64, %65, p, 1, 1, %68, %67;\n}\n"
    : "+f"(d[0]), "+f"(d[1]), "+f"(d[2]), "+f"(d[3]), "+f"(d[4]), "+f"(d[5]), "+f"(d[6]), "+f"(d[7]), "+f"(d[8]), "+f"(d[9]), "+f"(d[10]), "+f"(d[11]), "+f"(d[12]), "+f"(d[13]), "+f"(d[14]), "+f"(d[15]), "+f"(d[16]), "+f"(d[17]), "+f"(d[18]), "+f"(d[19]), "+f"(d[20]), "+f"(d[21]), "+f"(d[22]), "+f"(d[23]), "+f"(d[24]), "+f"(d[25]), "+f"(d[26]), "+f"(d[27]), "+f"(d[28]), "+f"(d[29]), "+f"(d[30]), "+f"(d[31]), "+f"(d[32]), "+f"(d[33]), "+f"(d[34]), "+f"(d[35]), "+f"(d[36]), "+f"(d[37]), "+f"(d[38]), "+f"(d[39]), "+f"(d[40]), "+f"(d[41]), "+f"(d[42]), "+f"(d[43]), "+f"(d[44]), "+f"(d[45]), "+f"(d[46]), "+f"(d[47]), "+f"(d[48]), "+f"(d[49]), "+f"(d[50]), "+f"(d[51]), "+f"(d[52]), "+f"(d[53]), "+f"(d[54]), "+f"(d[55]), "+f"(d[56]), "+f"(d[57]), "+f"(d[58]), "+f"(d[59]), "+f"(d[60]), "+f"(d[61]), "+f"(d[62]), "+f"(d[63])
    : "l"(da), "l"(db), "r"(scale_d), "n"(TB), "n"(TA));
}

template<int TB, int TA = 0> __device__ __forceinline__ void wgmma_ss_n64(float (&d)[32], uint64_t da, uint64_t db, int scale_d) {
  asm volatile("{\n.reg .pred p;\nsetp.ne.b32 p, %34, 0;\n"
    "wgmma.mma_async.sync.aligned.m64n64k16.f32.bf16.bf16 {%0, %1, %2, %3, %4, %5, %6, %7, %8, %9, %10, %11, %12, %13, %14, %15, %16, %17, %18, %19, %20, %21, %22, %23, %24, %25, %26, %27, %28, %29, %30, %31}, %32, %33, p, 1, 1, %36, %35;\n}\n"
    : "+f"(d[0]), "+f"(d[1]), "+f"(d[2]), "+f"(d[3]), "+f"(d[4]), "+f"(d[5]), "+f"(d[6]), "+f"(d[7]), "+f"(d[8]), "+f"(d[9]), "+f"(d[10]), "+f"(d[11]), "+f"(d[12]), "+f"(d[13]), "+f"(d[14]), "+f"(d[15]), "+f"(d[16]), "+f"(d[17]), "+f"(d[18]), "+f"(d[19]), "+f"(d[20]), "+f"(d[21]), "+f"(d[22]), "+f"(d[23]), "+f"(d[24]), "+f"(d[25]), "+f"(d[26]), "+f"(d[27]), "+f"(d[28]), "+f"(d[29]), "+f"(d[30]), "+f"(d[31])
    : "l"(da), "l"(db), "r"(scale_d), "n"(TB), "n"(TA));
}

template<int TB, int TA = 0> __device__ __forceinline__ void wgmma_ss_n8(float (&d)[4], uint64_t da, uint64_t db, int scale_d) {
  asm volatile("{\n.reg .pred p;\nsetp.ne.b32 p, %6, 0;\n"
    "wgmma.mma_async.sync.aligned.m64n8k16.f32.bf16.bf16 {%0, %1, %2, %3}, %4, %5, p, 1, 1, %8, %7;\n}\n"
    : "+f"(d[0]), "+f"(d[1]), "+f"(d[2]), "+f"(d[3])
    : "l"(da), "l"(db), "r"(scale_d), "n"(TB), "n"(TA));
}

template<int TB> __device__ __forceinline__ void wgmma_rs_n40(float (&d)[20], uint32_t a0, uint32_t a1, uint32_t a2, uint32_t a3, uint64_t db, int scale_d) {
  asm volatile("{\n.reg .pred p;\nsetp.ne.b32 p, %25, 0;\n"
    "wgmma.mma_async.sync.aligned.m64n40k16.f32.bf16.bf16 {%0, %1, %2, %3, %4, %5, %6, %7, %8, %9, %10, %11, %12, %13, %14, %15, %16, %17, %18, %19}, {%20, %21, %22, %23}, %24, p, 1, 1, %26;\n}\n"
    : "+f"(d[0]), "+f"(d[1]), "+f"(d[2]), "+f"(d[3]), "+f"(d[4]), "+f"(d[5]), "+f"(d[6]), "+f"(d[7]), "+f"(d[8]), "+f"(d[9]), "+f"(d[10]), "+f"(d[11]), "+f"(d[12]), "+f"(d[13]), "+f"(d[14]), "+f"(d[15]), "+f"(d[16]), "+f"(d[17]), "+f"(d[18]), "+f"(d[19])
    : "r"(a0), "r"(a1), "r"(a2), "r"(a3), "l"(db), "r"(scale_d), "n"(TB));
}

#define DEVI __device__ __forceinline__
DEVI uint32_t smem_u32(const void* p) { return (uint32_t)__cvta_generic_to_shared(p); }
DEVI void mbar_init(uint32_t bar, uint32_t cnt) { asm volatile("mbarrier.init.shared::cta.b64 [%0], %1;" :: "r"(bar), "r"(cnt)); }
DEVI void mbar_expect_tx(uint32_t bar, uint32_t bytes) { asm volatile("mbarrier.arrive.expect_tx.shared::cta.b64 _, [%0], %1;" :: "r"(bar), "r"(bytes) : "memory"); }
DEVI void mbar_arrive(uint32_t bar) { asm volatile("mbarrier.arrive.shared::cta.b64 _, [%0];" :: "r"(bar) : "memory"); }
DEVI void mbar_arrive_peer(uint32_t bar) {
  asm volatile("{\n.reg .b32 ra;\nmapa.shared::cluster.u32 ra, %0, %1;\nmbarrier.arrive.shared::cluster.b64 _, [ra];\n}" :: "r"(bar), "r"((blockIdx.x & 1) ^ 1) : "memory");
}
DEVI void bulk_s2peer(uint32_t a, uint32_t bytes, uint32_t bar) {
  asm volatile("{\n.reg .b32 ra, rb;\nmapa.shared::cluster.u32 ra, %0, %3;\nmapa.shared::cluster.u32 rb, %2, %3;\n"
               "cp.async.bulk.shared::cluster.shared::cta.mbarrier::complete_tx::bytes [ra], [%0], %1, [rb];\n}"
               :: "r"(a), "r"(bytes), "r"(bar), "r"((blockIdx.x & 1) ^ 1) : "memory");
}
DEVI void mbar_wait(uint32_t bar, uint32_t parity) {
  asm volatile("{\n.reg .pred p;\nLW:\nmbarrier.try_wait.parity.shared::cta.b64 p, [%0], %1;\n@!p bra LW;\n}" :: "r"(bar), "r"(parity) : "memory");
}
DEVI uint32_t mbar_test(uint32_t bar, uint32_t parity) {
  uint32_t r; asm volatile("{\n.reg .pred p;\nmbarrier.test_wait.parity.shared::cta.b64 p, [%1], %2;\nselp.u32 %0, 1, 0, p;\n}" : "=r"(r) : "r"(bar), "r"(parity) : "memory"); return r;
}
DEVI void mbar_wait_b(uint32_t bar, uint32_t parity) {
  asm volatile("{\n.reg .pred p;\n.reg .u32 it;\nmov.u32 it, 0;\nLW:\nmbarrier.try_wait.parity.shared::cta.b64 p, [%0], %1;\n@p bra LD;\n"
               "add.u32 it, it, 1;\nsetp.lt.u32 p, it, 0x1000000;\n@p bra LW;\ntrap;\nLD:\n}" :: "r"(bar), "r"(parity) : "memory");
}
DEVI void tma_2d(uint32_t dst, const CUtensorMap* m, int c0, int c1, uint32_t bar) {
  asm volatile("cp.async.bulk.tensor.2d.shared::cluster.global.mbarrier::complete_tx::bytes [%0], [%1, {%3, %4}], [%2];"
    :: "r"(dst), "l"(m), "r"(bar), "r"(c0), "r"(c1) : "memory");
}
DEVI void tma_3d(uint32_t dst, const CUtensorMap* m, int c0, int c1, int c2, uint32_t bar) {
  asm volatile("cp.async.bulk.tensor.3d.shared::cluster.global.mbarrier::complete_tx::bytes [%0], [%1, {%3, %4, %5}], [%2];"
    :: "r"(dst), "l"(m), "r"(bar), "r"(c0), "r"(c1), "r"(c2) : "memory");
}
#define POL_EF POL_FIRST
constexpr uint64_t POL_FIRST = 0x12F0000000000000ull, POL_NORMAL = 0x1000000000000000ull;
DEVI void tma_2d_h(uint32_t dst, const CUtensorMap* m, int c0, int c1, uint32_t bar, uint64_t pol) {
  asm volatile("cp.async.bulk.tensor.2d.shared::cluster.global.mbarrier::complete_tx::bytes.L2::cache_hint [%0], [%1, {%3, %4}], [%2], %5;"
    :: "r"(dst), "l"(m), "r"(bar), "r"(c0), "r"(c1), "l"(pol) : "memory");
}
DEVI void tma_3d_h(uint32_t dst, const CUtensorMap* m, int c0, int c1, int c2, uint32_t bar, uint64_t pol) {
  asm volatile("cp.async.bulk.tensor.3d.shared::cluster.global.mbarrier::complete_tx::bytes.L2::cache_hint [%0], [%1, {%3, %4, %5}], [%2], %6;"
    :: "r"(dst), "l"(m), "r"(bar), "r"(c0), "r"(c1), "r"(c2), "l"(pol) : "memory");
}
DEVI void bulk_g2s_h(uint32_t s, const void* g, uint32_t bytes, uint32_t bar, uint64_t pol = POL_EF) {
  asm volatile("cp.async.bulk.shared::cluster.global.mbarrier::complete_tx::bytes.L2::cache_hint [%0], [%1], %2, [%3], %4;"
    :: "r"(s), "l"(g), "r"(bytes), "r"(bar), "l"(pol) : "memory");
}
DEVI void tma_5d(uint32_t dst, const CUtensorMap* m, int c0, int c1, int c2, int c3, int c4, uint32_t bar, uint64_t pol) {
  asm volatile("cp.async.bulk.tensor.5d.shared::cluster.global.mbarrier::complete_tx::bytes.L2::cache_hint [%0], [%1, {%3, %4, %5, %6, %7}], [%2], %8;"
    :: "r"(dst), "l"(m), "r"(bar), "r"(c0), "r"(c1), "r"(c2), "r"(c3), "r"(c4), "l"(pol) : "memory");
}
DEVI void tma_prefetch_2d(const CUtensorMap* m, int c0, int c1) {
  asm volatile("cp.async.bulk.prefetch.tensor.2d.L2.global.tile [%0, {%1, %2}];" :: "l"(m), "r"(c0), "r"(c1) : "memory");
}
DEVI void tma_prefetch_3d(const CUtensorMap* m, int c0, int c1, int c2) {
  asm volatile("cp.async.bulk.prefetch.tensor.3d.L2.global.tile [%0, {%1, %2, %3}];" :: "l"(m), "r"(c0), "r"(c1), "r"(c2) : "memory");
}
DEVI void bulk_prefetch(const void* g, uint32_t bytes) { asm volatile("cp.async.bulk.prefetch.L2.global [%0], %1;" :: "l"(g), "r"(bytes) : "memory"); }
DEVI void bulk_g2s(uint32_t s, const void* g, uint32_t bytes, uint32_t bar) {
  asm volatile("cp.async.bulk.shared::cluster.global.mbarrier::complete_tx::bytes [%0], [%1], %2, [%3];" :: "r"(s), "l"(g), "r"(bytes), "r"(bar) : "memory");
}
DEVI void bulk_s2g(void* g, uint32_t s, uint32_t bytes) {
  asm volatile("cp.async.bulk.global.shared::cta.bulk_group [%0], [%1], %2;\ncp.async.bulk.commit_group;" :: "l"(g), "r"(s), "r"(bytes) : "memory");
}
template<int N> DEVI void bulk_wait() { asm volatile("cp.async.bulk.wait_group %0;" :: "n"(N) : "memory"); }
DEVI void fence_async_smem() { asm volatile("fence.proxy.async.shared::cta;" ::: "memory"); }
DEVI void fence_async_glob() { asm volatile("fence.proxy.async.global;" ::: "memory"); }
DEVI unsigned ld_rlx(const unsigned* p) { unsigned v; asm volatile("ld.relaxed.gpu.global.u32 %0, [%1];" : "=r"(v) : "l"(p) : "memory"); return v; }
DEVI void st_rlx(unsigned* p, unsigned v) { asm volatile("st.relaxed.gpu.global.u32 [%0], %1;" :: "l"(p), "r"(v) : "memory"); }
DEVI uint2 ldg_stream(const uint2* p) { uint2 v; asm volatile("ld.global.nc.L1::no_allocate.v2.u32 {%0, %1}, [%2];" : "=r"(v.x), "=r"(v.y) : "l"(p)); return v; }
DEVI void fence_rel() { asm volatile("fence.release.gpu;" ::: "memory"); }
DEVI uint4 ld_ll(const uint4* p) {
  uint4 v;
  asm volatile("{\n.reg .b128 t;\n.reg .b64 a, b;\nld.relaxed.gpu.global.b128 t, [%4];\nmov.b128 {a, b}, t;\nmov.b64 {%0, %1}, a;\nmov.b64 {%2, %3}, b;\n}"
               : "=r"(v.x), "=r"(v.y), "=r"(v.z), "=r"(v.w) : "l"(p) : "memory");
  return v;
}
DEVI void st_ll(uint4* p, uint32_t x, uint32_t y, uint32_t z, uint32_t w) {
  asm volatile("{\n.reg .b128 t;\n.reg .b64 a, b;\nmov.b64 a, {%1, %2};\nmov.b64 b, {%3, %4};\nmov.b128 t, {a, b};\nst.relaxed.gpu.global.b128 [%0], t;\n}"
               :: "l"(p), "r"(x), "r"(y), "r"(z), "r"(w) : "memory");
}
#define SPIN_MAX 0x1000000
DEVI uint4 poll_ll(const uint4* p, uint32_t mask, uint32_t tag) {
  uint4 v; int it = 0;
  do { v = ld_ll(p); if (++it > SPIN_MAX) __trap(); } while (!__all_sync(0xffffffffu, (v.w & mask) == tag));
  return v;
}
DEVI void poll_ll2(const uint4* p, const uint4* q, uint32_t mask, uint32_t tag, uint4& a, uint4& b) {
  int it = 0;
  do { a = ld_ll(p); b = ld_ll(q); if (++it > SPIN_MAX) __trap(); } while (!__all_sync(0xffffffffu, (a.w & mask) == tag && (b.w & mask) == tag));
}
DEVI void bar_sync(int id, int n) { asm volatile("bar.sync %0, %1;" :: "r"(id), "r"(n) : "memory"); }
DEVI void bar_arrive(int id, int n) { asm volatile("bar.arrive %0, %1;" :: "r"(id), "r"(n) : "memory"); }
DEVI void wg_fence() { asm volatile("wgmma.fence.sync.aligned;" ::: "memory"); }
DEVI void wg_commit() { asm volatile("wgmma.commit_group.sync.aligned;" ::: "memory"); }
template<int N> DEVI void wg_wait() { asm volatile("wgmma.wait_group.sync.aligned %0;" :: "n"(N) : "memory"); }
template<int N> DEVI void reg_inc() { asm volatile("setmaxnreg.inc.sync.aligned.u32 %0;" :: "n"(N)); }
template<int N> DEVI void reg_dec() { asm volatile("setmaxnreg.dec.sync.aligned.u32 %0;" :: "n"(N)); }
DEVI float ex2f(float x) { float y; asm("ex2.approx.ftz.f32 %0, %1;" : "=f"(y) : "f"(x)); return y; }
DEVI uint32_t pack_bf16(float lo, float hi) { uint32_t r; asm("cvt.rn.bf16x2.f32 %0, %1, %2;" : "=r"(r) : "f"(hi), "f"(lo)); return r; }
DEVI float bf_lo(uint32_t v) { return __uint_as_float(v << 16); }
DEVI float bf_hi(uint32_t v) { return __uint_as_float(v & 0xffff0000u); }
DEVI float bf_round(float x) { return bf_lo(pack_bf16(x, 0.f)); }
DEVI void stsm_x4(uint32_t addr, uint32_t a, uint32_t b, uint32_t c, uint32_t d) {
  asm volatile("stmatrix.sync.aligned.m8n8.x4.shared.b16 [%0], {%1,%2,%3,%4};" :: "r"(addr), "r"(a), "r"(b), "r"(c), "r"(d) : "memory");
}
DEVI void ldsm_x4(uint32_t addr, uint32_t& a, uint32_t& b, uint32_t& c, uint32_t& d) {
  asm volatile("ldmatrix.sync.aligned.m8n8.x4.shared.b16 {%0,%1,%2,%3}, [%4];" : "=r"(a), "=r"(b), "=r"(c), "=r"(d) : "r"(addr) : "memory");
}
DEVI uint4 lds128(uint32_t a) { uint4 v; asm volatile("ld.shared.v4.u32 {%0,%1,%2,%3}, [%4];" : "=r"(v.x), "=r"(v.y), "=r"(v.z), "=r"(v.w) : "r"(a) : "memory"); return v; }
DEVI void sts128(uint32_t a, uint4 v) { asm volatile("st.shared.v4.u32 [%0], {%1,%2,%3,%4};" :: "r"(a), "r"(v.x), "r"(v.y), "r"(v.z), "r"(v.w) : "memory"); }
DEVI float2 lds64f(uint32_t a) { float2 v; asm volatile("ld.shared.v2.f32 {%0,%1}, [%2];" : "=f"(v.x), "=f"(v.y) : "r"(a) : "memory"); return v; }
DEVI void sts64f(uint32_t a, float x, float y) { asm volatile("st.shared.v2.f32 [%0], {%1,%2};" :: "r"(a), "f"(x), "f"(y) : "memory"); }
DEVI uint32_t lds32(uint32_t a) { uint32_t v; asm volatile("ld.shared.u32 %0, [%1];" : "=r"(v) : "r"(a) : "memory"); return v; }
DEVI float lds32f(uint32_t a) { return __uint_as_float(lds32(a)); }
DEVI void sts32(uint32_t a, uint32_t v) { asm volatile("st.shared.u32 [%0], %1;" :: "r"(a), "r"(v) : "memory"); }
DEVI void sts32f(uint32_t a, float v) { sts32(a, __float_as_uint(v)); }
DEVI void sts16(uint32_t a, uint32_t v) { asm volatile("st.shared.u16 [%0], %1;" :: "r"(a), "h"((unsigned short)v) : "memory"); }
template<int N> DEVI void keep(float (&d)[N]) {
  #pragma unroll
  for (int i = 0; i < N; i++) asm volatile("" : "+f"(d[i]) :: "memory");
}
template<int N> DEVI void keep(uint32_t (&d)[N]) {
  #pragma unroll
  for (int i = 0; i < N; i++) asm volatile("" : "+r"(d[i]) :: "memory");
}
template<uint32_t HI> DEVI uint64_t mkd(uint32_t lo) { uint64_t r; asm("mov.b64 %0, {%1, %2};" : "=l"(r) : "r"(lo), "n"(HI)); return r; }
constexpr uint32_t HI128 = (1u << 30) | (1024 >> 4), HI64 = (2u << 30) | (512 >> 4);
#define VOFF(x) ((uint32_t)(x) * (uint32_t)(1 - 65536))
DEVI bool elect() { uint32_t p; asm volatile("{\n.reg .pred q;\nelect.sync _|q, 0xffffffff;\nselp.u32 %0, 1, 0, q;\n}" : "=r"(p)); return p; }
DEVI void warp_signal(uint32_t bar) { __syncwarp(); if (elect()) mbar_arrive(bar); }

struct Scratch {
  uint4 kv[128][4][1024];
  uint4 o[8][2][8][2][1024];
  uint4 x[8][16][2048];
  uint4 zero[1024];
  uint4 statP[8][2048];
  uint4 statF[2048];
  uint4 csP[16][8][96];
  uint4 best[8][16];
  uint4 row[16][256];
  uint4 yP[128][112][2];
  uint4 x2[8][256];
  uint4 patch[128][64];
  unsigned flagKV[128][32];
  unsigned flagO[8][32];
  unsigned flagX[8][32];
  unsigned epoch;
};
__device__ __align__(1024) Scratch g_scr;
#define PROFT(cond, slot)
#define PROFW(cond, slot)
#define PROFD(cond, slot)
#define PROFX(cond, slot)
#define PROFY(cond, slot)

constexpr uint32_t SB0 = 65536, HOLE = 90112, SA2 = 98304, SB1 = 131072, SB2 = 155648, STG = 180224;
constexpr uint32_t KVA = 0, KVB = 98304, QO = 65536;
constexpr uint32_t MISC = 229376, CS = MISC, ONES = MISC + 768, BARS = MISC + 1792, INFO = MISC + 2208, WR = MISC + 2224, X2SEG = MISC + 2736, INFO2 = MISC + 2992, DUMP = MISC + 3040;
constexpr uint32_t PAR = HOLE, HV = HOLE + 2048, RED = HOLE + 6144, PATCH = 196608;
constexpr uint32_t SMEM_BYTES = 232448;
enum { B_FULLQ = 0, B_EMPTYQ = 3, B_FULLW = 6, B_EMPTYW = 12, B_HAFREE = 18, B_OFREE = 20,
       B_XFREE = 21,
       B_KVRDY = 23, B_ORDY = 27, B_XRDY = 35, B_STGE = 39,
       B_KVFULL = 42, B_RES = 46, B_PAR = 47, B_STG = 48, B_PFREE = 51, B_COUNT = 52,
       B_ROW = 154 };
#define BAR(x) (sb + BARS + 8 * (x))
DEVI uint32_t qa_off(int s) { return s == 2 ? SA2 : (uint32_t)s * 32768u; }
DEVI uint32_t qb_off(int s) { return s == 0 ? SB0 : (s == 1 ? SB1 : SB2); }
DEVI int kb_order(int bc, int n) {
  const int e = n < 9 ? n - 2 : n - 9;
  return n < 2 ? 2 * bc + n : 2 * (((e < 4 ? e + 4 : e - 4 + (e - 4 >= (bc & 3))) + (bc & 4)) & 7) + (n >= 9);
}
DEVI int wo_order(int bc, int n) { return (n & 8) | ((n + (bc & 6)) & 7); }
DEVI uint32_t w_off(int s) { return (uint32_t)((0x143065 >> (4 * s)) & 7) * 32768u; }
DEVI uint32_t w_par(int n, int s, int L) { return (n >= 6 && n < 12) ^ (s == 5) ^ (s != 2 && L); }
DEVI int w_next(int n, int s) { return s == 5 ? 0 : (n == 13 ? 3 : s + 1); }

struct Params {
  CUtensorMap mX, mXh, mWq, mWo, mWg, mWu, mWp, mWd;
  const bf16 *x0, *wqkv, *wo, *wr, *wg, *wu, *wd;
  bf16* out;
  Scratch* g;
  unsigned map[128];
};
#define BID ((int)(P.map[blockIdx.x] & 255))
#define FID ((int)(P.map[blockIdx.x] >> 8))
DEVI uint32_t uni(uint32_t v) { return __shfl_sync(0xffffffffu, v, 0); }
#define PQ_N 8
#define PQ_T 700
#define PF0_N 10
#define PF0_T 1600
#define PF1_E 24
#define PF1_T 1100
#define POL_Q1 POL_NORMAL
#define POL_X POL_NORMAL
#define PFA0_BAR 3
#define PFA1_BAR 0
#define PFA0_M 0
#define PFA1_M 0
#define PFA0_T 900
#define PFA1_T 700
#define PF1_S PF0_N
#define PF1_D 0
#define POL_G POL_NORMAL
#define POL_U POL_FIRST
#define POL_D POL_FIRST
#define JQ_N 6
#define WDSRC (P.wd + (size_t)min(fid, 111) * 32768)
#define WDSRC2 (P.wd + FID * 32768)
#define WD_N 4
#define THR_N 5
#define KV_D 1800
#define XD_D 300
#define W0_BAR 3
#define QEF_N 99
#define PACE_T 300
#define IDLE_T 11000
#define POL_Q0 POL_NORMAL
constexpr float LN_EPS = 1e-5f;
constexpr float QSCALE = 0.17677669529663687f * 1.4426950408889634f;

DEVI void fma8(float (&a)[8], uint4 v, float h) {
  a[0] = fmaf(bf_lo(v.x), h, a[0]); a[1] = fmaf(bf_hi(v.x), h, a[1]); a[2] = fmaf(bf_lo(v.y), h, a[2]); a[3] = fmaf(bf_hi(v.y), h, a[3]);
  a[4] = fmaf(bf_lo(v.z), h, a[4]); a[5] = fmaf(bf_hi(v.z), h, a[5]); a[6] = fmaf(bf_lo(v.w), h, a[6]); a[7] = fmaf(bf_hi(v.w), h, a[7]);
}
DEVI uint4 ldsv128(uint32_t a) { uint4 v; asm volatile("ld.volatile.shared.v4.u32 {%0,%1,%2,%3}, [%4];" : "=r"(v.x), "=r"(v.y), "=r"(v.z), "=r"(v.w) : "r"(a) : "memory"); return v; }
DEVI float ldsv32f(uint32_t a) { float v; asm volatile("ld.volatile.shared.f32 %0, [%1];" : "=f"(v) : "r"(a) : "memory"); return v; }
DEVI uint32_t clk() { uint32_t t; asm volatile("mov.u32 %0, %%clock;" : "=r"(t)); return t; }
DEVI int fresh_tid() { int t; asm volatile("mov.u32 %0, %%tid.x;" : "=r"(t)); return t & 127; }
DEVI float fold8(const float (&a)[8]) {
  const int lane = threadIdx.x & 31;
  const bool u = lane & 16, v = lane & 8, x = lane & 4;
  float b0 = (u ? a[4] : a[0]) + __shfl_xor_sync(0xffffffffu, u ? a[0] : a[4], 16), b1 = (u ? a[5] : a[1]) + __shfl_xor_sync(0xffffffffu, u ? a[1] : a[5], 16);
  float b2 = (u ? a[6] : a[2]) + __shfl_xor_sync(0xffffffffu, u ? a[2] : a[6], 16), b3 = (u ? a[7] : a[3]) + __shfl_xor_sync(0xffffffffu, u ? a[3] : a[7], 16);
  float c0 = (v ? b2 : b0) + __shfl_xor_sync(0xffffffffu, v ? b0 : b2, 8), c1 = (v ? b3 : b1) + __shfl_xor_sync(0xffffffffu, v ? b1 : b3, 8);
  return (x ? c1 : c0) + __shfl_xor_sync(0xffffffffu, x ? c0 : c1, 4);
}
DEVI float swiglu(float g, float u) { g = bf_round(g); return bf_round(bf_round(__fdividef(g, 1.f + __expf(-g))) * bf_round(u)); }

DEVI void qk_issue(float (&s)[32], uint32_t qd, uint32_t kd) {
  wgmma_ss_n64<0>(s, mkd<HI64>(qd), mkd<HI64>(kd), 0);
  wgmma_ss_n64<0>(s, mkd<HI64>(qd + 2), mkd<HI64>(kd + 2), 1);
}
template<int J0, int J1> DEVI void exp_pack(const float (&s)[32], uint32_t (&p)[16]) {
  #pragma unroll
  for (int j = J0; j < J1; j++) p[j] = pack_bf16(ex2f(s[2 * j]), ex2f(s[2 * j + 1]));
}
DEVI bool attn_pack(const float (&o)[20], uint32_t (&ob)[8]) {
  const float lo = 5.421010862427522e-20f, hi = 1.8446744073709552e19f;
  float i0, i1; asm("rcp.approx.ftz.f32 %0, %1;" : "=f"(i0) : "f"(o[16])); asm("rcp.approx.ftz.f32 %0, %1;" : "=f"(i1) : "f"(o[18]));
  #pragma unroll
  for (int e = 0; e < 8; e++) ob[e] = pack_bf16(o[2 * e] * ((e & 1) ? i1 : i0), o[2 * e + 1] * ((e & 1) ? i1 : i0));
  return __all_sync(0xffffffffu, o[16] >= lo && o[16] <= hi && o[18] >= lo && o[18] <= hi);
}
DEVI void attn_store(const uint32_t (&ob)[8], bool ok, uint32_t st, uint32_t sb, uint32_t bar) {
  stsm_x4(ok ? st : sb + DUMP, ob[0], ob[1], ob[2], ob[3]); stsm_x4(ok ? st ^ 32 : sb + DUMP, ob[4], ob[5], ob[6], ob[7]);
  __syncwarp();
  asm volatile("{\n.reg .pred p, q;\nelect.sync _|q, 0xffffffff;\nsetp.ne.and.u32 p, %1, 0, q;\n@p mbarrier.arrive.shared::cta.b64 _, [%0];\n}" :: "r"(bar), "r"((uint32_t)ok) : "memory");
}
DEVI void attn_exact(uint32_t st, uint32_t kv, int t, bool hasprev, uint32_t bar) {
  const int lane = threadIdx.x & 31;
  #pragma unroll 1
  for (int row = ((threadIdx.x >> 5) & 3) * 16, n = 0; n < 16; n++, row++) {
    const int k1 = 256 + t * 64 + row;
    float m = -INFINITY, l = 0.f, o = 0.f;
    #pragma unroll 1
    for (int k0 = hasprev ? k1 - 255 : 256; k0 <= k1; k0 += 32) {
      const int k = min(k0 + lane, k1), r = k & 63;
      float sc = 0.f;
      #pragma unroll 1
      for (int c = 0; c < 16; c++) {
        uint32_t a = lds32(st + row * 64 + ((c * 4) ^ ((row & 6) << 3))), b = lds32(kv + (k >> 6) * 8192 + r * 64 + ((c * 4) ^ ((r & 6) << 3)));
        sc = fmaf(bf_lo(a), bf_lo(b), fmaf(bf_hi(a), bf_hi(b), sc));
      }
      float mn = fmaxf(m, sc);
      #pragma unroll 1
      for (int x = 16; x; x >>= 1) mn = fmaxf(mn, __shfl_xor_sync(0xffffffffu, mn, x));
      const float al = ex2f(m - mn), pr = ex2f(sc - mn);
      m = mn; l *= al; o *= al;
      #pragma unroll 1
      for (int q = k0; q <= min(k0 + 31, k1); q++) {
        const float z = __shfl_sync(0xffffffffu, pr, q - k0);
        uint32_t b = lds32(kv + (q >> 6) * 8192 + 4096 + (q & 63) * 64 + (((lane >> 1) * 4) ^ ((q & 6) << 3)));
        l += z; o = fmaf(z, (lane & 1) ? bf_hi(b) : bf_lo(b), o);
      }
    }
    __syncwarp();
    sts16(st + row * 64 + ((lane * 2) ^ ((row & 6) << 3)), pack_bf16(__fdividef(o, l), 0.f));
  }
  warp_signal(bar);
}

template<int K0, int K1, int DONE = 0> DEVI void exp_pv(const float (&s)[32], uint32_t (&p)[16], float (&o)[20], uint32_t vd, bool accum) {
  #pragma unroll
  for (int ks = K0; ks < K1; ks++) {
    if (ks >= DONE) {
      #pragma unroll
      for (int j = 4 * ks; j < 4 * ks + 4; j++) p[j] = pack_bf16(ex2f(s[2 * j]), ex2f(s[2 * j + 1]));
    }
    asm volatile("" : "+r"(p[4 * ks]), "+r"(p[4 * ks + 1]), "+r"(p[4 * ks + 2]), "+r"(p[4 * ks + 3]));
    wg_fence();
    wgmma_rs_n40<1>(o, p[ks * 4], p[ks * 4 + 1], p[ks * 4 + 2], p[ks * 4 + 3], mkd<HI64>(vd + VOFF(ks * 64)), ks ? 1 : accum);
  }
}
DEVI void exp_pv2(const float (&s)[32], const float (&sx)[32], uint32_t (&p)[16], uint32_t (&px)[16], float (&o)[20], uint32_t v0, uint32_t v4,
                  const uint32_t (&msk)[9], int tdiag) {
  #pragma unroll
  for (int ks = 0; ks < 4; ks++) {
    #pragma unroll
    for (int j = 4 * ks; j < 4 * ks + 4; j++) {
      const int c = 8 * (j >> 1) - 8 * (j & 1);
      const uint32_t e = pack_bf16(ex2f(c > tdiag ? s[2 * j] : sx[2 * j]), ex2f(c + 1 > tdiag ? s[2 * j + 1] : sx[2 * j + 1])), m = msk[(j >> 1) - (j & 1) + 1];
      p[j] = e & m; px[j] = e & ~m;
      asm volatile("" : "+r"(p[j]), "+r"(px[j]));
    }
    wg_fence();
    wgmma_rs_n40<1>(o, p[ks * 4], p[ks * 4 + 1], p[ks * 4 + 2], p[ks * 4 + 3], mkd<HI64>(v0 + VOFF(ks * 64)), 1);
    wgmma_rs_n40<1>(o, px[ks * 4], px[ks * 4 + 1], px[ks * 4 + 2], px[ks * 4 + 3], mkd<HI64>(v4 + VOFF(ks * 64)), 1);
  }
}

template<int J0> DEVI void qkv_store(const float (&a)[96], float p0, float p1, uint32_t d) {
  #pragma unroll
  for (int hh = 0; hh < 2; hh++) {
    const int j = 4 * (J0 + 2 * hh);
    stsm_x4(d ^ (hh << 5), pack_bf16(a[j] * p0, a[j + 1] * p0), pack_bf16(a[j + 2] * p1, a[j + 3] * p1),
                           pack_bf16(a[j + 4] * p0, a[j + 5] * p0), pack_bf16(a[j + 6] * p1, a[j + 7] * p1));
  }
}
DEVI void mean_step(float (&a)[96], float m0, float m1, uint32_t cd, bool z) {
  const uint32_t u0 = z ? 0u : __float_as_uint(m0), u1 = z ? 0u : __float_as_uint(m1);
  uint32_t ma[4] = {__byte_perm(u0, 0u, 0x1010), __byte_perm(u1, 0u, 0x1010), __byte_perm(u0, 0u, 0x3232), __byte_perm(u1, 0u, 0x3232)};
  keep(ma);
  wg_fence();
  wgmma_rs_n192<1>(a, ma[0], ma[1], ma[2], ma[3], mkd<2>(cd), 1);
  wg_commit();
}

template<bool FIRST> DEVI void qkv_block(float (&aX)[96], float (&aY)[96], uint32_t sb16, int s, int tX, int tY) {
  uint32_t a16 = sb16 + (qa_off(s) >> 4), b16 = (sb16 + (qb_off(s) >> 4)) | ((8192u >> 4) << 16);
  uint32_t ax = (a16 + tX * 512) | 0x10000u, ay = (a16 + tY * 512) | 0x10000u;
  wg_fence();
  #pragma unroll
  for (int ks = 0; ks < 4; ks++) {
    wgmma_ss_n192<1>(aX, mkd<HI128>(ax + ks * 2), mkd<HI128>(b16 + ks * 128), !(FIRST && ks == 0));
    wgmma_ss_n192<1>(aY, mkd<HI128>(ay + ks * 2), mkd<HI128>(b16 + ks * 128), !(FIRST && ks == 0));
  }
  wg_commit();
}
DEVI void qkv_half(float (&a)[96], uint32_t sb16, int t, uint32_t sa, uint32_t sbb) {
  wg_fence();
  #pragma unroll
  for (int ks = 0; ks < 4; ks++)
    wgmma_ss_n192<1>(a, mkd<HI128>(((sb16 + (sa >> 4) + t * 512) | 0x10000u) + ks * 2), mkd<HI128>(((sb16 + (sbb >> 4)) | ((8192u >> 4) << 16)) + ks * 128), 1);
  wg_commit();
}
DEVI void wo_block(float (&acc)[64], uint32_t sb16, int s, int wg) {
  uint32_t a16 = (sb16 + (w_off(s) >> 4) + wg * 256) | 0x10000u, b16 = (sb16 + (w_off(s) >> 4) + 1024) | ((8192u >> 4) << 16);
  wg_fence();
  #pragma unroll
  for (int ks = 0; ks < 4; ks++)
    wgmma_ss_n128<1>(acc, mkd<HI64>(a16 + (ks >> 1) * 512 + (ks & 1) * 2), mkd<HI128>(b16 + ks * 128), 1);
  wg_commit();
}
DEVI void consumer(const Params& P, uint32_t sb, int wg) {
  const int w = uni((threadIdx.x >> 5) & 3);
  #define LAYER uni(mbar_test(BAR(B_XRDY + wg * 2 + 1), 0))
  #define IDS L = LAYER; const int tid = fresh_tid(), lane = tid & 31
  const uint32_t ids = uni(P.map[blockIdx.x]);
  const int bi = (ids >> 4) & 7, rh = ids & 1, bc = (ids & 15) >> 1, fid = ids >> 8;
  const int tX = 3 - wg, tY = wg;
  constexpr uint32_t sb16 = 1024 >> 4;
  #pragma unroll 1
  while (true) {
    int L = LAYER;
    {
      float aX[96], aY[96];
      const bool lead = fresh_tid() == 0;
      mbar_wait(BAR(B_FULLQ), 0);
      PROFW(threadIdx.x == 0, L * 8 + 1);
      qkv_block<true>(aX, aY, sb16, 0, tX, tY);
      #pragma unroll 1
      for (int n = 1, s = 1, ps = 0, ph = 0; n < 14; n++) {
        mbar_wait(BAR(B_FULLQ + s), ph ^ (s ? L : 0));
        PROFD(threadIdx.x == 0 && L && (n == 2 || n == 3 || n == 7 || n == 11 || n == 13), n == 2 ? 48 : 49 + (n >> 2));
        qkv_block<false>(aX, aY, sb16, s, tX, tY);
        wg_wait<1>(); if (lead) mbar_arrive(BAR(B_EMPTYQ + ps));
        ps = s; if (s == 2) { s = 0; ph ^= 1; } else s++;
      }
      mbar_wait(BAR(B_FULLQ + 2), L);
      qkv_half(aX, sb16, tX, SA2, SB2);
      mbar_wait(BAR(B_ROW), L);
      IDS;
      const uint32_t pa = sb + PAR + (w * 16 + (lane >> 2)) * 8;
      float2 p0 = lds64f(pa + tX * 512), p1 = lds64f(pa + tX * 512 + 64), p2 = lds64f(pa + tY * 512), p3 = lds64f(pa + tY * 512 + 64);
      mean_step(aX, p0.y, p1.y, sb16 + (CS >> 4), lane & 3);
      mbar_wait(BAR(B_FULLQ), 1);
      qkv_half(aX, sb16, tX, 0, SB0);
      wg_wait<3>(); if (lead) mbar_arrive(BAR(B_EMPTYQ + 1));
      bar_sync(1, 256);
      qkv_half(aY, sb16, tY, SA2, SB2);
      wg_wait<1>(); keep(aX);
      const int srow = w * 16 + (lane & 15);
      const uint32_t x0 = sb + srow * 64 + (((lane >> 4) ^ ((srow >> 1) & 3)) << 4), xX = x0 + (4 + tX) * 8192, xY = x0 + (4 + tY) * 8192;
      qkv_store<8>(aX, p0.x, p1.x, xX + KVA); qkv_store<16>(aX, p0.x, p1.x, xX + KVA + 4096);
      warp_signal(BAR(B_KVRDY + wg * 2));
      qkv_half(aY, sb16, tY, 0, SB0);
      mean_step(aY, p2.y, p3.y, sb16 + (CS >> 4), fresh_tid() & 3);
      wg_wait<2>(); if (lead) mbar_arrive(BAR(B_EMPTYQ + 2));
      mbar_wait(BAR(B_EMPTYQ + 2), L);
      qkv_store<12>(aX, p0.x, p1.x, xX + KVB); qkv_store<20>(aX, p0.x, p1.x, xX + KVB + 4096);
      wg_wait<0>(); keep(aY);
      if (lead) mbar_arrive(BAR(B_EMPTYQ));
      PROFW(threadIdx.x == 0, L * 8 + 2);
      qkv_store<8>(aY, p2.x, p3.x, xY + KVA); qkv_store<16>(aY, p2.x, p3.x, xY + KVA + 4096);
      qkv_store<12>(aY, p2.x, p3.x, xY + KVB); qkv_store<20>(aY, p2.x, p3.x, xY + KVB + 4096);
      warp_signal(BAR(B_KVRDY + wg * 2 + 1));
      p0.x *= QSCALE; p1.x *= QSCALE; p2.x *= QSCALE; p3.x *= QSCALE;
      mbar_wait(BAR(B_EMPTYQ), 1);
      qkv_store<0>(aX, p0.x, p1.x, x0 + QO + tX * 4096);
      qkv_store<0>(aY, p2.x, p3.x, x0 + QO + tY * 4096); qkv_store<4>(aY, p2.x, p3.x, x0 + QO + 16384 + tY * 4096);
      mbar_wait(BAR(B_PAR), L);
      qkv_store<4>(aX, p0.x, p1.x, x0 + QO + 16384 + tX * 4096);
      const int prow = (int)uni(lds32(sb + INFO)) - bi * 256;
      if ((prow >> 4) == tX * 4 + w || (prow >> 4) == tY * 4 + w) {
        __syncwarp();
        if (lane < 24) sts128(sb + (prow & 63) * 64 + (((lane ^ (prow >> 1)) & 3) << 4) +
                              (lane < 8 ? QO + (lane >> 2) * 16384 + (prow >> 6) * 4096 : ((lane & 4) ? KVB : KVA) + (4 + (prow >> 6)) * 8192 + (lane >> 4) * 4096),
                              lds128(sb + PATCH + lane * 16));
      }
      fence_async_smem();
      bar_sync(1, 256);
    }
    PROFW(threadIdx.x == 0, L * 8 + 3);
    float2 fa, fb;
    { const float2* f = (const float2*)&P.g->statF[bi * 256 + rh * 128 + (wg ^ rh) * 64 + w * 16 + ((fresh_tid() & 31) >> 2)];
      fa = __ldcg(f); fb = __ldcg(f + 16); }
    {
      IDS;
      float s0[32], s1[32], sx[32], o[20], op[20];
      uint32_t p0[16], p1[16], px[16], msk[9];
      const int tdiag = w * 16 + (lane >> 2) - 2 * (lane & 3);
      #pragma unroll
      for (int e = 0; e < 9; e++) msk[e] = ((8 * e - 8 > tdiag) ? 0xFFFFu : 0u) | ((8 * e - 7 > tdiag) ? 0xFFFF0000u : 0u);
      keep(msk);
      const uint32_t ones = (sb16 + (ONES >> 4)) << 16;
      const uint32_t qX = (sb16 + (QO >> 4) + tX * 256) | 0x10000u, qY = (sb16 + (QO >> 4) + tY * 256) | 0x10000u;
      const uint32_t kXB = (sb16 + (KVB >> 4) + tX * 512) | 0x10000u;
      uint32_t redo = 0;
      const uint32_t ost = sb + QO + (w * 16 + (lane & 15)) * 64 + (((lane >> 4) ^ ((lane >> 1) & 3)) << 4);
      #define QK(s, q, k) do { wg_fence(); qk_issue(s, q, k); wg_commit(); } while (0)
      #define QK2(q, k) do { wg_fence(); qk_issue(s1, q, k); qk_issue(sx, q, (k) + 2048); wg_commit(); } while (0)
      #define VB(v, b) ((v) + VOFF((b) * 512))
      QK(s0, qX + 1024, kXB + 1536);
      #pragma unroll
      for (int e = 0; e < 20; e++) o[e] = 0.f;
      wg_wait<0>(); keep(s0);
      #pragma unroll 1
      for (int h = 1; h >= 0; h--) {
        const uint32_t kXA = kXB - ((KVB - KVA) >> 4), kX = h ? kXB : kXA, vX = VOFF((kX & 0xffffu) + 256) + ones;
        QK(s1, qX + h * 1024, kX + 1024);
        #pragma unroll
        for (int e = 0; e < 20; e++) op[e] = o[e];
        keep(op);
        exp_pv<0, 4>(s0, p0, o, VB(vX, 3), false); wg_commit();
        wg_wait<1>(); keep(s1);
        exp_pv<0, 2>(s1, p1, o, VB(vX, 2), true);
        bar_sync(h ? 12 + wg : 4 + wg * 4, h ? 128 : 160);
        QK(s0, qX, kXA + 512 + h * 1024);
        exp_pv<2, 4>(s1, p1, o, VB(vX, 2), true); wg_commit();
        wg_wait<0>(); keep(s0); keep(p0); keep(p1); keep(o);
      }
      #pragma unroll 1
      for (int h = 0; h < 2; h++) {
        const uint32_t kb16 = sb16 + ((h ? KVB : KVA) >> 4), kY = (kb16 + tY * 512) | 0x10000u, qy = qY + h * 1024;
        const uint32_t onesP = bi ? ones : (kb16 + 1984) << 16;
        const uint32_t vX = VOFF(kb16 + tX * 512 + 256), vY = VOFF(kb16 + tY * 512 + 256);
        uint32_t ob[8];
        QK2(qX + h * 1024, (kb16 + tX * 512) | 0x10000u);
        exp_pv<0, 4>(s0, p0, o, VB(vX + (wg ? onesP : ones), 1), true); wg_commit();
        wg_wait<1>(); keep(s1); keep(sx);
        QK(s0, qy, kY + 1536);
        exp_pv2(s1, sx, p1, px, o, vX + onesP, VB(vX + ones, 4), msk, tdiag); wg_commit();
        wg_wait<1>(); keep(s0); keep(p0);
        QK(s1, qy, kY + 1024);
        exp_pack<0, 4>(s0, p0);
        wg_wait<1>(); keep(o); keep(p1); keep(px);
        bool ok = attn_pack(o, ob); keep(ob);
        exp_pv<0, 4, 1>(s0, p0, o, VB(vY + (wg ? ones : onesP), 3), false); wg_commit();
        attn_store(ob, ok, ost + (h * 4 + tX) * 4096, sb, BAR(B_ORDY + wg * 4 + h * 2)); redo |= ok ? 0u : 1u << (h * 2);
        wg_wait<1>(); keep(s1);
        exp_pv<0, 2>(s1, p1, o, VB(vY + onesP, 2), true);
        bar_sync(5 + wg * 4 + h * 2, 160);
        QK(s0, qy, kY + 512);
        exp_pv<2, 4>(s1, p1, o, VB(vY + onesP, 2), true); wg_commit();
        wg_wait<1>(); keep(s0); keep(p0);
        QK2(qy, kY);
        exp_pv<0, 4>(s0, p0, o, VB(vY + onesP, 1), true); wg_commit();
        wg_wait<1>(); keep(s1); keep(sx); keep(p1);
        bar_sync(6 + wg * 4, h ? 128 : 160);
        QK(s0, h ? qy : qX + 1024, kXB + 512);
        exp_pv2(s1, sx, p1, px, o, vY + onesP, VB(vY + ones, 4), msk, tdiag); wg_commit();
        wg_wait<0>(); keep(o); keep(s0); keep(p0); keep(p1); keep(px);
        ok = attn_pack(o, ob); attn_store(ob, ok, ost + (h * 4 + tY) * 4096, sb, BAR(B_ORDY + wg * 4 + h * 2 + 1)); redo |= ok ? 0u : 2u << (h * 2);
        #pragma unroll
        for (int e = 0; e < 20; e++) o[e] = op[e];
      }
      #undef QK
      #undef QK2
      #undef VB
      if (redo) {
        #pragma unroll 1
        for (int u = 0; u < 4; u++) if ((redo >> u) & 1) {
          const int h = u >> 1, t = (u & 1) ? tY : tX;
          attn_exact(sb + QO + (h * 4 + t) * 4096, sb + (h ? KVB : KVA), t, bi > 0, BAR(B_ORDY + wg * 4 + u));
        }
      }
    }
    PROFW(threadIdx.x == 0, L * 8 + 4);
    {
      IDS;
      const int t256 = wg * 128 + tid;
      float acc[64];
      const int tt = wg ^ rh;
      const int grow = bi * 256 + rh * 128 + tt * 64 + w * 16 + (lane >> 2);
      float al0 = 1.f, be0 = 0.f, al1 = 1.f, be1 = 0.f;
      const int idx0 = (int)uni(lds32(sb + INFO));
      const uint32_t tag = lds32(sb + INFO + 8) + L;
      uint4* const sp = &P.g->statP[bc][grow + (lane & 1) * 8];
      uint4* const yp = &P.g->yP[t256 >> 1][min(fid, 111)][t256 & 1];
      if (L) {
        float r0 = rsqrtf(fa.y + LN_EPS), r1 = rsqrtf(fb.y + LN_EPS);
        if (grow != idx0) { al0 = 1.f + r0; be0 = -fa.x * r0; }
        if (grow + 8 != idx0) { al1 = 1.f + r1; be1 = -fb.x * r1; }
      }
      const int srow = tt * 64 + w * 16 + (lane & 15);
      const uint32_t ra = sb + srow * 128 + (((lane >> 4) ^ (srow & 7)) << 4);
      mbar_wait(BAR(B_FULLW + 5), L);
      if ((idx0 >> 4) == bi * 16 + rh * 8 + tt * 4 + w) {
        int r = idx0 & 127;
        if (lane < 16) sts128(sb + 32768 + (lane >> 3) * 16384 + r * 128 + (((lane & 7) ^ (r & 7)) << 4), lds128(sb + X2SEG + lane * 16));
        fence_async_smem();
        __syncwarp();
      }
      #pragma unroll
      for (int jj = 0; jj < 8; jj++) {
        uint32_t r[4]; ldsm_x4((ra + 32768 + (jj >> 2) * 16384) ^ ((jj & 3) << 5), r[0], r[1], r[2], r[3]);
        #pragma unroll
        for (int e = 0; e < 4; e++) {
          acc[8 * jj + 2 * e] = fmaf(bf_lo(r[e]), (e & 1) ? al1 : al0, (e & 1) ? be1 : be0);
          acc[8 * jj + 2 * e + 1] = fmaf(bf_hi(r[e]), (e & 1) ? al1 : al0, (e & 1) ? be1 : be0);
        }
      }
      keep(acc);
      bar_sync(12 + wg, 128);
      if (!(lane & 2)) st_ll(sp, 0u, 0u, 0u, 0u);
      uint2 wd[4];
      #pragma unroll
      for (int e = 0; e < 4; e++) { wd[e] = make_uint2(0u, 0u); if (L) wd[e] = ldg_stream((const uint2*)(WDSRC) + t256 + (28 + e) * 256); }
      PROFW(t256 == 0, L * 8 + 5);
      #pragma unroll 1
      for (int n = 0, q = 0, pq = 5; n < 16; n++) {
        mbar_wait(BAR(B_FULLW + q), w_par(n, q, L));
        PROFD(t256 == 0 && !L && (n == 4 || n == 7 || n == 8 || n == 12), (n == 7 ? 63 : 41 + (n >> 2)));
        wo_block(acc, sb16, q, tt);
        wg_wait<1>(); if (tid == 0) mbar_arrive(BAR(B_EMPTYW + pq));
        pq = q; q = w_next(n, q);
      }
      mbar_wait(BAR(B_EMPTYW + 5), L);
      wg_wait<0>(); keep(acc);
      if (tid == 0) mbar_arrive(BAR(B_EMPTYW + 4));
      PROFW(t256 == 0, L * 8 + 6);
      const uint32_t xa = ra + rh * 16384;
      #pragma unroll
      for (int jj = 0; jj < 8; jj++) {
        const float* a = acc + 8 * jj;
        stsm_x4((xa + (jj >> 2) * 32768) ^ ((jj & 3) << 5), pack_bf16(a[0], a[1]), pack_bf16(a[2], a[3]), pack_bf16(a[4], a[5]), pack_bf16(a[6], a[7]));
        if (jj == 7) fence_async_smem();
        if ((jj & 3) == 3) warp_signal(BAR(B_XRDY + wg * 2 + (jj >> 2)));
      }
      {
        float s1a = 0.f, s2a = 0.f, da = 0.f, s1b = 0.f, s2b = 0.f, db = 0.f;
        #pragma unroll
        for (int j = 0; j < 16; j++) {
          const float* a = acc + 4 * j; float2 wv = lds64f(sb + WR + j * 32 + (lane & 3) * 8);
          s1a += a[0] + a[1]; s1b += a[2] + a[3];
          s2a = fmaf(a[0], a[0], s2a); s2b = fmaf(a[2], a[2], s2b); s2a = fmaf(a[1], a[1], s2a); s2b = fmaf(a[3], a[3], s2b);
          da = fmaf(a[0], wv.x, da); db = fmaf(a[2], wv.x, db); da = fmaf(a[1], wv.y, da); db = fmaf(a[3], wv.y, db);
        }
        bool odd = lane & 1;
        float u1 = (odd ? s1b : s1a) + __shfl_xor_sync(0xffffffffu, odd ? s1a : s1b, 1);
        float u2 = (odd ? s2b : s2a) + __shfl_xor_sync(0xffffffffu, odd ? s2a : s2b, 1);
        float u3 = (odd ? db : da) + __shfl_xor_sync(0xffffffffu, odd ? da : db, 1);
        u1 += __shfl_xor_sync(0xffffffffu, u1, 2); u2 += __shfl_xor_sync(0xffffffffu, u2, 2); u3 += __shfl_xor_sync(0xffffffffu, u3, 2);
        if (!(lane & 2)) st_ll(sp, __float_as_uint(u1), __float_as_uint(u2), __float_as_uint(u3), tag);
      }
      PROFW(t256 == 0, L * 8 + 7);
      if (L) {
        mbar_wait(BAR(B_PAR), 0);
        { float2 pa = lds64f(sb + PAR + (grow & 127) * 8), pb = lds64f(sb + PAR + (grow & 127) * 8 + 64); al0 = pa.x; be0 = pa.y; al1 = pb.x; be1 = pb.y; }
        uint32_t rs[32];
        #pragma unroll
        for (int j = 0; j < 16; j++) {
          rs[2 * j] = pack_bf16(fmaf(acc[4 * j], al0, be0), fmaf(acc[4 * j + 1], al0, be0));
          rs[2 * j + 1] = pack_bf16(fmaf(acc[4 * j + 2], al1, be1), fmaf(acc[4 * j + 3], al1, be1));
        }
        #pragma unroll
        for (int jj = 0; jj < 8; jj++) stsm_x4((xa + (jj >> 2) * 32768) ^ ((jj & 3) << 5), rs[4 * jj], rs[4 * jj + 1], rs[4 * jj + 2], rs[4 * jj + 3]);
        PROFW(t256 == 0, 16);
        if (fid >= 112) bar_arrive(3, 384);
        else {
          float d[4] = {0.f, 0.f, 0.f, 0.f};
          mbar_wait(BAR(B_FULLW + wg * 3), 0); mbar_wait(BAR(B_FULLW + wg * 3 + 1), 0);
          bar_sync(3, 384);
          PROFW(t256 == 0, 29);
          #pragma unroll 1
          for (int g = 0; g < 4; g++) {
            const uint32_t ad = (sb16 + (wg ? 6144 : 10240) + (g >> 1) * 2048 + (g & 1) * 512) | (1024u << 16), bd = (sb16 + (HV >> 4) + wg * 64 + g * 16) | 0x10000u;
            wg_fence();
            #pragma unroll
            for (int ks = 0; ks < 8; ks++) wgmma_ss_n8<0, 1>(d, mkd<HI64>(ad + ks * 64), mkd<8>(bd + ks * 2), 1);
            wg_commit();
          }
          mbar_wait(BAR(B_FULLW + 2), 0);
          wg_wait<0>(); keep(d);
          if (!(lane & 3)) { sts32f(sb + PAR + 1024 + wg * 256 + w * 64 + lane, d[0]); sts32f(sb + PAR + 1056 + wg * 256 + w * 64 + lane, d[2]); }
          bar_sync(1, 256);
          const uint32_t ga = sb + PAR + 1024 + lane * 4, aa = sb + HV + (t256 >> 5) * 128;
          sts32f(aa + lane * 4, swiglu(lds32f(ga) + lds32f(ga + 256), lds32f(ga + 128) + lds32f(ga + 384)));
          __syncwarp();
          PROFW(t256 == 0, 26);
          float y0 = 0.f, y1 = 0.f, y2 = 0.f, y3 = 0.f;
          uint32_t tbl = rh ? 0x001459a8u : 0x023679a8u;
          uint4 a4 = lds128(aa + 112);
          #pragma unroll 2
          for (int n = 0; n < 8; n++, tbl >>= 4) {
            const uint32_t src = sb + t256 * 8 + (tbl & 15) * 8192;
            const uint4 an = lds128(aa + ((0x00123564u >> (4 * n)) & 15) * 16);
            #pragma unroll
            for (int e = 0; e < 4; e++) {
              const float av = __uint_as_float(e == 0 ? a4.x : (e == 1 ? a4.y : (e == 2 ? a4.z : a4.w)));
              y0 = fmaf(bf_lo(wd[e].x), av, y0); y1 = fmaf(bf_hi(wd[e].x), av, y1); y2 = fmaf(bf_lo(wd[e].y), av, y2); y3 = fmaf(bf_hi(wd[e].y), av, y3);
              const float2 v = lds64f(src + e * 2048); wd[e] = make_uint2(__float_as_uint(v.x), __float_as_uint(v.y));
            }
            a4 = an;
          }
          st_ll(yp, __float_as_uint(y0), __float_as_uint(y1), __float_as_uint(y2), (__float_as_uint(y3) & ~255u) | (lds32(sb + INFO + 12) + 1));
          PROFW(t256 == 0, 27);
        }
        return;
      }
      mbar_wait(BAR(B_XRDY + wg * 2 + 1), 0);
    }
  }
  #undef IDS
  #undef LAYER
}

DEVI void loader(const Params& P, uint32_t sb) {
  const int lane = threadIdx.x & 31;
  const int bid = uni(BID), bi = bid >> 4, bp = bid & 15, rh = bp & 1, bc = bp >> 1;
  uint32_t phq = 0, tag = 0;
  #pragma unroll 1
  for (int L = 0; L < 2; L++) {
    int s = 0;
    uint32_t rdy = 0;
    #pragma unroll 1
    for (int n = L ? 0 : 3; n < 16; n++) {
      int kb = L ? kb_order(bc, n) : n;
      mbar_wait(BAR(B_EMPTYQ + s), (phq >> s) & 1);
      phq ^= 1u << s;
      if (L && n == 1) { mbar_wait(BAR(B_XRDY + 1), 0); mbar_wait(BAR(B_XRDY + 3), 0); }
      if (lane == 0) {
        mbar_expect_tx(BAR(B_FULLQ + s), L && n < 2 ? 40960 : 57344);
        tma_3d_h(sb + qb_off(s), &P.mWq, bp * 64, kb * 64, 0, BAR(B_FULLQ + s), L && n >= QEF_N ? POL_FIRST : POL_NORMAL);
        if (!L) tma_2d(sb + qa_off(s), &P.mX, kb * 64, bi * 256, BAR(B_FULLQ + s));
      }
      if (L && n >= 2) {
        if (((rdy >> (2 * kb)) & 3) != 3) {
          do { rdy = __ballot_sync(0xffffffffu, ld_rlx(&P.g->flagX[bi][lane]) == tag); } while (((rdy >> (2 * kb)) & 3) != 3);
          fence_async_glob();
        }
        if (n == 3 || n == 4) mbar_wait(BAR(B_XFREE + n - 3), 0);
        if (lane == 0) bulk_g2s_h(sb + qa_off(s), P.g->x[bi][kb], 32768, BAR(B_FULLQ + s), POL_X);
      }
      PROFY(L && lane == 0 && (n == 2 || n == 3 || n == 9), n == 9 ? 60 : 56 + n);
      if (L && n == 2) { mbar_wait(BAR(B_FULLQ), 0); mbar_wait(BAR(B_FULLQ + 1), 1); if (lane < 2) mbar_arrive_peer(BAR(B_XFREE + lane)); }
      s = (s == 2) ? 0 : s + 1;
    }
    for (int q = 0; q < 3; q++) mbar_wait(BAR(B_EMPTYQ + q), (phq >> q) & 1);
    tag = lds32(sb + INFO + 8) + L;
    #pragma unroll 1
    for (int q = 0; q < 4; q++) {
            if (bi) {
        const unsigned* f = &P.g->flagKV[bid - 16][q];
        while (ld_rlx(f) != tag);
        fence_async_glob();
      }
      if (lane == 0) {
        mbar_expect_tx(BAR(B_KVFULL + q), 16384);
        bulk_g2s_h(sb + ((q >> 1) ? KVB : KVA) + ((q & 1) ? 0 : 16384), bi ? P.g->kv[bid - 16][q] : P.g->zero, 16384, BAR(B_KVFULL + q));
      }
      PROFY(!L && lane == 0 && bi && q != 2, 34 + (q + 1) / 2);
    }
    mbar_wait(BAR(B_ORDY), L);
    {
      const uint4* src = P.g->o[bi][0][0][rh];
      rdy = 0;
      #pragma unroll 1
      for (int n = 0, q = 0; n < 16; q = w_next(n, q), n++) {
        const int j = wo_order(bc, n);
        if (((rdy >> (2 * j)) & 3) != 3) {
          do { rdy = __ballot_sync(0xffffffffu, ld_rlx(&P.g->flagO[bi][lane]) == tag); } while (((rdy >> (2 * j)) & 3) != 3);
          fence_async_glob();
        }
        if (n >= 2) mbar_wait(n < 5 ? BAR(B_HAFREE + (n > 2)) : BAR(B_EMPTYW + q), n < 5 ? L : w_par(n, q, L) ^ 1);
        if (n == THR_N) mbar_wait(BAR(B_OFREE), L);
        if (lane == 0) { mbar_expect_tx(BAR(B_FULLW + q), 16384); bulk_g2s_h(sb + w_off(q), src + j * 2048, 16384, BAR(B_FULLW + q)); }
      }
    }
    mbar_wait(BAR(B_OFREE), L);
  }
}

DEVI void ffn_prefetch(const Params& P, int q) {
  bulk_prefetch(q < 16 ? ((q & 1) ? P.wu : P.wg) + ((q >> 1) * 128 + blockIdx.x) * 3584 : P.wd + (min(FID, 111) * 8 + q - 16) * 4096, q < 16 ? 7168 : 8192);
}
DEVI void storer(const Params& P, uint32_t sb, int wg) {
  const int bid = uni(BID), bi = bid >> 4, rh = bid & 1, bc = (bid & 15) >> 1;
  const bool one = (threadIdx.x & 31) == 0;
  char* const g = (char*)P.g;
  const uint32_t tag0 = uni(((ld_rlx(&P.g->epoch) % 16383u) + 1u) << 2);
  #pragma unroll 1
  for (int L = 0; L < 2; L++) {
    const uint32_t tag = tag0 + L;
    if (wg) {
      #pragma unroll 1
      for (int r = threadIdx.x & 31; r < 256; r += 32) {
        uint4 v;
        do v = ld_ll(&P.g->statF[bi * 256 + r]); while (!__all_sync(0xffffffffu, v.w == tag));
        float var = __uint_as_float(v.y), c = rsqrtf(var + LN_EPS);
        if (L) { c += 1.f; c *= rsqrtf(fmaf(var * c, c, LN_EPS)); }
        const float mh = bf_round(__uint_as_float(v.x));
        sts64f(sb + PAR + r * 8, c, __uint_as_float(pack_bf16(mh, __uint_as_float(v.x) - mh)));
      }
      if (!L) mbar_wait(BAR(B_PAR), 0);
      warp_signal(BAR(B_ROW));
    }
    if (wg) { mbar_wait(BAR(B_KVRDY), L); mbar_wait(BAR(B_KVRDY + 2), L); const uint32_t t0 = clk(); while (clk() - t0 < KV_D) __nanosleep(40); }
    #pragma unroll 1
    for (int u = 0; u < 2 + 4 * wg; u++) {
      const int h = u < 2 ? u : u >> 2, hi = (u & 1) ^ 1;
      uint32_t src, dst, fl, b0, b1;
      if (u < 2) {
        src = (h ? KVB : KVA) + (3 - wg) * 16384; dst = offsetof(Scratch, kv) + (bid * 4 + h * 2 + wg) * 16384; fl = offsetof(Scratch, flagKV) + (bid * 32 + h * 2 + wg) * 4;
        b0 = BAR(B_KVRDY + ((u | wg) ? 1 : 0)); b1 = b0 + 16;
      } else {
        src = QO + (h * 2 + hi) * 8192; dst = offsetof(Scratch, o) + ((((bi * 2 + h) * 8 + bc) * 2 + hi) * 2 + rh) * 8192;
        fl = offsetof(Scratch, flagO) + (bi * 32 + h * 16 + (bid & 15)) * 4;
        b0 = BAR(B_ORDY + u - 2); b1 = b0 + 32;
      }
      mbar_wait(b0, L); mbar_wait(b1, L);
      fence_async_smem();
      PROFY(one && !L && u == 3 * wg, u ? 46 : 8);
      if (one && (u >= 2 || bi < 7)) bulk_s2g(g + dst, sb + src, u < 2 ? 16384 : 8192);
      if (one && u == 5) mbar_arrive(BAR(B_HAFREE + 1));
      if (u == 2 || u == 4) continue;
      bulk_wait<0>();
      PROFY(one && !L && u == 3 * wg, u ? 61 : 62);
      fence_rel();
      if (one) { st_rlx((unsigned*)(g + fl), tag); if (!wg || u > 2) mbar_arrive(BAR(B_HAFREE + h + (wg & h))); }
      PROFY(one && !L && (u > 2 || u == wg), u > 2 ? (u == 3 ? 38 : 54) : 32 + u);
    }
    if (L == 0) {
      char* dst = g + (offsetof(Scratch, x) + (bi * 16 + 2 * bc) * 32768 + rh * 16384);
      unsigned* f = (unsigned*)(g + (offsetof(Scratch, flagX) + (bi * 32 + bc * 4 + rh) * 4));
      const uint32_t a = sb + rh * 16384;
      if (wg == 0) {
        mbar_wait(BAR(B_XRDY), 0); mbar_wait(BAR(B_XRDY + 2), 0);
        fence_async_smem();
        PROFY(one, 41);
        if (one) bulk_s2g(dst, a, 16384);
        bulk_wait<0>();
        PROFY(one, 45);
        if (one) { mbar_arrive(BAR(B_XFREE)); mbar_arrive(BAR(B_PFREE)); }
        fence_rel();
        mbar_wait(BAR(B_XRDY + 1), 0); mbar_wait(BAR(B_XRDY + 3), 0);
        if (one) { st_rlx(f, tag); bulk_s2g(dst + 32768, a + 32768, 16384); }
        PROFY(one, 56);
        bulk_wait<0>();
        if (one) mbar_arrive(BAR(B_XFREE + 1));
        fence_rel();
        if (one) st_rlx(f + 2, tag);
        PROFY(one, 57);
      } else {
        mbar_wait(BAR(B_XRDY + 1), 0); mbar_wait(BAR(B_XRDY + 3), 0);
        mbar_wait(BAR(B_PFREE), 0);
        if (one) bulk_s2peer(a, 16384, BAR(B_FULLQ));
        { const uint32_t t0 = clk(); while (clk() - t0 < XD_D); }
        if (one) bulk_s2peer(a + 32768, 16384, BAR(B_FULLQ + 1));
      }
      if (wg == 0) {
        uint32_t t0 = clk() + PF1_D;
        #pragma unroll 1
        for (int q = PF1_S; q < PF1_E; q++) { while ((int)(clk() - t0) < 0) __nanosleep(50); if (one) ffn_prefetch(P, q); t0 += PF1_T; }
      }
    }
  }
}

DEVI void stg_issue(const Params& P, int c, uint32_t d, uint32_t du, uint32_t b) {
  mbar_expect_tx(b, 16384);
  if (c < 8) { tma_2d_h(d, &P.mWg, FID * 32, c * 128, b, POL_G); tma_2d_h(d + du, &P.mWu, FID * 32, c * 128, b, POL_U); }
  else if (c < 12) tma_3d_h(d, &P.mWd, 0, FID * 32 + (c - 8) * 8, 0, b, POL_D);
  else tma_2d_h(d, &P.mWp, (c - 12) * 1024 + (BID >> 2) * 32, (BID & 3) * 256, b, POL_EF);
}
DEVI void pace() { const uint32_t t0 = clk(); while (clk() - t0 < PACE_T); }
DEVI void stager(const Params& P, uint32_t sb) {
  {
    const int b = blockIdx.x;
    uint32_t t0 = clk();
    #pragma unroll 1
    for (int q = 0; q < PQ_N; q++) { bulk_prefetch(P.wqkv + (q * 128 + b) * 3072, 6144); while (clk() - t0 < PQ_T) __nanosleep(50); t0 += PQ_T; }
    bulk_prefetch(P.wo + b * 8192, 16384);
    #pragma unroll 1
    for (int q = 0; q < PF0_N; q++) {
      while (clk() - t0 < PF0_T) __nanosleep(50);
      t0 += PF0_T;
      ffn_prefetch(P, q);
    }
  }
  const int bid = BID, bi = bid >> 4, rh = bid & 1, bc = (bid & 15) >> 1;
  #pragma unroll 1
  for (int L = 0; L < 2; L++) {
    const int nch = L ? (FID < 112 ? 8 : 0) : 15;
    mbar_wait(BAR(B_PAR), L); mbar_wait(BAR(B_KVFULL + W0_BAR), L);
    #pragma unroll 1
    for (int n = 0, q = 0; n < 16; q = w_next(n, q), n++) {
      if (n >= 2) mbar_wait(n < 5 ? BAR(B_HAFREE + (n > 2)) : BAR(B_EMPTYW + q), n < 5 ? L : w_par(n, q, L) ^ 1);
      if (n == THR_N) mbar_wait(BAR(B_OFREE), L);
      mbar_expect_tx(BAR(B_FULLW + q), 16384);
      tma_5d(sb + w_off(q) + 16384, &P.mWo, 0, 0, n >> 3, 2 * (wo_order(bc, n) & 7), 2 * bc, BAR(B_FULLW + q), L ? POL_EF : POL_NORMAL);
      if (n == 2) {
        #pragma unroll 1
        for (int e = 0; e < 2; e++) {
          mbar_expect_tx(BAR(B_FULLW + 5), 16384);
          if (L) bulk_g2s_h(sb + 32768 + e * 16384, P.g->x[bi][2 * bc + e] + rh * 1024, 16384, BAR(B_FULLW + 5));
          else tma_2d_h(sb + 32768 + e * 16384, &P.mXh, bc * 128 + e * 64, bi * 256 + rh * 128, BAR(B_FULLW + 5), POL_EF);
        }
      }
    }
    mbar_wait(BAR(B_EMPTYW + 5), L);
    if (L && nch) {
      const bf16* src = WDSRC2;
      mbar_expect_tx(BAR(B_FULLW + 2), 32768); mbar_expect_tx(BAR(B_FULLW + 2), 24576);
      #pragma unroll 1
      for (int e = 0; e < 3; e++) { bulk_g2s_h(sb + e * 32768 + (e < 2 ? (rh ^ 1) * 16384 : 0), src + e * 8192, e < 2 ? 16384 : 24576, BAR(B_FULLW + 2)); pace(); }
    }
    if (L == 0) { mbar_arrive_peer(BAR(B_PFREE)); mbar_wait(BAR(B_EMPTYW), 0); mbar_wait(BAR(B_EMPTYW + 1), 0); }
    #pragma unroll 1
    for (int c = FID < 112 ? 0 : 12, slot = 0; c < nch; c++, slot = slot == 2 ? 0 : slot + 1) {
      const int q = (c >> 1) + (c >> 2);
      mbar_wait(L ? BAR(B_EMPTYW + q) : BAR(B_STGE + slot), L | ((0x71c7 >> c) & 1));
      #define CC c
      stg_issue(P, CC, L ? sb + w_off(q) + (c & 1) * 8192 : sb + STG + slot * 16384, 8192 << L, L ? BAR(B_FULLW + q) : BAR(B_STG + slot));
      if (L) pace();
    }
  }
}
DEVI void sum8(uint4 v, float& s1, float& s2) {
  float e[8] = {bf_lo(v.x), bf_hi(v.x), bf_lo(v.y), bf_hi(v.y), bf_lo(v.z), bf_hi(v.z), bf_lo(v.w), bf_hi(v.w)};
  #pragma unroll
  for (int q = 0; q < 8; q++) { s1 += e[q]; s2 = fmaf(e[q], e[q], s2); }
}
DEVI uint4 norm8(uint4 x, float m, float rs) {
  #define HN(v) pack_bf16((bf_lo(v) - m) * rs, (bf_hi(v) - m) * rs)
  return make_uint4(HN(x.x), HN(x.y), HN(x.z), HN(x.w));
  #undef HN
}
DEVI void put_f32(uint4 b, uint32_t d, uint32_t d2) {
  sts128(d, make_uint4(b.x << 16, b.x & 0xffff0000u, b.y << 16, b.y & 0xffff0000u));
  sts128(d + d2, make_uint4(b.z << 16, b.z & 0xffff0000u, b.w << 16, b.w & 0xffff0000u));
}
DEVI void put_bf16(uint4 b, uint32_t d) {
  sts64f(d, __uint_as_float(b.x), __uint_as_float(b.y)); sts64f(d + 1024, __uint_as_float(b.z), __uint_as_float(b.w));
  fence_async_smem();
}
DEVI uint4 best4(uint32_t p) {
  uint4 a = lds128(p), b = lds128(p + 16), c = lds128(p + 32), d = lds128(p + 48);
  if (b.x > a.x) a = b;
  if (d.x > c.x) c = d;
  return c.x > a.x ? c : a;
}
#define FL(x) __uint_as_float(x)
#define UI(x) __float_as_uint(x)
DEVI void aux(const Params& P, uint32_t sb) {
  int tid = fresh_tid();
  #define lane (tid & 31)
  #define wq (tid >> 5)
  uint32_t ids = P.map[blockIdx.x], tag;
  #define bid ((int)(ids & 255))
  #define fid ((int)(ids >> 8))
  #define bi (bid >> 4)
  #define bp (bid & 15)
  #define bc (bp >> 1)
  #define FRESH() do { tid = fresh_tid(); uint4 z_ = ldsv128(sb + INFO2 + 16); ids = z_.y; tag = z_.z + L; idx = z_.w; } while (0)
  {
    const uint32_t epoch = ld_rlx(&P.g->epoch);
    if (tid == 0) {
      mbar_expect_tx(BAR(B_STG), 49152);
      tma_3d(sb + STG, &P.mWq, bp * 64, bi * 128, 0, BAR(B_STG));
      tma_3d(sb + STG + 24576, &P.mWq, bp * 64, bi * 128 + 64, 0, BAR(B_STG));
    }
    __syncwarp();
    sts64f(sb + ONES + tid * 8, FL(0x3F803F80u), FL(0x3F803F80u));
    float s1 = 0.f, s2 = 0.f;
    { uint4 v = __ldg((const uint4*)P.wr + tid);
      if ((tid >> 4) == bc) put_f32(v, sb + WR + (tid & 15) * 32, 16);
      sum8(v, s1, s2);
      #pragma unroll 1
      for (int o = 16; o; o >>= 1) s1 += __shfl_xor_sync(0xffffffffu, s1, o);
      sts32f(sb + INFO2 + wq * 4, s1); }
    const uint4* src = (const uint4*)(P.x0 + (size_t)bid * 16384) + (tid >> 3) * 128 + (tid & 7);
    s1 = 0.f; s2 = 0.f;
    #pragma unroll 1
    for (int it = 0; it < 16; it += 4) {
      uint4 v0 = __ldg(src + it * 8), v1 = __ldg(src + it * 8 + 8), v2 = __ldg(src + it * 8 + 16), v3 = __ldg(src + it * 8 + 24);
      #pragma unroll 1
      for (int q = 0; q < 4; q++) { sum8(v0, s1, s2); v0 = v1; v1 = v2; v2 = v3; }
    }
    #pragma unroll 1
    for (int o = 1; o < 8; o <<= 1) { s1 += __shfl_xor_sync(0xffffffffu, s1, o); s2 += __shfl_xor_sync(0xffffffffu, s2, o); }
    tag = ((epoch % 16383u) + 1u) << 2;
    if (tid == 0) { sts128(sb + INFO, make_uint4(0x40000000u, 0u, tag, ((epoch % 127u) + 1u) << 1)); sts128(sb + INFO2 + 16, make_uint4(epoch, ids, tag, 0x40000000u)); }
    float m = s1 * (1.f / 1024.f);
    if ((tid & 7) == 0) st_ll(&P.g->statF[bid * 16 + (tid >> 3)], UI(m), UI(fmaxf(fmaf(-m, m, s2 * (1.f / 1024.f)), 0.f)), 0u, tag);
    bar_sync(2, 128);
    mbar_wait_b(BAR(B_STG), 0);
    if (tid < 96) {
      s1 = 0.f; s2 = 0.f;
      #pragma unroll 1
      for (int r = 0; r < 16; r++) {
        const uint32_t a = sb + STG + (r >> 3) * 24576 + wq * 8192 + (r & 7) * 128 + ((lane * 4) ^ ((r & 7) << 4));
        #pragma unroll
        for (int e = 0; e < 8; e++) { uint32_t v = lds32(a + e * 1024); s1 += bf_lo(v); s2 += bf_hi(v); }
      }
      st_ll(&P.g->csP[bp][bi][tid], UI(s1), UI(s2), 0u, tag);
      s1 = 0.f; s2 = 0.f;
      #pragma unroll 1
      for (int q = 0; q < 8; q += 2) {
        uint4 a, b; poll_ll2(&P.g->csP[bp][q][tid], &P.g->csP[bp][q + 1][tid], 0xffffffffu, tag, a, b);
        s1 += FL(a.x) + FL(b.x); s2 += FL(a.y) + FL(b.y);
      }
      const uint32_t hi = pack_bf16(-s1, -s2);
      sts32(sb + CS + (tid >> 2) * 32 + (tid & 3) * 4, hi);
      sts32(sb + CS + (tid >> 2) * 32 + (tid & 3) * 4 + 16, pack_bf16(-s1 - bf_lo(hi), -s2 - bf_hi(hi)));
    }
    fence_async_smem();
  }
  int idx;
  #pragma unroll 1
  for (int L = 0; L < 2; L++) {
    FRESH();
    {
      if ((unsigned)(bi - (idx >> 8)) < 2u) {
        const uint4* src = &P.g->patch[bp * 8 + (tid >> 6) * 4][tid & 63];
        uint4 v0, v1, v2, v3; int it = 0;
        do { v0 = ld_ll(src); v1 = ld_ll(src + 64); v2 = ld_ll(src + 128); v3 = ld_ll(src + 192); if (++it > SPIN_MAX) __trap(); }
        while (!__all_sync(0xffffffffu, v0.w == tag && v1.w == tag && v2.w == tag && v3.w == tag));
        float q = (FL(v0.x) + FL(v1.x)) + (FL(v2.x) + FL(v3.x)), k = (FL(v0.y) + FL(v1.y)) + (FL(v2.y) + FL(v3.y)), v = (FL(v0.z) + FL(v1.z)) + (FL(v2.z) + FL(v3.z));
        q += __shfl_xor_sync(0xffffffffu, q, 1); k += __shfl_xor_sync(0xffffffffu, k, 1); v += __shfl_xor_sync(0xffffffffu, v, 1);
        bar_sync(2, 128);
        const uint32_t d = sb + PATCH + (tid & ~1), kv = pack_bf16(k, v);
        sts16(d, pack_bf16(q * QSCALE, 0.f)); sts16(d + 128, kv); sts16(d + 256, kv >> 16);
      }
      sts32(sb + INFO, idx);
      bar_sync(2, 128);
    }
    const uint4 fix = lds128(sb + PATCH + 128 + (lane & 4) * 32 + (wq >> 1) * 64 + (lane & 3) * 16);
    warp_signal(BAR(B_PAR));
    PROFX(tid == 0, L ? 23 : 17);
    mbar_wait_b(BAR(B_KVFULL + wq), L);
    if ((idx >> 7) == bi * 2 - 1 - (wq & 1)) {
      if (lane < 8) sts128(sb + ((wq >> 1) ? KVB : KVA) + ((idx >> 6) & 3) * 8192 + (lane >> 2) * 4096 + (idx & 63) * 64 + (((lane ^ (idx >> 1)) & 3) << 4), fix);
      fence_async_smem();
    }
    bar_arrive(4 + wq, 160); bar_arrive(8 + wq, 160);
    FRESH();
    mbar_wait_b(BAR(B_OFREE), L);
    #define blk (bi * 2 + (bid & 1))
    if (tid < 33) st_ll(tid < 32 ? &P.g->row[blk][bc * 32 + tid] : &P.g->best[bc][blk], 0u, 0u, 0u, 0u);
    mbar_wait_b(BAR(B_XRDY + 1), L); mbar_wait_b(BAR(B_XRDY + 3), L);
    PROFX(tid == 0, 37 + L * 16);
    FRESH();
    {
      float s1 = 0.f, s2 = 0.f, d = 0.f;
      #pragma unroll 1
      for (int q = 0; q < 8; q += 4) {
        const uint4* src = &P.g->statP[q][blk * 128 + tid];
        uint4 v0, v1, v2, v3; int it = 0;
        do { v0 = ld_ll(src); v1 = ld_ll(src + 2048); v2 = ld_ll(src + 4096); v3 = ld_ll(src + 6144); if (++it > SPIN_MAX) __trap(); }
        while (!__all_sync(0xffffffffu, v0.w == tag && v1.w == tag && v2.w == tag && v3.w == tag));
        s1 += (FL(v0.x) + FL(v1.x)) + (FL(v2.x) + FL(v3.x)); s2 += (FL(v0.y) + FL(v1.y)) + (FL(v2.y) + FL(v3.y)); d += (FL(v0.z) + FL(v1.z)) + (FL(v2.z) + FL(v3.z));
      }
      PROFX(tid == 0, 39 + L * 16);
      uint4 a = lds128(sb + INFO2), b, c;
      float m = s1 * (1.f / 1024.f), var = fmaxf(fmaf(-m, m, s2 * (1.f / 1024.f)), 0.f), rs = rsqrtf(var + LN_EPS);
      uint32_t key = UI(fmaf(-m, (FL(a.x) + FL(a.y)) + (FL(a.z) + FL(a.w)), d) * rs);
      key ^= (uint32_t)((int)key >> 31) | 0x80000000u;
      uint32_t win = __ballot_sync(0xffffffffu, key == __reduce_max_sync(0xffffffffu, key));
      if (lane == __ffs(win) - 1) sts128(sb + RED + wq * 16, make_uint4(key, UI(m), UI(rs), (tag << 11) | (uint32_t)(blk * 128 + tid)));
      if (L) sts64f(sb + PAR + tid * 8, 1.f + rs, -m * rs);
      else if ((tid >> 4) == bc) st_ll(&P.g->statF[blk * 128 + tid], UI(m), UI(var), 0u, tag + 1);
      bar_sync(2, 128);
      if (wq == 0) {
        a = best4(sb + RED);
        float2 v = lds64f(sb + (lane >> 4) * 32768 + (a.w & 255) * 128 + (((lane & 15) * 8) ^ ((a.w & 7) << 4)));
        st_ll(&P.g->row[blk][bc * 32 + lane], UI(v.x), UI(v.y), 0u, tag);
        if (lane == 0) st_ll(&P.g->best[bc][blk], a.x, a.y, a.z, a.w);
        __syncwarp();
        if (lane < 2 + 2 * L) mbar_arrive(L ? BAR(B_PAR) : BAR(B_XFREE + lane));
      }
      PROFX(tid == 0, 18 + L * 6);
      FRESH();
      a = poll_ll(&P.g->best[bc][lane & 15], 0xfffff800u, tag << 11);
      win = __ffs(__ballot_sync(0xffffffffu, a.x == __reduce_max_sync(0xffffffffu, a.x))) - 1;
      idx = __shfl_sync(0xffffffffu, a.w, win) & 2047;
      PROFX(tid == 0, 19 + L * 6);
      poll_ll2(&P.g->row[win][tid], &P.g->row[win][tid + 128], 0xffffffffu, tag, c, b);
      c.z = b.x; c.w = b.y;
      a.x = __shfl_sync(0xffffffffu, a.x, win); a.y = __shfl_sync(0xffffffffu, a.y, win); a.z = __shfl_sync(0xffffffffu, a.z, win);
      sts32(sb + INFO2 + 28, idx);
      PROFX(tid == 0, 61 + L);
      b = norm8(c, FL(a.y), FL(a.z));
      if (L) put_bf16(b, sb + HV + tid * 8); else put_f32(b, sb + HV + tid * 16, 2048);
      if ((tid >> 1) == (bid & 63)) {
        sts128(sb + RED + 64 + (tid & 1) * 16, bid < 64 ? make_uint4(c.x, c.y, b.x, b.y) : make_uint4(c.z, c.w, b.z, b.w));
        sts32(sb + RED + 96, a.x);
      }
      bar_sync(2 + L, 128 + L * 256);
      if (L) {
        const int r0 = blk * 128 + (tid >> 4);
        uint32_t src = sb + ((tid >> 3) & 1) * 32768 + (r0 & 255) * 128 + (((tid ^ r0) & 7) << 4);
        uint4* dst = (uint4*)(P.out + (size_t)r0 * 1024 + bc * 128) + (tid & 15);
        #pragma unroll 4
        for (int it = 0; it < 16; it++) { uint4 v = lds128(src + it * 1024); if (idx - r0 != it * 8) dst[it * 1024] = v; }
      }
    }
    #pragma unroll 1
    for (int st = L; st < 2; st++) {
      FRESH();
      float a[8] = {0.f, 0.f, 0.f, 0.f, 0.f, 0.f, 0.f, 0.f};
      if (L == 0 && fid < 112) {
        uint32_t ha = st ? sb + RED + 768 : sb + HV + ((wq & 1) * 64 + (lane >> 2)) * 4;
        uint32_t ph = st ? 0x1cu : 0x171u, bar = st ? BAR(B_STG + 2) : BAR(B_STG);
        uint32_t wa = sb + STG + wq * 4096 + (st ? 32768 + lane * 16 : (lane ^ (lane >> 3)) * 16);
        const uint32_t hx = st ? 256 : 512;
        const bool lead = lane == 0;
        uint4 vc = make_uint4(0u, 0u, 0u, 0u); float hc = 0.f;
        #pragma unroll 1
        do {
          mbar_wait(bar, ph & 1);
          PROFX(lead && threadIdx.x == 256 && st == 0 && (ph > 255 || ph < 4), 40 - 23 + __clz(ph));
          #pragma unroll
          for (int n = 0; n < 8; n++) { const uint4 v = lds128(wa + n * 512); const float h = lds32f(ha + n * 32); fma8(a, vc, hc); vc = v; hc = h; }
          __syncwarp();
          if (lead) mbar_arrive(bar - 8 * (B_STG - B_STGE));
          const bool wrap = bar == BAR(B_STG + 2);
          bar += wrap ? -16 : 8; wa += wrap ? -32768 : 16384; ha += hx;
          ph >>= 1;
        } while (ph != 1);
        fma8(a, vc, hc);
      }
      FRESH();
      if (st == 1) {
        const uint32_t t8 = lds32(sb + INFO + 12) + L;
        if (L == 0 && fid < 112) {
          const bool odd = lane & 1;
          #pragma unroll
          for (int e = 0; e < 4; e++) { float z = __shfl_xor_sync(0xffffffffu, odd ? a[e] : a[4 + e], 1); if (odd) a[e] = z; else a[4 + e] = z; }
          uint4* dst = &P.g->yP[tid & ~1][fid][tid & 1];
          st_ll(dst, UI(a[0]), UI(a[1]), UI(a[2]), (UI(a[3]) & ~255u) | t8);
          st_ll(dst + 224, UI(a[4]), UI(a[5]), UI(a[6]), (UI(a[7]) & ~255u) | t8);
          PROFX(tid == 0, 21);
        }
        if (tid == 0) { uint32_t k = lds32(sb + RED + 96); sts32f(sb + RED + 100, bf_round(__fdividef(1.f, 1.f + __expf(-bf_round(FL(k ^ (~(uint32_t)((int)k >> 31) | 0x80000000u))))))); }
        uint4 v0, v1;
        poll_ll2(&P.g->yP[bid][0][min(tid, 111)], &P.g->yP[bid][0][min(tid, 111) + 112], 255u, t8, v0, v1);
        const float lo = (tid < 112 && !(tid & 1)) ? 1.f : 0.f, hi = (tid < 112 && (tid & 1)) ? 1.f : 0.f;
        const float y0 = FL(v0.x) + FL(v1.x), y1 = FL(v0.y) + FL(v1.y), y2 = FL(v0.z) + FL(v1.z), y3 = FL((v0.w & ~255u) | 128u) + FL((v1.w & ~255u) | 128u);
        a[0] = y0 * lo; a[1] = y1 * lo; a[2] = y2 * lo; a[3] = y3 * lo; a[4] = y0 * hi; a[5] = y1 * hi; a[6] = y2 * hi; a[7] = y3 * hi;
      }
      sts32f(sb + RED + 256 + wq * 128 + ((lane & 3) * 8 + (lane >> 2)) * 4, fold8(a));
      bar_sync(2, 128);
      const uint32_t d = sb + RED + 256 + lane * 4;
      float z0 = lds32f(d) + lds32f(d + 128), z1 = lds32f(d + 256) + lds32f(d + 384);
      if (st == 0) {
        sts32f(sb + RED + 768 + lane * 32 + wq * 4, swiglu(z0, z1));
        bar_sync(2, 128);
        if (fid < 112) { st_ll(&P.g->yP[tid & ~1][fid][tid & 1], 0u, 0u, 0u, 0u); st_ll(&P.g->yP[tid | 1][fid][tid & 1], 0u, 0u, 0u, 0u); }
        else { const uint32_t t0 = clk(); while (clk() - t0 < IDLE_T) __nanosleep(200); }
        if (tid < 80) st_ll(tid < 64 ? &P.g->patch[bid][tid] : &P.g->x2[(tid >> 1) & 7][2 * bid + (tid & 1)], 0u, 0u, 0u, 0u);
        PROFX(tid == 0, 20); continue; }
      z0 += z1;
      z0 += __shfl_xor_sync(0xffffffffu, z0, 8); z0 += __shfl_xor_sync(0xffffffffu, z0, 16);
      uint32_t xw = lds32(sb + RED + 64 + (lane & 4) * 4 + (lane & 2) * 2), hw = lds32(sb + RED + 72 + (lane & 4) * 4 + (lane & 2) * 2);
      z0 = bf_round(((lane & 1) ? bf_hi(hw) : bf_lo(hw)) + bf_round(bf_round(z0) * lds32f(sb + RED + 100))) + ((lane & 1) ? bf_hi(xw) : bf_lo(xw));
      uint32_t v = pack_bf16(z0, __shfl_down_sync(0xffffffffu, z0, 1)), v2 = __shfl_down_sync(0xffffffffu, v, 2);
      if (L) { if (tid == 0 || tid == 4) *(uint2*)(P.out + (size_t)idx * 1024 + bid * 8 + tid) = make_uint2(v, v2); PROFW(tid == 0, 28); }
      else if ((tid & 3) == 0 && tid < 64) st_ll(&P.g->x2[tid >> 3][2 * bid + ((tid >> 2) & 1)], v, v2, 0u, tag + 1);
    }
    if (L == 0) {
      PROFX(tid == 0, 22);
      FRESH();
      uint4 x, y; poll_ll2(&P.g->x2[bi][tid], &P.g->x2[bi][tid + 128], 0xffffffffu, tag + 1, x, y);
      x.z = y.x; x.w = y.y;
      if (wq == (bc & 3)) sts64f(sb + X2SEG + lane * 8, FL(bc < 4 ? x.x : x.z), FL(bc < 4 ? x.y : x.w));
      float s1 = 0.f, s2 = 0.f;
      sum8(x, s1, s2);
      #pragma unroll
      for (int o = 16; o; o >>= 1) { s1 += __shfl_xor_sync(0xffffffffu, s1, o); s2 += __shfl_xor_sync(0xffffffffu, s2, o); }
      sts64f(sb + RED + wq * 8, s1, s2);
      bar_sync(2, 128);
      y = lds128(sb + RED); uint4 y2 = lds128(sb + RED + 16);
      float m = ((FL(y.x) + FL(y.z)) + (FL(y2.x) + FL(y2.z))) * (1.f / 1024.f);
      put_bf16(norm8(x, m, rsqrtf(fmaxf(fmaf(-m, m, ((FL(y.y) + FL(y.w)) + (FL(y2.y) + FL(y2.w))) * (1.f / 1024.f)), 0.f) + LN_EPS)), sb + HV + tid * 8);
      mbar_wait(BAR(B_STG), 1); mbar_wait(BAR(B_STG + 1), 0); mbar_wait(BAR(B_STG + 2), 0);
      bar_sync(2, 128);
      PROFX(tid == 0, 30);
      float d0[4] = {0.f, 0.f, 0.f, 0.f}, d1[4] = {0.f, 0.f, 0.f, 0.f}, d2[4] = {0.f, 0.f, 0.f, 0.f};
      const uint32_t bd = (64 + (HV >> 4) + uni(bid & 3) * 32) | 0x10000u;
      #pragma unroll 1
      for (int ks = 0; ks < 8; ks++) {
        const uint32_t ad = (64 + (STG >> 4) + ks * 128) | (64u << 16);
        wg_fence();
        wgmma_ss_n8<0, 1>(d0, mkd<HI64>(ad), mkd<8>(bd + ks * 4), 1);
        wgmma_ss_n8<0, 1>(d1, mkd<HI64>(ad + 1024), mkd<8>(bd + ks * 4), 1);
        wgmma_ss_n8<0, 1>(d2, mkd<HI64>(ad + 2048), mkd<8>(bd + ks * 4), 1);
        wg_commit();
      }
      wg_wait<0>(); keep(d0); keep(d1); keep(d2);
      FRESH();
      if ((lane & 3) == (wq >> 1)) {
        uint4* dst = &P.g->patch[bid][(wq & 1) * 32 + (lane >> 2) * 2 + (wq >> 1)];
        st_ll(dst, UI(d0[0]), UI(d1[0]), UI(d2[0]), tag + 1); st_ll(dst + 16, UI(d0[2]), UI(d1[2]), UI(d2[2]), tag + 1);
      }
      PROFX(tid == 0, 31);
    }
  }
  if (bid == 0 && tid == 0) P.g->epoch = lds32(sb + INFO2 + 16) + 1;
  #undef blk
  #undef bid
  #undef fid
  #undef bi
  #undef bp
  #undef bc
  #undef FRESH
  #undef lane
  #undef wq
}

__global__ void __cluster_dims__(2, 1, 1) __launch_bounds__(512, 1) fused_kernel(const __grid_constant__ Params P) {
  extern __shared__ __align__(1024) uint8_t smem_raw[];
  const uint32_t sb = smem_u32(smem_raw);
  PROFT(threadIdx.x == 0, 0);
  if (threadIdx.x == 0) {
    for (int s = 0; s < 3; s++) mbar_init(BAR(B_FULLQ + s), 1);
    asm volatile("fence.mbarrier_init.release.cluster;" ::: "memory");
    #pragma unroll 1
    for (int s = 0; s < 3; s++) {
      mbar_expect_tx(BAR(B_FULLQ + s), 57344);
      tma_2d(sb + qa_off(s), &P.mX, s * 64, (BID >> 4) * 256, BAR(B_FULLQ + s));
      tma_3d(sb + qb_off(s), &P.mWq, (BID & 15) * 64, s * 64, 0, BAR(B_FULLQ + s));
    }
    if ((sb & 0x3FFFFu) != 1024) __trap();
  } else if (threadIdx.x == 480) {
    asm volatile("prefetch.tensormap [%0];" :: "l"(&P.mWq) : "memory");
  } else if (threadIdx.x >= 32 && !(threadIdx.x & 28) && (threadIdx.x >> 3) + (threadIdx.x & 3) <= B_COUNT + 1) {
    int b = (threadIdx.x >> 3) + (threadIdx.x & 3) - 1;
    if (b == B_COUNT) b = B_ROW;
    const uint32_t cnt = b < B_XFREE ? (b == B_OFREE ? 1 : 2) : (b < B_KVRDY ? 3 : (b < B_KVFULL || b == B_PAR ? 4 : (b == B_PFREE ? 2 : 1)));
    mbar_init(BAR(b), cnt);
    asm volatile("fence.mbarrier_init.release.cluster;" ::: "memory");
  }
  __syncthreads();
  asm volatile("barrier.cluster.arrive.relaxed.aligned;" ::: "memory");
  const int wg = __shfl_sync(0xffffffffu, threadIdx.x >> 7, 0);
  if (wg < 2) { reg_inc<224>(); consumer(P, sb, wg); }
  else if (wg == 2) { reg_dec<40>(); aux(P, sb); }
  else {
    reg_dec<24>();
    asm volatile("barrier.cluster.wait.aligned;" ::: "memory");
    const int w = __shfl_sync(0xffffffffu, (threadIdx.x >> 5) & 3, 0);
    if (w == 0) loader(P, sb);
    else if (w < 3) storer(P, sb, w - 1);
    else if ((threadIdx.x & 31) == 0) stager(P, sb);
  }
}

typedef CUresult (*EncFn)(CUtensorMap*, CUtensorMapDataType, cuuint32_t, void*, const cuuint64_t*, const cuuint64_t*, const cuuint32_t*, const cuuint32_t*,
                          CUtensorMapInterleave, CUtensorMapSwizzle, CUtensorMapL2promotion, CUtensorMapFloatOOBfill);
static void mk_map(EncFn enc, CUtensorMap* m, const void* ptr, int rank, const cuuint64_t* dims, const cuuint64_t* strides, const cuuint32_t* box,
                   CUtensorMapSwizzle sw, CUtensorMapL2promotion pr) {
  cuuint32_t es[5] = {1, 1, 1, 1, 1};
  enc(m, CU_TENSOR_MAP_DATA_TYPE_BFLOAT16, rank, (void*)ptr, dims, strides, box, es, CU_TENSOR_MAP_INTERLEAVE_NONE, sw, pr, CU_TENSOR_MAP_FLOAT_OOB_FILL_NONE);
}
extern "C" void kernel_launch(void* const* d_in, const int* in_sizes, int n_in, void* d_out, int out_size) {
  (void)in_sizes; (void)n_in; (void)out_size;
  void* fn = nullptr; cudaDriverEntryPointQueryResult q;
  cudaGetDriverEntryPoint("cuTensorMapEncodeTiled", &fn, cudaEnableDefault, &q);
  EncFn enc = (EncFn)fn;
  cudaFuncSetAttribute(fused_kernel, cudaFuncAttributeMaxDynamicSharedMemorySize, SMEM_BYTES);
  Params P;
  const CUtensorMapSwizzle S128 = CU_TENSOR_MAP_SWIZZLE_128B, S64 = CU_TENSOR_MAP_SWIZZLE_64B, S0 = CU_TENSOR_MAP_SWIZZLE_NONE;
  const CUtensorMapL2promotion L256 = CU_TENSOR_MAP_L2_PROMOTION_L2_256B, L128 = CU_TENSOR_MAP_L2_PROMOTION_L2_128B;
  { cuuint64_t d[2] = {1024, 2048}, s[1] = {2048}; cuuint32_t b[2] = {64, 256}, bh[2] = {64, 128};
    mk_map(enc, &P.mX, d_in[0], 2, d, s, b, S128, L256); mk_map(enc, &P.mXh, d_in[0], 2, d, s, bh, S128, L256); }
  { cuuint64_t d[3] = {1024, 1024, 3}, s[2] = {6144, 2048}; cuuint32_t b[3] = {64, 64, 3}; mk_map(enc, &P.mWq, d_in[1], 3, d, s, b, S128, L256); }
  { cuuint64_t d[5] = {64, 32, 2, 16, 16}, s[4] = {2048, 65536, 131072, 128}; cuuint32_t b[5] = {64, 32, 1, 2, 2}; mk_map(enc, &P.mWo, d_in[2], 5, d, s, b, S128, L256); }
  { cuuint64_t d[2] = {3584, 1024}, s[1] = {7168}; cuuint32_t b[2] = {32, 128};
    mk_map(enc, &P.mWg, d_in[5], 2, d, s, b, S64, L128); mk_map(enc, &P.mWu, d_in[6], 2, d, s, b, S64, L128); }
  { cuuint64_t d[2] = {3072, 1024}, s[1] = {6144}; cuuint32_t b[2] = {32, 256}; mk_map(enc, &P.mWp, d_in[1], 2, d, s, b, S64, L128); }
  { cuuint64_t d[3] = {256, 3584, 4}, s[2] = {2048, 512}; cuuint32_t b[3] = {256, 8, 4}; mk_map(enc, &P.mWd, d_in[7], 3, d, s, b, S0, L128); }
  P.x0 = (const bf16*)d_in[0]; P.wqkv = (const bf16*)d_in[1]; P.wo = (const bf16*)d_in[2]; P.wr = (const bf16*)d_in[4]; P.wg = (const bf16*)d_in[5]; P.wu = (const bf16*)d_in[6]; P.wd = (const bf16*)d_in[7];
  P.out = (bf16*)d_out;
  cudaGetSymbolAddress((void**)&P.g, g_scr);
  for (int b = 0; b < 128; b++) {
    int j = b >> 1, quad = j < 4 ? 0 : (j < 36 ? 1 + (j - 4) % 8 : 9 + (j - 36) % 7), pos = j < 4 ? j : (j < 36 ? (j - 4) / 8 : (j - 36) / 7);
    int bid = ((quad >> 2) * 2 + (pos >> 1)) * 16 + ((quad & 3) * 2 + (pos & 1)) * 2 + (b & 1);
    int e = pos * 2 + (b & 1), fid = e < 7 ? quad * 7 + e : 112 + quad;
    P.map[b] = bid | fid << 8;
  }
  fused_kernel<<<128, 512, SMEM_BYTES>>>(P);
}
```

```cpp
#include <cuda_runtime.h>
#include <cuda_bf16.h>
#include <cuda.h>
#include <stdint.h>
#include <stddef.h>
typedef __nv_bfloat16 bf16;

template<int TB, int TA = 0> __device__ __forceinline__ void wgmma_ss_n192(float (&d)[96], uint64_t da, uint64_t db, int scale_d) {
  asm volatile("{\n.reg .pred p;\nsetp.ne.b32 p, %98, 0;\n"
    "wgmma.mma_async.sync.aligned.m64n192k16.f32.bf16.bf16 {%0, %1, %2, %3, %4, %5, %6, %7, %8, %9, %10, %11, %12, %13, %14, %15, %16, %17, %18, %19, %20, %21, %22, %23, %24, %25, %26, %27, %28, %29, %30, %31, %32, %33, %34, %35, %36, %37, %38, %39, %40, %41, %42, %43, %44, %45, %46, %47, %48, %49, %50, %51, %52, %53, %54, %55, %56, %57, %58, %59, %60, %61, %62, %63, %64, %65, %66, %67, %68, %69, %70, %71, %72, %73, %74, %75, %76, %77, %78, %79, %80, %81, %82, %83, %84, %85, %86, %87, %88, %89, %90, %91, %92, %93, %94, %95}, %96, %97, p, 1, 1, %100, %99;\n}\n"
    : "+f"(d[0]), "+f"(d[1]), "+f"(d[2]), "+f"(d[3]), "+f"(d[4]), "+f"(d[5]), "+f"(d[6]), "+f"(d[7]), "+f"(d[8]), "+f"(d[9]), "+f"(d[10]), "+f"(d[11]), "+f"(d[12]), "+f"(d[13]), "+f"(d[14]), "+f"(d[15]), "+f"(d[16]), "+f"(d[17]), "+f"(d[18]), "+f"(d[19]), "+f"(d[20]), "+f"(d[21]), "+f"(d[22]), "+f"(d[23]), "+f"(d[24]), "+f"(d[25]), "+f"(d[26]), "+f"(d[27]), "+f"(d[28]), "+f"(d[29]), "+f"(d[30]), "+f"(d[31]), "+f"(d[32]), "+f"(d[33]), "+f"(d[34]), "+f"(d[35]), "+f"(d[36]), "+f"(d[37]), "+f"(d[38]), "+f"(d[39]), "+f"(d[40]), "+f"(d[41]), "+f"(d[42]), "+f"(d[43]), "+f"(d[44]), "+f"(d[45]), "+f"(d[46]), "+f"(d[47]), "+f"(d[48]), "+f"(d[49]), "+f"(d[50]), "+f"(d[51]), "+f"(d[52]), "+f"(d[53]), "+f"(d[54]), "+f"(d[55]), "+f"(d[56]), "+f"(d[57]), "+f"(d[58]), "+f"(d[59]), "+f"(d[60]), "+f"(d[61]), "+f"(d[62]), "+f"(d[63]), "+f"(d[64]), "+f"(d[65]), "+f"(d[66]), "+f"(d[67]), "+f"(d[68]), "+f"(d[69]), "+f"(d[70]), "+f"(d[71]), "+f"(d[72]), "+f"(d[73]), "+f"(d[74]), "+f"(d[75]), "+f"(d[76]), "+f"(d[77]), "+f"(d[78]), "+f"(d[79]), "+f"(d[80]), "+f"(d[81]), "+f"(d[82]), "+f"(d[83]), "+f"(d[84]), "+f"(d[85]), "+f"(d[86]), "+f"(d[87]), "+f"(d[88]), "+f"(d[89]), "+f"(d[90]), "+f"(d[91]), "+f"(d[92]), "+f"(d[93]), "+f"(d[94]), "+f"(d[95])
    : "l"(da), "l"(db), "r"(scale_d), "n"(TB), "n"(TA));
}

template<int TB> __device__ __forceinline__ void wgmma_rs_n192(float (&d)[96], uint32_t a0, uint32_t a1, uint32_t a2, uint32_t a3, uint64_t db, int scale_d) {
  asm volatile("{\n.reg .pred p;\nsetp.ne.b32 p, %101, 0;\n"
    "wgmma.mma_async.sync.aligned.m64n192k16.f32.bf16.bf16 {%0, %1, %2, %3, %4, %5, %6, %7, %8, %9, %10, %11, %12, %13, %14, %15, %16, %17, %18, %19, %20, %21, %22, %23, %24, %25, %26, %27, %28, %29, %30, %31, %32, %33, %34, %35, %36, %37, %38, %39, %40, %41, %42, %43, %44, %45, %46, %47, %48, %49, %50, %51, %52, %53, %54, %55, %56, %57, %58, %59, %60, %61, %62, %63, %64, %65, %66, %67, %68, %69, %70, %71, %72, %73, %74, %75, %76, %77, %78, %79, %80, %81, %82, %83, %84, %85, %86, %87, %88, %89, %90, %91, %92, %93, %94, %95}, {%96, %97, %98, %99}, %100, p, 1, 1, %102;\n}\n"
    : "+f"(d[0]), "+f"(d[1]), "+f"(d[2]), "+f"(d[3]), "+f"(d[4]), "+f"(d[5]), "+f"(d[6]), "+f"(d[7]), "+f"(d[8]), "+f"(d[9]), "+f"(d[10]), "+f"(d[11]), "+f"(d[12]), "+f"(d[13]), "+f"(d[14]), "+f"(d[15]), "+f"(d[16]), "+f"(d[17]), "+f"(d[18]), "+f"(d[19]), "+f"(d[20]), "+f"(d[21]), "+f"(d[22]), "+f"(d[23]), "+f"(d[24]), "+f"(d[25]), "+f"(d[26]), "+f"(d[27]), "+f"(d[28]), "+f"(d[29]), "+f"(d[30]), "+f"(d[31]), "+f"(d[32]), "+f"(d[33]), "+f"(d[34]), "+f"(d[35]), "+f"(d[36]), "+f"(d[37]), "+f"(d[38]), "+f"(d[39]), "+f"(d[40]), "+f"(d[41]), "+f"(d[42]), "+f"(d[43]), "+f"(d[44]), "+f"(d[45]), "+f"(d[46]), "+f"(d[47]), "+f"(d[48]), "+f"(d[49]), "+f"(d[50]), "+f"(d[51]), "+f"(d[52]), "+f"(d[53]), "+f"(d[54]), "+f"(d[55]), "+f"(d[56]), "+f"(d[57]), "+f"(d[58]), "+f"(d[59]), "+f"(d[60]), "+f"(d[61]), "+f"(d[62]), "+f"(d[63]), "+f"(d[64]), "+f"(d[65]), "+f"(d[66]), "+f"(d[67]), "+f"(d[68]), "+f"(d[69]), "+f"(d[70]), "+f"(d[71]), "+f"(d[72]), "+f"(d[73]), "+f"(d[74]), "+f"(d[75]), "+f"(d[76]), "+f"(d[77]), "+f"(d[78]), "+f"(d[79]), "+f"(d[80]), "+f"(d[81]), "+f"(d[82]), "+f"(d[83]), "+f"(d[84]), "+f"(d[85]), "+f"(d[86]), "+f"(d[87]), "+f"(d[88]), "+f"(d[89]), "+f"(d[90]), "+f"(d[91]), "+f"(d[92]), "+f"(d[93]), "+f"(d[94]), "+f"(d[95])
    : "r"(a0), "r"(a1), "r"(a2), "r"(a3), "l"(db), "r"(scale_d), "n"(TB));
}

template<int TB, int TA = 0> __device__ __forceinline__ void wgmma_ss_n128(float (&d)[64], uint64_t da, uint64_t db, int scale_d) {
  asm volatile("{\n.reg .pred p;\nsetp.ne.b32 p, %66, 0;\n"
    "wgmma.mma_async.sync.aligned.m64n128k16.f32.bf16.bf16 {%0, %1, %2, %3, %4, %5, %6, %7, %8, %9, %10, %11, %12, %13, %14, %15, %16, %17, %18, %19, %20, %21, %22, %23, %24, %25, %26, %27, %28, %29, %30, %31, %32, %33, %34, %35, %36, %37, %38, %39, %40, %41, %42, %43, %44, %45, %46, %47, %48, %49, %50, %51, %52, %53, %54, %55, %56, %57, %58, %59, %60, %61, %62, %63}, %64, %65, p, 1, 1, %68, %67;\n}\n"
    : "+f"(d[0]), "+f"(d[1]), "+f"(d[2]), "+f"(d[3]), "+f"(d[4]), "+f"(d[5]), "+f"(d[6]), "+f"(d[7]), "+f"(d[8]), "+f"(d[9]), "+f"(d[10]), "+f"(d[11]), "+f"(d[12]), "+f"(d[13]), "+f"(d[14]), "+f"(d[15]), "+f"(d[16]), "+f"(d[17]), "+f"(d[18]), "+f"(d[19]), "+f"(d[20]), "+f"(d[21]), "+f"(d[22]), "+f"(d[23]), "+f"(d[24]), "+f"(d[25]), "+f"(d[26]), "+f"(d[27]), "+f"(d[28]), "+f"(d[29]), "+f"(d[30]), "+f"(d[31]), "+f"(d[32]), "+f"(d[33]), "+f"(d[34]), "+f"(d[35]), "+f"(d[36]), "+f"(d[37]), "+f"(d[38]), "+f"(d[39]), "+f"(d[40]), "+f"(d[41]), "+f"(d[42]), "+f"(d[43]), "+f"(d[44]), "+f"(d[45]), "+f"(d[46]), "+f"(d[47]), "+f"(d[48]), "+f"(d[49]), "+f"(d[50]), "+f"(d[51]), "+f"(d[52]), "+f"(d[53]), "+f"(d[54]), "+f"(d[55]), "+f"(d[56]), "+f"(d[57]), "+f"(d[58]), "+f"(d[59]), "+f"(d[60]), "+f"(d[61]), "+f"(d[62]), "+f"(d[63])
    : "l"(da), "l"(db), "r"(scale_d), "n"(TB), "n"(TA));
}

template<int TB, int TA = 0> __device__ __forceinline__ void wgmma_ss_n64(float (&d)[32], uint64_t da, uint64_t db, int scale_d) {
  asm volatile("{\n.reg .pred p;\nsetp.ne.b32 p, %34, 0;\n"
    "wgmma.mma_async.sync.aligned.m64n64k16.f32.bf16.bf16 {%0, %1, %2, %3, %4, %5, %6, %7, %8, %9, %10, %11, %12, %13, %14, %15, %16, %17, %18, %19, %20, %21, %22, %23, %24, %25, %26, %27, %28, %29, %30, %31}, %32, %33, p, 1, 1, %36, %35;\n}\n"
    : "+f"(d[0]), "+f"(d[1]), "+f"(d[2]), "+f"(d[3]), "+f"(d[4]), "+f"(d[5]), "+f"(d[6]), "+f"(d[7]), "+f"(d[8]), "+f"(d[9]), "+f"(d[10]), "+f"(d[11]), "+f"(d[12]), "+f"(d[13]), "+f"(d[14]), "+f"(d[15]), "+f"(d[16]), "+f"(d[17]), "+f"(d[18]), "+f"(d[19]), "+f"(d[20]), "+f"(d[21]), "+f"(d[22]), "+f"(d[23]), "+f"(d[24]), "+f"(d[25]), "+f"(d[26]), "+f"(d[27]), "+f"(d[28]), "+f"(d[29]), "+f"(d[30]), "+f"(d[31])
    : "l"(da), "l"(db), "r"(scale_d), "n"(TB), "n"(TA));
}

template<int TB, int TA = 0> __device__ __forceinline__ void wgmma_ss_n8(float (&d)[4], uint64_t da, uint64_t db, int scale_d) {
  asm volatile("{\n.reg .pred p;\nsetp.ne.b32 p, %6, 0;\n"
    "wgmma.mma_async.sync.aligned.m64n8k16.f32.bf16.bf16 {%0, %1, %2, %3}, %4, %5, p, 1, 1, %8, %7;\n}\n"
    : "+f"(d[0]), "+f"(d[1]), "+f"(d[2]), "+f"(d[3])
    : "l"(da), "l"(db), "r"(scale_d), "n"(TB), "n"(TA));
}

template<int TB> __device__ __forceinline__ void wgmma_rs_n40(float (&d)[20], uint32_t a0, uint32_t a1, uint32_t a2, uint32_t a3, uint64_t db, int scale_d) {
  asm volatile("{\n.reg .pred p;\nsetp.ne.b32 p, %25, 0;\n"
    "wgmma.mma_async.sync.aligned.m64n40k16.f32.bf16.bf16 {%0, %1, %2, %3, %4, %5, %6, %7, %8, %9, %10, %11, %12, %13, %14, %15, %16, %17, %18, %19}, {%20, %21, %22, %23}, %24, p, 1, 1, %26;\n}\n"
    : "+f"(d[0]), "+f"(d[1]), "+f"(d[2]), "+f"(d[3]), "+f"(d[4]), "+f"(d[5]), "+f"(d[6]), "+f"(d[7]), "+f"(d[8]), "+f"(d[9]), "+f"(d[10]), "+f"(d[11]), "+f"(d[12]), "+f"(d[13]), "+f"(d[14]), "+f"(d[15]), "+f"(d[16]), "+f"(d[17]), "+f"(d[18]), "+f"(d[19])
    : "r"(a0), "r"(a1), "r"(a2), "r"(a3), "l"(db), "r"(scale_d), "n"(TB));
}

#define DEVI __device__ __forceinline__
DEVI uint32_t smem_u32(const void* p) { return (uint32_t)__cvta_generic_to_shared(p); }
DEVI void mbar_init(uint32_t bar, uint32_t cnt) { asm volatile("mbarrier.init.shared::cta.b64 [%0], %1;" :: "r"(bar), "r"(cnt)); }
DEVI void mbar_expect_tx(uint32_t bar, uint32_t bytes) { asm volatile("mbarrier.arrive.expect_tx.shared::cta.b64 _, [%0], %1;" :: "r"(bar), "r"(bytes) : "memory"); }
DEVI void mbar_arrive(uint32_t bar) { asm volatile("mbarrier.arrive.shared::cta.b64 _, [%0];" :: "r"(bar) : "memory"); }
DEVI void mbar_arrive_peer(uint32_t bar) {
  asm volatile("{\n.reg .b32 ra;\nmapa.shared::cluster.u32 ra, %0, %1;\nmbarrier.arrive.shared::cluster.b64 _, [ra];\n}" :: "r"(bar), "r"((blockIdx.x & 1) ^ 1) : "memory");
}
DEVI void bulk_s2peer(uint32_t a, uint32_t bytes, uint32_t bar) {
  asm volatile("{\n.reg .b32 ra, rb;\nmapa.shared::cluster.u32 ra, %0, %3;\nmapa.shared::cluster.u32 rb, %2, %3;\n"
               "cp.async.bulk.shared::cluster.shared::cta.mbarrier::complete_tx::bytes [ra], [%0], %1, [rb];\n}"
               :: "r"(a), "r"(bytes), "r"(bar), "r"((blockIdx.x & 1) ^ 1) : "memory");
}
DEVI void mbar_wait(uint32_t bar, uint32_t parity) {
  asm volatile("{\n.reg .pred p;\nLW:\nmbarrier.try_wait.parity.shared::cta.b64 p, [%0], %1;\n@!p bra LW;\n}" :: "r"(bar), "r"(parity) : "memory");
}
DEVI uint32_t mbar_test(uint32_t bar, uint32_t parity) {
  uint32_t r; asm volatile("{\n.reg .pred p;\nmbarrier.test_wait.parity.shared::cta.b64 p, [%1], %2;\nselp.u32 %0, 1, 0, p;\n}" : "=r"(r) : "r"(bar), "r"(parity) : "memory"); return r;
}
DEVI void mbar_wait_b(uint32_t bar, uint32_t parity) {
  asm volatile("{\n.reg .pred p;\n.reg .u32 it;\nmov.u32 it, 0;\nLW:\nmbarrier.try_wait.parity.shared::cta.b64 p, [%0], %1;\n@p bra LD;\n"
               "add.u32 it, it, 1;\nsetp.lt.u32 p, it, 0x1000000;\n@p bra LW;\ntrap;\nLD:\n}" :: "r"(bar), "r"(parity) : "memory");
}
DEVI void tma_2d(uint32_t dst, const CUtensorMap* m, int c0, int c1, uint32_t bar) {
  asm volatile("cp.async.bulk.tensor.2d.shared::cluster.global.mbarrier::complete_tx::bytes [%0], [%1, {%3, %4}], [%2];"
    :: "r"(dst), "l"(m), "r"(bar), "r"(c0), "r"(c1) : "memory");
}
DEVI void tma_3d(uint32_t dst, const CUtensorMap* m, int c0, int c1, int c2, uint32_t bar) {
  asm volatile("cp.async.bulk.tensor.3d.shared::cluster.global.mbarrier::complete_tx::bytes [%0], [%1, {%3, %4, %5}], [%2];"
    :: "r"(dst), "l"(m), "r"(bar), "r"(c0), "r"(c1), "r"(c2) : "memory");
}
#define POL_EF POL_FIRST
constexpr uint64_t POL_FIRST = 0x12F0000000000000ull, POL_NORMAL = 0x1000000000000000ull;
DEVI void tma_2d_h(uint32_t dst, const CUtensorMap* m, int c0, int c1, uint32_t bar, uint64_t pol) {
  asm volatile("cp.async.bulk.tensor.2d.shared::cluster.global.mbarrier::complete_tx::bytes.L2::cache_hint [%0], [%1, {%3, %4}], [%2], %5;"
    :: "r"(dst), "l"(m), "r"(bar), "r"(c0), "r"(c1), "l"(pol) : "memory");
}
DEVI void tma_3d_h(uint32_t dst, const CUtensorMap* m, int c0, int c1, int c2, uint32_t bar, uint64_t pol) {
  asm volatile("cp.async.bulk.tensor.3d.shared::cluster.global.mbarrier::complete_tx::bytes.L2::cache_hint [%0], [%1, {%3, %4, %5}], [%2], %6;"
    :: "r"(dst), "l"(m), "r"(bar), "r"(c0), "r"(c1), "r"(c2), "l"(pol) : "memory");
}
DEVI void bulk_g2s_h(uint32_t s, const void* g, uint32_t bytes, uint32_t bar, uint64_t pol = POL_EF) {
  asm volatile("cp.async.bulk.shared::cluster.global.mbarrier::complete_tx::bytes.L2::cache_hint [%0], [%1], %2, [%3], %4;"
    :: "r"(s), "l"(g), "r"(bytes), "r"(bar), "l"(pol) : "memory");
}
DEVI void tma_5d(uint32_t dst, const CUtensorMap* m, int c0, int c1, int c2, int c3, int c4, uint32_t bar, uint64_t pol) {
  asm volatile("cp.async.bulk.tensor.5d.shared::cluster.global.mbarrier::complete_tx::bytes.L2::cache_hint [%0], [%1, {%3, %4, %5, %6, %7}], [%2], %8;"
    :: "r"(dst), "l"(m), "r"(bar), "r"(c0), "r"(c1), "r"(c2), "r"(c3), "r"(c4), "l"(pol) : "memory");
}
DEVI void tma_prefetch_2d(const CUtensorMap* m, int c0, int c1) {
  asm volatile("cp.async.bulk.prefetch.tensor.2d.L2.global.tile [%0, {%1, %2}];" :: "l"(m), "r"(c0), "r"(c1) : "memory");
}
DEVI void tma_prefetch_3d(const CUtensorMap* m, int c0, int c1, int c2) {
  asm volatile("cp.async.bulk.prefetch.tensor.3d.L2.global.tile [%0, {%1, %2, %3}];" :: "l"(m), "r"(c0), "r"(c1), "r"(c2) : "memory");
}
DEVI void bulk_prefetch(const void* g, uint32_t bytes) { asm volatile("cp.async.bulk.prefetch.L2.global [%0], %1;" :: "l"(g), "r"(bytes) : "memory"); }
DEVI void bulk_g2s(uint32_t s, const void* g, uint32_t bytes, uint32_t bar) {
  asm volatile("cp.async.bulk.shared::cluster.global.mbarrier::complete_tx::bytes [%0], [%1], %2, [%3];" :: "r"(s), "l"(g), "r"(bytes), "r"(bar) : "memory");
}
DEVI void bulk_s2g(void* g, uint32_t s, uint32_t bytes) {
  asm volatile("cp.async.bulk.global.shared::cta.bulk_group [%0], [%1], %2;\ncp.async.bulk.commit_group;" :: "l"(g), "r"(s), "r"(bytes) : "memory");
}
template<int N> DEVI void bulk_wait() { asm volatile("cp.async.bulk.wait_group %0;" :: "n"(N) : "memory"); }
DEVI void fence_async_smem() { asm volatile("fence.proxy.async.shared::cta;" ::: "memory"); }
DEVI void fence_async_glob() { asm volatile("fence.proxy.async.global;" ::: "memory"); }
DEVI unsigned ld_rlx(const unsigned* p) { unsigned v; asm volatile("ld.relaxed.gpu.global.u32 %0, [%1];" : "=r"(v) : "l"(p) : "memory"); return v; }
DEVI void st_rlx(unsigned* p, unsigned v) { asm volatile("st.relaxed.gpu.global.u32 [%0], %1;" :: "l"(p), "r"(v) : "memory"); }
DEVI uint2 ldg_stream(const uint2* p) { uint2 v; asm volatile("ld.global.nc.L1::no_allocate.v2.u32 {%0, %1}, [%2];" : "=r"(v.x), "=r"(v.y) : "l"(p)); return v; }
DEVI void fence_rel() { asm volatile("fence.release.gpu;" ::: "memory"); }
DEVI uint4 ld_ll(const uint4* p) {
  uint4 v;
  asm volatile("{\n.reg .b128 t;\n.reg .b64 a, b;\nld.relaxed.gpu.global.b128 t, [%4];\nmov.b128 {a, b}, t;\nmov.b64 {%0, %1}, a;\nmov.b64 {%2, %3}, b;\n}"
               : "=r"(v.x), "=r"(v.y), "=r"(v.z), "=r"(v.w) : "l"(p) : "memory");
  return v;
}
DEVI void st_ll(uint4* p, uint32_t x, uint32_t y, uint32_t z, uint32_t w) {
  asm volatile("{\n.reg .b128 t;\n.reg .b64 a, b;\nmov.b64 a, {%1, %2};\nmov.b64 b, {%3, %4};\nmov.b128 t, {a, b};\nst.relaxed.gpu.global.b128 [%0], t;\n}"
               :: "l"(p), "r"(x), "r"(y), "r"(z), "r"(w) : "memory");
}
#define SPIN_MAX 0x1000000
DEVI uint4 poll_ll(const uint4* p, uint32_t mask, uint32_t tag) {
  uint4 v; int it = 0;
  do { v = ld_ll(p); if (++it > SPIN_MAX) __trap(); } while (!__all_sync(0xffffffffu, (v.w & mask) == tag));
  return v;
}
DEVI void poll_ll2(const uint4* p, const uint4* q, uint32_t mask, uint32_t tag, uint4& a, uint4& b) {
  int it = 0;
  do { a = ld_ll(p); b = ld_ll(q); if (++it > SPIN_MAX) __trap(); } while (!__all_sync(0xffffffffu, (a.w & mask) == tag && (b.w & mask) == tag));
}
DEVI void bar_sync(int id, int n) { asm volatile("bar.sync %0, %1;" :: "r"(id), "r"(n) : "memory"); }
DEVI void bar_arrive(int id, int n) { asm volatile("bar.arrive %0, %1;" :: "r"(id), "r"(n) : "memory"); }
DEVI void wg_fence() { asm volatile("wgmma.fence.sync.aligned;" ::: "memory"); }
DEVI void wg_commit() { asm volatile("wgmma.commit_group.sync.aligned;" ::: "memory"); }
template<int N> DEVI void wg_wait() { asm volatile("wgmma.wait_group.sync.aligned %0;" :: "n"(N) : "memory"); }
template<int N> DEVI void reg_inc() { asm volatile("setmaxnreg.inc.sync.aligned.u32 %0;" :: "n"(N)); }
template<int N> DEVI void reg_dec() { asm volatile("setmaxnreg.dec.sync.aligned.u32 %0;" :: "n"(N)); }
DEVI float ex2f(float x) { float y; asm("ex2.approx.ftz.f32 %0, %1;" : "=f"(y) : "f"(x)); return y; }
DEVI uint32_t pack_bf16(float lo, float hi) { uint32_t r; asm("cvt.rn.bf16x2.f32 %0, %1, %2;" : "=r"(r) : "f"(hi), "f"(lo)); return r; }
DEVI float bf_lo(uint32_t v) { return __uint_as_float(v << 16); }
DEVI float bf_hi(uint32_t v) { return __uint_as_float(v & 0xffff0000u); }
DEVI float bf_round(float x) { return bf_lo(pack_bf16(x, 0.f)); }
DEVI void stsm_x4(uint32_t addr, uint32_t a, uint32_t b, uint32_t c, uint32_t d) {
  asm volatile("stmatrix.sync.aligned.m8n8.x4.shared.b16 [%0], {%1,%2,%3,%4};" :: "r"(addr), "r"(a), "r"(b), "r"(c), "r"(d) : "memory");
}
DEVI void ldsm_x4(uint32_t addr, uint32_t& a, uint32_t& b, uint32_t& c, uint32_t& d) {
  asm volatile("ldmatrix.sync.aligned.m8n8.x4.shared.b16 {%0,%1,%2,%3}, [%4];" : "=r"(a), "=r"(b), "=r"(c), "=r"(d) : "r"(addr) : "memory");
}
DEVI uint4 lds128(uint32_t a) { uint4 v; asm volatile("ld.shared.v4.u32 {%0,%1,%2,%3}, [%4];" : "=r"(v.x), "=r"(v.y), "=r"(v.z), "=r"(v.w) : "r"(a) : "memory"); return v; }
DEVI void sts128(uint32_t a, uint4 v) { asm volatile("st.shared.v4.u32 [%0], {%1,%2,%3,%4};" :: "r"(a), "r"(v.x), "r"(v.y), "r"(v.z), "r"(v.w) : "memory"); }
DEVI float2 lds64f(uint32_t a) { float2 v; asm volatile("ld.shared.v2.f32 {%0,%1}, [%2];" : "=f"(v.x), "=f"(v.y) : "r"(a) : "memory"); return v; }
DEVI void sts64f(uint32_t a, float x, float y) { asm volatile("st.shared.v2.f32 [%0], {%1,%2};" :: "r"(a), "f"(x), "f"(y) : "memory"); }
DEVI uint32_t lds32(uint32_t a) { uint32_t v; asm volatile("ld.shared.u32 %0, [%1];" : "=r"(v) : "r"(a) : "memory"); return v; }
DEVI float lds32f(uint32_t a) { return __uint_as_float(lds32(a)); }
DEVI void sts32(uint32_t a, uint32_t v) { asm volatile("st.shared.u32 [%0], %1;" :: "r"(a), "r"(v) : "memory"); }
DEVI void sts32f(uint32_t a, float v) { sts32(a, __float_as_uint(v)); }
DEVI void sts16(uint32_t a, uint32_t v) { asm volatile("st.shared.u16 [%0], %1;" :: "r"(a), "h"((unsigned short)v) : "memory"); }
template<int N> DEVI void keep(float (&d)[N]) {
  #pragma unroll
  for (int i = 0; i < N; i++) asm volatile("" : "+f"(d[i]) :: "memory");
}
template<int N> DEVI void keep(uint32_t (&d)[N]) {
  #pragma unroll
  for (int i = 0; i < N; i++) asm volatile("" : "+r"(d[i]) :: "memory");
}
template<uint32_t HI> DEVI uint64_t mkd(uint32_t lo) { uint64_t r; asm("mov.b64 %0, {%1, %2};" : "=l"(r) : "r"(lo), "n"(HI)); return r; }
constexpr uint32_t HI128 = (1u << 30) | (1024 >> 4), HI64 = (2u << 30) | (512 >> 4);
#define VOFF(x) ((uint32_t)(x) * (uint32_t)(1 - 65536))
DEVI bool elect() { uint32_t p; asm volatile("{\n.reg .pred q;\nelect.sync _|q, 0xffffffff;\nselp.u32 %0, 1, 0, q;\n}" : "=r"(p)); return p; }
DEVI void warp_signal(uint32_t bar) { __syncwarp(); if (elect()) mbar_arrive(bar); }

struct Scratch {
  uint4 kv[128][4][1024];
  uint4 o[8][2][8][2][1024];
  uint4 x[8][16][2048];
  uint4 zero[1024];
  uint4 statP[8][2048];
  uint4 statF[2048];
  uint4 csP[16][8][96];
  uint4 best[8][16];
  uint4 row[16][256];
  uint4 yP[128][112][2];
  uint4 x2[8][256];
  uint4 patch[128][64];
  unsigned flagKV[128][32];
  unsigned flagO[8][32];
  unsigned flagX[8][32];
  unsigned epoch;
};
__device__ __align__(1024) Scratch g_scr;
#define PROFT(cond, slot)
#define PROFW(cond, slot)
#define PROFD(cond, slot)
#define PROFX(cond, slot)
#define PROFY(cond, slot)

constexpr uint32_t SB0 = 65536, HOLE = 90112, SA2 = 98304, SB1 = 131072, SB2 = 155648, STG = 180224;
constexpr uint32_t KVA = 0, KVB = 98304, QO = 65536;
constexpr uint32_t MISC = 229376, CS = MISC, ONES = MISC + 768, BARS = MISC + 1792, INFO = MISC + 2208, WR = MISC + 2224, X2SEG = MISC + 2736, INFO2 = MISC + 2992, DUMP = MISC + 3040;
constexpr uint32_t PAR = HOLE, HV = HOLE + 2048, RED = HOLE + 6144, PATCH = 196608;
constexpr uint32_t SMEM_BYTES = 232448;
enum { B_FULLQ = 0, B_EMPTYQ = 3, B_FULLW = 6, B_EMPTYW = 12, B_HAFREE = 18, B_OFREE = 20,
       B_XFREE = 21,
       B_KVRDY = 23, B_ORDY = 27, B_XRDY = 35, B_STGE = 39,
       B_KVFULL = 42, B_RES = 46, B_PAR = 47, B_STG = 48, B_PFREE = 51, B_COUNT = 52,
       B_ROW = 154 };
#define BAR(x) (sb + BARS + 8 * (x))
DEVI uint32_t qa_off(int s) { return s == 2 ? SA2 : (uint32_t)s * 32768u; }
DEVI uint32_t qb_off(int s) { return s == 0 ? SB0 : (s == 1 ? SB1 : SB2); }
DEVI int kb_order(int bc, int n) {
  const int e = n < 9 ? n - 2 : n - 9;
  return n < 2 ? 2 * bc + n : 2 * (((e < 4 ? e + 4 : e - 4 + (e - 4 >= (bc & 3))) + (bc & 4)) & 7) + (n >= 9);
}
DEVI int wo_order(int bc, int n) { return (n & 8) | ((n + (bc & 6)) & 7); }
DEVI uint32_t w_off(int s) { return (uint32_t)((0x143065 >> (4 * s)) & 7) * 32768u; }
DEVI uint32_t w_par(int n, int s, int L) { return (n >= 6 && n < 12) ^ (s == 5) ^ (s != 2 && L); }
DEVI int w_next(int n, int s) { return s == 5 ? 0 : (n == 13 ? 3 : s + 1); }

struct Params {
  CUtensorMap mX, mXh, mWq, mWo, mWg, mWu, mWp, mWd;
  const bf16 *x0, *wqkv, *wo, *wr, *wg, *wu, *wd;
  bf16* out;
  Scratch* g;
  unsigned map[128];
};
#define BID ((int)(P.map[blockIdx.x] & 255))
#define FID ((int)(P.map[blockIdx.x] >> 8))
DEVI uint32_t uni(uint32_t v) { return __shfl_sync(0xffffffffu, v, 0); }
#define PQ_N 8
#define PQ_T 700
#define PF0_N 10
#define PF0_T 1600
#define PF1_E 24
#define PF1_T 1100
#define POL_Q1 POL_NORMAL
#define POL_X POL_NORMAL
#define PFA0_BAR 3
#define PFA1_BAR 0
#define PFA0_M 0
#define PFA1_M 0
#define PFA0_T 900
#define PFA1_T 700
#define PF1_S PF0_N
#define PF1_D 0
#define POL_G POL_NORMAL
#define POL_U POL_FIRST
#define POL_D POL_FIRST
#define JQ_N 6
#define WDSRC (P.wd + (size_t)min(fid, 111) * 32768)
#define WDSRC2 (P.wd + FID * 32768)
#define WD_N 4
#define THR_N 5
#define KV_D 1800
#define XD_D 300
#define W0_BAR 3
#define QEF_N 99
#define PACE_T 300
#define IDLE_T 11000
#define LATE_C 2
#define LATE_B B_XFREE + 1
#define LATE_P 0
#define POL_Q0 POL_NORMAL
constexpr float LN_EPS = 1e-5f;
constexpr float QSCALE = 0.17677669529663687f * 1.4426950408889634f;

DEVI void fma8(float (&a)[8], uint4 v, float h) {
  a[0] = fmaf(bf_lo(v.x), h, a[0]); a[1] = fmaf(bf_hi(v.x), h, a[1]); a[2] = fmaf(bf_lo(v.y), h, a[2]); a[3] = fmaf(bf_hi(v.y), h, a[3]);
  a[4] = fmaf(bf_lo(v.z), h, a[4]); a[5] = fmaf(bf_hi(v.z), h, a[5]); a[6] = fmaf(bf_lo(v.w), h, a[6]); a[7] = fmaf(bf_hi(v.w), h, a[7]);
}
DEVI uint4 ldsv128(uint32_t a) { uint4 v; asm volatile("ld.volatile.shared.v4.u32 {%0,%1,%2,%3}, [%4];" : "=r"(v.x), "=r"(v.y), "=r"(v.z), "=r"(v.w) : "r"(a) : "memory"); return v; }
DEVI float ldsv32f(uint32_t a) { float v; asm volatile("ld.volatile.shared.f32 %0, [%1];" : "=f"(v) : "r"(a) : "memory"); return v; }
DEVI uint32_t clk() { uint32_t t; asm volatile("mov.u32 %0, %%clock;" : "=r"(t)); return t; }
DEVI int fresh_tid() { int t; asm volatile("mov.u32 %0, %%tid.x;" : "=r"(t)); return t & 127; }
DEVI float fold8(const float (&a)[8]) {
  const int lane = threadIdx.x & 31;
  const bool u = lane & 16, v = lane & 8, x = lane & 4;
  float b0 = (u ? a[4] : a[0]) + __shfl_xor_sync(0xffffffffu, u ? a[0] : a[4], 16), b1 = (u ? a[5] : a[1]) + __shfl_xor_sync(0xffffffffu, u ? a[1] : a[5], 16);
  float b2 = (u ? a[6] : a[2]) + __shfl_xor_sync(0xffffffffu, u ? a[2] : a[6], 16), b3 = (u ? a[7] : a[3]) + __shfl_xor_sync(0xffffffffu, u ? a[3] : a[7], 16);
  float c0 = (v ? b2 : b0) + __shfl_xor_sync(0xffffffffu, v ? b0 : b2, 8), c1 = (v ? b3 : b1) + __shfl_xor_sync(0xffffffffu, v ? b1 : b3, 8);
  return (x ? c1 : c0) + __shfl_xor_sync(0xffffffffu, x ? c0 : c1, 4);
}
DEVI float swiglu(float g, float u) { g = bf_round(g); return bf_round(bf_round(__fdividef(g, 1.f + __expf(-g))) * bf_round(u)); }

DEVI void qk_issue(float (&s)[32], uint32_t qd, uint32_t kd) {
  wgmma_ss_n64<0>(s, mkd<HI64>(qd), mkd<HI64>(kd), 0);
  wgmma_ss_n64<0>(s, mkd<HI64>(qd + 2), mkd<HI64>(kd + 2), 1);
}
template<int J0, int J1> DEVI void exp_pack(const float (&s)[32], uint32_t (&p)[16]) {
  #pragma unroll
  for (int j = J0; j < J1; j++) p[j] = pack_bf16(ex2f(s[2 * j]), ex2f(s[2 * j + 1]));
}
DEVI bool attn_pack(const float (&o)[20], uint32_t (&ob)[8]) {
  const float lo = 5.421010862427522e-20f, hi = 1.8446744073709552e19f;
  float i0, i1; asm("rcp.approx.ftz.f32 %0, %1;" : "=f"(i0) : "f"(o[16])); asm("rcp.approx.ftz.f32 %0, %1;" : "=f"(i1) : "f"(o[18]));
  #pragma unroll
  for (int e = 0; e < 8; e++) ob[e] = pack_bf16(o[2 * e] * ((e & 1) ? i1 : i0), o[2 * e + 1] * ((e & 1) ? i1 : i0));
  return __all_sync(0xffffffffu, o[16] >= lo && o[16] <= hi && o[18] >= lo && o[18] <= hi);
}
DEVI void attn_store(const uint32_t (&ob)[8], bool ok, uint32_t st, uint32_t sb, uint32_t bar) {
  stsm_x4(ok ? st : sb + DUMP, ob[0], ob[1], ob[2], ob[3]); stsm_x4(ok ? st ^ 32 : sb + DUMP, ob[4], ob[5], ob[6], ob[7]);
  __syncwarp();
  asm volatile("{\n.reg .pred p, q;\nelect.sync _|q, 0xffffffff;\nsetp.ne.and.u32 p, %1, 0, q;\n@p mbarrier.arrive.shared::cta.b64 _, [%0];\n}" :: "r"(bar), "r"((uint32_t)ok) : "memory");
}
DEVI void attn_exact(uint32_t st, uint32_t kv, int t, bool hasprev, uint32_t bar) {
  const int lane = threadIdx.x & 31;
  #pragma unroll 1
  for (int row = ((threadIdx.x >> 5) & 3) * 16, n = 0; n < 16; n++, row++) {
    const int k1 = 256 + t * 64 + row;
    float m = -INFINITY, l = 0.f, o = 0.f;
    #pragma unroll 1
    for (int k0 = hasprev ? k1 - 255 : 256; k0 <= k1; k0 += 32) {
      const int k = min(k0 + lane, k1), r = k & 63;
      float sc = 0.f;
      #pragma unroll 1
      for (int c = 0; c < 16; c++) {
        uint32_t a = lds32(st + row * 64 + ((c * 4) ^ ((row & 6) << 3))), b = lds32(kv + (k >> 6) * 8192 + r * 64 + ((c * 4) ^ ((r & 6) << 3)));
        sc = fmaf(bf_lo(a), bf_lo(b), fmaf(bf_hi(a), bf_hi(b), sc));
      }
      float mn = fmaxf(m, sc);
      #pragma unroll 1
      for (int x = 16; x; x >>= 1) mn = fmaxf(mn, __shfl_xor_sync(0xffffffffu, mn, x));
      const float al = ex2f(m - mn), pr = ex2f(sc - mn);
      m = mn; l *= al; o *= al;
      #pragma unroll 1
      for (int q = k0; q <= min(k0 + 31, k1); q++) {
        const float z = __shfl_sync(0xffffffffu, pr, q - k0);
        uint32_t b = lds32(kv + (q >> 6) * 8192 + 4096 + (q & 63) * 64 + (((lane >> 1) * 4) ^ ((q & 6) << 3)));
        l += z; o = fmaf(z, (lane & 1) ? bf_hi(b) : bf_lo(b), o);
      }
    }
    __syncwarp();
    sts16(st + row * 64 + ((lane * 2) ^ ((row & 6) << 3)), pack_bf16(__fdividef(o, l), 0.f));
  }
  warp_signal(bar);
}

template<int K0, int K1, int DONE = 0> DEVI void exp_pv(const float (&s)[32], uint32_t (&p)[16], float (&o)[20], uint32_t vd, bool accum) {
  #pragma unroll
  for (int ks = K0; ks < K1; ks++) {
    if (ks >= DONE) {
      #pragma unroll
      for (int j = 4 * ks; j < 4 * ks + 4; j++) p[j] = pack_bf16(ex2f(s[2 * j]), ex2f(s[2 * j + 1]));
    }
    asm volatile("" : "+r"(p[4 * ks]), "+r"(p[4 * ks + 1]), "+r"(p[4 * ks + 2]), "+r"(p[4 * ks + 3]));
    wg_fence();
    wgmma_rs_n40<1>(o, p[ks * 4], p[ks * 4 + 1], p[ks * 4 + 2], p[ks * 4 + 3], mkd<HI64>(vd + VOFF(ks * 64)), ks ? 1 : accum);
  }
}
DEVI void exp_pv2(const float (&s)[32], const float (&sx)[32], uint32_t (&p)[16], uint32_t (&px)[16], float (&o)[20], uint32_t v0, uint32_t v4,
                  const uint32_t (&msk)[9], int tdiag) {
  #pragma unroll
  for (int ks = 0; ks < 4; ks++) {
    #pragma unroll
    for (int j = 4 * ks; j < 4 * ks + 4; j++) {
      const int c = 8 * (j >> 1) - 8 * (j & 1);
      const uint32_t e = pack_bf16(ex2f(c > tdiag ? s[2 * j] : sx[2 * j]), ex2f(c + 1 > tdiag ? s[2 * j + 1] : sx[2 * j + 1])), m = msk[(j >> 1) - (j & 1) + 1];
      p[j] = e & m; px[j] = e & ~m;
      asm volatile("" : "+r"(p[j]), "+r"(px[j]));
    }
    wg_fence();
    wgmma_rs_n40<1>(o, p[ks * 4], p[ks * 4 + 1], p[ks * 4 + 2], p[ks * 4 + 3], mkd<HI64>(v0 + VOFF(ks * 64)), 1);
    wgmma_rs_n40<1>(o, px[ks * 4], px[ks * 4 + 1], px[ks * 4 + 2], px[ks * 4 + 3], mkd<HI64>(v4 + VOFF(ks * 64)), 1);
  }
}

template<int J0> DEVI void qkv_store(const float (&a)[96], float p0, float p1, uint32_t d) {
  #pragma unroll
  for (int hh = 0; hh < 2; hh++) {
    const int j = 4 * (J0 + 2 * hh);
    stsm_x4(d ^ (hh << 5), pack_bf16(a[j] * p0, a[j + 1] * p0), pack_bf16(a[j + 2] * p1, a[j + 3] * p1),
                           pack_bf16(a[j + 4] * p0, a[j + 5] * p0), pack_bf16(a[j + 6] * p1, a[j + 7] * p1));
  }
}
DEVI void mean_step(float (&a)[96], float m0, float m1, uint32_t cd, bool z) {
  const uint32_t u0 = z ? 0u : __float_as_uint(m0), u1 = z ? 0u : __float_as_uint(m1);
  uint32_t ma[4] = {__byte_perm(u0, 0u, 0x1010), __byte_perm(u1, 0u, 0x1010), __byte_perm(u0, 0u, 0x3232), __byte_perm(u1, 0u, 0x3232)};
  keep(ma);
  wg_fence();
  wgmma_rs_n192<1>(a, ma[0], ma[1], ma[2], ma[3], mkd<2>(cd), 1);
  wg_commit();
}

template<bool FIRST> DEVI void qkv_block(float (&aX)[96], float (&aY)[96], uint32_t sb16, int s, int tX, int tY) {
  uint32_t a16 = sb16 + (qa_off(s) >> 4), b16 = (sb16 + (qb_off(s) >> 4)) | ((8192u >> 4) << 16);
  uint32_t ax = (a16 + tX * 512) | 0x10000u, ay = (a16 + tY * 512) | 0x10000u;
  wg_fence();
  #pragma unroll
  for (int ks = 0; ks < 4; ks++) {
    wgmma_ss_n192<1>(aX, mkd<HI128>(ax + ks * 2), mkd<HI128>(b16 + ks * 128), !(FIRST && ks == 0));
    wgmma_ss_n192<1>(aY, mkd<HI128>(ay + ks * 2), mkd<HI128>(b16 + ks * 128), !(FIRST && ks == 0));
  }
  wg_commit();
}
DEVI void qkv_half(float (&a)[96], uint32_t sb16, int t, uint32_t sa, uint32_t sbb) {
  wg_fence();
  #pragma unroll
  for (int ks = 0; ks < 4; ks++)
    wgmma_ss_n192<1>(a, mkd<HI128>(((sb16 + (sa >> 4) + t * 512) | 0x10000u) + ks * 2), mkd<HI128>(((sb16 + (sbb >> 4)) | ((8192u >> 4) << 16)) + ks * 128), 1);
  wg_commit();
}
DEVI void wo_block(float (&acc)[64], uint32_t sb16, int s, int wg) {
  uint32_t a16 = (sb16 + (w_off(s) >> 4) + wg * 256) | 0x10000u, b16 = (sb16 + (w_off(s) >> 4) + 1024) | ((8192u >> 4) << 16);
  wg_fence();
  #pragma unroll
  for (int ks = 0; ks < 4; ks++)
    wgmma_ss_n128<1>(acc, mkd<HI64>(a16 + (ks >> 1) * 512 + (ks & 1) * 2), mkd<HI128>(b16 + ks * 128), 1);
  wg_commit();
}
DEVI void consumer(const Params& P, uint32_t sb, int wg) {
  const int w = uni((threadIdx.x >> 5) & 3);
  #define LAYER uni(mbar_test(BAR(B_XRDY + wg * 2 + 1), 0))
  #define IDS L = LAYER; const int tid = fresh_tid(), lane = tid & 31
  const uint32_t ids = uni(P.map[blockIdx.x]);
  const int bi = (ids >> 4) & 7, rh = ids & 1, bc = (ids & 15) >> 1, fid = ids >> 8;
  const int tX = 3 - wg, tY = wg;
  constexpr uint32_t sb16 = 1024 >> 4;
  #pragma unroll 1
  while (true) {
    int L = LAYER;
    {
      float aX[96], aY[96];
      const bool lead = fresh_tid() == 0;
      mbar_wait(BAR(B_FULLQ), 0);
      PROFW(threadIdx.x == 0, L * 8 + 1);
      qkv_block<true>(aX, aY, sb16, 0, tX, tY);
      #pragma unroll 1
      for (int n = 1, s = 1, ps = 0, ph = 0; n < 14; n++) {
        mbar_wait(BAR(B_FULLQ + s), ph ^ (s ? L : 0));
        PROFD(threadIdx.x == 0 && L && (n == 2 || n == 3 || n == 7 || n == 11 || n == 13), n == 2 ? 48 : 49 + (n >> 2));
        qkv_block<false>(aX, aY, sb16, s, tX, tY);
        wg_wait<1>(); if (lead) mbar_arrive(BAR(B_EMPTYQ + ps));
        ps = s; if (s == 2) { s = 0; ph ^= 1; } else s++;
      }
      mbar_wait(BAR(B_FULLQ + 2), L);
      qkv_half(aX, sb16, tX, SA2, SB2);
      mbar_wait(BAR(B_ROW), L);
      IDS;
      const uint32_t pa = sb + PAR + (w * 16 + (lane >> 2)) * 8;
      float2 p0 = lds64f(pa + tX * 512), p1 = lds64f(pa + tX * 512 + 64), p2 = lds64f(pa + tY * 512), p3 = lds64f(pa + tY * 512 + 64);
      mean_step(aX, p0.y, p1.y, sb16 + (CS >> 4), lane & 3);
      mbar_wait(BAR(B_FULLQ), 1);
      qkv_half(aX, sb16, tX, 0, SB0);
      wg_wait<3>(); if (lead) mbar_arrive(BAR(B_EMPTYQ + 1));
      bar_sync(1, 256);
      qkv_half(aY, sb16, tY, SA2, SB2);
      wg_wait<1>(); keep(aX);
      const int srow = w * 16 + (lane & 15);
      const uint32_t x0 = sb + srow * 64 + (((lane >> 4) ^ ((srow >> 1) & 3)) << 4), xX = x0 + (4 + tX) * 8192, xY = x0 + (4 + tY) * 8192;
      qkv_store<8>(aX, p0.x, p1.x, xX + KVA); qkv_store<16>(aX, p0.x, p1.x, xX + KVA + 4096);
      warp_signal(BAR(B_KVRDY + wg * 2));
      qkv_half(aY, sb16, tY, 0, SB0);
      mean_step(aY, p2.y, p3.y, sb16 + (CS >> 4), fresh_tid() & 3);
      wg_wait<2>(); if (lead) mbar_arrive(BAR(B_EMPTYQ + 2));
      mbar_wait(BAR(B_EMPTYQ + 2), L);
      qkv_store<12>(aX, p0.x, p1.x, xX + KVB); qkv_store<20>(aX, p0.x, p1.x, xX + KVB + 4096);
      wg_wait<0>(); keep(aY);
      if (lead) mbar_arrive(BAR(B_EMPTYQ));
      PROFW(threadIdx.x == 0, L * 8 + 2);
      qkv_store<8>(aY, p2.x, p3.x, xY + KVA); qkv_store<16>(aY, p2.x, p3.x, xY + KVA + 4096);
      qkv_store<12>(aY, p2.x, p3.x, xY + KVB); qkv_store<20>(aY, p2.x, p3.x, xY + KVB + 4096);
      warp_signal(BAR(B_KVRDY + wg * 2 + 1));
      p0.x *= QSCALE; p1.x *= QSCALE; p2.x *= QSCALE; p3.x *= QSCALE;
      mbar_wait(BAR(B_EMPTYQ), 1);
      qkv_store<0>(aX, p0.x, p1.x, x0 + QO + tX * 4096);
      qkv_store<0>(aY, p2.x, p3.x, x0 + QO + tY * 4096); qkv_store<4>(aY, p2.x, p3.x, x0 + QO + 16384 + tY * 4096);
      mbar_wait(BAR(B_PAR), L);
      qkv_store<4>(aX, p0.x, p1.x, x0 + QO + 16384 + tX * 4096);
      const int prow = (int)uni(lds32(sb + INFO)) - bi * 256;
      if ((prow >> 4) == tX * 4 + w || (prow >> 4) == tY * 4 + w) {
        __syncwarp();
        if (lane < 24) sts128(sb + (prow & 63) * 64 + (((lane ^ (prow >> 1)) & 3) << 4) +
                              (lane < 8 ? QO + (lane >> 2) * 16384 + (prow >> 6) * 4096 : ((lane & 4) ? KVB : KVA) + (4 + (prow >> 6)) * 8192 + (lane >> 4) * 4096),
                              lds128(sb + PATCH + lane * 16));
      }
      fence_async_smem();
      bar_sync(1, 256);
    }
    PROFW(threadIdx.x == 0, L * 8 + 3);
    float2 fa, fb;
    { const float2* f = (const float2*)&P.g->statF[bi * 256 + rh * 128 + (wg ^ rh) * 64 + w * 16 + ((fresh_tid() & 31) >> 2)];
      fa = __ldcg(f); fb = __ldcg(f + 16); }
    {
      IDS;
      float s0[32], s1[32], sx[32], o[20], op[20];
      uint32_t p0[16], p1[16], px[16], msk[9];
      const int tdiag = w * 16 + (lane >> 2) - 2 * (lane & 3);
      #pragma unroll
      for (int e = 0; e < 9; e++) msk[e] = ((8 * e - 8 > tdiag) ? 0xFFFFu : 0u) | ((8 * e - 7 > tdiag) ? 0xFFFF0000u : 0u);
      keep(msk);
      const uint32_t ones = (sb16 + (ONES >> 4)) << 16;
      const uint32_t qX = (sb16 + (QO >> 4) + tX * 256) | 0x10000u, qY = (sb16 + (QO >> 4) + tY * 256) | 0x10000u;
      const uint32_t kXB = (sb16 + (KVB >> 4) + tX * 512) | 0x10000u;
      uint32_t redo = 0;
      const uint32_t ost = sb + QO + (w * 16 + (lane & 15)) * 64 + (((lane >> 4) ^ ((lane >> 1) & 3)) << 4);
      #define QK(s, q, k) do { wg_fence(); qk_issue(s, q, k); wg_commit(); } while (0)
      #define QK2(q, k) do { wg_fence(); qk_issue(s1, q, k); qk_issue(sx, q, (k) + 2048); wg_commit(); } while (0)
      #define VB(v, b) ((v) + VOFF((b) * 512))
      QK(s0, qX + 1024, kXB + 1536);
      #pragma unroll
      for (int e = 0; e < 20; e++) o[e] = 0.f;
      wg_wait<0>(); keep(s0);
      #pragma unroll 1
      for (int h = 1; h >= 0; h--) {
        const uint32_t kXA = kXB - ((KVB - KVA) >> 4), kX = h ? kXB : kXA, vX = VOFF((kX & 0xffffu) + 256) + ones;
        QK(s1, qX + h * 1024, kX + 1024);
        #pragma unroll
        for (int e = 0; e < 20; e++) op[e] = o[e];
        keep(op);
        exp_pv<0, 4>(s0, p0, o, VB(vX, 3), false); wg_commit();
        wg_wait<1>(); keep(s1);
        exp_pv<0, 2>(s1, p1, o, VB(vX, 2), true);
        bar_sync(h ? 12 + wg : 4 + wg * 4, h ? 128 : 160);
        QK(s0, qX, kXA + 512 + h * 1024);
        exp_pv<2, 4>(s1, p1, o, VB(vX, 2), true); wg_commit();
        wg_wait<0>(); keep(s0); keep(p0); keep(p1); keep(o);
      }
      #pragma unroll 1
      for (int h = 0; h < 2; h++) {
        const uint32_t kb16 = sb16 + ((h ? KVB : KVA) >> 4), kY = (kb16 + tY * 512) | 0x10000u, qy = qY + h * 1024;
        const uint32_t onesP = bi ? ones : (kb16 + 1984) << 16;
        const uint32_t vX = VOFF(kb16 + tX * 512 + 256), vY = VOFF(kb16 + tY * 512 + 256);
        uint32_t ob[8];
        QK2(qX + h * 1024, (kb16 + tX * 512) | 0x10000u);
        exp_pv<0, 4>(s0, p0, o, VB(vX + (wg ? onesP : ones), 1), true); wg_commit();
        wg_wait<1>(); keep(s1); keep(sx);
        QK(s0, qy, kY + 1536);
        exp_pv2(s1, sx, p1, px, o, vX + onesP, VB(vX + ones, 4), msk, tdiag); wg_commit();
        wg_wait<1>(); keep(s0); keep(p0);
        QK(s1, qy, kY + 1024);
        exp_pack<0, 4>(s0, p0);
        wg_wait<1>(); keep(o); keep(p1); keep(px);
        bool ok = attn_pack(o, ob); keep(ob);
        exp_pv<0, 4, 1>(s0, p0, o, VB(vY + (wg ? ones : onesP), 3), false); wg_commit();
        attn_store(ob, ok, ost + (h * 4 + tX) * 4096, sb, BAR(B_ORDY + wg * 4 + h * 2)); redo |= ok ? 0u : 1u << (h * 2);
        wg_wait<1>(); keep(s1);
        exp_pv<0, 2>(s1, p1, o, VB(vY + onesP, 2), true);
        bar_sync(5 + wg * 4 + h * 2, 160);
        QK(s0, qy, kY + 512);
        exp_pv<2, 4>(s1, p1, o, VB(vY + onesP, 2), true); wg_commit();
        wg_wait<1>(); keep(s0); keep(p0);
        QK2(qy, kY);
        exp_pv<0, 4>(s0, p0, o, VB(vY + onesP, 1), true); wg_commit();
        wg_wait<1>(); keep(s1); keep(sx); keep(p1);
        bar_sync(6 + wg * 4, h ? 128 : 160);
        QK(s0, h ? qy : qX + 1024, kXB + 512);
        exp_pv2(s1, sx, p1, px, o, vY + onesP, VB(vY + ones, 4), msk, tdiag); wg_commit();
        wg_wait<0>(); keep(o); keep(s0); keep(p0); keep(p1); keep(px);
        ok = attn_pack(o, ob); attn_store(ob, ok, ost + (h * 4 + tY) * 4096, sb, BAR(B_ORDY + wg * 4 + h * 2 + 1)); redo |= ok ? 0u : 2u << (h * 2);
        #pragma unroll
        for (int e = 0; e < 20; e++) o[e] = op[e];
      }
      #undef QK
      #undef QK2
      #undef VB
      if (redo) {
        #pragma unroll 1
        for (int u = 0; u < 4; u++) if ((redo >> u) & 1) {
          const int h = u >> 1, t = (u & 1) ? tY : tX;
          attn_exact(sb + QO + (h * 4 + t) * 4096, sb + (h ? KVB : KVA), t, bi > 0, BAR(B_ORDY + wg * 4 + u));
        }
      }
    }
    PROFW(threadIdx.x == 0, L * 8 + 4);
    {
      IDS;
      const int t256 = wg * 128 + tid;
      float acc[64];
      const int tt = wg ^ rh;
      const int grow = bi * 256 + rh * 128 + tt * 64 + w * 16 + (lane >> 2);
      float al0 = 1.f, be0 = 0.f, al1 = 1.f, be1 = 0.f;
      const int idx0 = (int)uni(lds32(sb + INFO));
      const uint32_t tag = lds32(sb + INFO + 8) + L;
      uint4* const sp = &P.g->statP[bc][grow + (lane & 1) * 8];
      uint4* const yp = &P.g->yP[t256 >> 1][min(fid, 111)][t256 & 1];
      if (L) {
        float r0 = rsqrtf(fa.y + LN_EPS), r1 = rsqrtf(fb.y + LN_EPS);
        if (grow != idx0) { al0 = 1.f + r0; be0 = -fa.x * r0; }
        if (grow + 8 != idx0) { al1 = 1.f + r1; be1 = -fb.x * r1; }
      }
      const int srow = tt * 64 + w * 16 + (lane & 15);
      const uint32_t ra = sb + srow * 128 + (((lane >> 4) ^ (srow & 7)) << 4);
      mbar_wait(BAR(B_FULLW + 5), L);
      if ((idx0 >> 4) == bi * 16 + rh * 8 + tt * 4 + w) {
        int r = idx0 & 127;
        if (lane < 16) sts128(sb + 32768 + (lane >> 3) * 16384 + r * 128 + (((lane & 7) ^ (r & 7)) << 4), lds128(sb + X2SEG + lane * 16));
        fence_async_smem();
        __syncwarp();
      }
      #pragma unroll
      for (int jj = 0; jj < 8; jj++) {
        uint32_t r[4]; ldsm_x4((ra + 32768 + (jj >> 2) * 16384) ^ ((jj & 3) << 5), r[0], r[1], r[2], r[3]);
        #pragma unroll
        for (int e = 0; e < 4; e++) {
          acc[8 * jj + 2 * e] = fmaf(bf_lo(r[e]), (e & 1) ? al1 : al0, (e & 1) ? be1 : be0);
          acc[8 * jj + 2 * e + 1] = fmaf(bf_hi(r[e]), (e & 1) ? al1 : al0, (e & 1) ? be1 : be0);
        }
      }
      keep(acc);
      bar_sync(12 + wg, 128);
      if (!(lane & 2)) st_ll(sp, 0u, 0u, 0u, 0u);
      uint2 wd[4];
      #pragma unroll
      for (int e = 0; e < 4; e++) { wd[e] = make_uint2(0u, 0u); if (L) wd[e] = ldg_stream((const uint2*)(WDSRC) + t256 + (28 + e) * 256); }
      PROFW(t256 == 0, L * 8 + 5);
      #pragma unroll 1
      for (int n = 0, q = 0, pq = 5; n < 16; n++) {
        mbar_wait(BAR(B_FULLW + q), w_par(n, q, L));
        PROFD(t256 == 0 && !L && (n == 4 || n == 7 || n == 8 || n == 12), (n == 7 ? 63 : 41 + (n >> 2)));
        wo_block(acc, sb16, q, tt);
        wg_wait<1>(); if (tid == 0) mbar_arrive(BAR(B_EMPTYW + pq));
        pq = q; q = w_next(n, q);
      }
      mbar_wait(BAR(B_EMPTYW + 5), L);
      wg_wait<0>(); keep(acc);
      if (tid == 0) mbar_arrive(BAR(B_EMPTYW + 4));
      PROFW(t256 == 0, L * 8 + 6);
      const uint32_t xa = ra + rh * 16384;
      #pragma unroll
      for (int jj = 0; jj < 8; jj++) {
        const float* a = acc + 8 * jj;
        stsm_x4((xa + (jj >> 2) * 32768) ^ ((jj & 3) << 5), pack_bf16(a[0], a[1]), pack_bf16(a[2], a[3]), pack_bf16(a[4], a[5]), pack_bf16(a[6], a[7]));
        if (jj == 7) fence_async_smem();
        if ((jj & 3) == 3) warp_signal(BAR(B_XRDY + wg * 2 + (jj >> 2)));
      }
      {
        float s1a = 0.f, s2a = 0.f, da = 0.f, s1b = 0.f, s2b = 0.f, db = 0.f;
        #pragma unroll
        for (int j = 0; j < 16; j++) {
          const float* a = acc + 4 * j; float2 wv = lds64f(sb + WR + j * 32 + (lane & 3) * 8);
          s1a += a[0] + a[1]; s1b += a[2] + a[3];
          s2a = fmaf(a[0], a[0], s2a); s2b = fmaf(a[2], a[2], s2b); s2a = fmaf(a[1], a[1], s2a); s2b = fmaf(a[3], a[3], s2b);
          da = fmaf(a[0], wv.x, da); db = fmaf(a[2], wv.x, db); da = fmaf(a[1], wv.y, da); db = fmaf(a[3], wv.y, db);
        }
        bool odd = lane & 1;
        float u1 = (odd ? s1b : s1a) + __shfl_xor_sync(0xffffffffu, odd ? s1a : s1b, 1);
        float u2 = (odd ? s2b : s2a) + __shfl_xor_sync(0xffffffffu, odd ? s2a : s2b, 1);
        float u3 = (odd ? db : da) + __shfl_xor_sync(0xffffffffu, odd ? da : db, 1);
        u1 += __shfl_xor_sync(0xffffffffu, u1, 2); u2 += __shfl_xor_sync(0xffffffffu, u2, 2); u3 += __shfl_xor_sync(0xffffffffu, u3, 2);
        if (!(lane & 2)) st_ll(sp, __float_as_uint(u1), __float_as_uint(u2), __float_as_uint(u3), tag);
      }
      PROFW(t256 == 0, L * 8 + 7);
      if (L) {
        mbar_wait(BAR(B_PAR), 0);
        { float2 pa = lds64f(sb + PAR + (grow & 127) * 8), pb = lds64f(sb + PAR + (grow & 127) * 8 + 64); al0 = pa.x; be0 = pa.y; al1 = pb.x; be1 = pb.y; }
        uint32_t rs[32];
        #pragma unroll
        for (int j = 0; j < 16; j++) {
          rs[2 * j] = pack_bf16(fmaf(acc[4 * j], al0, be0), fmaf(acc[4 * j + 1], al0, be0));
          rs[2 * j + 1] = pack_bf16(fmaf(acc[4 * j + 2], al1, be1), fmaf(acc[4 * j + 3], al1, be1));
        }
        #pragma unroll
        for (int jj = 0; jj < 8; jj++) stsm_x4((xa + (jj >> 2) * 32768) ^ ((jj & 3) << 5), rs[4 * jj], rs[4 * jj + 1], rs[4 * jj + 2], rs[4 * jj + 3]);
        PROFW(t256 == 0, 16);
        if (fid >= 112) bar_arrive(3, 384);
        else {
          float d[4] = {0.f, 0.f, 0.f, 0.f};
          mbar_wait(BAR(B_FULLW + wg * 3), 0); mbar_wait(BAR(B_FULLW + wg * 3 + 1), 0);
          bar_sync(3, 384);
          PROFW(t256 == 0, 29);
          #pragma unroll 1
          for (int g = 0; g < 4; g++) {
            const uint32_t ad = (sb16 + (wg ? 6144 : 10240) + (g >> 1) * 2048 + (g & 1) * 512) | (1024u << 16), bd = (sb16 + (HV >> 4) + wg * 64 + g * 16) | 0x10000u;
            wg_fence();
            #pragma unroll
            for (int ks = 0; ks < 8; ks++) wgmma_ss_n8<0, 1>(d, mkd<HI64>(ad + ks * 64), mkd<8>(bd + ks * 2), 1);
            wg_commit();
          }
          mbar_wait(BAR(B_FULLW + 2), 0);
          wg_wait<0>(); keep(d);
          if (!(lane & 3)) { sts32f(sb + PAR + 1024 + wg * 256 + w * 64 + lane, d[0]); sts32f(sb + PAR + 1056 + wg * 256 + w * 64 + lane, d[2]); }
          bar_sync(1, 256);
          const uint32_t ga = sb + PAR + 1024 + lane * 4, aa = sb + HV + (t256 >> 5) * 128;
          sts32f(aa + lane * 4, swiglu(lds32f(ga) + lds32f(ga + 256), lds32f(ga + 128) + lds32f(ga + 384)));
          __syncwarp();
          PROFW(t256 == 0, 26);
          float y0 = 0.f, y1 = 0.f, y2 = 0.f, y3 = 0.f;
          uint32_t tbl = rh ? 0x001459a8u : 0x023679a8u;
          uint4 a4 = lds128(aa + 112);
          #pragma unroll 2
          for (int n = 0; n < 8; n++, tbl >>= 4) {
            const uint32_t src = sb + t256 * 8 + (tbl & 15) * 8192;
            const uint4 an = lds128(aa + ((0x00123564u >> (4 * n)) & 15) * 16);
            #pragma unroll
            for (int e = 0; e < 4; e++) {
              const float av = __uint_as_float(e == 0 ? a4.x : (e == 1 ? a4.y : (e == 2 ? a4.z : a4.w)));
              y0 = fmaf(bf_lo(wd[e].x), av, y0); y1 = fmaf(bf_hi(wd[e].x), av, y1); y2 = fmaf(bf_lo(wd[e].y), av, y2); y3 = fmaf(bf_hi(wd[e].y), av, y3);
              const float2 v = lds64f(src + e * 2048); wd[e] = make_uint2(__float_as_uint(v.x), __float_as_uint(v.y));
            }
            a4 = an;
          }
          st_ll(yp, __float_as_uint(y0), __float_as_uint(y1), __float_as_uint(y2), (__float_as_uint(y3) & ~255u) | (lds32(sb + INFO + 12) + 1));
          PROFW(t256 == 0, 27);
        }
        return;
      }
      mbar_wait(BAR(B_XRDY + wg * 2 + 1), 0);
    }
  }
  #undef IDS
  #undef LAYER
}

DEVI void loader(const Params& P, uint32_t sb) {
  const int lane = threadIdx.x & 31;
  const int bid = uni(BID), bi = bid >> 4, bp = bid & 15, rh = bp & 1, bc = bp >> 1;
  uint32_t phq = 0, tag = 0;
  #pragma unroll 1
  for (int L = 0; L < 2; L++) {
    int s = 0;
    uint32_t rdy = 0;
    #pragma unroll 1
    for (int n = L ? 0 : 3; n < 16; n++) {
      int kb = L ? kb_order(bc, n) : n;
      mbar_wait(BAR(B_EMPTYQ + s), (phq >> s) & 1);
      phq ^= 1u << s;
      if (L && n == 1) { mbar_wait(BAR(B_XRDY + 1), 0); mbar_wait(BAR(B_XRDY + 3), 0); }
      if (lane == 0) {
        mbar_expect_tx(BAR(B_FULLQ + s), L && n < 2 ? 40960 : 57344);
        tma_3d_h(sb + qb_off(s), &P.mWq, bp * 64, kb * 64, 0, BAR(B_FULLQ + s), L && n >= QEF_N ? POL_FIRST : POL_NORMAL);
        if (!L) tma_2d(sb + qa_off(s), &P.mX, kb * 64, bi * 256, BAR(B_FULLQ + s));
      }
      if (L && n >= 2) {
        if (((rdy >> (2 * kb)) & 3) != 3) {
          do { rdy = __ballot_sync(0xffffffffu, ld_rlx(&P.g->flagX[bi][lane]) == tag); } while (((rdy >> (2 * kb)) & 3) != 3);
          fence_async_glob();
        }
        if (n == 3 || n == 4) mbar_wait(BAR(B_XFREE + n - 3), 0);
        if (lane == 0) bulk_g2s_h(sb + qa_off(s), P.g->x[bi][kb], 32768, BAR(B_FULLQ + s), POL_X);
      }
      PROFY(L && lane == 0 && (n == 2 || n == 3 || n == 9), n == 9 ? 60 : 56 + n);
      if (L && n == 2) { mbar_wait(BAR(B_FULLQ), 0); mbar_wait(BAR(B_FULLQ + 1), 1); if (lane < 2) mbar_arrive_peer(BAR(B_XFREE + lane)); }
      s = (s == 2) ? 0 : s + 1;
    }
    for (int q = 0; q < 3; q++) mbar_wait(BAR(B_EMPTYQ + q), (phq >> q) & 1);
    tag = lds32(sb + INFO + 8) + L;
    #pragma unroll 1
    for (int q = 0; q < 4; q++) {
            if (bi) {
        const unsigned* f = &P.g->flagKV[bid - 16][q];
        while (ld_rlx(f) != tag);
        fence_async_glob();
      }
      if (lane == 0) {
        mbar_expect_tx(BAR(B_KVFULL + q), 16384);
        bulk_g2s_h(sb + ((q >> 1) ? KVB : KVA) + ((q & 1) ? 0 : 16384), bi ? P.g->kv[bid - 16][q] : P.g->zero, 16384, BAR(B_KVFULL + q));
      }
      PROFY(!L && lane == 0 && bi && q != 2, 34 + (q + 1) / 2);
    }
    mbar_wait(BAR(B_ORDY), L);
    {
      const uint4* src = P.g->o[bi][0][0][rh];
      rdy = 0;
      #pragma unroll 1
      for (int n = 0, q = 0; n < 16; q = w_next(n, q), n++) {
        const int j = wo_order(bc, n);
        if (((rdy >> (2 * j)) & 3) != 3) {
          do { rdy = __ballot_sync(0xffffffffu, ld_rlx(&P.g->flagO[bi][lane]) == tag); } while (((rdy >> (2 * j)) & 3) != 3);
          fence_async_glob();
        }
        if (n >= 2) mbar_wait(n < 5 ? BAR(B_HAFREE + (n > 2)) : BAR(B_EMPTYW + q), n < 5 ? L : w_par(n, q, L) ^ 1);
        if (n == THR_N) mbar_wait(BAR(B_OFREE), L);
        if (lane == 0) { mbar_expect_tx(BAR(B_FULLW + q), 16384); bulk_g2s_h(sb + w_off(q), src + j * 2048, 16384, BAR(B_FULLW + q)); }
      }
    }
    mbar_wait(BAR(B_OFREE), L);
  }
}

DEVI void ffn_prefetch(const Params& P, int q) {
  bulk_prefetch(q < 16 ? ((q & 1) ? P.wu : P.wg) + ((q >> 1) * 128 + blockIdx.x) * 3584 : P.wd + (min(FID, 111) * 8 + q - 16) * 4096, q < 16 ? 7168 : 8192);
}
DEVI void storer(const Params& P, uint32_t sb, int wg) {
  const int bid = uni(BID), bi = bid >> 4, rh = bid & 1, bc = (bid & 15) >> 1;
  const bool one = (threadIdx.x & 31) == 0;
  char* const g = (char*)P.g;
  const uint32_t tag0 = uni(((ld_rlx(&P.g->epoch) % 16383u) + 1u) << 2);
  #pragma unroll 1
  for (int L = 0; L < 2; L++) {
    const uint32_t tag = tag0 + L;
    if (wg) {
      #pragma unroll 1
      for (int r = threadIdx.x & 31; r < 256; r += 32) {
        uint4 v;
        do v = ld_ll(&P.g->statF[bi * 256 + r]); while (!__all_sync(0xffffffffu, v.w == tag));
        float var = __uint_as_float(v.y), c = rsqrtf(var + LN_EPS);
        if (L) { c += 1.f; c *= rsqrtf(fmaf(var * c, c, LN_EPS)); }
        const float mh = bf_round(__uint_as_float(v.x));
        sts64f(sb + PAR + r * 8, c, __uint_as_float(pack_bf16(mh, __uint_as_float(v.x) - mh)));
      }
      if (!L) mbar_wait(BAR(B_PAR), 0);
      warp_signal(BAR(B_ROW));
    }
    if (wg) { mbar_wait(BAR(B_KVRDY), L); mbar_wait(BAR(B_KVRDY + 2), L); const uint32_t t0 = clk(); while (clk() - t0 < KV_D) __nanosleep(40); }
    #pragma unroll 1
    for (int u = 0; u < 2 + 4 * wg; u++) {
      const int h = u < 2 ? u : u >> 2, hi = (u & 1) ^ 1;
      uint32_t src, dst, fl, b0, b1;
      if (u < 2) {
        src = (h ? KVB : KVA) + (3 - wg) * 16384; dst = offsetof(Scratch, kv) + (bid * 4 + h * 2 + wg) * 16384; fl = offsetof(Scratch, flagKV) + (bid * 32 + h * 2 + wg) * 4;
        b0 = BAR(B_KVRDY + ((u | wg) ? 1 : 0)); b1 = b0 + 16;
      } else {
        src = QO + (h * 2 + hi) * 8192; dst = offsetof(Scratch, o) + ((((bi * 2 + h) * 8 + bc) * 2 + hi) * 2 + rh) * 8192;
        fl = offsetof(Scratch, flagO) + (bi * 32 + h * 16 + (bid & 15)) * 4;
        b0 = BAR(B_ORDY + u - 2); b1 = b0 + 32;
      }
      mbar_wait(b0, L); mbar_wait(b1, L);
      fence_async_smem();
      PROFY(one && !L && u == 3 * wg, u ? 46 : 8);
      if (one && (u >= 2 || bi < 7)) bulk_s2g(g + dst, sb + src, u < 2 ? 16384 : 8192);
      if (one && u == 5) mbar_arrive(BAR(B_HAFREE + 1));
      if (u == 2 || u == 4) continue;
      bulk_wait<0>();
      PROFY(one && !L && u == 3 * wg, u ? 61 : 62);
      fence_rel();
      if (one) { st_rlx((unsigned*)(g + fl), tag); if (!wg || u > 2) mbar_arrive(BAR(B_HAFREE + h + (wg & h))); }
      PROFY(one && !L && (u > 2 || u == wg), u > 2 ? (u == 3 ? 38 : 54) : 32 + u);
    }
    if (L == 0) {
      char* dst = g + (offsetof(Scratch, x) + (bi * 16 + 2 * bc) * 32768 + rh * 16384);
      unsigned* f = (unsigned*)(g + (offsetof(Scratch, flagX) + (bi * 32 + bc * 4 + rh) * 4));
      const uint32_t a = sb + rh * 16384;
      if (wg == 0) {
        mbar_wait(BAR(B_XRDY), 0); mbar_wait(BAR(B_XRDY + 2), 0);
        fence_async_smem();
        PROFY(one, 41);
        if (one) bulk_s2g(dst, a, 16384);
        bulk_wait<0>();
        PROFY(one, 45);
        if (one) { mbar_arrive(BAR(B_XFREE)); mbar_arrive(BAR(B_PFREE)); }
        fence_rel();
        mbar_wait(BAR(B_XRDY + 1), 0); mbar_wait(BAR(B_XRDY + 3), 0);
        if (one) { st_rlx(f, tag); bulk_s2g(dst + 32768, a + 32768, 16384); }
        PROFY(one, 56);
        bulk_wait<0>();
        if (one) mbar_arrive(BAR(B_XFREE + 1));
        fence_rel();
        if (one) st_rlx(f + 2, tag);
        PROFY(one, 57);
      } else {
        mbar_wait(BAR(B_XRDY + 1), 0); mbar_wait(BAR(B_XRDY + 3), 0);
        mbar_wait(BAR(B_PFREE), 0);
        if (one) bulk_s2peer(a, 16384, BAR(B_FULLQ));
        { const uint32_t t0 = clk(); while (clk() - t0 < XD_D); }
        if (one) bulk_s2peer(a + 32768, 16384, BAR(B_FULLQ + 1));
      }
      if (wg == 0) {
        uint32_t t0 = clk() + PF1_D;
        #pragma unroll 1
        for (int q = PF1_S; q < PF1_E; q++) { while ((int)(clk() - t0) < 0) __nanosleep(50); if (one) ffn_prefetch(P, q); t0 += PF1_T; }
      }
    }
  }
}

DEVI void stg_issue(const Params& P, int c, uint32_t d, uint32_t du, uint32_t b) {
  mbar_expect_tx(b, 16384);
  if (c < 8) { tma_2d_h(d, &P.mWg, FID * 32, c * 128, b, POL_G); tma_2d_h(d + du, &P.mWu, FID * 32, c * 128, b, POL_U); }
  else if (c < 12) tma_3d_h(d, &P.mWd, 0, FID * 32 + (c - 8) * 8, 0, b, POL_D);
  else tma_2d_h(d, &P.mWp, (c - 12) * 1024 + (BID >> 2) * 32, (BID & 3) * 256, b, POL_EF);
}
DEVI void pace() { const uint32_t t0 = clk(); while (clk() - t0 < PACE_T); }
DEVI void stager(const Params& P, uint32_t sb) {
  {
    const int b = blockIdx.x;
    uint32_t t0 = clk();
    #pragma unroll 1
    for (int q = 0; q < PQ_N; q++) { bulk_prefetch(P.wqkv + (q * 128 + b) * 3072, 6144); while (clk() - t0 < PQ_T) __nanosleep(50); t0 += PQ_T; }
    bulk_prefetch(P.wo + b * 8192, 16384);
    #pragma unroll 1
    for (int q = 0; q < PF0_N; q++) {
      while (clk() - t0 < PF0_T) __nanosleep(50);
      t0 += PF0_T;
      ffn_prefetch(P, q);
    }
  }
  const int bid = BID, bi = bid >> 4, rh = bid & 1, bc = (bid & 15) >> 1;
  #pragma unroll 1
  for (int L = 0; L < 2; L++) {
    const int nch = L ? (FID < 112 ? 8 : 0) : 15;
    mbar_wait(BAR(B_PAR), L); mbar_wait(BAR(B_KVFULL + W0_BAR), L);
    #pragma unroll 1
    for (int n = 0, q = 0; n < 16; q = w_next(n, q), n++) {
      if (n >= 2) mbar_wait(n < 5 ? BAR(B_HAFREE + (n > 2)) : BAR(B_EMPTYW + q), n < 5 ? L : w_par(n, q, L) ^ 1);
      if (n == THR_N) mbar_wait(BAR(B_OFREE), L);
      mbar_expect_tx(BAR(B_FULLW + q), 16384);
      tma_5d(sb + w_off(q) + 16384, &P.mWo, 0, 0, n >> 3, 2 * (wo_order(bc, n) & 7), 2 * bc, BAR(B_FULLW + q), L ? POL_EF : POL_NORMAL);
      if (n == 2) {
        #pragma unroll 1
        for (int e = 0; e < 2; e++) {
          mbar_expect_tx(BAR(B_FULLW + 5), 16384);
          if (L) bulk_g2s_h(sb + 32768 + e * 16384, P.g->x[bi][2 * bc + e] + rh * 1024, 16384, BAR(B_FULLW + 5));
          else tma_2d_h(sb + 32768 + e * 16384, &P.mXh, bc * 128 + e * 64, bi * 256 + rh * 128, BAR(B_FULLW + 5), POL_EF);
        }
      }
    }
    mbar_wait(BAR(B_EMPTYW + 5), L);
    if (L && nch) {
      const bf16* src = WDSRC2;
      mbar_expect_tx(BAR(B_FULLW + 2), 32768); mbar_expect_tx(BAR(B_FULLW + 2), 24576);
      #pragma unroll 1
      for (int e = 0; e < 3; e++) { bulk_g2s_h(sb + e * 32768 + (e < 2 ? (rh ^ 1) * 16384 : 0), src + e * 8192, e < 2 ? 16384 : 24576, BAR(B_FULLW + 2)); pace(); }
    }
        if (L == 0) { mbar_arrive_peer(BAR(B_PFREE)); mbar_wait(BAR(B_EMPTYW), 0); mbar_wait(BAR(B_EMPTYW + 1), 0); }
    #pragma unroll 1
    for (int c = FID < 112 ? 0 : 12, slot = 0; c < nch; c++, slot = slot == 2 ? 0 : slot + 1) {
      const int q = (c >> 1) + (c >> 2);
      if (!L && (c == LATE_C || c == 12)) mbar_wait(BAR(LATE_B), LATE_P);
      mbar_wait(L ? BAR(B_EMPTYW + q) : BAR(B_STGE + slot), L | ((0x71c7 >> c) & 1));
      #define CC c
      stg_issue(P, CC, L ? sb + w_off(q) + (c & 1) * 8192 : sb + STG + slot * 16384, 8192 << L, L ? BAR(B_FULLW + q) : BAR(B_STG + slot));
      if (L) pace();
    }
  }
}
DEVI void sum8(uint4 v, float& s1, float& s2) {
  float e[8] = {bf_lo(v.x), bf_hi(v.x), bf_lo(v.y), bf_hi(v.y), bf_lo(v.z), bf_hi(v.z), bf_lo(v.w), bf_hi(v.w)};
  #pragma unroll
  for (int q = 0; q < 8; q++) { s1 += e[q]; s2 = fmaf(e[q], e[q], s2); }
}
DEVI uint4 norm8(uint4 x, float m, float rs) {
  #define HN(v) pack_bf16((bf_lo(v) - m) * rs, (bf_hi(v) - m) * rs)
  return make_uint4(HN(x.x), HN(x.y), HN(x.z), HN(x.w));
  #undef HN
}
DEVI void put_f32(uint4 b, uint32_t d, uint32_t d2) {
  sts128(d, make_uint4(b.x << 16, b.x & 0xffff0000u, b.y << 16, b.y & 0xffff0000u));
  sts128(d + d2, make_uint4(b.z << 16, b.z & 0xffff0000u, b.w << 16, b.w & 0xffff0000u));
}
DEVI void put_bf16(uint4 b, uint32_t d) {
  sts64f(d, __uint_as_float(b.x), __uint_as_float(b.y)); sts64f(d + 1024, __uint_as_float(b.z), __uint_as_float(b.w));
  fence_async_smem();
}
DEVI uint4 best4(uint32_t p) {
  uint4 a = lds128(p), b = lds128(p + 16), c = lds128(p + 32), d = lds128(p + 48);
  if (b.x > a.x) a = b;
  if (d.x > c.x) c = d;
  return c.x > a.x ? c : a;
}
#define FL(x) __uint_as_float(x)
#define UI(x) __float_as_uint(x)
DEVI void aux(const Params& P, uint32_t sb) {
  int tid = fresh_tid();
  #define lane (tid & 31)
  #define wq (tid >> 5)
  uint32_t ids = P.map[blockIdx.x], tag;
  #define bid ((int)(ids & 255))
  #define fid ((int)(ids >> 8))
  #define bi (bid >> 4)
  #define bp (bid & 15)
  #define bc (bp >> 1)
  #define FRESH() do { tid = fresh_tid(); uint4 z_ = ldsv128(sb + INFO2 + 16); ids = z_.y; tag = z_.z + L; idx = z_.w; } while (0)
  {
    const uint32_t epoch = ld_rlx(&P.g->epoch);
    if (tid == 0) {
      mbar_expect_tx(BAR(B_STG), 49152);
      tma_3d(sb + STG, &P.mWq, bp * 64, bi * 128, 0, BAR(B_STG));
      tma_3d(sb + STG + 24576, &P.mWq, bp * 64, bi * 128 + 64, 0, BAR(B_STG));
    }
    __syncwarp();
    sts64f(sb + ONES + tid * 8, FL(0x3F803F80u), FL(0x3F803F80u));
    float s1 = 0.f, s2 = 0.f;
    { uint4 v = __ldg((const uint4*)P.wr + tid);
      if ((tid >> 4) == bc) put_f32(v, sb + WR + (tid & 15) * 32, 16);
      sum8(v, s1, s2);
      #pragma unroll 1
      for (int o = 16; o; o >>= 1) s1 += __shfl_xor_sync(0xffffffffu, s1, o);
      sts32f(sb + INFO2 + wq * 4, s1); }
    const uint4* src = (const uint4*)(P.x0 + (size_t)bid * 16384) + (tid >> 3) * 128 + (tid & 7);
    s1 = 0.f; s2 = 0.f;
    #pragma unroll 1
    for (int it = 0; it < 16; it += 4) {
      uint4 v0 = __ldg(src + it * 8), v1 = __ldg(src + it * 8 + 8), v2 = __ldg(src + it * 8 + 16), v3 = __ldg(src + it * 8 + 24);
      #pragma unroll 1
      for (int q = 0; q < 4; q++) { sum8(v0, s1, s2); v0 = v1; v1 = v2; v2 = v3; }
    }
    #pragma unroll 1
    for (int o = 1; o < 8; o <<= 1) { s1 += __shfl_xor_sync(0xffffffffu, s1, o); s2 += __shfl_xor_sync(0xffffffffu, s2, o); }
    tag = ((epoch % 16383u) + 1u) << 2;
    if (tid == 0) { sts128(sb + INFO, make_uint4(0x40000000u, 0u, tag, ((epoch % 127u) + 1u) << 1)); sts128(sb + INFO2 + 16, make_uint4(epoch, ids, tag, 0x40000000u)); }
    float m = s1 * (1.f / 1024.f);
    if ((tid & 7) == 0) st_ll(&P.g->statF[bid * 16 + (tid >> 3)], UI(m), UI(fmaxf(fmaf(-m, m, s2 * (1.f / 1024.f)), 0.f)), 0u, tag);
    bar_sync(2, 128);
    mbar_wait_b(BAR(B_STG), 0);
    if (tid < 96) {
      s1 = 0.f; s2 = 0.f;
      #pragma unroll 1
      for (int r = 0; r < 16; r++) {
        const uint32_t a = sb + STG + (r >> 3) * 24576 + wq * 8192 + (r & 7) * 128 + ((lane * 4) ^ ((r & 7) << 4));
        #pragma unroll
        for (int e = 0; e < 8; e++) { uint32_t v = lds32(a + e * 1024); s1 += bf_lo(v); s2 += bf_hi(v); }
      }
      st_ll(&P.g->csP[bp][bi][tid], UI(s1), UI(s2), 0u, tag);
      s1 = 0.f; s2 = 0.f;
      #pragma unroll 1
      for (int q = 0; q < 8; q += 2) {
        uint4 a, b; poll_ll2(&P.g->csP[bp][q][tid], &P.g->csP[bp][q + 1][tid], 0xffffffffu, tag, a, b);
        s1 += FL(a.x) + FL(b.x); s2 += FL(a.y) + FL(b.y);
      }
      const uint32_t hi = pack_bf16(-s1, -s2);
      sts32(sb + CS + (tid >> 2) * 32 + (tid & 3) * 4, hi);
      sts32(sb + CS + (tid >> 2) * 32 + (tid & 3) * 4 + 16, pack_bf16(-s1 - bf_lo(hi), -s2 - bf_hi(hi)));
    }
    fence_async_smem();
  }
  int idx;
  #pragma unroll 1
  for (int L = 0; L < 2; L++) {
    FRESH();
    {
      if ((unsigned)(bi - (idx >> 8)) < 2u) {
        const uint4* src = &P.g->patch[bp * 8 + (tid >> 6) * 4][tid & 63];
        uint4 v0, v1, v2, v3; int it = 0;
        do { v0 = ld_ll(src); v1 = ld_ll(src + 64); v2 = ld_ll(src + 128); v3 = ld_ll(src + 192); if (++it > SPIN_MAX) __trap(); }
        while (!__all_sync(0xffffffffu, v0.w == tag && v1.w == tag && v2.w == tag && v3.w == tag));
        float q = (FL(v0.x) + FL(v1.x)) + (FL(v2.x) + FL(v3.x)), k = (FL(v0.y) + FL(v1.y)) + (FL(v2.y) + FL(v3.y)), v = (FL(v0.z) + FL(v1.z)) + (FL(v2.z) + FL(v3.z));
        q += __shfl_xor_sync(0xffffffffu, q, 1); k += __shfl_xor_sync(0xffffffffu, k, 1); v += __shfl_xor_sync(0xffffffffu, v, 1);
        bar_sync(2, 128);
        const uint32_t d = sb + PATCH + (tid & ~1), kv = pack_bf16(k, v);
        sts16(d, pack_bf16(q * QSCALE, 0.f)); sts16(d + 128, kv); sts16(d + 256, kv >> 16);
      }
      sts32(sb + INFO, idx);
      bar_sync(2, 128);
    }
    const uint4 fix = lds128(sb + PATCH + 128 + (lane & 4) * 32 + (wq >> 1) * 64 + (lane & 3) * 16);
    warp_signal(BAR(B_PAR));
    PROFX(tid == 0, L ? 23 : 17);
    mbar_wait_b(BAR(B_KVFULL + wq), L);
    if ((idx >> 7) == bi * 2 - 1 - (wq & 1)) {
      if (lane < 8) sts128(sb + ((wq >> 1) ? KVB : KVA) + ((idx >> 6) & 3) * 8192 + (lane >> 2) * 4096 + (idx & 63) * 64 + (((lane ^ (idx >> 1)) & 3) << 4), fix);
      fence_async_smem();
    }
    bar_arrive(4 + wq, 160); bar_arrive(8 + wq, 160);
    FRESH();
    mbar_wait_b(BAR(B_OFREE), L);
    #define blk (bi * 2 + (bid & 1))
    if (tid < 33) st_ll(tid < 32 ? &P.g->row[blk][bc * 32 + tid] : &P.g->best[bc][blk], 0u, 0u, 0u, 0u);
    mbar_wait_b(BAR(B_XRDY + 1), L); mbar_wait_b(BAR(B_XRDY + 3), L);
    PROFX(tid == 0, 37 + L * 16);
    FRESH();
    {
      float s1 = 0.f, s2 = 0.f, d = 0.f;
      #pragma unroll 1
      for (int q = 0; q < 8; q += 4) {
        const uint4* src = &P.g->statP[q][blk * 128 + tid];
        uint4 v0, v1, v2, v3; int it = 0;
        do { v0 = ld_ll(src); v1 = ld_ll(src + 2048); v2 = ld_ll(src + 4096); v3 = ld_ll(src + 6144); if (++it > SPIN_MAX) __trap(); }
        while (!__all_sync(0xffffffffu, v0.w == tag && v1.w == tag && v2.w == tag && v3.w == tag));
        s1 += (FL(v0.x) + FL(v1.x)) + (FL(v2.x) + FL(v3.x)); s2 += (FL(v0.y) + FL(v1.y)) + (FL(v2.y) + FL(v3.y)); d += (FL(v0.z) + FL(v1.z)) + (FL(v2.z) + FL(v3.z));
      }
      PROFX(tid == 0, 39 + L * 16);
      uint4 a = lds128(sb + INFO2), b, c;
      float m = s1 * (1.f / 1024.f), var = fmaxf(fmaf(-m, m, s2 * (1.f / 1024.f)), 0.f), rs = rsqrtf(var + LN_EPS);
      uint32_t key = UI(fmaf(-m, (FL(a.x) + FL(a.y)) + (FL(a.z) + FL(a.w)), d) * rs);
      key ^= (uint32_t)((int)key >> 31) | 0x80000000u;
      uint32_t win = __ballot_sync(0xffffffffu, key == __reduce_max_sync(0xffffffffu, key));
      if (lane == __ffs(win) - 1) sts128(sb + RED + wq * 16, make_uint4(key, UI(m), UI(rs), (tag << 11) | (uint32_t)(blk * 128 + tid)));
      if (L) sts64f(sb + PAR + tid * 8, 1.f + rs, -m * rs);
      else if ((tid >> 4) == bc) st_ll(&P.g->statF[blk * 128 + tid], UI(m), UI(var), 0u, tag + 1);
      bar_sync(2, 128);
      if (wq == 0) {
        a = best4(sb + RED);
        float2 v = lds64f(sb + (lane >> 4) * 32768 + (a.w & 255) * 128 + (((lane & 15) * 8) ^ ((a.w & 7) << 4)));
        st_ll(&P.g->row[blk][bc * 32 + lane], UI(v.x), UI(v.y), 0u, tag);
        if (lane == 0) st_ll(&P.g->best[bc][blk], a.x, a.y, a.z, a.w);
        __syncwarp();
        if (lane < 2 + 2 * L) mbar_arrive(L ? BAR(B_PAR) : BAR(B_XFREE + lane));
      }
      PROFX(tid == 0, 18 + L * 6);
      FRESH();
      a = poll_ll(&P.g->best[bc][lane & 15], 0xfffff800u, tag << 11);
      win = __ffs(__ballot_sync(0xffffffffu, a.x == __reduce_max_sync(0xffffffffu, a.x))) - 1;
      idx = __shfl_sync(0xffffffffu, a.w, win) & 2047;
      PROFX(tid == 0, 19 + L * 6);
      poll_ll2(&P.g->row[win][tid], &P.g->row[win][tid + 128], 0xffffffffu, tag, c, b);
      c.z = b.x; c.w = b.y;
      a.x = __shfl_sync(0xffffffffu, a.x, win); a.y = __shfl_sync(0xffffffffu, a.y, win); a.z = __shfl_sync(0xffffffffu, a.z, win);
      sts32(sb + INFO2 + 28, idx);
      PROFX(tid == 0, 61 + L);
      b = norm8(c, FL(a.y), FL(a.z));
      if (L) put_bf16(b, sb + HV + tid * 8); else put_f32(b, sb + HV + tid * 16, 2048);
      if ((tid >> 1) == (bid & 63)) {
        sts128(sb + RED + 64 + (tid & 1) * 16, bid < 64 ? make_uint4(c.x, c.y, b.x, b.y) : make_uint4(c.z, c.w, b.z, b.w));
        sts32(sb + RED + 96, a.x);
      }
      bar_sync(2 + L, 128 + L * 256);
      if (L) {
        const int r0 = blk * 128 + (tid >> 4);
        uint32_t src = sb + ((tid >> 3) & 1) * 32768 + (r0 & 255) * 128 + (((tid ^ r0) & 7) << 4);
        uint4* dst = (uint4*)(P.out + (size_t)r0 * 1024 + bc * 128) + (tid & 15);
        #pragma unroll 4
        for (int it = 0; it < 16; it++) { uint4 v = lds128(src + it * 1024); if (idx - r0 != it * 8) dst[it * 1024] = v; }
      }
    }
    #pragma unroll 1
    for (int st = L; st < 2; st++) {
      FRESH();
      float a[8] = {0.f, 0.f, 0.f, 0.f, 0.f, 0.f, 0.f, 0.f};
      if (L == 0 && fid < 112) {
        uint32_t ha = st ? sb + RED + 768 : sb + HV + ((wq & 1) * 64 + (lane >> 2)) * 4;
        uint32_t ph = st ? 0x1cu : 0x171u, bar = st ? BAR(B_STG + 2) : BAR(B_STG);
        uint32_t wa = sb + STG + wq * 4096 + (st ? 32768 + lane * 16 : (lane ^ (lane >> 3)) * 16);
        const uint32_t hx = st ? 256 : 512;
        const bool lead = lane == 0;
        uint4 vc = make_uint4(0u, 0u, 0u, 0u); float hc = 0.f;
        #pragma unroll 1
        do {
          mbar_wait(bar, ph & 1);
          PROFX(lead && threadIdx.x == 256 && st == 0 && (ph > 255 || ph < 4), 40 - 23 + __clz(ph));
          #pragma unroll
          for (int n = 0; n < 8; n++) { const uint4 v = lds128(wa + n * 512); const float h = lds32f(ha + n * 32); fma8(a, vc, hc); vc = v; hc = h; }
          __syncwarp();
          if (lead) mbar_arrive(bar - 8 * (B_STG - B_STGE));
          const bool wrap = bar == BAR(B_STG + 2);
          bar += wrap ? -16 : 8; wa += wrap ? -32768 : 16384; ha += hx;
          ph >>= 1;
        } while (ph != 1);
        fma8(a, vc, hc);
      }
      FRESH();
      if (st == 1) {
        const uint32_t t8 = lds32(sb + INFO + 12) + L;
        if (L == 0 && fid < 112) {
          const bool odd = lane & 1;
          #pragma unroll
          for (int e = 0; e < 4; e++) { float z = __shfl_xor_sync(0xffffffffu, odd ? a[e] : a[4 + e], 1); if (odd) a[e] = z; else a[4 + e] = z; }
          uint4* dst = &P.g->yP[tid & ~1][fid][tid & 1];
          st_ll(dst, UI(a[0]), UI(a[1]), UI(a[2]), (UI(a[3]) & ~255u) | t8);
          st_ll(dst + 224, UI(a[4]), UI(a[5]), UI(a[6]), (UI(a[7]) & ~255u) | t8);
          PROFX(tid == 0, 21);
        }
        if (tid == 0) { uint32_t k = lds32(sb + RED + 96); sts32f(sb + RED + 100, bf_round(__fdividef(1.f, 1.f + __expf(-bf_round(FL(k ^ (~(uint32_t)((int)k >> 31) | 0x80000000u))))))); }
        uint4 v0, v1;
        poll_ll2(&P.g->yP[bid][0][min(tid, 111)], &P.g->yP[bid][0][min(tid, 111) + 112], 255u, t8, v0, v1);
        const float lo = (tid < 112 && !(tid & 1)) ? 1.f : 0.f, hi = (tid < 112 && (tid & 1)) ? 1.f : 0.f;
        const float y0 = FL(v0.x) + FL(v1.x), y1 = FL(v0.y) + FL(v1.y), y2 = FL(v0.z) + FL(v1.z), y3 = FL((v0.w & ~255u) | 128u) + FL((v1.w & ~255u) | 128u);
        a[0] = y0 * lo; a[1] = y1 * lo; a[2] = y2 * lo; a[3] = y3 * lo; a[4] = y0 * hi; a[5] = y1 * hi; a[6] = y2 * hi; a[7] = y3 * hi;
      }
      sts32f(sb + RED + 256 + wq * 128 + ((lane & 3) * 8 + (lane >> 2)) * 4, fold8(a));
      bar_sync(2, 128);
      const uint32_t d = sb + RED + 256 + lane * 4;
      float z0 = lds32f(d) + lds32f(d + 128), z1 = lds32f(d + 256) + lds32f(d + 384);
      if (st == 0) {
        sts32f(sb + RED + 768 + lane * 32 + wq * 4, swiglu(z0, z1));
        bar_sync(2, 128);
        if (fid < 112) { st_ll(&P.g->yP[tid & ~1][fid][tid & 1], 0u, 0u, 0u, 0u); st_ll(&P.g->yP[tid | 1][fid][tid & 1], 0u, 0u, 0u, 0u); }
        else { const uint32_t t0 = clk(); while (clk() - t0 < IDLE_T) __nanosleep(200); }
        if (tid < 80) st_ll(tid < 64 ? &P.g->patch[bid][tid] : &P.g->x2[(tid >> 1) & 7][2 * bid + (tid & 1)], 0u, 0u, 0u, 0u);
        PROFX(tid == 0, 20); continue; }
      z0 += z1;
      z0 += __shfl_xor_sync(0xffffffffu, z0, 8); z0 += __shfl_xor_sync(0xffffffffu, z0, 16);
      uint32_t xw = lds32(sb + RED + 64 + (lane & 4) * 4 + (lane & 2) * 2), hw = lds32(sb + RED + 72 + (lane & 4) * 4 + (lane & 2) * 2);
      z0 = bf_round(((lane & 1) ? bf_hi(hw) : bf_lo(hw)) + bf_round(bf_round(z0) * lds32f(sb + RED + 100))) + ((lane & 1) ? bf_hi(xw) : bf_lo(xw));
      uint32_t v = pack_bf16(z0, __shfl_down_sync(0xffffffffu, z0, 1)), v2 = __shfl_down_sync(0xffffffffu, v, 2);
      if (L) { if (tid == 0 || tid == 4) *(uint2*)(P.out + (size_t)idx * 1024 + bid * 8 + tid) = make_uint2(v, v2); PROFW(tid == 0, 28); }
      else if ((tid & 3) == 0 && tid < 64) st_ll(&P.g->x2[tid >> 3][2 * bid + ((tid >> 2) & 1)], v, v2, 0u, tag + 1);
    }
    if (L == 0) {
      PROFX(tid == 0, 22);
      FRESH();
      uint4 x, y; poll_ll2(&P.g->x2[bi][tid], &P.g->x2[bi][tid + 128], 0xffffffffu, tag + 1, x, y);
      x.z = y.x; x.w = y.y;
      if (wq == (bc & 3)) sts64f(sb + X2SEG + lane * 8, FL(bc < 4 ? x.x : x.z), FL(bc < 4 ? x.y : x.w));
      float s1 = 0.f, s2 = 0.f;
      sum8(x, s1, s2);
      #pragma unroll
      for (int o = 16; o; o >>= 1) { s1 += __shfl_xor_sync(0xffffffffu, s1, o); s2 += __shfl_xor_sync(0xffffffffu, s2, o); }
      sts64f(sb + RED + wq * 8, s1, s2);
      bar_sync(2, 128);
      y = lds128(sb + RED); uint4 y2 = lds128(sb + RED + 16);
      float m = ((FL(y.x) + FL(y.z)) + (FL(y2.x) + FL(y2.z))) * (1.f / 1024.f);
      put_bf16(norm8(x, m, rsqrtf(fmaxf(fmaf(-m, m, ((FL(y.y) + FL(y.w)) + (FL(y2.y) + FL(y2.w))) * (1.f / 1024.f)), 0.f) + LN_EPS)), sb + HV + tid * 8);
      mbar_wait(BAR(B_STG), 1); mbar_wait(BAR(B_STG + 1), 0); mbar_wait(BAR(B_STG + 2), 0);
      bar_sync(2, 128);
      PROFX(tid == 0, 30);
      float d0[4] = {0.f, 0.f, 0.f, 0.f}, d1[4] = {0.f, 0.f, 0.f, 0.f}, d2[4] = {0.f, 0.f, 0.f, 0.f};
      const uint32_t bd = (64 + (HV >> 4) + uni(bid & 3) * 32) | 0x10000u;
      #pragma unroll 1
      for (int ks = 0; ks < 8; ks++) {
        const uint32_t ad = (64 + (STG >> 4) + ks * 128) | (64u << 16);
        wg_fence();
        wgmma_ss_n8<0, 1>(d0, mkd<HI64>(ad), mkd<8>(bd + ks * 4), 1);
        wgmma_ss_n8<0, 1>(d1, mkd<HI64>(ad + 1024), mkd<8>(bd + ks * 4), 1);
        wgmma_ss_n8<0, 1>(d2, mkd<HI64>(ad + 2048), mkd<8>(bd + ks * 4), 1);
        wg_commit();
      }
      wg_wait<0>(); keep(d0); keep(d1); keep(d2);
      FRESH();
      if ((lane & 3) == (wq >> 1)) {
        uint4* dst = &P.g->patch[bid][(wq & 1) * 32 + (lane >> 2) * 2 + (wq >> 1)];
        st_ll(dst, UI(d0[0]), UI(d1[0]), UI(d2[0]), tag + 1); st_ll(dst + 16, UI(d0[2]), UI(d1[2]), UI(d2[2]), tag + 1);
      }
      PROFX(tid == 0, 31);
    }
  }
  if (bid == 0 && tid == 0) P.g->epoch = lds32(sb + INFO2 + 16) + 1;
  #undef blk
  #undef bid
  #undef fid
  #undef bi
  #undef bp
  #undef bc
  #undef FRESH
  #undef lane
  #undef wq
}

__global__ void __cluster_dims__(2, 1, 1) __launch_bounds__(512, 1) fused_kernel(const __grid_constant__ Params P) {
  extern __shared__ __align__(1024) uint8_t smem_raw[];
  const uint32_t sb = smem_u32(smem_raw);
  PROFT(threadIdx.x == 0, 0);
  if (threadIdx.x == 0) {
    for (int s = 0; s < 3; s++) mbar_init(BAR(B_FULLQ + s), 1);
    asm volatile("fence.mbarrier_init.release.cluster;" ::: "memory");
    #pragma unroll 1
    for (int s = 0; s < 3; s++) {
      mbar_expect_tx(BAR(B_FULLQ + s), 57344);
      tma_2d(sb + qa_off(s), &P.mX, s * 64, (BID >> 4) * 256, BAR(B_FULLQ + s));
      tma_3d(sb + qb_off(s), &P.mWq, (BID & 15) * 64, s * 64, 0, BAR(B_FULLQ + s));
    }
    if ((sb & 0x3FFFFu) != 1024) __trap();
  } else if (threadIdx.x == 480) {
    asm volatile("prefetch.tensormap [%0];" :: "l"(&P.mWq) : "memory");
  } else if (threadIdx.x >= 32 && !(threadIdx.x & 28) && (threadIdx.x >> 3) + (threadIdx.x & 3) <= B_COUNT + 1) {
    int b = (threadIdx.x >> 3) + (threadIdx.x & 3) - 1;
    if (b == B_COUNT) b = B_ROW;
    const uint32_t cnt = b < B_XFREE ? (b == B_OFREE ? 1 : 2) : (b < B_KVRDY ? 3 : (b < B_KVFULL || b == B_PAR ? 4 : (b == B_PFREE ? 2 : 1)));
    mbar_init(BAR(b), cnt);
    asm volatile("fence.mbarrier_init.release.cluster;" ::: "memory");
  }
  __syncthreads();
  asm volatile("barrier.cluster.arrive.relaxed.aligned;" ::: "memory");
  const int wg = __shfl_sync(0xffffffffu, threadIdx.x >> 7, 0);
  if (wg < 2) { reg_inc<224>(); consumer(P, sb, wg); }
  else if (wg == 2) { reg_dec<40>(); aux(P, sb); }
  else {
    reg_dec<24>();
    asm volatile("barrier.cluster.wait.aligned;" ::: "memory");
    const int w = __shfl_sync(0xffffffffu, (threadIdx.x >> 5) & 3, 0);
    if (w == 0) loader(P, sb);
    else if (w < 3) storer(P, sb, w - 1);
    else if ((threadIdx.x & 31) == 0) stager(P, sb);
  }
}

typedef CUresult (*EncFn)(CUtensorMap*, CUtensorMapDataType, cuuint32_t, void*, const cuuint64_t*, const cuuint64_t*, const cuuint32_t*, const cuuint32_t*,
                          CUtensorMapInterleave, CUtensorMapSwizzle, CUtensorMapL2promotion, CUtensorMapFloatOOBfill);
static void mk_map(EncFn enc, CUtensorMap* m, const void* ptr, int rank, const cuuint64_t* dims, const cuuint64_t* strides, const cuuint32_t* box,
                   CUtensorMapSwizzle sw, CUtensorMapL2promotion pr) {
  cuuint32_t es[5] = {1, 1, 1, 1, 1};
  enc(m, CU_TENSOR_MAP_DATA_TYPE_BFLOAT16, rank, (void*)ptr, dims, strides, box, es, CU_TENSOR_MAP_INTERLEAVE_NONE, sw, pr, CU_TENSOR_MAP_FLOAT_OOB_FILL_NONE);
}
extern "C" void kernel_launch(void* const* d_in, const int* in_sizes, int n_in, void* d_out, int out_size) {
  (void)in_sizes; (void)n_in; (void)out_size;
  void* fn = nullptr; cudaDriverEntryPointQueryResult q;
  cudaGetDriverEntryPoint("cuTensorMapEncodeTiled", &fn, cudaEnableDefault, &q);
  EncFn enc = (EncFn)fn;
  cudaFuncSetAttribute(fused_kernel, cudaFuncAttributeMaxDynamicSharedMemorySize, SMEM_BYTES);
  Params P;
  const CUtensorMapSwizzle S128 = CU_TENSOR_MAP_SWIZZLE_128B, S64 = CU_TENSOR_MAP_SWIZZLE_64B, S0 = CU_TENSOR_MAP_SWIZZLE_NONE;
  const CUtensorMapL2promotion L256 = CU_TENSOR_MAP_L2_PROMOTION_L2_256B, L128 = CU_TENSOR_MAP_L2_PROMOTION_L2_128B;
  { cuuint64_t d[2] = {1024, 2048}, s[1] = {2048}; cuuint32_t b[2] = {64, 256}, bh[2] = {64, 128};
    mk_map(enc, &P.mX, d_in[0], 2, d, s, b, S128, L256); mk_map(enc, &P.mXh, d_in[0], 2, d, s, bh, S128, L256); }
  { cuuint64_t d[3] = {1024, 1024, 3}, s[2] = {6144, 2048}; cuuint32_t b[3] = {64, 64, 3}; mk_map(enc, &P.mWq, d_in[1], 3, d, s, b, S128, L256); }
  { cuuint64_t d[5] = {64, 32, 2, 16, 16}, s[4] = {2048, 65536, 131072, 128}; cuuint32_t b[5] = {64, 32, 1, 2, 2}; mk_map(enc, &P.mWo, d_in[2], 5, d, s, b, S128, L256); }
  { cuuint64_t d[2] = {3584, 1024}, s[1] = {7168}; cuuint32_t b[2] = {32, 128};
    mk_map(enc, &P.mWg, d_in[5], 2, d, s, b, S64, L128); mk_map(enc, &P.mWu, d_in[6], 2, d, s, b, S64, L128); }
  { cuuint64_t d[2] = {3072, 1024}, s[1] = {6144}; cuuint32_t b[2] = {32, 256}; mk_map(enc, &P.mWp, d_in[1], 2, d, s, b, S64, L128); }
  { cuuint64_t d[3] = {256, 3584, 4}, s[2] = {2048, 512}; cuuint32_t b[3] = {256, 8, 4}; mk_map(enc, &P.mWd, d_in[7], 3, d, s, b, S0, L128); }
  P.x0 = (const bf16*)d_in[0]; P.wqkv = (const bf16*)d_in[1]; P.wo = (const bf16*)d_in[2]; P.wr = (const bf16*)d_in[4]; P.wg = (const bf16*)d_in[5]; P.wu = (const bf16*)d_in[6]; P.wd = (const bf16*)d_in[7];
  P.out = (bf16*)d_out;
  cudaGetSymbolAddress((void**)&P.g, g_scr);
  for (int b = 0; b < 128; b++) {
    int j = b >> 1, quad = j < 4 ? 0 : (j < 36 ? 1 + (j - 4) % 8 : 9 + (j - 36) % 7), pos = j < 4 ? j : (j < 36 ? (j - 4) / 8 : (j - 36) / 7);
    int bid = ((quad >> 2) * 2 + (pos >> 1)) * 16 + ((quad & 3) * 2 + (pos & 1)) * 2 + (b & 1);
    int e = pos * 2 + (b & 1), fid = e < 7 ? quad * 7 + e : 112 + quad;
    P.map[b] = bid | fid << 8;
  }
  fused_kernel<<<128, 512, SMEM_BYTES>>>(P);
}
```

```cpp
#include <cuda_runtime.h>
#include <cuda_bf16.h>
#include <cuda.h>
#include <stdint.h>
#include <stddef.h>
typedef __nv_bfloat16 bf16;

template<int TB, int TA = 0> __device__ __forceinline__ void wgmma_ss_n192(float (&d)[96], uint64_t da, uint64_t db, int scale_d) {
  asm volatile("{\n.reg .pred p;\nsetp.ne.b32 p, %98, 0;\n"
    "wgmma.mma_async.sync.aligned.m64n192k16.f32.bf16.bf16 {%0, %1, %2, %3, %4, %5, %6, %7, %8, %9, %10, %11, %12, %13, %14, %15, %16, %17, %18, %19, %20, %21, %22, %23, %24, %25, %26, %27, %28, %29, %30, %31, %32, %33, %34, %35, %36, %37, %38, %39, %40, %41, %42, %43, %44, %45, %46, %47, %48, %49, %50, %51, %52, %53, %54, %55, %56, %57, %58, %59, %60, %61, %62, %63, %64, %65, %66, %67, %68, %69, %70, %71, %72, %73, %74, %75, %76, %77, %78, %79, %80, %81, %82, %83, %84, %85, %86, %87, %88, %89, %90, %91, %92, %93, %94, %95}, %96, %97, p, 1, 1, %100, %99;\n}\n"
    : "+f"(d[0]), "+f"(d[1]), "+f"(d[2]), "+f"(d[3]), "+f"(d[4]), "+f"(d[5]), "+f"(d[6]), "+f"(d[7]), "+f"(d[8]), "+f"(d[9]), "+f"(d[10]), "+f"(d[11]), "+f"(d[12]), "+f"(d[13]), "+f"(d[14]), "+f"(d[15]), "+f"(d[16]), "+f"(d[17]), "+f"(d[18]), "+f"(d[19]), "+f"(d[20]), "+f"(d[21]), "+f"(d[22]), "+f"(d[23]), "+f"(d[24]), "+f"(d[25]), "+f"(d[26]), "+f"(d[27]), "+f"(d[28]), "+f"(d[29]), "+f"(d[30]), "+f"(d[31]), "+f"(d[32]), "+f"(d[33]), "+f"(d[34]), "+f"(d[35]), "+f"(d[36]), "+f"(d[37]), "+f"(d[38]), "+f"(d[39]), "+f"(d[40]), "+f"(d[41]), "+f"(d[42]), "+f"(d[43]), "+f"(d[44]), "+f"(d[45]), "+f"(d[46]), "+f"(d[47]), "+f"(d[48]), "+f"(d[49]), "+f"(d[50]), "+f"(d[51]), "+f"(d[52]), "+f"(d[53]), "+f"(d[54]), "+f"(d[55]), "+f"(d[56]), "+f"(d[57]), "+f"(d[58]), "+f"(d[59]), "+f"(d[60]), "+f"(d[61]), "+f"(d[62]), "+f"(d[63]), "+f"(d[64]), "+f"(d[65]), "+f"(d[66]), "+f"(d[67]), "+f"(d[68]), "+f"(d[69]), "+f"(d[70]), "+f"(d[71]), "+f"(d[72]), "+f"(d[73]), "+f"(d[74]), "+f"(d[75]), "+f"(d[76]), "+f"(d[77]), "+f"(d[78]), "+f"(d[79]), "+f"(d[80]), "+f"(d[81]), "+f"(d[82]), "+f"(d[83]), "+f"(d[84]), "+f"(d[85]), "+f"(d[86]), "+f"(d[87]), "+f"(d[88]), "+f"(d[89]), "+f"(d[90]), "+f"(d[91]), "+f"(d[92]), "+f"(d[93]), "+f"(d[94]), "+f"(d[95])
    : "l"(da), "l"(db), "r"(scale_d), "n"(TB), "n"(TA));
}

template<int TB> __device__ __forceinline__ void wgmma_rs_n192(float (&d)[96], uint32_t a0, uint32_t a1, uint32_t a2, uint32_t a3, uint64_t db, int scale_d) {
  asm volatile("{\n.reg .pred p;\nsetp.ne.b32 p, %101, 0;\n"
    "wgmma.mma_async.sync.aligned.m64n192k16.f32.bf16.bf16 {%0, %1, %2, %3, %4, %5, %6, %7, %8, %9, %10, %11, %12, %13, %14, %15, %16, %17, %18, %19, %20, %21, %22, %23, %24, %25, %26, %27, %28, %29, %30, %31, %32, %33, %34, %35, %36, %37, %38, %39, %40, %41, %42, %43, %44, %45, %46, %47, %48, %49, %50, %51, %52, %53, %54, %55, %56, %57, %58, %59, %60, %61, %62, %63, %64, %65, %66, %67, %68, %69, %70, %71, %72, %73, %74, %75, %76, %77, %78, %79, %80, %81, %82, %83, %84, %85, %86, %87, %88, %89, %90, %91, %92, %93, %94, %95}, {%96, %97, %98, %99}, %100, p, 1, 1, %102;\n}\n"
    : "+f"(d[0]), "+f"(d[1]), "+f"(d[2]), "+f"(d[3]), "+f"(d[4]), "+f"(d[5]), "+f"(d[6]), "+f"(d[7]), "+f"(d[8]), "+f"(d[9]), "+f"(d[10]), "+f"(d[11]), "+f"(d[12]), "+f"(d[13]), "+f"(d[14]), "+f"(d[15]), "+f"(d[16]), "+f"(d[17]), "+f"(d[18]), "+f"(d[19]), "+f"(d[20]), "+f"(d[21]), "+f"(d[22]), "+f"(d[23]), "+f"(d[24]), "+f"(d[25]), "+f"(d[26]), "+f"(d[27]), "+f"(d[28]), "+f"(d[29]), "+f"(d[30]), "+f"(d[31]), "+f"(d[32]), "+f"(d[33]), "+f"(d[34]), "+f"(d[35]), "+f"(d[36]), "+f"(d[37]), "+f"(d[38]), "+f"(d[39]), "+f"(d[40]), "+f"(d[41]), "+f"(d[42]), "+f"(d[43]), "+f"(d[44]), "+f"(d[45]), "+f"(d[46]), "+f"(d[47]), "+f"(d[48]), "+f"(d[49]), "+f"(d[50]), "+f"(d[51]), "+f"(d[52]), "+f"(d[53]), "+f"(d[54]), "+f"(d[55]), "+f"(d[56]), "+f"(d[57]), "+f"(d[58]), "+f"(d[59]), "+f"(d[60]), "+f"(d[61]), "+f"(d[62]), "+f"(d[63]), "+f"(d[64]), "+f"(d[65]), "+f"(d[66]), "+f"(d[67]), "+f"(d[68]), "+f"(d[69]), "+f"(d[70]), "+f"(d[71]), "+f"(d[72]), "+f"(d[73]), "+f"(d[74]), "+f"(d[75]), "+f"(d[76]), "+f"(d[77]), "+f"(d[78]), "+f"(d[79]), "+f"(d[80]), "+f"(d[81]), "+f"(d[82]), "+f"(d[83]), "+f"(d[84]), "+f"(d[85]), "+f"(d[86]), "+f"(d[87]), "+f"(d[88]), "+f"(d[89]), "+f"(d[90]), "+f"(d[91]), "+f"(d[92]), "+f"(d[93]), "+f"(d[94]), "+f"(d[95])
    : "r"(a0), "r"(a1), "r"(a2), "r"(a3), "l"(db), "r"(scale_d), "n"(TB));
}

template<int TB, int TA = 0> __device__ __forceinline__ void wgmma_ss_n128(float (&d)[64], uint64_t da, uint64_t db, int scale_d) {
  asm volatile("{\n.reg .pred p;\nsetp.ne.b32 p, %66, 0;\n"
    "wgmma.mma_async.sync.aligned.m64n128k16.f32.bf16.bf16 {%0, %1, %2, %3, %4, %5, %6, %7, %8, %9, %10, %11, %12, %13, %14, %15, %16, %17, %18, %19, %20, %21, %22, %23, %24, %25, %26, %27, %28, %29, %30, %31, %32, %33, %34, %35, %36, %37, %38, %39, %40, %41, %42, %43, %44, %45, %46, %47, %48, %49, %50, %51, %52, %53, %54, %55, %56, %57, %58, %59, %60, %61, %62, %63}, %64, %65, p, 1, 1, %68, %67;\n}\n"
    : "+f"(d[0]), "+f"(d[1]), "+f"(d[2]), "+f"(d[3]), "+f"(d[4]), "+f"(d[5]), "+f"(d[6]), "+f"(d[7]), "+f"(d[8]), "+f"(d[9]), "+f"(d[10]), "+f"(d[11]), "+f"(d[12]), "+f"(d[13]), "+f"(d[14]), "+f"(d[15]), "+f"(d[16]), "+f"(d[17]), "+f"(d[18]), "+f"(d[19]), "+f"(d[20]), "+f"(d[21]), "+f"(d[22]), "+f"(d[23]), "+f"(d[24]), "+f"(d[25]), "+f"(d[26]), "+f"(d[27]), "+f"(d[28]), "+f"(d[29]), "+f"(d[30]), "+f"(d[31]), "+f"(d[32]), "+f"(d[33]), "+f"(d[34]), "+f"(d[35]), "+f"(d[36]), "+f"(d[37]), "+f"(d[38]), "+f"(d[39]), "+f"(d[40]), "+f"(d[41]), "+f"(d[42]), "+f"(d[43]), "+f"(d[44]), "+f"(d[45]), "+f"(d[46]), "+f"(d[47]), "+f"(d[48]), "+f"(d[49]), "+f"(d[50]), "+f"(d[51]), "+f"(d[52]), "+f"(d[53]), "+f"(d[54]), "+f"(d[55]), "+f"(d[56]), "+f"(d[57]), "+f"(d[58]), "+f"(d[59]), "+f"(d[60]), "+f"(d[61]), "+f"(d[62]), "+f"(d[63])
    : "l"(da), "l"(db), "r"(scale_d), "n"(TB), "n"(TA));
}

template<int TB, int TA = 0> __device__ __forceinline__ void wgmma_ss_n64(float (&d)[32], uint64_t da, uint64_t db, int scale_d) {
  asm volatile("{\n.reg .pred p;\nsetp.ne.b32 p, %34, 0;\n"
    "wgmma.mma_async.sync.aligned.m64n64k16.f32.bf16.bf16 {%0, %1, %2, %3, %4, %5, %6, %7, %8, %9, %10, %11, %12, %13, %14, %15, %16, %17, %18, %19, %20, %21, %22, %23, %24, %25, %26, %27, %28, %29, %30, %31}, %32, %33, p, 1, 1, %36, %35;\n}\n"
    : "+f"(d[0]), "+f"(d[1]), "+f"(d[2]), "+f"(d[3]), "+f"(d[4]), "+f"(d[5]), "+f"(d[6]), "+f"(d[7]), "+f"(d[8]), "+f"(d[9]), "+f"(d[10]), "+f"(d[11]), "+f"(d[12]), "+f"(d[13]), "+f"(d[14]), "+f"(d[15]), "+f"(d[16]), "+f"(d[17]), "+f"(d[18]), "+f"(d[19]), "+f"(d[20]), "+f"(d[21]), "+f"(d[22]), "+f"(d[23]), "+f"(d[24]), "+f"(d[25]), "+f"(d[26]), "+f"(d[27]), "+f"(d[28]), "+f"(d[29]), "+f"(d[30]), "+f"(d[31])
    : "l"(da), "l"(db), "r"(scale_d), "n"(TB), "n"(TA));
}

template<int TB, int TA = 0> __device__ __forceinline__ void wgmma_ss_n8(float (&d)[4], uint64_t da, uint64_t db, int scale_d) {
  asm volatile("{\n.reg .pred p;\nsetp.ne.b32 p, %6, 0;\n"
    "wgmma.mma_async.sync.aligned.m64n8k16.f32.bf16.bf16 {%0, %1, %2, %3}, %4, %5, p, 1, 1, %8, %7;\n}\n"
    : "+f"(d[0]), "+f"(d[1]), "+f"(d[2]), "+f"(d[3])
    : "l"(da), "l"(db), "r"(scale_d), "n"(TB), "n"(TA));
}

template<int TB> __device__ __forceinline__ void wgmma_rs_n40(float (&d)[20], uint32_t a0, uint32_t a1, uint32_t a2, uint32_t a3, uint64_t db, int scale_d) {
  asm volatile("{\n.reg .pred p;\nsetp.ne.b32 p, %25, 0;\n"
    "wgmma.mma_async.sync.aligned.m64n40k16.f32.bf16.bf16 {%0, %1, %2, %3, %4, %5, %6, %7, %8, %9, %10, %11, %12, %13, %14, %15, %16, %17, %18, %19}, {%20, %21, %22, %23}, %24, p, 1, 1, %26;\n}\n"
    : "+f"(d[0]), "+f"(d[1]), "+f"(d[2]), "+f"(d[3]), "+f"(d[4]), "+f"(d[5]), "+f"(d[6]), "+f"(d[7]), "+f"(d[8]), "+f"(d[9]), "+f"(d[10]), "+f"(d[11]), "+f"(d[12]), "+f"(d[13]), "+f"(d[14]), "+f"(d[15]), "+f"(d[16]), "+f"(d[17]), "+f"(d[18]), "+f"(d[19])
    : "r"(a0), "r"(a1), "r"(a2), "r"(a3), "l"(db), "r"(scale_d), "n"(TB));
}

#define DEVI __device__ __forceinline__
DEVI uint32_t smem_u32(const void* p) { return (uint32_t)__cvta_generic_to_shared(p); }
DEVI void mbar_init(uint32_t bar, uint32_t cnt) { asm volatile("mbarrier.init.shared::cta.b64 [%0], %1;" :: "r"(bar), "r"(cnt)); }
DEVI void mbar_expect_tx(uint32_t bar, uint32_t bytes) { asm volatile("mbarrier.arrive.expect_tx.shared::cta.b64 _, [%0], %1;" :: "r"(bar), "r"(bytes) : "memory"); }
DEVI void mbar_arrive(uint32_t bar) { asm volatile("mbarrier.arrive.shared::cta.b64 _, [%0];" :: "r"(bar) : "memory"); }
DEVI void mbar_arrive_peer(uint32_t bar) {
  asm volatile("{\n.reg .b32 ra;\nmapa.shared::cluster.u32 ra, %0, %1;\nmbarrier.arrive.shared::cluster.b64 _, [ra];\n}" :: "r"(bar), "r"((blockIdx.x & 1) ^ 1) : "memory");
}
DEVI void bulk_s2peer(uint32_t a, uint32_t bytes, uint32_t bar) {
  asm volatile("{\n.reg .b32 ra, rb;\nmapa.shared::cluster.u32 ra, %0, %3;\nmapa.shared::cluster.u32 rb, %2, %3;\n"
               "cp.async.bulk.shared::cluster.shared::cta.mbarrier::complete_tx::bytes [ra], [%0], %1, [rb];\n}"
               :: "r"(a), "r"(bytes), "r"(bar), "r"((blockIdx.x & 1) ^ 1) : "memory");
}
DEVI void mbar_wait(uint32_t bar, uint32_t parity) {
  asm volatile("{\n.reg .pred p;\nLW:\nmbarrier.try_wait.parity.shared::cta.b64 p, [%0], %1;\n@!p bra LW;\n}" :: "r"(bar), "r"(parity) : "memory");
}
DEVI uint32_t mbar_test(uint32_t bar, uint32_t parity) {
  uint32_t r; asm volatile("{\n.reg .pred p;\nmbarrier.test_wait.parity.shared::cta.b64 p, [%1], %2;\nselp.u32 %0, 1, 0, p;\n}" : "=r"(r) : "r"(bar), "r"(parity) : "memory"); return r;
}
DEVI void mbar_wait_b(uint32_t bar, uint32_t parity) {
  asm volatile("{\n.reg .pred p;\n.reg .u32 it;\nmov.u32 it, 0;\nLW:\nmbarrier.try_wait.parity.shared::cta.b64 p, [%0], %1;\n@p bra LD;\n"
               "add.u32 it, it, 1;\nsetp.lt.u32 p, it, 0x1000000;\n@p bra LW;\ntrap;\nLD:\n}" :: "r"(bar), "r"(parity) : "memory");
}
DEVI void tma_2d(uint32_t dst, const CUtensorMap* m, int c0, int c1, uint32_t bar) {
  asm volatile("cp.async.bulk.tensor.2d.shared::cluster.global.mbarrier::complete_tx::bytes [%0], [%1, {%3, %4}], [%2];"
    :: "r"(dst), "l"(m), "r"(bar), "r"(c0), "r"(c1) : "memory");
}
DEVI void tma_3d(uint32_t dst, const CUtensorMap* m, int c0, int c1, int c2, uint32_t bar) {
  asm volatile("cp.async.bulk.tensor.3d.shared::cluster.global.mbarrier::complete_tx::bytes [%0], [%1, {%3, %4, %5}], [%2];"
    :: "r"(dst), "l"(m), "r"(bar), "r"(c0), "r"(c1), "r"(c2) : "memory");
}
#define POL_EF POL_FIRST
constexpr uint64_t POL_FIRST = 0x12F0000000000000ull, POL_NORMAL = 0x1000000000000000ull;
DEVI void tma_2d_h(uint32_t dst, const CUtensorMap* m, int c0, int c1, uint32_t bar, uint64_t pol) {
  asm volatile("cp.async.bulk.tensor.2d.shared::cluster.global.mbarrier::complete_tx::bytes.L2::cache_hint [%0], [%1, {%3, %4}], [%2], %5;"
    :: "r"(dst), "l"(m), "r"(bar), "r"(c0), "r"(c1), "l"(pol) : "memory");
}
DEVI void tma_3d_h(uint32_t dst, const CUtensorMap* m, int c0, int c1, int c2, uint32_t bar, uint64_t pol) {
  asm volatile("cp.async.bulk.tensor.3d.shared::cluster.global.mbarrier::complete_tx::bytes.L2::cache_hint [%0], [%1, {%3, %4, %5}], [%2], %6;"
    :: "r"(dst), "l"(m), "r"(bar), "r"(c0), "r"(c1), "r"(c2), "l"(pol) : "memory");
}
DEVI void bulk_g2s_h(uint32_t s, const void* g, uint32_t bytes, uint32_t bar, uint64_t pol = POL_EF) {
  asm volatile("cp.async.bulk.shared::cluster.global.mbarrier::complete_tx::bytes.L2::cache_hint [%0], [%1], %2, [%3], %4;"
    :: "r"(s), "l"(g), "r"(bytes), "r"(bar), "l"(pol) : "memory");
}
DEVI void tma_5d(uint32_t dst, const CUtensorMap* m, int c0, int c1, int c2, int c3, int c4, uint32_t bar, uint64_t pol) {
  asm volatile("cp.async.bulk.tensor.5d.shared::cluster.global.mbarrier::complete_tx::bytes.L2::cache_hint [%0], [%1, {%3, %4, %5, %6, %7}], [%2], %8;"
    :: "r"(dst), "l"(m), "r"(bar), "r"(c0), "r"(c1), "r"(c2), "r"(c3), "r"(c4), "l"(pol) : "memory");
}
DEVI void tma_prefetch_2d(const CUtensorMap* m, int c0, int c1) {
  asm volatile("cp.async.bulk.prefetch.tensor.2d.L2.global.tile [%0, {%1, %2}];" :: "l"(m), "r"(c0), "r"(c1) : "memory");
}
DEVI void tma_prefetch_3d(const CUtensorMap* m, int c0, int c1, int c2) {
  asm volatile("cp.async.bulk.prefetch.tensor.3d.L2.global.tile [%0, {%1, %2, %3}];" :: "l"(m), "r"(c0), "r"(c1), "r"(c2) : "memory");
}
DEVI void bulk_prefetch(const void* g, uint32_t bytes) { asm volatile("cp.async.bulk.prefetch.L2.global [%0], %1;" :: "l"(g), "r"(bytes) : "memory"); }
DEVI void bulk_g2s(uint32_t s, const void* g, uint32_t bytes, uint32_t bar) {
  asm volatile("cp.async.bulk.shared::cluster.global.mbarrier::complete_tx::bytes [%0], [%1], %2, [%3];" :: "r"(s), "l"(g), "r"(bytes), "r"(bar) : "memory");
}
DEVI void bulk_s2g(void* g, uint32_t s, uint32_t bytes) {
  asm volatile("cp.async.bulk.global.shared::cta.bulk_group [%0], [%1], %2;\ncp.async.bulk.commit_group;" :: "l"(g), "r"(s), "r"(bytes) : "memory");
}
template<int N> DEVI void bulk_wait() { asm volatile("cp.async.bulk.wait_group %0;" :: "n"(N) : "memory"); }
DEVI void fence_async_smem() { asm volatile("fence.proxy.async.shared::cta;" ::: "memory"); }
DEVI void fence_async_glob() { asm volatile("fence.proxy.async.global;" ::: "memory"); }
DEVI unsigned ld_rlx(const unsigned* p) { unsigned v; asm volatile("ld.relaxed.gpu.global.u32 %0, [%1];" : "=r"(v) : "l"(p) : "memory"); return v; }
DEVI void st_rlx(unsigned* p, unsigned v) { asm volatile("st.relaxed.gpu.global.u32 [%0], %1;" :: "l"(p), "r"(v) : "memory"); }
DEVI uint2 ldg_stream(const uint2* p) { uint2 v; asm volatile("ld.global.nc.L1::no_allocate.v2.u32 {%0, %1}, [%2];" : "=r"(v.x), "=r"(v.y) : "l"(p)); return v; }
DEVI void fence_rel() { asm volatile("fence.release.gpu;" ::: "memory"); }
DEVI uint4 ld_ll(const uint4* p) {
  uint4 v;
  asm volatile("{\n.reg .b128 t;\n.reg .b64 a, b;\nld.relaxed.gpu.global.b128 t, [%4];\nmov.b128 {a, b}, t;\nmov.b64 {%0, %1}, a;\nmov.b64 {%2, %3}, b;\n}"
               : "=r"(v.x), "=r"(v.y), "=r"(v.z), "=r"(v.w) : "l"(p) : "memory");
  return v;
}
DEVI void st_ll(uint4* p, uint32_t x, uint32_t y, uint32_t z, uint32_t w) {
  asm volatile("{\n.reg .b128 t;\n.reg .b64 a, b;\nmov.b64 a, {%1, %2};\nmov.b64 b, {%3, %4};\nmov.b128 t, {a, b};\nst.relaxed.gpu.global.b128 [%0], t;\n}"
               :: "l"(p), "r"(x), "r"(y), "r"(z), "r"(w) : "memory");
}
#define SPIN_MAX 0x1000000
DEVI uint4 poll_ll(const uint4* p, uint32_t mask, uint32_t tag) {
  uint4 v; int it = 0;
  do { v = ld_ll(p); if (++it > SPIN_MAX) __trap(); } while (!__all_sync(0xffffffffu, (v.w & mask) == tag));
  return v;
}
DEVI void poll_ll2(const uint4* p, const uint4* q, uint32_t mask, uint32_t tag, uint4& a, uint4& b) {
  int it = 0;
  do { a = ld_ll(p); b = ld_ll(q); if (++it > SPIN_MAX) __trap(); } while (!__all_sync(0xffffffffu, (a.w & mask) == tag && (b.w & mask) == tag));
}
DEVI void bar_sync(int id, int n) { asm volatile("bar.sync %0, %1;" :: "r"(id), "r"(n) : "memory"); }
DEVI void bar_arrive(int id, int n) { asm volatile("bar.arrive %0, %1;" :: "r"(id), "r"(n) : "memory"); }
DEVI void wg_fence() { asm volatile("wgmma.fence.sync.aligned;" ::: "memory"); }
DEVI void wg_commit() { asm volatile("wgmma.commit_group.sync.aligned;" ::: "memory"); }
template<int N> DEVI void wg_wait() { asm volatile("wgmma.wait_group.sync.aligned %0;" :: "n"(N) : "memory"); }
template<int N> DEVI void reg_inc() { asm volatile("setmaxnreg.inc.sync.aligned.u32 %0;" :: "n"(N)); }
template<int N> DEVI void reg_dec() { asm volatile("setmaxnreg.dec.sync.aligned.u32 %0;" :: "n"(N)); }
DEVI float ex2f(float x) { float y; asm("ex2.approx.ftz.f32 %0, %1;" : "=f"(y) : "f"(x)); return y; }
DEVI uint32_t pack_bf16(float lo, float hi) { uint32_t r; asm("cvt.rn.bf16x2.f32 %0, %1, %2;" : "=r"(r) : "f"(hi), "f"(lo)); return r; }
DEVI float bf_lo(uint32_t v) { return __uint_as_float(v << 16); }
DEVI float bf_hi(uint32_t v) { return __uint_as_float(v & 0xffff0000u); }
DEVI float bf_round(float x) { return bf_lo(pack_bf16(x, 0.f)); }
DEVI void stsm_x4(uint32_t addr, uint32_t a, uint32_t b, uint32_t c, uint32_t d) {
  asm volatile("stmatrix.sync.aligned.m8n8.x4.shared.b16 [%0], {%1,%2,%3,%4};" :: "r"(addr), "r"(a), "r"(b), "r"(c), "r"(d) : "memory");
}
DEVI void ldsm_x4(uint32_t addr, uint32_t& a, uint32_t& b, uint32_t& c, uint32_t& d) {
  asm volatile("ldmatrix.sync.aligned.m8n8.x4.shared.b16 {%0,%1,%2,%3}, [%4];" : "=r"(a), "=r"(b), "=r"(c), "=r"(d) : "r"(addr) : "memory");
}
DEVI uint4 lds128(uint32_t a) { uint4 v; asm volatile("ld.shared.v4.u32 {%0,%1,%2,%3}, [%4];" : "=r"(v.x), "=r"(v.y), "=r"(v.z), "=r"(v.w) : "r"(a) : "memory"); return v; }
DEVI void sts128(uint32_t a, uint4 v) { asm volatile("st.shared.v4.u32 [%0], {%1,%2,%3,%4};" :: "r"(a), "r"(v.x), "r"(v.y), "r"(v.z), "r"(v.w) : "memory"); }
DEVI float2 lds64f(uint32_t a) { float2 v; asm volatile("ld.shared.v2.f32 {%0,%1}, [%2];" : "=f"(v.x), "=f"(v.y) : "r"(a) : "memory"); return v; }
DEVI void sts64f(uint32_t a, float x, float y) { asm volatile("st.shared.v2.f32 [%0], {%1,%2};" :: "r"(a), "f"(x), "f"(y) : "memory"); }
DEVI uint32_t lds32(uint32_t a) { uint32_t v; asm volatile("ld.shared.u32 %0, [%1];" : "=r"(v) : "r"(a) : "memory"); return v; }
DEVI float lds32f(uint32_t a) { return __uint_as_float(lds32(a)); }
DEVI void sts32(uint32_t a, uint32_t v) { asm volatile("st.shared.u32 [%0], %1;" :: "r"(a), "r"(v) : "memory"); }
DEVI void sts32f(uint32_t a, float v) { sts32(a, __float_as_uint(v)); }
DEVI void sts16(uint32_t a, uint32_t v) { asm volatile("st.shared.u16 [%0], %1;" :: "r"(a), "h"((unsigned short)v) : "memory"); }
template<int N> DEVI void keep(float (&d)[N]) {
  #pragma unroll
  for (int i = 0; i < N; i++) asm volatile("" : "+f"(d[i]) :: "memory");
}
template<int N> DEVI void keep(uint32_t (&d)[N]) {
  #pragma unroll
  for (int i = 0; i < N; i++) asm volatile("" : "+r"(d[i]) :: "memory");
}
template<uint32_t HI> DEVI uint64_t mkd(uint32_t lo) { uint64_t r; asm("mov.b64 %0, {%1, %2};" : "=l"(r) : "r"(lo), "n"(HI)); return r; }
constexpr uint32_t HI128 = (1u << 30) | (1024 >> 4), HI64 = (2u << 30) | (512 >> 4);
#define VOFF(x) ((uint32_t)(x) * (uint32_t)(1 - 65536))
DEVI bool elect() { uint32_t p; asm volatile("{\n.reg .pred q;\nelect.sync _|q, 0xffffffff;\nselp.u32 %0, 1, 0, q;\n}" : "=r"(p)); return p; }
DEVI void warp_signal(uint32_t bar) { __syncwarp(); if (elect()) mbar_arrive(bar); }

struct Scratch {
  uint4 kv[128][4][1024];
  uint4 o[8][2][8][2][1024];
  uint4 x[8][16][2048];
  uint4 zero[1024];
  uint4 statP[8][2048];
  uint4 statF[2048];
  uint4 csP[16][8][96];
  uint4 best[8][16];
  uint4 row[16][256];
  uint4 yP[128][112][2];
  uint4 x2[8][256];
  uint4 patch[128][64];
  unsigned flagKV[128][32];
  unsigned flagO[8][32];
  unsigned flagX[8][32];
  unsigned epoch;
};
__device__ __align__(1024) Scratch g_scr;
#define PROFT(cond, slot)
#define PROFW(cond, slot)
#define PROFD(cond, slot)
#define PROFX(cond, slot)
#define PROFY(cond, slot)

constexpr uint32_t SB0 = 65536, HOLE = 90112, SA2 = 98304, SB1 = 131072, SB2 = 155648, STG = 180224;
constexpr uint32_t KVA = 0, KVB = 98304, QO = 65536;
constexpr uint32_t MISC = 229376, CS = MISC, ONES = MISC + 768, BARS = MISC + 1792, INFO = MISC + 2208, WR = MISC + 2224, X2SEG = MISC + 2736, INFO2 = MISC + 2992, DUMP = MISC + 3040;
constexpr uint32_t PAR = HOLE, HV = HOLE + 2048, RED = HOLE + 6144, PATCH = 196608;
constexpr uint32_t SMEM_BYTES = 232448;
enum { B_FULLQ = 0, B_EMPTYQ = 3, B_FULLW = 6, B_EMPTYW = 12, B_HAFREE = 18, B_OFREE = 20,
       B_XFREE = 21,
       B_KVRDY = 23, B_ORDY = 27, B_XRDY = 35, B_STGE = 39,
       B_KVFULL = 42, B_RES = 46, B_PAR = 47, B_STG = 48, B_PFREE = 51, B_COUNT = 52,
       B_ROW = 154 };
#define BAR(x) (sb + BARS + 8 * (x))
DEVI uint32_t qa_off(int s) { return s == 2 ? SA2 : (uint32_t)s * 32768u; }
DEVI uint32_t qb_off(int s) { return s == 0 ? SB0 : (s == 1 ? SB1 : SB2); }
DEVI int kb_order(int bc, int n) {
  const int e = n < 9 ? n - 2 : n - 9;
  return n < 2 ? 2 * bc + n : 2 * (((e < 4 ? e + 4 : e - 4 + (e - 4 >= (bc & 3))) + (bc & 4)) & 7) + (n >= 9);
}
DEVI int wo_order(int bc, int n) { return (n & 8) | ((n + (bc & 6)) & 7); }
DEVI uint32_t w_off(int s) { return (uint32_t)((0x143065 >> (4 * s)) & 7) * 32768u; }
DEVI uint32_t w_par(int n, int s, int L) { return (n >= 6 && n < 12) ^ (s == 5) ^ (s != 2 && L); }
DEVI int w_next(int n, int s) { return s == 5 ? 0 : (n == 13 ? 3 : s + 1); }

struct Params {
  CUtensorMap mX, mXh, mWq, mWo, mWg, mWu, mWp, mWd;
  const bf16 *x0, *wqkv, *wo, *wr, *wg, *wu, *wd;
  bf16* out;
  Scratch* g;
  unsigned map[128];
};
#define BID ((int)(P.map[blockIdx.x] & 255))
#define FID ((int)(P.map[blockIdx.x] >> 8))
DEVI uint32_t uni(uint32_t v) { return __shfl_sync(0xffffffffu, v, 0); }
#define PQ_N 8
#define PQ_T 700
#define PF0_N 10
#define PF0_T 1600
#define PF1_E 24
#define PF1_T 1100
#define POL_Q1 POL_NORMAL
#define POL_X POL_NORMAL
#define PFA0_BAR 3
#define PFA1_BAR 0
#define PFA0_M 0
#define PFA1_M 0
#define PFA0_T 900
#define PFA1_T 700
#define PF1_S PF0_N
#define PF1_D 0
#define POL_G POL_NORMAL
#define POL_U POL_FIRST
#define POL_D POL_FIRST
#define JQ_N 6
#define WDSRC (P.wd + (size_t)min(fid, 111) * 32768)
#define WDSRC2 (P.wd + FID * 32768)
#define WD_N 4
#define THR_N 5
#define KV_D 1800
#define XD_D 300
#define W0_BAR 3
#define QEF_N 99
#define PACE_T 300
#define IDLE_T 11000
#define LATE_C 2
#define LATE_B B_XFREE + 1
#define LATE_P 0
#define KV_D1 200
#define KV_D2 1200
#define KV_DL 0
#define POL_Q0 POL_NORMAL
constexpr float LN_EPS = 1e-5f;
constexpr float QSCALE = 0.17677669529663687f * 1.4426950408889634f;

DEVI void fma8(float (&a)[8], uint4 v, float h) {
  a[0] = fmaf(bf_lo(v.x), h, a[0]); a[1] = fmaf(bf_hi(v.x), h, a[1]); a[2] = fmaf(bf_lo(v.y), h, a[2]); a[3] = fmaf(bf_hi(v.y), h, a[3]);
  a[4] = fmaf(bf_lo(v.z), h, a[4]); a[5] = fmaf(bf_hi(v.z), h, a[5]); a[6] = fmaf(bf_lo(v.w), h, a[6]); a[7] = fmaf(bf_hi(v.w), h, a[7]);
}
DEVI uint4 ldsv128(uint32_t a) { uint4 v; asm volatile("ld.volatile.shared.v4.u32 {%0,%1,%2,%3}, [%4];" : "=r"(v.x), "=r"(v.y), "=r"(v.z), "=r"(v.w) : "r"(a) : "memory"); return v; }
DEVI float ldsv32f(uint32_t a) { float v; asm volatile("ld.volatile.shared.f32 %0, [%1];" : "=f"(v) : "r"(a) : "memory"); return v; }
DEVI uint32_t clk() { uint32_t t; asm volatile("mov.u32 %0, %%clock;" : "=r"(t)); return t; }
DEVI int fresh_tid() { int t; asm volatile("mov.u32 %0, %%tid.x;" : "=r"(t)); return t & 127; }
DEVI float fold8(const float (&a)[8]) {
  const int lane = threadIdx.x & 31;
  const bool u = lane & 16, v = lane & 8, x = lane & 4;
  float b0 = (u ? a[4] : a[0]) + __shfl_xor_sync(0xffffffffu, u ? a[0] : a[4], 16), b1 = (u ? a[5] : a[1]) + __shfl_xor_sync(0xffffffffu, u ? a[1] : a[5], 16);
  float b2 = (u ? a[6] : a[2]) + __shfl_xor_sync(0xffffffffu, u ? a[2] : a[6], 16), b3 = (u ? a[7] : a[3]) + __shfl_xor_sync(0xffffffffu, u ? a[3] : a[7], 16);
  float c0 = (v ? b2 : b0) + __shfl_xor_sync(0xffffffffu, v ? b0 : b2, 8), c1 = (v ? b3 : b1) + __shfl_xor_sync(0xffffffffu, v ? b1 : b3, 8);
  return (x ? c1 : c0) + __shfl_xor_sync(0xffffffffu, x ? c0 : c1, 4);
}
DEVI float swiglu(float g, float u) { g = bf_round(g); return bf_round(bf_round(__fdividef(g, 1.f + __expf(-g))) * bf_round(u)); }

DEVI void qk_issue(float (&s)[32], uint32_t qd, uint32_t kd) {
  wgmma_ss_n64<0>(s, mkd<HI64>(qd), mkd<HI64>(kd), 0);
  wgmma_ss_n64<0>(s, mkd<HI64>(qd + 2), mkd<HI64>(kd + 2), 1);
}
template<int J0, int J1> DEVI void exp_pack(const float (&s)[32], uint32_t (&p)[16]) {
  #pragma unroll
  for (int j = J0; j < J1; j++) p[j] = pack_bf16(ex2f(s[2 * j]), ex2f(s[2 * j + 1]));
}
DEVI bool attn_pack(const float (&o)[20], uint32_t (&ob)[8]) {
  const float lo = 5.421010862427522e-20f, hi = 1.8446744073709552e19f;
  float i0, i1; asm("rcp.approx.ftz.f32 %0, %1;" : "=f"(i0) : "f"(o[16])); asm("rcp.approx.ftz.f32 %0, %1;" : "=f"(i1) : "f"(o[18]));
  #pragma unroll
  for (int e = 0; e < 8; e++) ob[e] = pack_bf16(o[2 * e] * ((e & 1) ? i1 : i0), o[2 * e + 1] * ((e & 1) ? i1 : i0));
  return __all_sync(0xffffffffu, o[16] >= lo && o[16] <= hi && o[18] >= lo && o[18] <= hi);
}
DEVI void attn_store(const uint32_t (&ob)[8], bool ok, uint32_t st, uint32_t sb, uint32_t bar) {
  stsm_x4(ok ? st : sb + DUMP, ob[0], ob[1], ob[2], ob[3]); stsm_x4(ok ? st ^ 32 : sb + DUMP, ob[4], ob[5], ob[6], ob[7]);
  __syncwarp();
  asm volatile("{\n.reg .pred p, q;\nelect.sync _|q, 0xffffffff;\nsetp.ne.and.u32 p, %1, 0, q;\n@p mbarrier.arrive.shared::cta.b64 _, [%0];\n}" :: "r"(bar), "r"((uint32_t)ok) : "memory");
}
DEVI void attn_exact(uint32_t st, uint32_t kv, int t, bool hasprev, uint32_t bar) {
  const int lane = threadIdx.x & 31;
  #pragma unroll 1
  for (int row = ((threadIdx.x >> 5) & 3) * 16, n = 0; n < 16; n++, row++) {
    const int k1 = 256 + t * 64 + row;
    float m = -INFINITY, l = 0.f, o = 0.f;
    #pragma unroll 1
    for (int k0 = hasprev ? k1 - 255 : 256; k0 <= k1; k0 += 32) {
      const int k = min(k0 + lane, k1), r = k & 63;
      float sc = 0.f;
      #pragma unroll 1
      for (int c = 0; c < 16; c++) {
        uint32_t a = lds32(st + row * 64 + ((c * 4) ^ ((row & 6) << 3))), b = lds32(kv + (k >> 6) * 8192 + r * 64 + ((c * 4) ^ ((r & 6) << 3)));
        sc = fmaf(bf_lo(a), bf_lo(b), fmaf(bf_hi(a), bf_hi(b), sc));
      }
      float mn = fmaxf(m, sc);
      #pragma unroll 1
      for (int x = 16; x; x >>= 1) mn = fmaxf(mn, __shfl_xor_sync(0xffffffffu, mn, x));
      const float al = ex2f(m - mn), pr = ex2f(sc - mn);
      m = mn; l *= al; o *= al;
      #pragma unroll 1
      for (int q = k0; q <= min(k0 + 31, k1); q++) {
        const float z = __shfl_sync(0xffffffffu, pr, q - k0);
        uint32_t b = lds32(kv + (q >> 6) * 8192 + 4096 + (q & 63) * 64 + (((lane >> 1) * 4) ^ ((q & 6) << 3)));
        l += z; o = fmaf(z, (lane & 1) ? bf_hi(b) : bf_lo(b), o);
      }
    }
    __syncwarp();
    sts16(st + row * 64 + ((lane * 2) ^ ((row & 6) << 3)), pack_bf16(__fdividef(o, l), 0.f));
  }
  warp_signal(bar);
}

template<int K0, int K1, int DONE = 0> DEVI void exp_pv(const float (&s)[32], uint32_t (&p)[16], float (&o)[20], uint32_t vd, bool accum) {
  #pragma unroll
  for (int ks = K0; ks < K1; ks++) {
    if (ks >= DONE) {
      #pragma unroll
      for (int j = 4 * ks; j < 4 * ks + 4; j++) p[j] = pack_bf16(ex2f(s[2 * j]), ex2f(s[2 * j + 1]));
    }
    asm volatile("" : "+r"(p[4 * ks]), "+r"(p[4 * ks + 1]), "+r"(p[4 * ks + 2]), "+r"(p[4 * ks + 3]));
    wg_fence();
    wgmma_rs_n40<1>(o, p[ks * 4], p[ks * 4 + 1], p[ks * 4 + 2], p[ks * 4 + 3], mkd<HI64>(vd + VOFF(ks * 64)), ks ? 1 : accum);
  }
}
DEVI void exp_pv2(const float (&s)[32], const float (&sx)[32], uint32_t (&p)[16], uint32_t (&px)[16], float (&o)[20], uint32_t v0, uint32_t v4,
                  const uint32_t (&msk)[9], int tdiag) {
  #pragma unroll
  for (int ks = 0; ks < 4; ks++) {
    #pragma unroll
    for (int j = 4 * ks; j < 4 * ks + 4; j++) {
      const int c = 8 * (j >> 1) - 8 * (j & 1);
      const uint32_t e = pack_bf16(ex2f(c > tdiag ? s[2 * j] : sx[2 * j]), ex2f(c + 1 > tdiag ? s[2 * j + 1] : sx[2 * j + 1])), m = msk[(j >> 1) - (j & 1) + 1];
      p[j] = e & m; px[j] = e & ~m;
      asm volatile("" : "+r"(p[j]), "+r"(px[j]));
    }
    wg_fence();
    wgmma_rs_n40<1>(o, p[ks * 4], p[ks * 4 + 1], p[ks * 4 + 2], p[ks * 4 + 3], mkd<HI64>(v0 + VOFF(ks * 64)), 1);
    wgmma_rs_n40<1>(o, px[ks * 4], px[ks * 4 + 1], px[ks * 4 + 2], px[ks * 4 + 3], mkd<HI64>(v4 + VOFF(ks * 64)), 1);
  }
}

template<int J0> DEVI void qkv_store(const float (&a)[96], float p0, float p1, uint32_t d) {
  #pragma unroll
  for (int hh = 0; hh < 2; hh++) {
    const int j = 4 * (J0 + 2 * hh);
    stsm_x4(d ^ (hh << 5), pack_bf16(a[j] * p0, a[j + 1] * p0), pack_bf16(a[j + 2] * p1, a[j + 3] * p1),
                           pack_bf16(a[j + 4] * p0, a[j + 5] * p0), pack_bf16(a[j + 6] * p1, a[j + 7] * p1));
  }
}
DEVI void mean_step(float (&a)[96], float m0, float m1, uint32_t cd, bool z) {
  const uint32_t u0 = z ? 0u : __float_as_uint(m0), u1 = z ? 0u : __float_as_uint(m1);
  uint32_t ma[4] = {__byte_perm(u0, 0u, 0x1010), __byte_perm(u1, 0u, 0x1010), __byte_perm(u0, 0u, 0x3232), __byte_perm(u1, 0u, 0x3232)};
  keep(ma);
  wg_fence();
  wgmma_rs_n192<1>(a, ma[0], ma[1], ma[2], ma[3], mkd<2>(cd), 1);
  wg_commit();
}

template<bool FIRST> DEVI void qkv_block(float (&aX)[96], float (&aY)[96], uint32_t sb16, int s, int tX, int tY) {
  uint32_t a16 = sb16 + (qa_off(s) >> 4), b16 = (sb16 + (qb_off(s) >> 4)) | ((8192u >> 4) << 16);
  uint32_t ax = (a16 + tX * 512) | 0x10000u, ay = (a16 + tY * 512) | 0x10000u;
  wg_fence();
  #pragma unroll
  for (int ks = 0; ks < 4; ks++) {
    wgmma_ss_n192<1>(aX, mkd<HI128>(ax + ks * 2), mkd<HI128>(b16 + ks * 128), !(FIRST && ks == 0));
    wgmma_ss_n192<1>(aY, mkd<HI128>(ay + ks * 2), mkd<HI128>(b16 + ks * 128), !(FIRST && ks == 0));
  }
  wg_commit();
}
DEVI void qkv_half(float (&a)[96], uint32_t sb16, int t, uint32_t sa, uint32_t sbb) {
  wg_fence();
  #pragma unroll
  for (int ks = 0; ks < 4; ks++)
    wgmma_ss_n192<1>(a, mkd<HI128>(((sb16 + (sa >> 4) + t * 512) | 0x10000u) + ks * 2), mkd<HI128>(((sb16 + (sbb >> 4)) | ((8192u >> 4) << 16)) + ks * 128), 1);
  wg_commit();
}
DEVI void wo_block(float (&acc)[64], uint32_t sb16, int s, int wg) {
  uint32_t a16 = (sb16 + (w_off(s) >> 4) + wg * 256) | 0x10000u, b16 = (sb16 + (w_off(s) >> 4) + 1024) | ((8192u >> 4) << 16);
  wg_fence();
  #pragma unroll
  for (int ks = 0; ks < 4; ks++)
    wgmma_ss_n128<1>(acc, mkd<HI64>(a16 + (ks >> 1) * 512 + (ks & 1) * 2), mkd<HI128>(b16 + ks * 128), 1);
  wg_commit();
}
DEVI void consumer(const Params& P, uint32_t sb, int wg) {
  const int w = uni((threadIdx.x >> 5) & 3);
  #define LAYER uni(mbar_test(BAR(B_XRDY + wg * 2 + 1), 0))
  #define IDS L = LAYER; const int tid = fresh_tid(), lane = tid & 31
  const uint32_t ids = uni(P.map[blockIdx.x]);
  const int bi = (ids >> 4) & 7, rh = ids & 1, bc = (ids & 15) >> 1, fid = ids >> 8;
  const int tX = 3 - wg, tY = wg;
  constexpr uint32_t sb16 = 1024 >> 4;
  #pragma unroll 1
  while (true) {
    int L = LAYER;
    {
      float aX[96], aY[96];
      const bool lead = fresh_tid() == 0;
      mbar_wait(BAR(B_FULLQ), 0);
      PROFW(threadIdx.x == 0, L * 8 + 1);
      qkv_block<true>(aX, aY, sb16, 0, tX, tY);
      #pragma unroll 1
      for (int n = 1, s = 1, ps = 0, ph = 0; n < 14; n++) {
        mbar_wait(BAR(B_FULLQ + s), ph ^ (s ? L : 0));
        PROFD(threadIdx.x == 0 && L && (n == 2 || n == 3 || n == 7 || n == 11 || n == 13), n == 2 ? 48 : 49 + (n >> 2));
        qkv_block<false>(aX, aY, sb16, s, tX, tY);
        wg_wait<1>(); if (lead) mbar_arrive(BAR(B_EMPTYQ + ps));
        ps = s; if (s == 2) { s = 0; ph ^= 1; } else s++;
      }
      mbar_wait(BAR(B_FULLQ + 2), L);
      qkv_half(aX, sb16, tX, SA2, SB2);
      mbar_wait(BAR(B_ROW), L);
      IDS;
      const uint32_t pa = sb + PAR + (w * 16 + (lane >> 2)) * 8;
      float2 p0 = lds64f(pa + tX * 512), p1 = lds64f(pa + tX * 512 + 64), p2 = lds64f(pa + tY * 512), p3 = lds64f(pa + tY * 512 + 64);
      mean_step(aX, p0.y, p1.y, sb16 + (CS >> 4), lane & 3);
      mbar_wait(BAR(B_FULLQ), 1);
      qkv_half(aX, sb16, tX, 0, SB0);
      wg_wait<3>(); if (lead) mbar_arrive(BAR(B_EMPTYQ + 1));
      bar_sync(1, 256);
      qkv_half(aY, sb16, tY, SA2, SB2);
      wg_wait<1>(); keep(aX);
      const int srow = w * 16 + (lane & 15);
      const uint32_t x0 = sb + srow * 64 + (((lane >> 4) ^ ((srow >> 1) & 3)) << 4), xX = x0 + (4 + tX) * 8192, xY = x0 + (4 + tY) * 8192;
      qkv_store<8>(aX, p0.x, p1.x, xX + KVA); qkv_store<16>(aX, p0.x, p1.x, xX + KVA + 4096);
      warp_signal(BAR(B_KVRDY + wg * 2));
      qkv_half(aY, sb16, tY, 0, SB0);
      mean_step(aY, p2.y, p3.y, sb16 + (CS >> 4), fresh_tid() & 3);
      wg_wait<2>(); if (lead) mbar_arrive(BAR(B_EMPTYQ + 2));
      mbar_wait(BAR(B_EMPTYQ + 2), L);
      qkv_store<12>(aX, p0.x, p1.x, xX + KVB); qkv_store<20>(aX, p0.x, p1.x, xX + KVB + 4096);
      wg_wait<0>(); keep(aY);
      if (lead) mbar_arrive(BAR(B_EMPTYQ));
      PROFW(threadIdx.x == 0, L * 8 + 2);
      qkv_store<8>(aY, p2.x, p3.x, xY + KVA); qkv_store<16>(aY, p2.x, p3.x, xY + KVA + 4096);
      qkv_store<12>(aY, p2.x, p3.x, xY + KVB); qkv_store<20>(aY, p2.x, p3.x, xY + KVB + 4096);
      warp_signal(BAR(B_KVRDY + wg * 2 + 1));
      p0.x *= QSCALE; p1.x *= QSCALE; p2.x *= QSCALE; p3.x *= QSCALE;
      mbar_wait(BAR(B_EMPTYQ), 1);
      qkv_store<0>(aX, p0.x, p1.x, x0 + QO + tX * 4096);
      qkv_store<0>(aY, p2.x, p3.x, x0 + QO + tY * 4096); qkv_store<4>(aY, p2.x, p3.x, x0 + QO + 16384 + tY * 4096);
      mbar_wait(BAR(B_PAR), L);
      qkv_store<4>(aX, p0.x, p1.x, x0 + QO + 16384 + tX * 4096);
      const int prow = (int)uni(lds32(sb + INFO)) - bi * 256;
      if ((prow >> 4) == tX * 4 + w || (prow >> 4) == tY * 4 + w) {
        __syncwarp();
        if (lane < 24) sts128(sb + (prow & 63) * 64 + (((lane ^ (prow >> 1)) & 3) << 4) +
                              (lane < 8 ? QO + (lane >> 2) * 16384 + (prow >> 6) * 4096 : ((lane & 4) ? KVB : KVA) + (4 + (prow >> 6)) * 8192 + (lane >> 4) * 4096),
                              lds128(sb + PATCH + lane * 16));
      }
      fence_async_smem();
      bar_sync(1, 256);
    }
    PROFW(threadIdx.x == 0, L * 8 + 3);
    float2 fa, fb;
    { const float2* f = (const float2*)&P.g->statF[bi * 256 + rh * 128 + (wg ^ rh) * 64 + w * 16 + ((fresh_tid() & 31) >> 2)];
      fa = __ldcg(f); fb = __ldcg(f + 16); }
    {
      IDS;
      float s0[32], s1[32], sx[32], o[20], op[20];
      uint32_t p0[16], p1[16], px[16], msk[9];
      const int tdiag = w * 16 + (lane >> 2) - 2 * (lane & 3);
      #pragma unroll
      for (int e = 0; e < 9; e++) msk[e] = ((8 * e - 8 > tdiag) ? 0xFFFFu : 0u) | ((8 * e - 7 > tdiag) ? 0xFFFF0000u : 0u);
      keep(msk);
      const uint32_t ones = (sb16 + (ONES >> 4)) << 16;
      const uint32_t qX = (sb16 + (QO >> 4) + tX * 256) | 0x10000u, qY = (sb16 + (QO >> 4) + tY * 256) | 0x10000u;
      const uint32_t kXB = (sb16 + (KVB >> 4) + tX * 512) | 0x10000u;
      uint32_t redo = 0;
      const uint32_t ost = sb + QO + (w * 16 + (lane & 15)) * 64 + (((lane >> 4) ^ ((lane >> 1) & 3)) << 4);
      #define QK(s, q, k) do { wg_fence(); qk_issue(s, q, k); wg_commit(); } while (0)
      #define QK2(q, k) do { wg_fence(); qk_issue(s1, q, k); qk_issue(sx, q, (k) + 2048); wg_commit(); } while (0)
      #define VB(v, b) ((v) + VOFF((b) * 512))
      QK(s0, qX + 1024, kXB + 1536);
      #pragma unroll
      for (int e = 0; e < 20; e++) o[e] = 0.f;
      wg_wait<0>(); keep(s0);
      #pragma unroll 1
      for (int h = 1; h >= 0; h--) {
        const uint32_t kXA = kXB - ((KVB - KVA) >> 4), kX = h ? kXB : kXA, vX = VOFF((kX & 0xffffu) + 256) + ones;
        QK(s1, qX + h * 1024, kX + 1024);
        #pragma unroll
        for (int e = 0; e < 20; e++) op[e] = o[e];
        keep(op);
        exp_pv<0, 4>(s0, p0, o, VB(vX, 3), false); wg_commit();
        wg_wait<1>(); keep(s1);
        exp_pv<0, 2>(s1, p1, o, VB(vX, 2), true);
        bar_sync(h ? 12 + wg : 4 + wg * 4, h ? 128 : 160);
        QK(s0, qX, kXA + 512 + h * 1024);
        exp_pv<2, 4>(s1, p1, o, VB(vX, 2), true); wg_commit();
        wg_wait<0>(); keep(s0); keep(p0); keep(p1); keep(o);
      }
      #pragma unroll 1
      for (int h = 0; h < 2; h++) {
        const uint32_t kb16 = sb16 + ((h ? KVB : KVA) >> 4), kY = (kb16 + tY * 512) | 0x10000u, qy = qY + h * 1024;
        const uint32_t onesP = bi ? ones : (kb16 + 1984) << 16;
        const uint32_t vX = VOFF(kb16 + tX * 512 + 256), vY = VOFF(kb16 + tY * 512 + 256);
        uint32_t ob[8];
        QK2(qX + h * 1024, (kb16 + tX * 512) | 0x10000u);
        exp_pv<0, 4>(s0, p0, o, VB(vX + (wg ? onesP : ones), 1), true); wg_commit();
        wg_wait<1>(); keep(s1); keep(sx);
        QK(s0, qy, kY + 1536);
        exp_pv2(s1, sx, p1, px, o, vX + onesP, VB(vX + ones, 4), msk, tdiag); wg_commit();
        wg_wait<1>(); keep(s0); keep(p0);
        QK(s1, qy, kY + 1024);
        exp_pack<0, 4>(s0, p0);
        wg_wait<1>(); keep(o); keep(p1); keep(px);
        bool ok = attn_pack(o, ob); keep(ob);
        exp_pv<0, 4, 1>(s0, p0, o, VB(vY + (wg ? ones : onesP), 3), false); wg_commit();
        attn_store(ob, ok, ost + (h * 4 + tX) * 4096, sb, BAR(B_ORDY + wg * 4 + h * 2)); redo |= ok ? 0u : 1u << (h * 2);
        wg_wait<1>(); keep(s1);
        exp_pv<0, 2>(s1, p1, o, VB(vY + onesP, 2), true);
        bar_sync(5 + wg * 4 + h * 2, 160);
        QK(s0, qy, kY + 512);
        exp_pv<2, 4>(s1, p1, o, VB(vY + onesP, 2), true); wg_commit();
        wg_wait<1>(); keep(s0); keep(p0);
        QK2(qy, kY);
        exp_pv<0, 4>(s0, p0, o, VB(vY + onesP, 1), true); wg_commit();
        wg_wait<1>(); keep(s1); keep(sx); keep(p1);
        bar_sync(6 + wg * 4, h ? 128 : 160);
        QK(s0, h ? qy : qX + 1024, kXB + 512);
        exp_pv2(s1, sx, p1, px, o, vY + onesP, VB(vY + ones, 4), msk, tdiag); wg_commit();
        wg_wait<0>(); keep(o); keep(s0); keep(p0); keep(p1); keep(px);
        ok = attn_pack(o, ob); attn_store(ob, ok, ost + (h * 4 + tY) * 4096, sb, BAR(B_ORDY + wg * 4 + h * 2 + 1)); redo |= ok ? 0u : 2u << (h * 2);
        #pragma unroll
        for (int e = 0; e < 20; e++) o[e] = op[e];
      }
      #undef QK
      #undef QK2
      #undef VB
      if (redo) {
        #pragma unroll 1
        for (int u = 0; u < 4; u++) if ((redo >> u) & 1) {
          const int h = u >> 1, t = (u & 1) ? tY : tX;
          attn_exact(sb + QO + (h * 4 + t) * 4096, sb + (h ? KVB : KVA), t, bi > 0, BAR(B_ORDY + wg * 4 + u));
        }
      }
    }
    PROFW(threadIdx.x == 0, L * 8 + 4);
    {
      IDS;
      const int t256 = wg * 128 + tid;
      float acc[64];
      const int tt = wg ^ rh;
      const int grow = bi * 256 + rh * 128 + tt * 64 + w * 16 + (lane >> 2);
      float al0 = 1.f, be0 = 0.f, al1 = 1.f, be1 = 0.f;
      const int idx0 = (int)uni(lds32(sb + INFO));
      const uint32_t tag = lds32(sb + INFO + 8) + L;
      uint4* const sp = &P.g->statP[bc][grow + (lane & 1) * 8];
      uint4* const yp = &P.g->yP[t256 >> 1][min(fid, 111)][t256 & 1];
      if (L) {
        float r0 = rsqrtf(fa.y + LN_EPS), r1 = rsqrtf(fb.y + LN_EPS);
        if (grow != idx0) { al0 = 1.f + r0; be0 = -fa.x * r0; }
        if (grow + 8 != idx0) { al1 = 1.f + r1; be1 = -fb.x * r1; }
      }
      const int srow = tt * 64 + w * 16 + (lane & 15);
      const uint32_t ra = sb + srow * 128 + (((lane >> 4) ^ (srow & 7)) << 4);
      mbar_wait(BAR(B_FULLW + 5), L);
      if ((idx0 >> 4) == bi * 16 + rh * 8 + tt * 4 + w) {
        int r = idx0 & 127;
        if (lane < 16) sts128(sb + 32768 + (lane >> 3) * 16384 + r * 128 + (((lane & 7) ^ (r & 7)) << 4), lds128(sb + X2SEG + lane * 16));
        fence_async_smem();
        __syncwarp();
      }
      #pragma unroll
      for (int jj = 0; jj < 8; jj++) {
        uint32_t r[4]; ldsm_x4((ra + 32768 + (jj >> 2) * 16384) ^ ((jj & 3) << 5), r[0], r[1], r[2], r[3]);
        #pragma unroll
        for (int e = 0; e < 4; e++) {
          acc[8 * jj + 2 * e] = fmaf(bf_lo(r[e]), (e & 1) ? al1 : al0, (e & 1) ? be1 : be0);
          acc[8 * jj + 2 * e + 1] = fmaf(bf_hi(r[e]), (e & 1) ? al1 : al0, (e & 1) ? be1 : be0);
        }
      }
      keep(acc);
      bar_sync(12 + wg, 128);
      if (!(lane & 2)) st_ll(sp, 0u, 0u, 0u, 0u);
      uint2 wd[4];
      #pragma unroll
      for (int e = 0; e < 4; e++) { wd[e] = make_uint2(0u, 0u); if (L) wd[e] = ldg_stream((const uint2*)(WDSRC) + t256 + (28 + e) * 256); }
      PROFW(t256 == 0, L * 8 + 5);
      #pragma unroll 1
      for (int n = 0, q = 0, pq = 5; n < 16; n++) {
        mbar_wait(BAR(B_FULLW + q), w_par(n, q, L));
        PROFD(t256 == 0 && !L && (n == 4 || n == 7 || n == 8 || n == 12), (n == 7 ? 63 : 41 + (n >> 2)));
        wo_block(acc, sb16, q, tt);
        wg_wait<1>(); if (tid == 0) mbar_arrive(BAR(B_EMPTYW + pq));
        pq = q; q = w_next(n, q);
      }
      mbar_wait(BAR(B_EMPTYW + 5), L);
      wg_wait<0>(); keep(acc);
      if (tid == 0) mbar_arrive(BAR(B_EMPTYW + 4));
      PROFW(t256 == 0, L * 8 + 6);
      const uint32_t xa = ra + rh * 16384;
      #pragma unroll
      for (int jj = 0; jj < 8; jj++) {
        const float* a = acc + 8 * jj;
        stsm_x4((xa + (jj >> 2) * 32768) ^ ((jj & 3) << 5), pack_bf16(a[0], a[1]), pack_bf16(a[2], a[3]), pack_bf16(a[4], a[5]), pack_bf16(a[6], a[7]));
        if (jj == 7) fence_async_smem();
        if ((jj & 3) == 3) warp_signal(BAR(B_XRDY + wg * 2 + (jj >> 2)));
      }
      {
        float s1a = 0.f, s2a = 0.f, da = 0.f, s1b = 0.f, s2b = 0.f, db = 0.f;
        #pragma unroll
        for (int j = 0; j < 16; j++) {
          const float* a = acc + 4 * j; float2 wv = lds64f(sb + WR + j * 32 + (lane & 3) * 8);
          s1a += a[0] + a[1]; s1b += a[2] + a[3];
          s2a = fmaf(a[0], a[0], s2a); s2b = fmaf(a[2], a[2], s2b); s2a = fmaf(a[1], a[1], s2a); s2b = fmaf(a[3], a[3], s2b);
          da = fmaf(a[0], wv.x, da); db = fmaf(a[2], wv.x, db); da = fmaf(a[1], wv.y, da); db = fmaf(a[3], wv.y, db);
        }
        bool odd = lane & 1;
        float u1 = (odd ? s1b : s1a) + __shfl_xor_sync(0xffffffffu, odd ? s1a : s1b, 1);
        float u2 = (odd ? s2b : s2a) + __shfl_xor_sync(0xffffffffu, odd ? s2a : s2b, 1);
        float u3 = (odd ? db : da) + __shfl_xor_sync(0xffffffffu, odd ? da : db, 1);
        u1 += __shfl_xor_sync(0xffffffffu, u1, 2); u2 += __shfl_xor_sync(0xffffffffu, u2, 2); u3 += __shfl_xor_sync(0xffffffffu, u3, 2);
        if (!(lane & 2)) st_ll(sp, __float_as_uint(u1), __float_as_uint(u2), __float_as_uint(u3), tag);
      }
      PROFW(t256 == 0, L * 8 + 7);
      if (L) {
        mbar_wait(BAR(B_PAR), 0);
        { float2 pa = lds64f(sb + PAR + (grow & 127) * 8), pb = lds64f(sb + PAR + (grow & 127) * 8 + 64); al0 = pa.x; be0 = pa.y; al1 = pb.x; be1 = pb.y; }
        uint32_t rs[32];
        #pragma unroll
        for (int j = 0; j < 16; j++) {
          rs[2 * j] = pack_bf16(fmaf(acc[4 * j], al0, be0), fmaf(acc[4 * j + 1], al0, be0));
          rs[2 * j + 1] = pack_bf16(fmaf(acc[4 * j + 2], al1, be1), fmaf(acc[4 * j + 3], al1, be1));
        }
        #pragma unroll
        for (int jj = 0; jj < 8; jj++) stsm_x4((xa + (jj >> 2) * 32768) ^ ((jj & 3) << 5), rs[4 * jj], rs[4 * jj + 1], rs[4 * jj + 2], rs[4 * jj + 3]);
        PROFW(t256 == 0, 16);
        if (fid >= 112) bar_arrive(3, 384);
        else {
          float d[4] = {0.f, 0.f, 0.f, 0.f};
          mbar_wait(BAR(B_FULLW + wg * 3), 0); mbar_wait(BAR(B_FULLW + wg * 3 + 1), 0);
          bar_sync(3, 384);
          PROFW(t256 == 0, 29);
          #pragma unroll 1
          for (int g = 0; g < 4; g++) {
            const uint32_t ad = (sb16 + (wg ? 6144 : 10240) + (g >> 1) * 2048 + (g & 1) * 512) | (1024u << 16), bd = (sb16 + (HV >> 4) + wg * 64 + g * 16) | 0x10000u;
            wg_fence();
            #pragma unroll
            for (int ks = 0; ks < 8; ks++) wgmma_ss_n8<0, 1>(d, mkd<HI64>(ad + ks * 64), mkd<8>(bd + ks * 2), 1);
            wg_commit();
          }
          mbar_wait(BAR(B_FULLW + 2), 0);
          wg_wait<0>(); keep(d);
          if (!(lane & 3)) { sts32f(sb + PAR + 1024 + wg * 256 + w * 64 + lane, d[0]); sts32f(sb + PAR + 1056 + wg * 256 + w * 64 + lane, d[2]); }
          bar_sync(1, 256);
          const uint32_t ga = sb + PAR + 1024 + lane * 4, aa = sb + HV + (t256 >> 5) * 128;
          sts32f(aa + lane * 4, swiglu(lds32f(ga) + lds32f(ga + 256), lds32f(ga + 128) + lds32f(ga + 384)));
          __syncwarp();
          PROFW(t256 == 0, 26);
          float y0 = 0.f, y1 = 0.f, y2 = 0.f, y3 = 0.f;
          uint32_t tbl = rh ? 0x001459a8u : 0x023679a8u;
          uint4 a4 = lds128(aa + 112);
          #pragma unroll 2
          for (int n = 0; n < 8; n++, tbl >>= 4) {
            const uint32_t src = sb + t256 * 8 + (tbl & 15) * 8192;
            const uint4 an = lds128(aa + ((0x00123564u >> (4 * n)) & 15) * 16);
            #pragma unroll
            for (int e = 0; e < 4; e++) {
              const float av = __uint_as_float(e == 0 ? a4.x : (e == 1 ? a4.y : (e == 2 ? a4.z : a4.w)));
              y0 = fmaf(bf_lo(wd[e].x), av, y0); y1 = fmaf(bf_hi(wd[e].x), av, y1); y2 = fmaf(bf_lo(wd[e].y), av, y2); y3 = fmaf(bf_hi(wd[e].y), av, y3);
              const float2 v = lds64f(src + e * 2048); wd[e] = make_uint2(__float_as_uint(v.x), __float_as_uint(v.y));
            }
            a4 = an;
          }
          st_ll(yp, __float_as_uint(y0), __float_as_uint(y1), __float_as_uint(y2), (__float_as_uint(y3) & ~255u) | (lds32(sb + INFO + 12) + 1));
          PROFW(t256 == 0, 27);
        }
        return;
      }
      mbar_wait(BAR(B_XRDY + wg * 2 + 1), 0);
    }
  }
  #undef IDS
  #undef LAYER
}

DEVI void loader(const Params& P, uint32_t sb) {
  const int lane = threadIdx.x & 31;
  const int bid = uni(BID), bi = bid >> 4, bp = bid & 15, rh = bp & 1, bc = bp >> 1;
  uint32_t phq = 0, tag = 0;
  #pragma unroll 1
  for (int L = 0; L < 2; L++) {
    int s = 0;
    uint32_t rdy = 0;
    #pragma unroll 1
    for (int n = L ? 0 : 3; n < 16; n++) {
      int kb = L ? kb_order(bc, n) : n;
      mbar_wait(BAR(B_EMPTYQ + s), (phq >> s) & 1);
      phq ^= 1u << s;
      if (L && n == 1) { mbar_wait(BAR(B_XRDY + 1), 0); mbar_wait(BAR(B_XRDY + 3), 0); }
      if (lane == 0) {
        mbar_expect_tx(BAR(B_FULLQ + s), L && n < 2 ? 40960 : 57344);
        tma_3d_h(sb + qb_off(s), &P.mWq, bp * 64, kb * 64, 0, BAR(B_FULLQ + s), L && n >= QEF_N ? POL_FIRST : POL_NORMAL);
        if (!L) tma_2d(sb + qa_off(s), &P.mX, kb * 64, bi * 256, BAR(B_FULLQ + s));
      }
      if (L && n >= 2) {
        if (((rdy >> (2 * kb)) & 3) != 3) {
          do { rdy = __ballot_sync(0xffffffffu, ld_rlx(&P.g->flagX[bi][lane]) == tag); } while (((rdy >> (2 * kb)) & 3) != 3);
          fence_async_glob();
        }
        if (n == 3 || n == 4) mbar_wait(BAR(B_XFREE + n - 3), 0);
        if (lane == 0) bulk_g2s_h(sb + qa_off(s), P.g->x[bi][kb], 32768, BAR(B_FULLQ + s), POL_X);
      }
      PROFY(L && lane == 0 && (n == 2 || n == 3 || n == 9), n == 9 ? 60 : 56 + n);
      if (L && n == 2) { mbar_wait(BAR(B_FULLQ), 0); mbar_wait(BAR(B_FULLQ + 1), 1); if (lane < 2) mbar_arrive_peer(BAR(B_XFREE + lane)); }
      s = (s == 2) ? 0 : s + 1;
    }
    for (int q = 0; q < 3; q++) mbar_wait(BAR(B_EMPTYQ + q), (phq >> q) & 1);
    tag = lds32(sb + INFO + 8) + L;
    #pragma unroll 1
    for (int q = 0; q < 4; q++) {
            if (bi) {
        const unsigned* f = &P.g->flagKV[bid - 16][q];
        while (ld_rlx(f) != tag);
        fence_async_glob();
      }
      if (lane == 0) {
        mbar_expect_tx(BAR(B_KVFULL + q), 16384);
        bulk_g2s_h(sb + ((q >> 1) ? KVB : KVA) + ((q & 1) ? 0 : 16384), bi ? P.g->kv[bid - 16][q] : P.g->zero, 16384, BAR(B_KVFULL + q));
      }
      PROFY(!L && lane == 0 && bi && q != 2, 34 + (q + 1) / 2);
    }
    mbar_wait(BAR(B_ORDY), L);
    {
      const uint4* src = P.g->o[bi][0][0][rh];
      rdy = 0;
      #pragma unroll 1
      for (int n = 0, q = 0; n < 16; q = w_next(n, q), n++) {
        const int j = wo_order(bc, n);
        if (((rdy >> (2 * j)) & 3) != 3) {
          do { rdy = __ballot_sync(0xffffffffu, ld_rlx(&P.g->flagO[bi][lane]) == tag); } while (((rdy >> (2 * j)) & 3) != 3);
          fence_async_glob();
        }
        if (n >= 2) mbar_wait(n < 5 ? BAR(B_HAFREE + (n > 2)) : BAR(B_EMPTYW + q), n < 5 ? L : w_par(n, q, L) ^ 1);
        if (n == THR_N) mbar_wait(BAR(B_OFREE), L);
        if (lane == 0) { mbar_expect_tx(BAR(B_FULLW + q), 16384); bulk_g2s_h(sb + w_off(q), src + j * 2048, 16384, BAR(B_FULLW + q)); }
      }
    }
    mbar_wait(BAR(B_OFREE), L);
  }
}

DEVI void ffn_prefetch(const Params& P, int q) {
  bulk_prefetch(q < 16 ? ((q & 1) ? P.wu : P.wg) + ((q >> 1) * 128 + blockIdx.x) * 3584 : P.wd + (min(FID, 111) * 8 + q - 16) * 4096, q < 16 ? 7168 : 8192);
}
DEVI void storer(const Params& P, uint32_t sb, int wg) {
  const int bid = uni(BID), bi = bid >> 4, rh = bid & 1, bc = (bid & 15) >> 1;
  const bool one = (threadIdx.x & 31) == 0;
  char* const g = (char*)P.g;
  const uint32_t tag0 = uni(((ld_rlx(&P.g->epoch) % 16383u) + 1u) << 2);
  #pragma unroll 1
  for (int L = 0; L < 2; L++) {
    const uint32_t tag = tag0 + L;
    if (wg) {
      #pragma unroll 1
      for (int r = threadIdx.x & 31; r < 256; r += 32) {
        uint4 v;
        do v = ld_ll(&P.g->statF[bi * 256 + r]); while (!__all_sync(0xffffffffu, v.w == tag));
        float var = __uint_as_float(v.y), c = rsqrtf(var + LN_EPS);
        if (L) { c += 1.f; c *= rsqrtf(fmaf(var * c, c, LN_EPS)); }
        const float mh = bf_round(__uint_as_float(v.x));
        sts64f(sb + PAR + r * 8, c, __uint_as_float(pack_bf16(mh, __uint_as_float(v.x) - mh)));
      }
      if (!L) mbar_wait(BAR(B_PAR), 0);
      warp_signal(BAR(B_ROW));
    }
    #pragma unroll 1
    for (int u = 0; u < 2 + 4 * wg; u++) {
      const int h = u < 2 ? u : u >> 2, hi = (u & 1) ^ 1;
      uint32_t src, dst, fl, b0, b1;
      if (u < 2) {
        src = (h ? KVB : KVA) + (3 - wg) * 16384; dst = offsetof(Scratch, kv) + (bid * 4 + h * 2 + wg) * 16384; fl = offsetof(Scratch, flagKV) + (bid * 32 + h * 2 + wg) * 4;
        b0 = BAR(B_KVRDY + ((u | wg) ? 1 : 0)); b1 = b0 + 16;
      } else {
        src = QO + (h * 2 + hi) * 8192; dst = offsetof(Scratch, o) + ((((bi * 2 + h) * 8 + bc) * 2 + hi) * 2 + rh) * 8192;
        fl = offsetof(Scratch, flagO) + (bi * 32 + h * 16 + (bid & 15)) * 4;
        b0 = BAR(B_ORDY + u - 2); b1 = b0 + 32;
      }
      mbar_wait(b0, L); mbar_wait(b1, L);
      if (u + wg == 1) {
        mbar_wait(BAR(B_PAR), L);
        const uint32_t t0 = clk(), dt = (wg ? KV_D1 : KV_D2) + (L ? KV_DL : 0); while (clk() - t0 < dt) __nanosleep(40);
      }
      fence_async_smem();
      PROFY(one && !L && u == 3 * wg, u ? 46 : 8);
      if (one && (u >= 2 || bi < 7)) bulk_s2g(g + dst, sb + src, u < 2 ? 16384 : 8192);
      if (one && u == 5) mbar_arrive(BAR(B_HAFREE + 1));
      if (u == 2 || u == 4) continue;
      bulk_wait<0>();
      PROFY(one && !L && u == 3 * wg, u ? 61 : 62);
      fence_rel();
      if (one) { st_rlx((unsigned*)(g + fl), tag); if (!wg || u > 2) mbar_arrive(BAR(B_HAFREE + h + (wg & h))); }
      PROFY(one && !L && (u > 2 || u == wg), u > 2 ? (u == 3 ? 38 : 54) : 32 + u);
    }
    if (L == 0) {
      char* dst = g + (offsetof(Scratch, x) + (bi * 16 + 2 * bc) * 32768 + rh * 16384);
      unsigned* f = (unsigned*)(g + (offsetof(Scratch, flagX) + (bi * 32 + bc * 4 + rh) * 4));
      const uint32_t a = sb + rh * 16384;
      if (wg == 0) {
        mbar_wait(BAR(B_XRDY), 0); mbar_wait(BAR(B_XRDY + 2), 0);
        fence_async_smem();
        PROFY(one, 41);
        if (one) bulk_s2g(dst, a, 16384);
        bulk_wait<0>();
        PROFY(one, 45);
        if (one) { mbar_arrive(BAR(B_XFREE)); mbar_arrive(BAR(B_PFREE)); }
        fence_rel();
        mbar_wait(BAR(B_XRDY + 1), 0); mbar_wait(BAR(B_XRDY + 3), 0);
        if (one) { st_rlx(f, tag); bulk_s2g(dst + 32768, a + 32768, 16384); }
        PROFY(one, 56);
        bulk_wait<0>();
        if (one) mbar_arrive(BAR(B_XFREE + 1));
        fence_rel();
        if (one) st_rlx(f + 2, tag);
        PROFY(one, 57);
      } else {
        mbar_wait(BAR(B_XRDY + 1), 0); mbar_wait(BAR(B_XRDY + 3), 0);
        mbar_wait(BAR(B_PFREE), 0);
        if (one) bulk_s2peer(a, 16384, BAR(B_FULLQ));
        { const uint32_t t0 = clk(); while (clk() - t0 < XD_D); }
        if (one) bulk_s2peer(a + 32768, 16384, BAR(B_FULLQ + 1));
      }
      if (wg == 0) {
        uint32_t t0 = clk() + PF1_D;
        #pragma unroll 1
        for (int q = PF1_S; q < PF1_E; q++) { while ((int)(clk() - t0) < 0) __nanosleep(50); if (one) ffn_prefetch(P, q); t0 += PF1_T; }
      }
    }
  }
}

DEVI void stg_issue(const Params& P, int c, uint32_t d, uint32_t du, uint32_t b) {
  mbar_expect_tx(b, 16384);
  if (c < 8) { tma_2d_h(d, &P.mWg, FID * 32, c * 128, b, POL_G); tma_2d_h(d + du, &P.mWu, FID * 32, c * 128, b, POL_U); }
  else if (c < 12) tma_3d_h(d, &P.mWd, 0, FID * 32 + (c - 8) * 8, 0, b, POL_D);
  else tma_2d_h(d, &P.mWp, (c - 12) * 1024 + (BID >> 2) * 32, (BID & 3) * 256, b, POL_EF);
}
DEVI void pace() { const uint32_t t0 = clk(); while (clk() - t0 < PACE_T); }
DEVI void stager(const Params& P, uint32_t sb) {
  {
    const int b = blockIdx.x;
    uint32_t t0 = clk();
    #pragma unroll 1
    for (int q = 0; q < PQ_N; q++) { bulk_prefetch(P.wqkv + (q * 128 + b) * 3072, 6144); while (clk() - t0 < PQ_T) __nanosleep(50); t0 += PQ_T; }
    bulk_prefetch(P.wo + b * 8192, 16384);
    #pragma unroll 1
    for (int q = 0; q < PF0_N; q++) {
      while (clk() - t0 < PF0_T) __nanosleep(50);
      t0 += PF0_T;
      ffn_prefetch(P, q);
    }
  }
  const int bid = BID, bi = bid >> 4, rh = bid & 1, bc = (bid & 15) >> 1;
  #pragma unroll 1
  for (int L = 0; L < 2; L++) {
    const int nch = L ? (FID < 112 ? 8 : 0) : 15;
    mbar_wait(BAR(B_PAR), L); mbar_wait(BAR(B_KVFULL + W0_BAR), L);
    #pragma unroll 1
    for (int n = 0, q = 0; n < 16; q = w_next(n, q), n++) {
      if (n >= 2) mbar_wait(n < 5 ? BAR(B_HAFREE + (n > 2)) : BAR(B_EMPTYW + q), n < 5 ? L : w_par(n, q, L) ^ 1);
      if (n == THR_N) mbar_wait(BAR(B_OFREE), L);
      mbar_expect_tx(BAR(B_FULLW + q), 16384);
      tma_5d(sb + w_off(q) + 16384, &P.mWo, 0, 0, n >> 3, 2 * (wo_order(bc, n) & 7), 2 * bc, BAR(B_FULLW + q), L ? POL_EF : POL_NORMAL);
      if (n == 2) {
        #pragma unroll 1
        for (int e = 0; e < 2; e++) {
          mbar_expect_tx(BAR(B_FULLW + 5), 16384);
          if (L) bulk_g2s_h(sb + 32768 + e * 16384, P.g->x[bi][2 * bc + e] + rh * 1024, 16384, BAR(B_FULLW + 5));
          else tma_2d_h(sb + 32768 + e * 16384, &P.mXh, bc * 128 + e * 64, bi * 256 + rh * 128, BAR(B_FULLW + 5), POL_EF);
        }
      }
    }
    mbar_wait(BAR(B_EMPTYW + 5), L);
    if (L && nch) {
      const bf16* src = WDSRC2;
      mbar_expect_tx(BAR(B_FULLW + 2), 32768); mbar_expect_tx(BAR(B_FULLW + 2), 24576);
      #pragma unroll 1
      for (int e = 0; e < 3; e++) { bulk_g2s_h(sb + e * 32768 + (e < 2 ? (rh ^ 1) * 16384 : 0), src + e * 8192, e < 2 ? 16384 : 24576, BAR(B_FULLW + 2)); pace(); }
    }
        if (L == 0) { mbar_arrive_peer(BAR(B_PFREE)); mbar_wait(BAR(B_EMPTYW), 0); mbar_wait(BAR(B_EMPTYW + 1), 0); }
    #pragma unroll 1
    for (int c = FID < 112 ? 0 : 12, slot = 0; c < nch; c++, slot = slot == 2 ? 0 : slot + 1) {
      const int q = (c >> 1) + (c >> 2);
      if (!L && (c == LATE_C || c == 12)) mbar_wait(BAR(LATE_B), LATE_P);
      mbar_wait(L ? BAR(B_EMPTYW + q) : BAR(B_STGE + slot), L | ((0x71c7 >> c) & 1));
      #define CC c
      stg_issue(P, CC, L ? sb + w_off(q) + (c & 1) * 8192 : sb + STG + slot * 16384, 8192 << L, L ? BAR(B_FULLW + q) : BAR(B_STG + slot));
      if (L) pace();
    }
  }
}
DEVI void sum8(uint4 v, float& s1, float& s2) {
  float e[8] = {bf_lo(v.x), bf_hi(v.x), bf_lo(v.y), bf_hi(v.y), bf_lo(v.z), bf_hi(v.z), bf_lo(v.w), bf_hi(v.w)};
  #pragma unroll
  for (int q = 0; q < 8; q++) { s1 += e[q]; s2 = fmaf(e[q], e[q], s2); }
}
DEVI uint4 norm8(uint4 x, float m, float rs) {
  #define HN(v) pack_bf16((bf_lo(v) - m) * rs, (bf_hi(v) - m) * rs)
  return make_uint4(HN(x.x), HN(x.y), HN(x.z), HN(x.w));
  #undef HN
}
DEVI void put_f32(uint4 b, uint32_t d, uint32_t d2) {
  sts128(d, make_uint4(b.x << 16, b.x & 0xffff0000u, b.y << 16, b.y & 0xffff0000u));
  sts128(d + d2, make_uint4(b.z << 16, b.z & 0xffff0000u, b.w << 16, b.w & 0xffff0000u));
}
DEVI void put_bf16(uint4 b, uint32_t d) {
  sts64f(d, __uint_as_float(b.x), __uint_as_float(b.y)); sts64f(d + 1024, __uint_as_float(b.z), __uint_as_float(b.w));
  fence_async_smem();
}
DEVI uint4 best4(uint32_t p) {
  uint4 a = lds128(p), b = lds128(p + 16), c = lds128(p + 32), d = lds128(p + 48);
  if (b.x > a.x) a = b;
  if (d.x > c.x) c = d;
  return c.x > a.x ? c : a;
}
#define FL(x) __uint_as_float(x)
#define UI(x) __float_as_uint(x)
DEVI void aux(const Params& P, uint32_t sb) {
  int tid = fresh_tid();
  #define lane (tid & 31)
  #define wq (tid >> 5)
  uint32_t ids = P.map[blockIdx.x], tag;
  #define bid ((int)(ids & 255))
  #define fid ((int)(ids >> 8))
  #define bi (bid >> 4)
  #define bp (bid & 15)
  #define bc (bp >> 1)
  #define FRESH() do { tid = fresh_tid(); uint4 z_ = ldsv128(sb + INFO2 + 16); ids = z_.y; tag = z_.z + L; idx = z_.w; } while (0)
  {
    const uint32_t epoch = ld_rlx(&P.g->epoch);
    if (tid == 0) {
      mbar_expect_tx(BAR(B_STG), 49152);
      tma_3d(sb + STG, &P.mWq, bp * 64, bi * 128, 0, BAR(B_STG));
      tma_3d(sb + STG + 24576, &P.mWq, bp * 64, bi * 128 + 64, 0, BAR(B_STG));
    }
    __syncwarp();
    sts64f(sb + ONES + tid * 8, FL(0x3F803F80u), FL(0x3F803F80u));
    float s1 = 0.f, s2 = 0.f;
    { uint4 v = __ldg((const uint4*)P.wr + tid);
      if ((tid >> 4) == bc) put_f32(v, sb + WR + (tid & 15) * 32, 16);
      sum8(v, s1, s2);
      #pragma unroll 1
      for (int o = 16; o; o >>= 1) s1 += __shfl_xor_sync(0xffffffffu, s1, o);
      sts32f(sb + INFO2 + wq * 4, s1); }
    const uint4* src = (const uint4*)(P.x0 + (size_t)bid * 16384) + (tid >> 3) * 128 + (tid & 7);
    s1 = 0.f; s2 = 0.f;
    #pragma unroll 1
    for (int it = 0; it < 16; it += 4) {
      uint4 v0 = __ldg(src + it * 8), v1 = __ldg(src + it * 8 + 8), v2 = __ldg(src + it * 8 + 16), v3 = __ldg(src + it * 8 + 24);
      #pragma unroll 1
      for (int q = 0; q < 4; q++) { sum8(v0, s1, s2); v0 = v1; v1 = v2; v2 = v3; }
    }
    #pragma unroll 1
    for (int o = 1; o < 8; o <<= 1) { s1 += __shfl_xor_sync(0xffffffffu, s1, o); s2 += __shfl_xor_sync(0xffffffffu, s2, o); }
    tag = ((epoch % 16383u) + 1u) << 2;
    if (tid == 0) { sts128(sb + INFO, make_uint4(0x40000000u, 0u, tag, ((epoch % 127u) + 1u) << 1)); sts128(sb + INFO2 + 16, make_uint4(epoch, ids, tag, 0x40000000u)); }
    float m = s1 * (1.f / 1024.f);
    if ((tid & 7) == 0) st_ll(&P.g->statF[bid * 16 + (tid >> 3)], UI(m), UI(fmaxf(fmaf(-m, m, s2 * (1.f / 1024.f)), 0.f)), 0u, tag);
    bar_sync(2, 128);
    mbar_wait_b(BAR(B_STG), 0);
    if (tid < 96) {
      s1 = 0.f; s2 = 0.f;
      #pragma unroll 1
      for (int r = 0; r < 16; r++) {
        const uint32_t a = sb + STG + (r >> 3) * 24576 + wq * 8192 + (r & 7) * 128 + ((lane * 4) ^ ((r & 7) << 4));
        #pragma unroll
        for (int e = 0; e < 8; e++) { uint32_t v = lds32(a + e * 1024); s1 += bf_lo(v); s2 += bf_hi(v); }
      }
      st_ll(&P.g->csP[bp][bi][tid], UI(s1), UI(s2), 0u, tag);
      s1 = 0.f; s2 = 0.f;
      #pragma unroll 1
      for (int q = 0; q < 8; q += 2) {
        uint4 a, b; poll_ll2(&P.g->csP[bp][q][tid], &P.g->csP[bp][q + 1][tid], 0xffffffffu, tag, a, b);
        s1 += FL(a.x) + FL(b.x); s2 += FL(a.y) + FL(b.y);
      }
      const uint32_t hi = pack_bf16(-s1, -s2);
      sts32(sb + CS + (tid >> 2) * 32 + (tid & 3) * 4, hi);
      sts32(sb + CS + (tid >> 2) * 32 + (tid & 3) * 4 + 16, pack_bf16(-s1 - bf_lo(hi), -s2 - bf_hi(hi)));
    }
    fence_async_smem();
  }
  int idx;
  #pragma unroll 1
  for (int L = 0; L < 2; L++) {
    FRESH();
    {
      if ((unsigned)(bi - (idx >> 8)) < 2u) {
        const uint4* src = &P.g->patch[bp * 8 + (tid >> 6) * 4][tid & 63];
        uint4 v0, v1, v2, v3; int it = 0;
        do { v0 = ld_ll(src); v1 = ld_ll(src + 64); v2 = ld_ll(src + 128); v3 = ld_ll(src + 192); if (++it > SPIN_MAX) __trap(); }
        while (!__all_sync(0xffffffffu, v0.w == tag && v1.w == tag && v2.w == tag && v3.w == tag));
        float q = (FL(v0.x) + FL(v1.x)) + (FL(v2.x) + FL(v3.x)), k = (FL(v0.y) + FL(v1.y)) + (FL(v2.y) + FL(v3.y)), v = (FL(v0.z) + FL(v1.z)) + (FL(v2.z) + FL(v3.z));
        q += __shfl_xor_sync(0xffffffffu, q, 1); k += __shfl_xor_sync(0xffffffffu, k, 1); v += __shfl_xor_sync(0xffffffffu, v, 1);
        bar_sync(2, 128);
        const uint32_t d = sb + PATCH + (tid & ~1), kv = pack_bf16(k, v);
        sts16(d, pack_bf16(q * QSCALE, 0.f)); sts16(d + 128, kv); sts16(d + 256, kv >> 16);
      }
      sts32(sb + INFO, idx);
      bar_sync(2, 128);
    }
    const uint4 fix = lds128(sb + PATCH + 128 + (lane & 4) * 32 + (wq >> 1) * 64 + (lane & 3) * 16);
    warp_signal(BAR(B_PAR));
    PROFX(tid == 0, L ? 23 : 17);
    mbar_wait_b(BAR(B_KVFULL + wq), L);
    if ((idx >> 7) == bi * 2 - 1 - (wq & 1)) {
      if (lane < 8) sts128(sb + ((wq >> 1) ? KVB : KVA) + ((idx >> 6) & 3) * 8192 + (lane >> 2) * 4096 + (idx & 63) * 64 + (((lane ^ (idx >> 1)) & 3) << 4), fix);
      fence_async_smem();
    }
    bar_arrive(4 + wq, 160); bar_arrive(8 + wq, 160);
    FRESH();
    mbar_wait_b(BAR(B_OFREE), L);
    #define blk (bi * 2 + (bid & 1))
    if (tid < 33) st_ll(tid < 32 ? &P.g->row[blk][bc * 32 + tid] : &P.g->best[bc][blk], 0u, 0u, 0u, 0u);
    mbar_wait_b(BAR(B_XRDY + 1), L); mbar_wait_b(BAR(B_XRDY + 3), L);
    PROFX(tid == 0, 37 + L * 16);
    FRESH();
    {
      float s1 = 0.f, s2 = 0.f, d = 0.f;
      #pragma unroll 1
      for (int q = 0; q < 8; q += 4) {
        const uint4* src = &P.g->statP[q][blk * 128 + tid];
        uint4 v0, v1, v2, v3; int it = 0;
        do { v0 = ld_ll(src); v1 = ld_ll(src + 2048); v2 = ld_ll(src + 4096); v3 = ld_ll(src + 6144); if (++it > SPIN_MAX) __trap(); }
        while (!__all_sync(0xffffffffu, v0.w == tag && v1.w == tag && v2.w == tag && v3.w == tag));
        s1 += (FL(v0.x) + FL(v1.x)) + (FL(v2.x) + FL(v3.x)); s2 += (FL(v0.y) + FL(v1.y)) + (FL(v2.y) + FL(v3.y)); d += (FL(v0.z) + FL(v1.z)) + (FL(v2.z) + FL(v3.z));
      }
      PROFX(tid == 0, 39 + L * 16);
      uint4 a = lds128(sb + INFO2), b, c;
      float m = s1 * (1.f / 1024.f), var = fmaxf(fmaf(-m, m, s2 * (1.f / 1024.f)), 0.f), rs = rsqrtf(var + LN_EPS);
      uint32_t key = UI(fmaf(-m, (FL(a.x) + FL(a.y)) + (FL(a.z) + FL(a.w)), d) * rs);
      key ^= (uint32_t)((int)key >> 31) | 0x80000000u;
      uint32_t win = __ballot_sync(0xffffffffu, key == __reduce_max_sync(0xffffffffu, key));
      if (lane == __ffs(win) - 1) sts128(sb + RED + wq * 16, make_uint4(key, UI(m), UI(rs), (tag << 11) | (uint32_t)(blk * 128 + tid)));
      if (L) sts64f(sb + PAR + tid * 8, 1.f + rs, -m * rs);
      else if ((tid >> 4) == bc) st_ll(&P.g->statF[blk * 128 + tid], UI(m), UI(var), 0u, tag + 1);
      bar_sync(2, 128);
      if (wq == 0) {
        a = best4(sb + RED);
        float2 v = lds64f(sb + (lane >> 4) * 32768 + (a.w & 255) * 128 + (((lane & 15) * 8) ^ ((a.w & 7) << 4)));
        st_ll(&P.g->row[blk][bc * 32 + lane], UI(v.x), UI(v.y), 0u, tag);
        if (lane == 0) st_ll(&P.g->best[bc][blk], a.x, a.y, a.z, a.w);
        __syncwarp();
        if (lane < 2 + 2 * L) mbar_arrive(L ? BAR(B_PAR) : BAR(B_XFREE + lane));
      }
      PROFX(tid == 0, 18 + L * 6);
      FRESH();
      a = poll_ll(&P.g->best[bc][lane & 15], 0xfffff800u, tag << 11);
      win = __ffs(__ballot_sync(0xffffffffu, a.x == __reduce_max_sync(0xffffffffu, a.x))) - 1;
      idx = __shfl_sync(0xffffffffu, a.w, win) & 2047;
      PROFX(tid == 0, 19 + L * 6);
      poll_ll2(&P.g->row[win][tid], &P.g->row[win][tid + 128], 0xffffffffu, tag, c, b);
      c.z = b.x; c.w = b.y;
      a.x = __shfl_sync(0xffffffffu, a.x, win); a.y = __shfl_sync(0xffffffffu, a.y, win); a.z = __shfl_sync(0xffffffffu, a.z, win);
      sts32(sb + INFO2 + 28, idx);
      PROFX(tid == 0, 61 + L);
      b = norm8(c, FL(a.y), FL(a.z));
      if (L) put_bf16(b, sb + HV + tid * 8); else put_f32(b, sb + HV + tid * 16, 2048);
      if ((tid >> 1) == (bid & 63)) {
        sts128(sb + RED + 64 + (tid & 1) * 16, bid < 64 ? make_uint4(c.x, c.y, b.x, b.y) : make_uint4(c.z, c.w, b.z, b.w));
        sts32(sb + RED + 96, a.x);
      }
      bar_sync(2 + L, 128 + L * 256);
      if (L) {
        const int r0 = blk * 128 + (tid >> 4);
        uint32_t src = sb + ((tid >> 3) & 1) * 32768 + (r0 & 255) * 128 + (((tid ^ r0) & 7) << 4);
        uint4* dst = (uint4*)(P.out + (size_t)r0 * 1024 + bc * 128) + (tid & 15);
        #pragma unroll 4
        for (int it = 0; it < 16; it++) { uint4 v = lds128(src + it * 1024); if (idx - r0 != it * 8) dst[it * 1024] = v; }
      }
    }
    #pragma unroll 1
    for (int st = L; st < 2; st++) {
      FRESH();
      float a[8] = {0.f, 0.f, 0.f, 0.f, 0.f, 0.f, 0.f, 0.f};
      if (L == 0 && fid < 112) {
        uint32_t ha = st ? sb + RED + 768 : sb + HV + ((wq & 1) * 64 + (lane >> 2)) * 4;
        uint32_t ph = st ? 0x1cu : 0x171u, bar = st ? BAR(B_STG + 2) : BAR(B_STG);
        uint32_t wa = sb + STG + wq * 4096 + (st ? 32768 + lane * 16 : (lane ^ (lane >> 3)) * 16);
        const uint32_t hx = st ? 256 : 512;
        const bool lead = lane == 0;
        uint4 vc = make_uint4(0u, 0u, 0u, 0u); float hc = 0.f;
        #pragma unroll 1
        do {
          mbar_wait(bar, ph & 1);
          PROFX(lead && threadIdx.x == 256 && st == 0 && (ph > 255 || ph < 4), 40 - 23 + __clz(ph));
          #pragma unroll
          for (int n = 0; n < 8; n++) { const uint4 v = lds128(wa + n * 512); const float h = lds32f(ha + n * 32); fma8(a, vc, hc); vc = v; hc = h; }
          __syncwarp();
          if (lead) mbar_arrive(bar - 8 * (B_STG - B_STGE));
          const bool wrap = bar == BAR(B_STG + 2);
          bar += wrap ? -16 : 8; wa += wrap ? -32768 : 16384; ha += hx;
          ph >>= 1;
        } while (ph != 1);
        fma8(a, vc, hc);
      }
      FRESH();
      if (st == 1) {
        const uint32_t t8 = lds32(sb + INFO + 12) + L;
        if (L == 0 && fid < 112) {
          const bool odd = lane & 1;
          #pragma unroll
          for (int e = 0; e < 4; e++) { float z = __shfl_xor_sync(0xffffffffu, odd ? a[e] : a[4 + e], 1); if (odd) a[e] = z; else a[4 + e] = z; }
          uint4* dst = &P.g->yP[tid & ~1][fid][tid & 1];
          st_ll(dst, UI(a[0]), UI(a[1]), UI(a[2]), (UI(a[3]) & ~255u) | t8);
          st_ll(dst + 224, UI(a[4]), UI(a[5]), UI(a[6]), (UI(a[7]) & ~255u) | t8);
          PROFX(tid == 0, 21);
        }
        if (tid == 0) { uint32_t k = lds32(sb + RED + 96); sts32f(sb + RED + 100, bf_round(__fdividef(1.f, 1.f + __expf(-bf_round(FL(k ^ (~(uint32_t)((int)k >> 31) | 0x80000000u))))))); }
        uint4 v0, v1;
        poll_ll2(&P.g->yP[bid][0][min(tid, 111)], &P.g->yP[bid][0][min(tid, 111) + 112], 255u, t8, v0, v1);
        const float lo = (tid < 112 && !(tid & 1)) ? 1.f : 0.f, hi = (tid < 112 && (tid & 1)) ? 1.f : 0.f;
        const float y0 = FL(v0.x) + FL(v1.x), y1 = FL(v0.y) + FL(v1.y), y2 = FL(v0.z) + FL(v1.z), y3 = FL((v0.w & ~255u) | 128u) + FL((v1.w & ~255u) | 128u);
        a[0] = y0 * lo; a[1] = y1 * lo; a[2] = y2 * lo; a[3] = y3 * lo; a[4] = y0 * hi; a[5] = y1 * hi; a[6] = y2 * hi; a[7] = y3 * hi;
      }
      sts32f(sb + RED + 256 + wq * 128 + ((lane & 3) * 8 + (lane >> 2)) * 4, fold8(a));
      bar_sync(2, 128);
      const uint32_t d = sb + RED + 256 + lane * 4;
      float z0 = lds32f(d) + lds32f(d + 128), z1 = lds32f(d + 256) + lds32f(d + 384);
      if (st == 0) {
        sts32f(sb + RED + 768 + lane * 32 + wq * 4, swiglu(z0, z1));
        bar_sync(2, 128);
        if (fid < 112) { st_ll(&P.g->yP[tid & ~1][fid][tid & 1], 0u, 0u, 0u, 0u); st_ll(&P.g->yP[tid | 1][fid][tid & 1], 0u, 0u, 0u, 0u); }
        else { const uint32_t t0 = clk(); while (clk() - t0 < IDLE_T) __nanosleep(200); }
        if (tid < 80) st_ll(tid < 64 ? &P.g->patch[bid][tid] : &P.g->x2[(tid >> 1) & 7][2 * bid + (tid & 1)], 0u, 0u, 0u, 0u);
        PROFX(tid == 0, 20); continue; }
      z0 += z1;
      z0 += __shfl_xor_sync(0xffffffffu, z0, 8); z0 += __shfl_xor_sync(0xffffffffu, z0, 16);
      uint32_t xw = lds32(sb + RED + 64 + (lane & 4) * 4 + (lane & 2) * 2), hw = lds32(sb + RED + 72 + (lane & 4) * 4 + (lane & 2) * 2);
      z0 = bf_round(((lane & 1) ? bf_hi(hw) : bf_lo(hw)) + bf_round(bf_round(z0) * lds32f(sb + RED + 100))) + ((lane & 1) ? bf_hi(xw) : bf_lo(xw));
      uint32_t v = pack_bf16(z0, __shfl_down_sync(0xffffffffu, z0, 1)), v2 = __shfl_down_sync(0xffffffffu, v, 2);
      if (L) { if (tid == 0 || tid == 4) *(uint2*)(P.out + (size_t)idx * 1024 + bid * 8 + tid) = make_uint2(v, v2); PROFW(tid == 0, 28); }
      else if ((tid & 3) == 0 && tid < 64) st_ll(&P.g->x2[tid >> 3][2 * bid + ((tid >> 2) & 1)], v, v2, 0u, tag + 1);
    }
    if (L == 0) {
      PROFX(tid == 0, 22);
      FRESH();
      uint4 x, y; poll_ll2(&P.g->x2[bi][tid], &P.g->x2[bi][tid + 128], 0xffffffffu, tag + 1, x, y);
      x.z = y.x; x.w = y.y;
      if (wq == (bc & 3)) sts64f(sb + X2SEG + lane * 8, FL(bc < 4 ? x.x : x.z), FL(bc < 4 ? x.y : x.w));
      float s1 = 0.f, s2 = 0.f;
      sum8(x, s1, s2);
      #pragma unroll
      for (int o = 16; o; o >>= 1) { s1 += __shfl_xor_sync(0xffffffffu, s1, o); s2 += __shfl_xor_sync(0xffffffffu, s2, o); }
      sts64f(sb + RED + wq * 8, s1, s2);
      bar_sync(2, 128);
      y = lds128(sb + RED); uint4 y2 = lds128(sb + RED + 16);
      float m = ((FL(y.x) + FL(y.z)) + (FL(y2.x) + FL(y2.z))) * (1.f / 1024.f);
      put_bf16(norm8(x, m, rsqrtf(fmaxf(fmaf(-m, m, ((FL(y.y) + FL(y.w)) + (FL(y2.y) + FL(y2.w))) * (1.f / 1024.f)), 0.f) + LN_EPS)), sb + HV + tid * 8);
      mbar_wait(BAR(B_STG), 1); mbar_wait(BAR(B_STG + 1), 0); mbar_wait(BAR(B_STG + 2), 0);
      bar_sync(2, 128);
      PROFX(tid == 0, 30);
      float d0[4] = {0.f, 0.f, 0.f, 0.f}, d1[4] = {0.f, 0.f, 0.f, 0.f}, d2[4] = {0.f, 0.f, 0.f, 0.f};
      const uint32_t bd = (64 + (HV >> 4) + uni(bid & 3) * 32) | 0x10000u;
      #pragma unroll 1
      for (int ks = 0; ks < 8; ks++) {
        const uint32_t ad = (64 + (STG >> 4) + ks * 128) | (64u << 16);
        wg_fence();
        wgmma_ss_n8<0, 1>(d0, mkd<HI64>(ad), mkd<8>(bd + ks * 4), 1);
        wgmma_ss_n8<0, 1>(d1, mkd<HI64>(ad + 1024), mkd<8>(bd + ks * 4), 1);
        wgmma_ss_n8<0, 1>(d2, mkd<HI64>(ad + 2048), mkd<8>(bd + ks * 4), 1);
        wg_commit();
      }
      wg_wait<0>(); keep(d0); keep(d1); keep(d2);
      FRESH();
      if ((lane & 3) == (wq >> 1)) {
        uint4* dst = &P.g->patch[bid][(wq & 1) * 32 + (lane >> 2) * 2 + (wq >> 1)];
        st_ll(dst, UI(d0[0]), UI(d1[0]), UI(d2[0]), tag + 1); st_ll(dst + 16, UI(d0[2]), UI(d1[2]), UI(d2[2]), tag + 1);
      }
      PROFX(tid == 0, 31);
    }
  }
  if (bid == 0 && tid == 0) P.g->epoch = lds32(sb + INFO2 + 16) + 1;
  #undef blk
  #undef bid
  #undef fid
  #undef bi
  #undef bp
  #undef bc
  #undef FRESH
  #undef lane
  #undef wq
}

__global__ void __cluster_dims__(2, 1, 1) __launch_bounds__(512, 1) fused_kernel(const __grid_constant__ Params P) {
  extern __shared__ __align__(1024) uint8_t smem_raw[];
  const uint32_t sb = smem_u32(smem_raw);
  PROFT(threadIdx.x == 0, 0);
  if (threadIdx.x == 0) {
    for (int s = 0; s < 3; s++) mbar_init(BAR(B_FULLQ + s), 1);
    asm volatile("fence.mbarrier_init.release.cluster;" ::: "memory");
    #pragma unroll 1
    for (int s = 0; s < 3; s++) {
      mbar_expect_tx(BAR(B_FULLQ + s), 57344);
      tma_2d(sb + qa_off(s), &P.mX, s * 64, (BID >> 4) * 256, BAR(B_FULLQ + s));
      tma_3d(sb + qb_off(s), &P.mWq, (BID & 15) * 64, s * 64, 0, BAR(B_FULLQ + s));
    }
    if ((sb & 0x3FFFFu) != 1024) __trap();
  } else if (threadIdx.x == 480) {
    asm volatile("prefetch.tensormap [%0];" :: "l"(&P.mWq) : "memory");
  } else if (threadIdx.x >= 32 && !(threadIdx.x & 28) && (threadIdx.x >> 3) + (threadIdx.x & 3) <= B_COUNT + 1) {
    int b = (threadIdx.x >> 3) + (threadIdx.x & 3) - 1;
    if (b == B_COUNT) b = B_ROW;
    const uint32_t cnt = b < B_XFREE ? (b == B_OFREE ? 1 : 2) : (b < B_KVRDY ? 3 : (b < B_KVFULL || b == B_PAR ? 4 : (b == B_PFREE ? 2 : 1)));
    mbar_init(BAR(b), cnt);
    asm volatile("fence.mbarrier_init.release.cluster;" ::: "memory");
  }
  __syncthreads();
  asm volatile("barrier.cluster.arrive.relaxed.aligned;" ::: "memory");
  const int wg = __shfl_sync(0xffffffffu, threadIdx.x >> 7, 0);
  if (wg < 2) { reg_inc<224>(); consumer(P, sb, wg); }
  else if (wg == 2) { reg_dec<40>(); aux(P, sb); }
  else {
    reg_dec<24>();
    asm volatile("barrier.cluster.wait.aligned;" ::: "memory");
    const int w = __shfl_sync(0xffffffffu, (threadIdx.x >> 5) & 3, 0);
    if (w == 0) loader(P, sb);
    else if (w < 3) storer(P, sb, w - 1);
    else if ((threadIdx.x & 31) == 0) stager(P, sb);
  }
}

typedef CUresult (*EncFn)(CUtensorMap*, CUtensorMapDataType, cuuint32_t, void*, const cuuint64_t*, const cuuint64_t*, const cuuint32_t*, const cuuint32_t*,
                          CUtensorMapInterleave, CUtensorMapSwizzle, CUtensorMapL2promotion, CUtensorMapFloatOOBfill);
static void mk_map(EncFn enc, CUtensorMap* m, const void* ptr, int rank, const cuuint64_t* dims, const cuuint64_t* strides, const cuuint32_t* box,
                   CUtensorMapSwizzle sw, CUtensorMapL2promotion pr) {
  cuuint32_t es[5] = {1, 1, 1, 1, 1};
  enc(m, CU_TENSOR_MAP_DATA_TYPE_BFLOAT16, rank, (void*)ptr, dims, strides, box, es, CU_TENSOR_MAP_INTERLEAVE_NONE, sw, pr, CU_TENSOR_MAP_FLOAT_OOB_FILL_NONE);
}
extern "C" void kernel_launch(void* const* d_in, const int* in_sizes, int n_in, void* d_out, int out_size) {
  (void)in_sizes; (void)n_in; (void)out_size;
  void* fn = nullptr; cudaDriverEntryPointQueryResult q;
  cudaGetDriverEntryPoint("cuTensorMapEncodeTiled", &fn, cudaEnableDefault, &q);
  EncFn enc = (EncFn)fn;
  cudaFuncSetAttribute(fused_kernel, cudaFuncAttributeMaxDynamicSharedMemorySize, SMEM_BYTES);
  Params P;
  const CUtensorMapSwizzle S128 = CU_TENSOR_MAP_SWIZZLE_128B, S64 = CU_TENSOR_MAP_SWIZZLE_64B, S0 = CU_TENSOR_MAP_SWIZZLE_NONE;
  const CUtensorMapL2promotion L256 = CU_TENSOR_MAP_L2_PROMOTION_L2_256B, L128 = CU_TENSOR_MAP_L2_PROMOTION_L2_128B;
  { cuuint64_t d[2] = {1024, 2048}, s[1] = {2048}; cuuint32_t b[2] = {64, 256}, bh[2] = {64, 128};
    mk_map(enc, &P.mX, d_in[0], 2, d, s, b, S128, L256); mk_map(enc, &P.mXh, d_in[0], 2, d, s, bh, S128, L256); }
  { cuuint64_t d[3] = {1024, 1024, 3}, s[2] = {6144, 2048}; cuuint32_t b[3] = {64, 64, 3}; mk_map(enc, &P.mWq, d_in[1], 3, d, s, b, S128, L256); }
  { cuuint64_t d[5] = {64, 32, 2, 16, 16}, s[4] = {2048, 65536, 131072, 128}; cuuint32_t b[5] = {64, 32, 1, 2, 2}; mk_map(enc, &P.mWo, d_in[2], 5, d, s, b, S128, L256); }
  { cuuint64_t d[2] = {3584, 1024}, s[1] = {7168}; cuuint32_t b[2] = {32, 128};
    mk_map(enc, &P.mWg, d_in[5], 2, d, s, b, S64, L128); mk_map(enc, &P.mWu, d_in[6], 2, d, s, b, S64, L128); }
  { cuuint64_t d[2] = {3072, 1024}, s[1] = {6144}; cuuint32_t b[2] = {32, 256}; mk_map(enc, &P.mWp, d_in[1], 2, d, s, b, S64, L128); }
  { cuuint64_t d[3] = {256, 3584, 4}, s[2] = {2048, 512}; cuuint32_t b[3] = {256, 8, 4}; mk_map(enc, &P.mWd, d_in[7], 3, d, s, b, S0, L128); }
  P.x0 = (const bf16*)d_in[0]; P.wqkv = (const bf16*)d_in[1]; P.wo = (const bf16*)d_in[2]; P.wr = (const bf16*)d_in[4]; P.wg = (const bf16*)d_in[5]; P.wu = (const bf16*)d_in[6]; P.wd = (const bf16*)d_in[7];
  P.out = (bf16*)d_out;
  cudaGetSymbolAddress((void**)&P.g, g_scr);
  for (int b = 0; b < 128; b++) {
    int j = b >> 1, quad = j < 4 ? 0 : (j < 36 ? 1 + (j - 4) % 8 : 9 + (j - 36) % 7), pos = j < 4 ? j : (j < 36 ? (j - 4) / 8 : (j - 36) / 7);
    int bid = ((quad >> 2) * 2 + (pos >> 1)) * 16 + ((quad & 3) * 2 + (pos & 1)) * 2 + (b & 1);
    int e = pos * 2 + (b & 1), fid = e < 7 ? quad * 7 + e : 112 + quad;
    P.map[b] = bid | fid << 8;
  }
  fused_kernel<<<128, 512, SMEM_BYTES>>>(P);
}
```

```cpp
#include <cuda_runtime.h>
#include <cuda_bf16.h>
#include <cuda.h>
#include <stdint.h>
#include <stddef.h>
typedef __nv_bfloat16 bf16;

template<int TB, int TA = 0> __device__ __forceinline__ void wgmma_ss_n192(float (&d)[96], uint64_t da, uint64_t db, int scale_d) {
  asm volatile("{\n.reg .pred p;\nsetp.ne.b32 p, %98, 0;\n"
    "wgmma.mma_async.sync.aligned.m64n192k16.f32.bf16.bf16 {%0, %1, %2, %3, %4, %5, %6, %7, %8, %9, %10, %11, %12, %13, %14, %15, %16, %17, %18, %19, %20, %21, %22, %23, %24, %25, %26, %27, %28, %29, %30, %31, %32, %33, %34, %35, %36, %37, %38, %39, %40, %41, %42, %43, %44, %45, %46, %47, %48, %49, %50, %51, %52, %53, %54, %55, %56, %57, %58, %59, %60, %61, %62, %63, %64, %65, %66, %67, %68, %69, %70, %71, %72, %73, %74, %75, %76, %77, %78, %79, %80, %81, %82, %83, %84, %85, %86, %87, %88, %89, %90, %91, %92, %93, %94, %95}, %96, %97, p, 1, 1, %100, %99;\n}\n"
    : "+f"(d[0]), "+f"(d[1]), "+f"(d[2]), "+f"(d[3]), "+f"(d[4]), "+f"(d[5]), "+f"(d[6]), "+f"(d[7]), "+f"(d[8]), "+f"(d[9]), "+f"(d[10]), "+f"(d[11]), "+f"(d[12]), "+f"(d[13]), "+f"(d[14]), "+f"(d[15]), "+f"(d[16]), "+f"(d[17]), "+f"(d[18]), "+f"(d[19]), "+f"(d[20]), "+f"(d[21]), "+f"(d[22]), "+f"(d[23]), "+f"(d[24]), "+f"(d[25]), "+f"(d[26]), "+f"(d[27]), "+f"(d[28]), "+f"(d[29]), "+f"(d[30]), "+f"(d[31]), "+f"(d[32]), "+f"(d[33]), "+f"(d[34]), "+f"(d[35]), "+f"(d[36]), "+f"(d[37]), "+f"(d[38]), "+f"(d[39]), "+f"(d[40]), "+f"(d[41]), "+f"(d[42]), "+f"(d[43]), "+f"(d[44]), "+f"(d[45]), "+f"(d[46]), "+f"(d[47]), "+f"(d[48]), "+f"(d[49]), "+f"(d[50]), "+f"(d[51]), "+f"(d[52]), "+f"(d[53]), "+f"(d[54]), "+f"(d[55]), "+f"(d[56]), "+f"(d[57]), "+f"(d[58]), "+f"(d[59]), "+f"(d[60]), "+f"(d[61]), "+f"(d[62]), "+f"(d[63]), "+f"(d[64]), "+f"(d[65]), "+f"(d[66]), "+f"(d[67]), "+f"(d[68]), "+f"(d[69]), "+f"(d[70]), "+f"(d[71]), "+f"(d[72]), "+f"(d[73]), "+f"(d[74]), "+f"(d[75]), "+f"(d[76]), "+f"(d[77]), "+f"(d[78]), "+f"(d[79]), "+f"(d[80]), "+f"(d[81]), "+f"(d[82]), "+f"(d[83]), "+f"(d[84]), "+f"(d[85]), "+f"(d[86]), "+f"(d[87]), "+f"(d[88]), "+f"(d[89]), "+f"(d[90]), "+f"(d[91]), "+f"(d[92]), "+f"(d[93]), "+f"(d[94]), "+f"(d[95])
    : "l"(da), "l"(db), "r"(scale_d), "n"(TB), "n"(TA));
}

template<int TB> __device__ __forceinline__ void wgmma_rs_n192(float (&d)[96], uint32_t a0, uint32_t a1, uint32_t a2, uint32_t a3, uint64_t db, int scale_d) {
  asm volatile("{\n.reg .pred p;\nsetp.ne.b32 p, %101, 0;\n"
    "wgmma.mma_async.sync.aligned.m64n192k16.f32.bf16.bf16 {%0, %1, %2, %3, %4, %5, %6, %7, %8, %9, %10, %11, %12, %13, %14, %15, %16, %17, %18, %19, %20, %21, %22, %23, %24, %25, %26, %27, %28, %29, %30, %31, %32, %33, %34, %35, %36, %37, %38, %39, %40, %41, %42, %43, %44, %45, %46, %47, %48, %49, %50, %51, %52, %53, %54, %55, %56, %57, %58, %59, %60, %61, %62, %63, %64, %65, %66, %67, %68, %69, %70, %71, %72, %73, %74, %75, %76, %77, %78, %79, %80, %81, %82, %83, %84, %85, %86, %87, %88, %89, %90, %91, %92, %93, %94, %95}, {%96, %97, %98, %99}, %100, p, 1, 1, %102;\n}\n"
    : "+f"(d[0]), "+f"(d[1]), "+f"(d[2]), "+f"(d[3]), "+f"(d[4]), "+f"(d[5]), "+f"(d[6]), "+f"(d[7]), "+f"(d[8]), "+f"(d[9]), "+f"(d[10]), "+f"(d[11]), "+f"(d[12]), "+f"(d[13]), "+f"(d[14]), "+f"(d[15]), "+f"(d[16]), "+f"(d[17]), "+f"(d[18]), "+f"(d[19]), "+f"(d[20]), "+f"(d[21]), "+f"(d[22]), "+f"(d[23]), "+f"(d[24]), "+f"(d[25]), "+f"(d[26]), "+f"(d[27]), "+f"(d[28]), "+f"(d[29]), "+f"(d[30]), "+f"(d[31]), "+f"(d[32]), "+f"(d[33]), "+f"(d[34]), "+f"(d[35]), "+f"(d[36]), "+f"(d[37]), "+f"(d[38]), "+f"(d[39]), "+f"(d[40]), "+f"(d[41]), "+f"(d[42]), "+f"(d[43]), "+f"(d[44]), "+f"(d[45]), "+f"(d[46]), "+f"(d[47]), "+f"(d[48]), "+f"(d[49]), "+f"(d[50]), "+f"(d[51]), "+f"(d[52]), "+f"(d[53]), "+f"(d[54]), "+f"(d[55]), "+f"(d[56]), "+f"(d[57]), "+f"(d[58]), "+f"(d[59]), "+f"(d[60]), "+f"(d[61]), "+f"(d[62]), "+f"(d[63]), "+f"(d[64]), "+f"(d[65]), "+f"(d[66]), "+f"(d[67]), "+f"(d[68]), "+f"(d[69]), "+f"(d[70]), "+f"(d[71]), "+f"(d[72]), "+f"(d[73]), "+f"(d[74]), "+f"(d[75]), "+f"(d[76]), "+f"(d[77]), "+f"(d[78]), "+f"(d[79]), "+f"(d[80]), "+f"(d[81]), "+f"(d[82]), "+f"(d[83]), "+f"(d[84]), "+f"(d[85]), "+f"(d[86]), "+f"(d[87]), "+f"(d[88]), "+f"(d[89]), "+f"(d[90]), "+f"(d[91]), "+f"(d[92]), "+f"(d[93]), "+f"(d[94]), "+f"(d[95])
    : "r"(a0), "r"(a1), "r"(a2), "r"(a3), "l"(db), "r"(scale_d), "n"(TB));
}

template<int TB, int TA = 0> __device__ __forceinline__ void wgmma_ss_n128(float (&d)[64], uint64_t da, uint64_t db, int scale_d) {
  asm volatile("{\n.reg .pred p;\nsetp.ne.b32 p, %66, 0;\n"
    "wgmma.mma_async.sync.aligned.m64n128k16.f32.bf16.bf16 {%0, %1, %2, %3, %4, %5, %6, %7, %8, %9, %10, %11, %12, %13, %14, %15, %16, %17, %18, %19, %20, %21, %22, %23, %24, %25, %26, %27, %28, %29, %30, %31, %32, %33, %34, %35, %36, %37, %38, %39, %40, %41, %42, %43, %44, %45, %46, %47, %48, %49, %50, %51, %52, %53, %54, %55, %56, %57, %58, %59, %60, %61, %62, %63}, %64, %65, p, 1, 1, %68, %67;\n}\n"
    : "+f"(d[0]), "+f"(d[1]), "+f"(d[2]), "+f"(d[3]), "+f"(d[4]), "+f"(d[5]), "+f"(d[6]), "+f"(d[7]), "+f"(d[8]), "+f"(d[9]), "+f"(d[10]), "+f"(d[11]), "+f"(d[12]), "+f"(d[13]), "+f"(d[14]), "+f"(d[15]), "+f"(d[16]), "+f"(d[17]), "+f"(d[18]), "+f"(d[19]), "+f"(d[20]), "+f"(d[21]), "+f"(d[22]), "+f"(d[23]), "+f"(d[24]), "+f"(d[25]), "+f"(d[26]), "+f"(d[27]), "+f"(d[28]), "+f"(d[29]), "+f"(d[30]), "+f"(d[31]), "+f"(d[32]), "+f"(d[33]), "+f"(d[34]), "+f"(d[35]), "+f"(d[36]), "+f"(d[37]), "+f"(d[38]), "+f"(d[39]), "+f"(d[40]), "+f"(d[41]), "+f"(d[42]), "+f"(d[43]), "+f"(d[44]), "+f"(d[45]), "+f"(d[46]), "+f"(d[47]), "+f"(d[48]), "+f"(d[49]), "+f"(d[50]), "+f"(d[51]), "+f"(d[52]), "+f"(d[53]), "+f"(d[54]), "+f"(d[55]), "+f"(d[56]), "+f"(d[57]), "+f"(d[58]), "+f"(d[59]), "+f"(d[60]), "+f"(d[61]), "+f"(d[62]), "+f"(d[63])
    : "l"(da), "l"(db), "r"(scale_d), "n"(TB), "n"(TA));
}

template<int TB, int TA = 0> __device__ __forceinline__ void wgmma_ss_n64(float (&d)[32], uint64_t da, uint64_t db, int scale_d) {
  asm volatile("{\n.reg .pred p;\nsetp.ne.b32 p, %34, 0;\n"
    "wgmma.mma_async.sync.aligned.m64n64k16.f32.bf16.bf16 {%0, %1, %2, %3, %4, %5, %6, %7, %8, %9, %10, %11, %12, %13, %14, %15, %16, %17, %18, %19, %20, %21, %22, %23, %24, %25, %26, %27, %28, %29, %30, %31}, %32, %33, p, 1, 1, %36, %35;\n}\n"
    : "+f"(d[0]), "+f"(d[1]), "+f"(d[2]), "+f"(d[3]), "+f"(d[4]), "+f"(d[5]), "+f"(d[6]), "+f"(d[7]), "+f"(d[8]), "+f"(d[9]), "+f"(d[10]), "+f"(d[11]), "+f"(d[12]), "+f"(d[13]), "+f"(d[14]), "+f"(d[15]), "+f"(d[16]), "+f"(d[17]), "+f"(d[18]), "+f"(d[19]), "+f"(d[20]), "+f"(d[21]), "+f"(d[22]), "+f"(d[23]), "+f"(d[24]), "+f"(d[25]), "+f"(d[26]), "+f"(d[27]), "+f"(d[28]), "+f"(d[29]), "+f"(d[30]), "+f"(d[31])
    : "l"(da), "l"(db), "r"(scale_d), "n"(TB), "n"(TA));
}

template<int TB, int TA = 0> __device__ __forceinline__ void wgmma_ss_n8(float (&d)[4], uint64_t da, uint64_t db, int scale_d) {
  asm volatile("{\n.reg .pred p;\nsetp.ne.b32 p, %6, 0;\n"
    "wgmma.mma_async.sync.aligned.m64n8k16.f32.bf16.bf16 {%0, %1, %2, %3}, %4, %5, p, 1, 1, %8, %7;\n}\n"
    : "+f"(d[0]), "+f"(d[1]), "+f"(d[2]), "+f"(d[3])
    : "l"(da), "l"(db), "r"(scale_d), "n"(TB), "n"(TA));
}

template<int TB> __device__ __forceinline__ void wgmma_rs_n40(float (&d)[20], uint32_t a0, uint32_t a1, uint32_t a2, uint32_t a3, uint64_t db, int scale_d) {
  asm volatile("{\n.reg .pred p;\nsetp.ne.b32 p, %25, 0;\n"
    "wgmma.mma_async.sync.aligned.m64n40k16.f32.bf16.bf16 {%0, %1, %2, %3, %4, %5, %6, %7, %8, %9, %10, %11, %12, %13, %14, %15, %16, %17, %18, %19}, {%20, %21, %22, %23}, %24, p, 1, 1, %26;\n}\n"
    : "+f"(d[0]), "+f"(d[1]), "+f"(d[2]), "+f"(d[3]), "+f"(d[4]), "+f"(d[5]), "+f"(d[6]), "+f"(d[7]), "+f"(d[8]), "+f"(d[9]), "+f"(d[10]), "+f"(d[11]), "+f"(d[12]), "+f"(d[13]), "+f"(d[14]), "+f"(d[15]), "+f"(d[16]), "+f"(d[17]), "+f"(d[18]), "+f"(d[19])
    : "r"(a0), "r"(a1), "r"(a2), "r"(a3), "l"(db), "r"(scale_d), "n"(TB));
}

#define DEVI __device__ __forceinline__
DEVI uint32_t smem_u32(const void* p) { return (uint32_t)__cvta_generic_to_shared(p); }
DEVI void mbar_init(uint32_t bar, uint32_t cnt) { asm volatile("mbarrier.init.shared::cta.b64 [%0], %1;" :: "r"(bar), "r"(cnt)); }
DEVI void mbar_expect_tx(uint32_t bar, uint32_t bytes) { asm volatile("mbarrier.arrive.expect_tx.shared::cta.b64 _, [%0], %1;" :: "r"(bar), "r"(bytes) : "memory"); }
DEVI void mbar_arrive(uint32_t bar) { asm volatile("mbarrier.arrive.shared::cta.b64 _, [%0];" :: "r"(bar) : "memory"); }
DEVI void mbar_arrive_peer(uint32_t bar) {
  asm volatile("{\n.reg .b32 ra;\nmapa.shared::cluster.u32 ra, %0, %1;\nmbarrier.arrive.shared::cluster.b64 _, [ra];\n}" :: "r"(bar), "r"((blockIdx.x & 1) ^ 1) : "memory");
}
DEVI void bulk_s2peer(uint32_t a, uint32_t bytes, uint32_t bar) {
  asm volatile("{\n.reg .b32 ra, rb;\nmapa.shared::cluster.u32 ra, %0, %3;\nmapa.shared::cluster.u32 rb, %2, %3;\n"
               "cp.async.bulk.shared::cluster.shared::cta.mbarrier::complete_tx::bytes [ra], [%0], %1, [rb];\n}"
               :: "r"(a), "r"(bytes), "r"(bar), "r"((blockIdx.x & 1) ^ 1) : "memory");
}
DEVI void mbar_wait(uint32_t bar, uint32_t parity) {
  asm volatile("{\n.reg .pred p;\nLW:\nmbarrier.try_wait.parity.shared::cta.b64 p, [%0], %1;\n@!p bra LW;\n}" :: "r"(bar), "r"(parity) : "memory");
}
DEVI uint32_t mbar_test(uint32_t bar, uint32_t parity) {
  uint32_t r; asm volatile("{\n.reg .pred p;\nmbarrier.test_wait.parity.shared::cta.b64 p, [%1], %2;\nselp.u32 %0, 1, 0, p;\n}" : "=r"(r) : "r"(bar), "r"(parity) : "memory"); return r;
}
DEVI void mbar_wait_b(uint32_t bar, uint32_t parity) {
  asm volatile("{\n.reg .pred p;\n.reg .u32 it;\nmov.u32 it, 0;\nLW:\nmbarrier.try_wait.parity.shared::cta.b64 p, [%0], %1;\n@p bra LD;\n"
               "add.u32 it, it, 1;\nsetp.lt.u32 p, it, 0x1000000;\n@p bra LW;\ntrap;\nLD:\n}" :: "r"(bar), "r"(parity) : "memory");
}
DEVI void tma_2d(uint32_t dst, const CUtensorMap* m, int c0, int c1, uint32_t bar) {
  asm volatile("cp.async.bulk.tensor.2d.shared::cluster.global.mbarrier::complete_tx::bytes [%0], [%1, {%3, %4}], [%2];"
    :: "r"(dst), "l"(m), "r"(bar), "r"(c0), "r"(c1) : "memory");
}
DEVI void tma_3d(uint32_t dst, const CUtensorMap* m, int c0, int c1, int c2, uint32_t bar) {
  asm volatile("cp.async.bulk.tensor.3d.shared::cluster.global.mbarrier::complete_tx::bytes [%0], [%1, {%3, %4, %5}], [%2];"
    :: "r"(dst), "l"(m), "r"(bar), "r"(c0), "r"(c1), "r"(c2) : "memory");
}
#define POL_EF POL_FIRST
constexpr uint64_t POL_FIRST = 0x12F0000000000000ull, POL_NORMAL = 0x1000000000000000ull;
DEVI void tma_2d_h(uint32_t dst, const CUtensorMap* m, int c0, int c1, uint32_t bar, uint64_t pol) {
  asm volatile("cp.async.bulk.tensor.2d.shared::cluster.global.mbarrier::complete_tx::bytes.L2::cache_hint [%0], [%1, {%3, %4}], [%2], %5;"
    :: "r"(dst), "l"(m), "r"(bar), "r"(c0), "r"(c1), "l"(pol) : "memory");
}
DEVI void tma_3d_h(uint32_t dst, const CUtensorMap* m, int c0, int c1, int c2, uint32_t bar, uint64_t pol) {
  asm volatile("cp.async.bulk.tensor.3d.shared::cluster.global.mbarrier::complete_tx::bytes.L2::cache_hint [%0], [%1, {%3, %4, %5}], [%2], %6;"
    :: "r"(dst), "l"(m), "r"(bar), "r"(c0), "r"(c1), "r"(c2), "l"(pol) : "memory");
}
DEVI void bulk_g2s_h(uint32_t s, const void* g, uint32_t bytes, uint32_t bar, uint64_t pol = POL_EF) {
  asm volatile("cp.async.bulk.shared::cluster.global.mbarrier::complete_tx::bytes.L2::cache_hint [%0], [%1], %2, [%3], %4;"
    :: "r"(s), "l"(g), "r"(bytes), "r"(bar), "l"(pol) : "memory");
}
DEVI void tma_5d(uint32_t dst, const CUtensorMap* m, int c0, int c1, int c2, int c3, int c4, uint32_t bar, uint64_t pol) {
  asm volatile("cp.async.bulk.tensor.5d.shared::cluster.global.mbarrier::complete_tx::bytes.L2::cache_hint [%0], [%1, {%3, %4, %5, %6, %7}], [%2], %8;"
    :: "r"(dst), "l"(m), "r"(bar), "r"(c0), "r"(c1), "r"(c2), "r"(c3), "r"(c4), "l"(pol) : "memory");
}
DEVI void tma_prefetch_2d(const CUtensorMap* m, int c0, int c1) {
  asm volatile("cp.async.bulk.prefetch.tensor.2d.L2.global.tile [%0, {%1, %2}];" :: "l"(m), "r"(c0), "r"(c1) : "memory");
}
DEVI void tma_prefetch_3d(const CUtensorMap* m, int c0, int c1, int c2) {
  asm volatile("cp.async.bulk.prefetch.tensor.3d.L2.global.tile [%0, {%1, %2, %3}];" :: "l"(m), "r"(c0), "r"(c1), "r"(c2) : "memory");
}
DEVI void bulk_prefetch(const void* g, uint32_t bytes) { asm volatile("cp.async.bulk.prefetch.L2.global [%0], %1;" :: "l"(g), "r"(bytes) : "memory"); }
DEVI void bulk_g2s(uint32_t s, const void* g, uint32_t bytes, uint32_t bar) {
  asm volatile("cp.async.bulk.shared::cluster.global.mbarrier::complete_tx::bytes [%0], [%1], %2, [%3];" :: "r"(s), "l"(g), "r"(bytes), "r"(bar) : "memory");
}
DEVI void bulk_s2g(void* g, uint32_t s, uint32_t bytes) {
  asm volatile("cp.async.bulk.global.shared::cta.bulk_group [%0], [%1], %2;\ncp.async.bulk.commit_group;" :: "l"(g), "r"(s), "r"(bytes) : "memory");
}
template<int N> DEVI void bulk_wait() { asm volatile("cp.async.bulk.wait_group %0;" :: "n"(N) : "memory"); }
DEVI void fence_async_smem() { asm volatile("fence.proxy.async.shared::cta;" ::: "memory"); }
DEVI void fence_async_glob() { asm volatile("fence.proxy.async.global;" ::: "memory"); }
DEVI unsigned ld_rlx(const unsigned* p) { unsigned v; asm volatile("ld.relaxed.gpu.global.u32 %0, [%1];" : "=r"(v) : "l"(p) : "memory"); return v; }
DEVI void st_rlx(unsigned* p, unsigned v) { asm volatile("st.relaxed.gpu.global.u32 [%0], %1;" :: "l"(p), "r"(v) : "memory"); }
DEVI uint2 ldg_stream(const uint2* p) { uint2 v; asm volatile("ld.global.nc.L1::no_allocate.v2.u32 {%0, %1}, [%2];" : "=r"(v.x), "=r"(v.y) : "l"(p)); return v; }
DEVI void fence_rel() { asm volatile("fence.release.gpu;" ::: "memory"); }
DEVI uint4 ld_ll(const uint4* p) {
  uint4 v;
  asm volatile("{\n.reg .b128 t;\n.reg .b64 a, b;\nld.relaxed.gpu.global.b128 t, [%4];\nmov.b128 {a, b}, t;\nmov.b64 {%0, %1}, a;\nmov.b64 {%2, %3}, b;\n}"
               : "=r"(v.x), "=r"(v.y), "=r"(v.z), "=r"(v.w) : "l"(p) : "memory");
  return v;
}
DEVI void st_ll(uint4* p, uint32_t x, uint32_t y, uint32_t z, uint32_t w) {
  asm volatile("{\n.reg .b128 t;\n.reg .b64 a, b;\nmov.b64 a, {%1, %2};\nmov.b64 b, {%3, %4};\nmov.b128 t, {a, b};\nst.relaxed.gpu.global.b128 [%0], t;\n}"
               :: "l"(p), "r"(x), "r"(y), "r"(z), "r"(w) : "memory");
}
#define SPIN_MAX 0x1000000
DEVI uint4 poll_ll(const uint4* p, uint32_t mask, uint32_t tag) {
  uint4 v; int it = 0;
  do { v = ld_ll(p); if (++it > SPIN_MAX) __trap(); } while (!__all_sync(0xffffffffu, (v.w & mask) == tag));
  return v;
}
DEVI void poll_ll2(const uint4* p, const uint4* q, uint32_t mask, uint32_t tag, uint4& a, uint4& b) {
  int it = 0;
  do { a = ld_ll(p); b = ld_ll(q); if (++it > SPIN_MAX) __trap(); } while (!__all_sync(0xffffffffu, (a.w & mask) == tag && (b.w & mask) == tag));
}
DEVI void bar_sync(int id, int n) { asm volatile("bar.sync %0, %1;" :: "r"(id), "r"(n) : "memory"); }
DEVI void bar_arrive(int id, int n) { asm volatile("bar.arrive %0, %1;" :: "r"(id), "r"(n) : "memory"); }
DEVI void wg_fence() { asm volatile("wgmma.fence.sync.aligned;" ::: "memory"); }
DEVI void wg_commit() { asm volatile("wgmma.commit_group.sync.aligned;" ::: "memory"); }
template<int N> DEVI void wg_wait() { asm volatile("wgmma.wait_group.sync.aligned %0;" :: "n"(N) : "memory"); }
template<int N> DEVI void reg_inc() { asm volatile("setmaxnreg.inc.sync.aligned.u32 %0;" :: "n"(N)); }
template<int N> DEVI void reg_dec() { asm volatile("setmaxnreg.dec.sync.aligned.u32 %0;" :: "n"(N)); }
DEVI float ex2f(float x) { float y; asm("ex2.approx.ftz.f32 %0, %1;" : "=f"(y) : "f"(x)); return y; }
DEVI uint32_t pack_bf16(float lo, float hi) { uint32_t r; asm("cvt.rn.bf16x2.f32 %0, %1, %2;" : "=r"(r) : "f"(hi), "f"(lo)); return r; }
DEVI float bf_lo(uint32_t v) { return __uint_as_float(v << 16); }
DEVI float bf_hi(uint32_t v) { return __uint_as_float(v & 0xffff0000u); }
DEVI float bf_round(float x) { return bf_lo(pack_bf16(x, 0.f)); }
DEVI void stsm_x4(uint32_t addr, uint32_t a, uint32_t b, uint32_t c, uint32_t d) {
  asm volatile("stmatrix.sync.aligned.m8n8.x4.shared.b16 [%0], {%1,%2,%3,%4};" :: "r"(addr), "r"(a), "r"(b), "r"(c), "r"(d) : "memory");
}
DEVI void ldsm_x4(uint32_t addr, uint32_t& a, uint32_t& b, uint32_t& c, uint32_t& d) {
  asm volatile("ldmatrix.sync.aligned.m8n8.x4.shared.b16 {%0,%1,%2,%3}, [%4];" : "=r"(a), "=r"(b), "=r"(c), "=r"(d) : "r"(addr) : "memory");
}
DEVI uint4 lds128(uint32_t a) { uint4 v; asm volatile("ld.shared.v4.u32 {%0,%1,%2,%3}, [%4];" : "=r"(v.x), "=r"(v.y), "=r"(v.z), "=r"(v.w) : "r"(a) : "memory"); return v; }
DEVI void sts128(uint32_t a, uint4 v) { asm volatile("st.shared.v4.u32 [%0], {%1,%2,%3,%4};" :: "r"(a), "r"(v.x), "r"(v.y), "r"(v.z), "r"(v.w) : "memory"); }
DEVI float2 lds64f(uint32_t a) { float2 v; asm volatile("ld.shared.v2.f32 {%0,%1}, [%2];" : "=f"(v.x), "=f"(v.y) : "r"(a) : "memory"); return v; }
DEVI void sts64f(uint32_t a, float x, float y) { asm volatile("st.shared.v2.f32 [%0], {%1,%2};" :: "r"(a), "f"(x), "f"(y) : "memory"); }
DEVI uint32_t lds32(uint32_t a) { uint32_t v; asm volatile("ld.shared.u32 %0, [%1];" : "=r"(v) : "r"(a) : "memory"); return v; }
DEVI float lds32f(uint32_t a) { return __uint_as_float(lds32(a)); }
DEVI void sts32(uint32_t a, uint32_t v) { asm volatile("st.shared.u32 [%0], %1;" :: "r"(a), "r"(v) : "memory"); }
DEVI void sts32f(uint32_t a, float v) { sts32(a, __float_as_uint(v)); }
DEVI void sts16(uint32_t a, uint32_t v) { asm volatile("st.shared.u16 [%0], %1;" :: "r"(a), "h"((unsigned short)v) : "memory"); }
template<int N> DEVI void keep(float (&d)[N]) {
  #pragma unroll
  for (int i = 0; i < N; i++) asm volatile("" : "+f"(d[i]) :: "memory");
}
template<int N> DEVI void keep(uint32_t (&d)[N]) {
  #pragma unroll
  for (int i = 0; i < N; i++) asm volatile("" : "+r"(d[i]) :: "memory");
}
template<uint32_t HI> DEVI uint64_t mkd(uint32_t lo) { uint64_t r; asm("mov.b64 %0, {%1, %2};" : "=l"(r) : "r"(lo), "n"(HI)); return r; }
constexpr uint32_t HI128 = (1u << 30) | (1024 >> 4), HI64 = (2u << 30) | (512 >> 4);
#define VOFF(x) ((uint32_t)(x) * (uint32_t)(1 - 65536))
DEVI bool elect() { uint32_t p; asm volatile("{\n.reg .pred q;\nelect.sync _|q, 0xffffffff;\nselp.u32 %0, 1, 0, q;\n}" : "=r"(p)); return p; }
DEVI void warp_signal(uint32_t bar) { __syncwarp(); if (elect()) mbar_arrive(bar); }

struct Scratch {
  uint4 kv[128][4][1024];
  uint4 o[8][2][8][2][1024];
  uint4 x[8][16][2048];
  uint4 zero[1024];
  uint4 statP[8][2048];
  uint4 statF[2048];
  uint4 csP[16][8][96];
  uint4 best[8][16];
  uint4 row[16][256];
  uint4 yP[128][112][2];
  uint4 x2[8][256];
  uint4 patch[128][64];
  unsigned flagKV[128][32];
  unsigned flagO[8][32];
  unsigned flagX[8][32];
  unsigned epoch;
};
__device__ __align__(1024) Scratch g_scr;
#define PROFT(cond, slot)
#define PROFW(cond, slot)
#define PROFD(cond, slot)
#define PROFX(cond, slot)
#define PROFY(cond, slot)

constexpr uint32_t SB0 = 65536, HOLE = 90112, SA2 = 98304, SB1 = 131072, SB2 = 155648, STG = 180224;
constexpr uint32_t KVA = 0, KVB = 98304, QO = 65536;
constexpr uint32_t MISC = 229376, CS = MISC, ONES = MISC + 768, BARS = MISC + 1792, INFO = MISC + 2208, WR = MISC + 2224, X2SEG = MISC + 2736, INFO2 = MISC + 2992, DUMP = MISC + 3040;
constexpr uint32_t PAR = HOLE, HV = HOLE + 2048, RED = HOLE + 6144, PATCH = 196608;
constexpr uint32_t SMEM_BYTES = 232448;
enum { B_FULLQ = 0, B_EMPTYQ = 3, B_FULLW = 6, B_EMPTYW = 12, B_HAFREE = 18, B_OFREE = 20,
       B_XFREE = 21,
       B_KVRDY = 23, B_ORDY = 27, B_XRDY = 35, B_STGE = 39,
       B_KVFULL = 42, B_RES = 46, B_PAR = 47, B_STG = 48, B_PFREE = 51, B_COUNT = 52,
       B_ROW = 154 };
#define BAR(x) (sb + BARS + 8 * (x))
DEVI uint32_t qa_off(int s) { return s == 2 ? SA2 : (uint32_t)s * 32768u; }
DEVI uint32_t qb_off(int s) { return s == 0 ? SB0 : (s == 1 ? SB1 : SB2); }
DEVI int kb_order(int bc, int n) {
  const int e = n < 9 ? n - 2 : n - 9;
  return n < 2 ? 2 * bc + n : 2 * (((e < 4 ? e + 4 : e - 4 + (e - 4 >= (bc & 3))) + (bc & 4)) & 7) + (n >= 9);
}
DEVI int wo_order(int bc, int n) { return (n & 8) | ((n + (bc & 6)) & 7); }
DEVI uint32_t w_off(int s) { return (uint32_t)((0x143065 >> (4 * s)) & 7) * 32768u; }
DEVI uint32_t w_par(int n, int s, int L) { return (n >= 6 && n < 12) ^ (s == 5) ^ (s != 2 && L); }
DEVI int w_next(int n, int s) { return s == 5 ? 0 : (n == 13 ? 3 : s + 1); }

struct Params {
  CUtensorMap mX, mXh, mWq, mWo, mWg, mWu, mWp, mWd;
  const bf16 *x0, *wqkv, *wo, *wr, *wg, *wu, *wd;
  bf16* out;
  Scratch* g;
  unsigned map[128];
};
#define BID ((int)(P.map[blockIdx.x] & 255))
#define FID ((int)(P.map[blockIdx.x] >> 8))
DEVI uint32_t uni(uint32_t v) { return __shfl_sync(0xffffffffu, v, 0); }
#define PQ_N 8
#define PQ_T 700
#define PF0_N 10
#define PF0_T 1600
#define PF1_E 24
#define PF1_T 1100
#define POL_Q1 POL_NORMAL
#define POL_X POL_NORMAL
#define PFA0_BAR 3
#define PFA1_BAR 0
#define PFA0_M 0
#define PFA1_M 0
#define PFA0_T 900
#define PFA1_T 700
#define PF1_S PF0_N
#define PF1_D 0
#define POL_G POL_NORMAL
#define POL_U POL_FIRST
#define POL_D POL_FIRST
#define JQ_N 6
#define WDSRC (P.wd + (size_t)min(fid, 111) * 32768)
#define WDSRC2 (P.wd + FID * 32768)
#define WD_N 4
#define THR_N 5
#define KV_D 1800
#define XD_D 300
#define W0_BAR 3
#define QEF_N 99
#define PACE_T 300
#define IDLE_T 11000
#define LATE_C 2
#define LATE_B B_XFREE + 1
#define LATE_P 0
#define KV_D1 200
#define KV_D2 1200
#define KV_DL 0
#define POL_Q0 POL_NORMAL
constexpr float LN_EPS = 1e-5f;
constexpr float QSCALE = 0.17677669529663687f * 1.4426950408889634f;

DEVI void fma8(float (&a)[8], uint4 v, float h) {
  a[0] = fmaf(bf_lo(v.x), h, a[0]); a[1] = fmaf(bf_hi(v.x), h, a[1]); a[2] = fmaf(bf_lo(v.y), h, a[2]); a[3] = fmaf(bf_hi(v.y), h, a[3]);
  a[4] = fmaf(bf_lo(v.z), h, a[4]); a[5] = fmaf(bf_hi(v.z), h, a[5]); a[6] = fmaf(bf_lo(v.w), h, a[6]); a[7] = fmaf(bf_hi(v.w), h, a[7]);
}
DEVI uint4 ldsv128(uint32_t a) { uint4 v; asm volatile("ld.volatile.shared.v4.u32 {%0,%1,%2,%3}, [%4];" : "=r"(v.x), "=r"(v.y), "=r"(v.z), "=r"(v.w) : "r"(a) : "memory"); return v; }
DEVI float ldsv32f(uint32_t a) { float v; asm volatile("ld.volatile.shared.f32 %0, [%1];" : "=f"(v) : "r"(a) : "memory"); return v; }
DEVI uint32_t clk() { uint32_t t; asm volatile("mov.u32 %0, %%clock;" : "=r"(t)); return t; }
DEVI int fresh_tid() { int t; asm volatile("mov.u32 %0, %%tid.x;" : "=r"(t)); return t & 127; }
DEVI float fold8(const float (&a)[8]) {
  const int lane = threadIdx.x & 31;
  const bool u = lane & 16, v = lane & 8, x = lane & 4;
  float b0 = (u ? a[4] : a[0]) + __shfl_xor_sync(0xffffffffu, u ? a[0] : a[4], 16), b1 = (u ? a[5] : a[1]) + __shfl_xor_sync(0xffffffffu, u ? a[1] : a[5], 16);
  float b2 = (u ? a[6] : a[2]) + __shfl_xor_sync(0xffffffffu, u ? a[2] : a[6], 16), b3 = (u ? a[7] : a[3]) + __shfl_xor_sync(0xffffffffu, u ? a[3] : a[7], 16);
  float c0 = (v ? b2 : b0) + __shfl_xor_sync(0xffffffffu, v ? b0 : b2, 8), c1 = (v ? b3 : b1) + __shfl_xor_sync(0xffffffffu, v ? b1 : b3, 8);
  return (x ? c1 : c0) + __shfl_xor_sync(0xffffffffu, x ? c0 : c1, 4);
}
DEVI float swiglu(float g, float u) { g = bf_round(g); return bf_round(bf_round(__fdividef(g, 1.f + __expf(-g))) * bf_round(u)); }

DEVI void qk_issue(float (&s)[32], uint32_t qd, uint32_t kd) {
  wgmma_ss_n64<0>(s, mkd<HI64>(qd), mkd<HI64>(kd), 0);
  wgmma_ss_n64<0>(s, mkd<HI64>(qd + 2), mkd<HI64>(kd + 2), 1);
}
template<int J0, int J1> DEVI void exp_pack(const float (&s)[32], uint32_t (&p)[16]) {
  #pragma unroll
  for (int j = J0; j < J1; j++) p[j] = pack_bf16(ex2f(s[2 * j]), ex2f(s[2 * j + 1]));
}
DEVI bool attn_pack(const float (&o)[20], uint32_t (&ob)[8]) {
  const float lo = 5.421010862427522e-20f, hi = 1.8446744073709552e19f;
  float i0, i1; asm("rcp.approx.ftz.f32 %0, %1;" : "=f"(i0) : "f"(o[16])); asm("rcp.approx.ftz.f32 %0, %1;" : "=f"(i1) : "f"(o[18]));
  #pragma unroll
  for (int e = 0; e < 8; e++) ob[e] = pack_bf16(o[2 * e] * ((e & 1) ? i1 : i0), o[2 * e + 1] * ((e & 1) ? i1 : i0));
  return __all_sync(0xffffffffu, o[16] >= lo && o[16] <= hi && o[18] >= lo && o[18] <= hi);
}
DEVI void attn_store(const uint32_t (&ob)[8], bool ok, uint32_t st, uint32_t sb, uint32_t bar) {
  stsm_x4(ok ? st : sb + DUMP, ob[0], ob[1], ob[2], ob[3]); stsm_x4(ok ? st ^ 32 : sb + DUMP, ob[4], ob[5], ob[6], ob[7]);
  __syncwarp();
  asm volatile("{\n.reg .pred p, q;\nelect.sync _|q, 0xffffffff;\nsetp.ne.and.u32 p, %1, 0, q;\n@p mbarrier.arrive.shared::cta.b64 _, [%0];\n}" :: "r"(bar), "r"((uint32_t)ok) : "memory");
}
DEVI void attn_exact(uint32_t st, uint32_t kv, int t, bool hasprev, uint32_t bar) {
  const int lane = threadIdx.x & 31;
  #pragma unroll 1
  for (int row = ((threadIdx.x >> 5) & 3) * 16, n = 0; n < 16; n++, row++) {
    const int k1 = 256 + t * 64 + row;
    float m = -INFINITY, l = 0.f, o = 0.f;
    #pragma unroll 1
    for (int k0 = hasprev ? k1 - 255 : 256; k0 <= k1; k0 += 32) {
      const int k = min(k0 + lane, k1), r = k & 63;
      float sc = 0.f;
      #pragma unroll 1
      for (int c = 0; c < 16; c++) {
        uint32_t a = lds32(st + row * 64 + ((c * 4) ^ ((row & 6) << 3))), b = lds32(kv + (k >> 6) * 8192 + r * 64 + ((c * 4) ^ ((r & 6) << 3)));
        sc = fmaf(bf_lo(a), bf_lo(b), fmaf(bf_hi(a), bf_hi(b), sc));
      }
      float mn = fmaxf(m, sc);
      #pragma unroll 1
      for (int x = 16; x; x >>= 1) mn = fmaxf(mn, __shfl_xor_sync(0xffffffffu, mn, x));
      const float al = ex2f(m - mn), pr = ex2f(sc - mn);
      m = mn; l *= al; o *= al;
      #pragma unroll 1
      for (int q = k0; q <= min(k0 + 31, k1); q++) {
        const float z = __shfl_sync(0xffffffffu, pr, q - k0);
        uint32_t b = lds32(kv + (q >> 6) * 8192 + 4096 + (q & 63) * 64 + (((lane >> 1) * 4) ^ ((q & 6) << 3)));
        l += z; o = fmaf(z, (lane & 1) ? bf_hi(b) : bf_lo(b), o);
      }
    }
    __syncwarp();
    sts16(st + row * 64 + ((lane * 2) ^ ((row & 6) << 3)), pack_bf16(__fdividef(o, l), 0.f));
  }
  warp_signal(bar);
}

template<int K0, int K1, int DONE = 0> DEVI void exp_pv(const float (&s)[32], uint32_t (&p)[16], float (&o)[20], uint32_t vd, bool accum) {
  #pragma unroll
  for (int ks = K0; ks < K1; ks++) {
    if (ks >= DONE) {
      #pragma unroll
      for (int j = 4 * ks; j < 4 * ks + 4; j++) p[j] = pack_bf16(ex2f(s[2 * j]), ex2f(s[2 * j + 1]));
    }
    asm volatile("" : "+r"(p[4 * ks]), "+r"(p[4 * ks + 1]), "+r"(p[4 * ks + 2]), "+r"(p[4 * ks + 3]));
    wg_fence();
    wgmma_rs_n40<1>(o, p[ks * 4], p[ks * 4 + 1], p[ks * 4 + 2], p[ks * 4 + 3], mkd<HI64>(vd + VOFF(ks * 64)), ks ? 1 : accum);
  }
}
DEVI void exp_pv2(const float (&s)[32], const float (&sx)[32], uint32_t (&p)[16], uint32_t (&px)[16], float (&o)[20], uint32_t v0, uint32_t v4,
                  const uint32_t (&msk)[9], int tdiag) {
  #pragma unroll
  for (int ks = 0; ks < 4; ks++) {
    #pragma unroll
    for (int j = 4 * ks; j < 4 * ks + 4; j++) {
      const int c = 8 * (j >> 1) - 8 * (j & 1);
      const uint32_t e = pack_bf16(ex2f(c > tdiag ? s[2 * j] : sx[2 * j]), ex2f(c + 1 > tdiag ? s[2 * j + 1] : sx[2 * j + 1])), m = msk[(j >> 1) - (j & 1) + 1];
      p[j] = e & m; px[j] = e & ~m;
      asm volatile("" : "+r"(p[j]), "+r"(px[j]));
    }
    wg_fence();
    wgmma_rs_n40<1>(o, p[ks * 4], p[ks * 4 + 1], p[ks * 4 + 2], p[ks * 4 + 3], mkd<HI64>(v0 + VOFF(ks * 64)), 1);
    wgmma_rs_n40<1>(o, px[ks * 4], px[ks * 4 + 1], px[ks * 4 + 2], px[ks * 4 + 3], mkd<HI64>(v4 + VOFF(ks * 64)), 1);
  }
}

template<int J0> DEVI void qkv_store(const float (&a)[96], float p0, float p1, uint32_t d) {
  #pragma unroll
  for (int hh = 0; hh < 2; hh++) {
    const int j = 4 * (J0 + 2 * hh);
    stsm_x4(d ^ (hh << 5), pack_bf16(a[j] * p0, a[j + 1] * p0), pack_bf16(a[j + 2] * p1, a[j + 3] * p1),
                           pack_bf16(a[j + 4] * p0, a[j + 5] * p0), pack_bf16(a[j + 6] * p1, a[j + 7] * p1));
  }
}
DEVI void mean_step(float (&a)[96], float m0, float m1, uint32_t cd, bool z) {
  const uint32_t u0 = z ? 0u : __float_as_uint(m0), u1 = z ? 0u : __float_as_uint(m1);
  uint32_t ma[4] = {__byte_perm(u0, 0u, 0x1010), __byte_perm(u1, 0u, 0x1010), __byte_perm(u0, 0u, 0x3232), __byte_perm(u1, 0u, 0x3232)};
  keep(ma);
  wg_fence();
  wgmma_rs_n192<1>(a, ma[0], ma[1], ma[2], ma[3], mkd<2>(cd), 1);
  wg_commit();
}

template<bool FIRST> DEVI void qkv_block(float (&aX)[96], float (&aY)[96], uint32_t sb16, int s, int tX, int tY) {
  uint32_t a16 = sb16 + (qa_off(s) >> 4), b16 = (sb16 + (qb_off(s) >> 4)) | ((8192u >> 4) << 16);
  uint32_t ax = (a16 + tX * 512) | 0x10000u, ay = (a16 + tY * 512) | 0x10000u;
  wg_fence();
  #pragma unroll
  for (int ks = 0; ks < 4; ks++) {
    wgmma_ss_n192<1>(aX, mkd<HI128>(ax + ks * 2), mkd<HI128>(b16 + ks * 128), !(FIRST && ks == 0));
    wgmma_ss_n192<1>(aY, mkd<HI128>(ay + ks * 2), mkd<HI128>(b16 + ks * 128), !(FIRST && ks == 0));
  }
  wg_commit();
}
DEVI void qkv_half(float (&a)[96], uint32_t sb16, int t, uint32_t sa, uint32_t sbb) {
  wg_fence();
  #pragma unroll
  for (int ks = 0; ks < 4; ks++)
    wgmma_ss_n192<1>(a, mkd<HI128>(((sb16 + (sa >> 4) + t * 512) | 0x10000u) + ks * 2), mkd<HI128>(((sb16 + (sbb >> 4)) | ((8192u >> 4) << 16)) + ks * 128), 1);
  wg_commit();
}
DEVI void wo_block(float (&acc)[64], uint32_t sb16, int s, int wg) {
  uint32_t a16 = (sb16 + (w_off(s) >> 4) + wg * 256) | 0x10000u, b16 = (sb16 + (w_off(s) >> 4) + 1024) | ((8192u >> 4) << 16);
  wg_fence();
  #pragma unroll
  for (int ks = 0; ks < 4; ks++)
    wgmma_ss_n128<1>(acc, mkd<HI64>(a16 + (ks >> 1) * 512 + (ks & 1) * 2), mkd<HI128>(b16 + ks * 128), 1);
  wg_commit();
}
DEVI void consumer(const Params& P, uint32_t sb, int wg) {
  const int w = uni((threadIdx.x >> 5) & 3);
  #define LAYER uni(mbar_test(BAR(B_XRDY + wg * 2 + 1), 0))
  #define IDS L = LAYER; const int tid = fresh_tid(), lane = tid & 31
  const uint32_t ids = uni(P.map[blockIdx.x]);
  const int bi = (ids >> 4) & 7, rh = ids & 1, bc = (ids & 15) >> 1, fid = ids >> 8;
  const int tX = 3 - wg, tY = wg;
  constexpr uint32_t sb16 = 1024 >> 4;
  #pragma unroll 1
  while (true) {
    int L = LAYER;
    {
      float aX[96], aY[96];
      const bool lead = fresh_tid() == 0;
      mbar_wait(BAR(B_FULLQ), 0);
      PROFW(threadIdx.x == 0, L * 8 + 1);
      qkv_block<true>(aX, aY, sb16, 0, tX, tY);
      #pragma unroll 1
      for (int n = 1, s = 1, ps = 0, ph = 0; n < 14; n++) {
        mbar_wait(BAR(B_FULLQ + s), ph ^ (s ? L : 0));
        PROFD(threadIdx.x == 0 && L && (n == 2 || n == 3 || n == 7 || n == 11 || n == 13), n == 2 ? 48 : 49 + (n >> 2));
        qkv_block<false>(aX, aY, sb16, s, tX, tY);
        wg_wait<1>(); if (lead) mbar_arrive(BAR(B_EMPTYQ + ps));
        ps = s; if (s == 2) { s = 0; ph ^= 1; } else s++;
      }
      mbar_wait(BAR(B_FULLQ + 2), L);
      qkv_half(aX, sb16, tX, SA2, SB2);
      mbar_wait(BAR(B_ROW), L);
      IDS;
      const uint32_t pa = sb + PAR + (w * 16 + (lane >> 2)) * 8;
      float2 p0 = lds64f(pa + tX * 512), p1 = lds64f(pa + tX * 512 + 64), p2 = lds64f(pa + tY * 512), p3 = lds64f(pa + tY * 512 + 64);
      mean_step(aX, p0.y, p1.y, sb16 + (CS >> 4), lane & 3);
      mbar_wait(BAR(B_FULLQ), 1);
      qkv_half(aX, sb16, tX, 0, SB0);
      wg_wait<3>(); if (lead) mbar_arrive(BAR(B_EMPTYQ + 1));
      bar_sync(1, 256);
      qkv_half(aY, sb16, tY, SA2, SB2);
      wg_wait<1>(); keep(aX);
      const int srow = w * 16 + (lane & 15);
      const uint32_t x0 = sb + srow * 64 + (((lane >> 4) ^ ((srow >> 1) & 3)) << 4), xX = x0 + (4 + tX) * 8192, xY = x0 + (4 + tY) * 8192;
      qkv_store<8>(aX, p0.x, p1.x, xX + KVA); qkv_store<16>(aX, p0.x, p1.x, xX + KVA + 4096);
      warp_signal(BAR(B_KVRDY + wg * 2));
      qkv_half(aY, sb16, tY, 0, SB0);
      mean_step(aY, p2.y, p3.y, sb16 + (CS >> 4), fresh_tid() & 3);
      wg_wait<2>(); if (lead) mbar_arrive(BAR(B_EMPTYQ + 2));
      mbar_wait(BAR(B_EMPTYQ + 2), L);
      qkv_store<12>(aX, p0.x, p1.x, xX + KVB); qkv_store<20>(aX, p0.x, p1.x, xX + KVB + 4096);
      wg_wait<0>(); keep(aY);
      if (lead) mbar_arrive(BAR(B_EMPTYQ));
      PROFW(threadIdx.x == 0, L * 8 + 2);
      qkv_store<8>(aY, p2.x, p3.x, xY + KVA); qkv_store<16>(aY, p2.x, p3.x, xY + KVA + 4096);
      qkv_store<12>(aY, p2.x, p3.x, xY + KVB); qkv_store<20>(aY, p2.x, p3.x, xY + KVB + 4096);
      warp_signal(BAR(B_KVRDY + wg * 2 + 1));
      p0.x *= QSCALE; p1.x *= QSCALE; p2.x *= QSCALE; p3.x *= QSCALE;
      mbar_wait(BAR(B_EMPTYQ), 1);
      qkv_store<0>(aX, p0.x, p1.x, x0 + QO + tX * 4096);
      qkv_store<0>(aY, p2.x, p3.x, x0 + QO + tY * 4096); qkv_store<4>(aY, p2.x, p3.x, x0 + QO + 16384 + tY * 4096);
      mbar_wait(BAR(B_PAR), L);
      qkv_store<4>(aX, p0.x, p1.x, x0 + QO + 16384 + tX * 4096);
      const int prow = (int)uni(lds32(sb + INFO)) - bi * 256;
      if ((prow >> 4) == tX * 4 + w || (prow >> 4) == tY * 4 + w) {
        __syncwarp();
        if (lane < 24) sts128(sb + (prow & 63) * 64 + (((lane ^ (prow >> 1)) & 3) << 4) +
                              (lane < 8 ? QO + (lane >> 2) * 16384 + (prow >> 6) * 4096 : ((lane & 4) ? KVB : KVA) + (4 + (prow >> 6)) * 8192 + (lane >> 4) * 4096),
                              lds128(sb + PATCH + lane * 16));
      }
      fence_async_smem();
      bar_sync(1, 256);
    }
    PROFW(threadIdx.x == 0, L * 8 + 3);
    float2 fa, fb;
    { const float2* f = (const float2*)&P.g->statF[bi * 256 + rh * 128 + (wg ^ rh) * 64 + w * 16 + ((fresh_tid() & 31) >> 2)];
      fa = __ldcg(f); fb = __ldcg(f + 16); }
    {
      IDS;
      float s0[32], s1[32], sx[32], o[20], op[20];
      uint32_t p0[16], p1[16], px[16], msk[9];
      const int tdiag = w * 16 + (lane >> 2) - 2 * (lane & 3);
      #pragma unroll
      for (int e = 0; e < 9; e++) msk[e] = ((8 * e - 8 > tdiag) ? 0xFFFFu : 0u) | ((8 * e - 7 > tdiag) ? 0xFFFF0000u : 0u);
      keep(msk);
      const uint32_t ones = (sb16 + (ONES >> 4)) << 16;
      const uint32_t qX = (sb16 + (QO >> 4) + tX * 256) | 0x10000u, qY = (sb16 + (QO >> 4) + tY * 256) | 0x10000u;
      const uint32_t kXB = (sb16 + (KVB >> 4) + tX * 512) | 0x10000u;
      uint32_t redo = 0;
      const uint32_t ost = sb + QO + (w * 16 + (lane & 15)) * 64 + (((lane >> 4) ^ ((lane >> 1) & 3)) << 4);
      #define QK(s, q, k) do { wg_fence(); qk_issue(s, q, k); wg_commit(); } while (0)
      #define QK2(q, k) do { wg_fence(); qk_issue(s1, q, k); qk_issue(sx, q, (k) + 2048); wg_commit(); } while (0)
      #define VB(v, b) ((v) + VOFF((b) * 512))
      QK(s0, qX + 1024, kXB + 1536);
      #pragma unroll
      for (int e = 0; e < 20; e++) o[e] = 0.f;
      wg_wait<0>(); keep(s0);
      #pragma unroll 1
      for (int h = 1; h >= 0; h--) {
        const uint32_t kXA = kXB - ((KVB - KVA) >> 4), kX = h ? kXB : kXA, vX = VOFF((kX & 0xffffu) + 256) + ones;
        QK(s1, qX + h * 1024, kX + 1024);
        #pragma unroll
        for (int e = 0; e < 20; e++) op[e] = o[e];
        keep(op);
        exp_pv<0, 4>(s0, p0, o, VB(vX, 3), false); wg_commit();
        wg_wait<1>(); keep(s1);
        exp_pv<0, 2>(s1, p1, o, VB(vX, 2), true);
        bar_sync(h ? 12 + wg : 4 + wg * 4, h ? 128 : 160);
        QK(s0, qX, kXA + 512 + h * 1024);
        exp_pv<2, 4>(s1, p1, o, VB(vX, 2), true); wg_commit();
        wg_wait<0>(); keep(s0); keep(p0); keep(p1); keep(o);
      }
      #pragma unroll 1
      for (int h = 0; h < 2; h++) {
        const uint32_t kb16 = sb16 + ((h ? KVB : KVA) >> 4), kY = (kb16 + tY * 512) | 0x10000u, qy = qY + h * 1024;
        const uint32_t onesP = bi ? ones : (kb16 + 1984) << 16;
        const uint32_t vX = VOFF(kb16 + tX * 512 + 256), vY = VOFF(kb16 + tY * 512 + 256);
        uint32_t ob[8];
        QK2(qX + h * 1024, (kb16 + tX * 512) | 0x10000u);
        exp_pv<0, 4>(s0, p0, o, VB(vX + (wg ? onesP : ones), 1), true); wg_commit();
        wg_wait<1>(); keep(s1); keep(sx);
        QK(s0, qy, kY + 1536);
        exp_pv2(s1, sx, p1, px, o, vX + onesP, VB(vX + ones, 4), msk, tdiag); wg_commit();
        wg_wait<1>(); keep(s0); keep(p0);
        QK(s1, qy, kY + 1024);
        exp_pack<0, 4>(s0, p0);
        wg_wait<1>(); keep(o); keep(p1); keep(px);
        bool ok = attn_pack(o, ob); keep(ob);
        exp_pv<0, 4, 1>(s0, p0, o, VB(vY + (wg ? ones : onesP), 3), false); wg_commit();
        attn_store(ob, ok, ost + (h * 4 + tX) * 4096, sb, BAR(B_ORDY + wg * 4 + h * 2)); redo |= ok ? 0u : 1u << (h * 2);
        wg_wait<1>(); keep(s1);
        exp_pv<0, 2>(s1, p1, o, VB(vY + onesP, 2), true);
        bar_sync(5 + wg * 4 + h * 2, 160);
        QK(s0, qy, kY + 512);
        exp_pv<2, 4>(s1, p1, o, VB(vY + onesP, 2), true); wg_commit();
        wg_wait<1>(); keep(s0); keep(p0);
        QK2(qy, kY);
        exp_pv<0, 4>(s0, p0, o, VB(vY + onesP, 1), true); wg_commit();
        wg_wait<1>(); keep(s1); keep(sx); keep(p1);
        bar_sync(6 + wg * 4, h ? 128 : 160);
        QK(s0, h ? qy : qX + 1024, kXB + 512);
        exp_pv2(s1, sx, p1, px, o, vY + onesP, VB(vY + ones, 4), msk, tdiag); wg_commit();
        wg_wait<0>(); keep(o); keep(s0); keep(p0); keep(p1); keep(px);
        ok = attn_pack(o, ob); attn_store(ob, ok, ost + (h * 4 + tY) * 4096, sb, BAR(B_ORDY + wg * 4 + h * 2 + 1)); redo |= ok ? 0u : 2u << (h * 2);
        #pragma unroll
        for (int e = 0; e < 20; e++) o[e] = op[e];
      }
      #undef QK
      #undef QK2
      #undef VB
      if (redo) {
        #pragma unroll 1
        for (int u = 0; u < 4; u++) if ((redo >> u) & 1) {
          const int h = u >> 1, t = (u & 1) ? tY : tX;
          attn_exact(sb + QO + (h * 4 + t) * 4096, sb + (h ? KVB : KVA), t, bi > 0, BAR(B_ORDY + wg * 4 + u));
        }
      }
    }
    PROFW(threadIdx.x == 0, L * 8 + 4);
    {
      IDS;
      const int t256 = wg * 128 + tid;
      float acc[64];
      const int tt = wg ^ rh;
      const int grow = bi * 256 + rh * 128 + tt * 64 + w * 16 + (lane >> 2);
      float al0 = 1.f, be0 = 0.f, al1 = 1.f, be1 = 0.f;
      const int idx0 = (int)uni(lds32(sb + INFO));
      const uint32_t tag = lds32(sb + INFO + 8) + L;
      uint4* const sp = &P.g->statP[bc][grow + (lane & 1) * 8];
      uint4* const yp = &P.g->yP[t256 >> 1][min(fid, 111)][t256 & 1];
      if (L) {
        float r0 = rsqrtf(fa.y + LN_EPS), r1 = rsqrtf(fb.y + LN_EPS);
        if (grow != idx0) { al0 = 1.f + r0; be0 = -fa.x * r0; }
        if (grow + 8 != idx0) { al1 = 1.f + r1; be1 = -fb.x * r1; }
      }
      const int srow = tt * 64 + w * 16 + (lane & 15);
      const uint32_t ra = sb + srow * 128 + (((lane >> 4) ^ (srow & 7)) << 4);
      mbar_wait(BAR(B_FULLW + 5), L);
      if ((idx0 >> 4) == bi * 16 + rh * 8 + tt * 4 + w) {
        int r = idx0 & 127;
        if (lane < 16) sts128(sb + 32768 + (lane >> 3) * 16384 + r * 128 + (((lane & 7) ^ (r & 7)) << 4), lds128(sb + X2SEG + lane * 16));
        fence_async_smem();
        __syncwarp();
      }
      #pragma unroll
      for (int jj = 0; jj < 8; jj++) {
        uint32_t r[4]; ldsm_x4((ra + 32768 + (jj >> 2) * 16384) ^ ((jj & 3) << 5), r[0], r[1], r[2], r[3]);
        #pragma unroll
        for (int e = 0; e < 4; e++) {
          acc[8 * jj + 2 * e] = fmaf(bf_lo(r[e]), (e & 1) ? al1 : al0, (e & 1) ? be1 : be0);
          acc[8 * jj + 2 * e + 1] = fmaf(bf_hi(r[e]), (e & 1) ? al1 : al0, (e & 1) ? be1 : be0);
        }
      }
      keep(acc);
      bar_sync(12 + wg, 128);
      if (!(lane & 2)) st_ll(sp, 0u, 0u, 0u, 0u);
      uint2 wd[4];
      #pragma unroll
      for (int e = 0; e < 4; e++) { wd[e] = make_uint2(0u, 0u); if (L) wd[e] = ldg_stream((const uint2*)(WDSRC) + t256 + (28 + e) * 256); }
      PROFW(t256 == 0, L * 8 + 5);
      #pragma unroll 1
      for (int n = 0, q = 0, pq = 5; n < 16; n++) {
        mbar_wait(BAR(B_FULLW + q), w_par(n, q, L));
        PROFD(t256 == 0 && !L && (n == 4 || n == 7 || n == 8 || n == 12), (n == 7 ? 63 : 41 + (n >> 2)));
        wo_block(acc, sb16, q, tt);
        wg_wait<1>(); if (tid == 0) mbar_arrive(BAR(B_EMPTYW + pq));
        pq = q; q = w_next(n, q);
      }
      mbar_wait(BAR(B_EMPTYW + 5), L);
      wg_wait<0>(); keep(acc);
      if (tid == 0) mbar_arrive(BAR(B_EMPTYW + 4));
      PROFW(t256 == 0, L * 8 + 6);
      const uint32_t xa = ra + rh * 16384;
      #pragma unroll
      for (int jj = 0; jj < 8; jj++) {
        const float* a = acc + 8 * jj;
        stsm_x4((xa + (jj >> 2) * 32768) ^ ((jj & 3) << 5), pack_bf16(a[0], a[1]), pack_bf16(a[2], a[3]), pack_bf16(a[4], a[5]), pack_bf16(a[6], a[7]));
        if (jj == 7) fence_async_smem();
        if ((jj & 3) == 3) warp_signal(BAR(B_XRDY + wg * 2 + (jj >> 2)));
      }
      {
        float s1a = 0.f, s2a = 0.f, da = 0.f, s1b = 0.f, s2b = 0.f, db = 0.f;
        #pragma unroll
        for (int j = 0; j < 16; j++) {
          const float* a = acc + 4 * j; float2 wv = lds64f(sb + WR + j * 32 + (lane & 3) * 8);
          s1a += a[0] + a[1]; s1b += a[2] + a[3];
          s2a = fmaf(a[0], a[0], s2a); s2b = fmaf(a[2], a[2], s2b); s2a = fmaf(a[1], a[1], s2a); s2b = fmaf(a[3], a[3], s2b);
          da = fmaf(a[0], wv.x, da); db = fmaf(a[2], wv.x, db); da = fmaf(a[1], wv.y, da); db = fmaf(a[3], wv.y, db);
        }
        bool odd = lane & 1;
        float u1 = (odd ? s1b : s1a) + __shfl_xor_sync(0xffffffffu, odd ? s1a : s1b, 1);
        float u2 = (odd ? s2b : s2a) + __shfl_xor_sync(0xffffffffu, odd ? s2a : s2b, 1);
        float u3 = (odd ? db : da) + __shfl_xor_sync(0xffffffffu, odd ? da : db, 1);
        u1 += __shfl_xor_sync(0xffffffffu, u1, 2); u2 += __shfl_xor_sync(0xffffffffu, u2, 2); u3 += __shfl_xor_sync(0xffffffffu, u3, 2);
        if (!(lane & 2)) st_ll(sp, __float_as_uint(u1), __float_as_uint(u2), __float_as_uint(u3), tag);
      }
      PROFW(t256 == 0, L * 8 + 7);
      if (L) {
        mbar_wait(BAR(B_PAR), 0);
        { float2 pa = lds64f(sb + PAR + (grow & 127) * 8), pb = lds64f(sb + PAR + (grow & 127) * 8 + 64); al0 = pa.x; be0 = pa.y; al1 = pb.x; be1 = pb.y; }
        uint32_t rs[32];
        #pragma unroll
        for (int j = 0; j < 16; j++) {
          rs[2 * j] = pack_bf16(fmaf(acc[4 * j], al0, be0), fmaf(acc[4 * j + 1], al0, be0));
          rs[2 * j + 1] = pack_bf16(fmaf(acc[4 * j + 2], al1, be1), fmaf(acc[4 * j + 3], al1, be1));
        }
        #pragma unroll
        for (int jj = 0; jj < 8; jj++) stsm_x4((xa + (jj >> 2) * 32768) ^ ((jj & 3) << 5), rs[4 * jj], rs[4 * jj + 1], rs[4 * jj + 2], rs[4 * jj + 3]);
        PROFW(t256 == 0, 16);
        if (fid >= 112) bar_arrive(3, 384);
        else {
          float d[4] = {0.f, 0.f, 0.f, 0.f};
          mbar_wait(BAR(B_FULLW + wg * 3), 0); mbar_wait(BAR(B_FULLW + wg * 3 + 1), 0);
          bar_sync(3, 384);
          PROFW(t256 == 0, 29);
          #pragma unroll 1
          for (int g = 0; g < 4; g++) {
            const uint32_t ad = (sb16 + (wg ? 6144 : 10240) + (g >> 1) * 2048 + (g & 1) * 512) | (1024u << 16), bd = (sb16 + (HV >> 4) + wg * 64 + g * 16) | 0x10000u;
            wg_fence();
            #pragma unroll
            for (int ks = 0; ks < 8; ks++) wgmma_ss_n8<0, 1>(d, mkd<HI64>(ad + ks * 64), mkd<8>(bd + ks * 2), 1);
            wg_commit();
          }
          mbar_wait(BAR(B_FULLW + 2), 0);
          wg_wait<0>(); keep(d);
          if (!(lane & 3)) { sts32f(sb + PAR + 1024 + wg * 256 + w * 64 + lane, d[0]); sts32f(sb + PAR + 1056 + wg * 256 + w * 64 + lane, d[2]); }
          bar_sync(1, 256);
          const uint32_t ga = sb + PAR + 1024 + lane * 4, aa = sb + HV + (t256 >> 5) * 128;
          sts32f(aa + lane * 4, swiglu(lds32f(ga) + lds32f(ga + 256), lds32f(ga + 128) + lds32f(ga + 384)));
          __syncwarp();
          PROFW(t256 == 0, 26);
          float y0 = 0.f, y1 = 0.f, y2 = 0.f, y3 = 0.f;
          uint32_t tbl = rh ? 0x001459a8u : 0x023679a8u;
          uint4 a4 = lds128(aa + 112);
          #pragma unroll 2
          for (int n = 0; n < 8; n++, tbl >>= 4) {
            const uint32_t src = sb + t256 * 8 + (tbl & 15) * 8192;
            const uint4 an = lds128(aa + ((0x00123564u >> (4 * n)) & 15) * 16);
            #pragma unroll
            for (int e = 0; e < 4; e++) {
              const float av = __uint_as_float(e == 0 ? a4.x : (e == 1 ? a4.y : (e == 2 ? a4.z : a4.w)));
              y0 = fmaf(bf_lo(wd[e].x), av, y0); y1 = fmaf(bf_hi(wd[e].x), av, y1); y2 = fmaf(bf_lo(wd[e].y), av, y2); y3 = fmaf(bf_hi(wd[e].y), av, y3);
              const float2 v = lds64f(src + e * 2048); wd[e] = make_uint2(__float_as_uint(v.x), __float_as_uint(v.y));
            }
            a4 = an;
          }
          st_ll(yp, __float_as_uint(y0), __float_as_uint(y1), __float_as_uint(y2), (__float_as_uint(y3) & ~255u) | (lds32(sb + INFO + 12) + 1));
          PROFW(t256 == 0, 27);
        }
        return;
      }
      mbar_wait(BAR(B_XRDY + wg * 2 + 1), 0);
    }
  }
  #undef IDS
  #undef LAYER
}

DEVI void loader(const Params& P, uint32_t sb) {
  const int lane = threadIdx.x & 31;
  const int bid = uni(BID), bi = bid >> 4, bp = bid & 15, rh = bp & 1, bc = bp >> 1;
  uint32_t phq = 0, tag = 0;
  #pragma unroll 1
  for (int L = 0; L < 2; L++) {
    int s = 0;
    uint32_t rdy = 0;
    #pragma unroll 1
    for (int n = L ? 0 : 3; n < 16; n++) {
      int kb = L ? kb_order(bc, n) : n;
      mbar_wait(BAR(B_EMPTYQ + s), (phq >> s) & 1);
      phq ^= 1u << s;
      if (L && n == 1) { mbar_wait(BAR(B_XRDY + 1), 0); mbar_wait(BAR(B_XRDY + 3), 0); }
      if (elect()) {
        mbar_expect_tx(BAR(B_FULLQ + s), L && n < 2 ? 40960 : 57344);
        tma_3d_h(sb + qb_off(s), &P.mWq, bp * 64, kb * 64, 0, BAR(B_FULLQ + s), L && n >= QEF_N ? POL_FIRST : POL_NORMAL);
        if (!L) tma_2d(sb + qa_off(s), &P.mX, kb * 64, bi * 256, BAR(B_FULLQ + s));
      }
      if (L && n >= 2) {
        if (((rdy >> (2 * kb)) & 3) != 3) {
          do { rdy = __ballot_sync(0xffffffffu, ld_rlx(&P.g->flagX[bi][lane]) == tag); } while (((rdy >> (2 * kb)) & 3) != 3);
          fence_async_glob();
        }
        if (n == 3 || n == 4) mbar_wait(BAR(B_XFREE + n - 3), 0);
        if (elect()) bulk_g2s_h(sb + qa_off(s), P.g->x[bi][kb], 32768, BAR(B_FULLQ + s), POL_X);
      }
      PROFY(L && lane == 0 && (n == 2 || n == 3 || n == 9), n == 9 ? 60 : 56 + n);
      if (L && n == 2) { mbar_wait(BAR(B_FULLQ), 0); mbar_wait(BAR(B_FULLQ + 1), 1); if (lane < 2) mbar_arrive_peer(BAR(B_XFREE + lane)); }
      s = (s == 2) ? 0 : s + 1;
    }
    for (int q = 0; q < 3; q++) mbar_wait(BAR(B_EMPTYQ + q), (phq >> q) & 1);
    tag = lds32(sb + INFO + 8) + L;
    #pragma unroll 1
    for (int q = 0; q < 4; q++) {
            if (bi) {
        const unsigned* f = &P.g->flagKV[bid - 16][q];
        while (ld_rlx(f) != tag);
        fence_async_glob();
      }
      if (elect()) {
        mbar_expect_tx(BAR(B_KVFULL + q), 16384);
        bulk_g2s_h(sb + ((q >> 1) ? KVB : KVA) + ((q & 1) ? 0 : 16384), bi ? P.g->kv[bid - 16][q] : P.g->zero, 16384, BAR(B_KVFULL + q));
      }
      PROFY(!L && lane == 0 && bi && q != 2, 34 + (q + 1) / 2);
    }
    mbar_wait(BAR(B_ORDY), L);
    {
      const uint4* src = P.g->o[bi][0][0][rh];
      rdy = 0;
      #pragma unroll 1
      for (int n = 0, q = 0; n < 16; q = w_next(n, q), n++) {
        const int j = wo_order(bc, n);
        if (((rdy >> (2 * j)) & 3) != 3) {
          do { rdy = __ballot_sync(0xffffffffu, ld_rlx(&P.g->flagO[bi][lane]) == tag); } while (((rdy >> (2 * j)) & 3) != 3);
          fence_async_glob();
        }
        if (n >= 2) mbar_wait(n < 5 ? BAR(B_HAFREE + (n > 2)) : BAR(B_EMPTYW + q), n < 5 ? L : w_par(n, q, L) ^ 1);
        if (n == THR_N) mbar_wait(BAR(B_OFREE), L);
        if (elect()) { mbar_expect_tx(BAR(B_FULLW + q), 16384); bulk_g2s_h(sb + w_off(q), src + j * 2048, 16384, BAR(B_FULLW + q)); }
      }
    }
    mbar_wait(BAR(B_OFREE), L);
  }
}

DEVI void ffn_prefetch(const Params& P, int q) {
  bulk_prefetch(q < 16 ? ((q & 1) ? P.wu : P.wg) + ((q >> 1) * 128 + blockIdx.x) * 3584 : P.wd + (min(FID, 111) * 8 + q - 16) * 4096, q < 16 ? 7168 : 8192);
}
DEVI void storer(const Params& P, uint32_t sb, int wg) {
  const int bid = uni(BID), bi = bid >> 4, rh = bid & 1, bc = (bid & 15) >> 1;
  const bool one = (threadIdx.x & 31) == 0;
  char* const g = (char*)P.g;
  const uint32_t tag0 = uni(((ld_rlx(&P.g->epoch) % 16383u) + 1u) << 2);
  #pragma unroll 1
  for (int L = 0; L < 2; L++) {
    const uint32_t tag = tag0 + L;
    if (wg) {
      #pragma unroll 1
      for (int r = threadIdx.x & 31; r < 256; r += 32) {
        uint4 v;
        do v = ld_ll(&P.g->statF[bi * 256 + r]); while (!__all_sync(0xffffffffu, v.w == tag));
        float var = __uint_as_float(v.y), c = rsqrtf(var + LN_EPS);
        if (L) { c += 1.f; c *= rsqrtf(fmaf(var * c, c, LN_EPS)); }
        const float mh = bf_round(__uint_as_float(v.x));
        sts64f(sb + PAR + r * 8, c, __uint_as_float(pack_bf16(mh, __uint_as_float(v.x) - mh)));
      }
      if (!L) mbar_wait(BAR(B_PAR), 0);
      warp_signal(BAR(B_ROW));
    }
    #pragma unroll 1
    for (int u = 0; u < 2 + 4 * wg; u++) {
      const int h = u < 2 ? u : u >> 2, hi = (u & 1) ^ 1;
      uint32_t src, dst, fl, b0, b1;
      if (u < 2) {
        src = (h ? KVB : KVA) + (3 - wg) * 16384; dst = offsetof(Scratch, kv) + (bid * 4 + h * 2 + wg) * 16384; fl = offsetof(Scratch, flagKV) + (bid * 32 + h * 2 + wg) * 4;
        b0 = BAR(B_KVRDY + ((u | wg) ? 1 : 0)); b1 = b0 + 16;
      } else {
        src = QO + (h * 2 + hi) * 8192; dst = offsetof(Scratch, o) + ((((bi * 2 + h) * 8 + bc) * 2 + hi) * 2 + rh) * 8192;
        fl = offsetof(Scratch, flagO) + (bi * 32 + h * 16 + (bid & 15)) * 4;
        b0 = BAR(B_ORDY + u - 2); b1 = b0 + 32;
      }
      mbar_wait(b0, L); mbar_wait(b1, L);
      if (u + wg == 1) {
        mbar_wait(BAR(B_PAR), L);
        const uint32_t t0 = clk(), dt = (wg ? KV_D1 : KV_D2) + (L ? KV_DL : 0); while (clk() - t0 < dt) __nanosleep(40);
      }
      fence_async_smem();
      PROFY(one && !L && u == 3 * wg, u ? 46 : 8);
      if (one && (u >= 2 || bi < 7)) bulk_s2g(g + dst, sb + src, u < 2 ? 16384 : 8192);
      if (one && u == 5) mbar_arrive(BAR(B_HAFREE + 1));
      if (u == 2 || u == 4) continue;
      bulk_wait<0>();
      PROFY(one && !L && u == 3 * wg, u ? 61 : 62);
      fence_rel();
      if (one) { st_rlx((unsigned*)(g + fl), tag); if (!wg || u > 2) mbar_arrive(BAR(B_HAFREE + h + (wg & h))); }
      PROFY(one && !L && (u > 2 || u == wg), u > 2 ? (u == 3 ? 38 : 54) : 32 + u);
    }
    if (L == 0) {
      char* dst = g + (offsetof(Scratch, x) + (bi * 16 + 2 * bc) * 32768 + rh * 16384);
      unsigned* f = (unsigned*)(g + (offsetof(Scratch, flagX) + (bi * 32 + bc * 4 + rh) * 4));
      const uint32_t a = sb + rh * 16384;
      if (wg == 0) {
        mbar_wait(BAR(B_XRDY), 0); mbar_wait(BAR(B_XRDY + 2), 0);
        fence_async_smem();
        PROFY(one, 41);
        if (one) bulk_s2g(dst, a, 16384);
        bulk_wait<0>();
        PROFY(one, 45);
        if (one) { mbar_arrive(BAR(B_XFREE)); mbar_arrive(BAR(B_PFREE)); }
        fence_rel();
        mbar_wait(BAR(B_XRDY + 1), 0); mbar_wait(BAR(B_XRDY + 3), 0);
        if (one) { st_rlx(f, tag); bulk_s2g(dst + 32768, a + 32768, 16384); }
        PROFY(one, 56);
        bulk_wait<0>();
        if (one) mbar_arrive(BAR(B_XFREE + 1));
        fence_rel();
        if (one) st_rlx(f + 2, tag);
        PROFY(one, 57);
      } else {
        mbar_wait(BAR(B_XRDY + 1), 0); mbar_wait(BAR(B_XRDY + 3), 0);
        mbar_wait(BAR(B_PFREE), 0);
        if (one) bulk_s2peer(a, 16384, BAR(B_FULLQ));
        { const uint32_t t0 = clk(); while (clk() - t0 < XD_D); }
        if (one) bulk_s2peer(a + 32768, 16384, BAR(B_FULLQ + 1));
      }
      if (wg == 0) {
        uint32_t t0 = clk() + PF1_D;
        #pragma unroll 1
        for (int q = PF1_S; q < PF1_E; q++) { while ((int)(clk() - t0) < 0) __nanosleep(50); if (one) ffn_prefetch(P, q); t0 += PF1_T; }
      }
    }
  }
}

DEVI void stg_issue(const Params& P, int c, uint32_t d, uint32_t du, uint32_t b) {
  mbar_expect_tx(b, 16384);
  if (c < 8) { tma_2d_h(d, &P.mWg, FID * 32, c * 128, b, POL_G); tma_2d_h(d + du, &P.mWu, FID * 32, c * 128, b, POL_U); }
  else if (c < 12) tma_3d_h(d, &P.mWd, 0, FID * 32 + (c - 8) * 8, 0, b, POL_D);
  else tma_2d_h(d, &P.mWp, (c - 12) * 1024 + (BID >> 2) * 32, (BID & 3) * 256, b, POL_EF);
}
DEVI void pace() { const uint32_t t0 = clk(); while (clk() - t0 < PACE_T); }
DEVI void stager(const Params& P, uint32_t sb) {
  {
    const int b = blockIdx.x;
    uint32_t t0 = clk();
    #pragma unroll 1
    for (int q = 0; q < PQ_N; q++) { bulk_prefetch(P.wqkv + (q * 128 + b) * 3072, 6144); while (clk() - t0 < PQ_T) __nanosleep(50); t0 += PQ_T; }
    bulk_prefetch(P.wo + b * 8192, 16384);
    #pragma unroll 1
    for (int q = 0; q < PF0_N; q++) {
      while (clk() - t0 < PF0_T) __nanosleep(50);
      t0 += PF0_T;
      ffn_prefetch(P, q);
    }
  }
  const int bid = BID, bi = bid >> 4, rh = bid & 1, bc = (bid & 15) >> 1;
  #pragma unroll 1
  for (int L = 0; L < 2; L++) {
    const int nch = L ? (FID < 112 ? 8 : 0) : 15;
    mbar_wait(BAR(B_PAR), L); mbar_wait(BAR(B_KVFULL + W0_BAR), L);
    #pragma unroll 1
    for (int n = 0, q = 0; n < 16; q = w_next(n, q), n++) {
      if (n >= 2) mbar_wait(n < 5 ? BAR(B_HAFREE + (n > 2)) : BAR(B_EMPTYW + q), n < 5 ? L : w_par(n, q, L) ^ 1);
      if (n == THR_N) mbar_wait(BAR(B_OFREE), L);
      mbar_expect_tx(BAR(B_FULLW + q), 16384);
      tma_5d(sb + w_off(q) + 16384, &P.mWo, 0, 0, n >> 3, 2 * (wo_order(bc, n) & 7), 2 * bc, BAR(B_FULLW + q), L ? POL_EF : POL_NORMAL);
      if (n == 2) {
        #pragma unroll 1
        for (int e = 0; e < 2; e++) {
          mbar_expect_tx(BAR(B_FULLW + 5), 16384);
          if (L) bulk_g2s_h(sb + 32768 + e * 16384, P.g->x[bi][2 * bc + e] + rh * 1024, 16384, BAR(B_FULLW + 5));
          else tma_2d_h(sb + 32768 + e * 16384, &P.mXh, bc * 128 + e * 64, bi * 256 + rh * 128, BAR(B_FULLW + 5), POL_EF);
        }
      }
    }
    mbar_wait(BAR(B_EMPTYW + 5), L);
    if (L && nch) {
      const bf16* src = WDSRC2;
      mbar_expect_tx(BAR(B_FULLW + 2), 32768); mbar_expect_tx(BAR(B_FULLW + 2), 24576);
      #pragma unroll 1
      for (int e = 0; e < 3; e++) { bulk_g2s_h(sb + e * 32768 + (e < 2 ? (rh ^ 1) * 16384 : 0), src + e * 8192, e < 2 ? 16384 : 24576, BAR(B_FULLW + 2)); pace(); }
    }
        if (L == 0) { mbar_arrive_peer(BAR(B_PFREE)); mbar_wait(BAR(B_EMPTYW), 0); mbar_wait(BAR(B_EMPTYW + 1), 0); }
    #pragma unroll 1
    for (int c = FID < 112 ? 0 : 12, slot = 0; c < nch; c++, slot = slot == 2 ? 0 : slot + 1) {
      const int q = (c >> 1) + (c >> 2);
      if (!L && (c == LATE_C || c == 12)) mbar_wait(BAR(LATE_B), LATE_P);
      mbar_wait(L ? BAR(B_EMPTYW + q) : BAR(B_STGE + slot), L | ((0x71c7 >> c) & 1));
      #define CC c
      stg_issue(P, CC, L ? sb + w_off(q) + (c & 1) * 8192 : sb + STG + slot * 16384, 8192 << L, L ? BAR(B_FULLW + q) : BAR(B_STG + slot));
      if (L) pace();
    }
  }
}
DEVI void sum8(uint4 v, float& s1, float& s2) {
  float e[8] = {bf_lo(v.x), bf_hi(v.x), bf_lo(v.y), bf_hi(v.y), bf_lo(v.z), bf_hi(v.z), bf_lo(v.w), bf_hi(v.w)};
  #pragma unroll
  for (int q = 0; q < 8; q++) { s1 += e[q]; s2 = fmaf(e[q], e[q], s2); }
}
DEVI uint4 norm8(uint4 x, float m, float rs) {
  #define HN(v) pack_bf16((bf_lo(v) - m) * rs, (bf_hi(v) - m) * rs)
  return make_uint4(HN(x.x), HN(x.y), HN(x.z), HN(x.w));
  #undef HN
}
DEVI void put_f32(uint4 b, uint32_t d, uint32_t d2) {
  sts128(d, make_uint4(b.x << 16, b.x & 0xffff0000u, b.y << 16, b.y & 0xffff0000u));
  sts128(d + d2, make_uint4(b.z << 16, b.z & 0xffff0000u, b.w << 16, b.w & 0xffff0000u));
}
DEVI void put_bf16(uint4 b, uint32_t d) {
  sts64f(d, __uint_as_float(b.x), __uint_as_float(b.y)); sts64f(d + 1024, __uint_as_float(b.z), __uint_as_float(b.w));
  fence_async_smem();
}
DEVI uint4 best4(uint32_t p) {
  uint4 a = lds128(p), b = lds128(p + 16), c = lds128(p + 32), d = lds128(p + 48);
  if (b.x > a.x) a = b;
  if (d.x > c.x) c = d;
  return c.x > a.x ? c : a;
}
#define FL(x) __uint_as_float(x)
#define UI(x) __float_as_uint(x)
DEVI void aux(const Params& P, uint32_t sb) {
  int tid = fresh_tid();
  #define lane (tid & 31)
  #define wq (tid >> 5)
  uint32_t ids = P.map[blockIdx.x], tag;
  #define bid ((int)(ids & 255))
  #define fid ((int)(ids >> 8))
  #define bi (bid >> 4)
  #define bp (bid & 15)
  #define bc (bp >> 1)
  #define FRESH() do { tid = fresh_tid(); uint4 z_ = ldsv128(sb + INFO2 + 16); ids = z_.y; tag = z_.z + L; idx = z_.w; } while (0)
  {
    const uint32_t epoch = ld_rlx(&P.g->epoch);
    if (tid == 0) {
      mbar_expect_tx(BAR(B_STG), 49152);
      tma_3d(sb + STG, &P.mWq, bp * 64, bi * 128, 0, BAR(B_STG));
      tma_3d(sb + STG + 24576, &P.mWq, bp * 64, bi * 128 + 64, 0, BAR(B_STG));
    }
    __syncwarp();
    sts64f(sb + ONES + tid * 8, FL(0x3F803F80u), FL(0x3F803F80u));
    float s1 = 0.f, s2 = 0.f;
    { uint4 v = __ldg((const uint4*)P.wr + tid);
      if ((tid >> 4) == bc) put_f32(v, sb + WR + (tid & 15) * 32, 16);
      sum8(v, s1, s2);
      #pragma unroll 1
      for (int o = 16; o; o >>= 1) s1 += __shfl_xor_sync(0xffffffffu, s1, o);
      sts32f(sb + INFO2 + wq * 4, s1); }
    const uint4* src = (const uint4*)(P.x0 + (size_t)bid * 16384) + (tid >> 3) * 128 + (tid & 7);
    s1 = 0.f; s2 = 0.f;
    #pragma unroll 1
    for (int it = 0; it < 16; it += 4) {
      uint4 v0 = __ldg(src + it * 8), v1 = __ldg(src + it * 8 + 8), v2 = __ldg(src + it * 8 + 16), v3 = __ldg(src + it * 8 + 24);
      #pragma unroll 1
      for (int q = 0; q < 4; q++) { sum8(v0, s1, s2); v0 = v1; v1 = v2; v2 = v3; }
    }
    #pragma unroll 1
    for (int o = 1; o < 8; o <<= 1) { s1 += __shfl_xor_sync(0xffffffffu, s1, o); s2 += __shfl_xor_sync(0xffffffffu, s2, o); }
    tag = ((epoch % 16383u) + 1u) << 2;
    if (tid == 0) { sts128(sb + INFO, make_uint4(0x40000000u, 0u, tag, ((epoch % 127u) + 1u) << 1)); sts128(sb + INFO2 + 16, make_uint4(epoch, ids, tag, 0x40000000u)); }
    float m = s1 * (1.f / 1024.f);
    if ((tid & 7) == 0) st_ll(&P.g->statF[bid * 16 + (tid >> 3)], UI(m), UI(fmaxf(fmaf(-m, m, s2 * (1.f / 1024.f)), 0.f)), 0u, tag);
    bar_sync(2, 128);
    mbar_wait_b(BAR(B_STG), 0);
    if (tid < 96) {
      s1 = 0.f; s2 = 0.f;
      #pragma unroll 1
      for (int r = 0; r < 16; r++) {
        const uint32_t a = sb + STG + (r >> 3) * 24576 + wq * 8192 + (r & 7) * 128 + ((lane * 4) ^ ((r & 7) << 4));
        #pragma unroll
        for (int e = 0; e < 8; e++) { uint32_t v = lds32(a + e * 1024); s1 += bf_lo(v); s2 += bf_hi(v); }
      }
      st_ll(&P.g->csP[bp][bi][tid], UI(s1), UI(s2), 0u, tag);
      s1 = 0.f; s2 = 0.f;
      #pragma unroll 1
      for (int q = 0; q < 8; q += 2) {
        uint4 a, b; poll_ll2(&P.g->csP[bp][q][tid], &P.g->csP[bp][q + 1][tid], 0xffffffffu, tag, a, b);
        s1 += FL(a.x) + FL(b.x); s2 += FL(a.y) + FL(b.y);
      }
      const uint32_t hi = pack_bf16(-s1, -s2);
      sts32(sb + CS + (tid >> 2) * 32 + (tid & 3) * 4, hi);
      sts32(sb + CS + (tid >> 2) * 32 + (tid & 3) * 4 + 16, pack_bf16(-s1 - bf_lo(hi), -s2 - bf_hi(hi)));
    }
    fence_async_smem();
  }
  int idx;
  #pragma unroll 1
  for (int L = 0; L < 2; L++) {
    FRESH();
    {
      if ((unsigned)(bi - (idx >> 8)) < 2u) {
        const uint4* src = &P.g->patch[bp * 8 + (tid >> 6) * 4][tid & 63];
        uint4 v0, v1, v2, v3; int it = 0;
        do { v0 = ld_ll(src); v1 = ld_ll(src + 64); v2 = ld_ll(src + 128); v3 = ld_ll(src + 192); if (++it > SPIN_MAX) __trap(); }
        while (!__all_sync(0xffffffffu, v0.w == tag && v1.w == tag && v2.w == tag && v3.w == tag));
        float q = (FL(v0.x) + FL(v1.x)) + (FL(v2.x) + FL(v3.x)), k = (FL(v0.y) + FL(v1.y)) + (FL(v2.y) + FL(v3.y)), v = (FL(v0.z) + FL(v1.z)) + (FL(v2.z) + FL(v3.z));
        q += __shfl_xor_sync(0xffffffffu, q, 1); k += __shfl_xor_sync(0xffffffffu, k, 1); v += __shfl_xor_sync(0xffffffffu, v, 1);
        bar_sync(2, 128);
        const uint32_t d = sb + PATCH + (tid & ~1), kv = pack_bf16(k, v);
        sts16(d, pack_bf16(q * QSCALE, 0.f)); sts16(d + 128, kv); sts16(d + 256, kv >> 16);
      }
      sts32(sb + INFO, idx);
      bar_sync(2, 128);
    }
    const uint4 fix = lds128(sb + PATCH + 128 + (lane & 4) * 32 + (wq >> 1) * 64 + (lane & 3) * 16);
    warp_signal(BAR(B_PAR));
    PROFX(tid == 0, L ? 23 : 17);
    mbar_wait_b(BAR(B_KVFULL + wq), L);
    if ((idx >> 7) == bi * 2 - 1 - (wq & 1)) {
      if (lane < 8) sts128(sb + ((wq >> 1) ? KVB : KVA) + ((idx >> 6) & 3) * 8192 + (lane >> 2) * 4096 + (idx & 63) * 64 + (((lane ^ (idx >> 1)) & 3) << 4), fix);
      fence_async_smem();
    }
    bar_arrive(4 + wq, 160); bar_arrive(8 + wq, 160);
    FRESH();
    mbar_wait_b(BAR(B_OFREE), L);
    #define blk (bi * 2 + (bid & 1))
    if (tid < 33) st_ll(tid < 32 ? &P.g->row[blk][bc * 32 + tid] : &P.g->best[bc][blk], 0u, 0u, 0u, 0u);
    mbar_wait_b(BAR(B_XRDY + 1), L); mbar_wait_b(BAR(B_XRDY + 3), L);
    PROFX(tid == 0, 37 + L * 16);
    FRESH();
    {
      float s1 = 0.f, s2 = 0.f, d = 0.f;
      #pragma unroll 1
      for (int q = 0; q < 8; q += 4) {
        const uint4* src = &P.g->statP[q][blk * 128 + tid];
        uint4 v0, v1, v2, v3; int it = 0;
        do { v0 = ld_ll(src); v1 = ld_ll(src + 2048); v2 = ld_ll(src + 4096); v3 = ld_ll(src + 6144); if (++it > SPIN_MAX) __trap(); }
        while (!__all_sync(0xffffffffu, v0.w == tag && v1.w == tag && v2.w == tag && v3.w == tag));
        s1 += (FL(v0.x) + FL(v1.x)) + (FL(v2.x) + FL(v3.x)); s2 += (FL(v0.y) + FL(v1.y)) + (FL(v2.y) + FL(v3.y)); d += (FL(v0.z) + FL(v1.z)) + (FL(v2.z) + FL(v3.z));
      }
      PROFX(tid == 0, 39 + L * 16);
      uint4 a = lds128(sb + INFO2), b, c;
      float m = s1 * (1.f / 1024.f), var = fmaxf(fmaf(-m, m, s2 * (1.f / 1024.f)), 0.f), rs = rsqrtf(var + LN_EPS);
      uint32_t key = UI(fmaf(-m, (FL(a.x) + FL(a.y)) + (FL(a.z) + FL(a.w)), d) * rs);
      key ^= (uint32_t)((int)key >> 31) | 0x80000000u;
      uint32_t win = __ballot_sync(0xffffffffu, key == __reduce_max_sync(0xffffffffu, key));
      if (lane == __ffs(win) - 1) sts128(sb + RED + wq * 16, make_uint4(key, UI(m), UI(rs), (tag << 11) | (uint32_t)(blk * 128 + tid)));
      if (L) sts64f(sb + PAR + tid * 8, 1.f + rs, -m * rs);
      else if ((tid >> 4) == bc) st_ll(&P.g->statF[blk * 128 + tid], UI(m), UI(var), 0u, tag + 1);
      bar_sync(2, 128);
      if (wq == 0) {
        a = best4(sb + RED);
        float2 v = lds64f(sb + (lane >> 4) * 32768 + (a.w & 255) * 128 + (((lane & 15) * 8) ^ ((a.w & 7) << 4)));
        st_ll(&P.g->row[blk][bc * 32 + lane], UI(v.x), UI(v.y), 0u, tag);
        if (lane == 0) st_ll(&P.g->best[bc][blk], a.x, a.y, a.z, a.w);
        __syncwarp();
        if (lane < 2 + 2 * L) mbar_arrive(L ? BAR(B_PAR) : BAR(B_XFREE + lane));
      }
      PROFX(tid == 0, 18 + L * 6);
      FRESH();
      a = poll_ll(&P.g->best[bc][lane & 15], 0xfffff800u, tag << 11);
      win = __ffs(__ballot_sync(0xffffffffu, a.x == __reduce_max_sync(0xffffffffu, a.x))) - 1;
      idx = __shfl_sync(0xffffffffu, a.w, win) & 2047;
      PROFX(tid == 0, 19 + L * 6);
      poll_ll2(&P.g->row[win][tid], &P.g->row[win][tid + 128], 0xffffffffu, tag, c, b);
      c.z = b.x; c.w = b.y;
      a.x = __shfl_sync(0xffffffffu, a.x, win); a.y = __shfl_sync(0xffffffffu, a.y, win); a.z = __shfl_sync(0xffffffffu, a.z, win);
      sts32(sb + INFO2 + 28, idx);
      PROFX(tid == 0, 61 + L);
      b = norm8(c, FL(a.y), FL(a.z));
      if (L) put_bf16(b, sb + HV + tid * 8); else put_f32(b, sb + HV + tid * 16, 2048);
      if ((tid >> 1) == (bid & 63)) {
        sts128(sb + RED + 64 + (tid & 1) * 16, bid < 64 ? make_uint4(c.x, c.y, b.x, b.y) : make_uint4(c.z, c.w, b.z, b.w));
        sts32(sb + RED + 96, a.x);
      }
      bar_sync(2 + L, 128 + L * 256);
      if (L) {
        const int r0 = blk * 128 + (tid >> 4);
        uint32_t src = sb + ((tid >> 3) & 1) * 32768 + (r0 & 255) * 128 + (((tid ^ r0) & 7) << 4);
        uint4* dst = (uint4*)(P.out + (size_t)r0 * 1024 + bc * 128) + (tid & 15);
        #pragma unroll 4
        for (int it = 0; it < 16; it++) { uint4 v = lds128(src + it * 1024); if (idx - r0 != it * 8) dst[it * 1024] = v; }
      }
    }
    #pragma unroll 1
    for (int st = L; st < 2; st++) {
      FRESH();
      float a[8] = {0.f, 0.f, 0.f, 0.f, 0.f, 0.f, 0.f, 0.f};
      if (L == 0 && fid < 112) {
        uint32_t ha = st ? sb + RED + 768 : sb + HV + ((wq & 1) * 64 + (lane >> 2)) * 4;
        uint32_t ph = st ? 0x1cu : 0x171u, bar = st ? BAR(B_STG + 2) : BAR(B_STG);
        uint32_t wa = sb + STG + wq * 4096 + (st ? 32768 + lane * 16 : (lane ^ (lane >> 3)) * 16);
        const uint32_t hx = st ? 256 : 512;
        const bool lead = lane == 0;
        uint4 vc = make_uint4(0u, 0u, 0u, 0u); float hc = 0.f;
        #pragma unroll 1
        do {
          mbar_wait(bar, ph & 1);
          PROFX(lead && threadIdx.x == 256 && st == 0 && (ph > 255 || ph < 4), 40 - 23 + __clz(ph));
          #pragma unroll
          for (int n = 0; n < 8; n++) { const uint4 v = lds128(wa + n * 512); const float h = lds32f(ha + n * 32); fma8(a, vc, hc); vc = v; hc = h; }
          __syncwarp();
          if (lead) mbar_arrive(bar - 8 * (B_STG - B_STGE));
          const bool wrap = bar == BAR(B_STG + 2);
          bar += wrap ? -16 : 8; wa += wrap ? -32768 : 16384; ha += hx;
          ph >>= 1;
        } while (ph != 1);
        fma8(a, vc, hc);
      }
      FRESH();
      if (st == 1) {
        const uint32_t t8 = lds32(sb + INFO + 12) + L;
        if (L == 0 && fid < 112) {
          const bool odd = lane & 1;
          #pragma unroll
          for (int e = 0; e < 4; e++) { float z = __shfl_xor_sync(0xffffffffu, odd ? a[e] : a[4 + e], 1); if (odd) a[e] = z; else a[4 + e] = z; }
          uint4* dst = &P.g->yP[tid & ~1][fid][tid & 1];
          st_ll(dst, UI(a[0]), UI(a[1]), UI(a[2]), (UI(a[3]) & ~255u) | t8);
          st_ll(dst + 224, UI(a[4]), UI(a[5]), UI(a[6]), (UI(a[7]) & ~255u) | t8);
          PROFX(tid == 0, 21);
        }
        if (tid == 0) { uint32_t k = lds32(sb + RED + 96); sts32f(sb + RED + 100, bf_round(__fdividef(1.f, 1.f + __expf(-bf_round(FL(k ^ (~(uint32_t)((int)k >> 31) | 0x80000000u))))))); }
        uint4 v0, v1;
        poll_ll2(&P.g->yP[bid][0][min(tid, 111)], &P.g->yP[bid][0][min(tid, 111) + 112], 255u, t8, v0, v1);
        const float lo = (tid < 112 && !(tid & 1)) ? 1.f : 0.f, hi = (tid < 112 && (tid & 1)) ? 1.f : 0.f;
        const float y0 = FL(v0.x) + FL(v1.x), y1 = FL(v0.y) + FL(v1.y), y2 = FL(v0.z) + FL(v1.z), y3 = FL((v0.w & ~255u) | 128u) + FL((v1.w & ~255u) | 128u);
        a[0] = y0 * lo; a[1] = y1 * lo; a[2] = y2 * lo; a[3] = y3 * lo; a[4] = y0 * hi; a[5] = y1 * hi; a[6] = y2 * hi; a[7] = y3 * hi;
      }
      sts32f(sb + RED + 256 + wq * 128 + ((lane & 3) * 8 + (lane >> 2)) * 4, fold8(a));
      bar_sync(2, 128);
      const uint32_t d = sb + RED + 256 + lane * 4;
      float z0 = lds32f(d) + lds32f(d + 128), z1 = lds32f(d + 256) + lds32f(d + 384);
      if (st == 0) {
        sts32f(sb + RED + 768 + lane * 32 + wq * 4, swiglu(z0, z1));
        bar_sync(2, 128);
        if (fid < 112) { st_ll(&P.g->yP[tid & ~1][fid][tid & 1], 0u, 0u, 0u, 0u); st_ll(&P.g->yP[tid | 1][fid][tid & 1], 0u, 0u, 0u, 0u); }
        else { const uint32_t t0 = clk(); while (clk() - t0 < IDLE_T) __nanosleep(200); }
        if (tid < 80) st_ll(tid < 64 ? &P.g->patch[bid][tid] : &P.g->x2[(tid >> 1) & 7][2 * bid + (tid & 1)], 0u, 0u, 0u, 0u);
        PROFX(tid == 0, 20); continue; }
      z0 += z1;
      z0 += __shfl_xor_sync(0xffffffffu, z0, 8); z0 += __shfl_xor_sync(0xffffffffu, z0, 16);
      uint32_t xw = lds32(sb + RED + 64 + (lane & 4) * 4 + (lane & 2) * 2), hw = lds32(sb + RED + 72 + (lane & 4) * 4 + (lane & 2) * 2);
      z0 = bf_round(((lane & 1) ? bf_hi(hw) : bf_lo(hw)) + bf_round(bf_round(z0) * lds32f(sb + RED + 100))) + ((lane & 1) ? bf_hi(xw) : bf_lo(xw));
      uint32_t v = pack_bf16(z0, __shfl_down_sync(0xffffffffu, z0, 1)), v2 = __shfl_down_sync(0xffffffffu, v, 2);
      if (L) { if (tid == 0 || tid == 4) *(uint2*)(P.out + (size_t)idx * 1024 + bid * 8 + tid) = make_uint2(v, v2); PROFW(tid == 0, 28); }
      else if ((tid & 3) == 0 && tid < 64) st_ll(&P.g->x2[tid >> 3][2 * bid + ((tid >> 2) & 1)], v, v2, 0u, tag + 1);
    }
    if (L == 0) {
      PROFX(tid == 0, 22);
      FRESH();
      uint4 x, y; poll_ll2(&P.g->x2[bi][tid], &P.g->x2[bi][tid + 128], 0xffffffffu, tag + 1, x, y);
      x.z = y.x; x.w = y.y;
      if (wq == (bc & 3)) sts64f(sb + X2SEG + lane * 8, FL(bc < 4 ? x.x : x.z), FL(bc < 4 ? x.y : x.w));
      float s1 = 0.f, s2 = 0.f;
      sum8(x, s1, s2);
      #pragma unroll
      for (int o = 16; o; o >>= 1) { s1 += __shfl_xor_sync(0xffffffffu, s1, o); s2 += __shfl_xor_sync(0xffffffffu, s2, o); }
      sts64f(sb + RED + wq * 8, s1, s2);
      bar_sync(2, 128);
      y = lds128(sb + RED); uint4 y2 = lds128(sb + RED + 16);
      float m = ((FL(y.x) + FL(y.z)) + (FL(y2.x) + FL(y2.z))) * (1.f / 1024.f);
      put_bf16(norm8(x, m, rsqrtf(fmaxf(fmaf(-m, m, ((FL(y.y) + FL(y.w)) + (FL(y2.y) + FL(y2.w))) * (1.f / 1024.f)), 0.f) + LN_EPS)), sb + HV + tid * 8);
      mbar_wait(BAR(B_STG), 1); mbar_wait(BAR(B_STG + 1), 0); mbar_wait(BAR(B_STG + 2), 0);
      bar_sync(2, 128);
      PROFX(tid == 0, 30);
      float d0[4] = {0.f, 0.f, 0.f, 0.f}, d1[4] = {0.f, 0.f, 0.f, 0.f}, d2[4] = {0.f, 0.f, 0.f, 0.f};
      const uint32_t bd = (64 + (HV >> 4) + uni(bid & 3) * 32) | 0x10000u;
      #pragma unroll 1
      for (int ks = 0; ks < 8; ks++) {
        const uint32_t ad = (64 + (STG >> 4) + ks * 128) | (64u << 16);
        wg_fence();
        wgmma_ss_n8<0, 1>(d0, mkd<HI64>(ad), mkd<8>(bd + ks * 4), 1);
        wgmma_ss_n8<0, 1>(d1, mkd<HI64>(ad + 1024), mkd<8>(bd + ks * 4), 1);
        wgmma_ss_n8<0, 1>(d2, mkd<HI64>(ad + 2048), mkd<8>(bd + ks * 4), 1);
        wg_commit();
      }
      wg_wait<0>(); keep(d0); keep(d1); keep(d2);
      FRESH();
      if ((lane & 3) == (wq >> 1)) {
        uint4* dst = &P.g->patch[bid][(wq & 1) * 32 + (lane >> 2) * 2 + (wq >> 1)];
        st_ll(dst, UI(d0[0]), UI(d1[0]), UI(d2[0]), tag + 1); st_ll(dst + 16, UI(d0[2]), UI(d1[2]), UI(d2[2]), tag + 1);
      }
      PROFX(tid == 0, 31);
    }
  }
  if (bid == 0 && tid == 0) P.g->epoch = lds32(sb + INFO2 + 16) + 1;
  #undef blk
  #undef bid
  #undef fid
  #undef bi
  #undef bp
  #undef bc
  #undef FRESH
  #undef lane
  #undef wq
}

__global__ void __cluster_dims__(2, 1, 1) __launch_bounds__(512, 1) fused_kernel(const __grid_constant__ Params P) {
  extern __shared__ __align__(1024) uint8_t smem_raw[];
  const uint32_t sb = smem_u32(smem_raw);
  PROFT(threadIdx.x == 0, 0);
  if (threadIdx.x < 32) { if (elect()) {
    for (int s = 0; s < 3; s++) mbar_init(BAR(B_FULLQ + s), 1);
    asm volatile("fence.mbarrier_init.release.cluster;" ::: "memory");
    #pragma unroll 1
    for (int s = 0; s < 3; s++) {
      mbar_expect_tx(BAR(B_FULLQ + s), 57344);
      tma_2d(sb + qa_off(s), &P.mX, s * 64, (BID >> 4) * 256, BAR(B_FULLQ + s));
      tma_3d(sb + qb_off(s), &P.mWq, (BID & 15) * 64, s * 64, 0, BAR(B_FULLQ + s));
    }
    if ((sb & 0x3FFFFu) != 1024) __trap();
  } } else if (threadIdx.x == 480) {
    asm volatile("prefetch.tensormap [%0];" :: "l"(&P.mWq) : "memory");
  } else if (threadIdx.x >= 32 && !(threadIdx.x & 28) && (threadIdx.x >> 3) + (threadIdx.x & 3) <= B_COUNT + 1) {
    int b = (threadIdx.x >> 3) + (threadIdx.x & 3) - 1;
    if (b == B_COUNT) b = B_ROW;
    const uint32_t cnt = b < B_XFREE ? (b == B_OFREE ? 1 : 2) : (b < B_KVRDY ? 3 : (b < B_KVFULL || b == B_PAR ? 4 : (b == B_PFREE ? 2 : 1)));
    mbar_init(BAR(b), cnt);
    asm volatile("fence.mbarrier_init.release.cluster;" ::: "memory");
  }
  __syncthreads();
  asm volatile("barrier.cluster.arrive.relaxed.aligned;" ::: "memory");
  const int wg = __shfl_sync(0xffffffffu, threadIdx.x >> 7, 0);
  if (wg < 2) { reg_inc<224>(); consumer(P, sb, wg); }
  else if (wg == 2) { reg_dec<40>(); aux(P, sb); }
  else {
    reg_dec<24>();
    asm volatile("barrier.cluster.wait.aligned;" ::: "memory");
    const int w = __shfl_sync(0xffffffffu, (threadIdx.x >> 5) & 3, 0);
    if (w == 0) loader(P, sb);
    else if (w < 3) storer(P, sb, w - 1);
    else if (elect()) stager(P, sb);
  }
}

typedef CUresult (*EncFn)(CUtensorMap*, CUtensorMapDataType, cuuint32_t, void*, const cuuint64_t*, const cuuint64_t*, const cuuint32_t*, const cuuint32_t*,
                          CUtensorMapInterleave, CUtensorMapSwizzle, CUtensorMapL2promotion, CUtensorMapFloatOOBfill);
static void mk_map(EncFn enc, CUtensorMap* m, const void* ptr, int rank, const cuuint64_t* dims, const cuuint64_t* strides, const cuuint32_t* box,
                   CUtensorMapSwizzle sw, CUtensorMapL2promotion pr) {
  cuuint32_t es[5] = {1, 1, 1, 1, 1};
  enc(m, CU_TENSOR_MAP_DATA_TYPE_BFLOAT16, rank, (void*)ptr, dims, strides, box, es, CU_TENSOR_MAP_INTERLEAVE_NONE, sw, pr, CU_TENSOR_MAP_FLOAT_OOB_FILL_NONE);
}
extern "C" void kernel_launch(void* const* d_in, const int* in_sizes, int n_in, void* d_out, int out_size) {
  (void)in_sizes; (void)n_in; (void)out_size;
  void* fn = nullptr; cudaDriverEntryPointQueryResult q;
  cudaGetDriverEntryPoint("cuTensorMapEncodeTiled", &fn, cudaEnableDefault, &q);
  EncFn enc = (EncFn)fn;
  cudaFuncSetAttribute(fused_kernel, cudaFuncAttributeMaxDynamicSharedMemorySize, SMEM_BYTES);
  Params P;
  const CUtensorMapSwizzle S128 = CU_TENSOR_MAP_SWIZZLE_128B, S64 = CU_TENSOR_MAP_SWIZZLE_64B, S0 = CU_TENSOR_MAP_SWIZZLE_NONE;
  const CUtensorMapL2promotion L256 = CU_TENSOR_MAP_L2_PROMOTION_L2_256B, L128 = CU_TENSOR_MAP_L2_PROMOTION_L2_128B;
  { cuuint64_t d[2] = {1024, 2048}, s[1] = {2048}; cuuint32_t b[2] = {64, 256}, bh[2] = {64, 128};
    mk_map(enc, &P.mX, d_in[0], 2, d, s, b, S128, L256); mk_map(enc, &P.mXh, d_in[0], 2, d, s, bh, S128, L256); }
  { cuuint64_t d[3] = {1024, 1024, 3}, s[2] = {6144, 2048}; cuuint32_t b[3] = {64, 64, 3}; mk_map(enc, &P.mWq, d_in[1], 3, d, s, b, S128, L256); }
  { cuuint64_t d[5] = {64, 32, 2, 16, 16}, s[4] = {2048, 65536, 131072, 128}; cuuint32_t b[5] = {64, 32, 1, 2, 2}; mk_map(enc, &P.mWo, d_in[2], 5, d, s, b, S128, L256); }
  { cuuint64_t d[2] = {3584, 1024}, s[1] = {7168}; cuuint32_t b[2] = {32, 128};
    mk_map(enc, &P.mWg, d_in[5], 2, d, s, b, S64, L128); mk_map(enc, &P.mWu, d_in[6], 2, d, s, b, S64, L128); }
  { cuuint64_t d[2] = {3072, 1024}, s[1] = {6144}; cuuint32_t b[2] = {32, 256}; mk_map(enc, &P.mWp, d_in[1], 2, d, s, b, S64, L128); }
  { cuuint64_t d[3] = {256, 3584, 4}, s[2] = {2048, 512}; cuuint32_t b[3] = {256, 8, 4}; mk_map(enc, &P.mWd, d_in[7], 3, d, s, b, S0, L128); }
  P.x0 = (const bf16*)d_in[0]; P.wqkv = (const bf16*)d_in[1]; P.wo = (const bf16*)d_in[2]; P.wr = (const bf16*)d_in[4]; P.wg = (const bf16*)d_in[5]; P.wu = (const bf16*)d_in[6]; P.wd = (const bf16*)d_in[7];
  P.out = (bf16*)d_out;
  cudaGetSymbolAddress((void**)&P.g, g_scr);
  for (int b = 0; b < 128; b++) {
    int j = b >> 1, quad = j < 4 ? 0 : (j < 36 ? 1 + (j - 4) % 8 : 9 + (j - 36) % 7), pos = j < 4 ? j : (j < 36 ? (j - 4) / 8 : (j - 36) / 7);
    int bid = ((quad >> 2) * 2 + (pos >> 1)) * 16 + ((quad & 3) * 2 + (pos & 1)) * 2 + (b & 1);
    int e = pos * 2 + (b & 1), fid = e < 7 ? quad * 7 + e : 112 + quad;
    P.map[b] = bid | fid << 8;
  }
  fused_kernel<<<128, 512, SMEM_BYTES>>>(P);
}
```

```cpp
#include <cuda_runtime.h>
#include <cuda_bf16.h>
#include <cuda.h>
#include <stdint.h>
#include <stddef.h>
typedef __nv_bfloat16 bf16;

template<int TB, int TA = 0> __device__ __forceinline__ void wgmma_ss_n192(float (&d)[96], uint64_t da, uint64_t db, int scale_d) {
  asm volatile("{\n.reg .pred p;\nsetp.ne.b32 p, %98, 0;\n"
    "wgmma.mma_async.sync.aligned.m64n192k16.f32.bf16.bf16 {%0, %1, %2, %3, %4, %5, %6, %7, %8, %9, %10, %11, %12, %13, %14, %15, %16, %17, %18, %19, %20, %21, %22, %23, %24, %25, %26, %27, %28, %29, %30, %31, %32, %33, %34, %35, %36, %37, %38, %39, %40, %41, %42, %43, %44, %45, %46, %47, %48, %49, %50, %51, %52, %53, %54, %55, %56, %57, %58, %59, %60, %61, %62, %63, %64, %65, %66, %67, %68, %69, %70, %71, %72, %73, %74, %75, %76, %77, %78, %79, %80, %81, %82, %83, %84, %85, %86, %87, %88, %89, %90, %91, %92, %93, %94, %95}, %96, %97, p, 1, 1, %100, %99;\n}\n"
    : "+f"(d[0]), "+f"(d[1]), "+f"(d[2]), "+f"(d[3]), "+f"(d[4]), "+f"(d[5]), "+f"(d[6]), "+f"(d[7]), "+f"(d[8]), "+f"(d[9]), "+f"(d[10]), "+f"(d[11]), "+f"(d[12]), "+f"(d[13]), "+f"(d[14]), "+f"(d[15]), "+f"(d[16]), "+f"(d[17]), "+f"(d[18]), "+f"(d[19]), "+f"(d[20]), "+f"(d[21]), "+f"(d[22]), "+f"(d[23]), "+f"(d[24]), "+f"(d[25]), "+f"(d[26]), "+f"(d[27]), "+f"(d[28]), "+f"(d[29]), "+f"(d[30]), "+f"(d[31]), "+f"(d[32]), "+f"(d[33]), "+f"(d[34]), "+f"(d[35]), "+f"(d[36]), "+f"(d[37]), "+f"(d[38]), "+f"(d[39]), "+f"(d[40]), "+f"(d[41]), "+f"(d[42]), "+f"(d[43]), "+f"(d[44]), "+f"(d[45]), "+f"(d[46]), "+f"(d[47]), "+f"(d[48]), "+f"(d[49]), "+f"(d[50]), "+f"(d[51]), "+f"(d[52]), "+f"(d[53]), "+f"(d[54]), "+f"(d[55]), "+f"(d[56]), "+f"(d[57]), "+f"(d[58]), "+f"(d[59]), "+f"(d[60]), "+f"(d[61]), "+f"(d[62]), "+f"(d[63]), "+f"(d[64]), "+f"(d[65]), "+f"(d[66]), "+f"(d[67]), "+f"(d[68]), "+f"(d[69]), "+f"(d[70]), "+f"(d[71]), "+f"(d[72]), "+f"(d[73]), "+f"(d[74]), "+f"(d[75]), "+f"(d[76]), "+f"(d[77]), "+f"(d[78]), "+f"(d[79]), "+f"(d[80]), "+f"(d[81]), "+f"(d[82]), "+f"(d[83]), "+f"(d[84]), "+f"(d[85]), "+f"(d[86]), "+f"(d[87]), "+f"(d[88]), "+f"(d[89]), "+f"(d[90]), "+f"(d[91]), "+f"(d[92]), "+f"(d[93]), "+f"(d[94]), "+f"(d[95])
    : "l"(da), "l"(db), "r"(scale_d), "n"(TB), "n"(TA));
}

template<int TB> __device__ __forceinline__ void wgmma_rs_n192(float (&d)[96], uint32_t a0, uint32_t a1, uint32_t a2, uint32_t a3, uint64_t db, int scale_d) {
  asm volatile("{\n.reg .pred p;\nsetp.ne.b32 p, %101, 0;\n"
    "wgmma.mma_async.sync.aligned.m64n192k16.f32.bf16.bf16 {%0, %1, %2, %3, %4, %5, %6, %7, %8, %9, %10, %11, %12, %13, %14, %15, %16, %17, %18, %19, %20, %21, %22, %23, %24, %25, %26, %27, %28, %29, %30, %31, %32, %33, %34, %35, %36, %37, %38, %39, %40, %41, %42, %43, %44, %45, %46, %47, %48, %49, %50, %51, %52, %53, %54, %55, %56, %57, %58, %59, %60, %61, %62, %63, %64, %65, %66, %67, %68, %69, %70, %71, %72, %73, %74, %75, %76, %77, %78, %79, %80, %81, %82, %83, %84, %85, %86, %87, %88, %89, %90, %91, %92, %93, %94, %95}, {%96, %97, %98, %99}, %100, p, 1, 1, %102;\n}\n"
    : "+f"(d[0]), "+f"(d[1]), "+f"(d[2]), "+f"(d[3]), "+f"(d[4]), "+f"(d[5]), "+f"(d[6]), "+f"(d[7]), "+f"(d[8]), "+f"(d[9]), "+f"(d[10]), "+f"(d[11]), "+f"(d[12]), "+f"(d[13]), "+f"(d[14]), "+f"(d[15]), "+f"(d[16]), "+f"(d[17]), "+f"(d[18]), "+f"(d[19]), "+f"(d[20]), "+f"(d[21]), "+f"(d[22]), "+f"(d[23]), "+f"(d[24]), "+f"(d[25]), "+f"(d[26]), "+f"(d[27]), "+f"(d[28]), "+f"(d[29]), "+f"(d[30]), "+f"(d[31]), "+f"(d[32]), "+f"(d[33]), "+f"(d[34]), "+f"(d[35]), "+f"(d[36]), "+f"(d[37]), "+f"(d[38]), "+f"(d[39]), "+f"(d[40]), "+f"(d[41]), "+f"(d[42]), "+f"(d[43]), "+f"(d[44]), "+f"(d[45]), "+f"(d[46]), "+f"(d[47]), "+f"(d[48]), "+f"(d[49]), "+f"(d[50]), "+f"(d[51]), "+f"(d[52]), "+f"(d[53]), "+f"(d[54]), "+f"(d[55]), "+f"(d[56]), "+f"(d[57]), "+f"(d[58]), "+f"(d[59]), "+f"(d[60]), "+f"(d[61]), "+f"(d[62]), "+f"(d[63]), "+f"(d[64]), "+f"(d[65]), "+f"(d[66]), "+f"(d[67]), "+f"(d[68]), "+f"(d[69]), "+f"(d[70]), "+f"(d[71]), "+f"(d[72]), "+f"(d[73]), "+f"(d[74]), "+f"(d[75]), "+f"(d[76]), "+f"(d[77]), "+f"(d[78]), "+f"(d[79]), "+f"(d[80]), "+f"(d[81]), "+f"(d[82]), "+f"(d[83]), "+f"(d[84]), "+f"(d[85]), "+f"(d[86]), "+f"(d[87]), "+f"(d[88]), "+f"(d[89]), "+f"(d[90]), "+f"(d[91]), "+f"(d[92]), "+f"(d[93]), "+f"(d[94]), "+f"(d[95])
    : "r"(a0), "r"(a1), "r"(a2), "r"(a3), "l"(db), "r"(scale_d), "n"(TB));
}

template<int TB, int TA = 0> __device__ __forceinline__ void wgmma_ss_n128(float (&d)[64], uint64_t da, uint64_t db, int scale_d) {
  asm volatile("{\n.reg .pred p;\nsetp.ne.b32 p, %66, 0;\n"
    "wgmma.mma_async.sync.aligned.m64n128k16.f32.bf16.bf16 {%0, %1, %2, %3, %4, %5, %6, %7, %8, %9, %10, %11, %12, %13, %14, %15, %16, %17, %18, %19, %20, %21, %22, %23, %24, %25, %26, %27, %28, %29, %30, %31, %32, %33, %34, %35, %36, %37, %38, %39, %40, %41, %42, %43, %44, %45, %46, %47, %48, %49, %50, %51, %52, %53, %54, %55, %56, %57, %58, %59, %60, %61, %62, %63}, %64, %65, p, 1, 1, %68, %67;\n}\n"
    : "+f"(d[0]), "+f"(d[1]), "+f"(d[2]), "+f"(d[3]), "+f"(d[4]), "+f"(d[5]), "+f"(d[6]), "+f"(d[7]), "+f"(d[8]), "+f"(d[9]), "+f"(d[10]), "+f"(d[11]), "+f"(d[12]), "+f"(d[13]), "+f"(d[14]), "+f"(d[15]), "+f"(d[16]), "+f"(d[17]), "+f"(d[18]), "+f"(d[19]), "+f"(d[20]), "+f"(d[21]), "+f"(d[22]), "+f"(d[23]), "+f"(d[24]), "+f"(d[25]), "+f"(d[26]), "+f"(d[27]), "+f"(d[28]), "+f"(d[29]), "+f"(d[30]), "+f"(d[31]), "+f"(d[32]), "+f"(d[33]), "+f"(d[34]), "+f"(d[35]), "+f"(d[36]), "+f"(d[37]), "+f"(d[38]), "+f"(d[39]), "+f"(d[40]), "+f"(d[41]), "+f"(d[42]), "+f"(d[43]), "+f"(d[44]), "+f"(d[45]), "+f"(d[46]), "+f"(d[47]), "+f"(d[48]), "+f"(d[49]), "+f"(d[50]), "+f"(d[51]), "+f"(d[52]), "+f"(d[53]), "+f"(d[54]), "+f"(d[55]), "+f"(d[56]), "+f"(d[57]), "+f"(d[58]), "+f"(d[59]), "+f"(d[60]), "+f"(d[61]), "+f"(d[62]), "+f"(d[63])
    : "l"(da), "l"(db), "r"(scale_d), "n"(TB), "n"(TA));
}

template<int TB, int TA = 0> __device__ __forceinline__ void wgmma_ss_n64(float (&d)[32], uint64_t da, uint64_t db, int scale_d) {
  asm volatile("{\n.reg .pred p;\nsetp.ne.b32 p, %34, 0;\n"
    "wgmma.mma_async.sync.aligned.m64n64k16.f32.bf16.bf16 {%0, %1, %2, %3, %4, %5, %6, %7, %8, %9, %10, %11, %12, %13, %14, %15, %16, %17, %18, %19, %20, %21, %22, %23, %24, %25, %26, %27, %28, %29, %30, %31}, %32, %33, p, 1, 1, %36, %35;\n}\n"
    : "+f"(d[0]), "+f"(d[1]), "+f"(d[2]), "+f"(d[3]), "+f"(d[4]), "+f"(d[5]), "+f"(d[6]), "+f"(d[7]), "+f"(d[8]), "+f"(d[9]), "+f"(d[10]), "+f"(d[11]), "+f"(d[12]), "+f"(d[13]), "+f"(d[14]), "+f"(d[15]), "+f"(d[16]), "+f"(d[17]), "+f"(d[18]), "+f"(d[19]), "+f"(d[20]), "+f"(d[21]), "+f"(d[22]), "+f"(d[23]), "+f"(d[24]), "+f"(d[25]), "+f"(d[26]), "+f"(d[27]), "+f"(d[28]), "+f"(d[29]), "+f"(d[30]), "+f"(d[31])
    : "l"(da), "l"(db), "r"(scale_d), "n"(TB), "n"(TA));
}

template<int TB, int TA = 0> __device__ __forceinline__ void wgmma_ss_n8(float (&d)[4], uint64_t da, uint64_t db, int scale_d) {
  asm volatile("{\n.reg .pred p;\nsetp.ne.b32 p, %6, 0;\n"
    "wgmma.mma_async.sync.aligned.m64n8k16.f32.bf16.bf16 {%0, %1, %2, %3}, %4, %5, p, 1, 1, %8, %7;\n}\n"
    : "+f"(d[0]), "+f"(d[1]), "+f"(d[2]), "+f"(d[3])
    : "l"(da), "l"(db), "r"(scale_d), "n"(TB), "n"(TA));
}

template<int TB> __device__ __forceinline__ void wgmma_rs_n40(float (&d)[20], uint32_t a0, uint32_t a1, uint32_t a2, uint32_t a3, uint64_t db, int scale_d) {
  asm volatile("{\n.reg .pred p;\nsetp.ne.b32 p, %25, 0;\n"
    "wgmma.mma_async.sync.aligned.m64n40k16.f32.bf16.bf16 {%0, %1, %2, %3, %4, %5, %6, %7, %8, %9, %10, %11, %12, %13, %14, %15, %16, %17, %18, %19}, {%20, %21, %22, %23}, %24, p, 1, 1, %26;\n}\n"
    : "+f"(d[0]), "+f"(d[1]), "+f"(d[2]), "+f"(d[3]), "+f"(d[4]), "+f"(d[5]), "+f"(d[6]), "+f"(d[7]), "+f"(d[8]), "+f"(d[9]), "+f"(d[10]), "+f"(d[11]), "+f"(d[12]), "+f"(d[13]), "+f"(d[14]), "+f"(d[15]), "+f"(d[16]), "+f"(d[17]), "+f"(d[18]), "+f"(d[19])
    : "r"(a0), "r"(a1), "r"(a2), "r"(a3), "l"(db), "r"(scale_d), "n"(TB));
}

#define DEVI __device__ __forceinline__
DEVI uint32_t smem_u32(const void* p) { return (uint32_t)__cvta_generic_to_shared(p); }
DEVI void mbar_init(uint32_t bar, uint32_t cnt) { asm volatile("mbarrier.init.shared::cta.b64 [%0], %1;" :: "r"(bar), "r"(cnt)); }
DEVI void mbar_expect_tx(uint32_t bar, uint32_t bytes) { asm volatile("mbarrier.arrive.expect_tx.shared::cta.b64 _, [%0], %1;" :: "r"(bar), "r"(bytes) : "memory"); }
DEVI void mbar_arrive(uint32_t bar) { asm volatile("mbarrier.arrive.shared::cta.b64 _, [%0];" :: "r"(bar) : "memory"); }
DEVI void mbar_arrive_peer(uint32_t bar) {
  asm volatile("{\n.reg .b32 ra;\nmapa.shared::cluster.u32 ra, %0, %1;\nmbarrier.arrive.shared::cluster.b64 _, [ra];\n}" :: "r"(bar), "r"((blockIdx.x & 1) ^ 1) : "memory");
}
DEVI void bulk_s2peer(uint32_t a, uint32_t bytes, uint32_t bar) {
  asm volatile("{\n.reg .b32 ra, rb;\nmapa.shared::cluster.u32 ra, %0, %3;\nmapa.shared::cluster.u32 rb, %2, %3;\n"
               "cp.async.bulk.shared::cluster.shared::cta.mbarrier::complete_tx::bytes [ra], [%0], %1, [rb];\n}"
               :: "r"(a), "r"(bytes), "r"(bar), "r"((blockIdx.x & 1) ^ 1) : "memory");
}
DEVI void mbar_wait(uint32_t bar, uint32_t parity) {
  asm volatile("{\n.reg .pred p;\nLW:\nmbarrier.try_wait.parity.shared::cta.b64 p, [%0], %1;\n@!p bra LW;\n}" :: "r"(bar), "r"(parity) : "memory");
}
DEVI uint32_t mbar_test(uint32_t bar, uint32_t parity) {
  uint32_t r; asm volatile("{\n.reg .pred p;\nmbarrier.test_wait.parity.shared::cta.b64 p, [%1], %2;\nselp.u32 %0, 1, 0, p;\n}" : "=r"(r) : "r"(bar), "r"(parity) : "memory"); return r;
}
DEVI void mbar_wait_b(uint32_t bar, uint32_t parity) {
  asm volatile("{\n.reg .pred p;\n.reg .u32 it;\nmov.u32 it, 0;\nLW:\nmbarrier.try_wait.parity.shared::cta.b64 p, [%0], %1;\n@p bra LD;\n"
               "add.u32 it, it, 1;\nsetp.lt.u32 p, it, 0x1000000;\n@p bra LW;\ntrap;\nLD:\n}" :: "r"(bar), "r"(parity) : "memory");
}
DEVI void tma_2d(uint32_t dst, const CUtensorMap* m, int c0, int c1, uint32_t bar) {
  asm volatile("cp.async.bulk.tensor.2d.shared::cluster.global.mbarrier::complete_tx::bytes [%0], [%1, {%3, %4}], [%2];"
    :: "r"(dst), "l"(m), "r"(bar), "r"(c0), "r"(c1) : "memory");
}
DEVI void tma_3d(uint32_t dst, const CUtensorMap* m, int c0, int c1, int c2, uint32_t bar) {
  asm volatile("cp.async.bulk.tensor.3d.shared::cluster.global.mbarrier::complete_tx::bytes [%0], [%1, {%3, %4, %5}], [%2];"
    :: "r"(dst), "l"(m), "r"(bar), "r"(c0), "r"(c1), "r"(c2) : "memory");
}
#define POL_EF POL_FIRST
constexpr uint64_t POL_FIRST = 0x12F0000000000000ull, POL_NORMAL = 0x1000000000000000ull;
DEVI void tma_2d_h(uint32_t dst, const CUtensorMap* m, int c0, int c1, uint32_t bar, uint64_t pol) {
  asm volatile("cp.async.bulk.tensor.2d.shared::cluster.global.mbarrier::complete_tx::bytes.L2::cache_hint [%0], [%1, {%3, %4}], [%2], %5;"
    :: "r"(dst), "l"(m), "r"(bar), "r"(c0), "r"(c1), "l"(pol) : "memory");
}
DEVI void tma_3d_h(uint32_t dst, const CUtensorMap* m, int c0, int c1, int c2, uint32_t bar, uint64_t pol) {
  asm volatile("cp.async.bulk.tensor.3d.shared::cluster.global.mbarrier::complete_tx::bytes.L2::cache_hint [%0], [%1, {%3, %4, %5}], [%2], %6;"
    :: "r"(dst), "l"(m), "r"(bar), "r"(c0), "r"(c1), "r"(c2), "l"(pol) : "memory");
}
DEVI void bulk_g2s_h(uint32_t s, const void* g, uint32_t bytes, uint32_t bar, uint64_t pol = POL_EF) {
  asm volatile("cp.async.bulk.shared::cluster.global.mbarrier::complete_tx::bytes.L2::cache_hint [%0], [%1], %2, [%3], %4;"
    :: "r"(s), "l"(g), "r"(bytes), "r"(bar), "l"(pol) : "memory");
}
DEVI void tma_5d(uint32_t dst, const CUtensorMap* m, int c0, int c1, int c2, int c3, int c4, uint32_t bar, uint64_t pol) {
  asm volatile("cp.async.bulk.tensor.5d.shared::cluster.global.mbarrier::complete_tx::bytes.L2::cache_hint [%0], [%1, {%3, %4, %5, %6, %7}], [%2], %8;"
    :: "r"(dst), "l"(m), "r"(bar), "r"(c0), "r"(c1), "r"(c2), "r"(c3), "r"(c4), "l"(pol) : "memory");
}
DEVI void tma_prefetch_2d(const CUtensorMap* m, int c0, int c1) {
  asm volatile("cp.async.bulk.prefetch.tensor.2d.L2.global.tile [%0, {%1, %2}];" :: "l"(m), "r"(c0), "r"(c1) : "memory");
}
DEVI void tma_prefetch_3d(const CUtensorMap* m, int c0, int c1, int c2) {
  asm volatile("cp.async.bulk.prefetch.tensor.3d.L2.global.tile [%0, {%1, %2, %3}];" :: "l"(m), "r"(c0), "r"(c1), "r"(c2) : "memory");
}
DEVI void bulk_prefetch(const void* g, uint32_t bytes) { asm volatile("cp.async.bulk.prefetch.L2.global [%0], %1;" :: "l"(g), "r"(bytes) : "memory"); }
DEVI void bulk_g2s(uint32_t s, const void* g, uint32_t bytes, uint32_t bar) {
  asm volatile("cp.async.bulk.shared::cluster.global.mbarrier::complete_tx::bytes [%0], [%1], %2, [%3];" :: "r"(s), "l"(g), "r"(bytes), "r"(bar) : "memory");
}
DEVI void bulk_s2g(void* g, uint32_t s, uint32_t bytes) {
  asm volatile("cp.async.bulk.global.shared::cta.bulk_group [%0], [%1], %2;\ncp.async.bulk.commit_group;" :: "l"(g), "r"(s), "r"(bytes) : "memory");
}
template<int N> DEVI void bulk_wait() { asm volatile("cp.async.bulk.wait_group %0;" :: "n"(N) : "memory"); }
DEVI void fence_async_smem() { asm volatile("fence.proxy.async.shared::cta;" ::: "memory"); }
DEVI void fence_async_glob() { asm volatile("fence.proxy.async.global;" ::: "memory"); }
DEVI unsigned ld_rlx(const unsigned* p) { unsigned v; asm volatile("ld.relaxed.gpu.global.u32 %0, [%1];" : "=r"(v) : "l"(p) : "memory"); return v; }
DEVI void st_rlx(unsigned* p, unsigned v) { asm volatile("st.relaxed.gpu.global.u32 [%0], %1;" :: "l"(p), "r"(v) : "memory"); }
DEVI uint2 ldg_stream(const uint2* p) { uint2 v; asm volatile("ld.global.nc.L1::no_allocate.v2.u32 {%0, %1}, [%2];" : "=r"(v.x), "=r"(v.y) : "l"(p)); return v; }
DEVI void fence_rel() { asm volatile("fence.release.gpu;" ::: "memory"); }
DEVI uint4 ld_ll(const uint4* p) {
  uint4 v;
  asm volatile("{\n.reg .b128 t;\n.reg .b64 a, b;\nld.relaxed.gpu.global.b128 t, [%4];\nmov.b128 {a, b}, t;\nmov.b64 {%0, %1}, a;\nmov.b64 {%2, %3}, b;\n}"
               : "=r"(v.x), "=r"(v.y), "=r"(v.z), "=r"(v.w) : "l"(p) : "memory");
  return v;
}
DEVI void st_ll(uint4* p, uint32_t x, uint32_t y, uint32_t z, uint32_t w) {
  asm volatile("{\n.reg .b128 t;\n.reg .b64 a, b;\nmov.b64 a, {%1, %2};\nmov.b64 b, {%3, %4};\nmov.b128 t, {a, b};\nst.relaxed.gpu.global.b128 [%0], t;\n}"
               :: "l"(p), "r"(x), "r"(y), "r"(z), "r"(w) : "memory");
}
#define SPIN_MAX 0x1000000
DEVI uint4 poll_ll(const uint4* p, uint32_t mask, uint32_t tag) {
  uint4 v; int it = 0;
  do { v = ld_ll(p); if (++it > SPIN_MAX) __trap(); } while (!__all_sync(0xffffffffu, (v.w & mask) == tag));
  return v;
}
DEVI void poll_ll2(const uint4* p, const uint4* q, uint32_t mask, uint32_t tag, uint4& a, uint4& b) {
  int it = 0;
  do { a = ld_ll(p); b = ld_ll(q); if (++it > SPIN_MAX) __trap(); } while (!__all_sync(0xffffffffu, (a.w & mask) == tag && (b.w & mask) == tag));
}
DEVI float4 poll_sum4(const uint4* src, int stride, uint32_t tag) {
  uint4 v0, v1, v2, v3; int it = 0;
  do { v0 = ld_ll(src); v1 = ld_ll(src + stride); v2 = ld_ll(src + 2 * stride); v3 = ld_ll(src + 3 * stride); if (++it > SPIN_MAX) __trap(); }
  while (!__all_sync(0xffffffffu, v0.w == tag && v1.w == tag && v2.w == tag && v3.w == tag));
  #define S4(f) ((__uint_as_float(v0.f) + __uint_as_float(v1.f)) + (__uint_as_float(v2.f) + __uint_as_float(v3.f)))
  return make_float4(S4(x), S4(y), S4(z), 0.f);
  #undef S4
}
DEVI void bar_sync(int id, int n) { asm volatile("bar.sync %0, %1;" :: "r"(id), "r"(n) : "memory"); }
DEVI void bar_arrive(int id, int n) { asm volatile("bar.arrive %0, %1;" :: "r"(id), "r"(n) : "memory"); }
DEVI void wg_fence() { asm volatile("wgmma.fence.sync.aligned;" ::: "memory"); }
DEVI void wg_commit() { asm volatile("wgmma.commit_group.sync.aligned;" ::: "memory"); }
template<int N> DEVI void wg_wait() { asm volatile("wgmma.wait_group.sync.aligned %0;" :: "n"(N) : "memory"); }
template<int N> DEVI void reg_inc() { asm volatile("setmaxnreg.inc.sync.aligned.u32 %0;" :: "n"(N)); }
template<int N> DEVI void reg_dec() { asm volatile("setmaxnreg.dec.sync.aligned.u32 %0;" :: "n"(N)); }
DEVI float ex2f(float x) { float y; asm("ex2.approx.ftz.f32 %0, %1;" : "=f"(y) : "f"(x)); return y; }
DEVI uint32_t pack_bf16(float lo, float hi) { uint32_t r; asm("cvt.rn.bf16x2.f32 %0, %1, %2;" : "=r"(r) : "f"(hi), "f"(lo)); return r; }
DEVI float bf_lo(uint32_t v) { return __uint_as_float(v << 16); }
DEVI float bf_hi(uint32_t v) { return __uint_as_float(v & 0xffff0000u); }
DEVI float bf_round(float x) { return bf_lo(pack_bf16(x, 0.f)); }
DEVI void stsm_x4(uint32_t addr, uint32_t a, uint32_t b, uint32_t c, uint32_t d) {
  asm volatile("stmatrix.sync.aligned.m8n8.x4.shared.b16 [%0], {%1,%2,%3,%4};" :: "r"(addr), "r"(a), "r"(b), "r"(c), "r"(d) : "memory");
}
DEVI void ldsm_x4(uint32_t addr, uint32_t& a, uint32_t& b, uint32_t& c, uint32_t& d) {
  asm volatile("ldmatrix.sync.aligned.m8n8.x4.shared.b16 {%0,%1,%2,%3}, [%4];" : "=r"(a), "=r"(b), "=r"(c), "=r"(d) : "r"(addr) : "memory");
}
DEVI uint4 lds128(uint32_t a) { uint4 v; asm volatile("ld.shared.v4.u32 {%0,%1,%2,%3}, [%4];" : "=r"(v.x), "=r"(v.y), "=r"(v.z), "=r"(v.w) : "r"(a) : "memory"); return v; }
DEVI void sts128(uint32_t a, uint4 v) { asm volatile("st.shared.v4.u32 [%0], {%1,%2,%3,%4};" :: "r"(a), "r"(v.x), "r"(v.y), "r"(v.z), "r"(v.w) : "memory"); }
DEVI float2 lds64f(uint32_t a) { float2 v; asm volatile("ld.shared.v2.f32 {%0,%1}, [%2];" : "=f"(v.x), "=f"(v.y) : "r"(a) : "memory"); return v; }
DEVI void sts64f(uint32_t a, float x, float y) { asm volatile("st.shared.v2.f32 [%0], {%1,%2};" :: "r"(a), "f"(x), "f"(y) : "memory"); }
DEVI uint32_t lds32(uint32_t a) { uint32_t v; asm volatile("ld.shared.u32 %0, [%1];" : "=r"(v) : "r"(a) : "memory"); return v; }
DEVI float lds32f(uint32_t a) { return __uint_as_float(lds32(a)); }
DEVI void sts32(uint32_t a, uint32_t v) { asm volatile("st.shared.u32 [%0], %1;" :: "r"(a), "r"(v) : "memory"); }
DEVI void sts32f(uint32_t a, float v) { sts32(a, __float_as_uint(v)); }
DEVI void sts16(uint32_t a, uint32_t v) { asm volatile("st.shared.u16 [%0], %1;" :: "r"(a), "h"((unsigned short)v) : "memory"); }
template<int N> DEVI void keep(float (&d)[N]) {
  #pragma unroll
  for (int i = 0; i < N; i++) asm volatile("" : "+f"(d[i]) :: "memory");
}
template<int N> DEVI void keep(uint32_t (&d)[N]) {
  #pragma unroll
  for (int i = 0; i < N; i++) asm volatile("" : "+r"(d[i]) :: "memory");
}
template<uint32_t HI> DEVI uint64_t mkd(uint32_t lo) { uint64_t r; asm("mov.b64 %0, {%1, %2};" : "=l"(r) : "r"(lo), "n"(HI)); return r; }
constexpr uint32_t HI128 = (1u << 30) | (1024 >> 4), HI64 = (2u << 30) | (512 >> 4);
#define VOFF(x) ((uint32_t)(x) * (uint32_t)(1 - 65536))
DEVI bool elect() { uint32_t p; asm volatile("{\n.reg .pred q;\nelect.sync _|q, 0xffffffff;\nselp.u32 %0, 1, 0, q;\n}" : "=r"(p)); return p; }
DEVI void warp_signal(uint32_t bar) { __syncwarp(); if (elect()) mbar_arrive(bar); }

struct Scratch {
  uint4 kv[128][4][1024];
  uint4 o[8][2][8][2][1024];
  uint4 x[8][16][2048];
  uint4 zero[1024];
  uint4 statP[8][2048];
  uint4 statF[2048];
  uint4 csP[16][8][96];
  uint4 best[8][16];
  uint4 row[16][256];
  uint4 yP[128][112][2];
  uint4 x2[8][256];
  uint4 patch[128][64];
  unsigned flagKV[128][32];
  unsigned flagO[8][32];
  unsigned flagX[8][32];
  unsigned epoch;
};
__device__ __align__(1024) Scratch g_scr;
#define PROFT(cond, slot)
#define PROFW(cond, slot)
#define PROFD(cond, slot)
#define PROFX(cond, slot)
#define PROFY(cond, slot)

constexpr uint32_t SB0 = 65536, HOLE = 90112, SA2 = 98304, SB1 = 131072, SB2 = 155648, STG = 180224;
constexpr uint32_t KVA = 0, KVB = 98304, QO = 65536;
constexpr uint32_t MISC = 229376, CS = MISC, ONES = MISC + 768, BARS = MISC + 1792, INFO = MISC + 2208, WR = MISC + 2224, X2SEG = MISC + 2736, INFO2 = MISC + 2992, DUMP = MISC + 3040;
constexpr uint32_t PAR = HOLE, HV = HOLE + 2048, RED = HOLE + 6144, PATCH = 196608;
constexpr uint32_t SMEM_BYTES = 232448;
enum { B_FULLQ = 0, B_EMPTYQ = 3, B_FULLW = 6, B_EMPTYW = 12, B_HAFREE = 18, B_OFREE = 20,
       B_XFREE = 21,
       B_KVRDY = 23, B_ORDY = 27, B_XRDY = 35, B_STGE = 39,
       B_KVFULL = 42, B_RES = 46, B_PAR = 47, B_STG = 48, B_PFREE = 51, B_COUNT = 52,
       B_ROW = 154 };
#define BAR(x) (sb + BARS + 8 * (x))
DEVI uint32_t qa_off(int s) { return s == 2 ? SA2 : (uint32_t)s * 32768u; }
DEVI uint32_t qb_off(int s) { return s == 0 ? SB0 : (s == 1 ? SB1 : SB2); }
DEVI int kb_order(int bc, int n) {
  const int e = n < 9 ? n - 2 : n - 9;
  return n < 2 ? 2 * bc + n : 2 * (((e < 4 ? e + 4 : e - 4 + (e - 4 >= (bc & 3))) + (bc & 4)) & 7) + (n >= 9);
}
DEVI int wo_order(int bc, int n) { return (n & 8) | ((n + (bc & 6)) & 7); }
DEVI uint32_t w_off(int s) { return (uint32_t)((0x143065 >> (4 * s)) & 7) * 32768u; }
DEVI uint32_t w_par(int n, int s, int L) { return (n >= 6 && n < 12) ^ (s == 5) ^ (s != 2 && L); }
DEVI int w_next(int n, int s) { return s == 5 ? 0 : (n == 13 ? 3 : s + 1); }

struct Params {
  CUtensorMap mX, mXh, mWq, mWo, mWg, mWu, mWp, mWd;
  const bf16 *x0, *wqkv, *wo, *wr, *wg, *wu, *wd;
  bf16* out;
  Scratch* g;
  unsigned map[128];
};
#define BID ((int)(P.map[blockIdx.x] & 255))
#define FID ((int)(P.map[blockIdx.x] >> 8))
DEVI uint32_t uni(uint32_t v) { return __shfl_sync(0xffffffffu, v, 0); }
#define PQ_N 8
#define PQ_T 700
#define PF0_N 10
#define PF0_T 1600
#define PF1_E 24
#define PF1_T 1100
#define POL_Q1 POL_NORMAL
#define POL_X POL_NORMAL
#define PFA0_BAR 3
#define PFA1_BAR 0
#define PFA0_M 0
#define PFA1_M 0
#define PFA0_T 900
#define PFA1_T 700
#define PF1_S PF0_N
#define PF1_D 0
#define POL_G POL_NORMAL
#define POL_U POL_FIRST
#define POL_D POL_FIRST
#define JQ_N 6
#define WDSRC (P.wd + (size_t)min(fid, 111) * 32768)
#define WDSRC2 (P.wd + FID * 32768)
#define WD_N 4
#define THR_N 5
#define KV_D 1800
#define XD_D 300
#define W0_BAR 3
#define QEF_N 99
#define PACE_T 300
#define IDLE_T 11000
#define LATE_C 2
#define LATE_B B_XFREE + 1
#define LATE_P 0
#define KV_D1 200
#define KV_D2 1200
#define KV_DL 0
#define POL_KV0 POL_FIRST
#define POL_KV1 POL_FIRST
#define POL_O0 POL_FIRST
#define POL_O1 POL_FIRST
#define POL_W0 POL_NORMAL
#define POL_W1 POL_FIRST
#define POL_Q0 POL_NORMAL
constexpr float LN_EPS = 1e-5f;
constexpr float QSCALE = 0.17677669529663687f * 1.4426950408889634f;

DEVI void fma8(float (&a)[8], uint4 v, float h) {
  a[0] = fmaf(bf_lo(v.x), h, a[0]); a[1] = fmaf(bf_hi(v.x), h, a[1]); a[2] = fmaf(bf_lo(v.y), h, a[2]); a[3] = fmaf(bf_hi(v.y), h, a[3]);
  a[4] = fmaf(bf_lo(v.z), h, a[4]); a[5] = fmaf(bf_hi(v.z), h, a[5]); a[6] = fmaf(bf_lo(v.w), h, a[6]); a[7] = fmaf(bf_hi(v.w), h, a[7]);
}
DEVI uint4 ldsv128(uint32_t a) { uint4 v; asm volatile("ld.volatile.shared.v4.u32 {%0,%1,%2,%3}, [%4];" : "=r"(v.x), "=r"(v.y), "=r"(v.z), "=r"(v.w) : "r"(a) : "memory"); return v; }
DEVI float ldsv32f(uint32_t a) { float v; asm volatile("ld.volatile.shared.f32 %0, [%1];" : "=f"(v) : "r"(a) : "memory"); return v; }
DEVI uint32_t clk() { uint32_t t; asm volatile("mov.u32 %0, %%clock;" : "=r"(t)); return t; }
DEVI int fresh_tid() { int t; asm volatile("mov.u32 %0, %%tid.x;" : "=r"(t)); return t & 127; }
DEVI float fold8(const float (&a)[8]) {
  const int lane = threadIdx.x & 31;
  const bool u = lane & 16, v = lane & 8, x = lane & 4;
  float b0 = (u ? a[4] : a[0]) + __shfl_xor_sync(0xffffffffu, u ? a[0] : a[4], 16), b1 = (u ? a[5] : a[1]) + __shfl_xor_sync(0xffffffffu, u ? a[1] : a[5], 16);
  float b2 = (u ? a[6] : a[2]) + __shfl_xor_sync(0xffffffffu, u ? a[2] : a[6], 16), b3 = (u ? a[7] : a[3]) + __shfl_xor_sync(0xffffffffu, u ? a[3] : a[7], 16);
  float c0 = (v ? b2 : b0) + __shfl_xor_sync(0xffffffffu, v ? b0 : b2, 8), c1 = (v ? b3 : b1) + __shfl_xor_sync(0xffffffffu, v ? b1 : b3, 8);
  return (x ? c1 : c0) + __shfl_xor_sync(0xffffffffu, x ? c0 : c1, 4);
}
DEVI float swiglu(float g, float u) { g = bf_round(g); return bf_round(bf_round(__fdividef(g, 1.f + __expf(-g))) * bf_round(u)); }

DEVI void qk_issue(float (&s)[32], uint32_t qd, uint32_t kd) {
  wgmma_ss_n64<0>(s, mkd<HI64>(qd), mkd<HI64>(kd), 0);
  wgmma_ss_n64<0>(s, mkd<HI64>(qd + 2), mkd<HI64>(kd + 2), 1);
}
template<int J0, int J1> DEVI void exp_pack(const float (&s)[32], uint32_t (&p)[16]) {
  #pragma unroll
  for (int j = J0; j < J1; j++) p[j] = pack_bf16(ex2f(s[2 * j]), ex2f(s[2 * j + 1]));
}
DEVI bool attn_pack(const float (&o)[20], uint32_t (&ob)[8]) {
  const float lo = 5.421010862427522e-20f, hi = 1.8446744073709552e19f;
  float i0, i1; asm("rcp.approx.ftz.f32 %0, %1;" : "=f"(i0) : "f"(o[16])); asm("rcp.approx.ftz.f32 %0, %1;" : "=f"(i1) : "f"(o[18]));
  #pragma unroll
  for (int e = 0; e < 8; e++) ob[e] = pack_bf16(o[2 * e] * ((e & 1) ? i1 : i0), o[2 * e + 1] * ((e & 1) ? i1 : i0));
  return __all_sync(0xffffffffu, o[16] >= lo && o[16] <= hi && o[18] >= lo && o[18] <= hi);
}
DEVI void attn_store(const uint32_t (&ob)[8], bool ok, uint32_t st, uint32_t sb, uint32_t bar) {
  stsm_x4(ok ? st : sb + DUMP, ob[0], ob[1], ob[2], ob[3]); stsm_x4(ok ? st ^ 32 : sb + DUMP, ob[4], ob[5], ob[6], ob[7]);
  __syncwarp();
  asm volatile("{\n.reg .pred p, q;\nelect.sync _|q, 0xffffffff;\nsetp.ne.and.u32 p, %1, 0, q;\n@p mbarrier.arrive.shared::cta.b64 _, [%0];\n}" :: "r"(bar), "r"((uint32_t)ok) : "memory");
}
DEVI void attn_exact(uint32_t st, uint32_t kv, int t, bool hasprev, uint32_t bar) {
  const int lane = threadIdx.x & 31;
  #pragma unroll 1
  for (int row = ((threadIdx.x >> 5) & 3) * 16, n = 0; n < 16; n++, row++) {
    const int k1 = 256 + t * 64 + row;
    float m = -INFINITY, l = 0.f, o = 0.f;
    #pragma unroll 1
    for (int k0 = hasprev ? k1 - 255 : 256; k0 <= k1; k0 += 32) {
      const int k = min(k0 + lane, k1), r = k & 63;
      float sc = 0.f;
      #pragma unroll 1
      for (int c = 0; c < 16; c++) {
        uint32_t a = lds32(st + row * 64 + ((c * 4) ^ ((row & 6) << 3))), b = lds32(kv + (k >> 6) * 8192 + r * 64 + ((c * 4) ^ ((r & 6) << 3)));
        sc = fmaf(bf_lo(a), bf_lo(b), fmaf(bf_hi(a), bf_hi(b), sc));
      }
      float mn = fmaxf(m, sc);
      #pragma unroll 1
      for (int x = 16; x; x >>= 1) mn = fmaxf(mn, __shfl_xor_sync(0xffffffffu, mn, x));
      const float al = ex2f(m - mn), pr = ex2f(sc - mn);
      m = mn; l *= al; o *= al;
      #pragma unroll 1
      for (int q = k0; q <= min(k0 + 31, k1); q++) {
        const float z = __shfl_sync(0xffffffffu, pr, q - k0);
        uint32_t b = lds32(kv + (q >> 6) * 8192 + 4096 + (q & 63) * 64 + (((lane >> 1) * 4) ^ ((q & 6) << 3)));
        l += z; o = fmaf(z, (lane & 1) ? bf_hi(b) : bf_lo(b), o);
      }
    }
    __syncwarp();
    sts16(st + row * 64 + ((lane * 2) ^ ((row & 6) << 3)), pack_bf16(__fdividef(o, l), 0.f));
  }
  warp_signal(bar);
}

template<int K0, int K1, int DONE = 0> DEVI void exp_pv(const float (&s)[32], uint32_t (&p)[16], float (&o)[20], uint32_t vd, bool accum) {
  #pragma unroll
  for (int ks = K0; ks < K1; ks++) {
    if (ks >= DONE) {
      #pragma unroll
      for (int j = 4 * ks; j < 4 * ks + 4; j++) p[j] = pack_bf16(ex2f(s[2 * j]), ex2f(s[2 * j + 1]));
    }
    asm volatile("" : "+r"(p[4 * ks]), "+r"(p[4 * ks + 1]), "+r"(p[4 * ks + 2]), "+r"(p[4 * ks + 3]));
    wg_fence();
    wgmma_rs_n40<1>(o, p[ks * 4], p[ks * 4 + 1], p[ks * 4 + 2], p[ks * 4 + 3], mkd<HI64>(vd + VOFF(ks * 64)), ks ? 1 : accum);
  }
}
DEVI void exp_pv2(const float (&s)[32], const float (&sx)[32], uint32_t (&p)[16], uint32_t (&px)[16], float (&o)[20], uint32_t v0, uint32_t v4,
                  const uint32_t (&msk)[9], int tdiag) {
  #pragma unroll
  for (int ks = 0; ks < 4; ks++) {
    #pragma unroll
    for (int j = 4 * ks; j < 4 * ks + 4; j++) {
      const int c = 8 * (j >> 1) - 8 * (j & 1);
      const uint32_t e = pack_bf16(ex2f(c > tdiag ? s[2 * j] : sx[2 * j]), ex2f(c + 1 > tdiag ? s[2 * j + 1] : sx[2 * j + 1])), m = msk[(j >> 1) - (j & 1) + 1];
      p[j] = e & m; px[j] = e & ~m;
      asm volatile("" : "+r"(p[j]), "+r"(px[j]));
    }
    wg_fence();
    wgmma_rs_n40<1>(o, p[ks * 4], p[ks * 4 + 1], p[ks * 4 + 2], p[ks * 4 + 3], mkd<HI64>(v0 + VOFF(ks * 64)), 1);
    wgmma_rs_n40<1>(o, px[ks * 4], px[ks * 4 + 1], px[ks * 4 + 2], px[ks * 4 + 3], mkd<HI64>(v4 + VOFF(ks * 64)), 1);
  }
}

template<int J0> DEVI void qkv_store(const float (&a)[96], float p0, float p1, uint32_t d) {
  #pragma unroll
  for (int hh = 0; hh < 2; hh++) {
    const int j = 4 * (J0 + 2 * hh);
    stsm_x4(d ^ (hh << 5), pack_bf16(a[j] * p0, a[j + 1] * p0), pack_bf16(a[j + 2] * p1, a[j + 3] * p1),
                           pack_bf16(a[j + 4] * p0, a[j + 5] * p0), pack_bf16(a[j + 6] * p1, a[j + 7] * p1));
  }
}
DEVI void mean_step(float (&a)[96], float m0, float m1, uint32_t cd, bool z) {
  const uint32_t u0 = z ? 0u : __float_as_uint(m0), u1 = z ? 0u : __float_as_uint(m1);
  uint32_t ma[4] = {__byte_perm(u0, 0u, 0x1010), __byte_perm(u1, 0u, 0x1010), __byte_perm(u0, 0u, 0x3232), __byte_perm(u1, 0u, 0x3232)};
  keep(ma);
  wg_fence();
  wgmma_rs_n192<1>(a, ma[0], ma[1], ma[2], ma[3], mkd<2>(cd), 1);
  wg_commit();
}

template<bool FIRST> DEVI void qkv_block(float (&aX)[96], float (&aY)[96], uint32_t sb16, int s, int tX, int tY) {
  uint32_t a16 = sb16 + (qa_off(s) >> 4), b16 = (sb16 + (qb_off(s) >> 4)) | ((8192u >> 4) << 16);
  uint32_t ax = (a16 + tX * 512) | 0x10000u, ay = (a16 + tY * 512) | 0x10000u;
  wg_fence();
  #pragma unroll
  for (int ks = 0; ks < 4; ks++) {
    wgmma_ss_n192<1>(aX, mkd<HI128>(ax + ks * 2), mkd<HI128>(b16 + ks * 128), !(FIRST && ks == 0));
    wgmma_ss_n192<1>(aY, mkd<HI128>(ay + ks * 2), mkd<HI128>(b16 + ks * 128), !(FIRST && ks == 0));
  }
  wg_commit();
}
DEVI void qkv_half(float (&a)[96], uint32_t sb16, int t, uint32_t sa, uint32_t sbb) {
  wg_fence();
  #pragma unroll
  for (int ks = 0; ks < 4; ks++)
    wgmma_ss_n192<1>(a, mkd<HI128>(((sb16 + (sa >> 4) + t * 512) | 0x10000u) + ks * 2), mkd<HI128>(((sb16 + (sbb >> 4)) | ((8192u >> 4) << 16)) + ks * 128), 1);
  wg_commit();
}
DEVI void wo_block(float (&acc)[64], uint32_t sb16, int s, int wg) {
  uint32_t a16 = (sb16 + (w_off(s) >> 4) + wg * 256) | 0x10000u, b16 = (sb16 + (w_off(s) >> 4) + 1024) | ((8192u >> 4) << 16);
  wg_fence();
  #pragma unroll
  for (int ks = 0; ks < 4; ks++)
    wgmma_ss_n128<1>(acc, mkd<HI64>(a16 + (ks >> 1) * 512 + (ks & 1) * 2), mkd<HI128>(b16 + ks * 128), 1);
  wg_commit();
}
DEVI void consumer(const Params& P, uint32_t sb, int wg) {
  const int w = uni((threadIdx.x >> 5) & 3);
  #define LAYER uni(mbar_test(BAR(B_XRDY + wg * 2 + 1), 0))
  #define IDS L = LAYER; const int tid = fresh_tid(), lane = tid & 31
  const uint32_t ids = uni(P.map[blockIdx.x]);
  const int bi = (ids >> 4) & 7, rh = ids & 1, bc = (ids & 15) >> 1, fid = ids >> 8;
  const int tX = 3 - wg, tY = wg;
  constexpr uint32_t sb16 = 1024 >> 4;
  #pragma unroll 1
  while (true) {
    int L = LAYER;
    {
      float aX[96], aY[96];
      const bool lead = fresh_tid() == 0;
      mbar_wait(BAR(B_FULLQ), 0);
      PROFW(threadIdx.x == 0, L * 8 + 1);
      qkv_block<true>(aX, aY, sb16, 0, tX, tY);
      #pragma unroll 1
      for (int n = 1, s = 1, ps = 0, ph = 0; n < 14; n++) {
        mbar_wait(BAR(B_FULLQ + s), ph ^ (s ? L : 0));
        PROFD(threadIdx.x == 0 && L && (n == 2 || n == 3 || n == 7 || n == 11 || n == 13), n == 2 ? 48 : 49 + (n >> 2));
        qkv_block<false>(aX, aY, sb16, s, tX, tY);
        wg_wait<1>(); if (lead) mbar_arrive(BAR(B_EMPTYQ + ps));
        ps = s; if (s == 2) { s = 0; ph ^= 1; } else s++;
      }
      mbar_wait(BAR(B_FULLQ + 2), L);
      qkv_half(aX, sb16, tX, SA2, SB2);
      mbar_wait(BAR(B_ROW), L);
      IDS;
      const uint32_t pa = sb + PAR + (w * 16 + (lane >> 2)) * 8;
      float2 p0 = lds64f(pa + tX * 512), p1 = lds64f(pa + tX * 512 + 64), p2 = lds64f(pa + tY * 512), p3 = lds64f(pa + tY * 512 + 64);
      mean_step(aX, p0.y, p1.y, sb16 + (CS >> 4), lane & 3);
      mbar_wait(BAR(B_FULLQ), 1);
      qkv_half(aX, sb16, tX, 0, SB0);
      wg_wait<3>(); if (lead) mbar_arrive(BAR(B_EMPTYQ + 1));
      bar_sync(1, 256);
      qkv_half(aY, sb16, tY, SA2, SB2);
      wg_wait<1>(); keep(aX);
      const int srow = w * 16 + (lane & 15);
      const uint32_t x0 = sb + srow * 64 + (((lane >> 4) ^ ((srow >> 1) & 3)) << 4), xX = x0 + (4 + tX) * 8192, xY = x0 + (4 + tY) * 8192;
      qkv_store<8>(aX, p0.x, p1.x, xX + KVA); qkv_store<16>(aX, p0.x, p1.x, xX + KVA + 4096);
      warp_signal(BAR(B_KVRDY + wg * 2));
      qkv_half(aY, sb16, tY, 0, SB0);
      mean_step(aY, p2.y, p3.y, sb16 + (CS >> 4), fresh_tid() & 3);
      wg_wait<2>(); if (lead) mbar_arrive(BAR(B_EMPTYQ + 2));
      mbar_wait(BAR(B_EMPTYQ + 2), L);
      qkv_store<12>(aX, p0.x, p1.x, xX + KVB); qkv_store<20>(aX, p0.x, p1.x, xX + KVB + 4096);
      wg_wait<0>(); keep(aY);
      if (lead) mbar_arrive(BAR(B_EMPTYQ));
      PROFW(threadIdx.x == 0, L * 8 + 2);
      qkv_store<8>(aY, p2.x, p3.x, xY + KVA); qkv_store<16>(aY, p2.x, p3.x, xY + KVA + 4096);
      qkv_store<12>(aY, p2.x, p3.x, xY + KVB); qkv_store<20>(aY, p2.x, p3.x, xY + KVB + 4096);
      warp_signal(BAR(B_KVRDY + wg * 2 + 1));
      p0.x *= QSCALE; p1.x *= QSCALE; p2.x *= QSCALE; p3.x *= QSCALE;
      mbar_wait(BAR(B_EMPTYQ), 1);
      qkv_store<0>(aX, p0.x, p1.x, x0 + QO + tX * 4096);
      qkv_store<0>(aY, p2.x, p3.x, x0 + QO + tY * 4096); qkv_store<4>(aY, p2.x, p3.x, x0 + QO + 16384 + tY * 4096);
      mbar_wait(BAR(B_PAR), L);
      qkv_store<4>(aX, p0.x, p1.x, x0 + QO + 16384 + tX * 4096);
      const int prow = (int)uni(lds32(sb + INFO)) - bi * 256;
      if ((prow >> 4) == tX * 4 + w || (prow >> 4) == tY * 4 + w) {
        __syncwarp();
        if (lane < 24) sts128(sb + (prow & 63) * 64 + (((lane ^ (prow >> 1)) & 3) << 4) +
                              (lane < 8 ? QO + (lane >> 2) * 16384 + (prow >> 6) * 4096 : ((lane & 4) ? KVB : KVA) + (4 + (prow >> 6)) * 8192 + (lane >> 4) * 4096),
                              lds128(sb + PATCH + lane * 16));
      }
      fence_async_smem();
      bar_sync(1, 256);
    }
    PROFW(threadIdx.x == 0, L * 8 + 3);
    float2 fa, fb;
    { const float2* f = (const float2*)&P.g->statF[bi * 256 + rh * 128 + (wg ^ rh) * 64 + w * 16 + ((fresh_tid() & 31) >> 2)];
      fa = __ldcg(f); fb = __ldcg(f + 16); }
    {
      IDS;
      float s0[32], s1[32], sx[32], o[20], op[20];
      uint32_t p0[16], p1[16], px[16], msk[9];
      const int tdiag = w * 16 + (lane >> 2) - 2 * (lane & 3);
      #pragma unroll
      for (int e = 0; e < 9; e++) msk[e] = ((8 * e - 8 > tdiag) ? 0xFFFFu : 0u) | ((8 * e - 7 > tdiag) ? 0xFFFF0000u : 0u);
      keep(msk);
      const uint32_t ones = (sb16 + (ONES >> 4)) << 16;
      const uint32_t qX = (sb16 + (QO >> 4) + tX * 256) | 0x10000u, qY = (sb16 + (QO >> 4) + tY * 256) | 0x10000u;
      const uint32_t kXB = (sb16 + (KVB >> 4) + tX * 512) | 0x10000u;
      uint32_t redo = 0;
      const uint32_t ost = sb + QO + (w * 16 + (lane & 15)) * 64 + (((lane >> 4) ^ ((lane >> 1) & 3)) << 4);
      #define QK(s, q, k) do { wg_fence(); qk_issue(s, q, k); wg_commit(); } while (0)
      #define QK2(q, k) do { wg_fence(); qk_issue(s1, q, k); qk_issue(sx, q, (k) + 2048); wg_commit(); } while (0)
      #define VB(v, b) ((v) + VOFF((b) * 512))
      QK(s0, qX + 1024, kXB + 1536);
      #pragma unroll
      for (int e = 0; e < 20; e++) o[e] = 0.f;
      wg_wait<0>(); keep(s0);
      #pragma unroll 1
      for (int h = 1; h >= 0; h--) {
        const uint32_t kXA = kXB - ((KVB - KVA) >> 4), kX = h ? kXB : kXA, vX = VOFF((kX & 0xffffu) + 256) + ones;
        QK(s1, qX + h * 1024, kX + 1024);
        #pragma unroll
        for (int e = 0; e < 20; e++) op[e] = o[e];
        keep(op);
        exp_pv<0, 4>(s0, p0, o, VB(vX, 3), false); wg_commit();
        wg_wait<1>(); keep(s1);
        exp_pv<0, 2>(s1, p1, o, VB(vX, 2), true);
        bar_sync(h ? 12 + wg : 4 + wg * 4, h ? 128 : 160);
        QK(s0, qX, kXA + 512 + h * 1024);
        exp_pv<2, 4>(s1, p1, o, VB(vX, 2), true); wg_commit();
        wg_wait<0>(); keep(s0); keep(p0); keep(p1); keep(o);
      }
      #pragma unroll 1
      for (int h = 0; h < 2; h++) {
        const uint32_t kb16 = sb16 + ((h ? KVB : KVA) >> 4), kY = (kb16 + tY * 512) | 0x10000u, qy = qY + h * 1024;
        const uint32_t onesP = bi ? ones : (kb16 + 1984) << 16;
        const uint32_t vX = VOFF(kb16 + tX * 512 + 256), vY = VOFF(kb16 + tY * 512 + 256);
        uint32_t ob[8];
        QK2(qX + h * 1024, (kb16 + tX * 512) | 0x10000u);
        exp_pv<0, 4>(s0, p0, o, VB(vX + (wg ? onesP : ones), 1), true); wg_commit();
        wg_wait<1>(); keep(s1); keep(sx);
        QK(s0, qy, kY + 1536);
        exp_pv2(s1, sx, p1, px, o, vX + onesP, VB(vX + ones, 4), msk, tdiag); wg_commit();
        wg_wait<1>(); keep(s0); keep(p0);
        QK(s1, qy, kY + 1024);
        exp_pack<0, 4>(s0, p0);
        wg_wait<1>(); keep(o); keep(p1); keep(px);
        bool ok = attn_pack(o, ob); keep(ob);
        exp_pv<0, 4, 1>(s0, p0, o, VB(vY + (wg ? ones : onesP), 3), false); wg_commit();
        attn_store(ob, ok, ost + (h * 4 + tX) * 4096, sb, BAR(B_ORDY + wg * 4 + h * 2)); redo |= ok ? 0u : 1u << (h * 2);
        wg_wait<1>(); keep(s1);
        exp_pv<0, 2>(s1, p1, o, VB(vY + onesP, 2), true);
        bar_sync(5 + wg * 4 + h * 2, 160);
        QK(s0, qy, kY + 512);
        exp_pv<2, 4>(s1, p1, o, VB(vY + onesP, 2), true); wg_commit();
        wg_wait<1>(); keep(s0); keep(p0);
        QK2(qy, kY);
        exp_pv<0, 4>(s0, p0, o, VB(vY + onesP, 1), true); wg_commit();
        wg_wait<1>(); keep(s1); keep(sx); keep(p1);
        bar_sync(6 + wg * 4, h ? 128 : 160);
        QK(s0, h ? qy : qX + 1024, kXB + 512);
        exp_pv2(s1, sx, p1, px, o, vY + onesP, VB(vY + ones, 4), msk, tdiag); wg_commit();
        wg_wait<0>(); keep(o); keep(s0); keep(p0); keep(p1); keep(px);
        ok = attn_pack(o, ob); attn_store(ob, ok, ost + (h * 4 + tY) * 4096, sb, BAR(B_ORDY + wg * 4 + h * 2 + 1)); redo |= ok ? 0u : 2u << (h * 2);
        #pragma unroll
        for (int e = 0; e < 20; e++) o[e] = op[e];
      }
      #undef QK
      #undef QK2
      #undef VB
      if (redo) {
        #pragma unroll 1
        for (int u = 0; u < 4; u++) if ((redo >> u) & 1) {
          const int h = u >> 1, t = (u & 1) ? tY : tX;
          attn_exact(sb + QO + (h * 4 + t) * 4096, sb + (h ? KVB : KVA), t, bi > 0, BAR(B_ORDY + wg * 4 + u));
        }
      }
    }
    PROFW(threadIdx.x == 0, L * 8 + 4);
    {
      IDS;
      const int t256 = wg * 128 + tid;
      float acc[64];
      const int tt = wg ^ rh;
      const int grow = bi * 256 + rh * 128 + tt * 64 + w * 16 + (lane >> 2);
      float al0 = 1.f, be0 = 0.f, al1 = 1.f, be1 = 0.f;
      const int idx0 = (int)uni(lds32(sb + INFO));
      const uint32_t tag = lds32(sb + INFO + 8) + L;
      uint4* const sp = &P.g->statP[bc][grow + (lane & 1) * 8];
      uint4* const yp = &P.g->yP[t256 >> 1][min(fid, 111)][t256 & 1];
      if (L) {
        float r0 = rsqrtf(fa.y + LN_EPS), r1 = rsqrtf(fb.y + LN_EPS);
        if (grow != idx0) { al0 = 1.f + r0; be0 = -fa.x * r0; }
        if (grow + 8 != idx0) { al1 = 1.f + r1; be1 = -fb.x * r1; }
      }
      const int srow = tt * 64 + w * 16 + (lane & 15);
      const uint32_t ra = sb + srow * 128 + (((lane >> 4) ^ (srow & 7)) << 4);
      mbar_wait(BAR(B_FULLW + 5), L);
      if ((idx0 >> 4) == bi * 16 + rh * 8 + tt * 4 + w) {
        int r = idx0 & 127;
        if (lane < 16) sts128(sb + 32768 + (lane >> 3) * 16384 + r * 128 + (((lane & 7) ^ (r & 7)) << 4), lds128(sb + X2SEG + lane * 16));
        fence_async_smem();
        __syncwarp();
      }
      #pragma unroll
      for (int jj = 0; jj < 8; jj++) {
        uint32_t r[4]; ldsm_x4((ra + 32768 + (jj >> 2) * 16384) ^ ((jj & 3) << 5), r[0], r[1], r[2], r[3]);
        #pragma unroll
        for (int e = 0; e < 4; e++) {
          acc[8 * jj + 2 * e] = fmaf(bf_lo(r[e]), (e & 1) ? al1 : al0, (e & 1) ? be1 : be0);
          acc[8 * jj + 2 * e + 1] = fmaf(bf_hi(r[e]), (e & 1) ? al1 : al0, (e & 1) ? be1 : be0);
        }
      }
      keep(acc);
      bar_sync(12 + wg, 128);
      if (!(lane & 2)) st_ll(sp, 0u, 0u, 0u, 0u);
      uint2 wd[4];
      #pragma unroll
      for (int e = 0; e < 4; e++) { wd[e] = make_uint2(0u, 0u); if (L) wd[e] = ldg_stream((const uint2*)(WDSRC) + t256 + (28 + e) * 256); }
      PROFW(t256 == 0, L * 8 + 5);
      #pragma unroll 1
      for (int n = 0, q = 0, pq = 5; n < 16; n++) {
        mbar_wait(BAR(B_FULLW + q), w_par(n, q, L));
        PROFD(t256 == 0 && !L && (n == 4 || n == 7 || n == 8 || n == 12), (n == 7 ? 63 : 41 + (n >> 2)));
        wo_block(acc, sb16, q, tt);
        wg_wait<1>(); if (tid == 0) mbar_arrive(BAR(B_EMPTYW + pq));
        pq = q; q = w_next(n, q);
      }
      mbar_wait(BAR(B_EMPTYW + 5), L);
      wg_wait<0>(); keep(acc);
      if (tid == 0) mbar_arrive(BAR(B_EMPTYW + 4));
      PROFW(t256 == 0, L * 8 + 6);
      {
        float s1a = 0.f, s2a = 0.f, da = 0.f, s1b = 0.f, s2b = 0.f, db = 0.f;
        #pragma unroll
        for (int j = 0; j < 16; j++) {
          const float* a = acc + 4 * j; float2 wv = lds64f(sb + WR + j * 32 + (lane & 3) * 8);
          s1a += a[0] + a[1]; s1b += a[2] + a[3];
          s2a = fmaf(a[0], a[0], s2a); s2b = fmaf(a[2], a[2], s2b); s2a = fmaf(a[1], a[1], s2a); s2b = fmaf(a[3], a[3], s2b);
          da = fmaf(a[0], wv.x, da); db = fmaf(a[2], wv.x, db); da = fmaf(a[1], wv.y, da); db = fmaf(a[3], wv.y, db);
        }
        bool odd = lane & 1;
        float u1 = (odd ? s1b : s1a) + __shfl_xor_sync(0xffffffffu, odd ? s1a : s1b, 1);
        float u2 = (odd ? s2b : s2a) + __shfl_xor_sync(0xffffffffu, odd ? s2a : s2b, 1);
        float u3 = (odd ? db : da) + __shfl_xor_sync(0xffffffffu, odd ? da : db, 1);
        u1 += __shfl_xor_sync(0xffffffffu, u1, 2); u2 += __shfl_xor_sync(0xffffffffu, u2, 2); u3 += __shfl_xor_sync(0xffffffffu, u3, 2);
        if (!(lane & 2)) st_ll(sp, __float_as_uint(u1), __float_as_uint(u2), __float_as_uint(u3), tag);
      }
      const uint32_t xa = ra + rh * 16384;
      #pragma unroll
      for (int jj = 0; jj < 8; jj++) {
        const float* a = acc + 8 * jj;
        stsm_x4((xa + (jj >> 2) * 32768) ^ ((jj & 3) << 5), pack_bf16(a[0], a[1]), pack_bf16(a[2], a[3]), pack_bf16(a[4], a[5]), pack_bf16(a[6], a[7]));
        if (jj == 7) fence_async_smem();
        if ((jj & 3) == 3) warp_signal(BAR(B_XRDY + wg * 2 + (jj >> 2)));
      }
      PROFW(t256 == 0, L * 8 + 7);
      if (L) {
        mbar_wait(BAR(B_PAR), 0);
        { float2 pa = lds64f(sb + PAR + (grow & 127) * 8), pb = lds64f(sb + PAR + (grow & 127) * 8 + 64); al0 = pa.x; be0 = pa.y; al1 = pb.x; be1 = pb.y; }
        uint32_t rs[32];
        #pragma unroll
        for (int j = 0; j < 16; j++) {
          rs[2 * j] = pack_bf16(fmaf(acc[4 * j], al0, be0), fmaf(acc[4 * j + 1], al0, be0));
          rs[2 * j + 1] = pack_bf16(fmaf(acc[4 * j + 2], al1, be1), fmaf(acc[4 * j + 3], al1, be1));
        }
        #pragma unroll
        for (int jj = 0; jj < 8; jj++) stsm_x4((xa + (jj >> 2) * 32768) ^ ((jj & 3) << 5), rs[4 * jj], rs[4 * jj + 1], rs[4 * jj + 2], rs[4 * jj + 3]);
        PROFW(t256 == 0, 16);
        if (fid >= 112) bar_arrive(3, 384);
        else {
          float d[4] = {0.f, 0.f, 0.f, 0.f};
          mbar_wait(BAR(B_FULLW + wg * 3), 0); mbar_wait(BAR(B_FULLW + wg * 3 + 1), 0);
          bar_sync(3, 384);
          PROFW(t256 == 0, 29);
          #pragma unroll 1
          for (int g = 0; g < 4; g++) {
            const uint32_t ad = (sb16 + (wg ? 6144 : 10240) + (g >> 1) * 2048 + (g & 1) * 512) | (1024u << 16), bd = (sb16 + (HV >> 4) + wg * 64 + g * 16) | 0x10000u;
            wg_fence();
            #pragma unroll
            for (int ks = 0; ks < 8; ks++) wgmma_ss_n8<0, 1>(d, mkd<HI64>(ad + ks * 64), mkd<8>(bd + ks * 2), 1);
            wg_commit();
          }
          mbar_wait(BAR(B_FULLW + 2), 0);
          wg_wait<0>(); keep(d);
          if (!(lane & 3)) { sts32f(sb + PAR + 1024 + wg * 256 + w * 64 + lane, d[0]); sts32f(sb + PAR + 1056 + wg * 256 + w * 64 + lane, d[2]); }
          bar_sync(1, 256);
          const uint32_t ga = sb + PAR + 1024 + lane * 4, aa = sb + HV + (t256 >> 5) * 128;
          sts32f(aa + lane * 4, swiglu(lds32f(ga) + lds32f(ga + 256), lds32f(ga + 128) + lds32f(ga + 384)));
          __syncwarp();
          PROFW(t256 == 0, 26);
          float y0 = 0.f, y1 = 0.f, y2 = 0.f, y3 = 0.f;
          uint32_t tbl = rh ? 0x001459a8u : 0x023679a8u;
          uint4 a4 = lds128(aa + 112);
          #pragma unroll 2
          for (int n = 0; n < 8; n++, tbl >>= 4) {
            const uint32_t src = sb + t256 * 8 + (tbl & 15) * 8192;
            const uint4 an = lds128(aa + ((0x00123564u >> (4 * n)) & 15) * 16);
            #pragma unroll
            for (int e = 0; e < 4; e++) {
              const float av = __uint_as_float(e == 0 ? a4.x : (e == 1 ? a4.y : (e == 2 ? a4.z : a4.w)));
              y0 = fmaf(bf_lo(wd[e].x), av, y0); y1 = fmaf(bf_hi(wd[e].x), av, y1); y2 = fmaf(bf_lo(wd[e].y), av, y2); y3 = fmaf(bf_hi(wd[e].y), av, y3);
              const float2 v = lds64f(src + e * 2048); wd[e] = make_uint2(__float_as_uint(v.x), __float_as_uint(v.y));
            }
            a4 = an;
          }
          st_ll(yp, __float_as_uint(y0), __float_as_uint(y1), __float_as_uint(y2), (__float_as_uint(y3) & ~255u) | (lds32(sb + INFO + 12) + 1));
          PROFW(t256 == 0, 27);
        }
        return;
      }
      mbar_wait(BAR(B_XRDY + wg * 2 + 1), 0);
    }
  }
  #undef IDS
  #undef LAYER
}

DEVI void loader(const Params& P, uint32_t sb) {
  const int lane = threadIdx.x & 31;
  const int bid = uni(BID), bi = bid >> 4, bp = bid & 15, rh = bp & 1, bc = bp >> 1;
  uint32_t phq = 0, tag = 0;
  #pragma unroll 1
  for (int L = 0; L < 2; L++) {
    int s = 0;
    uint32_t rdy = 0;
    #pragma unroll 1
    for (int n = L ? 0 : 3; n < 16; n++) {
      int kb = L ? kb_order(bc, n) : n;
      mbar_wait(BAR(B_EMPTYQ + s), (phq >> s) & 1);
      phq ^= 1u << s;
      if (L && n == 1) { mbar_wait(BAR(B_XRDY + 1), 0); mbar_wait(BAR(B_XRDY + 3), 0); }
      if (elect()) {
        mbar_expect_tx(BAR(B_FULLQ + s), L && n < 2 ? 40960 : 57344);
        tma_3d_h(sb + qb_off(s), &P.mWq, bp * 64, kb * 64, 0, BAR(B_FULLQ + s), L && n >= QEF_N ? POL_FIRST : POL_NORMAL);
        if (!L) tma_2d(sb + qa_off(s), &P.mX, kb * 64, bi * 256, BAR(B_FULLQ + s));
      }
      if (L && n >= 2) {
        if (((rdy >> (2 * kb)) & 3) != 3) {
          do { rdy = __ballot_sync(0xffffffffu, ld_rlx(&P.g->flagX[bi][lane]) == tag); } while (((rdy >> (2 * kb)) & 3) != 3);
          fence_async_glob();
        }
        if (n == 3 || n == 4) mbar_wait(BAR(B_XFREE + n - 3), 0);
        if (elect()) bulk_g2s_h(sb + qa_off(s), P.g->x[bi][kb], 32768, BAR(B_FULLQ + s), POL_X);
      }
      PROFY(L && lane == 0 && (n == 2 || n == 3 || n == 9), n == 9 ? 60 : 56 + n);
      if (L && n == 2) { mbar_wait(BAR(B_FULLQ), 0); mbar_wait(BAR(B_FULLQ + 1), 1); if (lane < 2) mbar_arrive_peer(BAR(B_XFREE + lane)); }
      s = (s == 2) ? 0 : s + 1;
    }
    for (int q = 0; q < 3; q++) mbar_wait(BAR(B_EMPTYQ + q), (phq >> q) & 1);
    tag = lds32(sb + INFO + 8) + L;
    #pragma unroll 1
    for (int q = 0; q < 4; q++) {
            if (bi) {
        const unsigned* f = &P.g->flagKV[bid - 16][q];
        while (ld_rlx(f) != tag);
        fence_async_glob();
      }
      if (elect()) {
        mbar_expect_tx(BAR(B_KVFULL + q), 16384);
        bulk_g2s_h(sb + ((q >> 1) ? KVB : KVA) + ((q & 1) ? 0 : 16384), bi ? P.g->kv[bid - 16][q] : P.g->zero, 16384, BAR(B_KVFULL + q), L ? POL_KV1 : POL_KV0);
      }
      PROFY(!L && lane == 0 && bi && q != 2, 34 + (q + 1) / 2);
    }
    mbar_wait(BAR(B_ORDY), L);
    {
      const uint4* src = P.g->o[bi][0][0][rh];
      rdy = 0;
      #pragma unroll 1
      for (int n = 0, q = 0; n < 16; q = w_next(n, q), n++) {
        const int j = wo_order(bc, n);
        if (((rdy >> (2 * j)) & 3) != 3) {
          do { rdy = __ballot_sync(0xffffffffu, ld_rlx(&P.g->flagO[bi][lane]) == tag); } while (((rdy >> (2 * j)) & 3) != 3);
          fence_async_glob();
        }
        if (n >= 2) mbar_wait(n < 5 ? BAR(B_HAFREE + (n > 2)) : BAR(B_EMPTYW + q), n < 5 ? L : w_par(n, q, L) ^ 1);
        if (n == THR_N) mbar_wait(BAR(B_OFREE), L);
        if (elect()) { mbar_expect_tx(BAR(B_FULLW + q), 16384); bulk_g2s_h(sb + w_off(q), src + j * 2048, 16384, BAR(B_FULLW + q), L ? POL_O1 : POL_O0); }
      }
    }
    mbar_wait(BAR(B_OFREE), L);
  }
}

DEVI void ffn_prefetch(const Params& P, int q) {
  bulk_prefetch(q < 16 ? ((q & 1) ? P.wu : P.wg) + ((q >> 1) * 128 + blockIdx.x) * 3584 : P.wd + (min(FID, 111) * 8 + q - 16) * 4096, q < 16 ? 7168 : 8192);
}
DEVI void storer(const Params& P, uint32_t sb, int wg) {
  const int bid = uni(BID), bi = bid >> 4, rh = bid & 1, bc = (bid & 15) >> 1;
  const bool one = (threadIdx.x & 31) == 0;
  char* const g = (char*)P.g;
  const uint32_t tag0 = uni(((ld_rlx(&P.g->epoch) % 16383u) + 1u) << 2);
  #pragma unroll 1
  for (int L = 0; L < 2; L++) {
    const uint32_t tag = tag0 + L;
    if (wg) {
      #pragma unroll 1
      for (int r = threadIdx.x & 31; r < 256; r += 32) {
        uint4 v;
        do v = ld_ll(&P.g->statF[bi * 256 + r]); while (!__all_sync(0xffffffffu, v.w == tag));
        float var = __uint_as_float(v.y), c = rsqrtf(var + LN_EPS);
        if (L) { c += 1.f; c *= rsqrtf(fmaf(var * c, c, LN_EPS)); }
        const float mh = bf_round(__uint_as_float(v.x));
        sts64f(sb + PAR + r * 8, c, __uint_as_float(pack_bf16(mh, __uint_as_float(v.x) - mh)));
      }
      if (!L) mbar_wait(BAR(B_PAR), 0);
      warp_signal(BAR(B_ROW));
    }
    #pragma unroll 1
    for (int u = 0; u < 2 + 4 * wg; u++) {
      const int h = u < 2 ? u : u >> 2, hi = (u & 1) ^ 1;
      uint32_t src, dst, fl, b0, b1;
      if (u < 2) {
        src = (h ? KVB : KVA) + (3 - wg) * 16384; dst = offsetof(Scratch, kv) + (bid * 4 + h * 2 + wg) * 16384; fl = offsetof(Scratch, flagKV) + (bid * 32 + h * 2 + wg) * 4;
        b0 = BAR(B_KVRDY + ((u | wg) ? 1 : 0)); b1 = b0 + 16;
      } else {
        src = QO + (h * 2 + hi) * 8192; dst = offsetof(Scratch, o) + ((((bi * 2 + h) * 8 + bc) * 2 + hi) * 2 + rh) * 8192;
        fl = offsetof(Scratch, flagO) + (bi * 32 + h * 16 + (bid & 15)) * 4;
        b0 = BAR(B_ORDY + u - 2); b1 = b0 + 32;
      }
      mbar_wait(b0, L); mbar_wait(b1, L);
      if (u + wg == 1) {
        mbar_wait(BAR(B_PAR), L);
        const uint32_t t0 = clk(), dt = (wg ? KV_D1 : KV_D2) + (L ? KV_DL : 0); while (clk() - t0 < dt) __nanosleep(40);
      }
      fence_async_smem();
      PROFY(one && !L && u == 3 * wg, u ? 46 : 8);
      if (one && (u >= 2 || bi < 7)) bulk_s2g(g + dst, sb + src, u < 2 ? 16384 : 8192);
      if (one && u == 5) mbar_arrive(BAR(B_HAFREE + 1));
      if (u == 2 || u == 4) continue;
      bulk_wait<0>();
      PROFY(one && !L && u == 3 * wg, u ? 61 : 62);
      fence_rel();
      if (one) { st_rlx((unsigned*)(g + fl), tag); if (!wg || u > 2) mbar_arrive(BAR(B_HAFREE + h + (wg & h))); }
      PROFY(one && !L && (u > 2 || u == wg), u > 2 ? (u == 3 ? 38 : 54) : 32 + u);
    }
    if (L == 0) {
      char* dst = g + (offsetof(Scratch, x) + (bi * 16 + 2 * bc) * 32768 + rh * 16384);
      unsigned* f = (unsigned*)(g + (offsetof(Scratch, flagX) + (bi * 32 + bc * 4 + rh) * 4));
      const uint32_t a = sb + rh * 16384;
      if (wg == 0) {
        mbar_wait(BAR(B_XRDY), 0); mbar_wait(BAR(B_XRDY + 2), 0);
        fence_async_smem();
        PROFY(one, 41);
        if (one) bulk_s2g(dst, a, 16384);
        bulk_wait<0>();
        PROFY(one, 45);
        if (one) { mbar_arrive(BAR(B_XFREE)); mbar_arrive(BAR(B_PFREE)); }
        fence_rel();
        mbar_wait(BAR(B_XRDY + 1), 0); mbar_wait(BAR(B_XRDY + 3), 0);
        if (one) { st_rlx(f, tag); bulk_s2g(dst + 32768, a + 32768, 16384); }
        PROFY(one, 56);
        bulk_wait<0>();
        if (one) mbar_arrive(BAR(B_XFREE + 1));
        fence_rel();
        if (one) st_rlx(f + 2, tag);
        PROFY(one, 57);
      } else {
        mbar_wait(BAR(B_XRDY + 1), 0); mbar_wait(BAR(B_XRDY + 3), 0);
        mbar_wait(BAR(B_PFREE), 0);
        if (one) bulk_s2peer(a, 16384, BAR(B_FULLQ));
        { const uint32_t t0 = clk(); while (clk() - t0 < XD_D); }
        if (one) bulk_s2peer(a + 32768, 16384, BAR(B_FULLQ + 1));
      }
      if (wg == 0) {
        uint32_t t0 = clk() + PF1_D;
        #pragma unroll 1
        for (int q = PF1_S; q < PF1_E; q++) { while ((int)(clk() - t0) < 0) __nanosleep(50); if (one) ffn_prefetch(P, q); t0 += PF1_T; }
      }
    }
  }
}

DEVI void stg_issue(const Params& P, int c, uint32_t d, uint32_t du, uint32_t b) {
  mbar_expect_tx(b, 16384);
  if (c < 8) { tma_2d_h(d, &P.mWg, FID * 32, c * 128, b, POL_G); tma_2d_h(d + du, &P.mWu, FID * 32, c * 128, b, POL_U); }
  else if (c < 12) tma_3d_h(d, &P.mWd, 0, FID * 32 + (c - 8) * 8, 0, b, POL_D);
  else tma_2d_h(d, &P.mWp, (c - 12) * 1024 + (BID >> 2) * 32, (BID & 3) * 256, b, POL_EF);
}
DEVI void pace() { const uint32_t t0 = clk(); while (clk() - t0 < PACE_T); }
DEVI void stager(const Params& P, uint32_t sb) {
  {
    const int b = blockIdx.x;
    uint32_t t0 = clk();
    #pragma unroll 1
    for (int q = 0; q < PQ_N; q++) { bulk_prefetch(P.wqkv + (q * 128 + b) * 3072, 6144); while (clk() - t0 < PQ_T) __nanosleep(50); t0 += PQ_T; }
    bulk_prefetch(P.wo + b * 8192, 16384);
    #pragma unroll 1
    for (int q = 0; q < PF0_N; q++) {
      while (clk() - t0 < PF0_T) __nanosleep(50);
      t0 += PF0_T;
      ffn_prefetch(P, q);
    }
  }
  const int bid = BID, bi = bid >> 4, rh = bid & 1, bc = (bid & 15) >> 1;
  #pragma unroll 1
  for (int L = 0; L < 2; L++) {
    const int nch = L ? (FID < 112 ? 8 : 0) : 15;
    mbar_wait(BAR(B_PAR), L); mbar_wait(BAR(B_KVFULL + W0_BAR), L);
    #pragma unroll 1
    for (int n = 0, q = 0; n < 16; q = w_next(n, q), n++) {
      if (n >= 2) mbar_wait(n < 5 ? BAR(B_HAFREE + (n > 2)) : BAR(B_EMPTYW + q), n < 5 ? L : w_par(n, q, L) ^ 1);
      if (n == THR_N) mbar_wait(BAR(B_OFREE), L);
      mbar_expect_tx(BAR(B_FULLW + q), 16384);
      tma_5d(sb + w_off(q) + 16384, &P.mWo, 0, 0, n >> 3, 2 * (wo_order(bc, n) & 7), 2 * bc, BAR(B_FULLW + q), L ? POL_W1 : POL_W0);
      if (n == 2) {
        #pragma unroll 1
        for (int e = 0; e < 2; e++) {
          mbar_expect_tx(BAR(B_FULLW + 5), 16384);
          if (L) bulk_g2s_h(sb + 32768 + e * 16384, P.g->x[bi][2 * bc + e] + rh * 1024, 16384, BAR(B_FULLW + 5));
          else tma_2d_h(sb + 32768 + e * 16384, &P.mXh, bc * 128 + e * 64, bi * 256 + rh * 128, BAR(B_FULLW + 5), POL_EF);
        }
      }
    }
    mbar_wait(BAR(B_EMPTYW + 5), L);
    if (L && nch) {
      const bf16* src = WDSRC2;
      mbar_expect_tx(BAR(B_FULLW + 2), 32768); mbar_expect_tx(BAR(B_FULLW + 2), 24576);
      #pragma unroll 1
      for (int e = 0; e < 3; e++) { bulk_g2s_h(sb + e * 32768 + (e < 2 ? (rh ^ 1) * 16384 : 0), src + e * 8192, e < 2 ? 16384 : 24576, BAR(B_FULLW + 2)); pace(); }
    }
        if (L == 0) { mbar_arrive_peer(BAR(B_PFREE)); mbar_wait(BAR(B_EMPTYW), 0); mbar_wait(BAR(B_EMPTYW + 1), 0); }
    #pragma unroll 1
    for (int c = FID < 112 ? 0 : 12, slot = 0; c < nch; c++, slot = slot == 2 ? 0 : slot + 1) {
      const int q = (c >> 1) + (c >> 2);
      if (!L && (c == LATE_C || c == 12)) mbar_wait(BAR(LATE_B), LATE_P);
      mbar_wait(L ? BAR(B_EMPTYW + q) : BAR(B_STGE + slot), L | ((0x71c7 >> c) & 1));
      #define CC c
      stg_issue(P, CC, L ? sb + w_off(q) + (c & 1) * 8192 : sb + STG + slot * 16384, 8192 << L, L ? BAR(B_FULLW + q) : BAR(B_STG + slot));
      if (L) pace();
    }
  }
}
DEVI void sum8(uint4 v, float& s1, float& s2) {
  float e[8] = {bf_lo(v.x), bf_hi(v.x), bf_lo(v.y), bf_hi(v.y), bf_lo(v.z), bf_hi(v.z), bf_lo(v.w), bf_hi(v.w)};
  #pragma unroll
  for (int q = 0; q < 8; q++) { s1 += e[q]; s2 = fmaf(e[q], e[q], s2); }
}
DEVI uint4 norm8(uint4 x, float m, float rs) {
  #define HN(v) pack_bf16((bf_lo(v) - m) * rs, (bf_hi(v) - m) * rs)
  return make_uint4(HN(x.x), HN(x.y), HN(x.z), HN(x.w));
  #undef HN
}
DEVI void put_f32(uint4 b, uint32_t d, uint32_t d2) {
  sts128(d, make_uint4(b.x << 16, b.x & 0xffff0000u, b.y << 16, b.y & 0xffff0000u));
  sts128(d + d2, make_uint4(b.z << 16, b.z & 0xffff0000u, b.w << 16, b.w & 0xffff0000u));
}
DEVI void put_bf16(uint4 b, uint32_t d) {
  sts64f(d, __uint_as_float(b.x), __uint_as_float(b.y)); sts64f(d + 1024, __uint_as_float(b.z), __uint_as_float(b.w));
  fence_async_smem();
}
DEVI uint4 best4(uint32_t p) {
  uint4 a = lds128(p), b = lds128(p + 16), c = lds128(p + 32), d = lds128(p + 48);
  if (b.x > a.x) a = b;
  if (d.x > c.x) c = d;
  return c.x > a.x ? c : a;
}
#define FL(x) __uint_as_float(x)
#define UI(x) __float_as_uint(x)
DEVI void aux(const Params& P, uint32_t sb) {
  int tid = fresh_tid();
  #define lane (tid & 31)
  #define wq (tid >> 5)
  uint32_t ids = P.map[blockIdx.x], tag;
  #define bid ((int)(ids & 255))
  #define fid ((int)(ids >> 8))
  #define bi (bid >> 4)
  #define bp (bid & 15)
  #define bc (bp >> 1)
  #define FRESH() do { tid = fresh_tid(); uint4 z_ = ldsv128(sb + INFO2 + 16); ids = z_.y; tag = z_.z + L; idx = z_.w; } while (0)
  {
    const uint32_t epoch = ld_rlx(&P.g->epoch);
    if (tid == 0) {
      mbar_expect_tx(BAR(B_STG), 49152);
      tma_3d(sb + STG, &P.mWq, bp * 64, bi * 128, 0, BAR(B_STG));
      tma_3d(sb + STG + 24576, &P.mWq, bp * 64, bi * 128 + 64, 0, BAR(B_STG));
    }
    __syncwarp();
    sts64f(sb + ONES + tid * 8, FL(0x3F803F80u), FL(0x3F803F80u));
    float s1 = 0.f, s2 = 0.f;
    { uint4 v = __ldg((const uint4*)P.wr + tid);
      if ((tid >> 4) == bc) put_f32(v, sb + WR + (tid & 15) * 32, 16);
      sum8(v, s1, s2);
      #pragma unroll 1
      for (int o = 16; o; o >>= 1) s1 += __shfl_xor_sync(0xffffffffu, s1, o);
      sts32f(sb + INFO2 + wq * 4, s1); }
    const uint4* src = (const uint4*)(P.x0 + (size_t)bid * 16384) + (tid >> 3) * 128 + (tid & 7);
    s1 = 0.f; s2 = 0.f;
    #pragma unroll 1
    for (int it = 0; it < 16; it += 4) {
      uint4 v0 = __ldg(src + it * 8), v1 = __ldg(src + it * 8 + 8), v2 = __ldg(src + it * 8 + 16), v3 = __ldg(src + it * 8 + 24);
      #pragma unroll 1
      for (int q = 0; q < 4; q++) { sum8(v0, s1, s2); v0 = v1; v1 = v2; v2 = v3; }
    }
    #pragma unroll 1
    for (int o = 1; o < 8; o <<= 1) { s1 += __shfl_xor_sync(0xffffffffu, s1, o); s2 += __shfl_xor_sync(0xffffffffu, s2, o); }
    tag = ((epoch % 16383u) + 1u) << 2;
    if (tid == 0) { sts128(sb + INFO, make_uint4(0x40000000u, 0u, tag, ((epoch % 127u) + 1u) << 1)); sts128(sb + INFO2 + 16, make_uint4(epoch, ids, tag, 0x40000000u)); }
    float m = s1 * (1.f / 1024.f);
    if ((tid & 7) == 0) st_ll(&P.g->statF[bid * 16 + (tid >> 3)], UI(m), UI(fmaxf(fmaf(-m, m, s2 * (1.f / 1024.f)), 0.f)), 0u, tag);
    bar_sync(2, 128);
    mbar_wait_b(BAR(B_STG), 0);
    if (tid < 96) {
      s1 = 0.f; s2 = 0.f;
      #pragma unroll 1
      for (int r = 0; r < 16; r++) {
        const uint32_t a = sb + STG + (r >> 3) * 24576 + wq * 8192 + (r & 7) * 128 + ((lane * 4) ^ ((r & 7) << 4));
        #pragma unroll
        for (int e = 0; e < 8; e++) { uint32_t v = lds32(a + e * 1024); s1 += bf_lo(v); s2 += bf_hi(v); }
      }
      st_ll(&P.g->csP[bp][bi][tid], UI(s1), UI(s2), 0u, tag);
      s1 = 0.f; s2 = 0.f;
      #pragma unroll 1
      for (int q = 0; q < 8; q += 2) {
        uint4 a, b; poll_ll2(&P.g->csP[bp][q][tid], &P.g->csP[bp][q + 1][tid], 0xffffffffu, tag, a, b);
        s1 += FL(a.x) + FL(b.x); s2 += FL(a.y) + FL(b.y);
      }
      const uint32_t hi = pack_bf16(-s1, -s2);
      sts32(sb + CS + (tid >> 2) * 32 + (tid & 3) * 4, hi);
      sts32(sb + CS + (tid >> 2) * 32 + (tid & 3) * 4 + 16, pack_bf16(-s1 - bf_lo(hi), -s2 - bf_hi(hi)));
    }
    fence_async_smem();
  }
  int idx;
  #pragma unroll 1
  for (int L = 0; L < 2; L++) {
    FRESH();
    {
      if ((unsigned)(bi - (idx >> 8)) < 2u) {
        const uint4* src = &P.g->patch[bp * 8 + (tid >> 6) * 4][tid & 63];
        const float4 z = poll_sum4(src, 64, tag);
        float q = z.x, k = z.y, v = z.z;
        q += __shfl_xor_sync(0xffffffffu, q, 1); k += __shfl_xor_sync(0xffffffffu, k, 1); v += __shfl_xor_sync(0xffffffffu, v, 1);
        bar_sync(2, 128);
        const uint32_t d = sb + PATCH + (tid & ~1), kv = pack_bf16(k, v);
        sts16(d, pack_bf16(q * QSCALE, 0.f)); sts16(d + 128, kv); sts16(d + 256, kv >> 16);
      }
      sts32(sb + INFO, idx);
      bar_sync(2, 128);
    }
    const uint4 fix = lds128(sb + PATCH + 128 + (lane & 4) * 32 + (wq >> 1) * 64 + (lane & 3) * 16);
    warp_signal(BAR(B_PAR));
    PROFX(tid == 0, L ? 23 : 17);
    mbar_wait_b(BAR(B_KVFULL + wq), L);
    if ((idx >> 7) == bi * 2 - 1 - (wq & 1)) {
      if (lane < 8) sts128(sb + ((wq >> 1) ? KVB : KVA) + ((idx >> 6) & 3) * 8192 + (lane >> 2) * 4096 + (idx & 63) * 64 + (((lane ^ (idx >> 1)) & 3) << 4), fix);
      fence_async_smem();
    }
    bar_arrive(4 + wq, 160); bar_arrive(8 + wq, 160);
    FRESH();
    mbar_wait_b(BAR(B_OFREE), L);
    #define blk (bi * 2 + (bid & 1))
    if (tid < 33) st_ll(tid < 32 ? &P.g->row[blk][bc * 32 + tid] : &P.g->best[bc][blk], 0u, 0u, 0u, 0u);
    mbar_wait_b(BAR(B_XRDY), L);
    PROFX(tid == 0, 37 + L * 16);
    FRESH();
    {
      float s1 = 0.f, s2 = 0.f, d = 0.f;
      #pragma unroll 1
      for (int q = 0; q < 8; q += 4) { const float4 v = poll_sum4(&P.g->statP[q][blk * 128 + tid], 2048, tag); s1 += v.x; s2 += v.y; d += v.z; }
      PROFX(tid == 0, 39 + L * 16);
      uint4 a = lds128(sb + INFO2), b, c;
      float m = s1 * (1.f / 1024.f), var = fmaxf(fmaf(-m, m, s2 * (1.f / 1024.f)), 0.f), rs = rsqrtf(var + LN_EPS);
      uint32_t key = UI(fmaf(-m, (FL(a.x) + FL(a.y)) + (FL(a.z) + FL(a.w)), d) * rs);
      key ^= (uint32_t)((int)key >> 31) | 0x80000000u;
      uint32_t win = __ballot_sync(0xffffffffu, key == __reduce_max_sync(0xffffffffu, key));
      if (lane == __ffs(win) - 1) sts128(sb + RED + wq * 16, make_uint4(key, UI(m), UI(rs), (tag << 11) | (uint32_t)(blk * 128 + tid)));
      if (L) sts64f(sb + PAR + tid * 8, 1.f + rs, -m * rs);
      else if ((tid >> 4) == bc) st_ll(&P.g->statF[blk * 128 + tid], UI(m), UI(var), 0u, tag + 1);
      bar_sync(2, 128);
      if (wq == 0) {
        mbar_wait(BAR(B_XRDY + 1), L); mbar_wait(BAR(B_XRDY + 3), L);
        a = best4(sb + RED);
        float2 v = lds64f(sb + (lane >> 4) * 32768 + (a.w & 255) * 128 + (((lane & 15) * 8) ^ ((a.w & 7) << 4)));
        st_ll(&P.g->row[blk][bc * 32 + lane], UI(v.x), UI(v.y), 0u, tag);
        if (lane == 0) st_ll(&P.g->best[bc][blk], a.x, a.y, a.z, a.w);
        __syncwarp();
        if (lane < 2 + 2 * L) mbar_arrive(L ? BAR(B_PAR) : BAR(B_XFREE + lane));
      }
      PROFX(tid == 0, 18 + L * 6);
      FRESH();
      a = poll_ll(&P.g->best[bc][lane & 15], 0xfffff800u, tag << 11);
      win = __ffs(__ballot_sync(0xffffffffu, a.x == __reduce_max_sync(0xffffffffu, a.x))) - 1;
      idx = __shfl_sync(0xffffffffu, a.w, win) & 2047;
      PROFX(tid == 0, 19 + L * 6);
      poll_ll2(&P.g->row[win][tid], &P.g->row[win][tid + 128], 0xffffffffu, tag, c, b);
      c.z = b.x; c.w = b.y;
      a.x = __shfl_sync(0xffffffffu, a.x, win); a.y = __shfl_sync(0xffffffffu, a.y, win); a.z = __shfl_sync(0xffffffffu, a.z, win);
      sts32(sb + INFO2 + 28, idx);
      PROFX(tid == 0, 61 + L);
      b = norm8(c, FL(a.y), FL(a.z));
      if (L) put_bf16(b, sb + HV + tid * 8); else put_f32(b, sb + HV + tid * 16, 2048);
      if ((tid >> 1) == (bid & 63)) {
        sts128(sb + RED + 64 + (tid & 1) * 16, bid < 64 ? make_uint4(c.x, c.y, b.x, b.y) : make_uint4(c.z, c.w, b.z, b.w));
        sts32(sb + RED + 96, a.x);
      }
      bar_sync(2 + L, 128 + L * 256);
      if (L) {
        const int r0 = blk * 128 + (tid >> 4);
        uint32_t src = sb + ((tid >> 3) & 1) * 32768 + (r0 & 255) * 128 + (((tid ^ r0) & 7) << 4);
        uint4* dst = (uint4*)(P.out + (size_t)r0 * 1024 + bc * 128) + (tid & 15);
        #pragma unroll 4
        for (int it = 0; it < 16; it++) { uint4 v = lds128(src + it * 1024); if (idx - r0 != it * 8) dst[it * 1024] = v; }
      }
    }
    #pragma unroll 1
    for (int st = L; st < 2; st++) {
      FRESH();
      float a[8] = {0.f, 0.f, 0.f, 0.f, 0.f, 0.f, 0.f, 0.f};
      if (L == 0 && fid < 112) {
        uint32_t ha = st ? sb + RED + 768 : sb + HV + ((wq & 1) * 64 + (lane >> 2)) * 4;
        uint32_t ph = st ? 0x1cu : 0x171u, bar = st ? BAR(B_STG + 2) : BAR(B_STG);
        uint32_t wa = sb + STG + wq * 4096 + (st ? 32768 + lane * 16 : (lane ^ (lane >> 3)) * 16);
        const uint32_t hx = st ? 256 : 512;
        const bool lead = lane == 0;
        uint4 vc = make_uint4(0u, 0u, 0u, 0u); float hc = 0.f;
        #pragma unroll 1
        do {
          mbar_wait(bar, ph & 1);
          PROFX(lead && threadIdx.x == 256 && st == 0 && (ph > 255 || ph < 4), 40 - 23 + __clz(ph));
          #pragma unroll
          for (int n = 0; n < 8; n++) { const uint4 v = lds128(wa + n * 512); const float h = lds32f(ha + n * 32); fma8(a, vc, hc); vc = v; hc = h; }
          __syncwarp();
          if (lead) mbar_arrive(bar - 8 * (B_STG - B_STGE));
          const bool wrap = bar == BAR(B_STG + 2);
          bar += wrap ? -16 : 8; wa += wrap ? -32768 : 16384; ha += hx;
          ph >>= 1;
        } while (ph != 1);
        fma8(a, vc, hc);
      }
      FRESH();
      if (st == 1) {
        const uint32_t t8 = lds32(sb + INFO + 12) + L;
        if (L == 0 && fid < 112) {
          const bool odd = lane & 1;
          #pragma unroll
          for (int e = 0; e < 4; e++) { float z = __shfl_xor_sync(0xffffffffu, odd ? a[e] : a[4 + e], 1); if (odd) a[e] = z; else a[4 + e] = z; }
          uint4* dst = &P.g->yP[tid & ~1][fid][tid & 1];
          st_ll(dst, UI(a[0]), UI(a[1]), UI(a[2]), (UI(a[3]) & ~255u) | t8);
          st_ll(dst + 224, UI(a[4]), UI(a[5]), UI(a[6]), (UI(a[7]) & ~255u) | t8);
          PROFX(tid == 0, 21);
        }
        if (tid == 0) { uint32_t k = lds32(sb + RED + 96); sts32f(sb + RED + 100, bf_round(__fdividef(1.f, 1.f + __expf(-bf_round(FL(k ^ (~(uint32_t)((int)k >> 31) | 0x80000000u))))))); }
        uint4 v0, v1;
        poll_ll2(&P.g->yP[bid][0][min(tid, 111)], &P.g->yP[bid][0][min(tid, 111) + 112], 255u, t8, v0, v1);
        const float lo = (tid < 112 && !(tid & 1)) ? 1.f : 0.f, hi = (tid < 112 && (tid & 1)) ? 1.f : 0.f;
        const float y0 = FL(v0.x) + FL(v1.x), y1 = FL(v0.y) + FL(v1.y), y2 = FL(v0.z) + FL(v1.z), y3 = FL((v0.w & ~255u) | 128u) + FL((v1.w & ~255u) | 128u);
        a[0] = y0 * lo; a[1] = y1 * lo; a[2] = y2 * lo; a[3] = y3 * lo; a[4] = y0 * hi; a[5] = y1 * hi; a[6] = y2 * hi; a[7] = y3 * hi;
      }
      sts32f(sb + RED + 256 + wq * 128 + ((lane & 3) * 8 + (lane >> 2)) * 4, fold8(a));
      bar_sync(2, 128);
      const uint32_t d = sb + RED + 256 + lane * 4;
      float z0 = lds32f(d) + lds32f(d + 128), z1 = lds32f(d + 256) + lds32f(d + 384);
      if (st == 0) {
        sts32f(sb + RED + 768 + lane * 32 + wq * 4, swiglu(z0, z1));
        bar_sync(2, 128);
        if (fid < 112) { st_ll(&P.g->yP[tid & ~1][fid][tid & 1], 0u, 0u, 0u, 0u); st_ll(&P.g->yP[tid | 1][fid][tid & 1], 0u, 0u, 0u, 0u); }
        else { const uint32_t t0 = clk(); while (clk() - t0 < IDLE_T) __nanosleep(200); }
        if (tid < 80) st_ll(tid < 64 ? &P.g->patch[bid][tid] : &P.g->x2[(tid >> 1) & 7][2 * bid + (tid & 1)], 0u, 0u, 0u, 0u);
        PROFX(tid == 0, 20); continue; }
      z0 += z1;
      z0 += __shfl_xor_sync(0xffffffffu, z0, 8); z0 += __shfl_xor_sync(0xffffffffu, z0, 16);
      uint32_t xw = lds32(sb + RED + 64 + (lane & 4) * 4 + (lane & 2) * 2), hw = lds32(sb + RED + 72 + (lane & 4) * 4 + (lane & 2) * 2);
      z0 = bf_round(((lane & 1) ? bf_hi(hw) : bf_lo(hw)) + bf_round(bf_round(z0) * lds32f(sb + RED + 100))) + ((lane & 1) ? bf_hi(xw) : bf_lo(xw));
      uint32_t v = pack_bf16(z0, __shfl_down_sync(0xffffffffu, z0, 1)), v2 = __shfl_down_sync(0xffffffffu, v, 2);
      if (L) { if (tid == 0 || tid == 4) *(uint2*)(P.out + (size_t)idx * 1024 + bid * 8 + tid) = make_uint2(v, v2); PROFW(tid == 0, 28); }
      else if ((tid & 3) == 0 && tid < 64) st_ll(&P.g->x2[tid >> 3][2 * bid + ((tid >> 2) & 1)], v, v2, 0u, tag + 1);
    }
    if (L == 0) {
      PROFX(tid == 0, 22);
      FRESH();
      uint4 x, y; poll_ll2(&P.g->x2[bi][tid], &P.g->x2[bi][tid + 128], 0xffffffffu, tag + 1, x, y);
      x.z = y.x; x.w = y.y;
      if (wq == (bc & 3)) sts64f(sb + X2SEG + lane * 8, FL(bc < 4 ? x.x : x.z), FL(bc < 4 ? x.y : x.w));
      float s1 = 0.f, s2 = 0.f;
      sum8(x, s1, s2);
      #pragma unroll
      for (int o = 16; o; o >>= 1) { s1 += __shfl_xor_sync(0xffffffffu, s1, o); s2 += __shfl_xor_sync(0xffffffffu, s2, o); }
      sts64f(sb + RED + wq * 8, s1, s2);
      bar_sync(2, 128);
      y = lds128(sb + RED); uint4 y2 = lds128(sb + RED + 16);
      float m = ((FL(y.x) + FL(y.z)) + (FL(y2.x) + FL(y2.z))) * (1.f / 1024.f);
      put_bf16(norm8(x, m, rsqrtf(fmaxf(fmaf(-m, m, ((FL(y.y) + FL(y.w)) + (FL(y2.y) + FL(y2.w))) * (1.f / 1024.f)), 0.f) + LN_EPS)), sb + HV + tid * 8);
      mbar_wait(BAR(B_STG), 1); mbar_wait(BAR(B_STG + 1), 0); mbar_wait(BAR(B_STG + 2), 0);
      bar_sync(2, 128);
      PROFX(tid == 0, 30);
      float d0[4] = {0.f, 0.f, 0.f, 0.f}, d1[4] = {0.f, 0.f, 0.f, 0.f}, d2[4] = {0.f, 0.f, 0.f, 0.f};
      const uint32_t bd = (64 + (HV >> 4) + uni(bid & 3) * 32) | 0x10000u;
      #pragma unroll 1
      for (int ks = 0; ks < 8; ks++) {
        const uint32_t ad = (64 + (STG >> 4) + ks * 128) | (64u << 16);
        wg_fence();
        wgmma_ss_n8<0, 1>(d0, mkd<HI64>(ad), mkd<8>(bd + ks * 4), 1);
        wgmma_ss_n8<0, 1>(d1, mkd<HI64>(ad + 1024), mkd<8>(bd + ks * 4), 1);
        wgmma_ss_n8<0, 1>(d2, mkd<HI64>(ad + 2048), mkd<8>(bd + ks * 4), 1);
        wg_commit();
      }
      wg_wait<0>(); keep(d0); keep(d1); keep(d2);
      FRESH();
      if ((lane & 3) == (wq >> 1)) {
        uint4* dst = &P.g->patch[bid][(wq & 1) * 32 + (lane >> 2) * 2 + (wq >> 1)];
        st_ll(dst, UI(d0[0]), UI(d1[0]), UI(d2[0]), tag + 1); st_ll(dst + 16, UI(d0[2]), UI(d1[2]), UI(d2[2]), tag + 1);
      }
      PROFX(tid == 0, 31);
    }
  }
  if (bid == 0 && tid == 0) P.g->epoch = lds32(sb + INFO2 + 16) + 1;
  #undef blk
  #undef bid
  #undef fid
  #undef bi
  #undef bp
  #undef bc
  #undef FRESH
  #undef lane
  #undef wq
}

__global__ void __cluster_dims__(2, 1, 1) __launch_bounds__(512, 1) fused_kernel(const __grid_constant__ Params P) {
  extern __shared__ __align__(1024) uint8_t smem_raw[];
  const uint32_t sb = smem_u32(smem_raw);
  PROFT(threadIdx.x == 0, 0);
  if (threadIdx.x < 32) { if (elect()) {
    for (int s = 0; s < 3; s++) mbar_init(BAR(B_FULLQ + s), 1);
    asm volatile("fence.mbarrier_init.release.cluster;" ::: "memory");
    #pragma unroll 1
    for (int s = 0; s < 3; s++) {
      mbar_expect_tx(BAR(B_FULLQ + s), 57344);
      tma_2d(sb + qa_off(s), &P.mX, s * 64, (BID >> 4) * 256, BAR(B_FULLQ + s));
      tma_3d(sb + qb_off(s), &P.mWq, (BID & 15) * 64, s * 64, 0, BAR(B_FULLQ + s));
    }
    if ((sb & 0x3FFFFu) != 1024) __trap();
  } } else if (threadIdx.x == 480) {
    asm volatile("prefetch.tensormap [%0];" :: "l"(&P.mWq) : "memory");
  } else if (threadIdx.x >= 32 && !(threadIdx.x & 28) && (threadIdx.x >> 3) + (threadIdx.x & 3) <= B_COUNT + 1) {
    int b = (threadIdx.x >> 3) + (threadIdx.x & 3) - 1;
    if (b == B_COUNT) b = B_ROW;
    const uint32_t cnt = b < B_XFREE ? (b == B_OFREE ? 1 : 2) : (b < B_KVRDY ? 3 : (b < B_KVFULL || b == B_PAR ? 4 : (b == B_PFREE ? 2 : 1)));
    mbar_init(BAR(b), cnt);
    asm volatile("fence.mbarrier_init.release.cluster;" ::: "memory");
  }
  __syncthreads();
  asm volatile("barrier.cluster.arrive.relaxed.aligned;" ::: "memory");
  const int wg = __shfl_sync(0xffffffffu, threadIdx.x >> 7, 0);
  if (wg < 2) { reg_inc<224>(); consumer(P, sb, wg); }
  else if (wg == 2) { reg_dec<40>(); aux(P, sb); }
  else {
    reg_dec<24>();
    asm volatile("barrier.cluster.wait.aligned;" ::: "memory");
    const int w = __shfl_sync(0xffffffffu, (threadIdx.x >> 5) & 3, 0);
    if (w == 0) loader(P, sb);
    else if (w < 3) storer(P, sb, w - 1);
    else if (elect()) stager(P, sb);
  }
}

typedef CUresult (*EncFn)(CUtensorMap*, CUtensorMapDataType, cuuint32_t, void*, const cuuint64_t*, const cuuint64_t*, const cuuint32_t*, const cuuint32_t*,
                          CUtensorMapInterleave, CUtensorMapSwizzle, CUtensorMapL2promotion, CUtensorMapFloatOOBfill);
static void mk_map(EncFn enc, CUtensorMap* m, const void* ptr, int rank, const cuuint64_t* dims, const cuuint64_t* strides, const cuuint32_t* box,
                   CUtensorMapSwizzle sw, CUtensorMapL2promotion pr) {
  cuuint32_t es[5] = {1, 1, 1, 1, 1};
  enc(m, CU_TENSOR_MAP_DATA_TYPE_BFLOAT16, rank, (void*)ptr, dims, strides, box, es, CU_TENSOR_MAP_INTERLEAVE_NONE, sw, pr, CU_TENSOR_MAP_FLOAT_OOB_FILL_NONE);
}
extern "C" void kernel_launch(void* const* d_in, const int* in_sizes, int n_in, void* d_out, int out_size) {
  (void)in_sizes; (void)n_in; (void)out_size;
  void* fn = nullptr; cudaDriverEntryPointQueryResult q;
  cudaGetDriverEntryPoint("cuTensorMapEncodeTiled", &fn, cudaEnableDefault, &q);
  EncFn enc = (EncFn)fn;
  cudaFuncSetAttribute(fused_kernel, cudaFuncAttributeMaxDynamicSharedMemorySize, SMEM_BYTES);
  Params P;
  const CUtensorMapSwizzle S128 = CU_TENSOR_MAP_SWIZZLE_128B, S64 = CU_TENSOR_MAP_SWIZZLE_64B, S0 = CU_TENSOR_MAP_SWIZZLE_NONE;
  const CUtensorMapL2promotion L256 = CU_TENSOR_MAP_L2_PROMOTION_L2_256B, L128 = CU_TENSOR_MAP_L2_PROMOTION_L2_128B;
  { cuuint64_t d[2] = {1024, 2048}, s[1] = {2048}; cuuint32_t b[2] = {64, 256}, bh[2] = {64, 128};
    mk_map(enc, &P.mX, d_in[0], 2, d, s, b, S128, L256); mk_map(enc, &P.mXh, d_in[0], 2, d, s, bh, S128, L256); }
  { cuuint64_t d[3] = {1024, 1024, 3}, s[2] = {6144, 2048}; cuuint32_t b[3] = {64, 64, 3}; mk_map(enc, &P.mWq, d_in[1], 3, d, s, b, S128, L256); }
  { cuuint64_t d[5] = {64, 32, 2, 16, 16}, s[4] = {2048, 65536, 131072, 128}; cuuint32_t b[5] = {64, 32, 1, 2, 2}; mk_map(enc, &P.mWo, d_in[2], 5, d, s, b, S128, L256); }
  { cuuint64_t d[2] = {3584, 1024}, s[1] = {7168}; cuuint32_t b[2] = {32, 128};
    mk_map(enc, &P.mWg, d_in[5], 2, d, s, b, S64, L128); mk_map(enc, &P.mWu, d_in[6], 2, d, s, b, S64, L128); }
  { cuuint64_t d[2] = {3072, 1024}, s[1] = {6144}; cuuint32_t b[2] = {32, 256}; mk_map(enc, &P.mWp, d_in[1], 2, d, s, b, S64, L128); }
  { cuuint64_t d[3] = {256, 3584, 4}, s[2] = {2048, 512}; cuuint32_t b[3] = {256, 8, 4}; mk_map(enc, &P.mWd, d_in[7], 3, d, s, b, S0, L128); }
  P.x0 = (const bf16*)d_in[0]; P.wqkv = (const bf16*)d_in[1]; P.wo = (const bf16*)d_in[2]; P.wr = (const bf16*)d_in[4]; P.wg = (const bf16*)d_in[5]; P.wu = (const bf16*)d_in[6]; P.wd = (const bf16*)d_in[7];
  P.out = (bf16*)d_out;
  cudaGetSymbolAddress((void**)&P.g, g_scr);
  for (int b = 0; b < 128; b++) {
    int j = b >> 1, quad = j < 4 ? 0 : (j < 36 ? 1 + (j - 4) % 8 : 9 + (j - 36) % 7), pos = j < 4 ? j : (j < 36 ? (j - 4) / 8 : (j - 36) / 7);
    int bid = ((quad >> 2) * 2 + (pos >> 1)) * 16 + ((quad & 3) * 2 + (pos & 1)) * 2 + (b & 1);
    int e = pos * 2 + (b & 1), fid = e < 7 ? quad * 7 + e : 112 + quad;
    P.map[b] = bid | fid << 8;
  }
  fused_kernel<<<128, 512, SMEM_BYTES>>>(P);
}
```

```cpp
#include <cuda_runtime.h>
#include <cuda_bf16.h>
#include <cuda.h>
#include <stdint.h>
#include <stddef.h>
typedef __nv_bfloat16 bf16;

template<int TB, int TA = 0> __device__ __forceinline__ void wgmma_ss_n192(float (&d)[96], uint64_t da, uint64_t db, int scale_d) {
  asm volatile("{\n.reg .pred p;\nsetp.ne.b32 p, %98, 0;\n"
    "wgmma.mma_async.sync.aligned.m64n192k16.f32.bf16.bf16 {%0, %1, %2, %3, %4, %5, %6, %7, %8, %9, %10, %11, %12, %13, %14, %15, %16, %17, %18, %19, %20, %21, %22, %23, %24, %25, %26, %27, %28, %29, %30, %31, %32, %33, %34, %35, %36, %37, %38, %39, %40, %41, %42, %43, %44, %45, %46, %47, %48, %49, %50, %51, %52, %53, %54, %55, %56, %57, %58, %59, %60, %61, %62, %63, %64, %65, %66, %67, %68, %69, %70, %71, %72, %73, %74, %75, %76, %77, %78, %79, %80, %81, %82, %83, %84, %85, %86, %87, %88, %89, %90, %91, %92, %93, %94, %95}, %96, %97, p, 1, 1, %100, %99;\n}\n"
    : "+f"(d[0]), "+f"(d[1]), "+f"(d[2]), "+f"(d[3]), "+f"(d[4]), "+f"(d[5]), "+f"(d[6]), "+f"(d[7]), "+f"(d[8]), "+f"(d[9]), "+f"(d[10]), "+f"(d[11]), "+f"(d[12]), "+f"(d[13]), "+f"(d[14]), "+f"(d[15]), "+f"(d[16]), "+f"(d[17]), "+f"(d[18]), "+f"(d[19]), "+f"(d[20]), "+f"(d[21]), "+f"(d[22]), "+f"(d[23]), "+f"(d[24]), "+f"(d[25]), "+f"(d[26]), "+f"(d[27]), "+f"(d[28]), "+f"(d[29]), "+f"(d[30]), "+f"(d[31]), "+f"(d[32]), "+f"(d[33]), "+f"(d[34]), "+f"(d[35]), "+f"(d[36]), "+f"(d[37]), "+f"(d[38]), "+f"(d[39]), "+f"(d[40]), "+f"(d[41]), "+f"(d[42]), "+f"(d[43]), "+f"(d[44]), "+f"(d[45]), "+f"(d[46]), "+f"(d[47]), "+f"(d[48]), "+f"(d[49]), "+f"(d[50]), "+f"(d[51]), "+f"(d[52]), "+f"(d[53]), "+f"(d[54]), "+f"(d[55]), "+f"(d[56]), "+f"(d[57]), "+f"(d[58]), "+f"(d[59]), "+f"(d[60]), "+f"(d[61]), "+f"(d[62]), "+f"(d[63]), "+f"(d[64]), "+f"(d[65]), "+f"(d[66]), "+f"(d[67]), "+f"(d[68]), "+f"(d[69]), "+f"(d[70]), "+f"(d[71]), "+f"(d[72]), "+f"(d[73]), "+f"(d[74]), "+f"(d[75]), "+f"(d[76]), "+f"(d[77]), "+f"(d[78]), "+f"(d[79]), "+f"(d[80]), "+f"(d[81]), "+f"(d[82]), "+f"(d[83]), "+f"(d[84]), "+f"(d[85]), "+f"(d[86]), "+f"(d[87]), "+f"(d[88]), "+f"(d[89]), "+f"(d[90]), "+f"(d[91]), "+f"(d[92]), "+f"(d[93]), "+f"(d[94]), "+f"(d[95])
    : "l"(da), "l"(db), "r"(scale_d), "n"(TB), "n"(TA));
}

template<int TB> __device__ __forceinline__ void wgmma_rs_n192(float (&d)[96], uint32_t a0, uint32_t a1, uint32_t a2, uint32_t a3, uint64_t db, int scale_d) {
  asm volatile("{\n.reg .pred p;\nsetp.ne.b32 p, %101, 0;\n"
    "wgmma.mma_async.sync.aligned.m64n192k16.f32.bf16.bf16 {%0, %1, %2, %3, %4, %5, %6, %7, %8, %9, %10, %11, %12, %13, %14, %15, %16, %17, %18, %19, %20, %21, %22, %23, %24, %25, %26, %27, %28, %29, %30, %31, %32, %33, %34, %35, %36, %37, %38, %39, %40, %41, %42, %43, %44, %45, %46, %47, %48, %49, %50, %51, %52, %53, %54, %55, %56, %57, %58, %59, %60, %61, %62, %63, %64, %65, %66, %67, %68, %69, %70, %71, %72, %73, %74, %75, %76, %77, %78, %79, %80, %81, %82, %83, %84, %85, %86, %87, %88, %89, %90, %91, %92, %93, %94, %95}, {%96, %97, %98, %99}, %100, p, 1, 1, %102;\n}\n"
    : "+f"(d[0]), "+f"(d[1]), "+f"(d[2]), "+f"(d[3]), "+f"(d[4]), "+f"(d[5]), "+f"(d[6]), "+f"(d[7]), "+f"(d[8]), "+f"(d[9]), "+f"(d[10]), "+f"(d[11]), "+f"(d[12]), "+f"(d[13]), "+f"(d[14]), "+f"(d[15]), "+f"(d[16]), "+f"(d[17]), "+f"(d[18]), "+f"(d[19]), "+f"(d[20]), "+f"(d[21]), "+f"(d[22]), "+f"(d[23]), "+f"(d[24]), "+f"(d[25]), "+f"(d[26]), "+f"(d[27]), "+f"(d[28]), "+f"(d[29]), "+f"(d[30]), "+f"(d[31]), "+f"(d[32]), "+f"(d[33]), "+f"(d[34]), "+f"(d[35]), "+f"(d[36]), "+f"(d[37]), "+f"(d[38]), "+f"(d[39]), "+f"(d[40]), "+f"(d[41]), "+f"(d[42]), "+f"(d[43]), "+f"(d[44]), "+f"(d[45]), "+f"(d[46]), "+f"(d[47]), "+f"(d[48]), "+f"(d[49]), "+f"(d[50]), "+f"(d[51]), "+f"(d[52]), "+f"(d[53]), "+f"(d[54]), "+f"(d[55]), "+f"(d[56]), "+f"(d[57]), "+f"(d[58]), "+f"(d[59]), "+f"(d[60]), "+f"(d[61]), "+f"(d[62]), "+f"(d[63]), "+f"(d[64]), "+f"(d[65]), "+f"(d[66]), "+f"(d[67]), "+f"(d[68]), "+f"(d[69]), "+f"(d[70]), "+f"(d[71]), "+f"(d[72]), "+f"(d[73]), "+f"(d[74]), "+f"(d[75]), "+f"(d[76]), "+f"(d[77]), "+f"(d[78]), "+f"(d[79]), "+f"(d[80]), "+f"(d[81]), "+f"(d[82]), "+f"(d[83]), "+f"(d[84]), "+f"(d[85]), "+f"(d[86]), "+f"(d[87]), "+f"(d[88]), "+f"(d[89]), "+f"(d[90]), "+f"(d[91]), "+f"(d[92]), "+f"(d[93]), "+f"(d[94]), "+f"(d[95])
    : "r"(a0), "r"(a1), "r"(a2), "r"(a3), "l"(db), "r"(scale_d), "n"(TB));
}

template<int TB, int TA = 0> __device__ __forceinline__ void wgmma_ss_n128(float (&d)[64], uint64_t da, uint64_t db, int scale_d) {
  asm volatile("{\n.reg .pred p;\nsetp.ne.b32 p, %66, 0;\n"
    "wgmma.mma_async.sync.aligned.m64n128k16.f32.bf16.bf16 {%0, %1, %2, %3, %4, %5, %6, %7, %8, %9, %10, %11, %12, %13, %14, %15, %16, %17, %18, %19, %20, %21, %22, %23, %24, %25, %26, %27, %28, %29, %30, %31, %32, %33, %34, %35, %36, %37, %38, %39, %40, %41, %42, %43, %44, %45, %46, %47, %48, %49, %50, %51, %52, %53, %54, %55, %56, %57, %58, %59, %60, %61, %62, %63}, %64, %65, p, 1, 1, %68, %67;\n}\n"
    : "+f"(d[0]), "+f"(d[1]), "+f"(d[2]), "+f"(d[3]), "+f"(d[4]), "+f"(d[5]), "+f"(d[6]), "+f"(d[7]), "+f"(d[8]), "+f"(d[9]), "+f"(d[10]), "+f"(d[11]), "+f"(d[12]), "+f"(d[13]), "+f"(d[14]), "+f"(d[15]), "+f"(d[16]), "+f"(d[17]), "+f"(d[18]), "+f"(d[19]), "+f"(d[20]), "+f"(d[21]), "+f"(d[22]), "+f"(d[23]), "+f"(d[24]), "+f"(d[25]), "+f"(d[26]), "+f"(d[27]), "+f"(d[28]), "+f"(d[29]), "+f"(d[30]), "+f"(d[31]), "+f"(d[32]), "+f"(d[33]), "+f"(d[34]), "+f"(d[35]), "+f"(d[36]), "+f"(d[37]), "+f"(d[38]), "+f"(d[39]), "+f"(d[40]), "+f"(d[41]), "+f"(d[42]), "+f"(d[43]), "+f"(d[44]), "+f"(d[45]), "+f"(d[46]), "+f"(d[47]), "+f"(d[48]), "+f"(d[49]), "+f"(d[50]), "+f"(d[51]), "+f"(d[52]), "+f"(d[53]), "+f"(d[54]), "+f"(d[55]), "+f"(d[56]), "+f"(d[57]), "+f"(d[58]), "+f"(d[59]), "+f"(d[60]), "+f"(d[61]), "+f"(d[62]), "+f"(d[63])
    : "l"(da), "l"(db), "r"(scale_d), "n"(TB), "n"(TA));
}

template<int TB, int TA = 0> __device__ __forceinline__ void wgmma_ss_n64(float (&d)[32], uint64_t da, uint64_t db, int scale_d) {
  asm volatile("{\n.reg .pred p;\nsetp.ne.b32 p, %34, 0;\n"
    "wgmma.mma_async.sync.aligned.m64n64k16.f32.bf16.bf16 {%0, %1, %2, %3, %4, %5, %6, %7, %8, %9, %10, %11, %12, %13, %14, %15, %16, %17, %18, %19, %20, %21, %22, %23, %24, %25, %26, %27, %28, %29, %30, %31}, %32, %33, p, 1, 1, %36, %35;\n}\n"
    : "+f"(d[0]), "+f"(d[1]), "+f"(d[2]), "+f"(d[3]), "+f"(d[4]), "+f"(d[5]), "+f"(d[6]), "+f"(d[7]), "+f"(d[8]), "+f"(d[9]), "+f"(d[10]), "+f"(d[11]), "+f"(d[12]), "+f"(d[13]), "+f"(d[14]), "+f"(d[15]), "+f"(d[16]), "+f"(d[17]), "+f"(d[18]), "+f"(d[19]), "+f"(d[20]), "+f"(d[21]), "+f"(d[22]), "+f"(d[23]), "+f"(d[24]), "+f"(d[25]), "+f"(d[26]), "+f"(d[27]), "+f"(d[28]), "+f"(d[29]), "+f"(d[30]), "+f"(d[31])
    : "l"(da), "l"(db), "r"(scale_d), "n"(TB), "n"(TA));
}

template<int TB, int TA = 0> __device__ __forceinline__ void wgmma_ss_n8(float (&d)[4], uint64_t da, uint64_t db, int scale_d) {
  asm volatile("{\n.reg .pred p;\nsetp.ne.b32 p, %6, 0;\n"
    "wgmma.mma_async.sync.aligned.m64n8k16.f32.bf16.bf16 {%0, %1, %2, %3}, %4, %5, p, 1, 1, %8, %7;\n}\n"
    : "+f"(d[0]), "+f"(d[1]), "+f"(d[2]), "+f"(d[3])
    : "l"(da), "l"(db), "r"(scale_d), "n"(TB), "n"(TA));
}

template<int TB> __device__ __forceinline__ void wgmma_rs_n40(float (&d)[20], uint32_t a0, uint32_t a1, uint32_t a2, uint32_t a3, uint64_t db, int scale_d) {
  asm volatile("{\n.reg .pred p;\nsetp.ne.b32 p, %25, 0;\n"
    "wgmma.mma_async.sync.aligned.m64n40k16.f32.bf16.bf16 {%0, %1, %2, %3, %4, %5, %6, %7, %8, %9, %10, %11, %12, %13, %14, %15, %16, %17, %18, %19}, {%20, %21, %22, %23}, %24, p, 1, 1, %26;\n}\n"
    : "+f"(d[0]), "+f"(d[1]), "+f"(d[2]), "+f"(d[3]), "+f"(d[4]), "+f"(d[5]), "+f"(d[6]), "+f"(d[7]), "+f"(d[8]), "+f"(d[9]), "+f"(d[10]), "+f"(d[11]), "+f"(d[12]), "+f"(d[13]), "+f"(d[14]), "+f"(d[15]), "+f"(d[16]), "+f"(d[17]), "+f"(d[18]), "+f"(d[19])
    : "r"(a0), "r"(a1), "r"(a2), "r"(a3), "l"(db), "r"(scale_d), "n"(TB));
}

#define DEVI __device__ __forceinline__
DEVI uint32_t smem_u32(const void* p) { return (uint32_t)__cvta_generic_to_shared(p); }
DEVI void mbar_init(uint32_t bar, uint32_t cnt) { asm volatile("mbarrier.init.shared::cta.b64 [%0], %1;" :: "r"(bar), "r"(cnt)); }
DEVI void mbar_expect_tx(uint32_t bar, uint32_t bytes) { asm volatile("mbarrier.arrive.expect_tx.shared::cta.b64 _, [%0], %1;" :: "r"(bar), "r"(bytes) : "memory"); }
DEVI void mbar_arrive(uint32_t bar) { asm volatile("mbarrier.arrive.shared::cta.b64 _, [%0];" :: "r"(bar) : "memory"); }
DEVI void mbar_arrive_peer(uint32_t bar) {
  asm volatile("{\n.reg .b32 ra;\nmapa.shared::cluster.u32 ra, %0, %1;\nmbarrier.arrive.shared::cluster.b64 _, [ra];\n}" :: "r"(bar), "r"((blockIdx.x & 1) ^ 1) : "memory");
}
DEVI void bulk_s2peer(uint32_t a, uint32_t bytes, uint32_t bar) {
  asm volatile("{\n.reg .b32 ra, rb;\nmapa.shared::cluster.u32 ra, %0, %3;\nmapa.shared::cluster.u32 rb, %2, %3;\n"
               "cp.async.bulk.shared::cluster.shared::cta.mbarrier::complete_tx::bytes [ra], [%0], %1, [rb];\n}"
               :: "r"(a), "r"(bytes), "r"(bar), "r"((blockIdx.x & 1) ^ 1) : "memory");
}
DEVI void mbar_wait(uint32_t bar, uint32_t parity) {
  asm volatile("{\n.reg .pred p;\nLW:\nmbarrier.try_wait.parity.shared::cta.b64 p, [%0], %1;\n@!p bra LW;\n}" :: "r"(bar), "r"(parity) : "memory");
}
DEVI uint32_t mbar_test(uint32_t bar, uint32_t parity) {
  uint32_t r; asm volatile("{\n.reg .pred p;\nmbarrier.test_wait.parity.shared::cta.b64 p, [%1], %2;\nselp.u32 %0, 1, 0, p;\n}" : "=r"(r) : "r"(bar), "r"(parity) : "memory"); return r;
}
DEVI void mbar_wait_b(uint32_t bar, uint32_t parity) {
  asm volatile("{\n.reg .pred p;\n.reg .u32 it;\nmov.u32 it, 0;\nLW:\nmbarrier.try_wait.parity.shared::cta.b64 p, [%0], %1;\n@p bra LD;\n"
               "add.u32 it, it, 1;\nsetp.lt.u32 p, it, 0x1000000;\n@p bra LW;\ntrap;\nLD:\n}" :: "r"(bar), "r"(parity) : "memory");
}
DEVI void tma_2d(uint32_t dst, const CUtensorMap* m, int c0, int c1, uint32_t bar) {
  asm volatile("cp.async.bulk.tensor.2d.shared::cluster.global.mbarrier::complete_tx::bytes [%0], [%1, {%3, %4}], [%2];"
    :: "r"(dst), "l"(m), "r"(bar), "r"(c0), "r"(c1) : "memory");
}
DEVI void tma_3d(uint32_t dst, const CUtensorMap* m, int c0, int c1, int c2, uint32_t bar) {
  asm volatile("cp.async.bulk.tensor.3d.shared::cluster.global.mbarrier::complete_tx::bytes [%0], [%1, {%3, %4, %5}], [%2];"
    :: "r"(dst), "l"(m), "r"(bar), "r"(c0), "r"(c1), "r"(c2) : "memory");
}
#define POL_EF POL_FIRST
constexpr uint64_t POL_FIRST = 0x12F0000000000000ull, POL_NORMAL = 0x1000000000000000ull;
DEVI void tma_2d_h(uint32_t dst, const CUtensorMap* m, int c0, int c1, uint32_t bar, uint64_t pol) {
  asm volatile("cp.async.bulk.tensor.2d.shared::cluster.global.mbarrier::complete_tx::bytes.L2::cache_hint [%0], [%1, {%3, %4}], [%2], %5;"
    :: "r"(dst), "l"(m), "r"(bar), "r"(c0), "r"(c1), "l"(pol) : "memory");
}
DEVI void tma_3d_h(uint32_t dst, const CUtensorMap* m, int c0, int c1, int c2, uint32_t bar, uint64_t pol) {
  asm volatile("cp.async.bulk.tensor.3d.shared::cluster.global.mbarrier::complete_tx::bytes.L2::cache_hint [%0], [%1, {%3, %4, %5}], [%2], %6;"
    :: "r"(dst), "l"(m), "r"(bar), "r"(c0), "r"(c1), "r"(c2), "l"(pol) : "memory");
}
DEVI void bulk_g2s_h(uint32_t s, const void* g, uint32_t bytes, uint32_t bar, uint64_t pol = POL_EF) {
  asm volatile("cp.async.bulk.shared::cluster.global.mbarrier::complete_tx::bytes.L2::cache_hint [%0], [%1], %2, [%3], %4;"
    :: "r"(s), "l"(g), "r"(bytes), "r"(bar), "l"(pol) : "memory");
}
DEVI void tma_5d(uint32_t dst, const CUtensorMap* m, int c0, int c1, int c2, int c3, int c4, uint32_t bar, uint64_t pol) {
  asm volatile("cp.async.bulk.tensor.5d.shared::cluster.global.mbarrier::complete_tx::bytes.L2::cache_hint [%0], [%1, {%3, %4, %5, %6, %7}], [%2], %8;"
    :: "r"(dst), "l"(m), "r"(bar), "r"(c0), "r"(c1), "r"(c2), "r"(c3), "r"(c4), "l"(pol) : "memory");
}
DEVI void tma_prefetch_2d(const CUtensorMap* m, int c0, int c1) {
  asm volatile("cp.async.bulk.prefetch.tensor.2d.L2.global.tile [%0, {%1, %2}];" :: "l"(m), "r"(c0), "r"(c1) : "memory");
}
DEVI void tma_prefetch_3d(const CUtensorMap* m, int c0, int c1, int c2) {
  asm volatile("cp.async.bulk.prefetch.tensor.3d.L2.global.tile [%0, {%1, %2, %3}];" :: "l"(m), "r"(c0), "r"(c1), "r"(c2) : "memory");
}
DEVI void bulk_prefetch(const void* g, uint32_t bytes) { asm volatile("cp.async.bulk.prefetch.L2.global [%0], %1;" :: "l"(g), "r"(bytes) : "memory"); }
DEVI void bulk_g2s(uint32_t s, const void* g, uint32_t bytes, uint32_t bar) {
  asm volatile("cp.async.bulk.shared::cluster.global.mbarrier::complete_tx::bytes [%0], [%1], %2, [%3];" :: "r"(s), "l"(g), "r"(bytes), "r"(bar) : "memory");
}
DEVI void bulk_s2g(void* g, uint32_t s, uint32_t bytes, uint64_t pol = POL_NORMAL) {
  asm volatile("cp.async.bulk.global.shared::cta.bulk_group.L2::cache_hint [%0], [%1], %2, %3;\ncp.async.bulk.commit_group;" :: "l"(g), "r"(s), "r"(bytes), "l"(pol) : "memory");
}
template<int N> DEVI void bulk_wait() { asm volatile("cp.async.bulk.wait_group %0;" :: "n"(N) : "memory"); }
DEVI void fence_async_smem() { asm volatile("fence.proxy.async.shared::cta;" ::: "memory"); }
DEVI void fence_async_glob() { asm volatile("fence.proxy.async.global;" ::: "memory"); }
DEVI unsigned ld_rlx(const unsigned* p) { unsigned v; asm volatile("ld.relaxed.gpu.global.u32 %0, [%1];" : "=r"(v) : "l"(p) : "memory"); return v; }
DEVI void st_rlx(unsigned* p, unsigned v) { asm volatile("st.relaxed.gpu.global.u32 [%0], %1;" :: "l"(p), "r"(v) : "memory"); }
DEVI uint2 ldg_stream(const uint2* p) { uint2 v; asm volatile("ld.global.nc.L1::no_allocate.v2.u32 {%0, %1}, [%2];" : "=r"(v.x), "=r"(v.y) : "l"(p)); return v; }
DEVI void fence_rel() { asm volatile("fence.release.gpu;" ::: "memory"); }
DEVI uint4 ld_ll(const uint4* p) {
  uint4 v;
  asm volatile("{\n.reg .b128 t;\n.reg .b64 a, b;\nld.relaxed.gpu.global.b128 t, [%4];\nmov.b128 {a, b}, t;\nmov.b64 {%0, %1}, a;\nmov.b64 {%2, %3}, b;\n}"
               : "=r"(v.x), "=r"(v.y), "=r"(v.z), "=r"(v.w) : "l"(p) : "memory");
  return v;
}
DEVI void st_ll(uint4* p, uint32_t x, uint32_t y, uint32_t z, uint32_t w) {
  asm volatile("{\n.reg .b128 t;\n.reg .b64 a, b;\nmov.b64 a, {%1, %2};\nmov.b64 b, {%3, %4};\nmov.b128 t, {a, b};\nst.relaxed.gpu.global.b128 [%0], t;\n}"
               :: "l"(p), "r"(x), "r"(y), "r"(z), "r"(w) : "memory");
}
#define SPIN_MAX 0x1000000
DEVI uint4 poll_ll(const uint4* p, uint32_t mask, uint32_t tag) {
  uint4 v; int it = 0;
  do { v = ld_ll(p); if (++it > SPIN_MAX) __trap(); } while (!__all_sync(0xffffffffu, (v.w & mask) == tag));
  return v;
}
DEVI void poll_ll2(const uint4* p, const uint4* q, uint32_t mask, uint32_t tag, uint4& a, uint4& b) {
  int it = 0;
  do { a = ld_ll(p); b = ld_ll(q); if (++it > SPIN_MAX) __trap(); } while (!__all_sync(0xffffffffu, (a.w & mask) == tag && (b.w & mask) == tag));
}
DEVI float4 poll_sum4(const uint4* src, int stride, uint32_t tag) {
  uint4 v0, v1, v2, v3; int it = 0;
  do { v0 = ld_ll(src); v1 = ld_ll(src + stride); v2 = ld_ll(src + 2 * stride); v3 = ld_ll(src + 3 * stride); if (++it > SPIN_MAX) __trap(); }
  while (!__all_sync(0xffffffffu, v0.w == tag && v1.w == tag && v2.w == tag && v3.w == tag));
  #define S4(f) ((__uint_as_float(v0.f) + __uint_as_float(v1.f)) + (__uint_as_float(v2.f) + __uint_as_float(v3.f)))
  return make_float4(S4(x), S4(y), S4(z), 0.f);
  #undef S4
}
DEVI void bar_sync(int id, int n) { asm volatile("bar.sync %0, %1;" :: "r"(id), "r"(n) : "memory"); }
DEVI void bar_arrive(int id, int n) { asm volatile("bar.arrive %0, %1;" :: "r"(id), "r"(n) : "memory"); }
DEVI void wg_fence() { asm volatile("wgmma.fence.sync.aligned;" ::: "memory"); }
DEVI void wg_commit() { asm volatile("wgmma.commit_group.sync.aligned;" ::: "memory"); }
template<int N> DEVI void wg_wait() { asm volatile("wgmma.wait_group.sync.aligned %0;" :: "n"(N) : "memory"); }
template<int N> DEVI void reg_inc() { asm volatile("setmaxnreg.inc.sync.aligned.u32 %0;" :: "n"(N)); }
template<int N> DEVI void reg_dec() { asm volatile("setmaxnreg.dec.sync.aligned.u32 %0;" :: "n"(N)); }
DEVI float ex2f(float x) { float y; asm("ex2.approx.ftz.f32 %0, %1;" : "=f"(y) : "f"(x)); return y; }
DEVI uint32_t pack_bf16(float lo, float hi) { uint32_t r; asm("cvt.rn.bf16x2.f32 %0, %1, %2;" : "=r"(r) : "f"(hi), "f"(lo)); return r; }
DEVI float bf_lo(uint32_t v) { return __uint_as_float(v << 16); }
DEVI float bf_hi(uint32_t v) { return __uint_as_float(v & 0xffff0000u); }
DEVI float bf_round(float x) { return bf_lo(pack_bf16(x, 0.f)); }
DEVI void stsm_x4(uint32_t addr, uint32_t a, uint32_t b, uint32_t c, uint32_t d) {
  asm volatile("stmatrix.sync.aligned.m8n8.x4.shared.b16 [%0], {%1,%2,%3,%4};" :: "r"(addr), "r"(a), "r"(b), "r"(c), "r"(d) : "memory");
}
DEVI void ldsm_x4(uint32_t addr, uint32_t& a, uint32_t& b, uint32_t& c, uint32_t& d) {
  asm volatile("ldmatrix.sync.aligned.m8n8.x4.shared.b16 {%0,%1,%2,%3}, [%4];" : "=r"(a), "=r"(b), "=r"(c), "=r"(d) : "r"(addr) : "memory");
}
DEVI uint4 lds128(uint32_t a) { uint4 v; asm volatile("ld.shared.v4.u32 {%0,%1,%2,%3}, [%4];" : "=r"(v.x), "=r"(v.y), "=r"(v.z), "=r"(v.w) : "r"(a) : "memory"); return v; }
DEVI void sts128(uint32_t a, uint4 v) { asm volatile("st.shared.v4.u32 [%0], {%1,%2,%3,%4};" :: "r"(a), "r"(v.x), "r"(v.y), "r"(v.z), "r"(v.w) : "memory"); }
DEVI float2 lds64f(uint32_t a) { float2 v; asm volatile("ld.shared.v2.f32 {%0,%1}, [%2];" : "=f"(v.x), "=f"(v.y) : "r"(a) : "memory"); return v; }
DEVI void sts64f(uint32_t a, float x, float y) { asm volatile("st.shared.v2.f32 [%0], {%1,%2};" :: "r"(a), "f"(x), "f"(y) : "memory"); }
DEVI uint32_t lds32(uint32_t a) { uint32_t v; asm volatile("ld.shared.u32 %0, [%1];" : "=r"(v) : "r"(a) : "memory"); return v; }
DEVI float lds32f(uint32_t a) { return __uint_as_float(lds32(a)); }
DEVI void sts32(uint32_t a, uint32_t v) { asm volatile("st.shared.u32 [%0], %1;" :: "r"(a), "r"(v) : "memory"); }
DEVI void sts32f(uint32_t a, float v) { sts32(a, __float_as_uint(v)); }
DEVI void sts16(uint32_t a, uint32_t v) { asm volatile("st.shared.u16 [%0], %1;" :: "r"(a), "h"((unsigned short)v) : "memory"); }
template<int N> DEVI void keep(float (&d)[N]) {
  #pragma unroll
  for (int i = 0; i < N; i++) asm volatile("" : "+f"(d[i]) :: "memory");
}
template<int N> DEVI void keep(uint32_t (&d)[N]) {
  #pragma unroll
  for (int i = 0; i < N; i++) asm volatile("" : "+r"(d[i]) :: "memory");
}
template<uint32_t HI> DEVI uint64_t mkd(uint32_t lo) { uint64_t r; asm("mov.b64 %0, {%1, %2};" : "=l"(r) : "r"(lo), "n"(HI)); return r; }
constexpr uint32_t HI128 = (1u << 30) | (1024 >> 4), HI64 = (2u << 30) | (512 >> 4);
#define VOFF(x) ((uint32_t)(x) * (uint32_t)(1 - 65536))
DEVI bool elect() { uint32_t p; asm volatile("{\n.reg .pred q;\nelect.sync _|q, 0xffffffff;\nselp.u32 %0, 1, 0, q;\n}" : "=r"(p)); return p; }
DEVI void warp_signal(uint32_t bar) { __syncwarp(); if (elect()) mbar_arrive(bar); }

struct Scratch {
  uint4 kv[128][4][1024];
  uint4 o[8][2][8][2][1024];
  uint4 x[8][16][2048];
  uint4 zero[1024];
  uint4 statP[8][2048];
  uint4 statF[2048];
  uint4 csP[16][8][96];
  uint4 best[8][16];
  uint4 row[16][256];
  uint4 yP[128][112][2];
  uint4 x2[8][256];
  uint4 patch[128][64];
  unsigned flagKV[128][32];
  unsigned flagO[8][32];
  unsigned flagX[8][32];
  unsigned epoch;
};
__device__ __align__(1024) Scratch g_scr;
#define PROFT(cond, slot)
#define PROFW(cond, slot)
#define PROFD(cond, slot)
#define PROFX(cond, slot)
#define PROFY(cond, slot)

constexpr uint32_t SB0 = 65536, HOLE = 90112, SA2 = 98304, SB1 = 131072, SB2 = 155648, STG = 180224;
constexpr uint32_t KVA = 0, KVB = 98304, QO = 65536;
constexpr uint32_t MISC = 229376, CS = MISC, ONES = MISC + 768, BARS = MISC + 1792, INFO = MISC + 2208, WR = MISC + 2224, X2SEG = MISC + 2736, INFO2 = MISC + 2992, DUMP = MISC + 3040;
constexpr uint32_t PAR = HOLE, HV = HOLE + 2048, RED = HOLE + 6144, PATCH = 196608;
constexpr uint32_t SMEM_BYTES = 232448;
enum { B_FULLQ = 0, B_EMPTYQ = 3, B_FULLW = 6, B_EMPTYW = 12, B_HAFREE = 18, B_OFREE = 20,
       B_XFREE = 21,
       B_KVRDY = 23, B_ORDY = 27, B_XRDY = 35, B_STGE = 39,
       B_KVFULL = 42, B_RES = 46, B_PAR = 47, B_STG = 48, B_PFREE = 51, B_COUNT = 52,
       B_ROW = 154 };
#define BAR(x) (sb + BARS + 8 * (x))
DEVI uint32_t qa_off(int s) { return s == 2 ? SA2 : (uint32_t)s * 32768u; }
DEVI uint32_t qb_off(int s) { return s == 0 ? SB0 : (s == 1 ? SB1 : SB2); }
DEVI int kb_order(int bc, int n) {
  const int e = n < 9 ? n - 2 : n - 9;
  return n < 2 ? 2 * bc + n : 2 * (((e < 4 ? e + 4 : e - 4 + (e - 4 >= (bc & 3))) + (bc & 4)) & 7) + (n >= 9);
}
DEVI int wo_order(int bc, int n) { return (n & 8) | ((n + (bc & 6)) & 7); }
DEVI uint32_t w_off(int s) { return (uint32_t)((0x143065 >> (4 * s)) & 7) * 32768u; }
DEVI uint32_t w_par(int n, int s, int L) { return (n >= 6 && n < 12) ^ (s == 5) ^ (s != 2 && L); }
DEVI int w_next(int n, int s) { return s == 5 ? 0 : (n == 13 ? 3 : s + 1); }

struct Params {
  CUtensorMap mX, mXh, mWq, mWo, mWg, mWu, mWp, mWd;
  const bf16 *x0, *wqkv, *wo, *wr, *wg, *wu, *wd;
  bf16* out;
  Scratch* g;
  unsigned map[128];
};
#define BID ((int)(P.map[blockIdx.x] & 255))
#define FID ((int)(P.map[blockIdx.x] >> 8))
DEVI uint32_t uni(uint32_t v) { return __shfl_sync(0xffffffffu, v, 0); }
#define PQ_N 8
#define PQ_T 700
#define PF0_N 10
#define PF0_T 1600
#define PF1_E 24
#define PF1_T 1100
#define POL_Q1 POL_NORMAL
#define POL_X POL_NORMAL
#define PFA0_BAR 3
#define PFA1_BAR 0
#define PFA0_M 0
#define PFA1_M 0
#define PFA0_T 900
#define PFA1_T 700
#define PF1_S PF0_N
#define PF1_D 0
#define POL_G POL_NORMAL
#define POL_U POL_FIRST
#define POL_D POL_FIRST
#define JQ_N 6
#define WDSRC (P.wd + (size_t)min(fid, 111) * 32768)
#define WDSRC2 (P.wd + FID * 32768)
#define WD_N 4
#define THR_N 5
#define KV_D 1800
#define XD_D 300
#define W0_BAR 3
#define QEF_N 99
#define PACE_T 300
#define IDLE_T 11000
#define LATE_C 2
#define LATE_B B_XFREE + 1
#define LATE_P 0
#define KV_D1 200
#define KV_D2 1200
#define KV_DL 0
#define POL_KV0 POL_FIRST
#define POL_KV1 POL_FIRST
#define POL_O0 POL_FIRST
#define POL_O1 POL_FIRST
#define POL_W0 POL_NORMAL
#define POL_W1 POL_FIRST
#define POL_T POL_FIRST
#define U_C 8
#define ST_M 0
#define POL_Q0 POL_NORMAL
constexpr float LN_EPS = 1e-5f;
constexpr float QSCALE = 0.17677669529663687f * 1.4426950408889634f;

DEVI void fma8(float (&a)[8], uint4 v, float h) {
  a[0] = fmaf(bf_lo(v.x), h, a[0]); a[1] = fmaf(bf_hi(v.x), h, a[1]); a[2] = fmaf(bf_lo(v.y), h, a[2]); a[3] = fmaf(bf_hi(v.y), h, a[3]);
  a[4] = fmaf(bf_lo(v.z), h, a[4]); a[5] = fmaf(bf_hi(v.z), h, a[5]); a[6] = fmaf(bf_lo(v.w), h, a[6]); a[7] = fmaf(bf_hi(v.w), h, a[7]);
}
DEVI uint4 ldsv128(uint32_t a) { uint4 v; asm volatile("ld.volatile.shared.v4.u32 {%0,%1,%2,%3}, [%4];" : "=r"(v.x), "=r"(v.y), "=r"(v.z), "=r"(v.w) : "r"(a) : "memory"); return v; }
DEVI float ldsv32f(uint32_t a) { float v; asm volatile("ld.volatile.shared.f32 %0, [%1];" : "=f"(v) : "r"(a) : "memory"); return v; }
DEVI uint32_t clk() { uint32_t t; asm volatile("mov.u32 %0, %%clock;" : "=r"(t)); return t; }
DEVI int fresh_tid() { int t; asm volatile("mov.u32 %0, %%tid.x;" : "=r"(t)); return t & 127; }
DEVI float fold8(const float (&a)[8]) {
  const int lane = threadIdx.x & 31;
  const bool u = lane & 16, v = lane & 8, x = lane & 4;
  float b0 = (u ? a[4] : a[0]) + __shfl_xor_sync(0xffffffffu, u ? a[0] : a[4], 16), b1 = (u ? a[5] : a[1]) + __shfl_xor_sync(0xffffffffu, u ? a[1] : a[5], 16);
  float b2 = (u ? a[6] : a[2]) + __shfl_xor_sync(0xffffffffu, u ? a[2] : a[6], 16), b3 = (u ? a[7] : a[3]) + __shfl_xor_sync(0xffffffffu, u ? a[3] : a[7], 16);
  float c0 = (v ? b2 : b0) + __shfl_xor_sync(0xffffffffu, v ? b0 : b2, 8), c1 = (v ? b3 : b1) + __shfl_xor_sync(0xffffffffu, v ? b1 : b3, 8);
  return (x ? c1 : c0) + __shfl_xor_sync(0xffffffffu, x ? c0 : c1, 4);
}
DEVI float swiglu(float g, float u) { g = bf_round(g); return bf_round(bf_round(__fdividef(g, 1.f + __expf(-g))) * bf_round(u)); }

DEVI void qk_issue(float (&s)[32], uint32_t qd, uint32_t kd) {
  wgmma_ss_n64<0>(s, mkd<HI64>(qd), mkd<HI64>(kd), 0);
  wgmma_ss_n64<0>(s, mkd<HI64>(qd + 2), mkd<HI64>(kd + 2), 1);
}
template<int J0, int J1> DEVI void exp_pack(const float (&s)[32], uint32_t (&p)[16]) {
  #pragma unroll
  for (int j = J0; j < J1; j++) p[j] = pack_bf16(ex2f(s[2 * j]), ex2f(s[2 * j + 1]));
}
DEVI bool attn_pack(const float (&o)[20], uint32_t (&ob)[8]) {
  const float lo = 5.421010862427522e-20f, hi = 1.8446744073709552e19f;
  float i0, i1; asm("rcp.approx.ftz.f32 %0, %1;" : "=f"(i0) : "f"(o[16])); asm("rcp.approx.ftz.f32 %0, %1;" : "=f"(i1) : "f"(o[18]));
  #pragma unroll
  for (int e = 0; e < 8; e++) ob[e] = pack_bf16(o[2 * e] * ((e & 1) ? i1 : i0), o[2 * e + 1] * ((e & 1) ? i1 : i0));
  return __all_sync(0xffffffffu, o[16] >= lo && o[16] <= hi && o[18] >= lo && o[18] <= hi);
}
DEVI void attn_store(const uint32_t (&ob)[8], bool ok, uint32_t st, uint32_t sb, uint32_t bar) {
  stsm_x4(ok ? st : sb + DUMP, ob[0], ob[1], ob[2], ob[3]); stsm_x4(ok ? st ^ 32 : sb + DUMP, ob[4], ob[5], ob[6], ob[7]);
  __syncwarp();
  asm volatile("{\n.reg .pred p, q;\nelect.sync _|q, 0xffffffff;\nsetp.ne.and.u32 p, %1, 0, q;\n@p mbarrier.arrive.shared::cta.b64 _, [%0];\n}" :: "r"(bar), "r"((uint32_t)ok) : "memory");
}
DEVI void attn_exact(uint32_t st, uint32_t kv, int t, bool hasprev, uint32_t bar) {
  const int lane = threadIdx.x & 31;
  #pragma unroll 1
  for (int row = ((threadIdx.x >> 5) & 3) * 16, n = 0; n < 16; n++, row++) {
    const int k1 = 256 + t * 64 + row;
    float m = -INFINITY, l = 0.f, o = 0.f;
    #pragma unroll 1
    for (int k0 = hasprev ? k1 - 255 : 256; k0 <= k1; k0 += 32) {
      const int k = min(k0 + lane, k1), r = k & 63;
      float sc = 0.f;
      #pragma unroll 1
      for (int c = 0; c < 16; c++) {
        uint32_t a = lds32(st + row * 64 + ((c * 4) ^ ((row & 6) << 3))), b = lds32(kv + (k >> 6) * 8192 + r * 64 + ((c * 4) ^ ((r & 6) << 3)));
        sc = fmaf(bf_lo(a), bf_lo(b), fmaf(bf_hi(a), bf_hi(b), sc));
      }
      float mn = fmaxf(m, sc);
      #pragma unroll 1
      for (int x = 16; x; x >>= 1) mn = fmaxf(mn, __shfl_xor_sync(0xffffffffu, mn, x));
      const float al = ex2f(m - mn), pr = ex2f(sc - mn);
      m = mn; l *= al; o *= al;
      #pragma unroll 1
      for (int q = k0; q <= min(k0 + 31, k1); q++) {
        const float z = __shfl_sync(0xffffffffu, pr, q - k0);
        uint32_t b = lds32(kv + (q >> 6) * 8192 + 4096 + (q & 63) * 64 + (((lane >> 1) * 4) ^ ((q & 6) << 3)));
        l += z; o = fmaf(z, (lane & 1) ? bf_hi(b) : bf_lo(b), o);
      }
    }
    __syncwarp();
    sts16(st + row * 64 + ((lane * 2) ^ ((row & 6) << 3)), pack_bf16(__fdividef(o, l), 0.f));
  }
  warp_signal(bar);
}

template<int K0, int K1, int DONE = 0> DEVI void exp_pv(const float (&s)[32], uint32_t (&p)[16], float (&o)[20], uint32_t vd, bool accum) {
  #pragma unroll
  for (int ks = K0; ks < K1; ks++) {
    if (ks >= DONE) {
      #pragma unroll
      for (int j = 4 * ks; j < 4 * ks + 4; j++) p[j] = pack_bf16(ex2f(s[2 * j]), ex2f(s[2 * j + 1]));
    }
    asm volatile("" : "+r"(p[4 * ks]), "+r"(p[4 * ks + 1]), "+r"(p[4 * ks + 2]), "+r"(p[4 * ks + 3]));
    wg_fence();
    wgmma_rs_n40<1>(o, p[ks * 4], p[ks * 4 + 1], p[ks * 4 + 2], p[ks * 4 + 3], mkd<HI64>(vd + VOFF(ks * 64)), ks ? 1 : accum);
  }
}
DEVI void exp_pv2(const float (&s)[32], const float (&sx)[32], uint32_t (&p)[16], uint32_t (&px)[16], float (&o)[20], uint32_t v0, uint32_t v4,
                  const uint32_t (&msk)[9], int tdiag) {
  #pragma unroll
  for (int ks = 0; ks < 4; ks++) {
    #pragma unroll
    for (int j = 4 * ks; j < 4 * ks + 4; j++) {
      const int c = 8 * (j >> 1) - 8 * (j & 1);
      const uint32_t e = pack_bf16(ex2f(c > tdiag ? s[2 * j] : sx[2 * j]), ex2f(c + 1 > tdiag ? s[2 * j + 1] : sx[2 * j + 1])), m = msk[(j >> 1) - (j & 1) + 1];
      p[j] = e & m; px[j] = e & ~m;
      asm volatile("" : "+r"(p[j]), "+r"(px[j]));
    }
    wg_fence();
    wgmma_rs_n40<1>(o, p[ks * 4], p[ks * 4 + 1], p[ks * 4 + 2], p[ks * 4 + 3], mkd<HI64>(v0 + VOFF(ks * 64)), 1);
    wgmma_rs_n40<1>(o, px[ks * 4], px[ks * 4 + 1], px[ks * 4 + 2], px[ks * 4 + 3], mkd<HI64>(v4 + VOFF(ks * 64)), 1);
  }
}

template<int J0> DEVI void qkv_store(const float (&a)[96], float p0, float p1, uint32_t d) {
  #pragma unroll
  for (int hh = 0; hh < 2; hh++) {
    const int j = 4 * (J0 + 2 * hh);
    stsm_x4(d ^ (hh << 5), pack_bf16(a[j] * p0, a[j + 1] * p0), pack_bf16(a[j + 2] * p1, a[j + 3] * p1),
                           pack_bf16(a[j + 4] * p0, a[j + 5] * p0), pack_bf16(a[j + 6] * p1, a[j + 7] * p1));
  }
}
DEVI void mean_step(float (&a)[96], float m0, float m1, uint32_t cd, bool z) {
  const uint32_t u0 = z ? 0u : __float_as_uint(m0), u1 = z ? 0u : __float_as_uint(m1);
  uint32_t ma[4] = {__byte_perm(u0, 0u, 0x1010), __byte_perm(u1, 0u, 0x1010), __byte_perm(u0, 0u, 0x3232), __byte_perm(u1, 0u, 0x3232)};
  keep(ma);
  wg_fence();
  wgmma_rs_n192<1>(a, ma[0], ma[1], ma[2], ma[3], mkd<2>(cd), 1);
  wg_commit();
}

template<bool FIRST> DEVI void qkv_block(float (&aX)[96], float (&aY)[96], uint32_t sb16, int s, int tX, int tY) {
  uint32_t a16 = sb16 + (qa_off(s) >> 4), b16 = (sb16 + (qb_off(s) >> 4)) | ((8192u >> 4) << 16);
  uint32_t ax = (a16 + tX * 512) | 0x10000u, ay = (a16 + tY * 512) | 0x10000u;
  wg_fence();
  #pragma unroll
  for (int ks = 0; ks < 4; ks++) {
    wgmma_ss_n192<1>(aX, mkd<HI128>(ax + ks * 2), mkd<HI128>(b16 + ks * 128), !(FIRST && ks == 0));
    wgmma_ss_n192<1>(aY, mkd<HI128>(ay + ks * 2), mkd<HI128>(b16 + ks * 128), !(FIRST && ks == 0));
  }
  wg_commit();
}
DEVI void qkv_half(float (&a)[96], uint32_t sb16, int t, uint32_t sa, uint32_t sbb) {
  wg_fence();
  #pragma unroll
  for (int ks = 0; ks < 4; ks++)
    wgmma_ss_n192<1>(a, mkd<HI128>(((sb16 + (sa >> 4) + t * 512) | 0x10000u) + ks * 2), mkd<HI128>(((sb16 + (sbb >> 4)) | ((8192u >> 4) << 16)) + ks * 128), 1);
  wg_commit();
}
DEVI void wo_block(float (&acc)[64], uint32_t sb16, int s, int wg) {
  uint32_t a16 = (sb16 + (w_off(s) >> 4) + wg * 256) | 0x10000u, b16 = (sb16 + (w_off(s) >> 4) + 1024) | ((8192u >> 4) << 16);
  wg_fence();
  #pragma unroll
  for (int ks = 0; ks < 4; ks++)
    wgmma_ss_n128<1>(acc, mkd<HI64>(a16 + (ks >> 1) * 512 + (ks & 1) * 2), mkd<HI128>(b16 + ks * 128), 1);
  wg_commit();
}
DEVI void consumer(const Params& P, uint32_t sb, int wg) {
  const int w = uni((threadIdx.x >> 5) & 3);
  #define LAYER uni(mbar_test(BAR(B_XRDY + wg * 2 + 1), 0))
  #define IDS L = LAYER; const int tid = fresh_tid(), lane = tid & 31
  const uint32_t ids = uni(P.map[blockIdx.x]);
  const int bi = (ids >> 4) & 7, rh = ids & 1, bc = (ids & 15) >> 1, fid = ids >> 8;
  const int tX = 3 - wg, tY = wg;
  constexpr uint32_t sb16 = 1024 >> 4;
  #pragma unroll 1
  while (true) {
    int L = LAYER;
    {
      float aX[96], aY[96];
      const bool lead = fresh_tid() == 0;
      mbar_wait(BAR(B_FULLQ), 0);
      PROFW(threadIdx.x == 0, L * 8 + 1);
      qkv_block<true>(aX, aY, sb16, 0, tX, tY);
      #pragma unroll 1
      for (int n = 1, s = 1, ps = 0, ph = 0; n < 14; n++) {
        mbar_wait(BAR(B_FULLQ + s), ph ^ (s ? L : 0));
        PROFD(threadIdx.x == 0 && L && (n == 2 || n == 3 || n == 7 || n == 11 || n == 13), n == 2 ? 48 : 49 + (n >> 2));
        qkv_block<false>(aX, aY, sb16, s, tX, tY);
        wg_wait<1>(); if (lead) mbar_arrive(BAR(B_EMPTYQ + ps));
        ps = s; if (s == 2) { s = 0; ph ^= 1; } else s++;
      }
      mbar_wait(BAR(B_FULLQ + 2), L);
      qkv_half(aX, sb16, tX, SA2, SB2);
      mbar_wait(BAR(B_ROW), L);
      IDS;
      const uint32_t pa = sb + PAR + (w * 16 + (lane >> 2)) * 8;
      float2 p0 = lds64f(pa + tX * 512), p1 = lds64f(pa + tX * 512 + 64), p2 = lds64f(pa + tY * 512), p3 = lds64f(pa + tY * 512 + 64);
      mean_step(aX, p0.y, p1.y, sb16 + (CS >> 4), lane & 3);
      mbar_wait(BAR(B_FULLQ), 1);
      qkv_half(aX, sb16, tX, 0, SB0);
      wg_wait<3>(); if (lead) mbar_arrive(BAR(B_EMPTYQ + 1));
      bar_sync(1, 256);
      qkv_half(aY, sb16, tY, SA2, SB2);
      wg_wait<1>(); keep(aX);
      const int srow = w * 16 + (lane & 15);
      const uint32_t x0 = sb + srow * 64 + (((lane >> 4) ^ ((srow >> 1) & 3)) << 4), xX = x0 + (4 + tX) * 8192, xY = x0 + (4 + tY) * 8192;
      qkv_store<8>(aX, p0.x, p1.x, xX + KVA); qkv_store<16>(aX, p0.x, p1.x, xX + KVA + 4096);
      warp_signal(BAR(B_KVRDY + wg * 2));
      qkv_half(aY, sb16, tY, 0, SB0);
      mean_step(aY, p2.y, p3.y, sb16 + (CS >> 4), fresh_tid() & 3);
      wg_wait<2>(); if (lead) mbar_arrive(BAR(B_EMPTYQ + 2));
      mbar_wait(BAR(B_EMPTYQ + 2), L);
      qkv_store<12>(aX, p0.x, p1.x, xX + KVB); qkv_store<20>(aX, p0.x, p1.x, xX + KVB + 4096);
      wg_wait<0>(); keep(aY);
      if (lead) mbar_arrive(BAR(B_EMPTYQ));
      PROFW(threadIdx.x == 0, L * 8 + 2);
      qkv_store<8>(aY, p2.x, p3.x, xY + KVA); qkv_store<16>(aY, p2.x, p3.x, xY + KVA + 4096);
      qkv_store<12>(aY, p2.x, p3.x, xY + KVB); qkv_store<20>(aY, p2.x, p3.x, xY + KVB + 4096);
      warp_signal(BAR(B_KVRDY + wg * 2 + 1));
      p0.x *= QSCALE; p1.x *= QSCALE; p2.x *= QSCALE; p3.x *= QSCALE;
      mbar_wait(BAR(B_EMPTYQ), 1);
      qkv_store<0>(aX, p0.x, p1.x, x0 + QO + tX * 4096);
      qkv_store<0>(aY, p2.x, p3.x, x0 + QO + tY * 4096); qkv_store<4>(aY, p2.x, p3.x, x0 + QO + 16384 + tY * 4096);
      mbar_wait(BAR(B_PAR), L);
      qkv_store<4>(aX, p0.x, p1.x, x0 + QO + 16384 + tX * 4096);
      const int prow = (int)uni(lds32(sb + INFO)) - bi * 256;
      if ((prow >> 4) == tX * 4 + w || (prow >> 4) == tY * 4 + w) {
        __syncwarp();
        if (lane < 24) sts128(sb + (prow & 63) * 64 + (((lane ^ (prow >> 1)) & 3) << 4) +
                              (lane < 8 ? QO + (lane >> 2) * 16384 + (prow >> 6) * 4096 : ((lane & 4) ? KVB : KVA) + (4 + (prow >> 6)) * 8192 + (lane >> 4) * 4096),
                              lds128(sb + PATCH + lane * 16));
      }
      fence_async_smem();
      bar_sync(1, 256);
    }
    PROFW(threadIdx.x == 0, L * 8 + 3);
    float2 fa, fb;
    { const float2* f = (const float2*)&P.g->statF[bi * 256 + rh * 128 + (wg ^ rh) * 64 + w * 16 + ((fresh_tid() & 31) >> 2)];
      fa = __ldcg(f); fb = __ldcg(f + 16); }
    {
      IDS;
      float s0[32], s1[32], sx[32], o[20], op[20];
      uint32_t p0[16], p1[16], px[16], msk[9];
      const int tdiag = w * 16 + (lane >> 2) - 2 * (lane & 3);
      #pragma unroll
      for (int e = 0; e < 9; e++) msk[e] = ((8 * e - 8 > tdiag) ? 0xFFFFu : 0u) | ((8 * e - 7 > tdiag) ? 0xFFFF0000u : 0u);
      keep(msk);
      const uint32_t ones = (sb16 + (ONES >> 4)) << 16;
      const uint32_t qX = (sb16 + (QO >> 4) + tX * 256) | 0x10000u, qY = (sb16 + (QO >> 4) + tY * 256) | 0x10000u;
      const uint32_t kXB = (sb16 + (KVB >> 4) + tX * 512) | 0x10000u;
      uint32_t redo = 0;
      const uint32_t ost = sb + QO + (w * 16 + (lane & 15)) * 64 + (((lane >> 4) ^ ((lane >> 1) & 3)) << 4);
      #define QK(s, q, k) do { wg_fence(); qk_issue(s, q, k); wg_commit(); } while (0)
      #define QK2(q, k) do { wg_fence(); qk_issue(s1, q, k); qk_issue(sx, q, (k) + 2048); wg_commit(); } while (0)
      #define VB(v, b) ((v) + VOFF((b) * 512))
      QK(s0, qX + 1024, kXB + 1536);
      #pragma unroll
      for (int e = 0; e < 20; e++) o[e] = 0.f;
      wg_wait<0>(); keep(s0);
      #pragma unroll 1
      for (int h = 1; h >= 0; h--) {
        const uint32_t kXA = kXB - ((KVB - KVA) >> 4), kX = h ? kXB : kXA, vX = VOFF((kX & 0xffffu) + 256) + ones;
        QK(s1, qX + h * 1024, kX + 1024);
        #pragma unroll
        for (int e = 0; e < 20; e++) op[e] = o[e];
        keep(op);
        exp_pv<0, 4>(s0, p0, o, VB(vX, 3), false); wg_commit();
        wg_wait<1>(); keep(s1);
        exp_pv<0, 2>(s1, p1, o, VB(vX, 2), true);
        bar_sync(h ? 12 + wg : 4 + wg * 4, h ? 128 : 160);
        QK(s0, qX, kXA + 512 + h * 1024);
        exp_pv<2, 4>(s1, p1, o, VB(vX, 2), true); wg_commit();
        wg_wait<0>(); keep(s0); keep(p0); keep(p1); keep(o);
      }
      #pragma unroll 1
      for (int h = 0; h < 2; h++) {
        const uint32_t kb16 = sb16 + ((h ? KVB : KVA) >> 4), kY = (kb16 + tY * 512) | 0x10000u, qy = qY + h * 1024;
        const uint32_t onesP = bi ? ones : (kb16 + 1984) << 16;
        const uint32_t vX = VOFF(kb16 + tX * 512 + 256), vY = VOFF(kb16 + tY * 512 + 256);
        uint32_t ob[8];
        QK2(qX + h * 1024, (kb16 + tX * 512) | 0x10000u);
        exp_pv<0, 4>(s0, p0, o, VB(vX + (wg ? onesP : ones), 1), true); wg_commit();
        wg_wait<1>(); keep(s1); keep(sx);
        QK(s0, qy, kY + 1536);
        exp_pv2(s1, sx, p1, px, o, vX + onesP, VB(vX + ones, 4), msk, tdiag); wg_commit();
        wg_wait<1>(); keep(s0); keep(p0);
        QK(s1, qy, kY + 1024);
        exp_pack<0, 4>(s0, p0);
        wg_wait<1>(); keep(o); keep(p1); keep(px);
        bool ok = attn_pack(o, ob); keep(ob);
        exp_pv<0, 4, 1>(s0, p0, o, VB(vY + (wg ? ones : onesP), 3), false); wg_commit();
        attn_store(ob, ok, ost + (h * 4 + tX) * 4096, sb, BAR(B_ORDY + wg * 4 + h * 2)); redo |= ok ? 0u : 1u << (h * 2);
        wg_wait<1>(); keep(s1);
        exp_pv<0, 2>(s1, p1, o, VB(vY + onesP, 2), true);
        bar_sync(5 + wg * 4 + h * 2, 160);
        QK(s0, qy, kY + 512);
        exp_pv<2, 4>(s1, p1, o, VB(vY + onesP, 2), true); wg_commit();
        wg_wait<1>(); keep(s0); keep(p0);
        QK2(qy, kY);
        exp_pv<0, 4>(s0, p0, o, VB(vY + onesP, 1), true); wg_commit();
        wg_wait<1>(); keep(s1); keep(sx); keep(p1);
        bar_sync(6 + wg * 4, h ? 128 : 160);
        QK(s0, h ? qy : qX + 1024, kXB + 512);
        exp_pv2(s1, sx, p1, px, o, vY + onesP, VB(vY + ones, 4), msk, tdiag); wg_commit();
        wg_wait<0>(); keep(o); keep(s0); keep(p0); keep(p1); keep(px);
        ok = attn_pack(o, ob); attn_store(ob, ok, ost + (h * 4 + tY) * 4096, sb, BAR(B_ORDY + wg * 4 + h * 2 + 1)); redo |= ok ? 0u : 2u << (h * 2);
        #pragma unroll
        for (int e = 0; e < 20; e++) o[e] = op[e];
      }
      #undef QK
      #undef QK2
      #undef VB
      if (redo) {
        #pragma unroll 1
        for (int u = 0; u < 4; u++) if ((redo >> u) & 1) {
          const int h = u >> 1, t = (u & 1) ? tY : tX;
          attn_exact(sb + QO + (h * 4 + t) * 4096, sb + (h ? KVB : KVA), t, bi > 0, BAR(B_ORDY + wg * 4 + u));
        }
      }
    }
    PROFW(threadIdx.x == 0, L * 8 + 4);
    {
      IDS;
      const int t256 = wg * 128 + tid;
      float acc[64];
      const int tt = wg ^ rh;
      const int grow = bi * 256 + rh * 128 + tt * 64 + w * 16 + (lane >> 2);
      float al0 = 1.f, be0 = 0.f, al1 = 1.f, be1 = 0.f;
      const int idx0 = (int)uni(lds32(sb + INFO));
      const uint32_t tag = lds32(sb + INFO + 8) + L;
      uint4* const sp = &P.g->statP[bc][grow + (lane & 1) * 8];
      uint4* const yp = &P.g->yP[t256 >> 1][min(fid, 111)][t256 & 1];
      if (L) {
        float r0 = rsqrtf(fa.y + LN_EPS), r1 = rsqrtf(fb.y + LN_EPS);
        if (grow != idx0) { al0 = 1.f + r0; be0 = -fa.x * r0; }
        if (grow + 8 != idx0) { al1 = 1.f + r1; be1 = -fb.x * r1; }
      }
      const int srow = tt * 64 + w * 16 + (lane & 15);
      const uint32_t ra = sb + srow * 128 + (((lane >> 4) ^ (srow & 7)) << 4);
      mbar_wait(BAR(B_FULLW + 5), L);
      if ((idx0 >> 4) == bi * 16 + rh * 8 + tt * 4 + w) {
        int r = idx0 & 127;
        if (lane < 16) sts128(sb + 32768 + (lane >> 3) * 16384 + r * 128 + (((lane & 7) ^ (r & 7)) << 4), lds128(sb + X2SEG + lane * 16));
        fence_async_smem();
        __syncwarp();
      }
      #pragma unroll
      for (int jj = 0; jj < 8; jj++) {
        uint32_t r[4]; ldsm_x4((ra + 32768 + (jj >> 2) * 16384) ^ ((jj & 3) << 5), r[0], r[1], r[2], r[3]);
        #pragma unroll
        for (int e = 0; e < 4; e++) {
          acc[8 * jj + 2 * e] = fmaf(bf_lo(r[e]), (e & 1) ? al1 : al0, (e & 1) ? be1 : be0);
          acc[8 * jj + 2 * e + 1] = fmaf(bf_hi(r[e]), (e & 1) ? al1 : al0, (e & 1) ? be1 : be0);
        }
      }
      keep(acc);
      bar_sync(12 + wg, 128);
      if (!(lane & 2)) st_ll(sp, 0u, 0u, 0u, 0u);
      uint2 wd[4];
      #pragma unroll
      for (int e = 0; e < 4; e++) { wd[e] = make_uint2(0u, 0u); if (L) wd[e] = ldg_stream((const uint2*)(WDSRC) + t256 + (28 + e) * 256); }
      PROFW(t256 == 0, L * 8 + 5);
      #pragma unroll 1
      for (int n = 0, q = 0, pq = 5; n < 16; n++) {
        mbar_wait(BAR(B_FULLW + q), w_par(n, q, L));
        PROFD(t256 == 0 && !L && (n == 4 || n == 7 || n == 8 || n == 12), (n == 7 ? 63 : 41 + (n >> 2)));
        wo_block(acc, sb16, q, tt);
        wg_wait<1>(); if (tid == 0) mbar_arrive(BAR(B_EMPTYW + pq));
        pq = q; q = w_next(n, q);
      }
      mbar_wait(BAR(B_EMPTYW + 5), L);
      wg_wait<0>(); keep(acc);
      if (tid == 0) mbar_arrive(BAR(B_EMPTYW + 4));
      PROFW(t256 == 0, L * 8 + 6);
      {
        float s1a = 0.f, s2a = 0.f, da = 0.f, s1b = 0.f, s2b = 0.f, db = 0.f;
        #pragma unroll
        for (int j = 0; j < 16; j++) {
          const float* a = acc + 4 * j; float2 wv = lds64f(sb + WR + j * 32 + (lane & 3) * 8);
          s1a += a[0] + a[1]; s1b += a[2] + a[3];
          s2a = fmaf(a[0], a[0], s2a); s2b = fmaf(a[2], a[2], s2b); s2a = fmaf(a[1], a[1], s2a); s2b = fmaf(a[3], a[3], s2b);
          da = fmaf(a[0], wv.x, da); db = fmaf(a[2], wv.x, db); da = fmaf(a[1], wv.y, da); db = fmaf(a[3], wv.y, db);
        }
        bool odd = lane & 1;
        float u1 = (odd ? s1b : s1a) + __shfl_xor_sync(0xffffffffu, odd ? s1a : s1b, 1);
        float u2 = (odd ? s2b : s2a) + __shfl_xor_sync(0xffffffffu, odd ? s2a : s2b, 1);
        float u3 = (odd ? db : da) + __shfl_xor_sync(0xffffffffu, odd ? da : db, 1);
        u1 += __shfl_xor_sync(0xffffffffu, u1, 2); u2 += __shfl_xor_sync(0xffffffffu, u2, 2); u3 += __shfl_xor_sync(0xffffffffu, u3, 2);
        if (!(lane & 2)) st_ll(sp, __float_as_uint(u1), __float_as_uint(u2), __float_as_uint(u3), tag);
      }
      const uint32_t xa = ra + rh * 16384;
      #pragma unroll
      for (int jj = 0; jj < 8; jj++) {
        const float* a = acc + 8 * jj;
        stsm_x4((xa + (jj >> 2) * 32768) ^ ((jj & 3) << 5), pack_bf16(a[0], a[1]), pack_bf16(a[2], a[3]), pack_bf16(a[4], a[5]), pack_bf16(a[6], a[7]));
        if (jj == 7) fence_async_smem();
        if ((jj & 3) == 3) warp_signal(BAR(B_XRDY + wg * 2 + (jj >> 2)));
      }
      PROFW(t256 == 0, L * 8 + 7);
      if (L) {
        mbar_wait(BAR(B_PAR), 0);
        { float2 pa = lds64f(sb + PAR + (grow & 127) * 8), pb = lds64f(sb + PAR + (grow & 127) * 8 + 64); al0 = pa.x; be0 = pa.y; al1 = pb.x; be1 = pb.y; }
        uint32_t rs[32];
        #pragma unroll
        for (int j = 0; j < 16; j++) {
          rs[2 * j] = pack_bf16(fmaf(acc[4 * j], al0, be0), fmaf(acc[4 * j + 1], al0, be0));
          rs[2 * j + 1] = pack_bf16(fmaf(acc[4 * j + 2], al1, be1), fmaf(acc[4 * j + 3], al1, be1));
        }
        #pragma unroll
        for (int jj = 0; jj < 8; jj++) stsm_x4((xa + (jj >> 2) * 32768) ^ ((jj & 3) << 5), rs[4 * jj], rs[4 * jj + 1], rs[4 * jj + 2], rs[4 * jj + 3]);
        PROFW(t256 == 0, 16);
        if (fid >= 112) bar_arrive(3, 384);
        else {
          float d[4] = {0.f, 0.f, 0.f, 0.f};
          mbar_wait(BAR(B_FULLW + wg * 3), 0); mbar_wait(BAR(B_FULLW + wg * 3 + 1), 0);
          bar_sync(3, 384);
          PROFW(t256 == 0, 29);
          #pragma unroll 1
          for (int g = 0; g < 4; g++) {
            const uint32_t ad = (sb16 + (wg ? 6144 : 10240) + (g >> 1) * 2048 + (g & 1) * 512) | (1024u << 16), bd = (sb16 + (HV >> 4) + wg * 64 + g * 16) | 0x10000u;
            wg_fence();
            #pragma unroll
            for (int ks = 0; ks < 8; ks++) wgmma_ss_n8<0, 1>(d, mkd<HI64>(ad + ks * 64), mkd<8>(bd + ks * 2), 1);
            wg_commit();
          }
          mbar_wait(BAR(B_FULLW + 2), 0);
          wg_wait<0>(); keep(d);
          if (!(lane & 3)) { sts32f(sb + PAR + 1024 + wg * 256 + w * 64 + lane, d[0]); sts32f(sb + PAR + 1056 + wg * 256 + w * 64 + lane, d[2]); }
          bar_sync(1, 256);
          const uint32_t ga = sb + PAR + 1024 + lane * 4, aa = sb + HV + (t256 >> 5) * 128;
          sts32f(aa + lane * 4, swiglu(lds32f(ga) + lds32f(ga + 256), lds32f(ga + 128) + lds32f(ga + 384)));
          __syncwarp();
          PROFW(t256 == 0, 26);
          float y0 = 0.f, y1 = 0.f, y2 = 0.f, y3 = 0.f;
          uint32_t tbl = rh ? 0x001459a8u : 0x023679a8u;
          uint4 a4 = lds128(aa + 112);
          #pragma unroll 2
          for (int n = 0; n < 8; n++, tbl >>= 4) {
            const uint32_t src = sb + t256 * 8 + (tbl & 15) * 8192;
            const uint4 an = lds128(aa + ((0x00123564u >> (4 * n)) & 15) * 16);
            #pragma unroll
            for (int e = 0; e < 4; e++) {
              const float av = __uint_as_float(e == 0 ? a4.x : (e == 1 ? a4.y : (e == 2 ? a4.z : a4.w)));
              y0 = fmaf(bf_lo(wd[e].x), av, y0); y1 = fmaf(bf_hi(wd[e].x), av, y1); y2 = fmaf(bf_lo(wd[e].y), av, y2); y3 = fmaf(bf_hi(wd[e].y), av, y3);
              const float2 v = lds64f(src + e * 2048); wd[e] = make_uint2(__float_as_uint(v.x), __float_as_uint(v.y));
            }
            a4 = an;
          }
          st_ll(yp, __float_as_uint(y0), __float_as_uint(y1), __float_as_uint(y2), (__float_as_uint(y3) & ~255u) | (lds32(sb + INFO + 12) + 1));
          PROFW(t256 == 0, 27);
        }
        return;
      }
      mbar_wait(BAR(B_XRDY + wg * 2 + 1), 0);
    }
  }
  #undef IDS
  #undef LAYER
}

DEVI void loader(const Params& P, uint32_t sb) {
  const int lane = threadIdx.x & 31;
  const int bid = uni(BID), bi = bid >> 4, bp = bid & 15, rh = bp & 1, bc = bp >> 1;
  uint32_t phq = 0, tag = 0;
  #pragma unroll 1
  for (int L = 0; L < 2; L++) {
    int s = 0;
    uint32_t rdy = 0;
    #pragma unroll 1
    for (int n = L ? 0 : 3; n < 16; n++) {
      int kb = L ? kb_order(bc, n) : n;
      mbar_wait(BAR(B_EMPTYQ + s), (phq >> s) & 1);
      phq ^= 1u << s;
      if (L && n == 1) { mbar_wait(BAR(B_XRDY + 1), 0); mbar_wait(BAR(B_XRDY + 3), 0); }
      if (elect()) {
        mbar_expect_tx(BAR(B_FULLQ + s), L && n < 2 ? 40960 : 57344);
        tma_3d_h(sb + qb_off(s), &P.mWq, bp * 64, kb * 64, 0, BAR(B_FULLQ + s), L && n >= QEF_N ? POL_FIRST : POL_NORMAL);
        if (!L) tma_2d(sb + qa_off(s), &P.mX, kb * 64, bi * 256, BAR(B_FULLQ + s));
      }
      if (L && n >= 2) {
        if (((rdy >> (2 * kb)) & 3) != 3) {
          do { rdy = __ballot_sync(0xffffffffu, ld_rlx(&P.g->flagX[bi][lane]) == tag); } while (((rdy >> (2 * kb)) & 3) != 3);
          fence_async_glob();
        }
        if (n == 3 || n == 4) mbar_wait(BAR(B_XFREE + n - 3), 0);
        if (elect()) bulk_g2s_h(sb + qa_off(s), P.g->x[bi][kb], 32768, BAR(B_FULLQ + s), POL_X);
      }
      PROFY(L && lane == 0 && (n == 2 || n == 3 || n == 9), n == 9 ? 60 : 56 + n);
      if (L && n == 2) { mbar_wait(BAR(B_FULLQ), 0); mbar_wait(BAR(B_FULLQ + 1), 1); if (lane < 2) mbar_arrive_peer(BAR(B_XFREE + lane)); }
      s = (s == 2) ? 0 : s + 1;
    }
    for (int q = 0; q < 3; q++) mbar_wait(BAR(B_EMPTYQ + q), (phq >> q) & 1);
    tag = lds32(sb + INFO + 8) + L;
    #pragma unroll 1
    for (int q = 0; q < 4; q++) {
            if (bi) {
        const unsigned* f = &P.g->flagKV[bid - 16][q];
        while (ld_rlx(f) != tag);
        fence_async_glob();
      }
      if (elect()) {
        mbar_expect_tx(BAR(B_KVFULL + q), 16384);
        bulk_g2s_h(sb + ((q >> 1) ? KVB : KVA) + ((q & 1) ? 0 : 16384), bi ? P.g->kv[bid - 16][q] : P.g->zero, 16384, BAR(B_KVFULL + q), L ? POL_KV1 : POL_KV0);
      }
      PROFY(!L && lane == 0 && bi && q != 2, 34 + (q + 1) / 2);
    }
    mbar_wait(BAR(B_ORDY), L);
    {
      const uint4* src = P.g->o[bi][0][0][rh];
      rdy = 0;
      #pragma unroll 1
      for (int n = 0, q = 0; n < 16; q = w_next(n, q), n++) {
        const int j = wo_order(bc, n);
        if (((rdy >> (2 * j)) & 3) != 3) {
          do { rdy = __ballot_sync(0xffffffffu, ld_rlx(&P.g->flagO[bi][lane]) == tag); } while (((rdy >> (2 * j)) & 3) != 3);
          fence_async_glob();
        }
        if (n >= 2) mbar_wait(n < 5 ? BAR(B_HAFREE + (n > 2)) : BAR(B_EMPTYW + q), n < 5 ? L : w_par(n, q, L) ^ 1);
        if (n == THR_N) mbar_wait(BAR(B_OFREE), L);
        if (elect()) { mbar_expect_tx(BAR(B_FULLW + q), 16384); bulk_g2s_h(sb + w_off(q), src + j * 2048, 16384, BAR(B_FULLW + q), L ? POL_O1 : POL_O0); }
      }
    }
    mbar_wait(BAR(B_OFREE), L);
  }
}

DEVI void ffn_prefetch(const Params& P, int q) {
  bulk_prefetch(q < 16 ? ((q & 1) ? P.wu : P.wg) + ((q >> 1) * 128 + blockIdx.x) * 3584 : P.wd + (min(FID, 111) * 8 + q - 16) * 4096, q < 16 ? 7168 : 8192);
}
DEVI void storer(const Params& P, uint32_t sb, int wg) {
  const int bid = uni(BID), bi = bid >> 4, rh = bid & 1, bc = (bid & 15) >> 1;
  const bool one = (threadIdx.x & 31) == 0;
  char* const g = (char*)P.g;
  const uint32_t tag0 = uni(((ld_rlx(&P.g->epoch) % 16383u) + 1u) << 2);
  #pragma unroll 1
  for (int L = 0; L < 2; L++) {
    const uint32_t tag = tag0 + L;
    if (wg) {
      #pragma unroll 1
      for (int r = threadIdx.x & 31; r < 256; r += 32) {
        uint4 v;
        do v = ld_ll(&P.g->statF[bi * 256 + r]); while (!__all_sync(0xffffffffu, v.w == tag));
        float var = __uint_as_float(v.y), c = rsqrtf(var + LN_EPS);
        if (L) { c += 1.f; c *= rsqrtf(fmaf(var * c, c, LN_EPS)); }
        const float mh = bf_round(__uint_as_float(v.x));
        sts64f(sb + PAR + r * 8, c, __uint_as_float(pack_bf16(mh, __uint_as_float(v.x) - mh)));
      }
      if (!L) mbar_wait(BAR(B_PAR), 0);
      warp_signal(BAR(B_ROW));
    }
    #pragma unroll 1
    for (int u = 0; u < 2 + 4 * wg; u++) {
      const int h = u < 2 ? u : u >> 2, hi = (u & 1) ^ 1;
      uint32_t src, dst, fl, b0, b1;
      if (u < 2) {
        src = (h ? KVB : KVA) + (3 - wg) * 16384; dst = offsetof(Scratch, kv) + (bid * 4 + h * 2 + wg) * 16384; fl = offsetof(Scratch, flagKV) + (bid * 32 + h * 2 + wg) * 4;
        b0 = BAR(B_KVRDY + ((u | wg) ? 1 : 0)); b1 = b0 + 16;
      } else {
        src = QO + (h * 2 + hi) * 8192; dst = offsetof(Scratch, o) + ((((bi * 2 + h) * 8 + bc) * 2 + hi) * 2 + rh) * 8192;
        fl = offsetof(Scratch, flagO) + (bi * 32 + h * 16 + (bid & 15)) * 4;
        b0 = BAR(B_ORDY + u - 2); b1 = b0 + 32;
      }
      mbar_wait(b0, L); mbar_wait(b1, L);
      if (u + wg == 1) {
        mbar_wait(BAR(B_PAR), L);
        const uint32_t t0 = clk(), dt = (wg ? KV_D1 : KV_D2) + (L ? KV_DL : 0); while (clk() - t0 < dt) __nanosleep(40);
      }
      fence_async_smem();
      PROFY(one && !L && u == 3 * wg, u ? 46 : 8);
      if (one && (u >= 2 || bi < 7)) bulk_s2g(g + dst, sb + src, u < 2 ? 16384 : 8192, ((ST_M >> (L * 2 + (u >= 2))) & 1) ? POL_FIRST : POL_NORMAL);
      if (one && u == 5) mbar_arrive(BAR(B_HAFREE + 1));
      if (u == 2 || u == 4) continue;
      bulk_wait<0>();
      PROFY(one && !L && u == 3 * wg, u ? 61 : 62);
      fence_rel();
      if (one) { st_rlx((unsigned*)(g + fl), tag); if (!wg || u > 2) mbar_arrive(BAR(B_HAFREE + h + (wg & h))); }
      PROFY(one && !L && (u > 2 || u == wg), u > 2 ? (u == 3 ? 38 : 54) : 32 + u);
    }
    if (L == 0) {
      char* dst = g + (offsetof(Scratch, x) + (bi * 16 + 2 * bc) * 32768 + rh * 16384);
      unsigned* f = (unsigned*)(g + (offsetof(Scratch, flagX) + (bi * 32 + bc * 4 + rh) * 4));
      const uint32_t a = sb + rh * 16384;
      if (wg == 0) {
        mbar_wait(BAR(B_XRDY), 0); mbar_wait(BAR(B_XRDY + 2), 0);
        fence_async_smem();
        PROFY(one, 41);
        if (one) bulk_s2g(dst, a, 16384);
        bulk_wait<0>();
        PROFY(one, 45);
        if (one) { mbar_arrive(BAR(B_XFREE)); mbar_arrive(BAR(B_PFREE)); }
        fence_rel();
        mbar_wait(BAR(B_XRDY + 1), 0); mbar_wait(BAR(B_XRDY + 3), 0);
        if (one) { st_rlx(f, tag); bulk_s2g(dst + 32768, a + 32768, 16384); }
        PROFY(one, 56);
        bulk_wait<0>();
        if (one) mbar_arrive(BAR(B_XFREE + 1));
        fence_rel();
        if (one) st_rlx(f + 2, tag);
        PROFY(one, 57);
      } else {
        mbar_wait(BAR(B_XRDY + 1), 0); mbar_wait(BAR(B_XRDY + 3), 0);
        mbar_wait(BAR(B_PFREE), 0);
        if (one) bulk_s2peer(a, 16384, BAR(B_FULLQ));
        { const uint32_t t0 = clk(); while (clk() - t0 < XD_D); }
        if (one) bulk_s2peer(a + 32768, 16384, BAR(B_FULLQ + 1));
      }
      if (wg == 0) {
        uint32_t t0 = clk() + PF1_D;
        #pragma unroll 1
        for (int q = PF1_S; q < PF1_E; q++) { while ((int)(clk() - t0) < 0) __nanosleep(50); if (one) ffn_prefetch(P, q); t0 += PF1_T; }
      }
    }
  }
}

DEVI void stg_issue(const Params& P, int c, uint32_t d, uint32_t du, uint32_t b) {
  mbar_expect_tx(b, 16384);
  if (c < 8) { tma_2d_h(d, &P.mWg, FID * 32, c * 128, b, du > 8192 ? POL_T : POL_G); tma_2d_h(d + du, &P.mWu, FID * 32, c * 128, b, du > 8192 || c < U_C ? POL_FIRST : POL_NORMAL); }
  else if (c < 12) tma_3d_h(d, &P.mWd, 0, FID * 32 + (c - 8) * 8, 0, b, POL_D);
  else tma_2d_h(d, &P.mWp, (c - 12) * 1024 + (BID >> 2) * 32, (BID & 3) * 256, b, POL_EF);
}
DEVI void pace() { const uint32_t t0 = clk(); while (clk() - t0 < PACE_T); }
DEVI void stager(const Params& P, uint32_t sb) {
  {
    const int b = blockIdx.x;
    uint32_t t0 = clk();
    #pragma unroll 1
    for (int q = 0; q < PQ_N; q++) { bulk_prefetch(P.wqkv + (q * 128 + b) * 3072, 6144); while (clk() - t0 < PQ_T) __nanosleep(50); t0 += PQ_T; }
    bulk_prefetch(P.wo + b * 8192, 16384);
    #pragma unroll 1
    for (int q = 0; q < PF0_N; q++) {
      while (clk() - t0 < PF0_T) __nanosleep(50);
      t0 += PF0_T;
      ffn_prefetch(P, q);
    }
  }
  const int bid = BID, bi = bid >> 4, rh = bid & 1, bc = (bid & 15) >> 1;
  #pragma unroll 1
  for (int L = 0; L < 2; L++) {
    const int nch = L ? (FID < 112 ? 8 : 0) : 15;
    mbar_wait(BAR(B_PAR), L); mbar_wait(BAR(B_KVFULL + W0_BAR), L);
    #pragma unroll 1
    for (int n = 0, q = 0; n < 16; q = w_next(n, q), n++) {
      if (n >= 2) mbar_wait(n < 5 ? BAR(B_HAFREE + (n > 2)) : BAR(B_EMPTYW + q), n < 5 ? L : w_par(n, q, L) ^ 1);
      if (n == THR_N) mbar_wait(BAR(B_OFREE), L);
      mbar_expect_tx(BAR(B_FULLW + q), 16384);
      tma_5d(sb + w_off(q) + 16384, &P.mWo, 0, 0, n >> 3, 2 * (wo_order(bc, n) & 7), 2 * bc, BAR(B_FULLW + q), L ? POL_W1 : POL_W0);
      if (n == 2) {
        #pragma unroll 1
        for (int e = 0; e < 2; e++) {
          mbar_expect_tx(BAR(B_FULLW + 5), 16384);
          if (L) bulk_g2s_h(sb + 32768 + e * 16384, P.g->x[bi][2 * bc + e] + rh * 1024, 16384, BAR(B_FULLW + 5));
          else tma_2d_h(sb + 32768 + e * 16384, &P.mXh, bc * 128 + e * 64, bi * 256 + rh * 128, BAR(B_FULLW + 5), POL_EF);
        }
      }
    }
    mbar_wait(BAR(B_EMPTYW + 5), L);
    if (L && nch) {
      const bf16* src = WDSRC2;
      mbar_expect_tx(BAR(B_FULLW + 2), 32768); mbar_expect_tx(BAR(B_FULLW + 2), 24576);
      #pragma unroll 1
      for (int e = 0; e < 3; e++) { bulk_g2s_h(sb + e * 32768 + (e < 2 ? (rh ^ 1) * 16384 : 0), src + e * 8192, e < 2 ? 16384 : 24576, BAR(B_FULLW + 2)); pace(); }
    }
        if (L == 0) { mbar_arrive_peer(BAR(B_PFREE)); mbar_wait(BAR(B_EMPTYW), 0); mbar_wait(BAR(B_EMPTYW + 1), 0); }
    #pragma unroll 1
    for (int c = FID < 112 ? 0 : 12, slot = 0; c < nch; c++, slot = slot == 2 ? 0 : slot + 1) {
      const int q = (c >> 1) + (c >> 2);
      if (!L && (c == LATE_C || c == 12)) mbar_wait(BAR(LATE_B), LATE_P);
      mbar_wait(L ? BAR(B_EMPTYW + q) : BAR(B_STGE + slot), L | ((0x71c7 >> c) & 1));
      #define CC c
      stg_issue(P, CC, L ? sb + w_off(q) + (c & 1) * 8192 : sb + STG + slot * 16384, 8192 << L, L ? BAR(B_FULLW + q) : BAR(B_STG + slot));
      if (L) pace();
    }
  }
}
DEVI void sum8(uint4 v, float& s1, float& s2) {
  float e[8] = {bf_lo(v.x), bf_hi(v.x), bf_lo(v.y), bf_hi(v.y), bf_lo(v.z), bf_hi(v.z), bf_lo(v.w), bf_hi(v.w)};
  #pragma unroll
  for (int q = 0; q < 8; q++) { s1 += e[q]; s2 = fmaf(e[q], e[q], s2); }
}
DEVI uint4 norm8(uint4 x, float m, float rs) {
  #define HN(v) pack_bf16((bf_lo(v) - m) * rs, (bf_hi(v) - m) * rs)
  return make_uint4(HN(x.x), HN(x.y), HN(x.z), HN(x.w));
  #undef HN
}
DEVI void put_f32(uint4 b, uint32_t d, uint32_t d2) {
  sts128(d, make_uint4(b.x << 16, b.x & 0xffff0000u, b.y << 16, b.y & 0xffff0000u));
  sts128(d + d2, make_uint4(b.z << 16, b.z & 0xffff0000u, b.w << 16, b.w & 0xffff0000u));
}
DEVI void put_bf16(uint4 b, uint32_t d) {
  sts64f(d, __uint_as_float(b.x), __uint_as_float(b.y)); sts64f(d + 1024, __uint_as_float(b.z), __uint_as_float(b.w));
  fence_async_smem();
}
DEVI uint4 best4(uint32_t p) {
  uint4 a = lds128(p), b = lds128(p + 16), c = lds128(p + 32), d = lds128(p + 48);
  if (b.x > a.x) a = b;
  if (d.x > c.x) c = d;
  return c.x > a.x ? c : a;
}
#define FL(x) __uint_as_float(x)
#define UI(x) __float_as_uint(x)
DEVI void aux(const Params& P, uint32_t sb) {
  int tid = fresh_tid();
  #define lane (tid & 31)
  #define wq (tid >> 5)
  uint32_t ids = P.map[blockIdx.x], tag;
  #define bid ((int)(ids & 255))
  #define fid ((int)(ids >> 8))
  #define bi (bid >> 4)
  #define bp (bid & 15)
  #define bc (bp >> 1)
  #define FRESH() do { tid = fresh_tid(); uint4 z_ = ldsv128(sb + INFO2 + 16); ids = z_.y; tag = z_.z + L; idx = z_.w; } while (0)
  {
    const uint32_t epoch = ld_rlx(&P.g->epoch);
    if (tid == 0) {
      mbar_expect_tx(BAR(B_STG), 49152);
      tma_3d(sb + STG, &P.mWq, bp * 64, bi * 128, 0, BAR(B_STG));
      tma_3d(sb + STG + 24576, &P.mWq, bp * 64, bi * 128 + 64, 0, BAR(B_STG));
    }
    __syncwarp();
    sts64f(sb + ONES + tid * 8, FL(0x3F803F80u), FL(0x3F803F80u));
    float s1 = 0.f, s2 = 0.f;
    { uint4 v = __ldg((const uint4*)P.wr + tid);
      if ((tid >> 4) == bc) put_f32(v, sb + WR + (tid & 15) * 32, 16);
      sum8(v, s1, s2);
      #pragma unroll 1
      for (int o = 16; o; o >>= 1) s1 += __shfl_xor_sync(0xffffffffu, s1, o);
      sts32f(sb + INFO2 + wq * 4, s1); }
    const uint4* src = (const uint4*)(P.x0 + (size_t)bid * 16384) + (tid >> 3) * 128 + (tid & 7);
    s1 = 0.f; s2 = 0.f;
    #pragma unroll 1
    for (int it = 0; it < 16; it += 4) {
      uint4 v0 = __ldg(src + it * 8), v1 = __ldg(src + it * 8 + 8), v2 = __ldg(src + it * 8 + 16), v3 = __ldg(src + it * 8 + 24);
      #pragma unroll 1
      for (int q = 0; q < 4; q++) { sum8(v0, s1, s2); v0 = v1; v1 = v2; v2 = v3; }
    }
    #pragma unroll 1
    for (int o = 1; o < 8; o <<= 1) { s1 += __shfl_xor_sync(0xffffffffu, s1, o); s2 += __shfl_xor_sync(0xffffffffu, s2, o); }
    tag = ((epoch % 16383u) + 1u) << 2;
    if (tid == 0) { sts128(sb + INFO, make_uint4(0x40000000u, 0u, tag, ((epoch % 127u) + 1u) << 1)); sts128(sb + INFO2 + 16, make_uint4(epoch, ids, tag, 0x40000000u)); }
    float m = s1 * (1.f / 1024.f);
    if ((tid & 7) == 0) st_ll(&P.g->statF[bid * 16 + (tid >> 3)], UI(m), UI(fmaxf(fmaf(-m, m, s2 * (1.f / 1024.f)), 0.f)), 0u, tag);
    bar_sync(2, 128);
    mbar_wait_b(BAR(B_STG), 0);
    if (tid < 96) {
      s1 = 0.f; s2 = 0.f;
      #pragma unroll 1
      for (int r = 0; r < 16; r++) {
        const uint32_t a = sb + STG + (r >> 3) * 24576 + wq * 8192 + (r & 7) * 128 + ((lane * 4) ^ ((r & 7) << 4));
        #pragma unroll
        for (int e = 0; e < 8; e++) { uint32_t v = lds32(a + e * 1024); s1 += bf_lo(v); s2 += bf_hi(v); }
      }
      st_ll(&P.g->csP[bp][bi][tid], UI(s1), UI(s2), 0u, tag);
      s1 = 0.f; s2 = 0.f;
      #pragma unroll 1
      for (int q = 0; q < 8; q += 2) {
        uint4 a, b; poll_ll2(&P.g->csP[bp][q][tid], &P.g->csP[bp][q + 1][tid], 0xffffffffu, tag, a, b);
        s1 += FL(a.x) + FL(b.x); s2 += FL(a.y) + FL(b.y);
      }
      const uint32_t hi = pack_bf16(-s1, -s2);
      sts32(sb + CS + (tid >> 2) * 32 + (tid & 3) * 4, hi);
      sts32(sb + CS + (tid >> 2) * 32 + (tid & 3) * 4 + 16, pack_bf16(-s1 - bf_lo(hi), -s2 - bf_hi(hi)));
    }
    fence_async_smem();
  }
  int idx;
  #pragma unroll 1
  for (int L = 0; L < 2; L++) {
    FRESH();
    {
      if ((unsigned)(bi - (idx >> 8)) < 2u) {
        const uint4* src = &P.g->patch[bp * 8 + (tid >> 6) * 4][tid & 63];
        const float4 z = poll_sum4(src, 64, tag);
        float q = z.x, k = z.y, v = z.z;
        q += __shfl_xor_sync(0xffffffffu, q, 1); k += __shfl_xor_sync(0xffffffffu, k, 1); v += __shfl_xor_sync(0xffffffffu, v, 1);
        bar_sync(2, 128);
        const uint32_t d = sb + PATCH + (tid & ~1), kv = pack_bf16(k, v);
        sts16(d, pack_bf16(q * QSCALE, 0.f)); sts16(d + 128, kv); sts16(d + 256, kv >> 16);
      }
      sts32(sb + INFO, idx);
      bar_sync(2, 128);
    }
    const uint4 fix = lds128(sb + PATCH + 128 + (lane & 4) * 32 + (wq >> 1) * 64 + (lane & 3) * 16);
    warp_signal(BAR(B_PAR));
    PROFX(tid == 0, L ? 23 : 17);
    mbar_wait_b(BAR(B_KVFULL + wq), L);
    if ((idx >> 7) == bi * 2 - 1 - (wq & 1)) {
      if (lane < 8) sts128(sb + ((wq >> 1) ? KVB : KVA) + ((idx >> 6) & 3) * 8192 + (lane >> 2) * 4096 + (idx & 63) * 64 + (((lane ^ (idx >> 1)) & 3) << 4), fix);
      fence_async_smem();
    }
    bar_arrive(4 + wq, 160); bar_arrive(8 + wq, 160);
    FRESH();
    mbar_wait_b(BAR(B_OFREE), L);
    #define blk (bi * 2 + (bid & 1))
    if (tid < 33) st_ll(tid < 32 ? &P.g->row[blk][bc * 32 + tid] : &P.g->best[bc][blk], 0u, 0u, 0u, 0u);
    mbar_wait_b(BAR(B_XRDY), L);
    PROFX(tid == 0, 37 + L * 16);
    FRESH();
    {
      float s1 = 0.f, s2 = 0.f, d = 0.f;
      #pragma unroll 1
      for (int q = 0; q < 8; q += 4) { const float4 v = poll_sum4(&P.g->statP[q][blk * 128 + tid], 2048, tag); s1 += v.x; s2 += v.y; d += v.z; }
      PROFX(tid == 0, 39 + L * 16);
      uint4 a = lds128(sb + INFO2), b, c;
      float m = s1 * (1.f / 1024.f), var = fmaxf(fmaf(-m, m, s2 * (1.f / 1024.f)), 0.f), rs = rsqrtf(var + LN_EPS);
      uint32_t key = UI(fmaf(-m, (FL(a.x) + FL(a.y)) + (FL(a.z) + FL(a.w)), d) * rs);
      key ^= (uint32_t)((int)key >> 31) | 0x80000000u;
      uint32_t win = __ballot_sync(0xffffffffu, key == __reduce_max_sync(0xffffffffu, key));
      if (lane == __ffs(win) - 1) sts128(sb + RED + wq * 16, make_uint4(key, UI(m), UI(rs), (tag << 11) | (uint32_t)(blk * 128 + tid)));
      if (L) sts64f(sb + PAR + tid * 8, 1.f + rs, -m * rs);
      else if ((tid >> 4) == bc) st_ll(&P.g->statF[blk * 128 + tid], UI(m), UI(var), 0u, tag + 1);
      bar_sync(2, 128);
      if (wq == 0) {
        mbar_wait(BAR(B_XRDY + 1), L); mbar_wait(BAR(B_XRDY + 3), L);
        a = best4(sb + RED);
        float2 v = lds64f(sb + (lane >> 4) * 32768 + (a.w & 255) * 128 + (((lane & 15) * 8) ^ ((a.w & 7) << 4)));
        st_ll(&P.g->row[blk][bc * 32 + lane], UI(v.x), UI(v.y), 0u, tag);
        if (lane == 0) st_ll(&P.g->best[bc][blk], a.x, a.y, a.z, a.w);
        __syncwarp();
        if (lane < 2 + 2 * L) mbar_arrive(L ? BAR(B_PAR) : BAR(B_XFREE + lane));
      }
      PROFX(tid == 0, 18 + L * 6);
      FRESH();
      a = poll_ll(&P.g->best[bc][lane & 15], 0xfffff800u, tag << 11);
      win = __ffs(__ballot_sync(0xffffffffu, a.x == __reduce_max_sync(0xffffffffu, a.x))) - 1;
      idx = __shfl_sync(0xffffffffu, a.w, win) & 2047;
      PROFX(tid == 0, 19 + L * 6);
      poll_ll2(&P.g->row[win][tid], &P.g->row[win][tid + 128], 0xffffffffu, tag, c, b);
      c.z = b.x; c.w = b.y;
      a.x = __shfl_sync(0xffffffffu, a.x, win); a.y = __shfl_sync(0xffffffffu, a.y, win); a.z = __shfl_sync(0xffffffffu, a.z, win);
      sts32(sb + INFO2 + 28, idx);
      PROFX(tid == 0, 61 + L);
      b = norm8(c, FL(a.y), FL(a.z));
      if (L) put_bf16(b, sb + HV + tid * 8); else put_f32(b, sb + HV + tid * 16, 2048);
      if ((tid >> 1) == (bid & 63)) {
        sts128(sb + RED + 64 + (tid & 1) * 16, bid < 64 ? make_uint4(c.x, c.y, b.x, b.y) : make_uint4(c.z, c.w, b.z, b.w));
        sts32(sb + RED + 96, a.x);
      }
      bar_sync(2 + L, 128 + L * 256);
      if (L) {
        const int r0 = blk * 128 + (tid >> 4);
        uint32_t src = sb + ((tid >> 3) & 1) * 32768 + (r0 & 255) * 128 + (((tid ^ r0) & 7) << 4);
        uint4* dst = (uint4*)(P.out + (size_t)r0 * 1024 + bc * 128) + (tid & 15);
        #pragma unroll 4
        for (int it = 0; it < 16; it++) { uint4 v = lds128(src + it * 1024); if (idx - r0 != it * 8) dst[it * 1024] = v; }
      }
    }
    #pragma unroll 1
    for (int st = L; st < 2; st++) {
      FRESH();
      float a[8] = {0.f, 0.f, 0.f, 0.f, 0.f, 0.f, 0.f, 0.f};
      if (L == 0 && fid < 112) {
        uint32_t ha = st ? sb + RED + 768 : sb + HV + ((wq & 1) * 64 + (lane >> 2)) * 4;
        uint32_t ph = st ? 0x1cu : 0x171u, bar = st ? BAR(B_STG + 2) : BAR(B_STG);
        uint32_t wa = sb + STG + wq * 4096 + (st ? 32768 + lane * 16 : (lane ^ (lane >> 3)) * 16);
        const uint32_t hx = st ? 256 : 512;
        const bool lead = lane == 0;
        uint4 vc = make_uint4(0u, 0u, 0u, 0u); float hc = 0.f;
        #pragma unroll 1
        do {
          mbar_wait(bar, ph & 1);
          PROFX(lead && threadIdx.x == 256 && st == 0 && (ph > 255 || ph < 4), 40 - 23 + __clz(ph));
          #pragma unroll
          for (int n = 0; n < 8; n++) { const uint4 v = lds128(wa + n * 512); const float h = lds32f(ha + n * 32); fma8(a, vc, hc); vc = v; hc = h; }
          __syncwarp();
          if (lead) mbar_arrive(bar - 8 * (B_STG - B_STGE));
          const bool wrap = bar == BAR(B_STG + 2);
          bar += wrap ? -16 : 8; wa += wrap ? -32768 : 16384; ha += hx;
          ph >>= 1;
        } while (ph != 1);
        fma8(a, vc, hc);
      }
      FRESH();
      if (st == 1) {
        const uint32_t t8 = lds32(sb + INFO + 12) + L;
        if (L == 0 && fid < 112) {
          const bool odd = lane & 1;
          #pragma unroll
          for (int e = 0; e < 4; e++) { float z = __shfl_xor_sync(0xffffffffu, odd ? a[e] : a[4 + e], 1); if (odd) a[e] = z; else a[4 + e] = z; }
          uint4* dst = &P.g->yP[tid & ~1][fid][tid & 1];
          st_ll(dst, UI(a[0]), UI(a[1]), UI(a[2]), (UI(a[3]) & ~255u) | t8);
          st_ll(dst + 224, UI(a[4]), UI(a[5]), UI(a[6]), (UI(a[7]) & ~255u) | t8);
          PROFX(tid == 0, 21);
        }
        if (tid == 0) { uint32_t k = lds32(sb + RED + 96); sts32f(sb + RED + 100, bf_round(__fdividef(1.f, 1.f + __expf(-bf_round(FL(k ^ (~(uint32_t)((int)k >> 31) | 0x80000000u))))))); }
        uint4 v0, v1;
        poll_ll2(&P.g->yP[bid][0][min(tid, 111)], &P.g->yP[bid][0][min(tid, 111) + 112], 255u, t8, v0, v1);
        const float lo = (tid < 112 && !(tid & 1)) ? 1.f : 0.f, hi = (tid < 112 && (tid & 1)) ? 1.f : 0.f;
        const float y0 = FL(v0.x) + FL(v1.x), y1 = FL(v0.y) + FL(v1.y), y2 = FL(v0.z) + FL(v1.z), y3 = FL((v0.w & ~255u) | 128u) + FL((v1.w & ~255u) | 128u);
        a[0] = y0 * lo; a[1] = y1 * lo; a[2] = y2 * lo; a[3] = y3 * lo; a[4] = y0 * hi; a[5] = y1 * hi; a[6] = y2 * hi; a[7] = y3 * hi;
      }
      sts32f(sb + RED + 256 + wq * 128 + ((lane & 3) * 8 + (lane >> 2)) * 4, fold8(a));
      bar_sync(2, 128);
      const uint32_t d = sb + RED + 256 + lane * 4;
      float z0 = lds32f(d) + lds32f(d + 128), z1 = lds32f(d + 256) + lds32f(d + 384);
      if (st == 0) {
        sts32f(sb + RED + 768 + lane * 32 + wq * 4, swiglu(z0, z1));
        bar_sync(2, 128);
        if (fid < 112) { st_ll(&P.g->yP[tid & ~1][fid][tid & 1], 0u, 0u, 0u, 0u); st_ll(&P.g->yP[tid | 1][fid][tid & 1], 0u, 0u, 0u, 0u); }
        else { const uint32_t t0 = clk(); while (clk() - t0 < IDLE_T) __nanosleep(200); }
        if (tid < 80) st_ll(tid < 64 ? &P.g->patch[bid][tid] : &P.g->x2[(tid >> 1) & 7][2 * bid + (tid & 1)], 0u, 0u, 0u, 0u);
        PROFX(tid == 0, 20); continue; }
      z0 += z1;
      z0 += __shfl_xor_sync(0xffffffffu, z0, 8); z0 += __shfl_xor_sync(0xffffffffu, z0, 16);
      uint32_t xw = lds32(sb + RED + 64 + (lane & 4) * 4 + (lane & 2) * 2), hw = lds32(sb + RED + 72 + (lane & 4) * 4 + (lane & 2) * 2);
      z0 = bf_round(((lane & 1) ? bf_hi(hw) : bf_lo(hw)) + bf_round(bf_round(z0) * lds32f(sb + RED + 100))) + ((lane & 1) ? bf_hi(xw) : bf_lo(xw));
      uint32_t v = pack_bf16(z0, __shfl_down_sync(0xffffffffu, z0, 1)), v2 = __shfl_down_sync(0xffffffffu, v, 2);
      if (L) { if (tid == 0 || tid == 4) *(uint2*)(P.out + (size_t)idx * 1024 + bid * 8 + tid) = make_uint2(v, v2); PROFW(tid == 0, 28); }
      else if ((tid & 3) == 0 && tid < 64) st_ll(&P.g->x2[tid >> 3][2 * bid + ((tid >> 2) & 1)], v, v2, 0u, tag + 1);
    }
    if (L == 0) {
      PROFX(tid == 0, 22);
      FRESH();
      uint4 x, y; poll_ll2(&P.g->x2[bi][tid], &P.g->x2[bi][tid + 128], 0xffffffffu, tag + 1, x, y);
      x.z = y.x; x.w = y.y;
      if (wq == (bc & 3)) sts64f(sb + X2SEG + lane * 8, FL(bc < 4 ? x.x : x.z), FL(bc < 4 ? x.y : x.w));
      float s1 = 0.f, s2 = 0.f;
      sum8(x, s1, s2);
      #pragma unroll
      for (int o = 16; o; o >>= 1) { s1 += __shfl_xor_sync(0xffffffffu, s1, o); s2 += __shfl_xor_sync(0xffffffffu, s2, o); }
      sts64f(sb + RED + wq * 8, s1, s2);
      bar_sync(2, 128);
      y = lds128(sb + RED); uint4 y2 = lds128(sb + RED + 16);
      float m = ((FL(y.x) + FL(y.z)) + (FL(y2.x) + FL(y2.z))) * (1.f / 1024.f);
      put_bf16(norm8(x, m, rsqrtf(fmaxf(fmaf(-m, m, ((FL(y.y) + FL(y.w)) + (FL(y2.y) + FL(y2.w))) * (1.f / 1024.f)), 0.f) + LN_EPS)), sb + HV + tid * 8);
      mbar_wait(BAR(B_STG), 1); mbar_wait(BAR(B_STG + 1), 0); mbar_wait(BAR(B_STG + 2), 0);
      bar_sync(2, 128);
      PROFX(tid == 0, 30);
      float d0[4] = {0.f, 0.f, 0.f, 0.f}, d1[4] = {0.f, 0.f, 0.f, 0.f}, d2[4] = {0.f, 0.f, 0.f, 0.f};
      const uint32_t bd = (64 + (HV >> 4) + uni(bid & 3) * 32) | 0x10000u;
      #pragma unroll 1
      for (int ks = 0; ks < 8; ks++) {
        const uint32_t ad = (64 + (STG >> 4) + ks * 128) | (64u << 16);
        wg_fence();
        wgmma_ss_n8<0, 1>(d0, mkd<HI64>(ad), mkd<8>(bd + ks * 4), 1);
        wgmma_ss_n8<0, 1>(d1, mkd<HI64>(ad + 1024), mkd<8>(bd + ks * 4), 1);
        wgmma_ss_n8<0, 1>(d2, mkd<HI64>(ad + 2048), mkd<8>(bd + ks * 4), 1);
        wg_commit();
      }
      wg_wait<0>(); keep(d0); keep(d1); keep(d2);
      FRESH();
      if ((lane & 3) == (wq >> 1)) {
        uint4* dst = &P.g->patch[bid][(wq & 1) * 32 + (lane >> 2) * 2 + (wq >> 1)];
        st_ll(dst, UI(d0[0]), UI(d1[0]), UI(d2[0]), tag + 1); st_ll(dst + 16, UI(d0[2]), UI(d1[2]), UI(d2[2]), tag + 1);
      }
      PROFX(tid == 0, 31);
    }
  }
  if (bid == 0 && tid == 0) P.g->epoch = lds32(sb + INFO2 + 16) + 1;
  #undef blk
  #undef bid
  #undef fid
  #undef bi
  #undef bp
  #undef bc
  #undef FRESH
  #undef lane
  #undef wq
}

__global__ void __cluster_dims__(2, 1, 1) __launch_bounds__(512, 1) fused_kernel(const __grid_constant__ Params P) {
  extern __shared__ __align__(1024) uint8_t smem_raw[];
  const uint32_t sb = smem_u32(smem_raw);
  PROFT(threadIdx.x == 0, 0);
  if (threadIdx.x < 32) { if (elect()) {
    for (int s = 0; s < 3; s++) mbar_init(BAR(B_FULLQ + s), 1);
    asm volatile("fence.mbarrier_init.release.cluster;" ::: "memory");
    #pragma unroll 1
    for (int s = 0; s < 3; s++) {
      mbar_expect_tx(BAR(B_FULLQ + s), 57344);
      tma_2d(sb + qa_off(s), &P.mX, s * 64, (BID >> 4) * 256, BAR(B_FULLQ + s));
      tma_3d(sb + qb_off(s), &P.mWq, (BID & 15) * 64, s * 64, 0, BAR(B_FULLQ + s));
    }
    if ((sb & 0x3FFFFu) != 1024) __trap();
  } } else if (threadIdx.x == 480) {
    asm volatile("prefetch.tensormap [%0];" :: "l"(&P.mWq) : "memory");
  } else if (threadIdx.x >= 32 && !(threadIdx.x & 28) && (threadIdx.x >> 3) + (threadIdx.x & 3) <= B_COUNT + 1) {
    int b = (threadIdx.x >> 3) + (threadIdx.x & 3) - 1;
    if (b == B_COUNT) b = B_ROW;
    const uint32_t cnt = b < B_XFREE ? (b == B_OFREE ? 1 : 2) : (b < B_KVRDY ? 3 : (b < B_KVFULL || b == B_PAR ? 4 : (b == B_PFREE ? 2 : 1)));
    mbar_init(BAR(b), cnt);
    asm volatile("fence.mbarrier_init.release.cluster;" ::: "memory");
  }
  __syncthreads();
  asm volatile("barrier.cluster.arrive.relaxed.aligned;" ::: "memory");
  const int wg = __shfl_sync(0xffffffffu, threadIdx.x >> 7, 0);
  if (wg < 2) { reg_inc<224>(); consumer(P, sb, wg); }
  else if (wg == 2) { reg_dec<40>(); aux(P, sb); }
  else {
    reg_dec<24>();
    asm volatile("barrier.cluster.wait.aligned;" ::: "memory");
    const int w = __shfl_sync(0xffffffffu, (threadIdx.x >> 5) & 3, 0);
    if (w == 0) loader(P, sb);
    else if (w < 3) storer(P, sb, w - 1);
    else if (elect()) stager(P, sb);
  }
}

typedef CUresult (*EncFn)(CUtensorMap*, CUtensorMapDataType, cuuint32_t, void*, const cuuint64_t*, const cuuint64_t*, const cuuint32_t*, const cuuint32_t*,
                          CUtensorMapInterleave, CUtensorMapSwizzle, CUtensorMapL2promotion, CUtensorMapFloatOOBfill);
static void mk_map(EncFn enc, CUtensorMap* m, const void* ptr, int rank, const cuuint64_t* dims, const cuuint64_t* strides, const cuuint32_t* box,
                   CUtensorMapSwizzle sw, CUtensorMapL2promotion pr) {
  cuuint32_t es[5] = {1, 1, 1, 1, 1};
  enc(m, CU_TENSOR_MAP_DATA_TYPE_BFLOAT16, rank, (void*)ptr, dims, strides, box, es, CU_TENSOR_MAP_INTERLEAVE_NONE, sw, pr, CU_TENSOR_MAP_FLOAT_OOB_FILL_NONE);
}
extern "C" void kernel_launch(void* const* d_in, const int* in_sizes, int n_in, void* d_out, int out_size) {
  (void)in_sizes; (void)n_in; (void)out_size;
  void* fn = nullptr; cudaDriverEntryPointQueryResult q;
  cudaGetDriverEntryPoint("cuTensorMapEncodeTiled", &fn, cudaEnableDefault, &q);
  EncFn enc = (EncFn)fn;
  cudaFuncSetAttribute(fused_kernel, cudaFuncAttributeMaxDynamicSharedMemorySize, SMEM_BYTES);
  Params P;
  const CUtensorMapSwizzle S128 = CU_TENSOR_MAP_SWIZZLE_128B, S64 = CU_TENSOR_MAP_SWIZZLE_64B, S0 = CU_TENSOR_MAP_SWIZZLE_NONE;
  const CUtensorMapL2promotion L256 = CU_TENSOR_MAP_L2_PROMOTION_L2_256B, L128 = CU_TENSOR_MAP_L2_PROMOTION_L2_128B;
  { cuuint64_t d[2] = {1024, 2048}, s[1] = {2048}; cuuint32_t b[2] = {64, 256}, bh[2] = {64, 128};
    mk_map(enc, &P.mX, d_in[0], 2, d, s, b, S128, L256); mk_map(enc, &P.mXh, d_in[0], 2, d, s, bh, S128, L256); }
  { cuuint64_t d[3] = {1024, 1024, 3}, s[2] = {6144, 2048}; cuuint32_t b[3] = {64, 64, 3}; mk_map(enc, &P.mWq, d_in[1], 3, d, s, b, S128, L256); }
  { cuuint64_t d[5] = {64, 32, 2, 16, 16}, s[4] = {2048, 65536, 131072, 128}; cuuint32_t b[5] = {64, 32, 1, 2, 2}; mk_map(enc, &P.mWo, d_in[2], 5, d, s, b, S128, L256); }
  { cuuint64_t d[2] = {3584, 1024}, s[1] = {7168}; cuuint32_t b[2] = {32, 128};
    mk_map(enc, &P.mWg, d_in[5], 2, d, s, b, S64, L128); mk_map(enc, &P.mWu, d_in[6], 2, d, s, b, S64, L128); }
  { cuuint64_t d[2] = {3072, 1024}, s[1] = {6144}; cuuint32_t b[2] = {32, 256}; mk_map(enc, &P.mWp, d_in[1], 2, d, s, b, S64, L128); }
  { cuuint64_t d[3] = {256, 3584, 4}, s[2] = {2048, 512}; cuuint32_t b[3] = {256, 8, 4}; mk_map(enc, &P.mWd, d_in[7], 3, d, s, b, S0, L128); }
  P.x0 = (const bf16*)d_in[0]; P.wqkv = (const bf16*)d_in[1]; P.wo = (const bf16*)d_in[2]; P.wr = (const bf16*)d_in[4]; P.wg = (const bf16*)d_in[5]; P.wu = (const bf16*)d_in[6]; P.wd = (const bf16*)d_in[7];
  P.out = (bf16*)d_out;
  cudaGetSymbolAddress((void**)&P.g, g_scr);
  for (int b = 0; b < 128; b++) {
    int j = b >> 1, quad = j < 4 ? 0 : (j < 36 ? 1 + (j - 4) % 8 : 9 + (j - 36) % 7), pos = j < 4 ? j : (j < 36 ? (j - 4) / 8 : (j - 36) / 7);
    int bid = ((quad >> 2) * 2 + (pos >> 1)) * 16 + ((quad & 3) * 2 + (pos & 1)) * 2 + (b & 1);
    int e = pos * 2 + (b & 1), fid = e < 7 ? quad * 7 + e : 112 + quad;
    P.map[b] = bid | fid << 8;
  }
  fused_kernel<<<128, 512, SMEM_BYTES>>>(P);
}
```

```cpp
#include <cuda_runtime.h>
#include <cuda_bf16.h>
#include <cuda.h>
#include <stdint.h>
#include <stddef.h>
typedef __nv_bfloat16 bf16;

template<int TB, int TA = 0> __device__ __forceinline__ void wgmma_ss_n192(float (&d)[96], uint64_t da, uint64_t db, int scale_d) {
  asm volatile("{\n.reg .pred p;\nsetp.ne.b32 p, %98, 0;\n"
    "wgmma.mma_async.sync.aligned.m64n192k16.f32.bf16.bf16 {%0, %1, %2, %3, %4, %5, %6, %7, %8, %9, %10, %11, %12, %13, %14, %15, %16, %17, %18, %19, %20, %21, %22, %23, %24, %25, %26, %27, %28, %29, %30, %31, %32, %33, %34, %35, %36, %37, %38, %39, %40, %41, %42, %43, %44, %45, %46, %47, %48, %49, %50, %51, %52, %53, %54, %55, %56, %57, %58, %59, %60, %61, %62, %63, %64, %65, %66, %67, %68, %69, %70, %71, %72, %73, %74, %75, %76, %77, %78, %79, %80, %81, %82, %83, %84, %85, %86, %87, %88, %89, %90, %91, %92, %93, %94, %95}, %96, %97, p, 1, 1, %100, %99;\n}\n"
    : "+f"(d[0]), "+f"(d[1]), "+f"(d[2]), "+f"(d[3]), "+f"(d[4]), "+f"(d[5]), "+f"(d[6]), "+f"(d[7]), "+f"(d[8]), "+f"(d[9]), "+f"(d[10]), "+f"(d[11]), "+f"(d[12]), "+f"(d[13]), "+f"(d[14]), "+f"(d[15]), "+f"(d[16]), "+f"(d[17]), "+f"(d[18]), "+f"(d[19]), "+f"(d[20]), "+f"(d[21]), "+f"(d[22]), "+f"(d[23]), "+f"(d[24]), "+f"(d[25]), "+f"(d[26]), "+f"(d[27]), "+f"(d[28]), "+f"(d[29]), "+f"(d[30]), "+f"(d[31]), "+f"(d[32]), "+f"(d[33]), "+f"(d[34]), "+f"(d[35]), "+f"(d[36]), "+f"(d[37]), "+f"(d[38]), "+f"(d[39]), "+f"(d[40]), "+f"(d[41]), "+f"(d[42]), "+f"(d[43]), "+f"(d[44]), "+f"(d[45]), "+f"(d[46]), "+f"(d[47]), "+f"(d[48]), "+f"(d[49]), "+f"(d[50]), "+f"(d[51]), "+f"(d[52]), "+f"(d[53]), "+f"(d[54]), "+f"(d[55]), "+f"(d[56]), "+f"(d[57]), "+f"(d[58]), "+f"(d[59]), "+f"(d[60]), "+f"(d[61]), "+f"(d[62]), "+f"(d[63]), "+f"(d[64]), "+f"(d[65]), "+f"(d[66]), "+f"(d[67]), "+f"(d[68]), "+f"(d[69]), "+f"(d[70]), "+f"(d[71]), "+f"(d[72]), "+f"(d[73]), "+f"(d[74]), "+f"(d[75]), "+f"(d[76]), "+f"(d[77]), "+f"(d[78]), "+f"(d[79]), "+f"(d[80]), "+f"(d[81]), "+f"(d[82]), "+f"(d[83]), "+f"(d[84]), "+f"(d[85]), "+f"(d[86]), "+f"(d[87]), "+f"(d[88]), "+f"(d[89]), "+f"(d[90]), "+f"(d[91]), "+f"(d[92]), "+f"(d[93]), "+f"(d[94]), "+f"(d[95])
    : "l"(da), "l"(db), "r"(scale_d), "n"(TB), "n"(TA));
}

template<int TB> __device__ __forceinline__ void wgmma_rs_n192(float (&d)[96], uint32_t a0, uint32_t a1, uint32_t a2, uint32_t a3, uint64_t db, int scale_d) {
  asm volatile("{\n.reg .pred p;\nsetp.ne.b32 p, %101, 0;\n"
    "wgmma.mma_async.sync.aligned.m64n192k16.f32.bf16.bf16 {%0, %1, %2, %3, %4, %5, %6, %7, %8, %9, %10, %11, %12, %13, %14, %15, %16, %17, %18, %19, %20, %21, %22, %23, %24, %25, %26, %27, %28, %29, %30, %31, %32, %33, %34, %35, %36, %37, %38, %39, %40, %41, %42, %43, %44, %45, %46, %47, %48, %49, %50, %51, %52, %53, %54, %55, %56, %57, %58, %59, %60, %61, %62, %63, %64, %65, %66, %67, %68, %69, %70, %71, %72, %73, %74, %75, %76, %77, %78, %79, %80, %81, %82, %83, %84, %85, %86, %87, %88, %89, %90, %91, %92, %93, %94, %95}, {%96, %97, %98, %99}, %100, p, 1, 1, %102;\n}\n"
    : "+f"(d[0]), "+f"(d[1]), "+f"(d[2]), "+f"(d[3]), "+f"(d[4]), "+f"(d[5]), "+f"(d[6]), "+f"(d[7]), "+f"(d[8]), "+f"(d[9]), "+f"(d[10]), "+f"(d[11]), "+f"(d[12]), "+f"(d[13]), "+f"(d[14]), "+f"(d[15]), "+f"(d[16]), "+f"(d[17]), "+f"(d[18]), "+f"(d[19]), "+f"(d[20]), "+f"(d[21]), "+f"(d[22]), "+f"(d[23]), "+f"(d[24]), "+f"(d[25]), "+f"(d[26]), "+f"(d[27]), "+f"(d[28]), "+f"(d[29]), "+f"(d[30]), "+f"(d[31]), "+f"(d[32]), "+f"(d[33]), "+f"(d[34]), "+f"(d[35]), "+f"(d[36]), "+f"(d[37]), "+f"(d[38]), "+f"(d[39]), "+f"(d[40]), "+f"(d[41]), "+f"(d[42]), "+f"(d[43]), "+f"(d[44]), "+f"(d[45]), "+f"(d[46]), "+f"(d[47]), "+f"(d[48]), "+f"(d[49]), "+f"(d[50]), "+f"(d[51]), "+f"(d[52]), "+f"(d[53]), "+f"(d[54]), "+f"(d[55]), "+f"(d[56]), "+f"(d[57]), "+f"(d[58]), "+f"(d[59]), "+f"(d[60]), "+f"(d[61]), "+f"(d[62]), "+f"(d[63]), "+f"(d[64]), "+f"(d[65]), "+f"(d[66]), "+f"(d[67]), "+f"(d[68]), "+f"(d[69]), "+f"(d[70]), "+f"(d[71]), "+f"(d[72]), "+f"(d[73]), "+f"(d[74]), "+f"(d[75]), "+f"(d[76]), "+f"(d[77]), "+f"(d[78]), "+f"(d[79]), "+f"(d[80]), "+f"(d[81]), "+f"(d[82]), "+f"(d[83]), "+f"(d[84]), "+f"(d[85]), "+f"(d[86]), "+f"(d[87]), "+f"(d[88]), "+f"(d[89]), "+f"(d[90]), "+f"(d[91]), "+f"(d[92]), "+f"(d[93]), "+f"(d[94]), "+f"(d[95])
    : "r"(a0), "r"(a1), "r"(a2), "r"(a3), "l"(db), "r"(scale_d), "n"(TB));
}

template<int TB, int TA = 0> __device__ __forceinline__ void wgmma_ss_n128(float (&d)[64], uint64_t da, uint64_t db, int scale_d) {
  asm volatile("{\n.reg .pred p;\nsetp.ne.b32 p, %66, 0;\n"
    "wgmma.mma_async.sync.aligned.m64n128k16.f32.bf16.bf16 {%0, %1, %2, %3, %4, %5, %6, %7, %8, %9, %10, %11, %12, %13, %14, %15, %16, %17, %18, %19, %20, %21, %22, %23, %24, %25, %26, %27, %28, %29, %30, %31, %32, %33, %34, %35, %36, %37, %38, %39, %40, %41, %42, %43, %44, %45, %46, %47, %48, %49, %50, %51, %52, %53, %54, %55, %56, %57, %58, %59, %60, %61, %62, %63}, %64, %65, p, 1, 1, %68, %67;\n}\n"
    : "+f"(d[0]), "+f"(d[1]), "+f"(d[2]), "+f"(d[3]), "+f"(d[4]), "+f"(d[5]), "+f"(d[6]), "+f"(d[7]), "+f"(d[8]), "+f"(d[9]), "+f"(d[10]), "+f"(d[11]), "+f"(d[12]), "+f"(d[13]), "+f"(d[14]), "+f"(d[15]), "+f"(d[16]), "+f"(d[17]), "+f"(d[18]), "+f"(d[19]), "+f"(d[20]), "+f"(d[21]), "+f"(d[22]), "+f"(d[23]), "+f"(d[24]), "+f"(d[25]), "+f"(d[26]), "+f"(d[27]), "+f"(d[28]), "+f"(d[29]), "+f"(d[30]), "+f"(d[31]), "+f"(d[32]), "+f"(d[33]), "+f"(d[34]), "+f"(d[35]), "+f"(d[36]), "+f"(d[37]), "+f"(d[38]), "+f"(d[39]), "+f"(d[40]), "+f"(d[41]), "+f"(d[42]), "+f"(d[43]), "+f"(d[44]), "+f"(d[45]), "+f"(d[46]), "+f"(d[47]), "+f"(d[48]), "+f"(d[49]), "+f"(d[50]), "+f"(d[51]), "+f"(d[52]), "+f"(d[53]), "+f"(d[54]), "+f"(d[55]), "+f"(d[56]), "+f"(d[57]), "+f"(d[58]), "+f"(d[59]), "+f"(d[60]), "+f"(d[61]), "+f"(d[62]), "+f"(d[63])
    : "l"(da), "l"(db), "r"(scale_d), "n"(TB), "n"(TA));
}

template<int TB, int TA = 0> __device__ __forceinline__ void wgmma_ss_n64(float (&d)[32], uint64_t da, uint64_t db, int scale_d) {
  asm volatile("{\n.reg .pred p;\nsetp.ne.b32 p, %34, 0;\n"
    "wgmma.mma_async.sync.aligned.m64n64k16.f32.bf16.bf16 {%0, %1, %2, %3, %4, %5, %6, %7, %8, %9, %10, %11, %12, %13, %14, %15, %16, %17, %18, %19, %20, %21, %22, %23, %24, %25, %26, %27, %28, %29, %30, %31}, %32, %33, p, 1, 1, %36, %35;\n}\n"
    : "+f"(d[0]), "+f"(d[1]), "+f"(d[2]), "+f"(d[3]), "+f"(d[4]), "+f"(d[5]), "+f"(d[6]), "+f"(d[7]), "+f"(d[8]), "+f"(d[9]), "+f"(d[10]), "+f"(d[11]), "+f"(d[12]), "+f"(d[13]), "+f"(d[14]), "+f"(d[15]), "+f"(d[16]), "+f"(d[17]), "+f"(d[18]), "+f"(d[19]), "+f"(d[20]), "+f"(d[21]), "+f"(d[22]), "+f"(d[23]), "+f"(d[24]), "+f"(d[25]), "+f"(d[26]), "+f"(d[27]), "+f"(d[28]), "+f"(d[29]), "+f"(d[30]), "+f"(d[31])
    : "l"(da), "l"(db), "r"(scale_d), "n"(TB), "n"(TA));
}

template<int TB, int TA = 0> __device__ __forceinline__ void wgmma_ss_n8(float (&d)[4], uint64_t da, uint64_t db, int scale_d) {
  asm volatile("{\n.reg .pred p;\nsetp.ne.b32 p, %6, 0;\n"
    "wgmma.mma_async.sync.aligned.m64n8k16.f32.bf16.bf16 {%0, %1, %2, %3}, %4, %5, p, 1, 1, %8, %7;\n}\n"
    : "+f"(d[0]), "+f"(d[1]), "+f"(d[2]), "+f"(d[3])
    : "l"(da), "l"(db), "r"(scale_d), "n"(TB), "n"(TA));
}

template<int TB> __device__ __forceinline__ void wgmma_rs_n40(float (&d)[20], uint32_t a0, uint32_t a1, uint32_t a2, uint32_t a3, uint64_t db, int scale_d) {
  asm volatile("{\n.reg .pred p;\nsetp.ne.b32 p, %25, 0;\n"
    "wgmma.mma_async.sync.aligned.m64n40k16.f32.bf16.bf16 {%0, %1, %2, %3, %4, %5, %6, %7, %8, %9, %10, %11, %12, %13, %14, %15, %16, %17, %18, %19}, {%20, %21, %22, %23}, %24, p, 1, 1, %26;\n}\n"
    : "+f"(d[0]), "+f"(d[1]), "+f"(d[2]), "+f"(d[3]), "+f"(d[4]), "+f"(d[5]), "+f"(d[6]), "+f"(d[7]), "+f"(d[8]), "+f"(d[9]), "+f"(d[10]), "+f"(d[11]), "+f"(d[12]), "+f"(d[13]), "+f"(d[14]), "+f"(d[15]), "+f"(d[16]), "+f"(d[17]), "+f"(d[18]), "+f"(d[19])
    : "r"(a0), "r"(a1), "r"(a2), "r"(a3), "l"(db), "r"(scale_d), "n"(TB));
}

#define DEVI __device__ __forceinline__
DEVI uint32_t smem_u32(const void* p) { return (uint32_t)__cvta_generic_to_shared(p); }
DEVI void mbar_init(uint32_t bar, uint32_t cnt) { asm volatile("mbarrier.init.shared::cta.b64 [%0], %1;" :: "r"(bar), "r"(cnt)); }
DEVI void mbar_expect_tx(uint32_t bar, uint32_t bytes) { asm volatile("mbarrier.arrive.expect_tx.shared::cta.b64 _, [%0], %1;" :: "r"(bar), "r"(bytes) : "memory"); }
DEVI void mbar_arrive(uint32_t bar) { asm volatile("mbarrier.arrive.shared::cta.b64 _, [%0];" :: "r"(bar) : "memory"); }
DEVI void mbar_arrive_peer(uint32_t bar) {
  asm volatile("{\n.reg .b32 ra;\nmapa.shared::cluster.u32 ra, %0, %1;\nmbarrier.arrive.shared::cluster.b64 _, [ra];\n}" :: "r"(bar), "r"((blockIdx.x & 1) ^ 1) : "memory");
}
DEVI void bulk_s2peer(uint32_t a, uint32_t bytes, uint32_t bar) {
  asm volatile("{\n.reg .b32 ra, rb;\nmapa.shared::cluster.u32 ra, %0, %3;\nmapa.shared::cluster.u32 rb, %2, %3;\n"
               "cp.async.bulk.shared::cluster.shared::cta.mbarrier::complete_tx::bytes [ra], [%0], %1, [rb];\n}"
               :: "r"(a), "r"(bytes), "r"(bar), "r"((blockIdx.x & 1) ^ 1) : "memory");
}
DEVI void mbar_wait(uint32_t bar, uint32_t parity) {
  asm volatile("{\n.reg .pred p;\nLW:\nmbarrier.try_wait.parity.shared::cta.b64 p, [%0], %1;\n@!p bra LW;\n}" :: "r"(bar), "r"(parity) : "memory");
}
DEVI uint32_t mbar_test(uint32_t bar, uint32_t parity) {
  uint32_t r; asm volatile("{\n.reg .pred p;\nmbarrier.test_wait.parity.shared::cta.b64 p, [%1], %2;\nselp.u32 %0, 1, 0, p;\n}" : "=r"(r) : "r"(bar), "r"(parity) : "memory"); return r;
}
DEVI void mbar_wait_b(uint32_t bar, uint32_t parity) {
  asm volatile("{\n.reg .pred p;\n.reg .u32 it;\nmov.u32 it, 0;\nLW:\nmbarrier.try_wait.parity.shared::cta.b64 p, [%0], %1;\n@p bra LD;\n"
               "add.u32 it, it, 1;\nsetp.lt.u32 p, it, 0x1000000;\n@p bra LW;\ntrap;\nLD:\n}" :: "r"(bar), "r"(parity) : "memory");
}
DEVI void tma_2d(uint32_t dst, const CUtensorMap* m, int c0, int c1, uint32_t bar) {
  asm volatile("cp.async.bulk.tensor.2d.shared::cluster.global.mbarrier::complete_tx::bytes [%0], [%1, {%3, %4}], [%2];"
    :: "r"(dst), "l"(m), "r"(bar), "r"(c0), "r"(c1) : "memory");
}
DEVI void tma_3d(uint32_t dst, const CUtensorMap* m, int c0, int c1, int c2, uint32_t bar) {
  asm volatile("cp.async.bulk.tensor.3d.shared::cluster.global.mbarrier::complete_tx::bytes [%0], [%1, {%3, %4, %5}], [%2];"
    :: "r"(dst), "l"(m), "r"(bar), "r"(c0), "r"(c1), "r"(c2) : "memory");
}
#define POL_EF POL_FIRST
constexpr uint64_t POL_FIRST = 0x12F0000000000000ull, POL_NORMAL = 0x1000000000000000ull;
DEVI void tma_2d_h(uint32_t dst, const CUtensorMap* m, int c0, int c1, uint32_t bar, uint64_t pol) {
  asm volatile("cp.async.bulk.tensor.2d.shared::cluster.global.mbarrier::complete_tx::bytes.L2::cache_hint [%0], [%1, {%3, %4}], [%2], %5;"
    :: "r"(dst), "l"(m), "r"(bar), "r"(c0), "r"(c1), "l"(pol) : "memory");
}
DEVI void tma_3d_h(uint32_t dst, const CUtensorMap* m, int c0, int c1, int c2, uint32_t bar, uint64_t pol) {
  asm volatile("cp.async.bulk.tensor.3d.shared::cluster.global.mbarrier::complete_tx::bytes.L2::cache_hint [%0], [%1, {%3, %4, %5}], [%2], %6;"
    :: "r"(dst), "l"(m), "r"(bar), "r"(c0), "r"(c1), "r"(c2), "l"(pol) : "memory");
}
DEVI void bulk_g2s_h(uint32_t s, const void* g, uint32_t bytes, uint32_t bar, uint64_t pol = POL_EF) {
  asm volatile("cp.async.bulk.shared::cluster.global.mbarrier::complete_tx::bytes.L2::cache_hint [%0], [%1], %2, [%3], %4;"
    :: "r"(s), "l"(g), "r"(bytes), "r"(bar), "l"(pol) : "memory");
}
DEVI void tma_5d(uint32_t dst, const CUtensorMap* m, int c0, int c1, int c2, int c3, int c4, uint32_t bar, uint64_t pol) {
  asm volatile("cp.async.bulk.tensor.5d.shared::cluster.global.mbarrier::complete_tx::bytes.L2::cache_hint [%0], [%1, {%3, %4, %5, %6, %7}], [%2], %8;"
    :: "r"(dst), "l"(m), "r"(bar), "r"(c0), "r"(c1), "r"(c2), "r"(c3), "r"(c4), "l"(pol) : "memory");
}
DEVI void tma_prefetch_2d(const CUtensorMap* m, int c0, int c1) {
  asm volatile("cp.async.bulk.prefetch.tensor.2d.L2.global.tile [%0, {%1, %2}];" :: "l"(m), "r"(c0), "r"(c1) : "memory");
}
DEVI void tma_prefetch_3d(const CUtensorMap* m, int c0, int c1, int c2) {
  asm volatile("cp.async.bulk.prefetch.tensor.3d.L2.global.tile [%0, {%1, %2, %3}];" :: "l"(m), "r"(c0), "r"(c1), "r"(c2) : "memory");
}
DEVI void bulk_prefetch(const void* g, uint32_t bytes) { asm volatile("cp.async.bulk.prefetch.L2.global [%0], %1;" :: "l"(g), "r"(bytes) : "memory"); }
DEVI void bulk_g2s(uint32_t s, const void* g, uint32_t bytes, uint32_t bar) {
  asm volatile("cp.async.bulk.shared::cluster.global.mbarrier::complete_tx::bytes [%0], [%1], %2, [%3];" :: "r"(s), "l"(g), "r"(bytes), "r"(bar) : "memory");
}
DEVI void bulk_s2g(void* g, uint32_t s, uint32_t bytes, uint64_t pol = POL_NORMAL) {
  asm volatile("cp.async.bulk.global.shared::cta.bulk_group.L2::cache_hint [%0], [%1], %2, %3;\ncp.async.bulk.commit_group;" :: "l"(g), "r"(s), "r"(bytes), "l"(pol) : "memory");
}
template<int N> DEVI void bulk_wait() { asm volatile("cp.async.bulk.wait_group %0;" :: "n"(N) : "memory"); }
DEVI void fence_async_smem() { asm volatile("fence.proxy.async.shared::cta;" ::: "memory"); }
DEVI void fence_async_glob() { asm volatile("fence.proxy.async.global;" ::: "memory"); }
DEVI unsigned ld_rlx(const unsigned* p) { unsigned v; asm volatile("ld.relaxed.gpu.global.u32 %0, [%1];" : "=r"(v) : "l"(p) : "memory"); return v; }
DEVI void st_rlx(unsigned* p, unsigned v) { asm volatile("st.relaxed.gpu.global.u32 [%0], %1;" :: "l"(p), "r"(v) : "memory"); }
DEVI uint2 ldg_stream(const uint2* p) { uint2 v; asm volatile("ld.global.nc.L1::no_allocate.v2.u32 {%0, %1}, [%2];" : "=r"(v.x), "=r"(v.y) : "l"(p)); return v; }
DEVI void fence_rel() { asm volatile("fence.release.gpu;" ::: "memory"); }
DEVI uint4 ld_ll(const uint4* p) {
  uint4 v;
  asm volatile("{\n.reg .b128 t;\n.reg .b64 a, b;\nld.relaxed.gpu.global.b128 t, [%4];\nmov.b128 {a, b}, t;\nmov.b64 {%0, %1}, a;\nmov.b64 {%2, %3}, b;\n}"
               : "=r"(v.x), "=r"(v.y), "=r"(v.z), "=r"(v.w) : "l"(p) : "memory");
  return v;
}
DEVI void st_ll(uint4* p, uint32_t x, uint32_t y, uint32_t z, uint32_t w) {
  asm volatile("{\n.reg .b128 t;\n.reg .b64 a, b;\nmov.b64 a, {%1, %2};\nmov.b64 b, {%3, %4};\nmov.b128 t, {a, b};\nst.relaxed.gpu.global.b128 [%0], t;\n}"
               :: "l"(p), "r"(x), "r"(y), "r"(z), "r"(w) : "memory");
}
#define SPIN_MAX 0x1000000
DEVI uint4 poll_ll(const uint4* p, uint32_t mask, uint32_t tag) {
  uint4 v; int it = 0;
  do { v = ld_ll(p); if (++it > SPIN_MAX) __trap(); } while (!__all_sync(0xffffffffu, (v.w & mask) == tag));
  return v;
}
DEVI void poll_ll2(const uint4* p, const uint4* q, uint32_t mask, uint32_t tag, uint4& a, uint4& b) {
  int it = 0;
  do { a = ld_ll(p); b = ld_ll(q); if (++it > SPIN_MAX) __trap(); } while (!__all_sync(0xffffffffu, (a.w & mask) == tag && (b.w & mask) == tag));
}
DEVI float4 poll_sum4(const uint4* src, int stride, uint32_t tag) {
  uint4 v0, v1, v2, v3; int it = 0;
  do { v0 = ld_ll(src); v1 = ld_ll(src + stride); v2 = ld_ll(src + 2 * stride); v3 = ld_ll(src + 3 * stride); if (++it > SPIN_MAX) __trap(); }
  while (!__all_sync(0xffffffffu, v0.w == tag && v1.w == tag && v2.w == tag && v3.w == tag));
  #define S4(f) ((__uint_as_float(v0.f) + __uint_as_float(v1.f)) + (__uint_as_float(v2.f) + __uint_as_float(v3.f)))
  return make_float4(S4(x), S4(y), S4(z), 0.f);
  #undef S4
}
DEVI void bar_sync(int id, int n) { asm volatile("bar.sync %0, %1;" :: "r"(id), "r"(n) : "memory"); }
DEVI void bar_arrive(int id, int n) { asm volatile("bar.arrive %0, %1;" :: "r"(id), "r"(n) : "memory"); }
DEVI void wg_fence() { asm volatile("wgmma.fence.sync.aligned;" ::: "memory"); }
DEVI void wg_commit() { asm volatile("wgmma.commit_group.sync.aligned;" ::: "memory"); }
template<int N> DEVI void wg_wait() { asm volatile("wgmma.wait_group.sync.aligned %0;" :: "n"(N) : "memory"); }
template<int N> DEVI void reg_inc() { asm volatile("setmaxnreg.inc.sync.aligned.u32 %0;" :: "n"(N)); }
template<int N> DEVI void reg_dec() { asm volatile("setmaxnreg.dec.sync.aligned.u32 %0;" :: "n"(N)); }
DEVI float ex2f(float x) { float y; asm("ex2.approx.ftz.f32 %0, %1;" : "=f"(y) : "f"(x)); return y; }
DEVI uint32_t pack_bf16(float lo, float hi) { uint32_t r; asm("cvt.rn.bf16x2.f32 %0, %1, %2;" : "=r"(r) : "f"(hi), "f"(lo)); return r; }
DEVI float bf_lo(uint32_t v) { return __uint_as_float(v << 16); }
DEVI float bf_hi(uint32_t v) { return __uint_as_float(v & 0xffff0000u); }
DEVI float bf_round(float x) { return bf_lo(pack_bf16(x, 0.f)); }
DEVI void stsm_x4(uint32_t addr, uint32_t a, uint32_t b, uint32_t c, uint32_t d) {
  asm volatile("stmatrix.sync.aligned.m8n8.x4.shared.b16 [%0], {%1,%2,%3,%4};" :: "r"(addr), "r"(a), "r"(b), "r"(c), "r"(d) : "memory");
}
DEVI void ldsm_x4(uint32_t addr, uint32_t& a, uint32_t& b, uint32_t& c, uint32_t& d) {
  asm volatile("ldmatrix.sync.aligned.m8n8.x4.shared.b16 {%0,%1,%2,%3}, [%4];" : "=r"(a), "=r"(b), "=r"(c), "=r"(d) : "r"(addr) : "memory");
}
DEVI uint4 lds128(uint32_t a) { uint4 v; asm volatile("ld.shared.v4.u32 {%0,%1,%2,%3}, [%4];" : "=r"(v.x), "=r"(v.y), "=r"(v.z), "=r"(v.w) : "r"(a) : "memory"); return v; }
DEVI void sts128(uint32_t a, uint4 v) { asm volatile("st.shared.v4.u32 [%0], {%1,%2,%3,%4};" :: "r"(a), "r"(v.x), "r"(v.y), "r"(v.z), "r"(v.w) : "memory"); }
DEVI float2 lds64f(uint32_t a) { float2 v; asm volatile("ld.shared.v2.f32 {%0,%1}, [%2];" : "=f"(v.x), "=f"(v.y) : "r"(a) : "memory"); return v; }
DEVI void sts64f(uint32_t a, float x, float y) { asm volatile("st.shared.v2.f32 [%0], {%1,%2};" :: "r"(a), "f"(x), "f"(y) : "memory"); }
DEVI uint32_t lds32(uint32_t a) { uint32_t v; asm volatile("ld.shared.u32 %0, [%1];" : "=r"(v) : "r"(a) : "memory"); return v; }
DEVI float lds32f(uint32_t a) { return __uint_as_float(lds32(a)); }
DEVI void sts32(uint32_t a, uint32_t v) { asm volatile("st.shared.u32 [%0], %1;" :: "r"(a), "r"(v) : "memory"); }
DEVI void sts32f(uint32_t a, float v) { sts32(a, __float_as_uint(v)); }
DEVI void sts16(uint32_t a, uint32_t v) { asm volatile("st.shared.u16 [%0], %1;" :: "r"(a), "h"((unsigned short)v) : "memory"); }
template<int N> DEVI void keep(float (&d)[N]) {
  #pragma unroll
  for (int i = 0; i < N; i++) asm volatile("" : "+f"(d[i]) :: "memory");
}
template<int N> DEVI void keep(uint32_t (&d)[N]) {
  #pragma unroll
  for (int i = 0; i < N; i++) asm volatile("" : "+r"(d[i]) :: "memory");
}
template<uint32_t HI> DEVI uint64_t mkd(uint32_t lo) { uint64_t r; asm("mov.b64 %0, {%1, %2};" : "=l"(r) : "r"(lo), "n"(HI)); return r; }
constexpr uint32_t HI128 = (1u << 30) | (1024 >> 4), HI64 = (2u << 30) | (512 >> 4);
#define VOFF(x) ((uint32_t)(x) * (uint32_t)(1 - 65536))
DEVI bool elect() { uint32_t p; asm volatile("{\n.reg .pred q;\nelect.sync _|q, 0xffffffff;\nselp.u32 %0, 1, 0, q;\n}" : "=r"(p)); return p; }
DEVI void warp_signal(uint32_t bar) { __syncwarp(); if (elect()) mbar_arrive(bar); }

struct Scratch {
  uint4 kv[128][4][1024];
  uint4 o[8][2][8][2][1024];
  uint4 x[8][16][2048];
  uint4 zero[1024];
  uint4 statP[8][2048];
  uint4 statF[2048];
  uint4 csP[16][8][96];
  uint4 best[8][16];
  uint4 row[16][256];
  uint4 yP[128][112][2];
  uint4 x2[8][256];
  uint4 patch[128][64];
  unsigned flagKV[128][32];
  unsigned flagO[8][32];
  unsigned flagX[8][32];
  unsigned epoch;
};
__device__ __align__(1024) Scratch g_scr;
#define PROFT(cond, slot)
#define PROFW(cond, slot)
#define PROFD(cond, slot)
#define PROFX(cond, slot)
#define PROFY(cond, slot)

constexpr uint32_t SB0 = 65536, HOLE = 90112, SA2 = 98304, SB1 = 131072, SB2 = 155648, STG = 180224;
constexpr uint32_t KVA = 0, KVB = 98304, QO = 65536;
constexpr uint32_t MISC = 229376, CS = MISC, ONES = MISC + 768, BARS = MISC + 1792, INFO = MISC + 2208, WR = MISC + 2224, X2SEG = MISC + 2736, INFO2 = MISC + 2992, DUMP = MISC + 3040;
constexpr uint32_t PAR = HOLE, HV = HOLE + 2048, RED = HOLE + 6144, PATCH = 196608;
constexpr uint32_t SMEM_BYTES = 232448;
enum { B_FULLQ = 0, B_EMPTYQ = 3, B_FULLW = 6, B_EMPTYW = 12, B_HAFREE = 18, B_OFREE = 20,
       B_XFREE = 21,
       B_KVRDY = 23, B_ORDY = 27, B_XRDY = 35, B_STGE = 39,
       B_KVFULL = 42, B_RES = 46, B_PAR = 47, B_STG = 48, B_PFREE = 51, B_COUNT = 52,
       B_ROW = 154 };
#define BAR(x) (sb + BARS + 8 * (x))
DEVI uint32_t qa_off(int s) { return s == 2 ? SA2 : (uint32_t)s * 32768u; }
DEVI uint32_t qb_off(int s) { return s == 0 ? SB0 : (s == 1 ? SB1 : SB2); }
DEVI int kb_order(int bc, int n) {
  const int e = n < 9 ? n - 2 : n - 9;
  return n < 2 ? 2 * bc + n : 2 * (((e < 4 ? e + 4 : e - 4 + (e - 4 >= (bc & 3))) + (bc & 4)) & 7) + (n >= 9);
}
DEVI int wo_order(int bc, int n) { return (n & 8) | ((n + (bc & 6)) & 7); }
DEVI uint32_t w_off(int s) { return (uint32_t)((0x143065 >> (4 * s)) & 7) * 32768u; }
DEVI uint32_t w_par(int n, int s, int L) { return (n >= 6 && n < 12) ^ (s == 5) ^ (s != 2 && L); }
DEVI int w_next(int n, int s) { return s == 5 ? 0 : (n == 13 ? 3 : s + 1); }

struct Params {
  CUtensorMap mX, mXh, mWq, mWo, mWg, mWu, mWp, mWd;
  const bf16 *x0, *wqkv, *wo, *wr, *wg, *wu, *wd;
  bf16* out;
  Scratch* g;
  unsigned map[128];
};
#define BID ((int)(P.map[blockIdx.x] & 255))
#define FID ((int)(P.map[blockIdx.x] >> 8))
DEVI uint32_t uni(uint32_t v) { return __shfl_sync(0xffffffffu, v, 0); }
#define PQ_N 8
#define PQ_T 700
#define PF0_N 10
#define PF0_T 1600
#define PF1_E 24
#define PF1_T 1100
#define POL_Q1 POL_NORMAL
#define POL_X POL_NORMAL
#define PFA0_BAR 3
#define PFA1_BAR 0
#define PFA0_M 0
#define PFA1_M 0
#define PFA0_T 900
#define PFA1_T 700
#define PF1_S PF0_N
#define PF1_D 0
#define POL_G POL_NORMAL
#define POL_U POL_FIRST
#define POL_D POL_FIRST
#define JQ_N 6
#define WDSRC (P.wd + (size_t)min(fid, 111) * 32768)
#define WDSRC2 (P.wd + FID * 32768)
#define WD_N 4
#define THR_N 5
#define KV_D 1800
#define XD_D 300
#define W0_BAR 3
#define QEF_N 99
#define PACE_T 300
#define IDLE_T 11000
#define LATE_C 2
#define LATE_B B_XFREE + 1
#define LATE_P 0
#define KV_D1 200
#define KV_D2 1200
#define KV_DL 0
#define POL_KV0 POL_FIRST
#define POL_KV1 POL_FIRST
#define POL_O0 POL_FIRST
#define POL_O1 POL_FIRST
#define POL_W0 POL_NORMAL
#define POL_W1 POL_FIRST
#define POL_T POL_FIRST
#define U_C 8
#define ST_M 0
#define POL_Q0 POL_NORMAL
constexpr float LN_EPS = 1e-5f;
constexpr float QSCALE = 0.17677669529663687f * 1.4426950408889634f;

DEVI void fma8(float (&a)[8], uint4 v, float h) {
  a[0] = fmaf(bf_lo(v.x), h, a[0]); a[1] = fmaf(bf_hi(v.x), h, a[1]); a[2] = fmaf(bf_lo(v.y), h, a[2]); a[3] = fmaf(bf_hi(v.y), h, a[3]);
  a[4] = fmaf(bf_lo(v.z), h, a[4]); a[5] = fmaf(bf_hi(v.z), h, a[5]); a[6] = fmaf(bf_lo(v.w), h, a[6]); a[7] = fmaf(bf_hi(v.w), h, a[7]);
}
DEVI uint4 ldsv128(uint32_t a) { uint4 v; asm volatile("ld.volatile.shared.v4.u32 {%0,%1,%2,%3}, [%4];" : "=r"(v.x), "=r"(v.y), "=r"(v.z), "=r"(v.w) : "r"(a) : "memory"); return v; }
DEVI float ldsv32f(uint32_t a) { float v; asm volatile("ld.volatile.shared.f32 %0, [%1];" : "=f"(v) : "r"(a) : "memory"); return v; }
DEVI uint32_t clk() { uint32_t t; asm volatile("mov.u32 %0, %%clock;" : "=r"(t)); return t; }
DEVI int fresh_tid() { int t; asm volatile("mov.u32 %0, %%tid.x;" : "=r"(t)); return t & 127; }
DEVI float fold8(const float (&a)[8]) {
  const int lane = threadIdx.x & 31;
  const bool u = lane & 16, v = lane & 8, x = lane & 4;
  float b0 = (u ? a[4] : a[0]) + __shfl_xor_sync(0xffffffffu, u ? a[0] : a[4], 16), b1 = (u ? a[5] : a[1]) + __shfl_xor_sync(0xffffffffu, u ? a[1] : a[5], 16);
  float b2 = (u ? a[6] : a[2]) + __shfl_xor_sync(0xffffffffu, u ? a[2] : a[6], 16), b3 = (u ? a[7] : a[3]) + __shfl_xor_sync(0xffffffffu, u ? a[3] : a[7], 16);
  float c0 = (v ? b2 : b0) + __shfl_xor_sync(0xffffffffu, v ? b0 : b2, 8), c1 = (v ? b3 : b1) + __shfl_xor_sync(0xffffffffu, v ? b1 : b3, 8);
  return (x ? c1 : c0) + __shfl_xor_sync(0xffffffffu, x ? c0 : c1, 4);
}
DEVI float swiglu(float g, float u) { g = bf_round(g); return bf_round(bf_round(__fdividef(g, 1.f + __expf(-g))) * bf_round(u)); }

template<int J0, int J1> DEVI void exp_pack(const float (&s)[32], uint32_t (&p)[16]) {
  #pragma unroll
  for (int j = J0; j < J1; j++) p[j] = pack_bf16(ex2f(s[2 * j]), ex2f(s[2 * j + 1]));
}
DEVI bool attn_pack(const float (&o)[20], uint32_t (&ob)[8]) {
  const float lo = 5.421010862427522e-20f, hi = 1.8446744073709552e19f;
  float i0, i1; asm("rcp.approx.ftz.f32 %0, %1;" : "=f"(i0) : "f"(o[16])); asm("rcp.approx.ftz.f32 %0, %1;" : "=f"(i1) : "f"(o[18]));
  #pragma unroll
  for (int e = 0; e < 8; e++) ob[e] = pack_bf16(o[2 * e] * ((e & 1) ? i1 : i0), o[2 * e + 1] * ((e & 1) ? i1 : i0));
  return __all_sync(0xffffffffu, o[16] >= lo && o[16] <= hi && o[18] >= lo && o[18] <= hi);
}
DEVI void attn_store(const uint32_t (&ob)[8], bool ok, uint32_t st, uint32_t sb, uint32_t bar) {
  stsm_x4(ok ? st : sb + DUMP, ob[0], ob[1], ob[2], ob[3]); stsm_x4(ok ? st ^ 32 : sb + DUMP, ob[4], ob[5], ob[6], ob[7]);
  __syncwarp();
  asm volatile("{\n.reg .pred p, q;\nelect.sync _|q, 0xffffffff;\nsetp.ne.and.u32 p, %1, 0, q;\n@p mbarrier.arrive.shared::cta.b64 _, [%0];\n}" :: "r"(bar), "r"((uint32_t)ok) : "memory");
}
DEVI void attn_exact(uint32_t st, uint32_t kv, int t, bool hasprev, uint32_t bar) {
  const int lane = threadIdx.x & 31;
  #pragma unroll 1
  for (int row = ((threadIdx.x >> 5) & 3) * 16, n = 0; n < 16; n++, row++) {
    const int k1 = 256 + t * 64 + row;
    float m = -INFINITY, l = 0.f, o = 0.f;
    #pragma unroll 1
    for (int k0 = hasprev ? k1 - 255 : 256; k0 <= k1; k0 += 32) {
      const int k = min(k0 + lane, k1), r = k & 63;
      float sc = 0.f;
      #pragma unroll 1
      for (int c = 0; c < 16; c++) {
        uint32_t a = lds32(st + row * 64 + ((c * 4) ^ ((row & 6) << 3))), b = lds32(kv + (k >> 6) * 8192 + r * 64 + ((c * 4) ^ ((r & 6) << 3)));
        sc = fmaf(bf_lo(a), bf_lo(b), fmaf(bf_hi(a), bf_hi(b), sc));
      }
      float mn = fmaxf(m, sc);
      #pragma unroll 1
      for (int x = 16; x; x >>= 1) mn = fmaxf(mn, __shfl_xor_sync(0xffffffffu, mn, x));
      const float al = ex2f(m - mn), pr = ex2f(sc - mn);
      m = mn; l *= al; o *= al;
      #pragma unroll 1
      for (int q = k0; q <= min(k0 + 31, k1); q++) {
        const float z = __shfl_sync(0xffffffffu, pr, q - k0);
        uint32_t b = lds32(kv + (q >> 6) * 8192 + 4096 + (q & 63) * 64 + (((lane >> 1) * 4) ^ ((q & 6) << 3)));
        l += z; o = fmaf(z, (lane & 1) ? bf_hi(b) : bf_lo(b), o);
      }
    }
    __syncwarp();
    sts16(st + row * 64 + ((lane * 2) ^ ((row & 6) << 3)), pack_bf16(__fdividef(o, l), 0.f));
  }
  warp_signal(bar);
}

template<int K0, int K1, int DONE = 0> DEVI void exp_pv(const float (&s)[32], uint32_t (&p)[16], float (&o)[20], uint32_t vd, bool accum) {
  #pragma unroll
  for (int ks = K0; ks < K1; ks++) {
    if (ks >= DONE) {
      #pragma unroll
      for (int j = 4 * ks; j < 4 * ks + 4; j++) p[j] = pack_bf16(ex2f(s[2 * j]), ex2f(s[2 * j + 1]));
    }
    asm volatile("" : "+r"(p[4 * ks]), "+r"(p[4 * ks + 1]), "+r"(p[4 * ks + 2]), "+r"(p[4 * ks + 3]));
    wg_fence();
    wgmma_rs_n40<1>(o, p[ks * 4], p[ks * 4 + 1], p[ks * 4 + 2], p[ks * 4 + 3], mkd<HI64>(vd + VOFF(ks * 64)), ks ? 1 : accum);
  }
}
template<int K0, int K1> DEVI void exp_pv2(const float (&s)[32], const float (&sx)[32], uint32_t (&p)[16], uint32_t (&px)[16], float (&o)[20], uint32_t v0, uint32_t v4,
                  const uint32_t (&msk)[9], int tdiag) {
  #pragma unroll
  for (int ks = K0; ks < K1; ks++) {
    #pragma unroll
    for (int j = 4 * ks; j < 4 * ks + 4; j++) {
      const int c = 8 * (j >> 1) - 8 * (j & 1);
      const uint32_t e = pack_bf16(ex2f(c > tdiag ? s[2 * j] : sx[2 * j]), ex2f(c + 1 > tdiag ? s[2 * j + 1] : sx[2 * j + 1])), m = msk[(j >> 1) - (j & 1) + 1];
      p[j] = e & m; px[j] = e & ~m;
      asm volatile("" : "+r"(p[j]), "+r"(px[j]));
    }
    wg_fence();
    wgmma_rs_n40<1>(o, p[ks * 4], p[ks * 4 + 1], p[ks * 4 + 2], p[ks * 4 + 3], mkd<HI64>(v0 + VOFF(ks * 64)), 1);
    wgmma_rs_n40<1>(o, px[ks * 4], px[ks * 4 + 1], px[ks * 4 + 2], px[ks * 4 + 3], mkd<HI64>(v4 + VOFF(ks * 64)), 1);
  }
}

template<int J0> DEVI void qkv_store(const float (&a)[96], float p0, float p1, uint32_t d) {
  #pragma unroll
  for (int hh = 0; hh < 2; hh++) {
    const int j = 4 * (J0 + 2 * hh);
    stsm_x4(d ^ (hh << 5), pack_bf16(a[j] * p0, a[j + 1] * p0), pack_bf16(a[j + 2] * p1, a[j + 3] * p1),
                           pack_bf16(a[j + 4] * p0, a[j + 5] * p0), pack_bf16(a[j + 6] * p1, a[j + 7] * p1));
  }
}
DEVI void mean_step(float (&a)[96], float m0, float m1, uint32_t cd, bool z) {
  const uint32_t u0 = z ? 0u : __float_as_uint(m0), u1 = z ? 0u : __float_as_uint(m1);
  uint32_t ma[4] = {__byte_perm(u0, 0u, 0x1010), __byte_perm(u1, 0u, 0x1010), __byte_perm(u0, 0u, 0x3232), __byte_perm(u1, 0u, 0x3232)};
  keep(ma);
  wg_fence();
  wgmma_rs_n192<1>(a, ma[0], ma[1], ma[2], ma[3], mkd<2>(cd), 1);
  wg_commit();
}

template<bool FIRST> DEVI void qkv_block(float (&aX)[96], float (&aY)[96], uint32_t sb16, int s, int tX, int tY) {
  uint32_t a16 = sb16 + (qa_off(s) >> 4), b16 = (sb16 + (qb_off(s) >> 4)) | ((8192u >> 4) << 16);
  uint32_t ax = (a16 + tX * 512) | 0x10000u, ay = (a16 + tY * 512) | 0x10000u;
  wg_fence();
  #pragma unroll
  for (int ks = 0; ks < 4; ks++) {
    wgmma_ss_n192<1>(aX, mkd<HI128>(ax + ks * 2), mkd<HI128>(b16 + ks * 128), !(FIRST && ks == 0));
    wgmma_ss_n192<1>(aY, mkd<HI128>(ay + ks * 2), mkd<HI128>(b16 + ks * 128), !(FIRST && ks == 0));
  }
  wg_commit();
}
DEVI void qkv_half(float (&a)[96], uint32_t sb16, int t, uint32_t sa, uint32_t sbb) {
  wg_fence();
  #pragma unroll
  for (int ks = 0; ks < 4; ks++)
    wgmma_ss_n192<1>(a, mkd<HI128>(((sb16 + (sa >> 4) + t * 512) | 0x10000u) + ks * 2), mkd<HI128>(((sb16 + (sbb >> 4)) | ((8192u >> 4) << 16)) + ks * 128), 1);
  wg_commit();
}
DEVI void wo_block(float (&acc)[64], uint32_t sb16, int s, int wg) {
  uint32_t a16 = (sb16 + (w_off(s) >> 4) + wg * 256) | 0x10000u, b16 = (sb16 + (w_off(s) >> 4) + 1024) | ((8192u >> 4) << 16);
  wg_fence();
  #pragma unroll
  for (int ks = 0; ks < 4; ks++)
    wgmma_ss_n128<1>(acc, mkd<HI64>(a16 + (ks >> 1) * 512 + (ks & 1) * 2), mkd<HI128>(b16 + ks * 128), 1);
  wg_commit();
}
DEVI void consumer(const Params& P, uint32_t sb, int wg) {
  const int w = uni((threadIdx.x >> 5) & 3);
  #define LAYER uni(mbar_test(BAR(B_XRDY + wg * 2 + 1), 0))
  #define IDS L = LAYER; const int tid = fresh_tid(), lane = tid & 31
  const uint32_t ids = uni(P.map[blockIdx.x]);
  const int bi = (ids >> 4) & 7, rh = ids & 1, bc = (ids & 15) >> 1, fid = ids >> 8;
  const int tX = 3 - wg, tY = wg;
  constexpr uint32_t sb16 = 1024 >> 4;
  #pragma unroll 1
  while (true) {
    int L = LAYER;
    {
      float aX[96], aY[96];
      const bool lead = fresh_tid() == 0;
      mbar_wait(BAR(B_FULLQ), 0);
      PROFW(threadIdx.x == 0, L * 8 + 1);
      qkv_block<true>(aX, aY, sb16, 0, tX, tY);
      #pragma unroll 1
      for (int n = 1, s = 1, ps = 0, ph = 0; n < 14; n++) {
        mbar_wait(BAR(B_FULLQ + s), ph ^ (s ? L : 0));
        PROFD(threadIdx.x == 0 && L && (n == 2 || n == 3 || n == 7 || n == 11 || n == 13), n == 2 ? 48 : 49 + (n >> 2));
        qkv_block<false>(aX, aY, sb16, s, tX, tY);
        wg_wait<1>(); if (lead) mbar_arrive(BAR(B_EMPTYQ + ps));
        ps = s; if (s == 2) { s = 0; ph ^= 1; } else s++;
      }
      mbar_wait(BAR(B_FULLQ + 2), L);
      qkv_half(aX, sb16, tX, SA2, SB2);
      mbar_wait(BAR(B_ROW), L);
      IDS;
      const uint32_t pa = sb + PAR + (w * 16 + (lane >> 2)) * 8;
      float2 p0 = lds64f(pa + tX * 512), p1 = lds64f(pa + tX * 512 + 64), p2 = lds64f(pa + tY * 512), p3 = lds64f(pa + tY * 512 + 64);
      mean_step(aX, p0.y, p1.y, sb16 + (CS >> 4), lane & 3);
      mbar_wait(BAR(B_FULLQ), 1);
      qkv_half(aX, sb16, tX, 0, SB0);
      wg_wait<3>(); if (lead) mbar_arrive(BAR(B_EMPTYQ + 1));
      bar_sync(1, 256);
      qkv_half(aY, sb16, tY, SA2, SB2);
      wg_wait<1>(); keep(aX);
      const int srow = w * 16 + (lane & 15);
      const uint32_t x0 = sb + srow * 64 + (((lane >> 4) ^ ((srow >> 1) & 3)) << 4), xX = x0 + (4 + tX) * 8192, xY = x0 + (4 + tY) * 8192;
      qkv_store<8>(aX, p0.x, p1.x, xX + KVA); qkv_store<16>(aX, p0.x, p1.x, xX + KVA + 4096);
      warp_signal(BAR(B_KVRDY + wg * 2));
      qkv_half(aY, sb16, tY, 0, SB0);
      mean_step(aY, p2.y, p3.y, sb16 + (CS >> 4), fresh_tid() & 3);
      wg_wait<2>(); if (lead) mbar_arrive(BAR(B_EMPTYQ + 2));
      mbar_wait(BAR(B_EMPTYQ + 2), L);
      qkv_store<12>(aX, p0.x, p1.x, xX + KVB); qkv_store<20>(aX, p0.x, p1.x, xX + KVB + 4096);
      wg_wait<0>(); keep(aY);
      if (lead) mbar_arrive(BAR(B_EMPTYQ));
      PROFW(threadIdx.x == 0, L * 8 + 2);
      qkv_store<8>(aY, p2.x, p3.x, xY + KVA); qkv_store<16>(aY, p2.x, p3.x, xY + KVA + 4096);
      qkv_store<12>(aY, p2.x, p3.x, xY + KVB); qkv_store<20>(aY, p2.x, p3.x, xY + KVB + 4096);
      warp_signal(BAR(B_KVRDY + wg * 2 + 1));
      p0.x *= QSCALE; p1.x *= QSCALE; p2.x *= QSCALE; p3.x *= QSCALE;
      mbar_wait(BAR(B_EMPTYQ), 1);
      qkv_store<0>(aX, p0.x, p1.x, x0 + QO + tX * 4096);
      qkv_store<0>(aY, p2.x, p3.x, x0 + QO + tY * 4096); qkv_store<4>(aY, p2.x, p3.x, x0 + QO + 16384 + tY * 4096);
      mbar_wait(BAR(B_PAR), L);
      qkv_store<4>(aX, p0.x, p1.x, x0 + QO + 16384 + tX * 4096);
      const int prow = (int)uni(lds32(sb + INFO)) - bi * 256;
      if ((prow >> 4) == tX * 4 + w || (prow >> 4) == tY * 4 + w) {
        __syncwarp();
        if (lane < 24) sts128(sb + (prow & 63) * 64 + (((lane ^ (prow >> 1)) & 3) << 4) +
                              (lane < 8 ? QO + (lane >> 2) * 16384 + (prow >> 6) * 4096 : ((lane & 4) ? KVB : KVA) + (4 + (prow >> 6)) * 8192 + (lane >> 4) * 4096),
                              lds128(sb + PATCH + lane * 16));
      }
      fence_async_smem();
      bar_sync(1, 256);
    }
    PROFW(threadIdx.x == 0, L * 8 + 3);
    float2 fa, fb;
    { const float2* f = (const float2*)&P.g->statF[bi * 256 + rh * 128 + (wg ^ rh) * 64 + w * 16 + ((fresh_tid() & 31) >> 2)];
      fa = __ldcg(f); fb = __ldcg(f + 16); }
    {
      IDS;
      float s0[32], s1[32], sx[32], o[20], op[20];
      uint32_t p0[16], p1[16], px[16], msk[9];
      const int tdiag = w * 16 + (lane >> 2) - 2 * (lane & 3);
      #pragma unroll
      for (int e = 0; e < 9; e++) msk[e] = ((8 * e - 8 > tdiag) ? 0xFFFFu : 0u) | ((8 * e - 7 > tdiag) ? 0xFFFF0000u : 0u);
      keep(msk);
      const uint32_t ones = (sb16 + (ONES >> 4)) << 16;
      const uint32_t qX = (sb16 + (QO >> 4) + tX * 256) | 0x10000u, qY = (sb16 + (QO >> 4) + tY * 256) | 0x10000u;
      const uint32_t kXB = (sb16 + (KVB >> 4) + tX * 512) | 0x10000u;
      uint32_t redo = 0;
      const uint32_t ost = sb + QO + (w * 16 + (lane & 15)) * 64 + (((lane >> 4) ^ ((lane >> 1) & 3)) << 4);
      #define QA(s, q, k) do { wg_fence(); wgmma_ss_n64<0>(s, mkd<HI64>(q), mkd<HI64>(k), 0); } while (0)
      #define QB(s, q, k) wgmma_ss_n64<0>(s, mkd<HI64>((q) + 2), mkd<HI64>((k) + 2), 1)
      #define QA2(q, k) do { QA(s1, q, k); wgmma_ss_n64<0>(sx, mkd<HI64>(q), mkd<HI64>((k) + 2048), 0); } while (0)
      #define QB2(q, k) do { QB(s1, q, k); QB(sx, q, (k) + 2048); } while (0)
      #define VB(v, b) ((v) + VOFF((b) * 512))
      #define MID() do { wg_commit(); wg_wait<1>(); } while (0)
      QA(s0, qX + 1024, kXB + 1536); QB(s0, qX + 1024, kXB + 1536); wg_commit();
      #pragma unroll
      for (int e = 0; e < 20; e++) o[e] = 0.f;
      wg_wait<0>(); keep(s0);
      #pragma unroll 1
      for (int h = 1; h >= 0; h--) {
        const uint32_t kXA = kXB - ((KVB - KVA) >> 4), kX = h ? kXB : kXA, vX = VOFF((kX & 0xffffu) + 256) + ones;
        QA(s1, qX + h * 1024, kX + 1024);
        #pragma unroll
        for (int e = 0; e < 20; e++) op[e] = o[e];
        keep(op);
        exp_pv<0, 1>(s0, p0, o, VB(vX, 3), false); QB(s1, qX + h * 1024, kX + 1024); wg_commit();
        exp_pv<1, 2>(s0, p0, o, VB(vX, 3), true); MID(); keep(s1);
        exp_pv<2, 4>(s0, p0, o, VB(vX, 3), true);
        exp_pv<0, 2>(s1, p1, o, VB(vX, 2), true);
        bar_sync(h ? 12 + wg : 4 + wg * 4, h ? 128 : 160);
        QA(s0, qX, kXA + 512 + h * 1024);
        exp_pv<2, 3>(s1, p1, o, VB(vX, 2), true); QB(s0, qX, kXA + 512 + h * 1024);
        exp_pv<3, 4>(s1, p1, o, VB(vX, 2), true); wg_commit();
        wg_wait<0>(); keep(s0); keep(p0); keep(p1); keep(o);
      }
      #pragma unroll 1
      for (int h = 0; h < 2; h++) {
        const uint32_t kb16 = sb16 + ((h ? KVB : KVA) >> 4), kX = (kb16 + tX * 512) | 0x10000u, kY = (kb16 + tY * 512) | 0x10000u, qx = qX + h * 1024, qy = qY + h * 1024;
        const uint32_t onesP = bi ? ones : (kb16 + 1984) << 16;
        const uint32_t vX = VOFF(kb16 + tX * 512 + 256), vY = VOFF(kb16 + tY * 512 + 256);
        uint32_t ob[8], v;
        v = VB(vX + (wg ? onesP : ones), 1);
        QA2(qx, kX);
        exp_pv<0, 1>(s0, p0, o, v, true); QB2(qx, kX); wg_commit();
        exp_pv<1, 2>(s0, p0, o, v, true); MID(); keep(s1); keep(sx);
        exp_pv<2, 4>(s0, p0, o, v, true);
        QA(s0, qy, kY + 1536);
        exp_pv2<0, 1>(s1, sx, p1, px, o, vX + onesP, VB(vX + ones, 4), msk, tdiag); QB(s0, qy, kY + 1536); wg_commit();
        exp_pv2<1, 2>(s1, sx, p1, px, o, vX + onesP, VB(vX + ones, 4), msk, tdiag); MID(); keep(s0); keep(p0);
        exp_pv2<2, 4>(s1, sx, p1, px, o, vX + onesP, VB(vX + ones, 4), msk, tdiag); wg_commit();
        v = VB(vY + (wg ? ones : onesP), 3);
        QA(s1, qy, kY + 1024);
        exp_pack<0, 4>(s0, p0);
        QB(s1, qy, kY + 1024); MID(); keep(o); keep(p1); keep(px);
        bool ok = attn_pack(o, ob); keep(ob);
        exp_pv<0, 2, 1>(s0, p0, o, v, false); MID(); keep(s1);
        attn_store(ob, ok, ost + (h * 4 + tX) * 4096, sb, BAR(B_ORDY + wg * 4 + h * 2)); redo |= ok ? 0u : 1u << (h * 2);
        exp_pv<2, 4>(s0, p0, o, v, true);
        v = VB(vY + onesP, 2);
        exp_pv<0, 1>(s1, p1, o, v, true);
        bar_sync(5 + wg * 4 + h * 2, 160);
        QA(s0, qy, kY + 512);
        exp_pv<1, 2>(s1, p1, o, v, true); QB(s0, qy, kY + 512); wg_commit();
        exp_pv<2, 3>(s1, p1, o, v, true); MID(); keep(s0); keep(p0);
        exp_pv<3, 4>(s1, p1, o, v, true);
        v = VB(vY + onesP, 1);
        QA2(qy, kY);
        exp_pv<0, 1>(s0, p0, o, v, true); QB2(qy, kY); wg_commit();
        exp_pv<1, 2>(s0, p0, o, v, true); MID(); keep(s1); keep(sx); keep(p1);
        exp_pv<2, 4>(s0, p0, o, v, true);
        exp_pv2<0, 1>(s1, sx, p1, px, o, vY + onesP, VB(vY + ones, 4), msk, tdiag);
        bar_sync(6 + wg * 4, h ? 128 : 160);
        QA(s0, h ? qy : qX + 1024, kXB + 512);
        exp_pv2<1, 2>(s1, sx, p1, px, o, vY + onesP, VB(vY + ones, 4), msk, tdiag); QB(s0, h ? qy : qX + 1024, kXB + 512);
        exp_pv2<2, 4>(s1, sx, p1, px, o, vY + onesP, VB(vY + ones, 4), msk, tdiag); wg_commit();
        wg_wait<0>(); keep(o); keep(s0); keep(p0); keep(p1); keep(px);
        ok = attn_pack(o, ob); attn_store(ob, ok, ost + (h * 4 + tY) * 4096, sb, BAR(B_ORDY + wg * 4 + h * 2 + 1)); redo |= ok ? 0u : 2u << (h * 2);
        #pragma unroll
        for (int e = 0; e < 20; e++) o[e] = op[e];
      }
      #undef QA
      #undef QB
      #undef QA2
      #undef QB2
      #undef VB
      #undef MID
      if (redo) {
        #pragma unroll 1
        for (int u = 0; u < 4; u++) if ((redo >> u) & 1) {
          const int h = u >> 1, t = (u & 1) ? tY : tX;
          attn_exact(sb + QO + (h * 4 + t) * 4096, sb + (h ? KVB : KVA), t, bi > 0, BAR(B_ORDY + wg * 4 + u));
        }
      }
    }
    PROFW(threadIdx.x == 0, L * 8 + 4);
    {
      IDS;
      const int t256 = wg * 128 + tid;
      float acc[64];
      const int tt = wg ^ rh;
      const int grow = bi * 256 + rh * 128 + tt * 64 + w * 16 + (lane >> 2);
      float al0 = 1.f, be0 = 0.f, al1 = 1.f, be1 = 0.f;
      const int idx0 = (int)uni(lds32(sb + INFO));
      const uint32_t tag = lds32(sb + INFO + 8) + L;
      uint4* const sp = &P.g->statP[bc][grow + (lane & 1) * 8];
      uint4* const yp = &P.g->yP[t256 >> 1][min(fid, 111)][t256 & 1];
      if (L) {
        float r0 = rsqrtf(fa.y + LN_EPS), r1 = rsqrtf(fb.y + LN_EPS);
        if (grow != idx0) { al0 = 1.f + r0; be0 = -fa.x * r0; }
        if (grow + 8 != idx0) { al1 = 1.f + r1; be1 = -fb.x * r1; }
      }
      const int srow = tt * 64 + w * 16 + (lane & 15);
      const uint32_t ra = sb + srow * 128 + (((lane >> 4) ^ (srow & 7)) << 4);
      mbar_wait(BAR(B_FULLW + 5), L);
      if ((idx0 >> 4) == bi * 16 + rh * 8 + tt * 4 + w) {
        int r = idx0 & 127;
        if (lane < 16) sts128(sb + 32768 + (lane >> 3) * 16384 + r * 128 + (((lane & 7) ^ (r & 7)) << 4), lds128(sb + X2SEG + lane * 16));
        fence_async_smem();
        __syncwarp();
      }
      #pragma unroll
      for (int jj = 0; jj < 8; jj++) {
        uint32_t r[4]; ldsm_x4((ra + 32768 + (jj >> 2) * 16384) ^ ((jj & 3) << 5), r[0], r[1], r[2], r[3]);
        #pragma unroll
        for (int e = 0; e < 4; e++) {
          acc[8 * jj + 2 * e] = fmaf(bf_lo(r[e]), (e & 1) ? al1 : al0, (e & 1) ? be1 : be0);
          acc[8 * jj + 2 * e + 1] = fmaf(bf_hi(r[e]), (e & 1) ? al1 : al0, (e & 1) ? be1 : be0);
        }
      }
      keep(acc);
      bar_sync(12 + wg, 128);
      if (!(lane & 2)) st_ll(sp, 0u, 0u, 0u, 0u);
      uint2 wd[4];
      #pragma unroll
      for (int e = 0; e < 4; e++) { wd[e] = make_uint2(0u, 0u); if (L) wd[e] = ldg_stream((const uint2*)(WDSRC) + t256 + (28 + e) * 256); }
      PROFW(t256 == 0, L * 8 + 5);
      #pragma unroll 1
      for (int n = 0, q = 0, pq = 5; n < 16; n++) {
        mbar_wait(BAR(B_FULLW + q), w_par(n, q, L));
        PROFD(t256 == 0 && !L && (n == 4 || n == 7 || n == 8 || n == 12), (n == 7 ? 63 : 41 + (n >> 2)));
        wo_block(acc, sb16, q, tt);
        wg_wait<1>(); if (tid == 0) mbar_arrive(BAR(B_EMPTYW + pq));
        pq = q; q = w_next(n, q);
      }
      mbar_wait(BAR(B_EMPTYW + 5), L);
      wg_wait<0>(); keep(acc);
      if (tid == 0) mbar_arrive(BAR(B_EMPTYW + 4));
      PROFW(t256 == 0, L * 8 + 6);
      {
        float s1a = 0.f, s2a = 0.f, da = 0.f, s1b = 0.f, s2b = 0.f, db = 0.f;
        #pragma unroll
        for (int j = 0; j < 16; j++) {
          const float* a = acc + 4 * j; float2 wv = lds64f(sb + WR + j * 32 + (lane & 3) * 8);
          s1a += a[0] + a[1]; s1b += a[2] + a[3];
          s2a = fmaf(a[0], a[0], s2a); s2b = fmaf(a[2], a[2], s2b); s2a = fmaf(a[1], a[1], s2a); s2b = fmaf(a[3], a[3], s2b);
          da = fmaf(a[0], wv.x, da); db = fmaf(a[2], wv.x, db); da = fmaf(a[1], wv.y, da); db = fmaf(a[3], wv.y, db);
        }
        bool odd = lane & 1;
        float u1 = (odd ? s1b : s1a) + __shfl_xor_sync(0xffffffffu, odd ? s1a : s1b, 1);
        float u2 = (odd ? s2b : s2a) + __shfl_xor_sync(0xffffffffu, odd ? s2a : s2b, 1);
        float u3 = (odd ? db : da) + __shfl_xor_sync(0xffffffffu, odd ? da : db, 1);
        u1 += __shfl_xor_sync(0xffffffffu, u1, 2); u2 += __shfl_xor_sync(0xffffffffu, u2, 2); u3 += __shfl_xor_sync(0xffffffffu, u3, 2);
        if (!(lane & 2)) st_ll(sp, __float_as_uint(u1), __float_as_uint(u2), __float_as_uint(u3), tag);
      }
      const uint32_t xa = ra + rh * 16384;
      #pragma unroll
      for (int jj = 0; jj < 8; jj++) {
        const float* a = acc + 8 * jj;
        stsm_x4((xa + (jj >> 2) * 32768) ^ ((jj & 3) << 5), pack_bf16(a[0], a[1]), pack_bf16(a[2], a[3]), pack_bf16(a[4], a[5]), pack_bf16(a[6], a[7]));
        if (jj == 7) fence_async_smem();
        if ((jj & 3) == 3) warp_signal(BAR(B_XRDY + wg * 2 + (jj >> 2)));
      }
      PROFW(t256 == 0, L * 8 + 7);
      if (L) {
        mbar_wait(BAR(B_PAR), 0);
        { float2 pa = lds64f(sb + PAR + (grow & 127) * 8), pb = lds64f(sb + PAR + (grow & 127) * 8 + 64); al0 = pa.x; be0 = pa.y; al1 = pb.x; be1 = pb.y; }
        uint32_t rs[32];
        #pragma unroll
        for (int j = 0; j < 16; j++) {
          rs[2 * j] = pack_bf16(fmaf(acc[4 * j], al0, be0), fmaf(acc[4 * j + 1], al0, be0));
          rs[2 * j + 1] = pack_bf16(fmaf(acc[4 * j + 2], al1, be1), fmaf(acc[4 * j + 3], al1, be1));
        }
        #pragma unroll
        for (int jj = 0; jj < 8; jj++) stsm_x4((xa + (jj >> 2) * 32768) ^ ((jj & 3) << 5), rs[4 * jj], rs[4 * jj + 1], rs[4 * jj + 2], rs[4 * jj + 3]);
        PROFW(t256 == 0, 16);
        if (fid >= 112) bar_arrive(3, 384);
        else {
          float d[4] = {0.f, 0.f, 0.f, 0.f};
          mbar_wait(BAR(B_FULLW + wg * 3), 0); mbar_wait(BAR(B_FULLW + wg * 3 + 1), 0);
          bar_sync(3, 384);
          PROFW(t256 == 0, 29);
          #pragma unroll 1
          for (int g = 0; g < 4; g++) {
            const uint32_t ad = (sb16 + (wg ? 6144 : 10240) + (g >> 1) * 2048 + (g & 1) * 512) | (1024u << 16), bd = (sb16 + (HV >> 4) + wg * 64 + g * 16) | 0x10000u;
            wg_fence();
            #pragma unroll
            for (int ks = 0; ks < 8; ks++) wgmma_ss_n8<0, 1>(d, mkd<HI64>(ad + ks * 64), mkd<8>(bd + ks * 2), 1);
            wg_commit();
          }
          mbar_wait(BAR(B_FULLW + 2), 0);
          wg_wait<0>(); keep(d);
          if (!(lane & 3)) { sts32f(sb + PAR + 1024 + wg * 256 + w * 64 + lane, d[0]); sts32f(sb + PAR + 1056 + wg * 256 + w * 64 + lane, d[2]); }
          bar_sync(1, 256);
          const uint32_t ga = sb + PAR + 1024 + lane * 4, aa = sb + HV + (t256 >> 5) * 128;
          sts32f(aa + lane * 4, swiglu(lds32f(ga) + lds32f(ga + 256), lds32f(ga + 128) + lds32f(ga + 384)));
          __syncwarp();
          PROFW(t256 == 0, 26);
          float y0 = 0.f, y1 = 0.f, y2 = 0.f, y3 = 0.f;
          uint32_t tbl = rh ? 0x001459a8u : 0x023679a8u;
          uint4 a4 = lds128(aa + 112);
          #pragma unroll 2
          for (int n = 0; n < 8; n++, tbl >>= 4) {
            const uint32_t src = sb + t256 * 8 + (tbl & 15) * 8192;
            const uint4 an = lds128(aa + ((0x00123564u >> (4 * n)) & 15) * 16);
            #pragma unroll
            for (int e = 0; e < 4; e++) {
              const float av = __uint_as_float(e == 0 ? a4.x : (e == 1 ? a4.y : (e == 2 ? a4.z : a4.w)));
              y0 = fmaf(bf_lo(wd[e].x), av, y0); y1 = fmaf(bf_hi(wd[e].x), av, y1); y2 = fmaf(bf_lo(wd[e].y), av, y2); y3 = fmaf(bf_hi(wd[e].y), av, y3);
              const float2 v = lds64f(src + e * 2048); wd[e] = make_uint2(__float_as_uint(v.x), __float_as_uint(v.y));
            }
            a4 = an;
          }
          st_ll(yp, __float_as_uint(y0), __float_as_uint(y1), __float_as_uint(y2), (__float_as_uint(y3) & ~255u) | (lds32(sb + INFO + 12) + 1));
          PROFW(t256 == 0, 27);
        }
        return;
      }
      mbar_wait(BAR(B_XRDY + wg * 2 + 1), 0);
    }
  }
  #undef IDS
  #undef LAYER
}

DEVI void loader(const Params& P, uint32_t sb) {
  const int lane = threadIdx.x & 31;
  const int bid = uni(BID), bi = bid >> 4, bp = bid & 15, rh = bp & 1, bc = bp >> 1;
  uint32_t phq = 0, tag = 0;
  #pragma unroll 1
  for (int L = 0; L < 2; L++) {
    int s = 0;
    uint32_t rdy = 0;
    #pragma unroll 1
    for (int n = L ? 0 : 3; n < 16; n++) {
      int kb = L ? kb_order(bc, n) : n;
      mbar_wait(BAR(B_EMPTYQ + s), (phq >> s) & 1);
      phq ^= 1u << s;
      if (L && n == 1) { mbar_wait(BAR(B_XRDY + 1), 0); mbar_wait(BAR(B_XRDY + 3), 0); }
      if (elect()) {
        mbar_expect_tx(BAR(B_FULLQ + s), L && n < 2 ? 40960 : 57344);
        tma_3d_h(sb + qb_off(s), &P.mWq, bp * 64, kb * 64, 0, BAR(B_FULLQ + s), L && n >= QEF_N ? POL_FIRST : POL_NORMAL);
        if (!L) tma_2d(sb + qa_off(s), &P.mX, kb * 64, bi * 256, BAR(B_FULLQ + s));
      }
      if (L && n >= 2) {
        if (((rdy >> (2 * kb)) & 3) != 3) {
          do { rdy = __ballot_sync(0xffffffffu, ld_rlx(&P.g->flagX[bi][lane]) == tag); } while (((rdy >> (2 * kb)) & 3) != 3);
          fence_async_glob();
        }
        if (n == 3 || n == 4) mbar_wait(BAR(B_XFREE + n - 3), 0);
        if (elect()) bulk_g2s_h(sb + qa_off(s), P.g->x[bi][kb], 32768, BAR(B_FULLQ + s), POL_X);
      }
      PROFY(L && lane == 0 && (n == 2 || n == 3 || n == 9), n == 9 ? 60 : 56 + n);
      if (L && n == 2) { mbar_wait(BAR(B_FULLQ), 0); mbar_wait(BAR(B_FULLQ + 1), 1); if (lane < 2) mbar_arrive_peer(BAR(B_XFREE + lane)); }
      s = (s == 2) ? 0 : s + 1;
    }
    for (int q = 0; q < 3; q++) mbar_wait(BAR(B_EMPTYQ + q), (phq >> q) & 1);
    tag = lds32(sb + INFO + 8) + L;
    #pragma unroll 1
    for (int q = 0; q < 4; q++) {
            if (bi) {
        const unsigned* f = &P.g->flagKV[bid - 16][q];
        while (ld_rlx(f) != tag);
        fence_async_glob();
      }
      if (elect()) {
        mbar_expect_tx(BAR(B_KVFULL + q), 16384);
        bulk_g2s_h(sb + ((q >> 1) ? KVB : KVA) + ((q & 1) ? 0 : 16384), bi ? P.g->kv[bid - 16][q] : P.g->zero, 16384, BAR(B_KVFULL + q), L ? POL_KV1 : POL_KV0);
      }
      PROFY(!L && lane == 0 && bi && q != 2, 34 + (q + 1) / 2);
    }
    mbar_wait(BAR(B_ORDY), L);
    {
      const uint4* src = P.g->o[bi][0][0][rh];
      rdy = 0;
      #pragma unroll 1
      for (int n = 0, q = 0; n < 16; q = w_next(n, q), n++) {
        const int j = wo_order(bc, n);
        if (((rdy >> (2 * j)) & 3) != 3) {
          do { rdy = __ballot_sync(0xffffffffu, ld_rlx(&P.g->flagO[bi][lane]) == tag); } while (((rdy >> (2 * j)) & 3) != 3);
          fence_async_glob();
        }
        if (n >= 2) mbar_wait(n < 5 ? BAR(B_HAFREE + (n > 2)) : BAR(B_EMPTYW + q), n < 5 ? L : w_par(n, q, L) ^ 1);
        if (n == THR_N) mbar_wait(BAR(B_OFREE), L);
        if (elect()) { mbar_expect_tx(BAR(B_FULLW + q), 16384); bulk_g2s_h(sb + w_off(q), src + j * 2048, 16384, BAR(B_FULLW + q), L ? POL_O1 : POL_O0); }
      }
    }
    mbar_wait(BAR(B_OFREE), L);
  }
}

DEVI void ffn_prefetch(const Params& P, int q) {
  bulk_prefetch(q < 16 ? ((q & 1) ? P.wu : P.wg) + ((q >> 1) * 128 + blockIdx.x) * 3584 : P.wd + (min(FID, 111) * 8 + q - 16) * 4096, q < 16 ? 7168 : 8192);
}
DEVI void storer(const Params& P, uint32_t sb, int wg) {
  const int bid = uni(BID), bi = bid >> 4, rh = bid & 1, bc = (bid & 15) >> 1;
  const bool one = (threadIdx.x & 31) == 0;
  char* const g = (char*)P.g;
  const uint32_t tag0 = uni(((ld_rlx(&P.g->epoch) % 16383u) + 1u) << 2);
  #pragma unroll 1
  for (int L = 0; L < 2; L++) {
    const uint32_t tag = tag0 + L;
    if (wg) {
      #pragma unroll 1
      for (int r = threadIdx.x & 31; r < 256; r += 32) {
        uint4 v;
        do v = ld_ll(&P.g->statF[bi * 256 + r]); while (!__all_sync(0xffffffffu, v.w == tag));
        float var = __uint_as_float(v.y), c = rsqrtf(var + LN_EPS);
        if (L) { c += 1.f; c *= rsqrtf(fmaf(var * c, c, LN_EPS)); }
        const float mh = bf_round(__uint_as_float(v.x));
        sts64f(sb + PAR + r * 8, c, __uint_as_float(pack_bf16(mh, __uint_as_float(v.x) - mh)));
      }
      if (!L) mbar_wait(BAR(B_PAR), 0);
      warp_signal(BAR(B_ROW));
    }
    #pragma unroll 1
    for (int u = 0; u < 2 + 4 * wg; u++) {
      const int h = u < 2 ? u : u >> 2, hi = (u & 1) ^ 1;
      uint32_t src, dst, fl, b0, b1;
      if (u < 2) {
        src = (h ? KVB : KVA) + (3 - wg) * 16384; dst = offsetof(Scratch, kv) + (bid * 4 + h * 2 + wg) * 16384; fl = offsetof(Scratch, flagKV) + (bid * 32 + h * 2 + wg) * 4;
        b0 = BAR(B_KVRDY + ((u | wg) ? 1 : 0)); b1 = b0 + 16;
      } else {
        src = QO + (h * 2 + hi) * 8192; dst = offsetof(Scratch, o) + ((((bi * 2 + h) * 8 + bc) * 2 + hi) * 2 + rh) * 8192;
        fl = offsetof(Scratch, flagO) + (bi * 32 + h * 16 + (bid & 15)) * 4;
        b0 = BAR(B_ORDY + u - 2); b1 = b0 + 32;
      }
      mbar_wait(b0, L); mbar_wait(b1, L);
      if (u + wg == 1) {
        mbar_wait(BAR(B_PAR), L);
        const uint32_t t0 = clk(), dt = (wg ? KV_D1 : KV_D2) + (L ? KV_DL : 0); while (clk() - t0 < dt) __nanosleep(40);
      }
      fence_async_smem();
      PROFY(one && !L && u == 3 * wg, u ? 46 : 8);
      if (one && (u >= 2 || bi < 7)) bulk_s2g(g + dst, sb + src, u < 2 ? 16384 : 8192, ((ST_M >> (L * 2 + (u >= 2))) & 1) ? POL_FIRST : POL_NORMAL);
      if (one && u == 5) mbar_arrive(BAR(B_HAFREE + 1));
      if (u == 2 || u == 4) continue;
      bulk_wait<0>();
      PROFY(one && !L && u == 3 * wg, u ? 61 : 62);
      fence_rel();
      if (one) { st_rlx((unsigned*)(g + fl), tag); if (!wg || u > 2) mbar_arrive(BAR(B_HAFREE + h + (wg & h))); }
      PROFY(one && !L && (u > 2 || u == wg), u > 2 ? (u == 3 ? 38 : 54) : 32 + u);
    }
    if (L == 0) {
      char* dst = g + (offsetof(Scratch, x) + (bi * 16 + 2 * bc) * 32768 + rh * 16384);
      unsigned* f = (unsigned*)(g + (offsetof(Scratch, flagX) + (bi * 32 + bc * 4 + rh) * 4));
      const uint32_t a = sb + rh * 16384;
      if (wg == 0) {
        mbar_wait(BAR(B_XRDY), 0); mbar_wait(BAR(B_XRDY + 2), 0);
        fence_async_smem();
        PROFY(one, 41);
        if (one) bulk_s2g(dst, a, 16384);
        bulk_wait<0>();
        PROFY(one, 45);
        if (one) { mbar_arrive(BAR(B_XFREE)); mbar_arrive(BAR(B_PFREE)); }
        fence_rel();
        mbar_wait(BAR(B_XRDY + 1), 0); mbar_wait(BAR(B_XRDY + 3), 0);
        if (one) { st_rlx(f, tag); bulk_s2g(dst + 32768, a + 32768, 16384); }
        PROFY(one, 56);
        bulk_wait<0>();
        if (one) mbar_arrive(BAR(B_XFREE + 1));
        fence_rel();
        if (one) st_rlx(f + 2, tag);
        PROFY(one, 57);
      } else {
        mbar_wait(BAR(B_XRDY + 1), 0); mbar_wait(BAR(B_XRDY + 3), 0);
        mbar_wait(BAR(B_PFREE), 0);
        if (one) bulk_s2peer(a, 16384, BAR(B_FULLQ));
        { const uint32_t t0 = clk(); while (clk() - t0 < XD_D); }
        if (one) bulk_s2peer(a + 32768, 16384, BAR(B_FULLQ + 1));
      }
      if (wg == 0) {
        uint32_t t0 = clk() + PF1_D;
        #pragma unroll 1
        for (int q = PF1_S; q < PF1_E; q++) { while ((int)(clk() - t0) < 0) __nanosleep(50); if (one) ffn_prefetch(P, q); t0 += PF1_T; }
      }
    }
  }
}

DEVI void stg_issue(const Params& P, int c, uint32_t d, uint32_t du, uint32_t b) {
  mbar_expect_tx(b, 16384);
  if (c < 8) { tma_2d_h(d, &P.mWg, FID * 32, c * 128, b, du > 8192 ? POL_T : POL_G); tma_2d_h(d + du, &P.mWu, FID * 32, c * 128, b, du > 8192 || c < U_C ? POL_FIRST : POL_NORMAL); }
  else if (c < 12) tma_3d_h(d, &P.mWd, 0, FID * 32 + (c - 8) * 8, 0, b, POL_D);
  else tma_2d_h(d, &P.mWp, (c - 12) * 1024 + (BID >> 2) * 32, (BID & 3) * 256, b, POL_EF);
}
DEVI void pace() { const uint32_t t0 = clk(); while (clk() - t0 < PACE_T); }
DEVI void stager(const Params& P, uint32_t sb) {
  {
    const int b = blockIdx.x;
    uint32_t t0 = clk();
    #pragma unroll 1
    for (int q = 0; q < PQ_N; q++) { bulk_prefetch(P.wqkv + (q * 128 + b) * 3072, 6144); while (clk() - t0 < PQ_T) __nanosleep(50); t0 += PQ_T; }
    bulk_prefetch(P.wo + b * 8192, 16384);
    #pragma unroll 1
    for (int q = 0; q < PF0_N; q++) {
      while (clk() - t0 < PF0_T) __nanosleep(50);
      t0 += PF0_T;
      ffn_prefetch(P, q);
    }
  }
  const int bid = BID, bi = bid >> 4, rh = bid & 1, bc = (bid & 15) >> 1;
  #pragma unroll 1
  for (int L = 0; L < 2; L++) {
    const int nch = L ? (FID < 112 ? 8 : 0) : 15;
    mbar_wait(BAR(B_PAR), L); mbar_wait(BAR(B_KVFULL + W0_BAR), L);
    #pragma unroll 1
    for (int n = 0, q = 0; n < 16; q = w_next(n, q), n++) {
      if (n >= 2) mbar_wait(n < 5 ? BAR(B_HAFREE + (n > 2)) : BAR(B_EMPTYW + q), n < 5 ? L : w_par(n, q, L) ^ 1);
      if (n == THR_N) mbar_wait(BAR(B_OFREE), L);
      mbar_expect_tx(BAR(B_FULLW + q), 16384);
      tma_5d(sb + w_off(q) + 16384, &P.mWo, 0, 0, n >> 3, 2 * (wo_order(bc, n) & 7), 2 * bc, BAR(B_FULLW + q), L ? POL_W1 : POL_W0);
      if (n == 2) {
        #pragma unroll 1
        for (int e = 0; e < 2; e++) {
          mbar_expect_tx(BAR(B_FULLW + 5), 16384);
          if (L) bulk_g2s_h(sb + 32768 + e * 16384, P.g->x[bi][2 * bc + e] + rh * 1024, 16384, BAR(B_FULLW + 5));
          else tma_2d_h(sb + 32768 + e * 16384, &P.mXh, bc * 128 + e * 64, bi * 256 + rh * 128, BAR(B_FULLW + 5), POL_EF);
        }
      }
    }
    mbar_wait(BAR(B_EMPTYW + 5), L);
    if (L && nch) {
      const bf16* src = WDSRC2;
      mbar_expect_tx(BAR(B_FULLW + 2), 32768); mbar_expect_tx(BAR(B_FULLW + 2), 24576);
      #pragma unroll 1
      for (int e = 0; e < 3; e++) { bulk_g2s_h(sb + e * 32768 + (e < 2 ? (rh ^ 1) * 16384 : 0), src + e * 8192, e < 2 ? 16384 : 24576, BAR(B_FULLW + 2)); pace(); }
    }
        if (L == 0) { mbar_arrive_peer(BAR(B_PFREE)); mbar_wait(BAR(B_EMPTYW), 0); mbar_wait(BAR(B_EMPTYW + 1), 0); }
    #pragma unroll 1
    for (int c = FID < 112 ? 0 : 12, slot = 0; c < nch; c++, slot = slot == 2 ? 0 : slot + 1) {
      const int q = (c >> 1) + (c >> 2);
      if (!L && (c == LATE_C || c == 12)) mbar_wait(BAR(LATE_B), LATE_P);
      mbar_wait(L ? BAR(B_EMPTYW + q) : BAR(B_STGE + slot), L | ((0x71c7 >> c) & 1));
      #define CC c
      stg_issue(P, CC, L ? sb + w_off(q) + (c & 1) * 8192 : sb + STG + slot * 16384, 8192 << L, L ? BAR(B_FULLW + q) : BAR(B_STG + slot));
      if (L) pace();
    }
  }
}
DEVI void sum8(uint4 v, float& s1, float& s2) {
  float e[8] = {bf_lo(v.x), bf_hi(v.x), bf_lo(v.y), bf_hi(v.y), bf_lo(v.z), bf_hi(v.z), bf_lo(v.w), bf_hi(v.w)};
  #pragma unroll
  for (int q = 0; q < 8; q++) { s1 += e[q]; s2 = fmaf(e[q], e[q], s2); }
}
DEVI uint4 norm8(uint4 x, float m, float rs) {
  #define HN(v) pack_bf16((bf_lo(v) - m) * rs, (bf_hi(v) - m) * rs)
  return make_uint4(HN(x.x), HN(x.y), HN(x.z), HN(x.w));
  #undef HN
}
DEVI void put_f32(uint4 b, uint32_t d, uint32_t d2) {
  sts128(d, make_uint4(b.x << 16, b.x & 0xffff0000u, b.y << 16, b.y & 0xffff0000u));
  sts128(d + d2, make_uint4(b.z << 16, b.z & 0xffff0000u, b.w << 16, b.w & 0xffff0000u));
}
DEVI void put_bf16(uint4 b, uint32_t d) {
  sts64f(d, __uint_as_float(b.x), __uint_as_float(b.y)); sts64f(d + 1024, __uint_as_float(b.z), __uint_as_float(b.w));
  fence_async_smem();
}
DEVI uint4 best4(uint32_t p) {
  uint4 a = lds128(p), b = lds128(p + 16), c = lds128(p + 32), d = lds128(p + 48);
  if (b.x > a.x) a = b;
  if (d.x > c.x) c = d;
  return c.x > a.x ? c : a;
}
#define FL(x) __uint_as_float(x)
#define UI(x) __float_as_uint(x)
DEVI void aux(const Params& P, uint32_t sb) {
  int tid = fresh_tid();
  #define lane (tid & 31)
  #define wq (tid >> 5)
  uint32_t ids = P.map[blockIdx.x], tag;
  #define bid ((int)(ids & 255))
  #define fid ((int)(ids >> 8))
  #define bi (bid >> 4)
  #define bp (bid & 15)
  #define bc (bp >> 1)
  #define FRESH() do { tid = fresh_tid(); uint4 z_ = ldsv128(sb + INFO2 + 16); ids = z_.y; tag = z_.z + L; idx = z_.w; } while (0)
  {
    const uint32_t epoch = ld_rlx(&P.g->epoch);
    if (tid == 0) {
      mbar_expect_tx(BAR(B_STG), 49152);
      tma_3d(sb + STG, &P.mWq, bp * 64, bi * 128, 0, BAR(B_STG));
      tma_3d(sb + STG + 24576, &P.mWq, bp * 64, bi * 128 + 64, 0, BAR(B_STG));
    }
    __syncwarp();
    sts64f(sb + ONES + tid * 8, FL(0x3F803F80u), FL(0x3F803F80u));
    float s1 = 0.f, s2 = 0.f;
    { uint4 v = __ldg((const uint4*)P.wr + tid);
      if ((tid >> 4) == bc) put_f32(v, sb + WR + (tid & 15) * 32, 16);
      sum8(v, s1, s2);
      #pragma unroll 1
      for (int o = 16; o; o >>= 1) s1 += __shfl_xor_sync(0xffffffffu, s1, o);
      sts32f(sb + INFO2 + wq * 4, s1); }
    const uint4* src = (const uint4*)(P.x0 + (size_t)bid * 16384) + (tid >> 3) * 128 + (tid & 7);
    s1 = 0.f; s2 = 0.f;
    #pragma unroll 1
    for (int it = 0; it < 16; it += 4) {
      uint4 v0 = __ldg(src + it * 8), v1 = __ldg(src + it * 8 + 8), v2 = __ldg(src + it * 8 + 16), v3 = __ldg(src + it * 8 + 24);
      #pragma unroll 1
      for (int q = 0; q < 4; q++) { sum8(v0, s1, s2); v0 = v1; v1 = v2; v2 = v3; }
    }
    #pragma unroll 1
    for (int o = 1; o < 8; o <<= 1) { s1 += __shfl_xor_sync(0xffffffffu, s1, o); s2 += __shfl_xor_sync(0xffffffffu, s2, o); }
    tag = ((epoch % 16383u) + 1u) << 2;
    if (tid == 0) { sts128(sb + INFO, make_uint4(0x40000000u, 0u, tag, ((epoch % 127u) + 1u) << 1)); sts128(sb + INFO2 + 16, make_uint4(epoch, ids, tag, 0x40000000u)); }
    float m = s1 * (1.f / 1024.f);
    if ((tid & 7) == 0) st_ll(&P.g->statF[bid * 16 + (tid >> 3)], UI(m), UI(fmaxf(fmaf(-m, m, s2 * (1.f / 1024.f)), 0.f)), 0u, tag);
    bar_sync(2, 128);
    mbar_wait_b(BAR(B_STG), 0);
    if (tid < 96) {
      s1 = 0.f; s2 = 0.f;
      #pragma unroll 1
      for (int r = 0; r < 16; r++) {
        const uint32_t a = sb + STG + (r >> 3) * 24576 + wq * 8192 + (r & 7) * 128 + ((lane * 4) ^ ((r & 7) << 4));
        #pragma unroll
        for (int e = 0; e < 8; e++) { uint32_t v = lds32(a + e * 1024); s1 += bf_lo(v); s2 += bf_hi(v); }
      }
      st_ll(&P.g->csP[bp][bi][tid], UI(s1), UI(s2), 0u, tag);
      s1 = 0.f; s2 = 0.f;
      #pragma unroll 1
      for (int q = 0; q < 8; q += 2) {
        uint4 a, b; poll_ll2(&P.g->csP[bp][q][tid], &P.g->csP[bp][q + 1][tid], 0xffffffffu, tag, a, b);
        s1 += FL(a.x) + FL(b.x); s2 += FL(a.y) + FL(b.y);
      }
      const uint32_t hi = pack_bf16(-s1, -s2);
      sts32(sb + CS + (tid >> 2) * 32 + (tid & 3) * 4, hi);
      sts32(sb + CS + (tid >> 2) * 32 + (tid & 3) * 4 + 16, pack_bf16(-s1 - bf_lo(hi), -s2 - bf_hi(hi)));
    }
    fence_async_smem();
  }
  int idx;
  #pragma unroll 1
  for (int L = 0; L < 2; L++) {
    FRESH();
    {
      if ((unsigned)(bi - (idx >> 8)) < 2u) {
        const uint4* src = &P.g->patch[bp * 8 + (tid >> 6) * 4][tid & 63];
        const float4 z = poll_sum4(src, 64, tag);
        float q = z.x, k = z.y, v = z.z;
        q += __shfl_xor_sync(0xffffffffu, q, 1); k += __shfl_xor_sync(0xffffffffu, k, 1); v += __shfl_xor_sync(0xffffffffu, v, 1);
        bar_sync(2, 128);
        const uint32_t d = sb + PATCH + (tid & ~1), kv = pack_bf16(k, v);
        sts16(d, pack_bf16(q * QSCALE, 0.f)); sts16(d + 128, kv); sts16(d + 256, kv >> 16);
      }
      sts32(sb + INFO, idx);
      bar_sync(2, 128);
    }
    const uint4 fix = lds128(sb + PATCH + 128 + (lane & 4) * 32 + (wq >> 1) * 64 + (lane & 3) * 16);
    warp_signal(BAR(B_PAR));
    PROFX(tid == 0, L ? 23 : 17);
    mbar_wait_b(BAR(B_KVFULL + wq), L);
    if ((idx >> 7) == bi * 2 - 1 - (wq & 1)) {
      if (lane < 8) sts128(sb + ((wq >> 1) ? KVB : KVA) + ((idx >> 6) & 3) * 8192 + (lane >> 2) * 4096 + (idx & 63) * 64 + (((lane ^ (idx >> 1)) & 3) << 4), fix);
      fence_async_smem();
    }
    bar_arrive(4 + wq, 160); bar_arrive(8 + wq, 160);
    FRESH();
    mbar_wait_b(BAR(B_OFREE), L);
    #define blk (bi * 2 + (bid & 1))
    if (tid < 33) st_ll(tid < 32 ? &P.g->row[blk][bc * 32 + tid] : &P.g->best[bc][blk], 0u, 0u, 0u, 0u);
    mbar_wait_b(BAR(B_XRDY), L);
    PROFX(tid == 0, 37 + L * 16);
    FRESH();
    {
      float s1 = 0.f, s2 = 0.f, d = 0.f;
      #pragma unroll 1
      for (int q = 0; q < 8; q += 4) { const float4 v = poll_sum4(&P.g->statP[q][blk * 128 + tid], 2048, tag); s1 += v.x; s2 += v.y; d += v.z; }
      PROFX(tid == 0, 39 + L * 16);
      uint4 a = lds128(sb + INFO2), b, c;
      float m = s1 * (1.f / 1024.f), var = fmaxf(fmaf(-m, m, s2 * (1.f / 1024.f)), 0.f), rs = rsqrtf(var + LN_EPS);
      uint32_t key = UI(fmaf(-m, (FL(a.x) + FL(a.y)) + (FL(a.z) + FL(a.w)), d) * rs);
      key ^= (uint32_t)((int)key >> 31) | 0x80000000u;
      uint32_t win = __ballot_sync(0xffffffffu, key == __reduce_max_sync(0xffffffffu, key));
      if (lane == __ffs(win) - 1) sts128(sb + RED + wq * 16, make_uint4(key, UI(m), UI(rs), (tag << 11) | (uint32_t)(blk * 128 + tid)));
      if (L) sts64f(sb + PAR + tid * 8, 1.f + rs, -m * rs);
      else if ((tid >> 4) == bc) st_ll(&P.g->statF[blk * 128 + tid], UI(m), UI(var), 0u, tag + 1);
      bar_sync(2, 128);
      if (wq == 0) {
        mbar_wait(BAR(B_XRDY + 1), L); mbar_wait(BAR(B_XRDY + 3), L);
        a = best4(sb + RED);
        float2 v = lds64f(sb + (lane >> 4) * 32768 + (a.w & 255) * 128 + (((lane & 15) * 8) ^ ((a.w & 7) << 4)));
        st_ll(&P.g->row[blk][bc * 32 + lane], UI(v.x), UI(v.y), 0u, tag);
        if (lane == 0) st_ll(&P.g->best[bc][blk], a.x, a.y, a.z, a.w);
        __syncwarp();
        if (lane < 2 + 2 * L) mbar_arrive(L ? BAR(B_PAR) : BAR(B_XFREE + lane));
      }
      PROFX(tid == 0, 18 + L * 6);
      FRESH();
      a = poll_ll(&P.g->best[bc][lane & 15], 0xfffff800u, tag << 11);
      win = __ffs(__ballot_sync(0xffffffffu, a.x == __reduce_max_sync(0xffffffffu, a.x))) - 1;
      idx = __shfl_sync(0xffffffffu, a.w, win) & 2047;
      PROFX(tid == 0, 19 + L * 6);
      poll_ll2(&P.g->row[win][tid], &P.g->row[win][tid + 128], 0xffffffffu, tag, c, b);
      c.z = b.x; c.w = b.y;
      a.x = __shfl_sync(0xffffffffu, a.x, win); a.y = __shfl_sync(0xffffffffu, a.y, win); a.z = __shfl_sync(0xffffffffu, a.z, win);
      sts32(sb + INFO2 + 28, idx);
      PROFX(tid == 0, 61 + L);
      b = norm8(c, FL(a.y), FL(a.z));
      if (L) put_bf16(b, sb + HV + tid * 8); else put_f32(b, sb + HV + tid * 16, 2048);
      if ((tid >> 1) == (bid & 63)) {
        sts128(sb + RED + 64 + (tid & 1) * 16, bid < 64 ? make_uint4(c.x, c.y, b.x, b.y) : make_uint4(c.z, c.w, b.z, b.w));
        sts32(sb + RED + 96, a.x);
      }
      bar_sync(2 + L, 128 + L * 256);
      if (L) {
        const int r0 = blk * 128 + (tid >> 4);
        uint32_t src = sb + ((tid >> 3) & 1) * 32768 + (r0 & 255) * 128 + (((tid ^ r0) & 7) << 4);
        uint4* dst = (uint4*)(P.out + (size_t)r0 * 1024 + bc * 128) + (tid & 15);
        #pragma unroll 4
        for (int it = 0; it < 16; it++) { uint4 v = lds128(src + it * 1024); if (idx - r0 != it * 8) dst[it * 1024] = v; }
      }
    }
    #pragma unroll 1
    for (int st = L; st < 2; st++) {
      FRESH();
      float a[8] = {0.f, 0.f, 0.f, 0.f, 0.f, 0.f, 0.f, 0.f};
      if (L == 0 && fid < 112) {
        uint32_t ha = st ? sb + RED + 768 : sb + HV + ((wq & 1) * 64 + (lane >> 2)) * 4;
        uint32_t ph = st ? 0x1cu : 0x171u, bar = st ? BAR(B_STG + 2) : BAR(B_STG);
        uint32_t wa = sb + STG + wq * 4096 + (st ? 32768 + lane * 16 : (lane ^ (lane >> 3)) * 16);
        const uint32_t hx = st ? 256 : 512;
        const bool lead = lane == 0;
        uint4 vc = make_uint4(0u, 0u, 0u, 0u); float hc = 0.f;
        #pragma unroll 1
        do {
          mbar_wait(bar, ph & 1);
          PROFX(lead && threadIdx.x == 256 && st == 0 && (ph > 255 || ph < 4), 40 - 23 + __clz(ph));
          #pragma unroll
          for (int n = 0; n < 8; n++) { const uint4 v = lds128(wa + n * 512); const float h = lds32f(ha + n * 32); fma8(a, vc, hc); vc = v; hc = h; }
          __syncwarp();
          if (lead) mbar_arrive(bar - 8 * (B_STG - B_STGE));
          const bool wrap = bar == BAR(B_STG + 2);
          bar += wrap ? -16 : 8; wa += wrap ? -32768 : 16384; ha += hx;
          ph >>= 1;
        } while (ph != 1);
        fma8(a, vc, hc);
      }
      FRESH();
      if (st == 1) {
        const uint32_t t8 = lds32(sb + INFO + 12) + L;
        if (L == 0 && fid < 112) {
          const bool odd = lane & 1;
          #pragma unroll
          for (int e = 0; e < 4; e++) { float z = __shfl_xor_sync(0xffffffffu, odd ? a[e] : a[4 + e], 1); if (odd) a[e] = z; else a[4 + e] = z; }
          uint4* dst = &P.g->yP[tid & ~1][fid][tid & 1];
          st_ll(dst, UI(a[0]), UI(a[1]), UI(a[2]), (UI(a[3]) & ~255u) | t8);
          st_ll(dst + 224, UI(a[4]), UI(a[5]), UI(a[6]), (UI(a[7]) & ~255u) | t8);
          PROFX(tid == 0, 21);
        }
        if (tid == 0) { uint32_t k = lds32(sb + RED + 96); sts32f(sb + RED + 100, bf_round(__fdividef(1.f, 1.f + __expf(-bf_round(FL(k ^ (~(uint32_t)((int)k >> 31) | 0x80000000u))))))); }
        uint4 v0, v1;
        poll_ll2(&P.g->yP[bid][0][min(tid, 111)], &P.g->yP[bid][0][min(tid, 111) + 112], 255u, t8, v0, v1);
        const float lo = (tid < 112 && !(tid & 1)) ? 1.f : 0.f, hi = (tid < 112 && (tid & 1)) ? 1.f : 0.f;
        const float y0 = FL(v0.x) + FL(v1.x), y1 = FL(v0.y) + FL(v1.y), y2 = FL(v0.z) + FL(v1.z), y3 = FL((v0.w & ~255u) | 128u) + FL((v1.w & ~255u) | 128u);
        a[0] = y0 * lo; a[1] = y1 * lo; a[2] = y2 * lo; a[3] = y3 * lo; a[4] = y0 * hi; a[5] = y1 * hi; a[6] = y2 * hi; a[7] = y3 * hi;
      }
      sts32f(sb + RED + 256 + wq * 128 + ((lane & 3) * 8 + (lane >> 2)) * 4, fold8(a));
      bar_sync(2, 128);
      const uint32_t d = sb + RED + 256 + lane * 4;
      float z0 = lds32f(d) + lds32f(d + 128), z1 = lds32f(d + 256) + lds32f(d + 384);
      if (st == 0) {
        sts32f(sb + RED + 768 + lane * 32 + wq * 4, swiglu(z0, z1));
        bar_sync(2, 128);
        if (fid < 112) { st_ll(&P.g->yP[tid & ~1][fid][tid & 1], 0u, 0u, 0u, 0u); st_ll(&P.g->yP[tid | 1][fid][tid & 1], 0u, 0u, 0u, 0u); }
        else { const uint32_t t0 = clk(); while (clk() - t0 < IDLE_T) __nanosleep(200); }
        if (tid < 80) st_ll(tid < 64 ? &P.g->patch[bid][tid] : &P.g->x2[(tid >> 1) & 7][2 * bid + (tid & 1)], 0u, 0u, 0u, 0u);
        PROFX(tid == 0, 20); continue; }
      z0 += z1;
      z0 += __shfl_xor_sync(0xffffffffu, z0, 8); z0 += __shfl_xor_sync(0xffffffffu, z0, 16);
      uint32_t xw = lds32(sb + RED + 64 + (lane & 4) * 4 + (lane & 2) * 2), hw = lds32(sb + RED + 72 + (lane & 4) * 4 + (lane & 2) * 2);
      z0 = bf_round(((lane & 1) ? bf_hi(hw) : bf_lo(hw)) + bf_round(bf_round(z0) * lds32f(sb + RED + 100))) + ((lane & 1) ? bf_hi(xw) : bf_lo(xw));
      uint32_t v = pack_bf16(z0, __shfl_down_sync(0xffffffffu, z0, 1)), v2 = __shfl_down_sync(0xffffffffu, v, 2);
      if (L) { if (tid == 0 || tid == 4) *(uint2*)(P.out + (size_t)idx * 1024 + bid * 8 + tid) = make_uint2(v, v2); PROFW(tid == 0, 28); }
      else if ((tid & 3) == 0 && tid < 64) st_ll(&P.g->x2[tid >> 3][2 * bid + ((tid >> 2) & 1)], v, v2, 0u, tag + 1);
    }
    if (L == 0) {
      PROFX(tid == 0, 22);
      FRESH();
      uint4 x, y; poll_ll2(&P.g->x2[bi][tid], &P.g->x2[bi][tid + 128], 0xffffffffu, tag + 1, x, y);
      x.z = y.x; x.w = y.y;
      if (wq == (bc & 3)) sts64f(sb + X2SEG + lane * 8, FL(bc < 4 ? x.x : x.z), FL(bc < 4 ? x.y : x.w));
      float s1 = 0.f, s2 = 0.f;
      sum8(x, s1, s2);
      #pragma unroll
      for (int o = 16; o; o >>= 1) { s1 += __shfl_xor_sync(0xffffffffu, s1, o); s2 += __shfl_xor_sync(0xffffffffu, s2, o); }
      sts64f(sb + RED + wq * 8, s1, s2);
      bar_sync(2, 128);
      y = lds128(sb + RED); uint4 y2 = lds128(sb + RED + 16);
      float m = ((FL(y.x) + FL(y.z)) + (FL(y2.x) + FL(y2.z))) * (1.f / 1024.f);
      put_bf16(norm8(x, m, rsqrtf(fmaxf(fmaf(-m, m, ((FL(y.y) + FL(y.w)) + (FL(y2.y) + FL(y2.w))) * (1.f / 1024.f)), 0.f) + LN_EPS)), sb + HV + tid * 8);
      mbar_wait(BAR(B_STG), 1); mbar_wait(BAR(B_STG + 1), 0); mbar_wait(BAR(B_STG + 2), 0);
      bar_sync(2, 128);
      PROFX(tid == 0, 30);
      float d0[4] = {0.f, 0.f, 0.f, 0.f}, d1[4] = {0.f, 0.f, 0.f, 0.f}, d2[4] = {0.f, 0.f, 0.f, 0.f};
      const uint32_t bd = (64 + (HV >> 4) + uni(bid & 3) * 32) | 0x10000u;
      #pragma unroll 1
      for (int ks = 0; ks < 8; ks++) {
        const uint32_t ad = (64 + (STG >> 4) + ks * 128) | (64u << 16);
        wg_fence();
        wgmma_ss_n8<0, 1>(d0, mkd<HI64>(ad), mkd<8>(bd + ks * 4), 1);
        wgmma_ss_n8<0, 1>(d1, mkd<HI64>(ad + 1024), mkd<8>(bd + ks * 4), 1);
        wgmma_ss_n8<0, 1>(d2, mkd<HI64>(ad + 2048), mkd<8>(bd + ks * 4), 1);
        wg_commit();
      }
      wg_wait<0>(); keep(d0); keep(d1); keep(d2);
      FRESH();
      if ((lane & 3) == (wq >> 1)) {
        uint4* dst = &P.g->patch[bid][(wq & 1) * 32 + (lane >> 2) * 2 + (wq >> 1)];
        st_ll(dst, UI(d0[0]), UI(d1[0]), UI(d2[0]), tag + 1); st_ll(dst + 16, UI(d0[2]), UI(d1[2]), UI(d2[2]), tag + 1);
      }
      PROFX(tid == 0, 31);
    }
  }
  if (bid == 0 && tid == 0) P.g->epoch = lds32(sb + INFO2 + 16) + 1;
  #undef blk
  #undef bid
  #undef fid
  #undef bi
  #undef bp
  #undef bc
  #undef FRESH
  #undef lane
  #undef wq
}

__global__ void __cluster_dims__(2, 1, 1) __launch_bounds__(512, 1) fused_kernel(const __grid_constant__ Params P) {
  extern __shared__ __align__(1024) uint8_t smem_raw[];
  const uint32_t sb = smem_u32(smem_raw);
  PROFT(threadIdx.x == 0, 0);
  if (threadIdx.x < 32) { if (elect()) {
    for (int s = 0; s < 3; s++) mbar_init(BAR(B_FULLQ + s), 1);
    asm volatile("fence.mbarrier_init.release.cluster;" ::: "memory");
    #pragma unroll 1
    for (int s = 0; s < 3; s++) {
      mbar_expect_tx(BAR(B_FULLQ + s), 57344);
      tma_2d(sb + qa_off(s), &P.mX, s * 64, (BID >> 4) * 256, BAR(B_FULLQ + s));
      tma_3d(sb + qb_off(s), &P.mWq, (BID & 15) * 64, s * 64, 0, BAR(B_FULLQ + s));
    }
    if ((sb & 0x3FFFFu) != 1024) __trap();
  } } else if (threadIdx.x == 480) {
    asm volatile("prefetch.tensormap [%0];" :: "l"(&P.mWq) : "memory");
  } else if (threadIdx.x >= 32 && !(threadIdx.x & 28) && (threadIdx.x >> 3) + (threadIdx.x & 3) <= B_COUNT + 1) {
    int b = (threadIdx.x >> 3) + (threadIdx.x & 3) - 1;
    if (b == B_COUNT) b = B_ROW;
    const uint32_t cnt = b < B_XFREE ? (b == B_OFREE ? 1 : 2) : (b < B_KVRDY ? 3 : (b < B_KVFULL || b == B_PAR ? 4 : (b == B_PFREE ? 2 : 1)));
    mbar_init(BAR(b), cnt);
    asm volatile("fence.mbarrier_init.release.cluster;" ::: "memory");
  }
  __syncthreads();
  asm volatile("barrier.cluster.arrive.relaxed.aligned;" ::: "memory");
  const int wg = __shfl_sync(0xffffffffu, threadIdx.x >> 7, 0);
  if (wg < 2) { reg_inc<224>(); consumer(P, sb, wg); }
  else if (wg == 2) { reg_dec<40>(); aux(P, sb); }
  else {
    reg_dec<24>();
    asm volatile("barrier.cluster.wait.aligned;" ::: "memory");
    const int w = __shfl_sync(0xffffffffu, (threadIdx.x >> 5) & 3, 0);
    if (w == 0) loader(P, sb);
    else if (w < 3) storer(P, sb, w - 1);
    else if (elect()) stager(P, sb);
  }
}

typedef CUresult (*EncFn)(CUtensorMap*, CUtensorMapDataType, cuuint32_t, void*, const cuuint64_t*, const cuuint64_t*, const cuuint32_t*, const cuuint32_t*,
                          CUtensorMapInterleave, CUtensorMapSwizzle, CUtensorMapL2promotion, CUtensorMapFloatOOBfill);
static void mk_map(EncFn enc, CUtensorMap* m, const void* ptr, int rank, const cuuint64_t* dims, const cuuint64_t* strides, const cuuint32_t* box,
                   CUtensorMapSwizzle sw, CUtensorMapL2promotion pr) {
  cuuint32_t es[5] = {1, 1, 1, 1, 1};
  enc(m, CU_TENSOR_MAP_DATA_TYPE_BFLOAT16, rank, (void*)ptr, dims, strides, box, es, CU_TENSOR_MAP_INTERLEAVE_NONE, sw, pr, CU_TENSOR_MAP_FLOAT_OOB_FILL_NONE);
}
extern "C" void kernel_launch(void* const* d_in, const int* in_sizes, int n_in, void* d_out, int out_size) {
  (void)in_sizes; (void)n_in; (void)out_size;
  void* fn = nullptr; cudaDriverEntryPointQueryResult q;
  cudaGetDriverEntryPoint("cuTensorMapEncodeTiled", &fn, cudaEnableDefault, &q);
  EncFn enc = (EncFn)fn;
  cudaFuncSetAttribute(fused_kernel, cudaFuncAttributeMaxDynamicSharedMemorySize, SMEM_BYTES);
  Params P;
  const CUtensorMapSwizzle S128 = CU_TENSOR_MAP_SWIZZLE_128B, S64 = CU_TENSOR_MAP_SWIZZLE_64B, S0 = CU_TENSOR_MAP_SWIZZLE_NONE;
  const CUtensorMapL2promotion L256 = CU_TENSOR_MAP_L2_PROMOTION_L2_256B, L128 = CU_TENSOR_MAP_L2_PROMOTION_L2_128B;
  { cuuint64_t d[2] = {1024, 2048}, s[1] = {2048}; cuuint32_t b[2] = {64, 256}, bh[2] = {64, 128};
    mk_map(enc, &P.mX, d_in[0], 2, d, s, b, S128, L256); mk_map(enc, &P.mXh, d_in[0], 2, d, s, bh, S128, L256); }
  { cuuint64_t d[3] = {1024, 1024, 3}, s[2] = {6144, 2048}; cuuint32_t b[3] = {64, 64, 3}; mk_map(enc, &P.mWq, d_in[1], 3, d, s, b, S128, L256); }
  { cuuint64_t d[5] = {64, 32, 2, 16, 16}, s[4] = {2048, 65536, 131072, 128}; cuuint32_t b[5] = {64, 32, 1, 2, 2}; mk_map(enc, &P.mWo, d_in[2], 5, d, s, b, S128, L256); }
  { cuuint64_t d[2] = {3584, 1024}, s[1] = {7168}; cuuint32_t b[2] = {32, 128};
    mk_map(enc, &P.mWg, d_in[5], 2, d, s, b, S64, L128); mk_map(enc, &P.mWu, d_in[6], 2, d, s, b, S64, L128); }
  { cuuint64_t d[2] = {3072, 1024}, s[1] = {6144}; cuuint32_t b[2] = {32, 256}; mk_map(enc, &P.mWp, d_in[1], 2, d, s, b, S64, L128); }
  { cuuint64_t d[3] = {256, 3584, 4}, s[2] = {2048, 512}; cuuint32_t b[3] = {256, 8, 4}; mk_map(enc, &P.mWd, d_in[7], 3, d, s, b, S0, L128); }
  P.x0 = (const bf16*)d_in[0]; P.wqkv = (const bf16*)d_in[1]; P.wo = (const bf16*)d_in[2]; P.wr = (const bf16*)d_in[4]; P.wg = (const bf16*)d_in[5]; P.wu = (const bf16*)d_in[6]; P.wd = (const bf16*)d_in[7];
  P.out = (bf16*)d_out;
  cudaGetSymbolAddress((void**)&P.g, g_scr);
  for (int b = 0; b < 128; b++) {
    int j = b >> 1, quad = j < 4 ? 0 : (j < 36 ? 1 + (j - 4) % 8 : 9 + (j - 36) % 7), pos = j < 4 ? j : (j < 36 ? (j - 4) / 8 : (j - 36) / 7);
    int bid = ((quad >> 2) * 2 + (pos >> 1)) * 16 + ((quad & 3) * 2 + (pos & 1)) * 2 + (b & 1);
    int e = pos * 2 + (b & 1), fid = e < 7 ? quad * 7 + e : 112 + quad;
    P.map[b] = bid | fid << 8;
  }
  fused_kernel<<<128, 512, SMEM_BYTES>>>(P);
}
```

```cpp
#include <cuda_runtime.h>
#include <cuda_bf16.h>
#include <cuda.h>
#include <stdint.h>
#include <stddef.h>
typedef __nv_bfloat16 bf16;

template<int TB, int TA = 0> __device__ __forceinline__ void wgmma_ss_n192(float (&d)[96], uint64_t da, uint64_t db, int scale_d) {
  asm volatile("{\n.reg .pred p;\nsetp.ne.b32 p, %98, 0;\n"
    "wgmma.mma_async.sync.aligned.m64n192k16.f32.bf16.bf16 {%0, %1, %2, %3, %4, %5, %6, %7, %8, %9, %10, %11, %12, %13, %14, %15, %16, %17, %18, %19, %20, %21, %22, %23, %24, %25, %26, %27, %28, %29, %30, %31, %32, %33, %34, %35, %36, %37, %38, %39, %40, %41, %42, %43, %44, %45, %46, %47, %48, %49, %50, %51, %52, %53, %54, %55, %56, %57, %58, %59, %60, %61, %62, %63, %64, %65, %66, %67, %68, %69, %70, %71, %72, %73, %74, %75, %76, %77, %78, %79, %80, %81, %82, %83, %84, %85, %86, %87, %88, %89, %90, %91, %92, %93, %94, %95}, %96, %97, p, 1, 1, %100, %99;\n}\n"
    : "+f"(d[0]), "+f"(d[1]), "+f"(d[2]), "+f"(d[3]), "+f"(d[4]), "+f"(d[5]), "+f"(d[6]), "+f"(d[7]), "+f"(d[8]), "+f"(d[9]), "+f"(d[10]), "+f"(d[11]), "+f"(d[12]), "+f"(d[13]), "+f"(d[14]), "+f"(d[15]), "+f"(d[16]), "+f"(d[17]), "+f"(d[18]), "+f"(d[19]), "+f"(d[20]), "+f"(d[21]), "+f"(d[22]), "+f"(d[23]), "+f"(d[24]), "+f"(d[25]), "+f"(d[26]), "+f"(d[27]), "+f"(d[28]), "+f"(d[29]), "+f"(d[30]), "+f"(d[31]), "+f"(d[32]), "+f"(d[33]), "+f"(d[34]), "+f"(d[35]), "+f"(d[36]), "+f"(d[37]), "+f"(d[38]), "+f"(d[39]), "+f"(d[40]), "+f"(d[41]), "+f"(d[42]), "+f"(d[43]), "+f"(d[44]), "+f"(d[45]), "+f"(d[46]), "+f"(d[47]), "+f"(d[48]), "+f"(d[49]), "+f"(d[50]), "+f"(d[51]), "+f"(d[52]), "+f"(d[53]), "+f"(d[54]), "+f"(d[55]), "+f"(d[56]), "+f"(d[57]), "+f"(d[58]), "+f"(d[59]), "+f"(d[60]), "+f"(d[61]), "+f"(d[62]), "+f"(d[63]), "+f"(d[64]), "+f"(d[65]), "+f"(d[66]), "+f"(d[67]), "+f"(d[68]), "+f"(d[69]), "+f"(d[70]), "+f"(d[71]), "+f"(d[72]), "+f"(d[73]), "+f"(d[74]), "+f"(d[75]), "+f"(d[76]), "+f"(d[77]), "+f"(d[78]), "+f"(d[79]), "+f"(d[80]), "+f"(d[81]), "+f"(d[82]), "+f"(d[83]), "+f"(d[84]), "+f"(d[85]), "+f"(d[86]), "+f"(d[87]), "+f"(d[88]), "+f"(d[89]), "+f"(d[90]), "+f"(d[91]), "+f"(d[92]), "+f"(d[93]), "+f"(d[94]), "+f"(d[95])
    : "l"(da), "l"(db), "r"(scale_d), "n"(TB), "n"(TA));
}

template<int TB> __device__ __forceinline__ void wgmma_rs_n192(float (&d)[96], uint32_t a0, uint32_t a1, uint32_t a2, uint32_t a3, uint64_t db, int scale_d) {
  asm volatile("{\n.reg .pred p;\nsetp.ne.b32 p, %101, 0;\n"
    "wgmma.mma_async.sync.aligned.m64n192k16.f32.bf16.bf16 {%0, %1, %2, %3, %4, %5, %6, %7, %8, %9, %10, %11, %12, %13, %14, %15, %16, %17, %18, %19, %20, %21, %22, %23, %24, %25, %26, %27, %28, %29, %30, %31, %32, %33, %34, %35, %36, %37, %38, %39, %40, %41, %42, %43, %44, %45, %46, %47, %48, %49, %50, %51, %52, %53, %54, %55, %56, %57, %58, %59, %60, %61, %62, %63, %64, %65, %66, %67, %68, %69, %70, %71, %72, %73, %74, %75, %76, %77, %78, %79, %80, %81, %82, %83, %84, %85, %86, %87, %88, %89, %90, %91, %92, %93, %94, %95}, {%96, %97, %98, %99}, %100, p, 1, 1, %102;\n}\n"
    : "+f"(d[0]), "+f"(d[1]), "+f"(d[2]), "+f"(d[3]), "+f"(d[4]), "+f"(d[5]), "+f"(d[6]), "+f"(d[7]), "+f"(d[8]), "+f"(d[9]), "+f"(d[10]), "+f"(d[11]), "+f"(d[12]), "+f"(d[13]), "+f"(d[14]), "+f"(d[15]), "+f"(d[16]), "+f"(d[17]), "+f"(d[18]), "+f"(d[19]), "+f"(d[20]), "+f"(d[21]), "+f"(d[22]), "+f"(d[23]), "+f"(d[24]), "+f"(d[25]), "+f"(d[26]), "+f"(d[27]), "+f"(d[28]), "+f"(d[29]), "+f"(d[30]), "+f"(d[31]), "+f"(d[32]), "+f"(d[33]), "+f"(d[34]), "+f"(d[35]), "+f"(d[36]), "+f"(d[37]), "+f"(d[38]), "+f"(d[39]), "+f"(d[40]), "+f"(d[41]), "+f"(d[42]), "+f"(d[43]), "+f"(d[44]), "+f"(d[45]), "+f"(d[46]), "+f"(d[47]), "+f"(d[48]), "+f"(d[49]), "+f"(d[50]), "+f"(d[51]), "+f"(d[52]), "+f"(d[53]), "+f"(d[54]), "+f"(d[55]), "+f"(d[56]), "+f"(d[57]), "+f"(d[58]), "+f"(d[59]), "+f"(d[60]), "+f"(d[61]), "+f"(d[62]), "+f"(d[63]), "+f"(d[64]), "+f"(d[65]), "+f"(d[66]), "+f"(d[67]), "+f"(d[68]), "+f"(d[69]), "+f"(d[70]), "+f"(d[71]), "+f"(d[72]), "+f"(d[73]), "+f"(d[74]), "+f"(d[75]), "+f"(d[76]), "+f"(d[77]), "+f"(d[78]), "+f"(d[79]), "+f"(d[80]), "+f"(d[81]), "+f"(d[82]), "+f"(d[83]), "+f"(d[84]), "+f"(d[85]), "+f"(d[86]), "+f"(d[87]), "+f"(d[88]), "+f"(d[89]), "+f"(d[90]), "+f"(d[91]), "+f"(d[92]), "+f"(d[93]), "+f"(d[94]), "+f"(d[95])
    : "r"(a0), "r"(a1), "r"(a2), "r"(a3), "l"(db), "r"(scale_d), "n"(TB));
}

template<int TB, int TA = 0> __device__ __forceinline__ void wgmma_ss_n128(float (&d)[64], uint64_t da, uint64_t db, int scale_d) {
  asm volatile("{\n.reg .pred p;\nsetp.ne.b32 p, %66, 0;\n"
    "wgmma.mma_async.sync.aligned.m64n128k16.f32.bf16.bf16 {%0, %1, %2, %3, %4, %5, %6, %7, %8, %9, %10, %11, %12, %13, %14, %15, %16, %17, %18, %19, %20, %21, %22, %23, %24, %25, %26, %27, %28, %29, %30, %31, %32, %33, %34, %35, %36, %37, %38, %39, %40, %41, %42, %43, %44, %45, %46, %47, %48, %49, %50, %51, %52, %53, %54, %55, %56, %57, %58, %59, %60, %61, %62, %63}, %64, %65, p, 1, 1, %68, %67;\n}\n"
    : "+f"(d[0]), "+f"(d[1]), "+f"(d[2]), "+f"(d[3]), "+f"(d[4]), "+f"(d[5]), "+f"(d[6]), "+f"(d[7]), "+f"(d[8]), "+f"(d[9]), "+f"(d[10]), "+f"(d[11]), "+f"(d[12]), "+f"(d[13]), "+f"(d[14]), "+f"(d[15]), "+f"(d[16]), "+f"(d[17]), "+f"(d[18]), "+f"(d[19]), "+f"(d[20]), "+f"(d[21]), "+f"(d[22]), "+f"(d[23]), "+f"(d[24]), "+f"(d[25]), "+f"(d[26]), "+f"(d[27]), "+f"(d[28]), "+f"(d[29]), "+f"(d[30]), "+f"(d[31]), "+f"(d[32]), "+f"(d[33]), "+f"(d[34]), "+f"(d[35]), "+f"(d[36]), "+f"(d[37]), "+f"(d[38]), "+f"(d[39]), "+f"(d[40]), "+f"(d[41]), "+f"(d[42]), "+f"(d[43]), "+f"(d[44]), "+f"(d[45]), "+f"(d[46]), "+f"(d[47]), "+f"(d[48]), "+f"(d[49]), "+f"(d[50]), "+f"(d[51]), "+f"(d[52]), "+f"(d[53]), "+f"(d[54]), "+f"(d[55]), "+f"(d[56]), "+f"(d[57]), "+f"(d[58]), "+f"(d[59]), "+f"(d[60]), "+f"(d[61]), "+f"(d[62]), "+f"(d[63])
    : "l"(da), "l"(db), "r"(scale_d), "n"(TB), "n"(TA));
}

template<int TB, int TA = 0> __device__ __forceinline__ void wgmma_ss_n64(float (&d)[32], uint64_t da, uint64_t db, int scale_d) {
  asm volatile("{\n.reg .pred p;\nsetp.ne.b32 p, %34, 0;\n"
    "wgmma.mma_async.sync.aligned.m64n64k16.f32.bf16.bf16 {%0, %1, %2, %3, %4, %5, %6, %7, %8, %9, %10, %11, %12, %13, %14, %15, %16, %17, %18, %19, %20, %21, %22, %23, %24, %25, %26, %27, %28, %29, %30, %31}, %32, %33, p, 1, 1, %36, %35;\n}\n"
    : "+f"(d[0]), "+f"(d[1]), "+f"(d[2]), "+f"(d[3]), "+f"(d[4]), "+f"(d[5]), "+f"(d[6]), "+f"(d[7]), "+f"(d[8]), "+f"(d[9]), "+f"(d[10]), "+f"(d[11]), "+f"(d[12]), "+f"(d[13]), "+f"(d[14]), "+f"(d[15]), "+f"(d[16]), "+f"(d[17]), "+f"(d[18]), "+f"(d[19]), "+f"(d[20]), "+f"(d[21]), "+f"(d[22]), "+f"(d[23]), "+f"(d[24]), "+f"(d[25]), "+f"(d[26]), "+f"(d[27]), "+f"(d[28]), "+f"(d[29]), "+f"(d[30]), "+f"(d[31])
    : "l"(da), "l"(db), "r"(scale_d), "n"(TB), "n"(TA));
}

template<int TB, int TA = 0> __device__ __forceinline__ void wgmma_ss_n8(float (&d)[4], uint64_t da, uint64_t db, int scale_d) {
  asm volatile("{\n.reg .pred p;\nsetp.ne.b32 p, %6, 0;\n"
    "wgmma.mma_async.sync.aligned.m64n8k16.f32.bf16.bf16 {%0, %1, %2, %3}, %4, %5, p, 1, 1, %8, %7;\n}\n"
    : "+f"(d[0]), "+f"(d[1]), "+f"(d[2]), "+f"(d[3])
    : "l"(da), "l"(db), "r"(scale_d), "n"(TB), "n"(TA));
}

template<int TB> __device__ __forceinline__ void wgmma_rs_n40(float (&d)[20], uint32_t a0, uint32_t a1, uint32_t a2, uint32_t a3, uint64_t db, int scale_d) {
  asm volatile("{\n.reg .pred p;\nsetp.ne.b32 p, %25, 0;\n"
    "wgmma.mma_async.sync.aligned.m64n40k16.f32.bf16.bf16 {%0, %1, %2, %3, %4, %5, %6, %7, %8, %9, %10, %11, %12, %13, %14, %15, %16, %17, %18, %19}, {%20, %21, %22, %23}, %24, p, 1, 1, %26;\n}\n"
    : "+f"(d[0]), "+f"(d[1]), "+f"(d[2]), "+f"(d[3]), "+f"(d[4]), "+f"(d[5]), "+f"(d[6]), "+f"(d[7]), "+f"(d[8]), "+f"(d[9]), "+f"(d[10]), "+f"(d[11]), "+f"(d[12]), "+f"(d[13]), "+f"(d[14]), "+f"(d[15]), "+f"(d[16]), "+f"(d[17]), "+f"(d[18]), "+f"(d[19])
    : "r"(a0), "r"(a1), "r"(a2), "r"(a3), "l"(db), "r"(scale_d), "n"(TB));
}

#define DEVI __device__ __forceinline__
DEVI uint32_t smem_u32(const void* p) { return (uint32_t)__cvta_generic_to_shared(p); }
DEVI void mbar_init(uint32_t bar, uint32_t cnt) { asm volatile("mbarrier.init.shared::cta.b64 [%0], %1;" :: "r"(bar), "r"(cnt)); }
DEVI void mbar_expect_tx(uint32_t bar, uint32_t bytes) { asm volatile("mbarrier.arrive.expect_tx.shared::cta.b64 _, [%0], %1;" :: "r"(bar), "r"(bytes) : "memory"); }
DEVI void mbar_arrive(uint32_t bar) { asm volatile("mbarrier.arrive.shared::cta.b64 _, [%0];" :: "r"(bar) : "memory"); }
DEVI void mbar_arrive_peer(uint32_t bar) {
  asm volatile("{\n.reg .b32 ra;\nmapa.shared::cluster.u32 ra, %0, %1;\nmbarrier.arrive.shared::cluster.b64 _, [ra];\n}" :: "r"(bar), "r"((blockIdx.x & 1) ^ 1) : "memory");
}
DEVI void bulk_s2peer(uint32_t a, uint32_t bytes, uint32_t bar) {
  asm volatile("{\n.reg .b32 ra, rb;\nmapa.shared::cluster.u32 ra, %0, %3;\nmapa.shared::cluster.u32 rb, %2, %3;\n"
               "cp.async.bulk.shared::cluster.shared::cta.mbarrier::complete_tx::bytes [ra], [%0], %1, [rb];\n}"
               :: "r"(a), "r"(bytes), "r"(bar), "r"((blockIdx.x & 1) ^ 1) : "memory");
}
DEVI void mbar_wait(uint32_t bar, uint32_t parity) {
  asm volatile("{\n.reg .pred p;\nLW:\nmbarrier.try_wait.parity.shared::cta.b64 p, [%0], %1;\n@!p bra LW;\n}" :: "r"(bar), "r"(parity) : "memory");
}
DEVI uint32_t mbar_test(uint32_t bar, uint32_t parity) {
  uint32_t r; asm volatile("{\n.reg .pred p;\nmbarrier.test_wait.parity.shared::cta.b64 p, [%1], %2;\nselp.u32 %0, 1, 0, p;\n}" : "=r"(r) : "r"(bar), "r"(parity) : "memory"); return r;
}
DEVI void mbar_wait_b(uint32_t bar, uint32_t parity) {
  asm volatile("{\n.reg .pred p;\n.reg .u32 it;\nmov.u32 it, 0;\nLW:\nmbarrier.try_wait.parity.shared::cta.b64 p, [%0], %1;\n@p bra LD;\n"
               "add.u32 it, it, 1;\nsetp.lt.u32 p, it, 0x1000000;\n@p bra LW;\ntrap;\nLD:\n}" :: "r"(bar), "r"(parity) : "memory");
}
DEVI void tma_2d(uint32_t dst, const CUtensorMap* m, int c0, int c1, uint32_t bar) {
  asm volatile("cp.async.bulk.tensor.2d.shared::cluster.global.mbarrier::complete_tx::bytes [%0], [%1, {%3, %4}], [%2];"
    :: "r"(dst), "l"(m), "r"(bar), "r"(c0), "r"(c1) : "memory");
}
DEVI void tma_3d(uint32_t dst, const CUtensorMap* m, int c0, int c1, int c2, uint32_t bar) {
  asm volatile("cp.async.bulk.tensor.3d.shared::cluster.global.mbarrier::complete_tx::bytes [%0], [%1, {%3, %4, %5}], [%2];"
    :: "r"(dst), "l"(m), "r"(bar), "r"(c0), "r"(c1), "r"(c2) : "memory");
}
#define POL_EF POL_FIRST
constexpr uint64_t POL_FIRST = 0x12F0000000000000ull, POL_NORMAL = 0x1000000000000000ull;
DEVI void tma_2d_h(uint32_t dst, const CUtensorMap* m, int c0, int c1, uint32_t bar, uint64_t pol) {
  asm volatile("cp.async.bulk.tensor.2d.shared::cluster.global.mbarrier::complete_tx::bytes.L2::cache_hint [%0], [%1, {%3, %4}], [%2], %5;"
    :: "r"(dst), "l"(m), "r"(bar), "r"(c0), "r"(c1), "l"(pol) : "memory");
}
DEVI void tma_3d_h(uint32_t dst, const CUtensorMap* m, int c0, int c1, int c2, uint32_t bar, uint64_t pol) {
  asm volatile("cp.async.bulk.tensor.3d.shared::cluster.global.mbarrier::complete_tx::bytes.L2::cache_hint [%0], [%1, {%3, %4, %5}], [%2], %6;"
    :: "r"(dst), "l"(m), "r"(bar), "r"(c0), "r"(c1), "r"(c2), "l"(pol) : "memory");
}
DEVI void bulk_g2s_h(uint32_t s, const void* g, uint32_t bytes, uint32_t bar, uint64_t pol = POL_EF) {
  asm volatile("cp.async.bulk.shared::cluster.global.mbarrier::complete_tx::bytes.L2::cache_hint [%0], [%1], %2, [%3], %4;"
    :: "r"(s), "l"(g), "r"(bytes), "r"(bar), "l"(pol) : "memory");
}
DEVI void tma_5d(uint32_t dst, const CUtensorMap* m, int c0, int c1, int c2, int c3, int c4, uint32_t bar, uint64_t pol) {
  asm volatile("cp.async.bulk.tensor.5d.shared::cluster.global.mbarrier::complete_tx::bytes.L2::cache_hint [%0], [%1, {%3, %4, %5, %6, %7}], [%2], %8;"
    :: "r"(dst), "l"(m), "r"(bar), "r"(c0), "r"(c1), "r"(c2), "r"(c3), "r"(c4), "l"(pol) : "memory");
}
DEVI void tma_prefetch_2d(const CUtensorMap* m, int c0, int c1) {
  asm volatile("cp.async.bulk.prefetch.tensor.2d.L2.global.tile [%0, {%1, %2}];" :: "l"(m), "r"(c0), "r"(c1) : "memory");
}
DEVI void tma_prefetch_3d(const CUtensorMap* m, int c0, int c1, int c2) {
  asm volatile("cp.async.bulk.prefetch.tensor.3d.L2.global.tile [%0, {%1, %2, %3}];" :: "l"(m), "r"(c0), "r"(c1), "r"(c2) : "memory");
}
DEVI void bulk_prefetch(const void* g, uint32_t bytes) { asm volatile("cp.async.bulk.prefetch.L2.global [%0], %1;" :: "l"(g), "r"(bytes) : "memory"); }
DEVI void bulk_g2s(uint32_t s, const void* g, uint32_t bytes, uint32_t bar) {
  asm volatile("cp.async.bulk.shared::cluster.global.mbarrier::complete_tx::bytes [%0], [%1], %2, [%3];" :: "r"(s), "l"(g), "r"(bytes), "r"(bar) : "memory");
}
DEVI void bulk_s2g(void* g, uint32_t s, uint32_t bytes, uint64_t pol = POL_NORMAL) {
  asm volatile("cp.async.bulk.global.shared::cta.bulk_group.L2::cache_hint [%0], [%1], %2, %3;\ncp.async.bulk.commit_group;" :: "l"(g), "r"(s), "r"(bytes), "l"(pol) : "memory");
}
template<int N> DEVI void bulk_wait() { asm volatile("cp.async.bulk.wait_group %0;" :: "n"(N) : "memory"); }
DEVI void fence_async_smem() { asm volatile("fence.proxy.async.shared::cta;" ::: "memory"); }
DEVI void fence_async_glob() { asm volatile("fence.proxy.async.global;" ::: "memory"); }
DEVI unsigned ld_rlx(const unsigned* p) { unsigned v; asm volatile("ld.relaxed.gpu.global.u32 %0, [%1];" : "=r"(v) : "l"(p) : "memory"); return v; }
DEVI void st_rlx(unsigned* p, unsigned v) { asm volatile("st.relaxed.gpu.global.u32 [%0], %1;" :: "l"(p), "r"(v) : "memory"); }
DEVI uint2 ldg_stream(const uint2* p) { uint2 v; asm volatile("ld.global.nc.L1::no_allocate.v2.u32 {%0, %1}, [%2];" : "=r"(v.x), "=r"(v.y) : "l"(p)); return v; }
DEVI void fence_rel() { asm volatile("fence.release.gpu;" ::: "memory"); }
DEVI uint4 ld_ll(const uint4* p) {
  uint4 v;
  asm volatile("{\n.reg .b128 t;\n.reg .b64 a, b;\nld.relaxed.gpu.global.b128 t, [%4];\nmov.b128 {a, b}, t;\nmov.b64 {%0, %1}, a;\nmov.b64 {%2, %3}, b;\n}"
               : "=r"(v.x), "=r"(v.y), "=r"(v.z), "=r"(v.w) : "l"(p) : "memory");
  return v;
}
DEVI void st_ll(uint4* p, uint32_t x, uint32_t y, uint32_t z, uint32_t w) {
  asm volatile("{\n.reg .b128 t;\n.reg .b64 a, b;\nmov.b64 a, {%1, %2};\nmov.b64 b, {%3, %4};\nmov.b128 t, {a, b};\nst.relaxed.gpu.global.b128 [%0], t;\n}"
               :: "l"(p), "r"(x), "r"(y), "r"(z), "r"(w) : "memory");
}
#define SPIN_MAX 0x1000000
DEVI uint4 poll_ll(const uint4* p, uint32_t mask, uint32_t tag) {
  uint4 v; int it = 0;
  do { v = ld_ll(p); if (++it > SPIN_MAX) __trap(); } while (!__all_sync(0xffffffffu, (v.w & mask) == tag));
  return v;
}
DEVI void poll_ll2(const uint4* p, const uint4* q, uint32_t mask, uint32_t tag, uint4& a, uint4& b) {
  int it = 0;
  do { a = ld_ll(p); b = ld_ll(q); if (++it > SPIN_MAX) __trap(); } while (!__all_sync(0xffffffffu, (a.w & mask) == tag && (b.w & mask) == tag));
}
DEVI float4 poll_sum4(const uint4* src, int stride, uint32_t tag) {
  uint4 v0, v1, v2, v3; int it = 0;
  do { v0 = ld_ll(src); v1 = ld_ll(src + stride); v2 = ld_ll(src + 2 * stride); v3 = ld_ll(src + 3 * stride); if (++it > SPIN_MAX) __trap(); }
  while (!__all_sync(0xffffffffu, v0.w == tag && v1.w == tag && v2.w == tag && v3.w == tag));
  #define S4(f) ((__uint_as_float(v0.f) + __uint_as_float(v1.f)) + (__uint_as_float(v2.f) + __uint_as_float(v3.f)))
  return make_float4(S4(x), S4(y), S4(z), 0.f);
  #undef S4
}
DEVI void bar_sync(int id, int n) { asm volatile("bar.sync %0, %1;" :: "r"(id), "r"(n) : "memory"); }
DEVI void bar_arrive(int id, int n) { asm volatile("bar.arrive %0, %1;" :: "r"(id), "r"(n) : "memory"); }
DEVI void wg_fence() { asm volatile("wgmma.fence.sync.aligned;" ::: "memory"); }
DEVI void wg_commit() { asm volatile("wgmma.commit_group.sync.aligned;" ::: "memory"); }
template<int N> DEVI void wg_wait() { asm volatile("wgmma.wait_group.sync.aligned %0;" :: "n"(N) : "memory"); }
template<int N> DEVI void reg_inc() { asm volatile("setmaxnreg.inc.sync.aligned.u32 %0;" :: "n"(N)); }
template<int N> DEVI void reg_dec() { asm volatile("setmaxnreg.dec.sync.aligned.u32 %0;" :: "n"(N)); }
DEVI float ex2f(float x) { float y; asm("ex2.approx.ftz.f32 %0, %1;" : "=f"(y) : "f"(x)); return y; }
DEVI uint32_t pack_bf16(float lo, float hi) { uint32_t r; asm("cvt.rn.bf16x2.f32 %0, %1, %2;" : "=r"(r) : "f"(hi), "f"(lo)); return r; }
DEVI float bf_lo(uint32_t v) { return __uint_as_float(v << 16); }
DEVI float bf_hi(uint32_t v) { return __uint_as_float(v & 0xffff0000u); }
DEVI float bf_round(float x) { return bf_lo(pack_bf16(x, 0.f)); }
DEVI void stsm_x4(uint32_t addr, uint32_t a, uint32_t b, uint32_t c, uint32_t d) {
  asm volatile("stmatrix.sync.aligned.m8n8.x4.shared.b16 [%0], {%1,%2,%3,%4};" :: "r"(addr), "r"(a), "r"(b), "r"(c), "r"(d) : "memory");
}
DEVI void ldsm_x4(uint32_t addr, uint32_t& a, uint32_t& b, uint32_t& c, uint32_t& d) {
  asm volatile("ldmatrix.sync.aligned.m8n8.x4.shared.b16 {%0,%1,%2,%3}, [%4];" : "=r"(a), "=r"(b), "=r"(c), "=r"(d) : "r"(addr) : "memory");
}
DEVI uint4 lds128(uint32_t a) { uint4 v; asm volatile("ld.shared.v4.u32 {%0,%1,%2,%3}, [%4];" : "=r"(v.x), "=r"(v.y), "=r"(v.z), "=r"(v.w) : "r"(a) : "memory"); return v; }
DEVI void sts128(uint32_t a, uint4 v) { asm volatile("st.shared.v4.u32 [%0], {%1,%2,%3,%4};" :: "r"(a), "r"(v.x), "r"(v.y), "r"(v.z), "r"(v.w) : "memory"); }
DEVI float2 lds64f(uint32_t a) { float2 v; asm volatile("ld.shared.v2.f32 {%0,%1}, [%2];" : "=f"(v.x), "=f"(v.y) : "r"(a) : "memory"); return v; }
DEVI void sts64f(uint32_t a, float x, float y) { asm volatile("st.shared.v2.f32 [%0], {%1,%2};" :: "r"(a), "f"(x), "f"(y) : "memory"); }
DEVI uint32_t lds32(uint32_t a) { uint32_t v; asm volatile("ld.shared.u32 %0, [%1];" : "=r"(v) : "r"(a) : "memory"); return v; }
DEVI float lds32f(uint32_t a) { return __uint_as_float(lds32(a)); }
DEVI void sts32(uint32_t a, uint32_t v) { asm volatile("st.shared.u32 [%0], %1;" :: "r"(a), "r"(v) : "memory"); }
DEVI void sts32f(uint32_t a, float v) { sts32(a, __float_as_uint(v)); }
DEVI void sts16(uint32_t a, uint32_t v) { asm volatile("st.shared.u16 [%0], %1;" :: "r"(a), "h"((unsigned short)v) : "memory"); }
template<int N> DEVI void keep(float (&d)[N]) {
  #pragma unroll
  for (int i = 0; i < N; i++) asm volatile("" : "+f"(d[i]) :: "memory");
}
template<int N> DEVI void keep(uint32_t (&d)[N]) {
  #pragma unroll
  for (int i = 0; i < N; i++) asm volatile("" : "+r"(d[i]) :: "memory");
}
template<uint32_t HI> DEVI uint64_t mkd(uint32_t lo) { uint64_t r; asm("mov.b64 %0, {%1, %2};" : "=l"(r) : "r"(lo), "n"(HI)); return r; }
constexpr uint32_t HI128 = (1u << 30) | (1024 >> 4), HI64 = (2u << 30) | (512 >> 4);
#define VOFF(x) ((uint32_t)(x) * (uint32_t)(1 - 65536))
DEVI bool elect() { uint32_t p; asm volatile("{\n.reg .pred q;\nelect.sync _|q, 0xffffffff;\nselp.u32 %0, 1, 0, q;\n}" : "=r"(p)); return p; }
DEVI void warp_signal(uint32_t bar) { __syncwarp(); if (elect()) mbar_arrive(bar); }

struct Scratch {
  uint4 kv[128][4][1024];
  uint4 o[8][2][8][2][1024];
  uint4 x[8][16][2048];
  uint4 zero[1024];
  uint4 statP[8][2048];
  uint4 statF[2048];
  uint4 csP[16][8][96];
  uint4 best[8][16];
  uint4 row[16][256];
  uint4 yP[128][112][2];
  uint4 x2[8][256];
  uint4 patch[128][64];
  unsigned flagKV[128][32];
  unsigned flagO[8][32];
  unsigned flagX[8][32];
  unsigned epoch;
};
__device__ __align__(1024) Scratch g_scr;
#define PROFT(cond, slot)
#define PROFW(cond, slot)
#define PROFD(cond, slot)
#define PROFX(cond, slot)
#define PROFY(cond, slot)

constexpr uint32_t SB0 = 65536, HOLE = 90112, SA2 = 98304, SB1 = 131072, SB2 = 155648, STG = 180224;
constexpr uint32_t KVA = 0, KVB = 98304, QO = 65536;
constexpr uint32_t MISC = 229376, CS = MISC, ONES = MISC + 768, BARS = MISC + 1792, INFO = MISC + 2208, WR = MISC + 2224, X2SEG = MISC + 2736, INFO2 = MISC + 2992, DUMP = MISC + 3040;
constexpr uint32_t PAR = HOLE, HV = HOLE + 2048, RED = HOLE + 6144, PATCH = 196608;
constexpr uint32_t SMEM_BYTES = 232448;
enum { B_FULLQ = 0, B_EMPTYQ = 3, B_FULLW = 6, B_EMPTYW = 12, B_HAFREE = 18, B_OFREE = 20,
       B_XFREE = 21,
       B_KVRDY = 23, B_ORDY = 27, B_XRDY = 35, B_STGE = 39,
       B_KVFULL = 42, B_RES = 46, B_PAR = 47, B_STG = 48, B_PFREE = 51, B_COUNT = 52,
       B_ROW = 154 };
#define BAR(x) (sb + BARS + 8 * (x))
DEVI uint32_t qa_off(int s) { return s == 2 ? SA2 : (uint32_t)s * 32768u; }
DEVI uint32_t qb_off(int s) { return s == 0 ? SB0 : (s == 1 ? SB1 : SB2); }
DEVI int kb_order(int bc, int n) {
  const int e = n < 9 ? n - 2 : n - 9;
  return n < 2 ? 2 * bc + n : 2 * (((e < 4 ? e + 4 : e - 4 + (e - 4 >= (bc & 3))) + (bc & 4)) & 7) + (n >= 9);
}
DEVI int wo_order(int bc, int n) { return (n & 8) | ((n + (bc & 6)) & 7); }
DEVI uint32_t w_off(int s) { return (uint32_t)((0x143065 >> (4 * s)) & 7) * 32768u; }
DEVI uint32_t w_par(int n, int s, int L) { return (n >= 6 && n < 12) ^ (s == 5) ^ (s != 2 && L); }
DEVI int w_next(int n, int s) { return s == 5 ? 0 : (n == 13 ? 3 : s + 1); }

struct Params {
  CUtensorMap mX, mXh, mWq, mWo, mWg, mWu, mWp, mWd;
  const bf16 *x0, *wqkv, *wo, *wr, *wg, *wu, *wd;
  bf16* out;
  Scratch* g;
  unsigned map[128];
};
#define BID ((int)(P.map[blockIdx.x] & 255))
#define FID ((int)(P.map[blockIdx.x] >> 8))
DEVI uint32_t uni(uint32_t v) { return __shfl_sync(0xffffffffu, v, 0); }
#define PQ_N 8
#define PQ_T 700
#define PF0_N 10
#define PF0_T 1600
#define PF1_E 24
#define PF1_T 1100
#define POL_Q1 POL_NORMAL
#define POL_X POL_NORMAL
#define PFA0_BAR 3
#define PFA1_BAR 0
#define PFA0_M 0
#define PFA1_M 0
#define PFA0_T 900
#define PFA1_T 700
#define PF1_S PF0_N
#define PF1_D 0
#define POL_G POL_NORMAL
#define POL_U POL_FIRST
#define POL_D POL_FIRST
#define JQ_N 6
#define WDSRC (P.wd + (size_t)min(fid, 111) * 32768)
#define WDSRC2 (P.wd + FID * 32768)
#define WD_N 4
#define THR_N 5
#define KV_D 1800
#define XD_D 300
#define W0_BAR 3
#define QEF_N 99
#define PACE_T 300
#define IDLE_T 11000
#define LATE_C 2
#define LATE_B B_XFREE + 1
#define LATE_P 0
#define KV_D1 200
#define KV_D2 1200
#define KV_DL 0
#define POL_KV0 POL_FIRST
#define POL_KV1 POL_FIRST
#define POL_O0 POL_FIRST
#define POL_O1 POL_FIRST
#define POL_W0 POL_NORMAL
#define POL_W1 POL_FIRST
#define POL_T POL_FIRST
#define U_C 8
#define ST_M 0
#define POL_Q0 POL_NORMAL
constexpr float LN_EPS = 1e-5f;
constexpr float QSCALE = 0.17677669529663687f * 1.4426950408889634f;

DEVI void fma8(float (&a)[8], uint4 v, float h) {
  a[0] = fmaf(bf_lo(v.x), h, a[0]); a[1] = fmaf(bf_hi(v.x), h, a[1]); a[2] = fmaf(bf_lo(v.y), h, a[2]); a[3] = fmaf(bf_hi(v.y), h, a[3]);
  a[4] = fmaf(bf_lo(v.z), h, a[4]); a[5] = fmaf(bf_hi(v.z), h, a[5]); a[6] = fmaf(bf_lo(v.w), h, a[6]); a[7] = fmaf(bf_hi(v.w), h, a[7]);
}
DEVI uint4 ldsv128(uint32_t a) { uint4 v; asm volatile("ld.volatile.shared.v4.u32 {%0,%1,%2,%3}, [%4];" : "=r"(v.x), "=r"(v.y), "=r"(v.z), "=r"(v.w) : "r"(a) : "memory"); return v; }
DEVI float ldsv32f(uint32_t a) { float v; asm volatile("ld.volatile.shared.f32 %0, [%1];" : "=f"(v) : "r"(a) : "memory"); return v; }
DEVI uint32_t clk() { uint32_t t; asm volatile("mov.u32 %0, %%clock;" : "=r"(t)); return t; }
DEVI int fresh_tid() { int t; asm volatile("mov.u32 %0, %%tid.x;" : "=r"(t)); return t & 127; }
DEVI float fold8(const float (&a)[8]) {
  const int lane = threadIdx.x & 31;
  const bool u = lane & 16, v = lane & 8, x = lane & 4;
  float b0 = (u ? a[4] : a[0]) + __shfl_xor_sync(0xffffffffu, u ? a[0] : a[4], 16), b1 = (u ? a[5] : a[1]) + __shfl_xor_sync(0xffffffffu, u ? a[1] : a[5], 16);
  float b2 = (u ? a[6] : a[2]) + __shfl_xor_sync(0xffffffffu, u ? a[2] : a[6], 16), b3 = (u ? a[7] : a[3]) + __shfl_xor_sync(0xffffffffu, u ? a[3] : a[7], 16);
  float c0 = (v ? b2 : b0) + __shfl_xor_sync(0xffffffffu, v ? b0 : b2, 8), c1 = (v ? b3 : b1) + __shfl_xor_sync(0xffffffffu, v ? b1 : b3, 8);
  return (x ? c1 : c0) + __shfl_xor_sync(0xffffffffu, x ? c0 : c1, 4);
}
DEVI float swiglu(float g, float u) { g = bf_round(g); return bf_round(bf_round(__fdividef(g, 1.f + __expf(-g))) * bf_round(u)); }

template<int J0, int J1> DEVI void exp_pack(const float (&s)[32], uint32_t (&p)[16]) {
  #pragma unroll
  for (int j = J0; j < J1; j++) p[j] = pack_bf16(ex2f(s[2 * j]), ex2f(s[2 * j + 1]));
}
DEVI bool attn_pack(const float (&o)[20], uint32_t (&ob)[8]) {
  const float lo = 5.421010862427522e-20f, hi = 1.8446744073709552e19f;
  float i0, i1; asm("rcp.approx.ftz.f32 %0, %1;" : "=f"(i0) : "f"(o[16])); asm("rcp.approx.ftz.f32 %0, %1;" : "=f"(i1) : "f"(o[18]));
  #pragma unroll
  for (int e = 0; e < 8; e++) ob[e] = pack_bf16(o[2 * e] * ((e & 1) ? i1 : i0), o[2 * e + 1] * ((e & 1) ? i1 : i0));
  return __all_sync(0xffffffffu, o[16] >= lo && o[16] <= hi && o[18] >= lo && o[18] <= hi);
}
DEVI void attn_store(const uint32_t (&ob)[8], bool ok, uint32_t st, uint32_t sb, uint32_t bar) {
  stsm_x4(ok ? st : sb + DUMP, ob[0], ob[1], ob[2], ob[3]); stsm_x4(ok ? st ^ 32 : sb + DUMP, ob[4], ob[5], ob[6], ob[7]);
  __syncwarp();
  asm volatile("{\n.reg .pred p, q;\nelect.sync _|q, 0xffffffff;\nsetp.ne.and.u32 p, %1, 0, q;\n@p mbarrier.arrive.shared::cta.b64 _, [%0];\n}" :: "r"(bar), "r"((uint32_t)ok) : "memory");
}
DEVI void attn_exact(uint32_t st, uint32_t kv, int t, bool hasprev, uint32_t bar) {
  const int lane = threadIdx.x & 31;
  #pragma unroll 1
  for (int row = ((threadIdx.x >> 5) & 3) * 16, n = 0; n < 16; n++, row++) {
    const int k1 = 256 + t * 64 + row;
    float m = -INFINITY, l = 0.f, o = 0.f;
    #pragma unroll 1
    for (int k0 = hasprev ? k1 - 255 : 256; k0 <= k1; k0 += 32) {
      const int k = min(k0 + lane, k1), r = k & 63;
      float sc = 0.f;
      #pragma unroll 1
      for (int c = 0; c < 16; c++) {
        uint32_t a = lds32(st + row * 64 + ((c * 4) ^ ((row & 6) << 3))), b = lds32(kv + (k >> 6) * 8192 + r * 64 + ((c * 4) ^ ((r & 6) << 3)));
        sc = fmaf(bf_lo(a), bf_lo(b), fmaf(bf_hi(a), bf_hi(b), sc));
      }
      float mn = fmaxf(m, sc);
      #pragma unroll 1
      for (int x = 16; x; x >>= 1) mn = fmaxf(mn, __shfl_xor_sync(0xffffffffu, mn, x));
      const float al = ex2f(m - mn), pr = ex2f(sc - mn);
      m = mn; l *= al; o *= al;
      #pragma unroll 1
      for (int q = k0; q <= min(k0 + 31, k1); q++) {
        const float z = __shfl_sync(0xffffffffu, pr, q - k0);
        uint32_t b = lds32(kv + (q >> 6) * 8192 + 4096 + (q & 63) * 64 + (((lane >> 1) * 4) ^ ((q & 6) << 3)));
        l += z; o = fmaf(z, (lane & 1) ? bf_hi(b) : bf_lo(b), o);
      }
    }
    __syncwarp();
    sts16(st + row * 64 + ((lane * 2) ^ ((row & 6) << 3)), pack_bf16(__fdividef(o, l), 0.f));
  }
  warp_signal(bar);
}

template<int K0, int K1, int DONE = 0> DEVI void exp_pv(const float (&s)[32], uint32_t (&p)[16], float (&o)[20], uint32_t vd, bool accum) {
  #pragma unroll
  for (int ks = K0; ks < K1; ks++) {
    if (ks >= DONE) {
      #pragma unroll
      for (int j = 4 * ks; j < 4 * ks + 4; j++) p[j] = pack_bf16(ex2f(s[2 * j]), ex2f(s[2 * j + 1]));
    }
    asm volatile("" : "+r"(p[4 * ks]), "+r"(p[4 * ks + 1]), "+r"(p[4 * ks + 2]), "+r"(p[4 * ks + 3]));
    wg_fence();
    wgmma_rs_n40<1>(o, p[ks * 4], p[ks * 4 + 1], p[ks * 4 + 2], p[ks * 4 + 3], mkd<HI64>(vd + VOFF(ks * 64)), ks ? 1 : accum);
  }
}
template<int K0, int K1> DEVI void exp_pv2(const float (&s)[32], const float (&sx)[32], uint32_t (&p)[16], uint32_t (&px)[16], float (&o)[20], uint32_t v0, uint32_t v4,
                  const uint32_t (&msk)[9], int tdiag) {
  #pragma unroll
  for (int ks = K0; ks < K1; ks++) {
    #pragma unroll
    for (int j = 4 * ks; j < 4 * ks + 4; j++) {
      const int c = 8 * (j >> 1) - 8 * (j & 1);
      const uint32_t e = pack_bf16(ex2f(c > tdiag ? s[2 * j] : sx[2 * j]), ex2f(c + 1 > tdiag ? s[2 * j + 1] : sx[2 * j + 1])), m = msk[(j >> 1) - (j & 1) + 1];
      p[j] = e & m; px[j] = e & ~m;
      asm volatile("" : "+r"(p[j]), "+r"(px[j]));
    }
    wg_fence();
    wgmma_rs_n40<1>(o, p[ks * 4], p[ks * 4 + 1], p[ks * 4 + 2], p[ks * 4 + 3], mkd<HI64>(v0 + VOFF(ks * 64)), 1);
    wgmma_rs_n40<1>(o, px[ks * 4], px[ks * 4 + 1], px[ks * 4 + 2], px[ks * 4 + 3], mkd<HI64>(v4 + VOFF(ks * 64)), 1);
  }
}

template<int J0> DEVI void qkv_store(const float (&a)[96], float p0, float p1, uint32_t d) {
  #pragma unroll
  for (int hh = 0; hh < 2; hh++) {
    const int j = 4 * (J0 + 2 * hh);
    stsm_x4(d ^ (hh << 5), pack_bf16(a[j] * p0, a[j + 1] * p0), pack_bf16(a[j + 2] * p1, a[j + 3] * p1),
                           pack_bf16(a[j + 4] * p0, a[j + 5] * p0), pack_bf16(a[j + 6] * p1, a[j + 7] * p1));
  }
}
DEVI void mean_step(float (&a)[96], float m0, float m1, uint32_t cd, bool z) {
  const uint32_t u0 = z ? 0u : __float_as_uint(m0), u1 = z ? 0u : __float_as_uint(m1);
  uint32_t ma[4] = {__byte_perm(u0, 0u, 0x1010), __byte_perm(u1, 0u, 0x1010), __byte_perm(u0, 0u, 0x3232), __byte_perm(u1, 0u, 0x3232)};
  keep(ma);
  wg_fence();
  wgmma_rs_n192<1>(a, ma[0], ma[1], ma[2], ma[3], mkd<2>(cd), 1);
  wg_commit();
}

template<bool FIRST> DEVI void qkv_block(float (&aX)[96], float (&aY)[96], uint32_t sb16, int s, int tX, int tY) {
  uint32_t a16 = sb16 + (qa_off(s) >> 4), b16 = (sb16 + (qb_off(s) >> 4)) | ((8192u >> 4) << 16);
  uint32_t ax = (a16 + tX * 512) | 0x10000u, ay = (a16 + tY * 512) | 0x10000u;
  wg_fence();
  #pragma unroll
  for (int ks = 0; ks < 4; ks++) {
    wgmma_ss_n192<1>(aX, mkd<HI128>(ax + ks * 2), mkd<HI128>(b16 + ks * 128), !(FIRST && ks == 0));
    wgmma_ss_n192<1>(aY, mkd<HI128>(ay + ks * 2), mkd<HI128>(b16 + ks * 128), !(FIRST && ks == 0));
  }
  wg_commit();
}
DEVI void qkv_half(float (&a)[96], uint32_t sb16, int t, uint32_t sa, uint32_t sbb) {
  wg_fence();
  #pragma unroll
  for (int ks = 0; ks < 4; ks++)
    wgmma_ss_n192<1>(a, mkd<HI128>(((sb16 + (sa >> 4) + t * 512) | 0x10000u) + ks * 2), mkd<HI128>(((sb16 + (sbb >> 4)) | ((8192u >> 4) << 16)) + ks * 128), 1);
  wg_commit();
}
DEVI void wo_block(float (&acc)[64], uint32_t sb16, int s, int wg) {
  uint32_t a16 = (sb16 + (w_off(s) >> 4) + wg * 256) | 0x10000u, b16 = (sb16 + (w_off(s) >> 4) + 1024) | ((8192u >> 4) << 16);
  wg_fence();
  #pragma unroll
  for (int ks = 0; ks < 4; ks++)
    wgmma_ss_n128<1>(acc, mkd<HI64>(a16 + (ks >> 1) * 512 + (ks & 1) * 2), mkd<HI128>(b16 + ks * 128), 1);
  wg_commit();
}
DEVI void consumer(const Params& P, uint32_t sb, int wg) {
  const int w = uni((threadIdx.x >> 5) & 3);
  #define LAYER uni(mbar_test(BAR(B_XRDY + wg * 2 + 1), 0))
  #define IDS L = LAYER; const int tid = fresh_tid(), lane = tid & 31
  const uint32_t ids = uni(P.map[blockIdx.x]);
  const int bi = (ids >> 4) & 7, rh = ids & 1, bc = (ids & 15) >> 1, fid = ids >> 8;
  const int tX = 3 - wg, tY = wg;
  constexpr uint32_t sb16 = 1024 >> 4;
  #pragma unroll 1
  while (true) {
    int L = LAYER;
    float2 fa, fb;
    {
      float aX[96], aY[96];
      const bool lead = fresh_tid() == 0;
      mbar_wait(BAR(B_FULLQ), 0);
      PROFW(threadIdx.x == 0, L * 8 + 1);
      qkv_block<true>(aX, aY, sb16, 0, tX, tY);
      #pragma unroll 1
      for (int n = 1, s = 1, ps = 0, ph = 0; n < 14; n++) {
        mbar_wait(BAR(B_FULLQ + s), ph ^ (s ? L : 0));
        PROFD(threadIdx.x == 0 && L && (n == 2 || n == 3 || n == 7 || n == 11 || n == 13), n == 2 ? 48 : 49 + (n >> 2));
        qkv_block<false>(aX, aY, sb16, s, tX, tY);
        wg_wait<1>(); if (lead) mbar_arrive(BAR(B_EMPTYQ + ps));
        ps = s; if (s == 2) { s = 0; ph ^= 1; } else s++;
      }
      mbar_wait(BAR(B_FULLQ + 2), L);
      qkv_half(aX, sb16, tX, SA2, SB2);
      mbar_wait(BAR(B_ROW), L);
      IDS;
      const uint32_t pa = sb + PAR + (w * 16 + (lane >> 2)) * 8;
      float2 p0 = lds64f(pa + tX * 512), p1 = lds64f(pa + tX * 512 + 64), p2 = lds64f(pa + tY * 512), p3 = lds64f(pa + tY * 512 + 64);
      mean_step(aX, p0.y, p1.y, sb16 + (CS >> 4), lane & 3);
      mbar_wait(BAR(B_FULLQ), 1);
      qkv_half(aX, sb16, tX, 0, SB0);
      wg_wait<3>(); if (lead) mbar_arrive(BAR(B_EMPTYQ + 1));
      bar_sync(1, 256);
      qkv_half(aY, sb16, tY, SA2, SB2);
      wg_wait<1>(); keep(aX);
      const int srow = w * 16 + (lane & 15);
      const uint32_t x0 = sb + srow * 64 + (((lane >> 4) ^ ((srow >> 1) & 3)) << 4), xX = x0 + (4 + tX) * 8192, xY = x0 + (4 + tY) * 8192;
      qkv_store<8>(aX, p0.x, p1.x, xX + KVA); qkv_store<16>(aX, p0.x, p1.x, xX + KVA + 4096);
      warp_signal(BAR(B_KVRDY + wg * 2));
      qkv_half(aY, sb16, tY, 0, SB0);
      mean_step(aY, p2.y, p3.y, sb16 + (CS >> 4), fresh_tid() & 3);
      wg_wait<2>(); if (lead) mbar_arrive(BAR(B_EMPTYQ + 2));
      mbar_wait(BAR(B_EMPTYQ + 2), L);
      qkv_store<12>(aX, p0.x, p1.x, xX + KVB); qkv_store<20>(aX, p0.x, p1.x, xX + KVB + 4096);
      wg_wait<0>(); keep(aY);
      if (lead) mbar_arrive(BAR(B_EMPTYQ));
      PROFW(threadIdx.x == 0, L * 8 + 2);
      qkv_store<8>(aY, p2.x, p3.x, xY + KVA); qkv_store<16>(aY, p2.x, p3.x, xY + KVA + 4096);
      qkv_store<12>(aY, p2.x, p3.x, xY + KVB); qkv_store<20>(aY, p2.x, p3.x, xY + KVB + 4096);
      warp_signal(BAR(B_KVRDY + wg * 2 + 1));
      p0.x *= QSCALE; p1.x *= QSCALE; p2.x *= QSCALE; p3.x *= QSCALE;
      mbar_wait(BAR(B_EMPTYQ), 1);
      qkv_store<0>(aX, p0.x, p1.x, x0 + QO + tX * 4096);
      qkv_store<0>(aY, p2.x, p3.x, x0 + QO + tY * 4096); qkv_store<4>(aY, p2.x, p3.x, x0 + QO + 16384 + tY * 4096);
      { const float2* f = (const float2*)&P.g->statF[bi * 256 + rh * 128 + (wg ^ rh) * 64 + w * 16 + (lane >> 2)]; fa = __ldcg(f); fb = __ldcg(f + 16); }
      mbar_wait(BAR(B_PAR), L);
      qkv_store<4>(aX, p0.x, p1.x, x0 + QO + 16384 + tX * 4096);
      const int prow = (int)uni(lds32(sb + INFO)) - bi * 256;
      if ((prow >> 4) == tX * 4 + w || (prow >> 4) == tY * 4 + w) {
        __syncwarp();
        if (lane < 24) sts128(sb + (prow & 63) * 64 + (((lane ^ (prow >> 1)) & 3) << 4) +
                              (lane < 8 ? QO + (lane >> 2) * 16384 + (prow >> 6) * 4096 : ((lane & 4) ? KVB : KVA) + (4 + (prow >> 6)) * 8192 + (lane >> 4) * 4096),
                              lds128(sb + PATCH + lane * 16));
      }
      fence_async_smem();
      bar_sync(1, 256);
    }
    PROFW(threadIdx.x == 0, L * 8 + 3);
    {
      IDS;
      float s0[32], s1[32], sx[32], o[20], op[20];
      uint32_t p0[16], p1[16], px[16], msk[9];
      const int tdiag = w * 16 + (lane >> 2) - 2 * (lane & 3);
      const uint32_t ones = (sb16 + (ONES >> 4)) << 16;
      const uint32_t qX = (sb16 + (QO >> 4) + tX * 256) | 0x10000u, qY = (sb16 + (QO >> 4) + tY * 256) | 0x10000u;
      const uint32_t kXB = (sb16 + (KVB >> 4) + tX * 512) | 0x10000u;
      uint32_t redo = 0;
      const uint32_t ost = sb + QO + (w * 16 + (lane & 15)) * 64 + (((lane >> 4) ^ ((lane >> 1) & 3)) << 4);
      #define QA(s, q, k) do { wg_fence(); wgmma_ss_n64<0>(s, mkd<HI64>(q), mkd<HI64>(k), 0); } while (0)
      #define QB(s, q, k) wgmma_ss_n64<0>(s, mkd<HI64>((q) + 2), mkd<HI64>((k) + 2), 1)
      #define QA2(q, k) do { QA(s1, q, k); wgmma_ss_n64<0>(sx, mkd<HI64>(q), mkd<HI64>((k) + 2048), 0); } while (0)
      #define QB2(q, k) do { QB(s1, q, k); QB(sx, q, (k) + 2048); } while (0)
      #define VB(v, b) ((v) + VOFF((b) * 512))
      #define MID() do { wg_commit(); wg_wait<1>(); } while (0)
      QA(s0, qX + 1024, kXB + 1536); QB(s0, qX + 1024, kXB + 1536); wg_commit();
      #pragma unroll
      for (int e = 0; e < 20; e++) o[e] = 0.f;
      wg_wait<0>(); keep(s0);
      #pragma unroll 1
      for (int h = 1; h >= 0; h--) {
        const uint32_t kXA = kXB - ((KVB - KVA) >> 4), kX = h ? kXB : kXA, vX = VOFF((kX & 0xffffu) + 256) + ones;
        QA(s1, qX + h * 1024, kX + 1024);
        #pragma unroll
        for (int e = 0; e < 20; e++) op[e] = o[e];
        keep(op);
        exp_pv<0, 1>(s0, p0, o, VB(vX, 3), false); QB(s1, qX + h * 1024, kX + 1024); wg_commit();
        exp_pv<1, 2>(s0, p0, o, VB(vX, 3), true); MID(); keep(s1);
        exp_pv<2, 4>(s0, p0, o, VB(vX, 3), true);
        { int td = tdiag; asm volatile("" : "+r"(td));
          #pragma unroll
          for (int e = 0; e < 9; e++) msk[e] = ((8 * e - 8 > td) ? 0xFFFFu : 0u) | ((8 * e - 7 > td) ? 0xFFFF0000u : 0u);
          keep(msk); }
        exp_pv<0, 2>(s1, p1, o, VB(vX, 2), true);
        bar_sync(h ? 12 + wg : 4 + wg * 4, h ? 128 : 160);
        QA(s0, qX, kXA + 512 + h * 1024);
        exp_pv<2, 3>(s1, p1, o, VB(vX, 2), true); QB(s0, qX, kXA + 512 + h * 1024);
        exp_pv<3, 4>(s1, p1, o, VB(vX, 2), true); wg_commit();
        wg_wait<0>(); keep(s0); keep(p0); keep(p1); keep(o);
      }
      #pragma unroll 1
      for (int h = 0; h < 2; h++) {
        const uint32_t kb16 = sb16 + ((h ? KVB : KVA) >> 4), kX = (kb16 + tX * 512) | 0x10000u, kY = (kb16 + tY * 512) | 0x10000u, qx = qX + h * 1024, qy = qY + h * 1024;
        const uint32_t onesP = bi ? ones : (kb16 + 1984) << 16;
        const uint32_t vX = VOFF(kb16 + tX * 512 + 256), vY = VOFF(kb16 + tY * 512 + 256);
        uint32_t ob[8], v;
        v = VB(vX + (wg ? onesP : ones), 1);
        QA2(qx, kX);
        exp_pv<0, 1>(s0, p0, o, v, true); QB2(qx, kX); wg_commit();
        exp_pv<1, 2>(s0, p0, o, v, true); MID(); keep(s1); keep(sx);
        exp_pv<2, 4>(s0, p0, o, v, true);
        QA(s0, qy, kY + 1536);
        exp_pv2<0, 1>(s1, sx, p1, px, o, vX + onesP, VB(vX + ones, 4), msk, tdiag); QB(s0, qy, kY + 1536); wg_commit();
        exp_pv2<1, 2>(s1, sx, p1, px, o, vX + onesP, VB(vX + ones, 4), msk, tdiag); MID(); keep(s0); keep(p0);
        exp_pv2<2, 4>(s1, sx, p1, px, o, vX + onesP, VB(vX + ones, 4), msk, tdiag); wg_commit();
        v = VB(vY + (wg ? ones : onesP), 3);
        QA(s1, qy, kY + 1024);
        exp_pack<0, 4>(s0, p0);
        QB(s1, qy, kY + 1024); MID(); keep(o); keep(p1); keep(px);
        bool ok = attn_pack(o, ob); keep(ob);
        exp_pv<0, 2, 1>(s0, p0, o, v, false); MID(); keep(s1);
        attn_store(ob, ok, ost + (h * 4 + tX) * 4096, sb, BAR(B_ORDY + wg * 4 + h * 2)); redo |= ok ? 0u : 1u << (h * 2);
        exp_pv<2, 4>(s0, p0, o, v, true);
        v = VB(vY + onesP, 2);
        exp_pv<0, 1>(s1, p1, o, v, true);
        bar_sync(5 + wg * 4 + h * 2, 160);
        QA(s0, qy, kY + 512);
        exp_pv<1, 2>(s1, p1, o, v, true); QB(s0, qy, kY + 512); wg_commit();
        exp_pv<2, 3>(s1, p1, o, v, true); MID(); keep(s0); keep(p0);
        exp_pv<3, 4>(s1, p1, o, v, true);
        v = VB(vY + onesP, 1);
        QA2(qy, kY);
        exp_pv<0, 1>(s0, p0, o, v, true); QB2(qy, kY); wg_commit();
        exp_pv<1, 2>(s0, p0, o, v, true); MID(); keep(s1); keep(sx); keep(p1);
        exp_pv<2, 4>(s0, p0, o, v, true);
        exp_pv2<0, 1>(s1, sx, p1, px, o, vY + onesP, VB(vY + ones, 4), msk, tdiag);
        bar_sync(6 + wg * 4, h ? 128 : 160);
        QA(s0, h ? qy : qX + 1024, kXB + 512);
        exp_pv2<1, 2>(s1, sx, p1, px, o, vY + onesP, VB(vY + ones, 4), msk, tdiag); QB(s0, h ? qy : qX + 1024, kXB + 512);
        exp_pv2<2, 4>(s1, sx, p1, px, o, vY + onesP, VB(vY + ones, 4), msk, tdiag); wg_commit();
        wg_wait<0>(); keep(o); keep(s0); keep(p0); keep(p1); keep(px);
        ok = attn_pack(o, ob); attn_store(ob, ok, ost + (h * 4 + tY) * 4096, sb, BAR(B_ORDY + wg * 4 + h * 2 + 1)); redo |= ok ? 0u : 2u << (h * 2);
        #pragma unroll
        for (int e = 0; e < 20; e++) o[e] = op[e];
      }
      #undef QA
      #undef QB
      #undef QA2
      #undef QB2
      #undef VB
      #undef MID
      if (redo) {
        #pragma unroll 1
        for (int u = 0; u < 4; u++) if ((redo >> u) & 1) {
          const int h = u >> 1, t = (u & 1) ? tY : tX;
          attn_exact(sb + QO + (h * 4 + t) * 4096, sb + (h ? KVB : KVA), t, bi > 0, BAR(B_ORDY + wg * 4 + u));
        }
      }
    }
    PROFW(threadIdx.x == 0, L * 8 + 4);
    {
      IDS;
      const int t256 = wg * 128 + tid;
      float acc[64];
      const int tt = wg ^ rh;
      const int grow = bi * 256 + rh * 128 + tt * 64 + w * 16 + (lane >> 2);
      float al0 = 1.f, be0 = 0.f, al1 = 1.f, be1 = 0.f;
      const int idx0 = (int)uni(lds32(sb + INFO));
      const uint32_t tag = lds32(sb + INFO + 8) + L;
      uint4* const sp = &P.g->statP[bc][grow + (lane & 1) * 8];
      uint4* const yp = &P.g->yP[t256 >> 1][min(fid, 111)][t256 & 1];
      if (L) {
        float r0 = rsqrtf(fa.y + LN_EPS), r1 = rsqrtf(fb.y + LN_EPS);
        if (grow != idx0) { al0 = 1.f + r0; be0 = -fa.x * r0; }
        if (grow + 8 != idx0) { al1 = 1.f + r1; be1 = -fb.x * r1; }
      }
      const int srow = tt * 64 + w * 16 + (lane & 15);
      const uint32_t ra = sb + srow * 128 + (((lane >> 4) ^ (srow & 7)) << 4);
      mbar_wait(BAR(B_FULLW + 5), L);
      if ((idx0 >> 4) == bi * 16 + rh * 8 + tt * 4 + w) {
        int r = idx0 & 127;
        if (lane < 16) sts128(sb + 32768 + (lane >> 3) * 16384 + r * 128 + (((lane & 7) ^ (r & 7)) << 4), lds128(sb + X2SEG + lane * 16));
        fence_async_smem();
        __syncwarp();
      }
      #pragma unroll
      for (int jj = 0; jj < 8; jj++) {
        uint32_t r[4]; ldsm_x4((ra + 32768 + (jj >> 2) * 16384) ^ ((jj & 3) << 5), r[0], r[1], r[2], r[3]);
        #pragma unroll
        for (int e = 0; e < 4; e++) {
          acc[8 * jj + 2 * e] = fmaf(bf_lo(r[e]), (e & 1) ? al1 : al0, (e & 1) ? be1 : be0);
          acc[8 * jj + 2 * e + 1] = fmaf(bf_hi(r[e]), (e & 1) ? al1 : al0, (e & 1) ? be1 : be0);
        }
      }
      keep(acc);
      bar_sync(12 + wg, 128);
      if (!(lane & 2)) st_ll(sp, 0u, 0u, 0u, 0u);
      uint2 wd[4];
      #pragma unroll
      for (int e = 0; e < 4; e++) { wd[e] = make_uint2(0u, 0u); if (L) wd[e] = ldg_stream((const uint2*)(WDSRC) + t256 + (28 + e) * 256); }
      PROFW(t256 == 0, L * 8 + 5);
      #pragma unroll 1
      for (int n = 0, q = 0, pq = 5; n < 16; n++) {
        mbar_wait(BAR(B_FULLW + q), w_par(n, q, L));
        PROFD(t256 == 0 && !L && (n == 4 || n == 7 || n == 8 || n == 12), (n == 7 ? 63 : 41 + (n >> 2)));
        wo_block(acc, sb16, q, tt);
        wg_wait<1>(); if (tid == 0) mbar_arrive(BAR(B_EMPTYW + pq));
        pq = q; q = w_next(n, q);
      }
      mbar_wait(BAR(B_EMPTYW + 5), L);
      wg_wait<0>(); keep(acc);
      if (tid == 0) mbar_arrive(BAR(B_EMPTYW + 4));
      PROFW(t256 == 0, L * 8 + 6);
      {
        float s1a = 0.f, s2a = 0.f, da = 0.f, s1b = 0.f, s2b = 0.f, db = 0.f;
        #pragma unroll
        for (int j = 0; j < 16; j++) {
          const float* a = acc + 4 * j; float2 wv = lds64f(sb + WR + j * 32 + (lane & 3) * 8);
          s1a += a[0] + a[1]; s1b += a[2] + a[3];
          s2a = fmaf(a[0], a[0], s2a); s2b = fmaf(a[2], a[2], s2b); s2a = fmaf(a[1], a[1], s2a); s2b = fmaf(a[3], a[3], s2b);
          da = fmaf(a[0], wv.x, da); db = fmaf(a[2], wv.x, db); da = fmaf(a[1], wv.y, da); db = fmaf(a[3], wv.y, db);
        }
        bool odd = lane & 1;
        float u1 = (odd ? s1b : s1a) + __shfl_xor_sync(0xffffffffu, odd ? s1a : s1b, 1);
        float u2 = (odd ? s2b : s2a) + __shfl_xor_sync(0xffffffffu, odd ? s2a : s2b, 1);
        float u3 = (odd ? db : da) + __shfl_xor_sync(0xffffffffu, odd ? da : db, 1);
        u1 += __shfl_xor_sync(0xffffffffu, u1, 2); u2 += __shfl_xor_sync(0xffffffffu, u2, 2); u3 += __shfl_xor_sync(0xffffffffu, u3, 2);
        if (!(lane & 2)) st_ll(sp, __float_as_uint(u1), __float_as_uint(u2), __float_as_uint(u3), tag);
      }
      const uint32_t xa = ra + rh * 16384;
      #pragma unroll
      for (int jj = 0; jj < 8; jj++) {
        const float* a = acc + 8 * jj;
        stsm_x4((xa + (jj >> 2) * 32768) ^ ((jj & 3) << 5), pack_bf16(a[0], a[1]), pack_bf16(a[2], a[3]), pack_bf16(a[4], a[5]), pack_bf16(a[6], a[7]));
        if (jj == 7) fence_async_smem();
        if ((jj & 3) == 3) warp_signal(BAR(B_XRDY + wg * 2 + (jj >> 2)));
      }
      PROFW(t256 == 0, L * 8 + 7);
      if (L) {
        mbar_wait(BAR(B_PAR), 0);
        { float2 pa = lds64f(sb + PAR + (grow & 127) * 8), pb = lds64f(sb + PAR + (grow & 127) * 8 + 64); al0 = pa.x; be0 = pa.y; al1 = pb.x; be1 = pb.y; }
        uint32_t rs[32];
        #pragma unroll
        for (int j = 0; j < 16; j++) {
          rs[2 * j] = pack_bf16(fmaf(acc[4 * j], al0, be0), fmaf(acc[4 * j + 1], al0, be0));
          rs[2 * j + 1] = pack_bf16(fmaf(acc[4 * j + 2], al1, be1), fmaf(acc[4 * j + 3], al1, be1));
        }
        #pragma unroll
        for (int jj = 0; jj < 8; jj++) stsm_x4((xa + (jj >> 2) * 32768) ^ ((jj & 3) << 5), rs[4 * jj], rs[4 * jj + 1], rs[4 * jj + 2], rs[4 * jj + 3]);
        PROFW(t256 == 0, 16);
        if (fid >= 112) bar_arrive(3, 384);
        else {
          float d[4] = {0.f, 0.f, 0.f, 0.f};
          mbar_wait(BAR(B_FULLW + wg * 3), 0); mbar_wait(BAR(B_FULLW + wg * 3 + 1), 0);
          bar_sync(3, 384);
          PROFW(t256 == 0, 29);
          #pragma unroll 1
          for (int g = 0; g < 4; g++) {
            const uint32_t ad = (sb16 + (wg ? 6144 : 10240) + (g >> 1) * 2048 + (g & 1) * 512) | (1024u << 16), bd = (sb16 + (HV >> 4) + wg * 64 + g * 16) | 0x10000u;
            wg_fence();
            #pragma unroll
            for (int ks = 0; ks < 8; ks++) wgmma_ss_n8<0, 1>(d, mkd<HI64>(ad + ks * 64), mkd<8>(bd + ks * 2), 1);
            wg_commit();
          }
          mbar_wait(BAR(B_FULLW + 2), 0);
          wg_wait<0>(); keep(d);
          if (!(lane & 3)) { sts32f(sb + PAR + 1024 + wg * 256 + w * 64 + lane, d[0]); sts32f(sb + PAR + 1056 + wg * 256 + w * 64 + lane, d[2]); }
          bar_sync(1, 256);
          const uint32_t ga = sb + PAR + 1024 + lane * 4, aa = sb + HV + (t256 >> 5) * 128;
          sts32f(aa + lane * 4, swiglu(lds32f(ga) + lds32f(ga + 256), lds32f(ga + 128) + lds32f(ga + 384)));
          __syncwarp();
          PROFW(t256 == 0, 26);
          float y0 = 0.f, y1 = 0.f, y2 = 0.f, y3 = 0.f;
          uint32_t tbl = rh ? 0x001459a8u : 0x023679a8u;
          uint4 a4 = lds128(aa + 112);
          #pragma unroll 2
          for (int n = 0; n < 8; n++, tbl >>= 4) {
            const uint32_t src = sb + t256 * 8 + (tbl & 15) * 8192;
            const uint4 an = lds128(aa + ((0x00123564u >> (4 * n)) & 15) * 16);
            #pragma unroll
            for (int e = 0; e < 4; e++) {
              const float av = __uint_as_float(e == 0 ? a4.x : (e == 1 ? a4.y : (e == 2 ? a4.z : a4.w)));
              y0 = fmaf(bf_lo(wd[e].x), av, y0); y1 = fmaf(bf_hi(wd[e].x), av, y1); y2 = fmaf(bf_lo(wd[e].y), av, y2); y3 = fmaf(bf_hi(wd[e].y), av, y3);
              const float2 v = lds64f(src + e * 2048); wd[e] = make_uint2(__float_as_uint(v.x), __float_as_uint(v.y));
            }
            a4 = an;
          }
          st_ll(yp, __float_as_uint(y0), __float_as_uint(y1), __float_as_uint(y2), (__float_as_uint(y3) & ~255u) | (lds32(sb + INFO + 12) + 1));
          PROFW(t256 == 0, 27);
        }
        return;
      }
      mbar_wait(BAR(B_XRDY + wg * 2 + 1), 0);
    }
  }
  #undef IDS
  #undef LAYER
}

DEVI void loader(const Params& P, uint32_t sb) {
  const int lane = threadIdx.x & 31;
  const int bid = uni(BID), bi = bid >> 4, bp = bid & 15, rh = bp & 1, bc = bp >> 1;
  uint32_t phq = 0, tag = 0;
  #pragma unroll 1
  for (int L = 0; L < 2; L++) {
    int s = 0;
    uint32_t rdy = 0;
    #pragma unroll 1
    for (int n = L ? 0 : 3; n < 16; n++) {
      int kb = L ? kb_order(bc, n) : n;
      mbar_wait(BAR(B_EMPTYQ + s), (phq >> s) & 1);
      phq ^= 1u << s;
      if (L && n == 1) { mbar_wait(BAR(B_XRDY + 1), 0); mbar_wait(BAR(B_XRDY + 3), 0); }
      if (elect()) {
        mbar_expect_tx(BAR(B_FULLQ + s), L && n < 2 ? 40960 : 57344);
        tma_3d_h(sb + qb_off(s), &P.mWq, bp * 64, kb * 64, 0, BAR(B_FULLQ + s), L && n >= QEF_N ? POL_FIRST : POL_NORMAL);
        if (!L) tma_2d(sb + qa_off(s), &P.mX, kb * 64, bi * 256, BAR(B_FULLQ + s));
      }
      if (L && n >= 2) {
        if (((rdy >> (2 * kb)) & 3) != 3) {
          do { rdy = __ballot_sync(0xffffffffu, ld_rlx(&P.g->flagX[bi][lane]) == tag); } while (((rdy >> (2 * kb)) & 3) != 3);
          fence_async_glob();
        }
        if (n == 3 || n == 4) mbar_wait(BAR(B_XFREE + n - 3), 0);
        if (elect()) bulk_g2s_h(sb + qa_off(s), P.g->x[bi][kb], 32768, BAR(B_FULLQ + s), POL_X);
      }
      PROFY(L && lane == 0 && (n == 2 || n == 3 || n == 9), n == 9 ? 60 : 56 + n);
      if (L && n == 2) { mbar_wait(BAR(B_FULLQ), 0); mbar_wait(BAR(B_FULLQ + 1), 1); if (lane < 2) mbar_arrive_peer(BAR(B_XFREE + lane)); }
      s = (s == 2) ? 0 : s + 1;
    }
    for (int q = 0; q < 3; q++) mbar_wait(BAR(B_EMPTYQ + q), (phq >> q) & 1);
    tag = lds32(sb + INFO + 8) + L;
    #pragma unroll 1
    for (int q = 0; q < 4; q++) {
            if (bi) {
        const unsigned* f = &P.g->flagKV[bid - 16][q];
        while (ld_rlx(f) != tag);
        fence_async_glob();
      }
      if (elect()) {
        mbar_expect_tx(BAR(B_KVFULL + q), 16384);
        bulk_g2s_h(sb + ((q >> 1) ? KVB : KVA) + ((q & 1) ? 0 : 16384), bi ? P.g->kv[bid - 16][q] : P.g->zero, 16384, BAR(B_KVFULL + q), L ? POL_KV1 : POL_KV0);
      }
      PROFY(!L && lane == 0 && bi && q != 2, 34 + (q + 1) / 2);
    }
    mbar_wait(BAR(B_ORDY), L);
    {
      const uint4* src = P.g->o[bi][0][0][rh];
      rdy = 0;
      #pragma unroll 1
      for (int n = 0, q = 0; n < 16; q = w_next(n, q), n++) {
        const int j = wo_order(bc, n);
        if (((rdy >> (2 * j)) & 3) != 3) {
          do { rdy = __ballot_sync(0xffffffffu, ld_rlx(&P.g->flagO[bi][lane]) == tag); } while (((rdy >> (2 * j)) & 3) != 3);
          fence_async_glob();
        }
        if (n >= 2) mbar_wait(n < 5 ? BAR(B_HAFREE + (n > 2)) : BAR(B_EMPTYW + q), n < 5 ? L : w_par(n, q, L) ^ 1);
        if (n == THR_N) mbar_wait(BAR(B_OFREE), L);
        if (elect()) { mbar_expect_tx(BAR(B_FULLW + q), 16384); bulk_g2s_h(sb + w_off(q), src + j * 2048, 16384, BAR(B_FULLW + q), L ? POL_O1 : POL_O0); }
      }
    }
    mbar_wait(BAR(B_OFREE), L);
  }
}

DEVI void ffn_prefetch(const Params& P, int q) {
  bulk_prefetch(q < 16 ? ((q & 1) ? P.wu : P.wg) + ((q >> 1) * 128 + blockIdx.x) * 3584 : P.wd + (min(FID, 111) * 8 + q - 16) * 4096, q < 16 ? 7168 : 8192);
}
DEVI void storer(const Params& P, uint32_t sb, int wg) {
  const int bid = uni(BID), bi = bid >> 4, rh = bid & 1, bc = (bid & 15) >> 1;
  const bool one = (threadIdx.x & 31) == 0;
  char* const g = (char*)P.g;
  const uint32_t tag0 = uni(((ld_rlx(&P.g->epoch) % 16383u) + 1u) << 2);
  #pragma unroll 1
  for (int L = 0; L < 2; L++) {
    const uint32_t tag = tag0 + L;
    if (wg) {
      #pragma unroll 1
      for (int r = threadIdx.x & 31; r < 256; r += 32) {
        uint4 v;
        do v = ld_ll(&P.g->statF[bi * 256 + r]); while (!__all_sync(0xffffffffu, v.w == tag));
        float var = __uint_as_float(v.y), c = rsqrtf(var + LN_EPS);
        if (L) { c += 1.f; c *= rsqrtf(fmaf(var * c, c, LN_EPS)); }
        const float mh = bf_round(__uint_as_float(v.x));
        sts64f(sb + PAR + r * 8, c, __uint_as_float(pack_bf16(mh, __uint_as_float(v.x) - mh)));
      }
      if (!L) mbar_wait(BAR(B_PAR), 0);
      warp_signal(BAR(B_ROW));
    }
    #pragma unroll 1
    for (int u = 0; u < 2 + 4 * wg; u++) {
      const int h = u < 2 ? u : u >> 2, hi = (u & 1) ^ 1;
      uint32_t src, dst, fl, b0, b1;
      if (u < 2) {
        src = (h ? KVB : KVA) + (3 - wg) * 16384; dst = offsetof(Scratch, kv) + (bid * 4 + h * 2 + wg) * 16384; fl = offsetof(Scratch, flagKV) + (bid * 32 + h * 2 + wg) * 4;
        b0 = BAR(B_KVRDY + ((u | wg) ? 1 : 0)); b1 = b0 + 16;
      } else {
        src = QO + (h * 2 + hi) * 8192; dst = offsetof(Scratch, o) + ((((bi * 2 + h) * 8 + bc) * 2 + hi) * 2 + rh) * 8192;
        fl = offsetof(Scratch, flagO) + (bi * 32 + h * 16 + (bid & 15)) * 4;
        b0 = BAR(B_ORDY + u - 2); b1 = b0 + 32;
      }
      mbar_wait(b0, L); mbar_wait(b1, L);
      if (u + wg == 1) {
        mbar_wait(BAR(B_PAR), L);
        const uint32_t t0 = clk(), dt = (wg ? KV_D1 : KV_D2) + (L ? KV_DL : 0); while (clk() - t0 < dt) __nanosleep(40);
      }
      fence_async_smem();
      PROFY(one && !L && u == 3 * wg, u ? 46 : 8);
      if (one && (u >= 2 || bi < 7)) bulk_s2g(g + dst, sb + src, u < 2 ? 16384 : 8192, ((ST_M >> (L * 2 + (u >= 2))) & 1) ? POL_FIRST : POL_NORMAL);
      if (one && u == 5) mbar_arrive(BAR(B_HAFREE + 1));
      if (u == 2 || u == 4) continue;
      bulk_wait<0>();
      PROFY(one && !L && u == 3 * wg, u ? 61 : 62);
      fence_rel();
      if (one) { st_rlx((unsigned*)(g + fl), tag); if (!wg || u > 2) mbar_arrive(BAR(B_HAFREE + h + (wg & h))); }
      PROFY(one && !L && (u > 2 || u == wg), u > 2 ? (u == 3 ? 38 : 54) : 32 + u);
    }
    if (L == 0) {
      char* dst = g + (offsetof(Scratch, x) + (bi * 16 + 2 * bc) * 32768 + rh * 16384);
      unsigned* f = (unsigned*)(g + (offsetof(Scratch, flagX) + (bi * 32 + bc * 4 + rh) * 4));
      const uint32_t a = sb + rh * 16384;
      if (wg == 0) {
        mbar_wait(BAR(B_XRDY), 0); mbar_wait(BAR(B_XRDY + 2), 0);
        fence_async_smem();
        PROFY(one, 41);
        if (one) bulk_s2g(dst, a, 16384);
        bulk_wait<0>();
        PROFY(one, 45);
        if (one) { mbar_arrive(BAR(B_XFREE)); mbar_arrive(BAR(B_PFREE)); }
        fence_rel();
        mbar_wait(BAR(B_XRDY + 1), 0); mbar_wait(BAR(B_XRDY + 3), 0);
        if (one) { st_rlx(f, tag); bulk_s2g(dst + 32768, a + 32768, 16384); }
        PROFY(one, 56);
        bulk_wait<0>();
        if (one) mbar_arrive(BAR(B_XFREE + 1));
        fence_rel();
        if (one) st_rlx(f + 2, tag);
        PROFY(one, 57);
      } else {
        mbar_wait(BAR(B_XRDY + 1), 0); mbar_wait(BAR(B_XRDY + 3), 0);
        mbar_wait(BAR(B_PFREE), 0);
        if (one) bulk_s2peer(a, 16384, BAR(B_FULLQ));
        { const uint32_t t0 = clk(); while (clk() - t0 < XD_D); }
        if (one) bulk_s2peer(a + 32768, 16384, BAR(B_FULLQ + 1));
      }
      if (wg == 0) {
        uint32_t t0 = clk() + PF1_D;
        #pragma unroll 1
        for (int q = PF1_S; q < PF1_E; q++) { while ((int)(clk() - t0) < 0) __nanosleep(50); if (one) ffn_prefetch(P, q); t0 += PF1_T; }
      }
    }
  }
}

DEVI void stg_issue(const Params& P, int c, uint32_t d, uint32_t du, uint32_t b) {
  mbar_expect_tx(b, 16384);
  if (c < 8) { tma_2d_h(d, &P.mWg, FID * 32, c * 128, b, du > 8192 ? POL_T : POL_G); tma_2d_h(d + du, &P.mWu, FID * 32, c * 128, b, du > 8192 || c < U_C ? POL_FIRST : POL_NORMAL); }
  else if (c < 12) tma_3d_h(d, &P.mWd, 0, FID * 32 + (c - 8) * 8, 0, b, POL_D);
  else tma_2d_h(d, &P.mWp, (c - 12) * 1024 + (BID >> 2) * 32, (BID & 3) * 256, b, POL_EF);
}
DEVI void pace() { const uint32_t t0 = clk(); while (clk() - t0 < PACE_T); }
DEVI void stager(const Params& P, uint32_t sb) {
  {
    const int b = blockIdx.x;
    uint32_t t0 = clk();
    #pragma unroll 1
    for (int q = 0; q < PQ_N; q++) { bulk_prefetch(P.wqkv + (q * 128 + b) * 3072, 6144); while (clk() - t0 < PQ_T) __nanosleep(50); t0 += PQ_T; }
    bulk_prefetch(P.wo + b * 8192, 16384);
    #pragma unroll 1
    for (int q = 0; q < PF0_N; q++) {
      while (clk() - t0 < PF0_T) __nanosleep(50);
      t0 += PF0_T;
      ffn_prefetch(P, q);
    }
  }
  const int bid = BID, bi = bid >> 4, rh = bid & 1, bc = (bid & 15) >> 1;
  #pragma unroll 1
  for (int L = 0; L < 2; L++) {
    const int nch = L ? (FID < 112 ? 8 : 0) : 15;
    mbar_wait(BAR(B_PAR), L); mbar_wait(BAR(B_KVFULL + W0_BAR), L);
    #pragma unroll 1
    for (int n = 0, q = 0; n < 16; q = w_next(n, q), n++) {
      if (n >= 2) mbar_wait(n < 5 ? BAR(B_HAFREE + (n > 2)) : BAR(B_EMPTYW + q), n < 5 ? L : w_par(n, q, L) ^ 1);
      if (n == THR_N) mbar_wait(BAR(B_OFREE), L);
      mbar_expect_tx(BAR(B_FULLW + q), 16384);
      tma_5d(sb + w_off(q) + 16384, &P.mWo, 0, 0, n >> 3, 2 * (wo_order(bc, n) & 7), 2 * bc, BAR(B_FULLW + q), L ? POL_W1 : POL_W0);
      if (n == 2) {
        #pragma unroll 1
        for (int e = 0; e < 2; e++) {
          mbar_expect_tx(BAR(B_FULLW + 5), 16384);
          if (L) bulk_g2s_h(sb + 32768 + e * 16384, P.g->x[bi][2 * bc + e] + rh * 1024, 16384, BAR(B_FULLW + 5));
          else tma_2d_h(sb + 32768 + e * 16384, &P.mXh, bc * 128 + e * 64, bi * 256 + rh * 128, BAR(B_FULLW + 5), POL_EF);
        }
      }
    }
    mbar_wait(BAR(B_EMPTYW + 5), L);
    if (L && nch) {
      const bf16* src = WDSRC2;
      mbar_expect_tx(BAR(B_FULLW + 2), 32768); mbar_expect_tx(BAR(B_FULLW + 2), 24576);
      #pragma unroll 1
      for (int e = 0; e < 3; e++) { bulk_g2s_h(sb + e * 32768 + (e < 2 ? (rh ^ 1) * 16384 : 0), src + e * 8192, e < 2 ? 16384 : 24576, BAR(B_FULLW + 2)); pace(); }
    }
        if (L == 0) { mbar_arrive_peer(BAR(B_PFREE)); mbar_wait(BAR(B_EMPTYW), 0); mbar_wait(BAR(B_EMPTYW + 1), 0); }
    #pragma unroll 1
    for (int c = FID < 112 ? 0 : 12, slot = 0; c < nch; c++, slot = slot == 2 ? 0 : slot + 1) {
      const int q = (c >> 1) + (c >> 2);
      if (!L && (c == LATE_C || c == 12)) mbar_wait(BAR(LATE_B), LATE_P);
      mbar_wait(L ? BAR(B_EMPTYW + q) : BAR(B_STGE + slot), L | ((0x71c7 >> c) & 1));
      #define CC c
      stg_issue(P, CC, L ? sb + w_off(q) + (c & 1) * 8192 : sb + STG + slot * 16384, 8192 << L, L ? BAR(B_FULLW + q) : BAR(B_STG + slot));
      if (L) pace();
    }
  }
}
DEVI void sum8(uint4 v, float& s1, float& s2) {
  float e[8] = {bf_lo(v.x), bf_hi(v.x), bf_lo(v.y), bf_hi(v.y), bf_lo(v.z), bf_hi(v.z), bf_lo(v.w), bf_hi(v.w)};
  #pragma unroll
  for (int q = 0; q < 8; q++) { s1 += e[q]; s2 = fmaf(e[q], e[q], s2); }
}
DEVI uint4 norm8(uint4 x, float m, float rs) {
  #define HN(v) pack_bf16((bf_lo(v) - m) * rs, (bf_hi(v) - m) * rs)
  return make_uint4(HN(x.x), HN(x.y), HN(x.z), HN(x.w));
  #undef HN
}
DEVI void put_f32(uint4 b, uint32_t d, uint32_t d2) {
  sts128(d, make_uint4(b.x << 16, b.x & 0xffff0000u, b.y << 16, b.y & 0xffff0000u));
  sts128(d + d2, make_uint4(b.z << 16, b.z & 0xffff0000u, b.w << 16, b.w & 0xffff0000u));
}
DEVI void put_bf16(uint4 b, uint32_t d) {
  sts64f(d, __uint_as_float(b.x), __uint_as_float(b.y)); sts64f(d + 1024, __uint_as_float(b.z), __uint_as_float(b.w));
  fence_async_smem();
}
DEVI uint4 best4(uint32_t p) {
  uint4 a = lds128(p), b = lds128(p + 16), c = lds128(p + 32), d = lds128(p + 48);
  if (b.x > a.x) a = b;
  if (d.x > c.x) c = d;
  return c.x > a.x ? c : a;
}
#define FL(x) __uint_as_float(x)
#define UI(x) __float_as_uint(x)
DEVI void aux(const Params& P, uint32_t sb) {
  int tid = fresh_tid();
  #define lane (tid & 31)
  #define wq (tid >> 5)
  uint32_t ids = P.map[blockIdx.x], tag;
  #define bid ((int)(ids & 255))
  #define fid ((int)(ids >> 8))
  #define bi (bid >> 4)
  #define bp (bid & 15)
  #define bc (bp >> 1)
  #define FRESH() do { tid = fresh_tid(); uint4 z_ = ldsv128(sb + INFO2 + 16); ids = z_.y; tag = z_.z + L; idx = z_.w; } while (0)
  {
    const uint32_t epoch = ld_rlx(&P.g->epoch);
    if (tid == 0) {
      mbar_expect_tx(BAR(B_STG), 49152);
      tma_3d(sb + STG, &P.mWq, bp * 64, bi * 128, 0, BAR(B_STG));
      tma_3d(sb + STG + 24576, &P.mWq, bp * 64, bi * 128 + 64, 0, BAR(B_STG));
    }
    __syncwarp();
    sts64f(sb + ONES + tid * 8, FL(0x3F803F80u), FL(0x3F803F80u));
    float s1 = 0.f, s2 = 0.f;
    { uint4 v = __ldg((const uint4*)P.wr + tid);
      if ((tid >> 4) == bc) put_f32(v, sb + WR + (tid & 15) * 32, 16);
      sum8(v, s1, s2);
      #pragma unroll 1
      for (int o = 16; o; o >>= 1) s1 += __shfl_xor_sync(0xffffffffu, s1, o);
      sts32f(sb + INFO2 + wq * 4, s1); }
    const uint4* src = (const uint4*)(P.x0 + (size_t)bid * 16384) + (tid >> 3) * 128 + (tid & 7);
    s1 = 0.f; s2 = 0.f;
    #pragma unroll 1
    for (int it = 0; it < 16; it += 4) {
      uint4 v0 = __ldg(src + it * 8), v1 = __ldg(src + it * 8 + 8), v2 = __ldg(src + it * 8 + 16), v3 = __ldg(src + it * 8 + 24);
      #pragma unroll 1
      for (int q = 0; q < 4; q++) { sum8(v0, s1, s2); v0 = v1; v1 = v2; v2 = v3; }
    }
    #pragma unroll 1
    for (int o = 1; o < 8; o <<= 1) { s1 += __shfl_xor_sync(0xffffffffu, s1, o); s2 += __shfl_xor_sync(0xffffffffu, s2, o); }
    tag = ((epoch % 16383u) + 1u) << 2;
    if (tid == 0) { sts128(sb + INFO, make_uint4(0x40000000u, 0u, tag, ((epoch % 127u) + 1u) << 1)); sts128(sb + INFO2 + 16, make_uint4(epoch, ids, tag, 0x40000000u)); }
    float m = s1 * (1.f / 1024.f);
    if ((tid & 7) == 0) st_ll(&P.g->statF[bid * 16 + (tid >> 3)], UI(m), UI(fmaxf(fmaf(-m, m, s2 * (1.f / 1024.f)), 0.f)), 0u, tag);
    bar_sync(2, 128);
    mbar_wait_b(BAR(B_STG), 0);
    if (tid < 96) {
      s1 = 0.f; s2 = 0.f;
      #pragma unroll 1
      for (int r = 0; r < 16; r++) {
        const uint32_t a = sb + STG + (r >> 3) * 24576 + wq * 8192 + (r & 7) * 128 + ((lane * 4) ^ ((r & 7) << 4));
        #pragma unroll
        for (int e = 0; e < 8; e++) { uint32_t v = lds32(a + e * 1024); s1 += bf_lo(v); s2 += bf_hi(v); }
      }
      st_ll(&P.g->csP[bp][bi][tid], UI(s1), UI(s2), 0u, tag);
      s1 = 0.f; s2 = 0.f;
      #pragma unroll 1
      for (int q = 0; q < 8; q += 2) {
        uint4 a, b; poll_ll2(&P.g->csP[bp][q][tid], &P.g->csP[bp][q + 1][tid], 0xffffffffu, tag, a, b);
        s1 += FL(a.x) + FL(b.x); s2 += FL(a.y) + FL(b.y);
      }
      const uint32_t hi = pack_bf16(-s1, -s2);
      sts32(sb + CS + (tid >> 2) * 32 + (tid & 3) * 4, hi);
      sts32(sb + CS + (tid >> 2) * 32 + (tid & 3) * 4 + 16, pack_bf16(-s1 - bf_lo(hi), -s2 - bf_hi(hi)));
    }
    fence_async_smem();
  }
  int idx;
  #pragma unroll 1
  for (int L = 0; L < 2; L++) {
    FRESH();
    {
      if ((unsigned)(bi - (idx >> 8)) < 2u) {
        const uint4* src = &P.g->patch[bp * 8 + (tid >> 6) * 4][tid & 63];
        const float4 z = poll_sum4(src, 64, tag);
        float q = z.x, k = z.y, v = z.z;
        q += __shfl_xor_sync(0xffffffffu, q, 1); k += __shfl_xor_sync(0xffffffffu, k, 1); v += __shfl_xor_sync(0xffffffffu, v, 1);
        bar_sync(2, 128);
        const uint32_t d = sb + PATCH + (tid & ~1), kv = pack_bf16(k, v);
        sts16(d, pack_bf16(q * QSCALE, 0.f)); sts16(d + 128, kv); sts16(d + 256, kv >> 16);
      }
      sts32(sb + INFO, idx);
      bar_sync(2, 128);
    }
    const uint4 fix = lds128(sb + PATCH + 128 + (lane & 4) * 32 + (wq >> 1) * 64 + (lane & 3) * 16);
    warp_signal(BAR(B_PAR));
    PROFX(tid == 0, L ? 23 : 17);
    mbar_wait_b(BAR(B_KVFULL + wq), L);
    if ((idx >> 7) == bi * 2 - 1 - (wq & 1)) {
      if (lane < 8) sts128(sb + ((wq >> 1) ? KVB : KVA) + ((idx >> 6) & 3) * 8192 + (lane >> 2) * 4096 + (idx & 63) * 64 + (((lane ^ (idx >> 1)) & 3) << 4), fix);
      fence_async_smem();
    }
    bar_arrive(4 + wq, 160); bar_arrive(8 + wq, 160);
    FRESH();
    mbar_wait_b(BAR(B_OFREE), L);
    #define blk (bi * 2 + (bid & 1))
    if (tid < 33) st_ll(tid < 32 ? &P.g->row[blk][bc * 32 + tid] : &P.g->best[bc][blk], 0u, 0u, 0u, 0u);
    mbar_wait_b(BAR(B_XRDY), L);
    PROFX(tid == 0, 37 + L * 16);
    FRESH();
    {
      float s1 = 0.f, s2 = 0.f, d = 0.f;
      #pragma unroll 1
      for (int q = 0; q < 8; q += 4) { const float4 v = poll_sum4(&P.g->statP[q][blk * 128 + tid], 2048, tag); s1 += v.x; s2 += v.y; d += v.z; }
      PROFX(tid == 0, 39 + L * 16);
      uint4 a = lds128(sb + INFO2), b, c;
      float m = s1 * (1.f / 1024.f), var = fmaxf(fmaf(-m, m, s2 * (1.f / 1024.f)), 0.f), rs = rsqrtf(var + LN_EPS);
      uint32_t key = UI(fmaf(-m, (FL(a.x) + FL(a.y)) + (FL(a.z) + FL(a.w)), d) * rs);
      key ^= (uint32_t)((int)key >> 31) | 0x80000000u;
      uint32_t win = __ballot_sync(0xffffffffu, key == __reduce_max_sync(0xffffffffu, key));
      if (lane == __ffs(win) - 1) sts128(sb + RED + wq * 16, make_uint4(key, UI(m), UI(rs), (tag << 11) | (uint32_t)(blk * 128 + tid)));
      if (L) sts64f(sb + PAR + tid * 8, 1.f + rs, -m * rs);
      else if ((tid >> 4) == bc) st_ll(&P.g->statF[blk * 128 + tid], UI(m), UI(var), 0u, tag + 1);
      bar_sync(2, 128);
      if (wq == 0) {
        mbar_wait(BAR(B_XRDY + 1), L); mbar_wait(BAR(B_XRDY + 3), L);
        a = best4(sb + RED);
        float2 v = lds64f(sb + (lane >> 4) * 32768 + (a.w & 255) * 128 + (((lane & 15) * 8) ^ ((a.w & 7) << 4)));
        st_ll(&P.g->row[blk][bc * 32 + lane], UI(v.x), UI(v.y), 0u, tag);
        if (lane == 0) st_ll(&P.g->best[bc][blk], a.x, a.y, a.z, a.w);
        __syncwarp();
        if (lane < 2 + 2 * L) mbar_arrive(L ? BAR(B_PAR) : BAR(B_XFREE + lane));
      }
      PROFX(tid == 0, 18 + L * 6);
      FRESH();
      a = poll_ll(&P.g->best[bc][lane & 15], 0xfffff800u, tag << 11);
      win = __ffs(__ballot_sync(0xffffffffu, a.x == __reduce_max_sync(0xffffffffu, a.x))) - 1;
      idx = __shfl_sync(0xffffffffu, a.w, win) & 2047;
      PROFX(tid == 0, 19 + L * 6);
      poll_ll2(&P.g->row[win][tid], &P.g->row[win][tid + 128], 0xffffffffu, tag, c, b);
      c.z = b.x; c.w = b.y;
      a.x = __shfl_sync(0xffffffffu, a.x, win); a.y = __shfl_sync(0xffffffffu, a.y, win); a.z = __shfl_sync(0xffffffffu, a.z, win);
      sts32(sb + INFO2 + 28, idx);
      PROFX(tid == 0, 61 + L);
      b = norm8(c, FL(a.y), FL(a.z));
      if (L) put_bf16(b, sb + HV + tid * 8); else put_f32(b, sb + HV + tid * 16, 2048);
      if ((tid >> 1) == (bid & 63)) {
        sts128(sb + RED + 64 + (tid & 1) * 16, bid < 64 ? make_uint4(c.x, c.y, b.x, b.y) : make_uint4(c.z, c.w, b.z, b.w));
        sts32(sb + RED + 96, a.x);
      }
      bar_sync(2 + L, 128 + L * 256);
      if (L) {
        const int r0 = blk * 128 + (tid >> 4);
        uint32_t src = sb + ((tid >> 3) & 1) * 32768 + (r0 & 255) * 128 + (((tid ^ r0) & 7) << 4);
        uint4* dst = (uint4*)(P.out + (size_t)r0 * 1024 + bc * 128) + (tid & 15);
        #pragma unroll 4
        for (int it = 0; it < 16; it++) { uint4 v = lds128(src + it * 1024); if (idx - r0 != it * 8) dst[it * 1024] = v; }
      }
    }
    #pragma unroll 1
    for (int st = L; st < 2; st++) {
      FRESH();
      float a[8] = {0.f, 0.f, 0.f, 0.f, 0.f, 0.f, 0.f, 0.f};
      if (L == 0 && fid < 112) {
        uint32_t ha = st ? sb + RED + 768 : sb + HV + ((wq & 1) * 64 + (lane >> 2)) * 4;
        uint32_t ph = st ? 0x1cu : 0x171u, bar = st ? BAR(B_STG + 2) : BAR(B_STG);
        uint32_t wa = sb + STG + wq * 4096 + (st ? 32768 + lane * 16 : (lane ^ (lane >> 3)) * 16);
        const uint32_t hx = st ? 256 : 512;
        const bool lead = lane == 0;
        uint4 vc = make_uint4(0u, 0u, 0u, 0u); float hc = 0.f;
        #pragma unroll 1
        do {
          mbar_wait(bar, ph & 1);
          PROFX(lead && threadIdx.x == 256 && st == 0 && (ph > 255 || ph < 4), 40 - 23 + __clz(ph));
          #pragma unroll
          for (int n = 0; n < 8; n++) { const uint4 v = lds128(wa + n * 512); const float h = lds32f(ha + n * 32); fma8(a, vc, hc); vc = v; hc = h; }
          __syncwarp();
          if (lead) mbar_arrive(bar - 8 * (B_STG - B_STGE));
          const bool wrap = bar == BAR(B_STG + 2);
          bar += wrap ? -16 : 8; wa += wrap ? -32768 : 16384; ha += hx;
          ph >>= 1;
        } while (ph != 1);
        fma8(a, vc, hc);
      }
      FRESH();
      if (st == 1) {
        const uint32_t t8 = lds32(sb + INFO + 12) + L;
        if (L == 0 && fid < 112) {
          const bool odd = lane & 1;
          #pragma unroll
          for (int e = 0; e < 4; e++) { float z = __shfl_xor_sync(0xffffffffu, odd ? a[e] : a[4 + e], 1); if (odd) a[e] = z; else a[4 + e] = z; }
          uint4* dst = &P.g->yP[tid & ~1][fid][tid & 1];
          st_ll(dst, UI(a[0]), UI(a[1]), UI(a[2]), (UI(a[3]) & ~255u) | t8);
          st_ll(dst + 224, UI(a[4]), UI(a[5]), UI(a[6]), (UI(a[7]) & ~255u) | t8);
          PROFX(tid == 0, 21);
        }
        if (tid == 0) { uint32_t k = lds32(sb + RED + 96); sts32f(sb + RED + 100, bf_round(__fdividef(1.f, 1.f + __expf(-bf_round(FL(k ^ (~(uint32_t)((int)k >> 31) | 0x80000000u))))))); }
        uint4 v0, v1;
        poll_ll2(&P.g->yP[bid][0][min(tid, 111)], &P.g->yP[bid][0][min(tid, 111) + 112], 255u, t8, v0, v1);
        const float lo = (tid < 112 && !(tid & 1)) ? 1.f : 0.f, hi = (tid < 112 && (tid & 1)) ? 1.f : 0.f;
        const float y0 = FL(v0.x) + FL(v1.x), y1 = FL(v0.y) + FL(v1.y), y2 = FL(v0.z) + FL(v1.z), y3 = FL((v0.w & ~255u) | 128u) + FL((v1.w & ~255u) | 128u);
        a[0] = y0 * lo; a[1] = y1 * lo; a[2] = y2 * lo; a[3] = y3 * lo; a[4] = y0 * hi; a[5] = y1 * hi; a[6] = y2 * hi; a[7] = y3 * hi;
      }
      sts32f(sb + RED + 256 + wq * 128 + ((lane & 3) * 8 + (lane >> 2)) * 4, fold8(a));
      bar_sync(2, 128);
      const uint32_t d = sb + RED + 256 + lane * 4;
      float z0 = lds32f(d) + lds32f(d + 128), z1 = lds32f(d + 256) + lds32f(d + 384);
      if (st == 0) {
        sts32f(sb + RED + 768 + lane * 32 + wq * 4, swiglu(z0, z1));
        bar_sync(2, 128);
        if (fid < 112) { st_ll(&P.g->yP[tid & ~1][fid][tid & 1], 0u, 0u, 0u, 0u); st_ll(&P.g->yP[tid | 1][fid][tid & 1], 0u, 0u, 0u, 0u); }
        else { const uint32_t t0 = clk(); while (clk() - t0 < IDLE_T) __nanosleep(200); }
        if (tid < 80) st_ll(tid < 64 ? &P.g->patch[bid][tid] : &P.g->x2[(tid >> 1) & 7][2 * bid + (tid & 1)], 0u, 0u, 0u, 0u);
        PROFX(tid == 0, 20); continue; }
      z0 += z1;
      z0 += __shfl_xor_sync(0xffffffffu, z0, 8); z0 += __shfl_xor_sync(0xffffffffu, z0, 16);
      uint32_t xw = lds32(sb + RED + 64 + (lane & 4) * 4 + (lane & 2) * 2), hw = lds32(sb + RED + 72 + (lane & 4) * 4 + (lane & 2) * 2);
      z0 = bf_round(((lane & 1) ? bf_hi(hw) : bf_lo(hw)) + bf_round(bf_round(z0) * lds32f(sb + RED + 100))) + ((lane & 1) ? bf_hi(xw) : bf_lo(xw));
      uint32_t v = pack_bf16(z0, __shfl_down_sync(0xffffffffu, z0, 1)), v2 = __shfl_down_sync(0xffffffffu, v, 2);
      if (L) { if (tid == 0 || tid == 4) *(uint2*)(P.out + (size_t)idx * 1024 + bid * 8 + tid) = make_uint2(v, v2); PROFW(tid == 0, 28); }
      else if ((tid & 3) == 0 && tid < 64) st_ll(&P.g->x2[tid >> 3][2 * bid + ((tid >> 2) & 1)], v, v2, 0u, tag + 1);
    }
    if (L == 0) {
      PROFX(tid == 0, 22);
      FRESH();
      uint4 x, y; poll_ll2(&P.g->x2[bi][tid], &P.g->x2[bi][tid + 128], 0xffffffffu, tag + 1, x, y);
      x.z = y.x; x.w = y.y;
      if (wq == (bc & 3)) sts64f(sb + X2SEG + lane * 8, FL(bc < 4 ? x.x : x.z), FL(bc < 4 ? x.y : x.w));
      float s1 = 0.f, s2 = 0.f;
      sum8(x, s1, s2);
      #pragma unroll
      for (int o = 16; o; o >>= 1) { s1 += __shfl_xor_sync(0xffffffffu, s1, o); s2 += __shfl_xor_sync(0xffffffffu, s2, o); }
      sts64f(sb + RED + wq * 8, s1, s2);
      bar_sync(2, 128);
      y = lds128(sb + RED); uint4 y2 = lds128(sb + RED + 16);
      float m = ((FL(y.x) + FL(y.z)) + (FL(y2.x) + FL(y2.z))) * (1.f / 1024.f);
      put_bf16(norm8(x, m, rsqrtf(fmaxf(fmaf(-m, m, ((FL(y.y) + FL(y.w)) + (FL(y2.y) + FL(y2.w))) * (1.f / 1024.f)), 0.f) + LN_EPS)), sb + HV + tid * 8);
      mbar_wait(BAR(B_STG), 1); mbar_wait(BAR(B_STG + 1), 0); mbar_wait(BAR(B_STG + 2), 0);
      bar_sync(2, 128);
      PROFX(tid == 0, 30);
      float d0[4] = {0.f, 0.f, 0.f, 0.f}, d1[4] = {0.f, 0.f, 0.f, 0.f}, d2[4] = {0.f, 0.f, 0.f, 0.f};
      const uint32_t bd = (64 + (HV >> 4) + uni(bid & 3) * 32) | 0x10000u;
      #pragma unroll 1
      for (int ks = 0; ks < 8; ks++) {
        const uint32_t ad = (64 + (STG >> 4) + ks * 128) | (64u << 16);
        wg_fence();
        wgmma_ss_n8<0, 1>(d0, mkd<HI64>(ad), mkd<8>(bd + ks * 4), 1);
        wgmma_ss_n8<0, 1>(d1, mkd<HI64>(ad + 1024), mkd<8>(bd + ks * 4), 1);
        wgmma_ss_n8<0, 1>(d2, mkd<HI64>(ad + 2048), mkd<8>(bd + ks * 4), 1);
        wg_commit();
      }
      wg_wait<0>(); keep(d0); keep(d1); keep(d2);
      FRESH();
      if ((lane & 3) == (wq >> 1)) {
        uint4* dst = &P.g->patch[bid][(wq & 1) * 32 + (lane >> 2) * 2 + (wq >> 1)];
        st_ll(dst, UI(d0[0]), UI(d1[0]), UI(d2[0]), tag + 1); st_ll(dst + 16, UI(d0[2]), UI(d1[2]), UI(d2[2]), tag + 1);
      }
      PROFX(tid == 0, 31);
    }
  }
  if (bid == 0 && tid == 0) P.g->epoch = lds32(sb + INFO2 + 16) + 1;
  #undef blk
  #undef bid
  #undef fid
  #undef bi
  #undef bp
  #undef bc
  #undef FRESH
  #undef lane
  #undef wq
}

__global__ void __cluster_dims__(2, 1, 1) __launch_bounds__(512, 1) fused_kernel(const __grid_constant__ Params P) {
  extern __shared__ __align__(1024) uint8_t smem_raw[];
  const uint32_t sb = smem_u32(smem_raw);
  PROFT(threadIdx.x == 0, 0);
  if (threadIdx.x < 32) { if (elect()) {
    for (int s = 0; s < 3; s++) mbar_init(BAR(B_FULLQ + s), 1);
    asm volatile("fence.mbarrier_init.release.cluster;" ::: "memory");
    #pragma unroll 1
    for (int s = 0; s < 3; s++) {
      mbar_expect_tx(BAR(B_FULLQ + s), 57344);
      tma_2d(sb + qa_off(s), &P.mX, s * 64, (BID >> 4) * 256, BAR(B_FULLQ + s));
      tma_3d(sb + qb_off(s), &P.mWq, (BID & 15) * 64, s * 64, 0, BAR(B_FULLQ + s));
    }
    if ((sb & 0x3FFFFu) != 1024) __trap();
  } } else if (threadIdx.x == 480) {
    asm volatile("prefetch.tensormap [%0];" :: "l"(&P.mWq) : "memory");
  } else if (threadIdx.x >= 32 && !(threadIdx.x & 28) && (threadIdx.x >> 3) + (threadIdx.x & 3) <= B_COUNT + 1) {
    int b = (threadIdx.x >> 3) + (threadIdx.x & 3) - 1;
    if (b == B_COUNT) b = B_ROW;
    const uint32_t cnt = b < B_XFREE ? (b == B_OFREE ? 1 : 2) : (b < B_KVRDY ? 3 : (b < B_KVFULL || b == B_PAR ? 4 : (b == B_PFREE ? 2 : 1)));
    mbar_init(BAR(b), cnt);
    asm volatile("fence.mbarrier_init.release.cluster;" ::: "memory");
  }
  __syncthreads();
  asm volatile("barrier.cluster.arrive.relaxed.aligned;" ::: "memory");
  const int wg = __shfl_sync(0xffffffffu, threadIdx.x >> 7, 0);
  if (wg < 2) { reg_inc<224>(); consumer(P, sb, wg); }
  else if (wg == 2) { reg_dec<40>(); aux(P, sb); }
  else {
    reg_dec<24>();
    asm volatile("barrier.cluster.wait.aligned;" ::: "memory");
    const int w = __shfl_sync(0xffffffffu, (threadIdx.x >> 5) & 3, 0);
    if (w == 0) loader(P, sb);
    else if (w < 3) storer(P, sb, w - 1);
    else if (elect()) stager(P, sb);
  }
}

typedef CUresult (*EncFn)(CUtensorMap*, CUtensorMapDataType, cuuint32_t, void*, const cuuint64_t*, const cuuint64_t*, const cuuint32_t*, const cuuint32_t*,
                          CUtensorMapInterleave, CUtensorMapSwizzle, CUtensorMapL2promotion, CUtensorMapFloatOOBfill);
static void mk_map(EncFn enc, CUtensorMap* m, const void* ptr, int rank, const cuuint64_t* dims, const cuuint64_t* strides, const cuuint32_t* box,
                   CUtensorMapSwizzle sw, CUtensorMapL2promotion pr) {
  cuuint32_t es[5] = {1, 1, 1, 1, 1};
  enc(m, CU_TENSOR_MAP_DATA_TYPE_BFLOAT16, rank, (void*)ptr, dims, strides, box, es, CU_TENSOR_MAP_INTERLEAVE_NONE, sw, pr, CU_TENSOR_MAP_FLOAT_OOB_FILL_NONE);
}
extern "C" void kernel_launch(void* const* d_in, const int* in_sizes, int n_in, void* d_out, int out_size) {
  (void)in_sizes; (void)n_in; (void)out_size;
  void* fn = nullptr; cudaDriverEntryPointQueryResult q;
  cudaGetDriverEntryPoint("cuTensorMapEncodeTiled", &fn, cudaEnableDefault, &q);
  EncFn enc = (EncFn)fn;
  cudaFuncSetAttribute(fused_kernel, cudaFuncAttributeMaxDynamicSharedMemorySize, SMEM_BYTES);
  Params P;
  const CUtensorMapSwizzle S128 = CU_TENSOR_MAP_SWIZZLE_128B, S64 = CU_TENSOR_MAP_SWIZZLE_64B, S0 = CU_TENSOR_MAP_SWIZZLE_NONE;
  const CUtensorMapL2promotion L256 = CU_TENSOR_MAP_L2_PROMOTION_L2_256B, L128 = CU_TENSOR_MAP_L2_PROMOTION_L2_128B;
  { cuuint64_t d[2] = {1024, 2048}, s[1] = {2048}; cuuint32_t b[2] = {64, 256}, bh[2] = {64, 128};
    mk_map(enc, &P.mX, d_in[0], 2, d, s, b, S128, L256); mk_map(enc, &P.mXh, d_in[0], 2, d, s, bh, S128, L256); }
  { cuuint64_t d[3] = {1024, 1024, 3}, s[2] = {6144, 2048}; cuuint32_t b[3] = {64, 64, 3}; mk_map(enc, &P.mWq, d_in[1], 3, d, s, b, S128, L256); }
  { cuuint64_t d[5] = {64, 32, 2, 16, 16}, s[4] = {2048, 65536, 131072, 128}; cuuint32_t b[5] = {64, 32, 1, 2, 2}; mk_map(enc, &P.mWo, d_in[2], 5, d, s, b, S128, L256); }
  { cuuint64_t d[2] = {3584, 1024}, s[1] = {7168}; cuuint32_t b[2] = {32, 128};
    mk_map(enc, &P.mWg, d_in[5], 2, d, s, b, S64, L128); mk_map(enc, &P.mWu, d_in[6], 2, d, s, b, S64, L128); }
  { cuuint64_t d[2] = {3072, 1024}, s[1] = {6144}; cuuint32_t b[2] = {32, 256}; mk_map(enc, &P.mWp, d_in[1], 2, d, s, b, S64, L128); }
  { cuuint64_t d[3] = {256, 3584, 4}, s[2] = {2048, 512}; cuuint32_t b[3] = {256, 8, 4}; mk_map(enc, &P.mWd, d_in[7], 3, d, s, b, S0, L128); }
  P.x0 = (const bf16*)d_in[0]; P.wqkv = (const bf16*)d_in[1]; P.wo = (const bf16*)d_in[2]; P.wr = (const bf16*)d_in[4]; P.wg = (const bf16*)d_in[5]; P.wu = (const bf16*)d_in[6]; P.wd = (const bf16*)d_in[7];
  P.out = (bf16*)d_out;
  cudaGetSymbolAddress((void**)&P.g, g_scr);
  for (int b = 0; b < 128; b++) {
    int j = b >> 1, quad = j < 4 ? 0 : (j < 36 ? 1 + (j - 4) % 8 : 9 + (j - 36) % 7), pos = j < 4 ? j : (j < 36 ? (j - 4) / 8 : (j - 36) / 7);
    int bid = ((quad >> 2) * 2 + (pos >> 1)) * 16 + ((quad & 3) * 2 + (pos & 1)) * 2 + (b & 1);
    int e = pos * 2 + (b & 1), fid = e < 7 ? quad * 7 + e : 112 + quad;
    P.map[b] = bid | fid << 8;
  }
  fused_kernel<<<128, 512, SMEM_BYTES>>>(P);
}
```

```cpp
#include <cuda_runtime.h>
#include <cuda_bf16.h>
#include <cuda.h>
#include <stdint.h>
#include <stddef.h>
typedef __nv_bfloat16 bf16;

template<int TB, int TA = 0> __device__ __forceinline__ void wgmma_ss_n192(float (&d)[96], uint64_t da, uint64_t db, int scale_d) {
  asm volatile("{\n.reg .pred p;\nsetp.ne.b32 p, %98, 0;\n"
    "wgmma.mma_async.sync.aligned.m64n192k16.f32.bf16.bf16 {%0, %1, %2, %3, %4, %5, %6, %7, %8, %9, %10, %11, %12, %13, %14, %15, %16, %17, %18, %19, %20, %21, %22, %23, %24, %25, %26, %27, %28, %29, %30, %31, %32, %33, %34, %35, %36, %37, %38, %39, %40, %41, %42, %43, %44, %45, %46, %47, %48, %49, %50, %51, %52, %53, %54, %55, %56, %57, %58, %59, %60, %61, %62, %63, %64, %65, %66, %67, %68, %69, %70, %71, %72, %73, %74, %75, %76, %77, %78, %79, %80, %81, %82, %83, %84, %85, %86, %87, %88, %89, %90, %91, %92, %93, %94, %95}, %96, %97, p, 1, 1, %100, %99;\n}\n"
    : "+f"(d[0]), "+f"(d[1]), "+f"(d[2]), "+f"(d[3]), "+f"(d[4]), "+f"(d[5]), "+f"(d[6]), "+f"(d[7]), "+f"(d[8]), "+f"(d[9]), "+f"(d[10]), "+f"(d[11]), "+f"(d[12]), "+f"(d[13]), "+f"(d[14]), "+f"(d[15]), "+f"(d[16]), "+f"(d[17]), "+f"(d[18]), "+f"(d[19]), "+f"(d[20]), "+f"(d[21]), "+f"(d[22]), "+f"(d[23]), "+f"(d[24]), "+f"(d[25]), "+f"(d[26]), "+f"(d[27]), "+f"(d[28]), "+f"(d[29]), "+f"(d[30]), "+f"(d[31]), "+f"(d[32]), "+f"(d[33]), "+f"(d[34]), "+f"(d[35]), "+f"(d[36]), "+f"(d[37]), "+f"(d[38]), "+f"(d[39]), "+f"(d[40]), "+f"(d[41]), "+f"(d[42]), "+f"(d[43]), "+f"(d[44]), "+f"(d[45]), "+f"(d[46]), "+f"(d[47]), "+f"(d[48]), "+f"(d[49]), "+f"(d[50]), "+f"(d[51]), "+f"(d[52]), "+f"(d[53]), "+f"(d[54]), "+f"(d[55]), "+f"(d[56]), "+f"(d[57]), "+f"(d[58]), "+f"(d[59]), "+f"(d[60]), "+f"(d[61]), "+f"(d[62]), "+f"(d[63]), "+f"(d[64]), "+f"(d[65]), "+f"(d[66]), "+f"(d[67]), "+f"(d[68]), "+f"(d[69]), "+f"(d[70]), "+f"(d[71]), "+f"(d[72]), "+f"(d[73]), "+f"(d[74]), "+f"(d[75]), "+f"(d[76]), "+f"(d[77]), "+f"(d[78]), "+f"(d[79]), "+f"(d[80]), "+f"(d[81]), "+f"(d[82]), "+f"(d[83]), "+f"(d[84]), "+f"(d[85]), "+f"(d[86]), "+f"(d[87]), "+f"(d[88]), "+f"(d[89]), "+f"(d[90]), "+f"(d[91]), "+f"(d[92]), "+f"(d[93]), "+f"(d[94]), "+f"(d[95])
    : "l"(da), "l"(db), "r"(scale_d), "n"(TB), "n"(TA));
}

template<int TB> __device__ __forceinline__ void wgmma_rs_n192(float (&d)[96], uint32_t a0, uint32_t a1, uint32_t a2, uint32_t a3, uint64_t db, int scale_d) {
  asm volatile("{\n.reg .pred p;\nsetp.ne.b32 p, %101, 0;\n"
    "wgmma.mma_async.sync.aligned.m64n192k16.f32.bf16.bf16 {%0, %1, %2, %3, %4, %5, %6, %7, %8, %9, %10, %11, %12, %13, %14, %15, %16, %17, %18, %19, %20, %21, %22, %23, %24, %25, %26, %27, %28, %29, %30, %31, %32, %33, %34, %35, %36, %37, %38, %39, %40, %41, %42, %43, %44, %45, %46, %47, %48, %49, %50, %51, %52, %53, %54, %55, %56, %57, %58, %59, %60, %61, %62, %63, %64, %65, %66, %67, %68, %69, %70, %71, %72, %73, %74, %75, %76, %77, %78, %79, %80, %81, %82, %83, %84, %85, %86, %87, %88, %89, %90, %91, %92, %93, %94, %95}, {%96, %97, %98, %99}, %100, p, 1, 1, %102;\n}\n"
    : "+f"(d[0]), "+f"(d[1]), "+f"(d[2]), "+f"(d[3]), "+f"(d[4]), "+f"(d[5]), "+f"(d[6]), "+f"(d[7]), "+f"(d[8]), "+f"(d[9]), "+f"(d[10]), "+f"(d[11]), "+f"(d[12]), "+f"(d[13]), "+f"(d[14]), "+f"(d[15]), "+f"(d[16]), "+f"(d[17]), "+f"(d[18]), "+f"(d[19]), "+f"(d[20]), "+f"(d[21]), "+f"(d[22]), "+f"(d[23]), "+f"(d[24]), "+f"(d[25]), "+f"(d[26]), "+f"(d[27]), "+f"(d[28]), "+f"(d[29]), "+f"(d[30]), "+f"(d[31]), "+f"(d[32]), "+f"(d[33]), "+f"(d[34]), "+f"(d[35]), "+f"(d[36]), "+f"(d[37]), "+f"(d[38]), "+f"(d[39]), "+f"(d[40]), "+f"(d[41]), "+f"(d[42]), "+f"(d[43]), "+f"(d[44]), "+f"(d[45]), "+f"(d[46]), "+f"(d[47]), "+f"(d[48]), "+f"(d[49]), "+f"(d[50]), "+f"(d[51]), "+f"(d[52]), "+f"(d[53]), "+f"(d[54]), "+f"(d[55]), "+f"(d[56]), "+f"(d[57]), "+f"(d[58]), "+f"(d[59]), "+f"(d[60]), "+f"(d[61]), "+f"(d[62]), "+f"(d[63]), "+f"(d[64]), "+f"(d[65]), "+f"(d[66]), "+f"(d[67]), "+f"(d[68]), "+f"(d[69]), "+f"(d[70]), "+f"(d[71]), "+f"(d[72]), "+f"(d[73]), "+f"(d[74]), "+f"(d[75]), "+f"(d[76]), "+f"(d[77]), "+f"(d[78]), "+f"(d[79]), "+f"(d[80]), "+f"(d[81]), "+f"(d[82]), "+f"(d[83]), "+f"(d[84]), "+f"(d[85]), "+f"(d[86]), "+f"(d[87]), "+f"(d[88]), "+f"(d[89]), "+f"(d[90]), "+f"(d[91]), "+f"(d[92]), "+f"(d[93]), "+f"(d[94]), "+f"(d[95])
    : "r"(a0), "r"(a1), "r"(a2), "r"(a3), "l"(db), "r"(scale_d), "n"(TB));
}

template<int TB, int TA = 0> __device__ __forceinline__ void wgmma_ss_n128(float (&d)[64], uint64_t da, uint64_t db, int scale_d) {
  asm volatile("{\n.reg .pred p;\nsetp.ne.b32 p, %66, 0;\n"
    "wgmma.mma_async.sync.aligned.m64n128k16.f32.bf16.bf16 {%0, %1, %2, %3, %4, %5, %6, %7, %8, %9, %10, %11, %12, %13, %14, %15, %16, %17, %18, %19, %20, %21, %22, %23, %24, %25, %26, %27, %28, %29, %30, %31, %32, %33, %34, %35, %36, %37, %38, %39, %40, %41, %42, %43, %44, %45, %46, %47, %48, %49, %50, %51, %52, %53, %54, %55, %56, %57, %58, %59, %60, %61, %62, %63}, %64, %65, p, 1, 1, %68, %67;\n}\n"
    : "+f"(d[0]), "+f"(d[1]), "+f"(d[2]), "+f"(d[3]), "+f"(d[4]), "+f"(d[5]), "+f"(d[6]), "+f"(d[7]), "+f"(d[8]), "+f"(d[9]), "+f"(d[10]), "+f"(d[11]), "+f"(d[12]), "+f"(d[13]), "+f"(d[14]), "+f"(d[15]), "+f"(d[16]), "+f"(d[17]), "+f"(d[18]), "+f"(d[19]), "+f"(d[20]), "+f"(d[21]), "+f"(d[22]), "+f"(d[23]), "+f"(d[24]), "+f"(d[25]), "+f"(d[26]), "+f"(d[27]), "+f"(d[28]), "+f"(d[29]), "+f"(d[30]), "+f"(d[31]), "+f"(d[32]), "+f"(d[33]), "+f"(d[34]), "+f"(d[35]), "+f"(d[36]), "+f"(d[37]), "+f"(d[38]), "+f"(d[39]), "+f"(d[40]), "+f"(d[41]), "+f"(d[42]), "+f"(d[43]), "+f"(d[44]), "+f"(d[45]), "+f"(d[46]), "+f"(d[47]), "+f"(d[48]), "+f"(d[49]), "+f"(d[50]), "+f"(d[51]), "+f"(d[52]), "+f"(d[53]), "+f"(d[54]), "+f"(d[55]), "+f"(d[56]), "+f"(d[57]), "+f"(d[58]), "+f"(d[59]), "+f"(d[60]), "+f"(d[61]), "+f"(d[62]), "+f"(d[63])
    : "l"(da), "l"(db), "r"(scale_d), "n"(TB), "n"(TA));
}

template<int TB, int TA = 0> __device__ __forceinline__ void wgmma_ss_n64(float (&d)[32], uint64_t da, uint64_t db, int scale_d) {
  asm volatile("{\n.reg .pred p;\nsetp.ne.b32 p, %34, 0;\n"
    "wgmma.mma_async.sync.aligned.m64n64k16.f32.bf16.bf16 {%0, %1, %2, %3, %4, %5, %6, %7, %8, %9, %10, %11, %12, %13, %14, %15, %16, %17, %18, %19, %20, %21, %22, %23, %24, %25, %26, %27, %28, %29, %30, %31}, %32, %33, p, 1, 1, %36, %35;\n}\n"
    : "+f"(d[0]), "+f"(d[1]), "+f"(d[2]), "+f"(d[3]), "+f"(d[4]), "+f"(d[5]), "+f"(d[6]), "+f"(d[7]), "+f"(d[8]), "+f"(d[9]), "+f"(d[10]), "+f"(d[11]), "+f"(d[12]), "+f"(d[13]), "+f"(d[14]), "+f"(d[15]), "+f"(d[16]), "+f"(d[17]), "+f"(d[18]), "+f"(d[19]), "+f"(d[20]), "+f"(d[21]), "+f"(d[22]), "+f"(d[23]), "+f"(d[24]), "+f"(d[25]), "+f"(d[26]), "+f"(d[27]), "+f"(d[28]), "+f"(d[29]), "+f"(d[30]), "+f"(d[31])
    : "l"(da), "l"(db), "r"(scale_d), "n"(TB), "n"(TA));
}

template<int TB, int TA = 0> __device__ __forceinline__ void wgmma_ss_n8(float (&d)[4], uint64_t da, uint64_t db, int scale_d) {
  asm volatile("{\n.reg .pred p;\nsetp.ne.b32 p, %6, 0;\n"
    "wgmma.mma_async.sync.aligned.m64n8k16.f32.bf16.bf16 {%0, %1, %2, %3}, %4, %5, p, 1, 1, %8, %7;\n}\n"
    : "+f"(d[0]), "+f"(d[1]), "+f"(d[2]), "+f"(d[3])
    : "l"(da), "l"(db), "r"(scale_d), "n"(TB), "n"(TA));
}

template<int TB> __device__ __forceinline__ void wgmma_rs_n40(float (&d)[20], uint32_t a0, uint32_t a1, uint32_t a2, uint32_t a3, uint64_t db, int scale_d) {
  asm volatile("{\n.reg .pred p;\nsetp.ne.b32 p, %25, 0;\n"
    "wgmma.mma_async.sync.aligned.m64n40k16.f32.bf16.bf16 {%0, %1, %2, %3, %4, %5, %6, %7, %8, %9, %10, %11, %12, %13, %14, %15, %16, %17, %18, %19}, {%20, %21, %22, %23}, %24, p, 1, 1, %26;\n}\n"
    : "+f"(d[0]), "+f"(d[1]), "+f"(d[2]), "+f"(d[3]), "+f"(d[4]), "+f"(d[5]), "+f"(d[6]), "+f"(d[7]), "+f"(d[8]), "+f"(d[9]), "+f"(d[10]), "+f"(d[11]), "+f"(d[12]), "+f"(d[13]), "+f"(d[14]), "+f"(d[15]), "+f"(d[16]), "+f"(d[17]), "+f"(d[18]), "+f"(d[19])
    : "r"(a0), "r"(a1), "r"(a2), "r"(a3), "l"(db), "r"(scale_d), "n"(TB));
}

#define DEVI __device__ __forceinline__
DEVI uint32_t smem_u32(const void* p) { return (uint32_t)__cvta_generic_to_shared(p); }
DEVI void mbar_init(uint32_t bar, uint32_t cnt) { asm volatile("mbarrier.init.shared::cta.b64 [%0], %1;" :: "r"(bar), "r"(cnt)); }
DEVI void mbar_expect_tx(uint32_t bar, uint32_t bytes) { asm volatile("mbarrier.arrive.expect_tx.shared::cta.b64 _, [%0], %1;" :: "r"(bar), "r"(bytes) : "memory"); }
DEVI void mbar_arrive(uint32_t bar) { asm volatile("mbarrier.arrive.shared::cta.b64 _, [%0];" :: "r"(bar) : "memory"); }
DEVI void mbar_arrive_peer(uint32_t bar) {
  asm volatile("{\n.reg .b32 ra;\nmapa.shared::cluster.u32 ra, %0, %1;\nmbarrier.arrive.shared::cluster.b64 _, [ra];\n}" :: "r"(bar), "r"((blockIdx.x & 1) ^ 1) : "memory");
}
DEVI void bulk_s2peer(uint32_t a, uint32_t bytes, uint32_t bar) {
  asm volatile("{\n.reg .b32 ra, rb;\nmapa.shared::cluster.u32 ra, %0, %3;\nmapa.shared::cluster.u32 rb, %2, %3;\n"
               "cp.async.bulk.shared::cluster.shared::cta.mbarrier::complete_tx::bytes [ra], [%0], %1, [rb];\n}"
               :: "r"(a), "r"(bytes), "r"(bar), "r"((blockIdx.x & 1) ^ 1) : "memory");
}
DEVI void mbar_wait(uint32_t bar, uint32_t parity) {
  asm volatile("{\n.reg .pred p;\nLW:\nmbarrier.try_wait.parity.shared::cta.b64 p, [%0], %1;\n@!p bra LW;\n}" :: "r"(bar), "r"(parity) : "memory");
}
DEVI uint32_t mbar_test(uint32_t bar, uint32_t parity) {
  uint32_t r; asm volatile("{\n.reg .pred p;\nmbarrier.test_wait.parity.shared::cta.b64 p, [%1], %2;\nselp.u32 %0, 1, 0, p;\n}" : "=r"(r) : "r"(bar), "r"(parity) : "memory"); return r;
}
DEVI void mbar_wait_b(uint32_t bar, uint32_t parity) {
  asm volatile("{\n.reg .pred p;\n.reg .u32 it;\nmov.u32 it, 0;\nLW:\nmbarrier.try_wait.parity.shared::cta.b64 p, [%0], %1;\n@p bra LD;\n"
               "add.u32 it, it, 1;\nsetp.lt.u32 p, it, 0x1000000;\n@p bra LW;\ntrap;\nLD:\n}" :: "r"(bar), "r"(parity) : "memory");
}
DEVI void tma_2d(uint32_t dst, const CUtensorMap* m, int c0, int c1, uint32_t bar) {
  asm volatile("cp.async.bulk.tensor.2d.shared::cluster.global.mbarrier::complete_tx::bytes [%0], [%1, {%3, %4}], [%2];"
    :: "r"(dst), "l"(m), "r"(bar), "r"(c0), "r"(c1) : "memory");
}
DEVI void tma_3d(uint32_t dst, const CUtensorMap* m, int c0, int c1, int c2, uint32_t bar) {
  asm volatile("cp.async.bulk.tensor.3d.shared::cluster.global.mbarrier::complete_tx::bytes [%0], [%1, {%3, %4, %5}], [%2];"
    :: "r"(dst), "l"(m), "r"(bar), "r"(c0), "r"(c1), "r"(c2) : "memory");
}
#define POL_EF POL_FIRST
constexpr uint64_t POL_FIRST = 0x12F0000000000000ull, POL_NORMAL = 0x1000000000000000ull;
DEVI void tma_2d_h(uint32_t dst, const CUtensorMap* m, int c0, int c1, uint32_t bar, uint64_t pol) {
  asm volatile("cp.async.bulk.tensor.2d.shared::cluster.global.mbarrier::complete_tx::bytes.L2::cache_hint [%0], [%1, {%3, %4}], [%2], %5;"
    :: "r"(dst), "l"(m), "r"(bar), "r"(c0), "r"(c1), "l"(pol) : "memory");
}
DEVI void tma_3d_h(uint32_t dst, const CUtensorMap* m, int c0, int c1, int c2, uint32_t bar, uint64_t pol) {
  asm volatile("cp.async.bulk.tensor.3d.shared::cluster.global.mbarrier::complete_tx::bytes.L2::cache_hint [%0], [%1, {%3, %4, %5}], [%2], %6;"
    :: "r"(dst), "l"(m), "r"(bar), "r"(c0), "r"(c1), "r"(c2), "l"(pol) : "memory");
}
DEVI void bulk_g2s_h(uint32_t s, const void* g, uint32_t bytes, uint32_t bar, uint64_t pol = POL_EF) {
  asm volatile("cp.async.bulk.shared::cluster.global.mbarrier::complete_tx::bytes.L2::cache_hint [%0], [%1], %2, [%3], %4;"
    :: "r"(s), "l"(g), "r"(bytes), "r"(bar), "l"(pol) : "memory");
}
DEVI void tma_5d(uint32_t dst, const CUtensorMap* m, int c0, int c1, int c2, int c3, int c4, uint32_t bar, uint64_t pol) {
  asm volatile("cp.async.bulk.tensor.5d.shared::cluster.global.mbarrier::complete_tx::bytes.L2::cache_hint [%0], [%1, {%3, %4, %5, %6, %7}], [%2], %8;"
    :: "r"(dst), "l"(m), "r"(bar), "r"(c0), "r"(c1), "r"(c2), "r"(c3), "r"(c4), "l"(pol) : "memory");
}
DEVI void tma_prefetch_2d(const CUtensorMap* m, int c0, int c1) {
  asm volatile("cp.async.bulk.prefetch.tensor.2d.L2.global.tile [%0, {%1, %2}];" :: "l"(m), "r"(c0), "r"(c1) : "memory");
}
DEVI void tma_prefetch_3d(const CUtensorMap* m, int c0, int c1, int c2) {
  asm volatile("cp.async.bulk.prefetch.tensor.3d.L2.global.tile [%0, {%1, %2, %3}];" :: "l"(m), "r"(c0), "r"(c1), "r"(c2) : "memory");
}
DEVI void bulk_prefetch(const void* g, uint32_t bytes) { asm volatile("cp.async.bulk.prefetch.L2.global [%0], %1;" :: "l"(g), "r"(bytes) : "memory"); }
DEVI void bulk_g2s(uint32_t s, const void* g, uint32_t bytes, uint32_t bar) {
  asm volatile("cp.async.bulk.shared::cluster.global.mbarrier::complete_tx::bytes [%0], [%1], %2, [%3];" :: "r"(s), "l"(g), "r"(bytes), "r"(bar) : "memory");
}
DEVI void bulk_s2g(void* g, uint32_t s, uint32_t bytes, uint64_t pol = POL_NORMAL) {
  asm volatile("cp.async.bulk.global.shared::cta.bulk_group.L2::cache_hint [%0], [%1], %2, %3;\ncp.async.bulk.commit_group;" :: "l"(g), "r"(s), "r"(bytes), "l"(pol) : "memory");
}
template<int N> DEVI void bulk_wait() { asm volatile("cp.async.bulk.wait_group %0;" :: "n"(N) : "memory"); }
DEVI void fence_async_smem() { asm volatile("fence.proxy.async.shared::cta;" ::: "memory"); }
DEVI void fence_async_glob() { asm volatile("fence.proxy.async.global;" ::: "memory"); }
DEVI unsigned ld_rlx(const unsigned* p) { unsigned v; asm volatile("ld.relaxed.gpu.global.u32 %0, [%1];" : "=r"(v) : "l"(p) : "memory"); return v; }
DEVI void st_rlx(unsigned* p, unsigned v) { asm volatile("st.relaxed.gpu.global.u32 [%0], %1;" :: "l"(p), "r"(v) : "memory"); }
DEVI uint2 ldg_stream(const uint2* p) { uint2 v; asm volatile("ld.global.nc.L1::no_allocate.v2.u32 {%0, %1}, [%2];" : "=r"(v.x), "=r"(v.y) : "l"(p)); return v; }
DEVI void fence_rel() { asm volatile("fence.release.gpu;" ::: "memory"); }
DEVI uint4 ld_ll(const uint4* p) {
  uint4 v;
  asm volatile("{\n.reg .b128 t;\n.reg .b64 a, b;\nld.relaxed.gpu.global.b128 t, [%4];\nmov.b128 {a, b}, t;\nmov.b64 {%0, %1}, a;\nmov.b64 {%2, %3}, b;\n}"
               : "=r"(v.x), "=r"(v.y), "=r"(v.z), "=r"(v.w) : "l"(p) : "memory");
  return v;
}
DEVI void st_ll(uint4* p, uint32_t x, uint32_t y, uint32_t z, uint32_t w) {
  asm volatile("{\n.reg .b128 t;\n.reg .b64 a, b;\nmov.b64 a, {%1, %2};\nmov.b64 b, {%3, %4};\nmov.b128 t, {a, b};\nst.relaxed.gpu.global.b128 [%0], t;\n}"
               :: "l"(p), "r"(x), "r"(y), "r"(z), "r"(w) : "memory");
}
#define SPIN_MAX 0x1000000
DEVI uint4 poll_ll(const uint4* p, uint32_t mask, uint32_t tag) {
  uint4 v; int it = 0;
  do { v = ld_ll(p); if (++it > SPIN_MAX) __trap(); } while (!__all_sync(0xffffffffu, (v.w & mask) == tag));
  return v;
}
DEVI void poll_ll2(const uint4* p, const uint4* q, uint32_t mask, uint32_t tag, uint4& a, uint4& b) {
  int it = 0;
  do { a = ld_ll(p); b = ld_ll(q); if (++it > SPIN_MAX) __trap(); } while (!__all_sync(0xffffffffu, (a.w & mask) == tag && (b.w & mask) == tag));
}
DEVI float4 poll_sum4(const uint4* src, int stride, uint32_t tag) {
  uint4 v0, v1, v2, v3; int it = 0;
  do { v0 = ld_ll(src); v1 = ld_ll(src + stride); v2 = ld_ll(src + 2 * stride); v3 = ld_ll(src + 3 * stride); if (++it > SPIN_MAX) __trap(); }
  while (!__all_sync(0xffffffffu, v0.w == tag && v1.w == tag && v2.w == tag && v3.w == tag));
  #define S4(f) ((__uint_as_float(v0.f) + __uint_as_float(v1.f)) + (__uint_as_float(v2.f) + __uint_as_float(v3.f)))
  return make_float4(S4(x), S4(y), S4(z), 0.f);
  #undef S4
}
DEVI void bar_sync(int id, int n) { asm volatile("bar.sync %0, %1;" :: "r"(id), "r"(n) : "memory"); }
DEVI void bar_arrive(int id, int n) { asm volatile("bar.arrive %0, %1;" :: "r"(id), "r"(n) : "memory"); }
DEVI void wg_fence() { asm volatile("wgmma.fence.sync.aligned;" ::: "memory"); }
DEVI void wg_commit() { asm volatile("wgmma.commit_group.sync.aligned;" ::: "memory"); }
template<int N> DEVI void wg_wait() { asm volatile("wgmma.wait_group.sync.aligned %0;" :: "n"(N) : "memory"); }
template<int N> DEVI void reg_inc() { asm volatile("setmaxnreg.inc.sync.aligned.u32 %0;" :: "n"(N)); }
template<int N> DEVI void reg_dec() { asm volatile("setmaxnreg.dec.sync.aligned.u32 %0;" :: "n"(N)); }
DEVI float ex2f(float x) { float y; asm("ex2.approx.ftz.f32 %0, %1;" : "=f"(y) : "f"(x)); return y; }
DEVI uint32_t pack_bf16(float lo, float hi) { uint32_t r; asm("cvt.rn.bf16x2.f32 %0, %1, %2;" : "=r"(r) : "f"(hi), "f"(lo)); return r; }
DEVI float bf_lo(uint32_t v) { return __uint_as_float(v << 16); }
DEVI float bf_hi(uint32_t v) { return __uint_as_float(v & 0xffff0000u); }
DEVI float bf_round(float x) { return bf_lo(pack_bf16(x, 0.f)); }
DEVI void stsm_x4(uint32_t addr, uint32_t a, uint32_t b, uint32_t c, uint32_t d) {
  asm volatile("stmatrix.sync.aligned.m8n8.x4.shared.b16 [%0], {%1,%2,%3,%4};" :: "r"(addr), "r"(a), "r"(b), "r"(c), "r"(d) : "memory");
}
DEVI void ldsm_x4(uint32_t addr, uint32_t& a, uint32_t& b, uint32_t& c, uint32_t& d) {
  asm volatile("ldmatrix.sync.aligned.m8n8.x4.shared.b16 {%0,%1,%2,%3}, [%4];" : "=r"(a), "=r"(b), "=r"(c), "=r"(d) : "r"(addr) : "memory");
}
DEVI uint4 lds128(uint32_t a) { uint4 v; asm volatile("ld.shared.v4.u32 {%0,%1,%2,%3}, [%4];" : "=r"(v.x), "=r"(v.y), "=r"(v.z), "=r"(v.w) : "r"(a) : "memory"); return v; }
DEVI void sts128(uint32_t a, uint4 v) { asm volatile("st.shared.v4.u32 [%0], {%1,%2,%3,%4};" :: "r"(a), "r"(v.x), "r"(v.y), "r"(v.z), "r"(v.w) : "memory"); }
DEVI float2 lds64f(uint32_t a) { float2 v; asm volatile("ld.shared.v2.f32 {%0,%1}, [%2];" : "=f"(v.x), "=f"(v.y) : "r"(a) : "memory"); return v; }
DEVI void sts64f(uint32_t a, float x, float y) { asm volatile("st.shared.v2.f32 [%0], {%1,%2};" :: "r"(a), "f"(x), "f"(y) : "memory"); }
DEVI uint32_t lds32(uint32_t a) { uint32_t v; asm volatile("ld.shared.u32 %0, [%1];" : "=r"(v) : "r"(a) : "memory"); return v; }
DEVI float lds32f(uint32_t a) { return __uint_as_float(lds32(a)); }
DEVI void sts32(uint32_t a, uint32_t v) { asm volatile("st.shared.u32 [%0], %1;" :: "r"(a), "r"(v) : "memory"); }
DEVI void sts32f(uint32_t a, float v) { sts32(a, __float_as_uint(v)); }
DEVI void sts16(uint32_t a, uint32_t v) { asm volatile("st.shared.u16 [%0], %1;" :: "r"(a), "h"((unsigned short)v) : "memory"); }
template<int N> DEVI void keep(float (&d)[N]) {
  #pragma unroll
  for (int i = 0; i < N; i++) asm volatile("" : "+f"(d[i]) :: "memory");
}
template<int N> DEVI void keep(uint32_t (&d)[N]) {
  #pragma unroll
  for (int i = 0; i < N; i++) asm volatile("" : "+r"(d[i]) :: "memory");
}
template<uint32_t HI> DEVI uint64_t mkd(uint32_t lo) { uint64_t r; asm("mov.b64 %0, {%1, %2};" : "=l"(r) : "r"(lo), "n"(HI)); return r; }
constexpr uint32_t HI128 = (1u << 30) | (1024 >> 4), HI64 = (2u << 30) | (512 >> 4);
#define VOFF(x) ((uint32_t)(x) * (uint32_t)(1 - 65536))
DEVI bool elect() { uint32_t p; asm volatile("{\n.reg .pred q;\nelect.sync _|q, 0xffffffff;\nselp.u32 %0, 1, 0, q;\n}" : "=r"(p)); return p; }
DEVI void warp_signal(uint32_t bar) { __syncwarp(); if (elect()) mbar_arrive(bar); }

struct Scratch {
  uint4 kv[128][4][1024];
  uint4 o[8][2][8][2][1024];
  uint4 x[8][16][2048];
  uint4 zero[1024];
  uint4 statP[8][2048];
  uint4 statF[2048];
  uint4 csP[16][8][96];
  uint4 best[8][16];
  uint4 row[16][256];
  uint4 yP[128][112][2];
  uint4 x2[8][256];
  uint4 patch[128][64];
  unsigned flagKV[128][32];
  unsigned flagO[8][32];
  unsigned flagX[8][32];
  unsigned epoch;
};
__device__ __align__(1024) Scratch g_scr;
#define PROFT(cond, slot)
#define PROFW(cond, slot)
#define PROFD(cond, slot)
#define PROFX(cond, slot)
#define PROFY(cond, slot)

constexpr uint32_t SB0 = 65536, HOLE = 90112, SA2 = 98304, SB1 = 131072, SB2 = 155648, STG = 180224;
constexpr uint32_t KVA = 0, KVB = 98304, QO = 65536;
constexpr uint32_t MISC = 229376, CS = MISC, ONES = MISC + 768, BARS = MISC + 1792, INFO = MISC + 2208, WR = MISC + 2224, X2SEG = MISC + 2736, INFO2 = MISC + 2992, DUMP = MISC + 3040;
constexpr uint32_t PAR = HOLE, HV = HOLE + 2048, RED = HOLE + 6144, PATCH = 196608;
constexpr uint32_t SMEM_BYTES = 232448;
enum { B_FULLQ = 0, B_EMPTYQ = 3, B_FULLW = 6, B_EMPTYW = 12, B_HAFREE = 18, B_OFREE = 20,
       B_XFREE = 21,
       B_KVRDY = 23, B_ORDY = 27, B_XRDY = 35, B_STGE = 39,
       B_KVFULL = 42, B_RES = 46, B_PAR = 47, B_STG = 48, B_PFREE = 51, B_COUNT = 52,
       B_ROW = 154 };
#define BAR(x) (sb + BARS + 8 * (x))
DEVI uint32_t qa_off(int s) { return s == 2 ? SA2 : (uint32_t)s * 32768u; }
DEVI uint32_t qb_off(int s) { return s == 0 ? SB0 : (s == 1 ? SB1 : SB2); }
DEVI int kb_order(int bc, int n) {
  const int e = n < 9 ? n - 2 : n - 9;
  return n < 2 ? 2 * bc + n : 2 * (((e < 4 ? e + 4 : e - 4 + (e - 4 >= (bc & 3))) + (bc & 4)) & 7) + (n >= 9);
}
DEVI int wo_order(int bc, int n) { return (n & 8) | ((n + (bc & 6)) & 7); }
DEVI uint32_t w_off(int s) { return (uint32_t)((0x143065 >> (4 * s)) & 7) * 32768u; }
DEVI uint32_t w_par(int n, int s, int L) { return (n >= 6 && n < 12) ^ (s == 5) ^ (s != 2 && L); }
DEVI uint32_t w_aoff(int n, int s) { return n == 3 ? QO : w_off(s); }
DEVI int w_next(int n, int s) { return s == 5 ? 0 : (n == 13 ? 3 : s + 1); }

struct Params {
  CUtensorMap mX, mXh, mWq, mWo, mWg, mWu, mWp, mWd;
  const bf16 *x0, *wqkv, *wo, *wr, *wg, *wu, *wd;
  bf16* out;
  Scratch* g;
  unsigned map[128];
};
#define BID ((int)(P.map[blockIdx.x] & 255))
#define FID ((int)(P.map[blockIdx.x] >> 8))
DEVI uint32_t uni(uint32_t v) { return __shfl_sync(0xffffffffu, v, 0); }
#define PQ_N 8
#define PQ_T 700
#define PF0_N 10
#define PF0_T 1600
#define PF1_E 24
#define PF1_T 1100
#define POL_Q1 POL_NORMAL
#define POL_X POL_NORMAL
#define PFA0_BAR 3
#define PFA1_BAR 0
#define PFA0_M 0
#define PFA1_M 0
#define PFA0_T 900
#define PFA1_T 700
#define PF1_S PF0_N
#define PF1_D 0
#define POL_G POL_NORMAL
#define POL_U POL_FIRST
#define POL_D POL_FIRST
#define JQ_N 6
#define WDSRC (P.wd + (size_t)min(fid, 111) * 32768)
#define WDSRC2 (P.wd + FID * 32768)
#define WD_N 4
#define THR_N 5
#define KV_D 1800
#define XD_D 300
#define W0_BAR 3
#define QEF_N 99
#define PACE_T 300
#define IDLE_T 11000
#define LATE_C 2
#define LATE_B B_XFREE + 1
#define LATE_P 0
#define KV_D1 200
#define KV_D2 1200
#define KV_DL 0
#define POL_KV0 POL_FIRST
#define POL_KV1 POL_FIRST
#define POL_O0 POL_FIRST
#define POL_O1 POL_FIRST
#define POL_W0 POL_NORMAL
#define POL_W1 POL_FIRST
#define POL_T POL_FIRST
#define U_C 8
#define ST_M 0
#define POL_Q0 POL_NORMAL
constexpr float LN_EPS = 1e-5f;
constexpr float QSCALE = 0.17677669529663687f * 1.4426950408889634f;

DEVI void fma8(float (&a)[8], uint4 v, float h) {
  a[0] = fmaf(bf_lo(v.x), h, a[0]); a[1] = fmaf(bf_hi(v.x), h, a[1]); a[2] = fmaf(bf_lo(v.y), h, a[2]); a[3] = fmaf(bf_hi(v.y), h, a[3]);
  a[4] = fmaf(bf_lo(v.z), h, a[4]); a[5] = fmaf(bf_hi(v.z), h, a[5]); a[6] = fmaf(bf_lo(v.w), h, a[6]); a[7] = fmaf(bf_hi(v.w), h, a[7]);
}
DEVI uint4 ldsv128(uint32_t a) { uint4 v; asm volatile("ld.volatile.shared.v4.u32 {%0,%1,%2,%3}, [%4];" : "=r"(v.x), "=r"(v.y), "=r"(v.z), "=r"(v.w) : "r"(a) : "memory"); return v; }
DEVI float ldsv32f(uint32_t a) { float v; asm volatile("ld.volatile.shared.f32 %0, [%1];" : "=f"(v) : "r"(a) : "memory"); return v; }
DEVI uint32_t clk() { uint32_t t; asm volatile("mov.u32 %0, %%clock;" : "=r"(t)); return t; }
DEVI int fresh_tid() { int t; asm volatile("mov.u32 %0, %%tid.x;" : "=r"(t)); return t & 127; }
DEVI float fold8(const float (&a)[8]) {
  const int lane = threadIdx.x & 31;
  const bool u = lane & 16, v = lane & 8, x = lane & 4;
  float b0 = (u ? a[4] : a[0]) + __shfl_xor_sync(0xffffffffu, u ? a[0] : a[4], 16), b1 = (u ? a[5] : a[1]) + __shfl_xor_sync(0xffffffffu, u ? a[1] : a[5], 16);
  float b2 = (u ? a[6] : a[2]) + __shfl_xor_sync(0xffffffffu, u ? a[2] : a[6], 16), b3 = (u ? a[7] : a[3]) + __shfl_xor_sync(0xffffffffu, u ? a[3] : a[7], 16);
  float c0 = (v ? b2 : b0) + __shfl_xor_sync(0xffffffffu, v ? b0 : b2, 8), c1 = (v ? b3 : b1) + __shfl_xor_sync(0xffffffffu, v ? b1 : b3, 8);
  return (x ? c1 : c0) + __shfl_xor_sync(0xffffffffu, x ? c0 : c1, 4);
}
DEVI float swiglu(float g, float u) { g = bf_round(g); return bf_round(bf_round(__fdividef(g, 1.f + __expf(-g))) * bf_round(u)); }

template<int J0, int J1> DEVI void exp_pack(const float (&s)[32], uint32_t (&p)[16]) {
  #pragma unroll
  for (int j = J0; j < J1; j++) p[j] = pack_bf16(ex2f(s[2 * j]), ex2f(s[2 * j + 1]));
}
DEVI bool attn_pack(const float (&o)[20], uint32_t (&ob)[8]) {
  const float lo = 5.421010862427522e-20f, hi = 1.8446744073709552e19f;
  float i0, i1; asm("rcp.approx.ftz.f32 %0, %1;" : "=f"(i0) : "f"(o[16])); asm("rcp.approx.ftz.f32 %0, %1;" : "=f"(i1) : "f"(o[18]));
  #pragma unroll
  for (int e = 0; e < 8; e++) ob[e] = pack_bf16(o[2 * e] * ((e & 1) ? i1 : i0), o[2 * e + 1] * ((e & 1) ? i1 : i0));
  return __all_sync(0xffffffffu, o[16] >= lo && o[16] <= hi && o[18] >= lo && o[18] <= hi);
}
DEVI void attn_store(const uint32_t (&ob)[8], bool ok, uint32_t st, uint32_t sb, uint32_t bar) {
  stsm_x4(ok ? st : sb + DUMP, ob[0], ob[1], ob[2], ob[3]); stsm_x4(ok ? st ^ 32 : sb + DUMP, ob[4], ob[5], ob[6], ob[7]);
  __syncwarp();
  asm volatile("{\n.reg .pred p, q;\nelect.sync _|q, 0xffffffff;\nsetp.ne.and.u32 p, %1, 0, q;\n@p mbarrier.arrive.shared::cta.b64 _, [%0];\n}" :: "r"(bar), "r"((uint32_t)ok) : "memory");
}
DEVI void attn_exact(uint32_t st, uint32_t kv, int t, bool hasprev, uint32_t bar) {
  const int lane = threadIdx.x & 31;
  #pragma unroll 1
  for (int row = ((threadIdx.x >> 5) & 3) * 16, n = 0; n < 16; n++, row++) {
    const int k1 = 256 + t * 64 + row;
    float m = -INFINITY, l = 0.f, o = 0.f;
    #pragma unroll 1
    for (int k0 = hasprev ? k1 - 255 : 256; k0 <= k1; k0 += 32) {
      const int k = min(k0 + lane, k1), r = k & 63;
      float sc = 0.f;
      #pragma unroll 1
      for (int c = 0; c < 16; c++) {
        uint32_t a = lds32(st + row * 64 + ((c * 4) ^ ((row & 6) << 3))), b = lds32(kv + (k >> 6) * 8192 + r * 64 + ((c * 4) ^ ((r & 6) << 3)));
        sc = fmaf(bf_lo(a), bf_lo(b), fmaf(bf_hi(a), bf_hi(b), sc));
      }
      float mn = fmaxf(m, sc);
      #pragma unroll 1
      for (int x = 16; x; x >>= 1) mn = fmaxf(mn, __shfl_xor_sync(0xffffffffu, mn, x));
      const float al = ex2f(m - mn), pr = ex2f(sc - mn);
      m = mn; l *= al; o *= al;
      #pragma unroll 1
      for (int q = k0; q <= min(k0 + 31, k1); q++) {
        const float z = __shfl_sync(0xffffffffu, pr, q - k0);
        uint32_t b = lds32(kv + (q >> 6) * 8192 + 4096 + (q & 63) * 64 + (((lane >> 1) * 4) ^ ((q & 6) << 3)));
        l += z; o = fmaf(z, (lane & 1) ? bf_hi(b) : bf_lo(b), o);
      }
    }
    __syncwarp();
    sts16(st + row * 64 + ((lane * 2) ^ ((row & 6) << 3)), pack_bf16(__fdividef(o, l), 0.f));
  }
  warp_signal(bar);
}

template<int K0, int K1, int DONE = 0> DEVI void exp_pv(const float (&s)[32], uint32_t (&p)[16], float (&o)[20], uint32_t vd, bool accum) {
  #pragma unroll
  for (int ks = K0; ks < K1; ks++) {
    if (ks >= DONE) {
      #pragma unroll
      for (int j = 4 * ks; j < 4 * ks + 4; j++) p[j] = pack_bf16(ex2f(s[2 * j]), ex2f(s[2 * j + 1]));
    }
    asm volatile("" : "+r"(p[4 * ks]), "+r"(p[4 * ks + 1]), "+r"(p[4 * ks + 2]), "+r"(p[4 * ks + 3]));
    wg_fence();
    wgmma_rs_n40<1>(o, p[ks * 4], p[ks * 4 + 1], p[ks * 4 + 2], p[ks * 4 + 3], mkd<HI64>(vd + VOFF(ks * 64)), ks ? 1 : accum);
  }
}
template<int K0, int K1> DEVI void exp_pv2(const float (&s)[32], const float (&sx)[32], uint32_t (&p)[16], uint32_t (&px)[16], float (&o)[20], uint32_t v0, uint32_t v4,
                  const uint32_t (&msk)[9], int tdiag) {
  #pragma unroll
  for (int ks = K0; ks < K1; ks++) {
    #pragma unroll
    for (int j = 4 * ks; j < 4 * ks + 4; j++) {
      const int c = 8 * (j >> 1) - 8 * (j & 1);
      const uint32_t e = pack_bf16(ex2f(c > tdiag ? s[2 * j] : sx[2 * j]), ex2f(c + 1 > tdiag ? s[2 * j + 1] : sx[2 * j + 1])), m = msk[(j >> 1) - (j & 1) + 1];
      p[j] = e & m; px[j] = e & ~m;
      asm volatile("" : "+r"(p[j]), "+r"(px[j]));
    }
    wg_fence();
    wgmma_rs_n40<1>(o, p[ks * 4], p[ks * 4 + 1], p[ks * 4 + 2], p[ks * 4 + 3], mkd<HI64>(v0 + VOFF(ks * 64)), 1);
    wgmma_rs_n40<1>(o, px[ks * 4], px[ks * 4 + 1], px[ks * 4 + 2], px[ks * 4 + 3], mkd<HI64>(v4 + VOFF(ks * 64)), 1);
  }
}

template<int J0> DEVI void qkv_store(const float (&a)[96], float p0, float p1, uint32_t d) {
  #pragma unroll
  for (int hh = 0; hh < 2; hh++) {
    const int j = 4 * (J0 + 2 * hh);
    stsm_x4(d ^ (hh << 5), pack_bf16(a[j] * p0, a[j + 1] * p0), pack_bf16(a[j + 2] * p1, a[j + 3] * p1),
                           pack_bf16(a[j + 4] * p0, a[j + 5] * p0), pack_bf16(a[j + 6] * p1, a[j + 7] * p1));
  }
}
DEVI void mean_step(float (&a)[96], float m0, float m1, uint32_t cd, bool z) {
  const uint32_t u0 = z ? 0u : __float_as_uint(m0), u1 = z ? 0u : __float_as_uint(m1);
  uint32_t ma[4] = {__byte_perm(u0, 0u, 0x1010), __byte_perm(u1, 0u, 0x1010), __byte_perm(u0, 0u, 0x3232), __byte_perm(u1, 0u, 0x3232)};
  keep(ma);
  wg_fence();
  wgmma_rs_n192<1>(a, ma[0], ma[1], ma[2], ma[3], mkd<2>(cd), 1);
  wg_commit();
}

template<bool FIRST> DEVI void qkv_block(float (&aX)[96], float (&aY)[96], uint32_t sb16, int s, int tX, int tY) {
  uint32_t a16 = sb16 + (qa_off(s) >> 4), b16 = (sb16 + (qb_off(s) >> 4)) | ((8192u >> 4) << 16);
  uint32_t ax = (a16 + tX * 512) | 0x10000u, ay = (a16 + tY * 512) | 0x10000u;
  wg_fence();
  #pragma unroll
  for (int ks = 0; ks < 4; ks++) {
    wgmma_ss_n192<1>(aX, mkd<HI128>(ax + ks * 2), mkd<HI128>(b16 + ks * 128), !(FIRST && ks == 0));
    wgmma_ss_n192<1>(aY, mkd<HI128>(ay + ks * 2), mkd<HI128>(b16 + ks * 128), !(FIRST && ks == 0));
  }
  wg_commit();
}
DEVI void qkv_half(float (&a)[96], uint32_t sb16, int t, uint32_t sa, uint32_t sbb) {
  wg_fence();
  #pragma unroll
  for (int ks = 0; ks < 4; ks++)
    wgmma_ss_n192<1>(a, mkd<HI128>(((sb16 + (sa >> 4) + t * 512) | 0x10000u) + ks * 2), mkd<HI128>(((sb16 + (sbb >> 4)) | ((8192u >> 4) << 16)) + ks * 128), 1);
  wg_commit();
}
DEVI void wo_block(float (&acc)[64], uint32_t sb16, int n, int s, int wg) {
  uint32_t a16 = (sb16 + (w_aoff(n, s) >> 4) + wg * 256) | 0x10000u, b16 = (sb16 + (w_off(s) >> 4) + 1024) | ((8192u >> 4) << 16);
  wg_fence();
  #pragma unroll
  for (int ks = 0; ks < 4; ks++)
    wgmma_ss_n128<1>(acc, mkd<HI64>(a16 + (ks >> 1) * 512 + (ks & 1) * 2), mkd<HI128>(b16 + ks * 128), 1);
  wg_commit();
}
DEVI void consumer(const Params& P, uint32_t sb, int wg) {
  const int w = uni((threadIdx.x >> 5) & 3);
  #define LAYER uni(mbar_test(BAR(B_XRDY + wg * 2 + 1), 0))
  #define IDS L = LAYER; const int tid = fresh_tid(), lane = tid & 31
  const uint32_t ids = uni(P.map[blockIdx.x]);
  const int bi = (ids >> 4) & 7, rh = ids & 1, bc = (ids & 15) >> 1, fid = ids >> 8;
  const int tX = 3 - wg, tY = wg;
  constexpr uint32_t sb16 = 1024 >> 4;
  #pragma unroll 1
  while (true) {
    int L = LAYER;
    float2 fa, fb;
    {
      float aX[96], aY[96];
      const bool lead = fresh_tid() == 0;
      mbar_wait(BAR(B_FULLQ), 0);
      PROFW(threadIdx.x == 0, L * 8 + 1);
      qkv_block<true>(aX, aY, sb16, 0, tX, tY);
      #pragma unroll 1
      for (int n = 1, s = 1, ps = 0, ph = 0; n < 14; n++) {
        mbar_wait(BAR(B_FULLQ + s), ph ^ (s ? L : 0));
        PROFD(threadIdx.x == 0 && L && (n == 2 || n == 3 || n == 7 || n == 11 || n == 13), n == 2 ? 48 : 49 + (n >> 2));
        qkv_block<false>(aX, aY, sb16, s, tX, tY);
        wg_wait<1>(); if (lead) mbar_arrive(BAR(B_EMPTYQ + ps));
        ps = s; if (s == 2) { s = 0; ph ^= 1; } else s++;
      }
      mbar_wait(BAR(B_FULLQ + 2), L);
      qkv_half(aX, sb16, tX, SA2, SB2);
      mbar_wait(BAR(B_ROW), L);
      IDS;
      const uint32_t pa = sb + PAR + (w * 16 + (lane >> 2)) * 8;
      float2 p0 = lds64f(pa + tX * 512), p1 = lds64f(pa + tX * 512 + 64), p2 = lds64f(pa + tY * 512), p3 = lds64f(pa + tY * 512 + 64);
      mean_step(aX, p0.y, p1.y, sb16 + (CS >> 4), lane & 3);
      mbar_wait(BAR(B_FULLQ), 1);
      qkv_half(aX, sb16, tX, 0, SB0);
      wg_wait<3>(); if (lead) mbar_arrive(BAR(B_EMPTYQ + 1));
      bar_sync(1, 256);
      qkv_half(aY, sb16, tY, SA2, SB2);
      wg_wait<1>(); keep(aX);
      const int srow = w * 16 + (lane & 15);
      const uint32_t x0 = sb + srow * 64 + (((lane >> 4) ^ ((srow >> 1) & 3)) << 4), xX = x0 + (4 + tX) * 8192, xY = x0 + (4 + tY) * 8192;
      qkv_store<8>(aX, p0.x, p1.x, xX + KVA); qkv_store<16>(aX, p0.x, p1.x, xX + KVA + 4096);
      warp_signal(BAR(B_KVRDY + wg * 2));
      qkv_half(aY, sb16, tY, 0, SB0);
      mean_step(aY, p2.y, p3.y, sb16 + (CS >> 4), fresh_tid() & 3);
      wg_wait<2>(); if (lead) mbar_arrive(BAR(B_EMPTYQ + 2));
      mbar_wait(BAR(B_EMPTYQ + 2), L);
      qkv_store<12>(aX, p0.x, p1.x, xX + KVB); qkv_store<20>(aX, p0.x, p1.x, xX + KVB + 4096);
      wg_wait<0>(); keep(aY);
      if (lead) mbar_arrive(BAR(B_EMPTYQ));
      PROFW(threadIdx.x == 0, L * 8 + 2);
      qkv_store<8>(aY, p2.x, p3.x, xY + KVA); qkv_store<16>(aY, p2.x, p3.x, xY + KVA + 4096);
      qkv_store<12>(aY, p2.x, p3.x, xY + KVB); qkv_store<20>(aY, p2.x, p3.x, xY + KVB + 4096);
      warp_signal(BAR(B_KVRDY + wg * 2 + 1));
      p0.x *= QSCALE; p1.x *= QSCALE; p2.x *= QSCALE; p3.x *= QSCALE;
      mbar_wait(BAR(B_EMPTYQ), 1);
      qkv_store<0>(aX, p0.x, p1.x, x0 + QO + tX * 4096);
      qkv_store<0>(aY, p2.x, p3.x, x0 + QO + tY * 4096); qkv_store<4>(aY, p2.x, p3.x, x0 + QO + 16384 + tY * 4096);
      { const float2* f = (const float2*)&P.g->statF[bi * 256 + rh * 128 + (wg ^ rh) * 64 + w * 16 + (lane >> 2)]; fa = __ldcg(f); fb = __ldcg(f + 16); }
      mbar_wait(BAR(B_PAR), L);
      qkv_store<4>(aX, p0.x, p1.x, x0 + QO + 16384 + tX * 4096);
      const int prow = (int)uni(lds32(sb + INFO)) - bi * 256;
      if ((prow >> 4) == tX * 4 + w || (prow >> 4) == tY * 4 + w) {
        __syncwarp();
        if (lane < 24) sts128(sb + (prow & 63) * 64 + (((lane ^ (prow >> 1)) & 3) << 4) +
                              (lane < 8 ? QO + (lane >> 2) * 16384 + (prow >> 6) * 4096 : ((lane & 4) ? KVB : KVA) + (4 + (prow >> 6)) * 8192 + (lane >> 4) * 4096),
                              lds128(sb + PATCH + lane * 16));
      }
      fence_async_smem();
      bar_sync(1, 256);
    }
    PROFW(threadIdx.x == 0, L * 8 + 3);
    {
      IDS;
      float s0[32], s1[32], sx[32], o[20], op[20];
      uint32_t p0[16], p1[16], px[16], msk[9];
      const int tdiag = w * 16 + (lane >> 2) - 2 * (lane & 3);
      const uint32_t ones = (sb16 + (ONES >> 4)) << 16;
      const uint32_t qX = (sb16 + (QO >> 4) + tX * 256) | 0x10000u, qY = (sb16 + (QO >> 4) + tY * 256) | 0x10000u;
      const uint32_t kXB = (sb16 + (KVB >> 4) + tX * 512) | 0x10000u;
      uint32_t redo = 0;
      const uint32_t ost = sb + QO + (w * 16 + (lane & 15)) * 64 + (((lane >> 4) ^ ((lane >> 1) & 3)) << 4);
      #define QA(s, q, k) do { wg_fence(); wgmma_ss_n64<0>(s, mkd<HI64>(q), mkd<HI64>(k), 0); } while (0)
      #define QB(s, q, k) wgmma_ss_n64<0>(s, mkd<HI64>((q) + 2), mkd<HI64>((k) + 2), 1)
      #define QA2(q, k) do { QA(s1, q, k); wgmma_ss_n64<0>(sx, mkd<HI64>(q), mkd<HI64>((k) + 2048), 0); } while (0)
      #define QB2(q, k) do { QB(s1, q, k); QB(sx, q, (k) + 2048); } while (0)
      #define VB(v, b) ((v) + VOFF((b) * 512))
      #define MID() do { wg_commit(); wg_wait<1>(); } while (0)
      QA(s0, qX + 1024, kXB + 1536); QB(s0, qX + 1024, kXB + 1536); wg_commit();
      #pragma unroll
      for (int e = 0; e < 20; e++) o[e] = 0.f;
      wg_wait<0>(); keep(s0);
      #pragma unroll 1
      for (int h = 1; h >= 0; h--) {
        const uint32_t kXA = kXB - ((KVB - KVA) >> 4), kX = h ? kXB : kXA, vX = VOFF((kX & 0xffffu) + 256) + ones;
        QA(s1, qX + h * 1024, kX + 1024);
        #pragma unroll
        for (int e = 0; e < 20; e++) op[e] = o[e];
        keep(op);
        exp_pv<0, 1>(s0, p0, o, VB(vX, 3), false); QB(s1, qX + h * 1024, kX + 1024); wg_commit();
        exp_pv<1, 2>(s0, p0, o, VB(vX, 3), true); MID(); keep(s1);
        exp_pv<2, 4>(s0, p0, o, VB(vX, 3), true);
        { int td = tdiag; asm volatile("" : "+r"(td));
          #pragma unroll
          for (int e = 0; e < 9; e++) msk[e] = ((8 * e - 8 > td) ? 0xFFFFu : 0u) | ((8 * e - 7 > td) ? 0xFFFF0000u : 0u);
          keep(msk); }
        exp_pv<0, 2>(s1, p1, o, VB(vX, 2), true);
        bar_sync(h ? 12 + wg : 4 + wg * 4, h ? 128 : 160);
        QA(s0, qX, kXA + 512 + h * 1024);
        exp_pv<2, 3>(s1, p1, o, VB(vX, 2), true); QB(s0, qX, kXA + 512 + h * 1024);
        exp_pv<3, 4>(s1, p1, o, VB(vX, 2), true); wg_commit();
        wg_wait<0>(); keep(s0); keep(p0); keep(p1); keep(o);
      }
      #pragma unroll 1
      for (int h = 0; h < 2; h++) {
        const uint32_t kb16 = sb16 + ((h ? KVB : KVA) >> 4), kX = (kb16 + tX * 512) | 0x10000u, kY = (kb16 + tY * 512) | 0x10000u, qx = qX + h * 1024, qy = qY + h * 1024;
        const uint32_t onesP = bi ? ones : (kb16 + 1984) << 16;
        const uint32_t vX = VOFF(kb16 + tX * 512 + 256), vY = VOFF(kb16 + tY * 512 + 256);
        uint32_t ob[8], v;
        v = VB(vX + (wg ? onesP : ones), 1);
        QA2(qx, kX);
        exp_pv<0, 1>(s0, p0, o, v, true); QB2(qx, kX); wg_commit();
        exp_pv<1, 2>(s0, p0, o, v, true); MID(); keep(s1); keep(sx);
        exp_pv<2, 4>(s0, p0, o, v, true);
        QA(s0, qy, kY + 1536);
        exp_pv2<0, 1>(s1, sx, p1, px, o, vX + onesP, VB(vX + ones, 4), msk, tdiag); QB(s0, qy, kY + 1536); wg_commit();
        exp_pv2<1, 2>(s1, sx, p1, px, o, vX + onesP, VB(vX + ones, 4), msk, tdiag); MID(); keep(s0); keep(p0);
        exp_pv2<2, 4>(s1, sx, p1, px, o, vX + onesP, VB(vX + ones, 4), msk, tdiag); wg_commit();
        v = VB(vY + (wg ? ones : onesP), 3);
        QA(s1, qy, kY + 1024);
        exp_pack<0, 4>(s0, p0);
        QB(s1, qy, kY + 1024); MID(); keep(o); keep(p1); keep(px);
        bool ok = attn_pack(o, ob); keep(ob);
        exp_pv<0, 2, 1>(s0, p0, o, v, false); MID(); keep(s1);
        attn_store(ob, ok, ost + (h * 4 + tX) * 4096, sb, BAR(B_ORDY + wg * 4 + h * 2)); redo |= ok ? 0u : 1u << (h * 2);
        exp_pv<2, 4>(s0, p0, o, v, true);
        v = VB(vY + onesP, 2);
        exp_pv<0, 1>(s1, p1, o, v, true);
        bar_sync(5 + wg * 4 + h * 2, 160);
        QA(s0, qy, kY + 512);
        exp_pv<1, 2>(s1, p1, o, v, true); QB(s0, qy, kY + 512); wg_commit();
        exp_pv<2, 3>(s1, p1, o, v, true); MID(); keep(s0); keep(p0);
        exp_pv<3, 4>(s1, p1, o, v, true);
        v = VB(vY + onesP, 1);
        QA2(qy, kY);
        exp_pv<0, 1>(s0, p0, o, v, true); QB2(qy, kY); wg_commit();
        exp_pv<1, 2>(s0, p0, o, v, true); MID(); keep(s1); keep(sx); keep(p1);
        exp_pv<2, 4>(s0, p0, o, v, true);
        exp_pv2<0, 1>(s1, sx, p1, px, o, vY + onesP, VB(vY + ones, 4), msk, tdiag);
        bar_sync(6 + wg * 4, h ? 128 : 160);
        QA(s0, h ? qy : qX + 1024, kXB + 512);
        exp_pv2<1, 2>(s1, sx, p1, px, o, vY + onesP, VB(vY + ones, 4), msk, tdiag); QB(s0, h ? qy : qX + 1024, kXB + 512);
        exp_pv2<2, 4>(s1, sx, p1, px, o, vY + onesP, VB(vY + ones, 4), msk, tdiag); wg_commit();
        wg_wait<0>(); keep(o); keep(s0); keep(p0); keep(p1); keep(px);
        ok = attn_pack(o, ob); attn_store(ob, ok, ost + (h * 4 + tY) * 4096, sb, BAR(B_ORDY + wg * 4 + h * 2 + 1)); redo |= ok ? 0u : 2u << (h * 2);
        #pragma unroll
        for (int e = 0; e < 20; e++) o[e] = op[e];
      }
      #undef QA
      #undef QB
      #undef QA2
      #undef QB2
      #undef VB
      #undef MID
      if (redo) {
        #pragma unroll 1
        for (int u = 0; u < 4; u++) if ((redo >> u) & 1) {
          const int h = u >> 1, t = (u & 1) ? tY : tX;
          attn_exact(sb + QO + (h * 4 + t) * 4096, sb + (h ? KVB : KVA), t, bi > 0, BAR(B_ORDY + wg * 4 + u));
        }
      }
    }
    PROFW(threadIdx.x == 0, L * 8 + 4);
    {
      IDS;
      const int t256 = wg * 128 + tid;
      float acc[64];
      const int tt = wg ^ rh;
      const int grow = bi * 256 + rh * 128 + tt * 64 + w * 16 + (lane >> 2);
      float al0 = 1.f, be0 = 0.f, al1 = 1.f, be1 = 0.f;
      const int idx0 = (int)uni(lds32(sb + INFO));
      const uint32_t tag = lds32(sb + INFO + 8) + L;
      uint4* const sp = &P.g->statP[bc][grow + (lane & 1) * 8];
      uint4* const yp = &P.g->yP[t256 >> 1][min(fid, 111)][t256 & 1];
      if (L) {
        float r0 = rsqrtf(fa.y + LN_EPS), r1 = rsqrtf(fb.y + LN_EPS);
        if (grow != idx0) { al0 = 1.f + r0; be0 = -fa.x * r0; }
        if (grow + 8 != idx0) { al1 = 1.f + r1; be1 = -fb.x * r1; }
      }
      const int srow = tt * 64 + w * 16 + (lane & 15);
      const uint32_t ra = sb + srow * 128 + (((lane >> 4) ^ (srow & 7)) << 4);
      mbar_wait(BAR(B_FULLW + 5), L);
      if ((idx0 >> 4) == bi * 16 + rh * 8 + tt * 4 + w) {
        int r = idx0 & 127;
        if (lane < 16) sts128(sb + 32768 + (lane >> 3) * 16384 + r * 128 + (((lane & 7) ^ (r & 7)) << 4), lds128(sb + X2SEG + lane * 16));
        fence_async_smem();
        __syncwarp();
      }
      #pragma unroll
      for (int jj = 0; jj < 8; jj++) {
        uint32_t r[4]; ldsm_x4((ra + 32768 + (jj >> 2) * 16384) ^ ((jj & 3) << 5), r[0], r[1], r[2], r[3]);
        #pragma unroll
        for (int e = 0; e < 4; e++) {
          acc[8 * jj + 2 * e] = fmaf(bf_lo(r[e]), (e & 1) ? al1 : al0, (e & 1) ? be1 : be0);
          acc[8 * jj + 2 * e + 1] = fmaf(bf_hi(r[e]), (e & 1) ? al1 : al0, (e & 1) ? be1 : be0);
        }
      }
      keep(acc);
      bar_sync(12 + wg, 128);
      if (!(lane & 2)) st_ll(sp, 0u, 0u, 0u, 0u);
      uint2 wd[4];
      #pragma unroll
      for (int e = 0; e < 4; e++) { wd[e] = make_uint2(0u, 0u); if (L) wd[e] = ldg_stream((const uint2*)(WDSRC) + t256 + (28 + e) * 256); }
      PROFW(t256 == 0, L * 8 + 5);
      #pragma unroll 1
      for (int n = 0, q = 0, pq = 5; n < 16; n++) {
        mbar_wait(BAR(B_FULLW + q), w_par(n, q, L));
        PROFD(t256 == 0 && !L && (n == 4 || n == 7 || n == 8 || n == 12), (n == 7 ? 63 : 41 + (n >> 2)));
        wo_block(acc, sb16, n, q, tt);
        wg_wait<1>(); if (tid == 0) mbar_arrive(BAR(B_EMPTYW + pq));
        pq = q; q = w_next(n, q);
      }
      mbar_wait(BAR(B_EMPTYW + 5), L);
      wg_wait<0>(); keep(acc);
      if (tid == 0) mbar_arrive(BAR(B_EMPTYW + 4));
      PROFW(t256 == 0, L * 8 + 6);
      {
        float s1a = 0.f, s2a = 0.f, da = 0.f, s1b = 0.f, s2b = 0.f, db = 0.f;
        #pragma unroll
        for (int j = 0; j < 16; j++) {
          const float* a = acc + 4 * j; float2 wv = lds64f(sb + WR + j * 32 + (lane & 3) * 8);
          s1a += a[0] + a[1]; s1b += a[2] + a[3];
          s2a = fmaf(a[0], a[0], s2a); s2b = fmaf(a[2], a[2], s2b); s2a = fmaf(a[1], a[1], s2a); s2b = fmaf(a[3], a[3], s2b);
          da = fmaf(a[0], wv.x, da); db = fmaf(a[2], wv.x, db); da = fmaf(a[1], wv.y, da); db = fmaf(a[3], wv.y, db);
        }
        bool odd = lane & 1;
        float u1 = (odd ? s1b : s1a) + __shfl_xor_sync(0xffffffffu, odd ? s1a : s1b, 1);
        float u2 = (odd ? s2b : s2a) + __shfl_xor_sync(0xffffffffu, odd ? s2a : s2b, 1);
        float u3 = (odd ? db : da) + __shfl_xor_sync(0xffffffffu, odd ? da : db, 1);
        u1 += __shfl_xor_sync(0xffffffffu, u1, 2); u2 += __shfl_xor_sync(0xffffffffu, u2, 2); u3 += __shfl_xor_sync(0xffffffffu, u3, 2);
        if (!(lane & 2)) st_ll(sp, __float_as_uint(u1), __float_as_uint(u2), __float_as_uint(u3), tag);
      }
      const uint32_t xa = ra + rh * 16384;
      #pragma unroll
      for (int jj = 0; jj < 8; jj++) {
        const float* a = acc + 8 * jj;
        stsm_x4((xa + (jj >> 2) * 32768) ^ ((jj & 3) << 5), pack_bf16(a[0], a[1]), pack_bf16(a[2], a[3]), pack_bf16(a[4], a[5]), pack_bf16(a[6], a[7]));
        if (jj == 7) fence_async_smem();
        if ((jj & 3) == 3) warp_signal(BAR(B_XRDY + wg * 2 + (jj >> 2)));
      }
      PROFW(t256 == 0, L * 8 + 7);
      if (L) {
        mbar_wait(BAR(B_PAR), 0);
        { float2 pa = lds64f(sb + PAR + (grow & 127) * 8), pb = lds64f(sb + PAR + (grow & 127) * 8 + 64); al0 = pa.x; be0 = pa.y; al1 = pb.x; be1 = pb.y; }
        uint32_t rs[32];
        #pragma unroll
        for (int j = 0; j < 16; j++) {
          rs[2 * j] = pack_bf16(fmaf(acc[4 * j], al0, be0), fmaf(acc[4 * j + 1], al0, be0));
          rs[2 * j + 1] = pack_bf16(fmaf(acc[4 * j + 2], al1, be1), fmaf(acc[4 * j + 3], al1, be1));
        }
        #pragma unroll
        for (int jj = 0; jj < 8; jj++) stsm_x4((xa + (jj >> 2) * 32768) ^ ((jj & 3) << 5), rs[4 * jj], rs[4 * jj + 1], rs[4 * jj + 2], rs[4 * jj + 3]);
        PROFW(t256 == 0, 16);
        if (fid >= 112) bar_arrive(3, 384);
        else {
          float d[4] = {0.f, 0.f, 0.f, 0.f};
          mbar_wait(BAR(B_FULLW + wg * 3), 0); mbar_wait(BAR(B_FULLW + wg * 3 + 1), 0);
          bar_sync(3, 384);
          PROFW(t256 == 0, 29);
          #pragma unroll 1
          for (int g = 0; g < 4; g++) {
            const uint32_t ad = (sb16 + (wg ? 6144 : 10240) + (g >> 1) * 2048 + (g & 1) * 512) | (1024u << 16), bd = (sb16 + (HV >> 4) + wg * 64 + g * 16) | 0x10000u;
            wg_fence();
            #pragma unroll
            for (int ks = 0; ks < 8; ks++) wgmma_ss_n8<0, 1>(d, mkd<HI64>(ad + ks * 64), mkd<8>(bd + ks * 2), 1);
            wg_commit();
          }
          mbar_wait(BAR(B_FULLW + 2), 0);
          wg_wait<0>(); keep(d);
          if (!(lane & 3)) { sts32f(sb + PAR + 1024 + wg * 256 + w * 64 + lane, d[0]); sts32f(sb + PAR + 1056 + wg * 256 + w * 64 + lane, d[2]); }
          bar_sync(1, 256);
          const uint32_t ga = sb + PAR + 1024 + lane * 4, aa = sb + HV + (t256 >> 5) * 128;
          sts32f(aa + lane * 4, swiglu(lds32f(ga) + lds32f(ga + 256), lds32f(ga + 128) + lds32f(ga + 384)));
          __syncwarp();
          PROFW(t256 == 0, 26);
          float y0 = 0.f, y1 = 0.f, y2 = 0.f, y3 = 0.f;
          uint32_t tbl = rh ? 0x001459a8u : 0x023679a8u;
          uint4 a4 = lds128(aa + 112);
          #pragma unroll 2
          for (int n = 0; n < 8; n++, tbl >>= 4) {
            const uint32_t src = sb + t256 * 8 + (tbl & 15) * 8192;
            const uint4 an = lds128(aa + ((0x00123564u >> (4 * n)) & 15) * 16);
            #pragma unroll
            for (int e = 0; e < 4; e++) {
              const float av = __uint_as_float(e == 0 ? a4.x : (e == 1 ? a4.y : (e == 2 ? a4.z : a4.w)));
              y0 = fmaf(bf_lo(wd[e].x), av, y0); y1 = fmaf(bf_hi(wd[e].x), av, y1); y2 = fmaf(bf_lo(wd[e].y), av, y2); y3 = fmaf(bf_hi(wd[e].y), av, y3);
              const float2 v = lds64f(src + e * 2048); wd[e] = make_uint2(__float_as_uint(v.x), __float_as_uint(v.y));
            }
            a4 = an;
          }
          st_ll(yp, __float_as_uint(y0), __float_as_uint(y1), __float_as_uint(y2), (__float_as_uint(y3) & ~255u) | (lds32(sb + INFO + 12) + 1));
          PROFW(t256 == 0, 27);
        }
        return;
      }
      mbar_wait(BAR(B_XRDY + wg * 2 + 1), 0);
    }
  }
  #undef IDS
  #undef LAYER
}

DEVI void loader(const Params& P, uint32_t sb) {
  const int lane = threadIdx.x & 31;
  const int bid = uni(BID), bi = bid >> 4, bp = bid & 15, rh = bp & 1, bc = bp >> 1;
  uint32_t phq = 0, tag = 0;
  #pragma unroll 1
  for (int L = 0; L < 2; L++) {
    int s = 0;
    uint32_t rdy = 0;
    #pragma unroll 1
    for (int n = L ? 0 : 3; n < 16; n++) {
      int kb = L ? kb_order(bc, n) : n;
      mbar_wait(BAR(B_EMPTYQ + s), (phq >> s) & 1);
      phq ^= 1u << s;
      if (L && n == 1) { mbar_wait(BAR(B_XRDY + 1), 0); mbar_wait(BAR(B_XRDY + 3), 0); }
      if (elect()) {
        mbar_expect_tx(BAR(B_FULLQ + s), L && n < 2 ? 40960 : 57344);
        tma_3d_h(sb + qb_off(s), &P.mWq, bp * 64, kb * 64, 0, BAR(B_FULLQ + s), L && n >= QEF_N ? POL_FIRST : POL_NORMAL);
        if (!L) tma_2d(sb + qa_off(s), &P.mX, kb * 64, bi * 256, BAR(B_FULLQ + s));
      }
      if (L && n >= 2) {
        if (((rdy >> (2 * kb)) & 3) != 3) {
          do { rdy = __ballot_sync(0xffffffffu, ld_rlx(&P.g->flagX[bi][lane]) == tag); } while (((rdy >> (2 * kb)) & 3) != 3);
          fence_async_glob();
        }
        if (n == 3 || n == 4) mbar_wait(BAR(B_XFREE + n - 3), 0);
        if (elect()) bulk_g2s_h(sb + qa_off(s), P.g->x[bi][kb], 32768, BAR(B_FULLQ + s), POL_X);
      }
      PROFY(L && lane == 0 && (n == 2 || n == 3 || n == 9), n == 9 ? 60 : 56 + n);
      if (L && n == 2) { mbar_wait(BAR(B_FULLQ), 0); mbar_wait(BAR(B_FULLQ + 1), 1); if (lane < 2) mbar_arrive_peer(BAR(B_XFREE + lane)); }
      s = (s == 2) ? 0 : s + 1;
    }
    for (int q = 0; q < 3; q++) mbar_wait(BAR(B_EMPTYQ + q), (phq >> q) & 1);
    tag = lds32(sb + INFO + 8) + L;
    #pragma unroll 1
    for (int q = 0; q < 4; q++) {
            if (bi) {
        const unsigned* f = &P.g->flagKV[bid - 16][q];
        while (ld_rlx(f) != tag);
        fence_async_glob();
      }
      if (elect()) {
        mbar_expect_tx(BAR(B_KVFULL + q), 16384);
        bulk_g2s_h(sb + ((q >> 1) ? KVB : KVA) + ((q & 1) ? 0 : 16384), bi ? P.g->kv[bid - 16][q] : P.g->zero, 16384, BAR(B_KVFULL + q), L ? POL_KV1 : POL_KV0);
      }
      PROFY(!L && lane == 0 && bi && q != 2, 34 + (q + 1) / 2);
    }
    mbar_wait(BAR(B_ORDY), L);
    {
      const uint4* src = P.g->o[bi][0][0][rh];
      rdy = 0;
      #pragma unroll 1
      for (int n = 0, q = 0; n < 16; q = w_next(n, q), n++) {
        const int j = wo_order(bc, n);
        if (((rdy >> (2 * j)) & 3) != 3) {
          do { rdy = __ballot_sync(0xffffffffu, ld_rlx(&P.g->flagO[bi][lane]) == tag); } while (((rdy >> (2 * j)) & 3) != 3);
          fence_async_glob();
        }
        if (n >= 2) mbar_wait(n < 5 ? BAR(B_HAFREE + (n > 3)) : BAR(B_EMPTYW + q), n < 5 ? L : w_par(n, q, L) ^ 1);
        if (n == THR_N) mbar_wait(BAR(B_OFREE), L);
        if (elect()) { mbar_expect_tx(BAR(B_FULLW + q), 16384); bulk_g2s_h(sb + w_aoff(n, q), src + j * 2048, 16384, BAR(B_FULLW + q), L ? POL_O1 : POL_O0); }
      }
    }
    mbar_wait(BAR(B_OFREE), L);
  }
}

DEVI void ffn_prefetch(const Params& P, int q) {
  bulk_prefetch(q < 16 ? ((q & 1) ? P.wu : P.wg) + ((q >> 1) * 128 + blockIdx.x) * 3584 : P.wd + (min(FID, 111) * 8 + q - 16) * 4096, q < 16 ? 7168 : 8192);
}
DEVI void storer(const Params& P, uint32_t sb, int wg) {
  const int bid = uni(BID), bi = bid >> 4, rh = bid & 1, bc = (bid & 15) >> 1;
  const bool one = (threadIdx.x & 31) == 0;
  char* const g = (char*)P.g;
  const uint32_t tag0 = uni(((ld_rlx(&P.g->epoch) % 16383u) + 1u) << 2);
  #pragma unroll 1
  for (int L = 0; L < 2; L++) {
    const uint32_t tag = tag0 + L;
    if (wg) {
      #pragma unroll 1
      for (int r = threadIdx.x & 31; r < 256; r += 32) {
        uint4 v;
        do v = ld_ll(&P.g->statF[bi * 256 + r]); while (!__all_sync(0xffffffffu, v.w == tag));
        float var = __uint_as_float(v.y), c = rsqrtf(var + LN_EPS);
        if (L) { c += 1.f; c *= rsqrtf(fmaf(var * c, c, LN_EPS)); }
        const float mh = bf_round(__uint_as_float(v.x));
        sts64f(sb + PAR + r * 8, c, __uint_as_float(pack_bf16(mh, __uint_as_float(v.x) - mh)));
      }
      if (!L) mbar_wait(BAR(B_PAR), 0);
      warp_signal(BAR(B_ROW));
    }
    #pragma unroll 1
    for (int u = 0; u < 2 + 4 * wg; u++) {
      const int h = u < 2 ? u : u >> 2, hi = (u & 1) ^ 1;
      uint32_t src, dst, fl, b0, b1;
      if (u < 2) {
        src = (h ? KVB : KVA) + (3 - wg) * 16384; dst = offsetof(Scratch, kv) + (bid * 4 + h * 2 + wg) * 16384; fl = offsetof(Scratch, flagKV) + (bid * 32 + h * 2 + wg) * 4;
        b0 = BAR(B_KVRDY + ((u | wg) ? 1 : 0)); b1 = b0 + 16;
      } else {
        src = QO + (h * 2 + hi) * 8192; dst = offsetof(Scratch, o) + ((((bi * 2 + h) * 8 + bc) * 2 + hi) * 2 + rh) * 8192;
        fl = offsetof(Scratch, flagO) + (bi * 32 + h * 16 + (bid & 15)) * 4;
        b0 = BAR(B_ORDY + u - 2); b1 = b0 + 32;
      }
      mbar_wait(b0, L); mbar_wait(b1, L);
      if (u + wg == 1) {
        mbar_wait(BAR(B_PAR), L);
        const uint32_t t0 = clk(), dt = (wg ? KV_D1 : KV_D2) + (L ? KV_DL : 0); while (clk() - t0 < dt) __nanosleep(40);
      }
      fence_async_smem();
      PROFY(one && !L && u == 3 * wg, u ? 46 : 8);
      if (one && (u >= 2 || bi < 7)) bulk_s2g(g + dst, sb + src, u < 2 ? 16384 : 8192, ((ST_M >> (L * 2 + (u >= 2))) & 1) ? POL_FIRST : POL_NORMAL);
      if (one && u == 5) mbar_arrive(BAR(B_HAFREE + 1));
      if (u == 2 || u == 4) continue;
      bulk_wait<0>();
      PROFY(one && !L && u == 3 * wg, u ? 61 : 62);
      fence_rel();
      if (one) { st_rlx((unsigned*)(g + fl), tag); if (!wg || u > 2) mbar_arrive(BAR(B_HAFREE + h + (wg & h))); if (!wg && u) mbar_arrive(BAR(B_RES)); }
      PROFY(one && !L && (u > 2 || u == wg), u > 2 ? (u == 3 ? 38 : 54) : 32 + u);
    }
    if (L == 0) {
      char* dst = g + (offsetof(Scratch, x) + (bi * 16 + 2 * bc) * 32768 + rh * 16384);
      unsigned* f = (unsigned*)(g + (offsetof(Scratch, flagX) + (bi * 32 + bc * 4 + rh) * 4));
      const uint32_t a = sb + rh * 16384;
      if (wg == 0) {
        mbar_wait(BAR(B_XRDY), 0); mbar_wait(BAR(B_XRDY + 2), 0);
        fence_async_smem();
        PROFY(one, 41);
        if (one) bulk_s2g(dst, a, 16384);
        bulk_wait<0>();
        PROFY(one, 45);
        if (one) { mbar_arrive(BAR(B_XFREE)); mbar_arrive(BAR(B_PFREE)); }
        fence_rel();
        mbar_wait(BAR(B_XRDY + 1), 0); mbar_wait(BAR(B_XRDY + 3), 0);
        if (one) { st_rlx(f, tag); bulk_s2g(dst + 32768, a + 32768, 16384); }
        PROFY(one, 56);
        bulk_wait<0>();
        if (one) mbar_arrive(BAR(B_XFREE + 1));
        fence_rel();
        if (one) st_rlx(f + 2, tag);
        PROFY(one, 57);
      } else {
        mbar_wait(BAR(B_XRDY + 1), 0); mbar_wait(BAR(B_XRDY + 3), 0);
        mbar_wait(BAR(B_PFREE), 0);
        if (one) bulk_s2peer(a, 16384, BAR(B_FULLQ));
        { const uint32_t t0 = clk(); while (clk() - t0 < XD_D); }
        if (one) bulk_s2peer(a + 32768, 16384, BAR(B_FULLQ + 1));
      }
      if (wg == 0) {
        uint32_t t0 = clk() + PF1_D;
        #pragma unroll 1
        for (int q = PF1_S; q < PF1_E; q++) { while ((int)(clk() - t0) < 0) __nanosleep(50); if (one) ffn_prefetch(P, q); t0 += PF1_T; }
      }
    }
  }
}

DEVI void stg_issue(const Params& P, int c, uint32_t d, uint32_t du, uint32_t b) {
  mbar_expect_tx(b, 16384);
  if (c < 8) { tma_2d_h(d, &P.mWg, FID * 32, c * 128, b, du > 8192 ? POL_T : POL_G); tma_2d_h(d + du, &P.mWu, FID * 32, c * 128, b, du > 8192 || c < U_C ? POL_FIRST : POL_NORMAL); }
  else if (c < 12) tma_3d_h(d, &P.mWd, 0, FID * 32 + (c - 8) * 8, 0, b, POL_D);
  else tma_2d_h(d, &P.mWp, (c - 12) * 1024 + (BID >> 2) * 32, (BID & 3) * 256, b, POL_EF);
}
DEVI void pace() { const uint32_t t0 = clk(); while (clk() - t0 < PACE_T); }
DEVI void stager(const Params& P, uint32_t sb) {
  {
    const int b = blockIdx.x;
    uint32_t t0 = clk();
    #pragma unroll 1
    for (int q = 0; q < PQ_N; q++) { bulk_prefetch(P.wqkv + (q * 128 + b) * 3072, 6144); while (clk() - t0 < PQ_T) __nanosleep(50); t0 += PQ_T; }
    bulk_prefetch(P.wo + b * 8192, 16384);
    #pragma unroll 1
    for (int q = 0; q < PF0_N; q++) {
      while (clk() - t0 < PF0_T) __nanosleep(50);
      t0 += PF0_T;
      ffn_prefetch(P, q);
    }
  }
  const int bid = BID, bi = bid >> 4, rh = bid & 1, bc = (bid & 15) >> 1;
  #pragma unroll 1
  for (int L = 0; L < 2; L++) {
    const int nch = L ? (FID < 112 ? 8 : 0) : 15;
    mbar_wait(BAR(B_PAR), L); mbar_wait(BAR(B_KVFULL + W0_BAR), L);
    #pragma unroll 1
    for (int m = 0, r = 0; m < 16; r = w_next(m, r), m++) {
      const int sw = (m == 3 || m == 4) ? 7 : 0, n = m ^ sw, q = r ^ sw;
      if (n == 4) { mbar_wait(BAR(B_RES), L); mbar_wait(BAR(B_ORDY + 2), L); mbar_wait(BAR(B_ORDY + 6), L); }
      else if (n >= 2) mbar_wait(n < 5 ? BAR(B_HAFREE + (n > 2)) : BAR(B_EMPTYW + q), n < 5 ? L : w_par(n, q, L) ^ 1);
      if (n == THR_N) mbar_wait(BAR(B_OFREE), L);
      mbar_expect_tx(BAR(B_FULLW + q), 16384);
      tma_5d(sb + w_off(q) + 16384, &P.mWo, 0, 0, n >> 3, 2 * (wo_order(bc, n) & 7), 2 * bc, BAR(B_FULLW + q), L ? POL_W1 : POL_W0);
      if (n == 2) {
        #pragma unroll 1
        for (int e = 0; e < 2; e++) {
          mbar_expect_tx(BAR(B_FULLW + 5), 16384);
          if (L) bulk_g2s_h(sb + 32768 + e * 16384, P.g->x[bi][2 * bc + e] + rh * 1024, 16384, BAR(B_FULLW + 5));
          else tma_2d_h(sb + 32768 + e * 16384, &P.mXh, bc * 128 + e * 64, bi * 256 + rh * 128, BAR(B_FULLW + 5), POL_EF);
        }
      }
    }
    mbar_wait(BAR(B_EMPTYW + 5), L);
    if (L && nch) {
      const bf16* src = WDSRC2;
      mbar_expect_tx(BAR(B_FULLW + 2), 32768); mbar_expect_tx(BAR(B_FULLW + 2), 24576);
      #pragma unroll 1
      for (int e = 0; e < 3; e++) { bulk_g2s_h(sb + e * 32768 + (e < 2 ? (rh ^ 1) * 16384 : 0), src + e * 8192, e < 2 ? 16384 : 24576, BAR(B_FULLW + 2)); pace(); }
    }
        if (L == 0) { mbar_arrive_peer(BAR(B_PFREE)); mbar_wait(BAR(B_EMPTYW), 0); mbar_wait(BAR(B_EMPTYW + 1), 0); }
    #pragma unroll 1
    for (int c = FID < 112 ? 0 : 12, slot = 0; c < nch; c++, slot = slot == 2 ? 0 : slot + 1) {
      const int q = (c >> 1) + (c >> 2);
      if (!L && (c == LATE_C || c == 12)) mbar_wait(BAR(LATE_B), LATE_P);
      mbar_wait(L ? BAR(B_EMPTYW + q) : BAR(B_STGE + slot), L | ((0x71c7 >> c) & 1));
      #define CC c
      stg_issue(P, CC, L ? sb + w_off(q) + (c & 1) * 8192 : sb + STG + slot * 16384, 8192 << L, L ? BAR(B_FULLW + q) : BAR(B_STG + slot));
      if (L) pace();
    }
  }
}
DEVI void sum8(uint4 v, float& s1, float& s2) {
  float e[8] = {bf_lo(v.x), bf_hi(v.x), bf_lo(v.y), bf_hi(v.y), bf_lo(v.z), bf_hi(v.z), bf_lo(v.w), bf_hi(v.w)};
  #pragma unroll
  for (int q = 0; q < 8; q++) { s1 += e[q]; s2 = fmaf(e[q], e[q], s2); }
}
DEVI uint4 norm8(uint4 x, float m, float rs) {
  #define HN(v) pack_bf16((bf_lo(v) - m) * rs, (bf_hi(v) - m) * rs)
  return make_uint4(HN(x.x), HN(x.y), HN(x.z), HN(x.w));
  #undef HN
}
DEVI void put_f32(uint4 b, uint32_t d, uint32_t d2) {
  sts128(d, make_uint4(b.x << 16, b.x & 0xffff0000u, b.y << 16, b.y & 0xffff0000u));
  sts128(d + d2, make_uint4(b.z << 16, b.z & 0xffff0000u, b.w << 16, b.w & 0xffff0000u));
}
DEVI void put_bf16(uint4 b, uint32_t d) {
  sts64f(d, __uint_as_float(b.x), __uint_as_float(b.y)); sts64f(d + 1024, __uint_as_float(b.z), __uint_as_float(b.w));
  fence_async_smem();
}
DEVI uint4 best4(uint32_t p) {
  uint4 a = lds128(p), b = lds128(p + 16), c = lds128(p + 32), d = lds128(p + 48);
  if (b.x > a.x) a = b;
  if (d.x > c.x) c = d;
  return c.x > a.x ? c : a;
}
#define FL(x) __uint_as_float(x)
#define UI(x) __float_as_uint(x)
DEVI void aux(const Params& P, uint32_t sb) {
  int tid = fresh_tid();
  #define lane (tid & 31)
  #define wq (tid >> 5)
  uint32_t ids = P.map[blockIdx.x], tag;
  #define bid ((int)(ids & 255))
  #define fid ((int)(ids >> 8))
  #define bi (bid >> 4)
  #define bp (bid & 15)
  #define bc (bp >> 1)
  #define FRESH() do { tid = fresh_tid(); uint4 z_ = ldsv128(sb + INFO2 + 16); ids = z_.y; tag = z_.z + L; idx = z_.w; } while (0)
  {
    const uint32_t epoch = ld_rlx(&P.g->epoch);
    if (tid == 0) {
      mbar_expect_tx(BAR(B_STG), 49152);
      tma_3d(sb + STG, &P.mWq, bp * 64, bi * 128, 0, BAR(B_STG));
      tma_3d(sb + STG + 24576, &P.mWq, bp * 64, bi * 128 + 64, 0, BAR(B_STG));
    }
    __syncwarp();
    sts64f(sb + ONES + tid * 8, FL(0x3F803F80u), FL(0x3F803F80u));
    float s1 = 0.f, s2 = 0.f;
    { uint4 v = __ldg((const uint4*)P.wr + tid);
      if ((tid >> 4) == bc) put_f32(v, sb + WR + (tid & 15) * 32, 16);
      sum8(v, s1, s2);
      #pragma unroll 1
      for (int o = 16; o; o >>= 1) s1 += __shfl_xor_sync(0xffffffffu, s1, o);
      sts32f(sb + INFO2 + wq * 4, s1); }
    const uint4* src = (const uint4*)(P.x0 + (size_t)bid * 16384) + (tid >> 3) * 128 + (tid & 7);
    s1 = 0.f; s2 = 0.f;
    #pragma unroll 1
    for (int it = 0; it < 16; it += 4) {
      uint4 v0 = __ldg(src + it * 8), v1 = __ldg(src + it * 8 + 8), v2 = __ldg(src + it * 8 + 16), v3 = __ldg(src + it * 8 + 24);
      #pragma unroll 1
      for (int q = 0; q < 4; q++) { sum8(v0, s1, s2); v0 = v1; v1 = v2; v2 = v3; }
    }
    #pragma unroll 1
    for (int o = 1; o < 8; o <<= 1) { s1 += __shfl_xor_sync(0xffffffffu, s1, o); s2 += __shfl_xor_sync(0xffffffffu, s2, o); }
    tag = ((epoch % 16383u) + 1u) << 2;
    if (tid == 0) { sts128(sb + INFO, make_uint4(0x40000000u, 0u, tag, ((epoch % 127u) + 1u) << 1)); sts128(sb + INFO2 + 16, make_uint4(epoch, ids, tag, 0x40000000u)); }
    float m = s1 * (1.f / 1024.f);
    if ((tid & 7) == 0) st_ll(&P.g->statF[bid * 16 + (tid >> 3)], UI(m), UI(fmaxf(fmaf(-m, m, s2 * (1.f / 1024.f)), 0.f)), 0u, tag);
    bar_sync(2, 128);
    mbar_wait_b(BAR(B_STG), 0);
    if (tid < 96) {
      s1 = 0.f; s2 = 0.f;
      #pragma unroll 1
      for (int r = 0; r < 16; r++) {
        const uint32_t a = sb + STG + (r >> 3) * 24576 + wq * 8192 + (r & 7) * 128 + ((lane * 4) ^ ((r & 7) << 4));
        #pragma unroll
        for (int e = 0; e < 8; e++) { uint32_t v = lds32(a + e * 1024); s1 += bf_lo(v); s2 += bf_hi(v); }
      }
      st_ll(&P.g->csP[bp][bi][tid], UI(s1), UI(s2), 0u, tag);
      s1 = 0.f; s2 = 0.f;
      #pragma unroll 1
      for (int q = 0; q < 8; q += 2) {
        uint4 a, b; poll_ll2(&P.g->csP[bp][q][tid], &P.g->csP[bp][q + 1][tid], 0xffffffffu, tag, a, b);
        s1 += FL(a.x) + FL(b.x); s2 += FL(a.y) + FL(b.y);
      }
      const uint32_t hi = pack_bf16(-s1, -s2);
      sts32(sb + CS + (tid >> 2) * 32 + (tid & 3) * 4, hi);
      sts32(sb + CS + (tid >> 2) * 32 + (tid & 3) * 4 + 16, pack_bf16(-s1 - bf_lo(hi), -s2 - bf_hi(hi)));
    }
    fence_async_smem();
  }
  int idx;
  #pragma unroll 1
  for (int L = 0; L < 2; L++) {
    FRESH();
    {
      if ((unsigned)(bi - (idx >> 8)) < 2u) {
        const uint4* src = &P.g->patch[bp * 8 + (tid >> 6) * 4][tid & 63];
        const float4 z = poll_sum4(src, 64, tag);
        float q = z.x, k = z.y, v = z.z;
        q += __shfl_xor_sync(0xffffffffu, q, 1); k += __shfl_xor_sync(0xffffffffu, k, 1); v += __shfl_xor_sync(0xffffffffu, v, 1);
        bar_sync(2, 128);
        const uint32_t d = sb + PATCH + (tid & ~1), kv = pack_bf16(k, v);
        sts16(d, pack_bf16(q * QSCALE, 0.f)); sts16(d + 128, kv); sts16(d + 256, kv >> 16);
      }
      sts32(sb + INFO, idx);
      bar_sync(2, 128);
    }
    const uint4 fix = lds128(sb + PATCH + 128 + (lane & 4) * 32 + (wq >> 1) * 64 + (lane & 3) * 16);
    warp_signal(BAR(B_PAR));
    PROFX(tid == 0, L ? 23 : 17);
    mbar_wait_b(BAR(B_KVFULL + wq), L);
    if ((idx >> 7) == bi * 2 - 1 - (wq & 1)) {
      if (lane < 8) sts128(sb + ((wq >> 1) ? KVB : KVA) + ((idx >> 6) & 3) * 8192 + (lane >> 2) * 4096 + (idx & 63) * 64 + (((lane ^ (idx >> 1)) & 3) << 4), fix);
      fence_async_smem();
    }
    bar_arrive(4 + wq, 160); bar_arrive(8 + wq, 160);
    FRESH();
    mbar_wait_b(BAR(B_OFREE), L);
    #define blk (bi * 2 + (bid & 1))
    if (tid < 33) st_ll(tid < 32 ? &P.g->row[blk][bc * 32 + tid] : &P.g->best[bc][blk], 0u, 0u, 0u, 0u);
    mbar_wait_b(BAR(B_XRDY), L);
    PROFX(tid == 0, 37 + L * 16);
    FRESH();
    {
      float s1 = 0.f, s2 = 0.f, d = 0.f;
      #pragma unroll 1
      for (int q = 0; q < 8; q += 4) { const float4 v = poll_sum4(&P.g->statP[q][blk * 128 + tid], 2048, tag); s1 += v.x; s2 += v.y; d += v.z; }
      PROFX(tid == 0, 39 + L * 16);
      uint4 a = lds128(sb + INFO2), b, c;
      float m = s1 * (1.f / 1024.f), var = fmaxf(fmaf(-m, m, s2 * (1.f / 1024.f)), 0.f), rs = rsqrtf(var + LN_EPS);
      uint32_t key = UI(fmaf(-m, (FL(a.x) + FL(a.y)) + (FL(a.z) + FL(a.w)), d) * rs);
      key ^= (uint32_t)((int)key >> 31) | 0x80000000u;
      uint32_t win = __ballot_sync(0xffffffffu, key == __reduce_max_sync(0xffffffffu, key));
      if (lane == __ffs(win) - 1) sts128(sb + RED + wq * 16, make_uint4(key, UI(m), UI(rs), (tag << 11) | (uint32_t)(blk * 128 + tid)));
      if (L) sts64f(sb + PAR + tid * 8, 1.f + rs, -m * rs);
      else if ((tid >> 4) == bc) st_ll(&P.g->statF[blk * 128 + tid], UI(m), UI(var), 0u, tag + 1);
      bar_sync(2, 128);
      if (wq == 0) {
        mbar_wait(BAR(B_XRDY + 1), L); mbar_wait(BAR(B_XRDY + 3), L);
        a = best4(sb + RED);
        float2 v = lds64f(sb + (lane >> 4) * 32768 + (a.w & 255) * 128 + (((lane & 15) * 8) ^ ((a.w & 7) << 4)));
        st_ll(&P.g->row[blk][bc * 32 + lane], UI(v.x), UI(v.y), 0u, tag);
        if (lane == 0) st_ll(&P.g->best[bc][blk], a.x, a.y, a.z, a.w);
        __syncwarp();
        if (lane < 2 + 2 * L) mbar_arrive(L ? BAR(B_PAR) : BAR(B_XFREE + lane));
      }
      PROFX(tid == 0, 18 + L * 6);
      FRESH();
      a = poll_ll(&P.g->best[bc][lane & 15], 0xfffff800u, tag << 11);
      win = __ffs(__ballot_sync(0xffffffffu, a.x == __reduce_max_sync(0xffffffffu, a.x))) - 1;
      idx = __shfl_sync(0xffffffffu, a.w, win) & 2047;
      PROFX(tid == 0, 19 + L * 6);
      poll_ll2(&P.g->row[win][tid], &P.g->row[win][tid + 128], 0xffffffffu, tag, c, b);
      c.z = b.x; c.w = b.y;
      a.x = __shfl_sync(0xffffffffu, a.x, win); a.y = __shfl_sync(0xffffffffu, a.y, win); a.z = __shfl_sync(0xffffffffu, a.z, win);
      sts32(sb + INFO2 + 28, idx);
      PROFX(tid == 0, 61 + L);
      b = norm8(c, FL(a.y), FL(a.z));
      if (L) put_bf16(b, sb + HV + tid * 8); else put_f32(b, sb + HV + tid * 16, 2048);
      if ((tid >> 1) == (bid & 63)) {
        sts128(sb + RED + 64 + (tid & 1) * 16, bid < 64 ? make_uint4(c.x, c.y, b.x, b.y) : make_uint4(c.z, c.w, b.z, b.w));
        sts32(sb + RED + 96, a.x);
      }
      bar_sync(2 + L, 128 + L * 256);
      if (L) {
        const int r0 = blk * 128 + (tid >> 4);
        uint32_t src = sb + ((tid >> 3) & 1) * 32768 + (r0 & 255) * 128 + (((tid ^ r0) & 7) << 4);
        uint4* dst = (uint4*)(P.out + (size_t)r0 * 1024 + bc * 128) + (tid & 15);
        #pragma unroll 4
        for (int it = 0; it < 16; it++) { uint4 v = lds128(src + it * 1024); if (idx - r0 != it * 8) dst[it * 1024] = v; }
      }
    }
    #pragma unroll 1
    for (int st = L; st < 2; st++) {
      FRESH();
      float a[8] = {0.f, 0.f, 0.f, 0.f, 0.f, 0.f, 0.f, 0.f};
      if (L == 0 && fid < 112) {
        uint32_t ha = st ? sb + RED + 768 : sb + HV + ((wq & 1) * 64 + (lane >> 2)) * 4;
        uint32_t ph = st ? 0x1cu : 0x171u, bar = st ? BAR(B_STG + 2) : BAR(B_STG);
        uint32_t wa = sb + STG + wq * 4096 + (st ? 32768 + lane * 16 : (lane ^ (lane >> 3)) * 16);
        const uint32_t hx = st ? 256 : 512;
        const bool lead = lane == 0;
        uint4 vc = make_uint4(0u, 0u, 0u, 0u); float hc = 0.f;
        #pragma unroll 1
        do {
          mbar_wait(bar, ph & 1);
          PROFX(lead && threadIdx.x == 256 && st == 0 && (ph > 255 || ph < 4), 40 - 23 + __clz(ph));
          #pragma unroll
          for (int n = 0; n < 8; n++) { const uint4 v = lds128(wa + n * 512); const float h = lds32f(ha + n * 32); fma8(a, vc, hc); vc = v; hc = h; }
          __syncwarp();
          if (lead) mbar_arrive(bar - 8 * (B_STG - B_STGE));
          const bool wrap = bar == BAR(B_STG + 2);
          bar += wrap ? -16 : 8; wa += wrap ? -32768 : 16384; ha += hx;
          ph >>= 1;
        } while (ph != 1);
        fma8(a, vc, hc);
      }
      FRESH();
      if (st == 1) {
        const uint32_t t8 = lds32(sb + INFO + 12) + L;
        if (L == 0 && fid < 112) {
          const bool odd = lane & 1;
          #pragma unroll
          for (int e = 0; e < 4; e++) { float z = __shfl_xor_sync(0xffffffffu, odd ? a[e] : a[4 + e], 1); if (odd) a[e] = z; else a[4 + e] = z; }
          uint4* dst = &P.g->yP[tid & ~1][fid][tid & 1];
          st_ll(dst, UI(a[0]), UI(a[1]), UI(a[2]), (UI(a[3]) & ~255u) | t8);
          st_ll(dst + 224, UI(a[4]), UI(a[5]), UI(a[6]), (UI(a[7]) & ~255u) | t8);
          PROFX(tid == 0, 21);
        }
        if (tid == 0) { uint32_t k = lds32(sb + RED + 96); sts32f(sb + RED + 100, bf_round(__fdividef(1.f, 1.f + __expf(-bf_round(FL(k ^ (~(uint32_t)((int)k >> 31) | 0x80000000u))))))); }
        uint4 v0, v1;
        poll_ll2(&P.g->yP[bid][0][min(tid, 111)], &P.g->yP[bid][0][min(tid, 111) + 112], 255u, t8, v0, v1);
        const float lo = (tid < 112 && !(tid & 1)) ? 1.f : 0.f, hi = (tid < 112 && (tid & 1)) ? 1.f : 0.f;
        const float y0 = FL(v0.x) + FL(v1.x), y1 = FL(v0.y) + FL(v1.y), y2 = FL(v0.z) + FL(v1.z), y3 = FL((v0.w & ~255u) | 128u) + FL((v1.w & ~255u) | 128u);
        a[0] = y0 * lo; a[1] = y1 * lo; a[2] = y2 * lo; a[3] = y3 * lo; a[4] = y0 * hi; a[5] = y1 * hi; a[6] = y2 * hi; a[7] = y3 * hi;
      }
      sts32f(sb + RED + 256 + wq * 128 + ((lane & 3) * 8 + (lane >> 2)) * 4, fold8(a));
      bar_sync(2, 128);
      const uint32_t d = sb + RED + 256 + lane * 4;
      float z0 = lds32f(d) + lds32f(d + 128), z1 = lds32f(d + 256) + lds32f(d + 384);
      if (st == 0) {
        sts32f(sb + RED + 768 + lane * 32 + wq * 4, swiglu(z0, z1));
        bar_sync(2, 128);
        if (fid < 112) { st_ll(&P.g->yP[tid & ~1][fid][tid & 1], 0u, 0u, 0u, 0u); st_ll(&P.g->yP[tid | 1][fid][tid & 1], 0u, 0u, 0u, 0u); }
        else { const uint32_t t0 = clk(); while (clk() - t0 < IDLE_T) __nanosleep(200); }
        if (tid < 80) st_ll(tid < 64 ? &P.g->patch[bid][tid] : &P.g->x2[(tid >> 1) & 7][2 * bid + (tid & 1)], 0u, 0u, 0u, 0u);
        PROFX(tid == 0, 20); continue; }
      z0 += z1;
      z0 += __shfl_xor_sync(0xffffffffu, z0, 8); z0 += __shfl_xor_sync(0xffffffffu, z0, 16);
      uint32_t xw = lds32(sb + RED + 64 + (lane & 4) * 4 + (lane & 2) * 2), hw = lds32(sb + RED + 72 + (lane & 4) * 4 + (lane & 2) * 2);
      z0 = bf_round(((lane & 1) ? bf_hi(hw) : bf_lo(hw)) + bf_round(bf_round(z0) * lds32f(sb + RED + 100))) + ((lane & 1) ? bf_hi(xw) : bf_lo(xw));
      uint32_t v = pack_bf16(z0, __shfl_down_sync(0xffffffffu, z0, 1)), v2 = __shfl_down_sync(0xffffffffu, v, 2);
      if (L) { if (tid == 0 || tid == 4) *(uint2*)(P.out + (size_t)idx * 1024 + bid * 8 + tid) = make_uint2(v, v2); PROFW(tid == 0, 28); }
      else if ((tid & 3) == 0 && tid < 64) st_ll(&P.g->x2[tid >> 3][2 * bid + ((tid >> 2) & 1)], v, v2, 0u, tag + 1);
    }
    if (L == 0) {
      PROFX(tid == 0, 22);
      FRESH();
      uint4 x, y; poll_ll2(&P.g->x2[bi][tid], &P.g->x2[bi][tid + 128], 0xffffffffu, tag + 1, x, y);
      x.z = y.x; x.w = y.y;
      if (wq == (bc & 3)) sts64f(sb + X2SEG + lane * 8, FL(bc < 4 ? x.x : x.z), FL(bc < 4 ? x.y : x.w));
      float s1 = 0.f, s2 = 0.f;
      sum8(x, s1, s2);
      #pragma unroll
      for (int o = 16; o; o >>= 1) { s1 += __shfl_xor_sync(0xffffffffu, s1, o); s2 += __shfl_xor_sync(0xffffffffu, s2, o); }
      sts64f(sb + RED + wq * 8, s1, s2);
      bar_sync(2, 128);
      y = lds128(sb + RED); uint4 y2 = lds128(sb + RED + 16);
      float m = ((FL(y.x) + FL(y.z)) + (FL(y2.x) + FL(y2.z))) * (1.f / 1024.f);
      put_bf16(norm8(x, m, rsqrtf(fmaxf(fmaf(-m, m, ((FL(y.y) + FL(y.w)) + (FL(y2.y) + FL(y2.w))) * (1.f / 1024.f)), 0.f) + LN_EPS)), sb + HV + tid * 8);
      mbar_wait(BAR(B_STG), 1); mbar_wait(BAR(B_STG + 1), 0); mbar_wait(BAR(B_STG + 2), 0);
      bar_sync(2, 128);
      PROFX(tid == 0, 30);
      float d0[4] = {0.f, 0.f, 0.f, 0.f}, d1[4] = {0.f, 0.f, 0.f, 0.f}, d2[4] = {0.f, 0.f, 0.f, 0.f};
      const uint32_t bd = (64 + (HV >> 4) + uni(bid & 3) * 32) | 0x10000u;
      #pragma unroll 1
      for (int ks = 0; ks < 8; ks++) {
        const uint32_t ad = (64 + (STG >> 4) + ks * 128) | (64u << 16);
        wg_fence();
        wgmma_ss_n8<0, 1>(d0, mkd<HI64>(ad), mkd<8>(bd + ks * 4), 1);
        wgmma_ss_n8<0, 1>(d1, mkd<HI64>(ad + 1024), mkd<8>(bd + ks * 4), 1);
        wgmma_ss_n8<0, 1>(d2, mkd<HI64>(ad + 2048), mkd<8>(bd + ks * 4), 1);
        wg_commit();
      }
      wg_wait<0>(); keep(d0); keep(d1); keep(d2);
      FRESH();
      if ((lane & 3) == (wq >> 1)) {
        uint4* dst = &P.g->patch[bid][(wq & 1) * 32 + (lane >> 2) * 2 + (wq >> 1)];
        st_ll(dst, UI(d0[0]), UI(d1[0]), UI(d2[0]), tag + 1); st_ll(dst + 16, UI(d0[2]), UI(d1[2]), UI(d2[2]), tag + 1);
      }
      PROFX(tid == 0, 31);
    }
  }
  if (bid == 0 && tid == 0) P.g->epoch = lds32(sb + INFO2 + 16) + 1;
  #undef blk
  #undef bid
  #undef fid
  #undef bi
  #undef bp
  #undef bc
  #undef FRESH
  #undef lane
  #undef wq
}

__global__ void __cluster_dims__(2, 1, 1) __launch_bounds__(512, 1) fused_kernel(const __grid_constant__ Params P) {
  extern __shared__ __align__(1024) uint8_t smem_raw[];
  const uint32_t sb = smem_u32(smem_raw);
  PROFT(threadIdx.x == 0, 0);
  if (threadIdx.x < 32) { if (elect()) {
    for (int s = 0; s < 3; s++) mbar_init(BAR(B_FULLQ + s), 1);
    asm volatile("fence.mbarrier_init.release.cluster;" ::: "memory");
    #pragma unroll 1
    for (int s = 0; s < 3; s++) {
      mbar_expect_tx(BAR(B_FULLQ + s), 57344);
      tma_2d(sb + qa_off(s), &P.mX, s * 64, (BID >> 4) * 256, BAR(B_FULLQ + s));
      tma_3d(sb + qb_off(s), &P.mWq, (BID & 15) * 64, s * 64, 0, BAR(B_FULLQ + s));
    }
    if ((sb & 0x3FFFFu) != 1024) __trap();
  } } else if (threadIdx.x == 480) {
    asm volatile("prefetch.tensormap [%0];" :: "l"(&P.mWq) : "memory");
  } else if (threadIdx.x >= 32 && !(threadIdx.x & 28) && (threadIdx.x >> 3) + (threadIdx.x & 3) <= B_COUNT + 1) {
    int b = (threadIdx.x >> 3) + (threadIdx.x & 3) - 1;
    if (b == B_COUNT) b = B_ROW;
    const uint32_t cnt = b < B_XFREE ? (b == B_OFREE ? 1 : 2) : (b < B_KVRDY ? 3 : (b < B_KVFULL || b == B_PAR ? 4 : (b == B_PFREE ? 2 : 1)));
    mbar_init(BAR(b), cnt);
    asm volatile("fence.mbarrier_init.release.cluster;" ::: "memory");
  }
  __syncthreads();
  asm volatile("barrier.cluster.arrive.relaxed.aligned;" ::: "memory");
  const int wg = __shfl_sync(0xffffffffu, threadIdx.x >> 7, 0);
  if (wg < 2) { reg_inc<224>(); consumer(P, sb, wg); }
  else if (wg == 2) { reg_dec<40>(); aux(P, sb); }
  else {
    reg_dec<24>();
    asm volatile("barrier.cluster.wait.aligned;" ::: "memory");
    const int w = __shfl_sync(0xffffffffu, (threadIdx.x >> 5) & 3, 0);
    if (w == 0) loader(P, sb);
    else if (w < 3) storer(P, sb, w - 1);
    else if (elect()) stager(P, sb);
  }
}

typedef CUresult (*EncFn)(CUtensorMap*, CUtensorMapDataType, cuuint32_t, void*, const cuuint64_t*, const cuuint64_t*, const cuuint32_t*, const cuuint32_t*,
                          CUtensorMapInterleave, CUtensorMapSwizzle, CUtensorMapL2promotion, CUtensorMapFloatOOBfill);
static void mk_map(EncFn enc, CUtensorMap* m, const void* ptr, int rank, const cuuint64_t* dims, const cuuint64_t* strides, const cuuint32_t* box,
                   CUtensorMapSwizzle sw, CUtensorMapL2promotion pr) {
  cuuint32_t es[5] = {1, 1, 1, 1, 1};
  enc(m, CU_TENSOR_MAP_DATA_TYPE_BFLOAT16, rank, (void*)ptr, dims, strides, box, es, CU_TENSOR_MAP_INTERLEAVE_NONE, sw, pr, CU_TENSOR_MAP_FLOAT_OOB_FILL_NONE);
}
extern "C" void kernel_launch(void* const* d_in, const int* in_sizes, int n_in, void* d_out, int out_size) {
  (void)in_sizes; (void)n_in; (void)out_size;
  void* fn = nullptr; cudaDriverEntryPointQueryResult q;
  cudaGetDriverEntryPoint("cuTensorMapEncodeTiled", &fn, cudaEnableDefault, &q);
  EncFn enc = (EncFn)fn;
  cudaFuncSetAttribute(fused_kernel, cudaFuncAttributeMaxDynamicSharedMemorySize, SMEM_BYTES);
  Params P;
  const CUtensorMapSwizzle S128 = CU_TENSOR_MAP_SWIZZLE_128B, S64 = CU_TENSOR_MAP_SWIZZLE_64B, S0 = CU_TENSOR_MAP_SWIZZLE_NONE;
  const CUtensorMapL2promotion L256 = CU_TENSOR_MAP_L2_PROMOTION_L2_256B, L128 = CU_TENSOR_MAP_L2_PROMOTION_L2_128B;
  { cuuint64_t d[2] = {1024, 2048}, s[1] = {2048}; cuuint32_t b[2] = {64, 256}, bh[2] = {64, 128};
    mk_map(enc, &P.mX, d_in[0], 2, d, s, b, S128, L256); mk_map(enc, &P.mXh, d_in[0], 2, d, s, bh, S128, L256); }
  { cuuint64_t d[3] = {1024, 1024, 3}, s[2] = {6144, 2048}; cuuint32_t b[3] = {64, 64, 3}; mk_map(enc, &P.mWq, d_in[1], 3, d, s, b, S128, L256); }
  { cuuint64_t d[5] = {64, 32, 2, 16, 16}, s[4] = {2048, 65536, 131072, 128}; cuuint32_t b[5] = {64, 32, 1, 2, 2}; mk_map(enc, &P.mWo, d_in[2], 5, d, s, b, S128, L256); }
  { cuuint64_t d[2] = {3584, 1024}, s[1] = {7168}; cuuint32_t b[2] = {32, 128};
    mk_map(enc, &P.mWg, d_in[5], 2, d, s, b, S64, L128); mk_map(enc, &P.mWu, d_in[6], 2, d, s, b, S64, L128); }
  { cuuint64_t d[2] = {3072, 1024}, s[1] = {6144}; cuuint32_t b[2] = {32, 256}; mk_map(enc, &P.mWp, d_in[1], 2, d, s, b, S64, L128); }
  { cuuint64_t d[3] = {256, 3584, 4}, s[2] = {2048, 512}; cuuint32_t b[3] = {256, 8, 4}; mk_map(enc, &P.mWd, d_in[7], 3, d, s, b, S0, L128); }
  P.x0 = (const bf16*)d_in[0]; P.wqkv = (const bf16*)d_in[1]; P.wo = (const bf16*)d_in[2]; P.wr = (const bf16*)d_in[4]; P.wg = (const bf16*)d_in[5]; P.wu = (const bf16*)d_in[6]; P.wd = (const bf16*)d_in[7];
  P.out = (bf16*)d_out;
  cudaGetSymbolAddress((void**)&P.g, g_scr);
  for (int b = 0; b < 128; b++) {
    int j = b >> 1, quad = j < 4 ? 0 : (j < 36 ? 1 + (j - 4) % 8 : 9 + (j - 36) % 7), pos = j < 4 ? j : (j < 36 ? (j - 4) / 8 : (j - 36) / 7);
    int bid = ((quad >> 2) * 2 + (pos >> 1)) * 16 + ((quad & 3) * 2 + (pos & 1)) * 2 + (b & 1);
    int e = pos * 2 + (b & 1), fid = e < 7 ? quad * 7 + e : 112 + quad;
    P.map[b] = bid | fid << 8;
  }
  fused_kernel<<<128, 512, SMEM_BYTES>>>(P);
}
```

```cpp
#include <cuda_runtime.h>
#include <cuda_bf16.h>
#include <cuda.h>
#include <stdint.h>
#include <stddef.h>
typedef __nv_bfloat16 bf16;

template<int TB, int TA = 0> __device__ __forceinline__ void wgmma_ss_n192(float (&d)[96], uint64_t da, uint64_t db, int scale_d) {
  asm volatile("{\n.reg .pred p;\nsetp.ne.b32 p, %98, 0;\n"
    "wgmma.mma_async.sync.aligned.m64n192k16.f32.bf16.bf16 {%0, %1, %2, %3, %4, %5, %6, %7, %8, %9, %10, %11, %12, %13, %14, %15, %16, %17, %18, %19, %20, %21, %22, %23, %24, %25, %26, %27, %28, %29, %30, %31, %32, %33, %34, %35, %36, %37, %38, %39, %40, %41, %42, %43, %44, %45, %46, %47, %48, %49, %50, %51, %52, %53, %54, %55, %56, %57, %58, %59, %60, %61, %62, %63, %64, %65, %66, %67, %68, %69, %70, %71, %72, %73, %74, %75, %76, %77, %78, %79, %80, %81, %82, %83, %84, %85, %86, %87, %88, %89, %90, %91, %92, %93, %94, %95}, %96, %97, p, 1, 1, %100, %99;\n}\n"
    : "+f"(d[0]), "+f"(d[1]), "+f"(d[2]), "+f"(d[3]), "+f"(d[4]), "+f"(d[5]), "+f"(d[6]), "+f"(d[7]), "+f"(d[8]), "+f"(d[9]), "+f"(d[10]), "+f"(d[11]), "+f"(d[12]), "+f"(d[13]), "+f"(d[14]), "+f"(d[15]), "+f"(d[16]), "+f"(d[17]), "+f"(d[18]), "+f"(d[19]), "+f"(d[20]), "+f"(d[21]), "+f"(d[22]), "+f"(d[23]), "+f"(d[24]), "+f"(d[25]), "+f"(d[26]), "+f"(d[27]), "+f"(d[28]), "+f"(d[29]), "+f"(d[30]), "+f"(d[31]), "+f"(d[32]), "+f"(d[33]), "+f"(d[34]), "+f"(d[35]), "+f"(d[36]), "+f"(d[37]), "+f"(d[38]), "+f"(d[39]), "+f"(d[40]), "+f"(d[41]), "+f"(d[42]), "+f"(d[43]), "+f"(d[44]), "+f"(d[45]), "+f"(d[46]), "+f"(d[47]), "+f"(d[48]), "+f"(d[49]), "+f"(d[50]), "+f"(d[51]), "+f"(d[52]), "+f"(d[53]), "+f"(d[54]), "+f"(d[55]), "+f"(d[56]), "+f"(d[57]), "+f"(d[58]), "+f"(d[59]), "+f"(d[60]), "+f"(d[61]), "+f"(d[62]), "+f"(d[63]), "+f"(d[64]), "+f"(d[65]), "+f"(d[66]), "+f"(d[67]), "+f"(d[68]), "+f"(d[69]), "+f"(d[70]), "+f"(d[71]), "+f"(d[72]), "+f"(d[73]), "+f"(d[74]), "+f"(d[75]), "+f"(d[76]), "+f"(d[77]), "+f"(d[78]), "+f"(d[79]), "+f"(d[80]), "+f"(d[81]), "+f"(d[82]), "+f"(d[83]), "+f"(d[84]), "+f"(d[85]), "+f"(d[86]), "+f"(d[87]), "+f"(d[88]), "+f"(d[89]), "+f"(d[90]), "+f"(d[91]), "+f"(d[92]), "+f"(d[93]), "+f"(d[94]), "+f"(d[95])
    : "l"(da), "l"(db), "r"(scale_d), "n"(TB), "n"(TA));
}

template<int TB> __device__ __forceinline__ void wgmma_rs_n192(float (&d)[96], uint32_t a0, uint32_t a1, uint32_t a2, uint32_t a3, uint64_t db, int scale_d) {
  asm volatile("{\n.reg .pred p;\nsetp.ne.b32 p, %101, 0;\n"
    "wgmma.mma_async.sync.aligned.m64n192k16.f32.bf16.bf16 {%0, %1, %2, %3, %4, %5, %6, %7, %8, %9, %10, %11, %12, %13, %14, %15, %16, %17, %18, %19, %20, %21, %22, %23, %24, %25, %26, %27, %28, %29, %30, %31, %32, %33, %34, %35, %36, %37, %38, %39, %40, %41, %42, %43, %44, %45, %46, %47, %48, %49, %50, %51, %52, %53, %54, %55, %56, %57, %58, %59, %60, %61, %62, %63, %64, %65, %66, %67, %68, %69, %70, %71, %72, %73, %74, %75, %76, %77, %78, %79, %80, %81, %82, %83, %84, %85, %86, %87, %88, %89, %90, %91, %92, %93, %94, %95}, {%96, %97, %98, %99}, %100, p, 1, 1, %102;\n}\n"
    : "+f"(d[0]), "+f"(d[1]), "+f"(d[2]), "+f"(d[3]), "+f"(d[4]), "+f"(d[5]), "+f"(d[6]), "+f"(d[7]), "+f"(d[8]), "+f"(d[9]), "+f"(d[10]), "+f"(d[11]), "+f"(d[12]), "+f"(d[13]), "+f"(d[14]), "+f"(d[15]), "+f"(d[16]), "+f"(d[17]), "+f"(d[18]), "+f"(d[19]), "+f"(d[20]), "+f"(d[21]), "+f"(d[22]), "+f"(d[23]), "+f"(d[24]), "+f"(d[25]), "+f"(d[26]), "+f"(d[27]), "+f"(d[28]), "+f"(d[29]), "+f"(d[30]), "+f"(d[31]), "+f"(d[32]), "+f"(d[33]), "+f"(d[34]), "+f"(d[35]), "+f"(d[36]), "+f"(d[37]), "+f"(d[38]), "+f"(d[39]), "+f"(d[40]), "+f"(d[41]), "+f"(d[42]), "+f"(d[43]), "+f"(d[44]), "+f"(d[45]), "+f"(d[46]), "+f"(d[47]), "+f"(d[48]), "+f"(d[49]), "+f"(d[50]), "+f"(d[51]), "+f"(d[52]), "+f"(d[53]), "+f"(d[54]), "+f"(d[55]), "+f"(d[56]), "+f"(d[57]), "+f"(d[58]), "+f"(d[59]), "+f"(d[60]), "+f"(d[61]), "+f"(d[62]), "+f"(d[63]), "+f"(d[64]), "+f"(d[65]), "+f"(d[66]), "+f"(d[67]), "+f"(d[68]), "+f"(d[69]), "+f"(d[70]), "+f"(d[71]), "+f"(d[72]), "+f"(d[73]), "+f"(d[74]), "+f"(d[75]), "+f"(d[76]), "+f"(d[77]), "+f"(d[78]), "+f"(d[79]), "+f"(d[80]), "+f"(d[81]), "+f"(d[82]), "+f"(d[83]), "+f"(d[84]), "+f"(d[85]), "+f"(d[86]), "+f"(d[87]), "+f"(d[88]), "+f"(d[89]), "+f"(d[90]), "+f"(d[91]), "+f"(d[92]), "+f"(d[93]), "+f"(d[94]), "+f"(d[95])
    : "r"(a0), "r"(a1), "r"(a2), "r"(a3), "l"(db), "r"(scale_d), "n"(TB));
}

template<int TB, int TA = 0> __device__ __forceinline__ void wgmma_ss_n128(float (&d)[64], uint64_t da, uint64_t db, int scale_d) {
  asm volatile("{\n.reg .pred p;\nsetp.ne.b32 p, %66, 0;\n"
    "wgmma.mma_async.sync.aligned.m64n128k16.f32.bf16.bf16 {%0, %1, %2, %3, %4, %5, %6, %7, %8, %9, %10, %11, %12, %13, %14, %15, %16, %17, %18, %19, %20, %21, %22, %23, %24, %25, %26, %27, %28, %29, %30, %31, %32, %33, %34, %35, %36, %37, %38, %39, %40, %41, %42, %43, %44, %45, %46, %47, %48, %49, %50, %51, %52, %53, %54, %55, %56, %57, %58, %59, %60, %61, %62, %63}, %64, %65, p, 1, 1, %68, %67;\n}\n"
    : "+f"(d[0]), "+f"(d[1]), "+f"(d[2]), "+f"(d[3]), "+f"(d[4]), "+f"(d[5]), "+f"(d[6]), "+f"(d[7]), "+f"(d[8]), "+f"(d[9]), "+f"(d[10]), "+f"(d[11]), "+f"(d[12]), "+f"(d[13]), "+f"(d[14]), "+f"(d[15]), "+f"(d[16]), "+f"(d[17]), "+f"(d[18]), "+f"(d[19]), "+f"(d[20]), "+f"(d[21]), "+f"(d[22]), "+f"(d[23]), "+f"(d[24]), "+f"(d[25]), "+f"(d[26]), "+f"(d[27]), "+f"(d[28]), "+f"(d[29]), "+f"(d[30]), "+f"(d[31]), "+f"(d[32]), "+f"(d[33]), "+f"(d[34]), "+f"(d[35]), "+f"(d[36]), "+f"(d[37]), "+f"(d[38]), "+f"(d[39]), "+f"(d[40]), "+f"(d[41]), "+f"(d[42]), "+f"(d[43]), "+f"(d[44]), "+f"(d[45]), "+f"(d[46]), "+f"(d[47]), "+f"(d[48]), "+f"(d[49]), "+f"(d[50]), "+f"(d[51]), "+f"(d[52]), "+f"(d[53]), "+f"(d[54]), "+f"(d[55]), "+f"(d[56]), "+f"(d[57]), "+f"(d[58]), "+f"(d[59]), "+f"(d[60]), "+f"(d[61]), "+f"(d[62]), "+f"(d[63])
    : "l"(da), "l"(db), "r"(scale_d), "n"(TB), "n"(TA));
}

template<int TB, int TA = 0> __device__ __forceinline__ void wgmma_ss_n64(float (&d)[32], uint64_t da, uint64_t db, int scale_d) {
  asm volatile("{\n.reg .pred p;\nsetp.ne.b32 p, %34, 0;\n"
    "wgmma.mma_async.sync.aligned.m64n64k16.f32.bf16.bf16 {%0, %1, %2, %3, %4, %5, %6, %7, %8, %9, %10, %11, %12, %13, %14, %15, %16, %17, %18, %19, %20, %21, %22, %23, %24, %25, %26, %27, %28, %29, %30, %31}, %32, %33, p, 1, 1, %36, %35;\n}\n"
    : "+f"(d[0]), "+f"(d[1]), "+f"(d[2]), "+f"(d[3]), "+f"(d[4]), "+f"(d[5]), "+f"(d[6]), "+f"(d[7]), "+f"(d[8]), "+f"(d[9]), "+f"(d[10]), "+f"(d[11]), "+f"(d[12]), "+f"(d[13]), "+f"(d[14]), "+f"(d[15]), "+f"(d[16]), "+f"(d[17]), "+f"(d[18]), "+f"(d[19]), "+f"(d[20]), "+f"(d[21]), "+f"(d[22]), "+f"(d[23]), "+f"(d[24]), "+f"(d[25]), "+f"(d[26]), "+f"(d[27]), "+f"(d[28]), "+f"(d[29]), "+f"(d[30]), "+f"(d[31])
    : "l"(da), "l"(db), "r"(scale_d), "n"(TB), "n"(TA));
}

template<int TB, int TA = 0> __device__ __forceinline__ void wgmma_ss_n8(float (&d)[4], uint64_t da, uint64_t db, int scale_d) {
  asm volatile("{\n.reg .pred p;\nsetp.ne.b32 p, %6, 0;\n"
    "wgmma.mma_async.sync.aligned.m64n8k16.f32.bf16.bf16 {%0, %1, %2, %3}, %4, %5, p, 1, 1, %8, %7;\n}\n"
    : "+f"(d[0]), "+f"(d[1]), "+f"(d[2]), "+f"(d[3])
    : "l"(da), "l"(db), "r"(scale_d), "n"(TB), "n"(TA));
}

template<int TB> __device__ __forceinline__ void wgmma_rs_n40(float (&d)[20], uint32_t a0, uint32_t a1, uint32_t a2, uint32_t a3, uint64_t db, int scale_d) {
  asm volatile("{\n.reg .pred p;\nsetp.ne.b32 p, %25, 0;\n"
    "wgmma.mma_async.sync.aligned.m64n40k16.f32.bf16.bf16 {%0, %1, %2, %3, %4, %5, %6, %7, %8, %9, %10, %11, %12, %13, %14, %15, %16, %17, %18, %19}, {%20, %21, %22, %23}, %24, p, 1, 1, %26;\n}\n"
    : "+f"(d[0]), "+f"(d[1]), "+f"(d[2]), "+f"(d[3]), "+f"(d[4]), "+f"(d[5]), "+f"(d[6]), "+f"(d[7]), "+f"(d[8]), "+f"(d[9]), "+f"(d[10]), "+f"(d[11]), "+f"(d[12]), "+f"(d[13]), "+f"(d[14]), "+f"(d[15]), "+f"(d[16]), "+f"(d[17]), "+f"(d[18]), "+f"(d[19])
    : "r"(a0), "r"(a1), "r"(a2), "r"(a3), "l"(db), "r"(scale_d), "n"(TB));
}

#define DEVI __device__ __forceinline__
DEVI uint32_t smem_u32(const void* p) { return (uint32_t)__cvta_generic_to_shared(p); }
DEVI void mbar_init(uint32_t bar, uint32_t cnt) { asm volatile("mbarrier.init.shared::cta.b64 [%0], %1;" :: "r"(bar), "r"(cnt)); }
DEVI void mbar_expect_tx(uint32_t bar, uint32_t bytes) { asm volatile("mbarrier.arrive.expect_tx.shared::cta.b64 _, [%0], %1;" :: "r"(bar), "r"(bytes) : "memory"); }
DEVI void mbar_arrive(uint32_t bar) { asm volatile("mbarrier.arrive.shared::cta.b64 _, [%0];" :: "r"(bar) : "memory"); }
DEVI void mbar_arrive_peer(uint32_t bar) {
  asm volatile("{\n.reg .b32 ra;\nmapa.shared::cluster.u32 ra, %0, %1;\nmbarrier.arrive.shared::cluster.b64 _, [ra];\n}" :: "r"(bar), "r"((blockIdx.x & 1) ^ 1) : "memory");
}
DEVI void bulk_s2peer(uint32_t a, uint32_t bytes, uint32_t bar) {
  asm volatile("{\n.reg .b32 ra, rb;\nmapa.shared::cluster.u32 ra, %0, %3;\nmapa.shared::cluster.u32 rb, %2, %3;\n"
               "cp.async.bulk.shared::cluster.shared::cta.mbarrier::complete_tx::bytes [ra], [%0], %1, [rb];\n}"
               :: "r"(a), "r"(bytes), "r"(bar), "r"((blockIdx.x & 1) ^ 1) : "memory");
}
DEVI void mbar_wait(uint32_t bar, uint32_t parity) {
  asm volatile("{\n.reg .pred p;\nLW:\nmbarrier.try_wait.parity.shared::cta.b64 p, [%0], %1;\n@!p bra LW;\n}" :: "r"(bar), "r"(parity) : "memory");
}
DEVI uint32_t mbar_test(uint32_t bar, uint32_t parity) {
  uint32_t r; asm volatile("{\n.reg .pred p;\nmbarrier.test_wait.parity.shared::cta.b64 p, [%1], %2;\nselp.u32 %0, 1, 0, p;\n}" : "=r"(r) : "r"(bar), "r"(parity) : "memory"); return r;
}
DEVI void mbar_wait_b(uint32_t bar, uint32_t parity) {
  asm volatile("{\n.reg .pred p;\n.reg .u32 it;\nmov.u32 it, 0;\nLW:\nmbarrier.try_wait.parity.shared::cta.b64 p, [%0], %1;\n@p bra LD;\n"
               "add.u32 it, it, 1;\nsetp.lt.u32 p, it, 0x1000000;\n@p bra LW;\ntrap;\nLD:\n}" :: "r"(bar), "r"(parity) : "memory");
}
DEVI void tma_2d(uint32_t dst, const CUtensorMap* m, int c0, int c1, uint32_t bar) {
  asm volatile("cp.async.bulk.tensor.2d.shared::cluster.global.mbarrier::complete_tx::bytes [%0], [%1, {%3, %4}], [%2];"
    :: "r"(dst), "l"(m), "r"(bar), "r"(c0), "r"(c1) : "memory");
}
DEVI void tma_3d(uint32_t dst, const CUtensorMap* m, int c0, int c1, int c2, uint32_t bar) {
  asm volatile("cp.async.bulk.tensor.3d.shared::cluster.global.mbarrier::complete_tx::bytes [%0], [%1, {%3, %4, %5}], [%2];"
    :: "r"(dst), "l"(m), "r"(bar), "r"(c0), "r"(c1), "r"(c2) : "memory");
}
#define POL_EF POL_FIRST
constexpr uint64_t POL_FIRST = 0x12F0000000000000ull, POL_NORMAL = 0x1000000000000000ull;
DEVI void tma_2d_h(uint32_t dst, const CUtensorMap* m, int c0, int c1, uint32_t bar, uint64_t pol) {
  asm volatile("cp.async.bulk.tensor.2d.shared::cluster.global.mbarrier::complete_tx::bytes.L2::cache_hint [%0], [%1, {%3, %4}], [%2], %5;"
    :: "r"(dst), "l"(m), "r"(bar), "r"(c0), "r"(c1), "l"(pol) : "memory");
}
DEVI void tma_3d_h(uint32_t dst, const CUtensorMap* m, int c0, int c1, int c2, uint32_t bar, uint64_t pol) {
  asm volatile("cp.async.bulk.tensor.3d.shared::cluster.global.mbarrier::complete_tx::bytes.L2::cache_hint [%0], [%1, {%3, %4, %5}], [%2], %6;"
    :: "r"(dst), "l"(m), "r"(bar), "r"(c0), "r"(c1), "r"(c2), "l"(pol) : "memory");
}
DEVI void bulk_g2s_h(uint32_t s, const void* g, uint32_t bytes, uint32_t bar, uint64_t pol = POL_EF) {
  asm volatile("cp.async.bulk.shared::cluster.global.mbarrier::complete_tx::bytes.L2::cache_hint [%0], [%1], %2, [%3], %4;"
    :: "r"(s), "l"(g), "r"(bytes), "r"(bar), "l"(pol) : "memory");
}
DEVI void tma_5d(uint32_t dst, const CUtensorMap* m, int c0, int c1, int c2, int c3, int c4, uint32_t bar, uint64_t pol) {
  asm volatile("cp.async.bulk.tensor.5d.shared::cluster.global.mbarrier::complete_tx::bytes.L2::cache_hint [%0], [%1, {%3, %4, %5, %6, %7}], [%2], %8;"
    :: "r"(dst), "l"(m), "r"(bar), "r"(c0), "r"(c1), "r"(c2), "r"(c3), "r"(c4), "l"(pol) : "memory");
}
DEVI void tma_prefetch_2d(const CUtensorMap* m, int c0, int c1) {
  asm volatile("cp.async.bulk.prefetch.tensor.2d.L2.global.tile [%0, {%1, %2}];" :: "l"(m), "r"(c0), "r"(c1) : "memory");
}
DEVI void tma_prefetch_3d(const CUtensorMap* m, int c0, int c1, int c2) {
  asm volatile("cp.async.bulk.prefetch.tensor.3d.L2.global.tile [%0, {%1, %2, %3}];" :: "l"(m), "r"(c0), "r"(c1), "r"(c2) : "memory");
}
DEVI void bulk_prefetch(const void* g, uint32_t bytes) { asm volatile("cp.async.bulk.prefetch.L2.global [%0], %1;" :: "l"(g), "r"(bytes) : "memory"); }
DEVI void bulk_g2s(uint32_t s, const void* g, uint32_t bytes, uint32_t bar) {
  asm volatile("cp.async.bulk.shared::cluster.global.mbarrier::complete_tx::bytes [%0], [%1], %2, [%3];" :: "r"(s), "l"(g), "r"(bytes), "r"(bar) : "memory");
}
DEVI void bulk_s2g(void* g, uint32_t s, uint32_t bytes, uint64_t pol = POL_NORMAL) {
  asm volatile("cp.async.bulk.global.shared::cta.bulk_group.L2::cache_hint [%0], [%1], %2, %3;\ncp.async.bulk.commit_group;" :: "l"(g), "r"(s), "r"(bytes), "l"(pol) : "memory");
}
template<int N> DEVI void bulk_wait() { asm volatile("cp.async.bulk.wait_group %0;" :: "n"(N) : "memory"); }
DEVI void fence_async_smem() { asm volatile("fence.proxy.async.shared::cta;" ::: "memory"); }
DEVI void fence_async_glob() { asm volatile("fence.proxy.async.global;" ::: "memory"); }
DEVI unsigned ld_rlx(const unsigned* p) { unsigned v; asm volatile("ld.relaxed.gpu.global.u32 %0, [%1];" : "=r"(v) : "l"(p) : "memory"); return v; }
DEVI void st_rlx(unsigned* p, unsigned v) { asm volatile("st.relaxed.gpu.global.u32 [%0], %1;" :: "l"(p), "r"(v) : "memory"); }
DEVI uint2 ldg_stream(const uint2* p) { uint2 v; asm volatile("ld.global.nc.L1::no_allocate.v2.u32 {%0, %1}, [%2];" : "=r"(v.x), "=r"(v.y) : "l"(p)); return v; }
DEVI void fence_rel() { asm volatile("fence.release.gpu;" ::: "memory"); }
DEVI uint4 ld_ll(const uint4* p) {
  uint4 v;
  asm volatile("{\n.reg .b128 t;\n.reg .b64 a, b;\nld.relaxed.gpu.global.b128 t, [%4];\nmov.b128 {a, b}, t;\nmov.b64 {%0, %1}, a;\nmov.b64 {%2, %3}, b;\n}"
               : "=r"(v.x), "=r"(v.y), "=r"(v.z), "=r"(v.w) : "l"(p) : "memory");
  return v;
}
DEVI void st_ll(uint4* p, uint32_t x, uint32_t y, uint32_t z, uint32_t w) {
  asm volatile("{\n.reg .b128 t;\n.reg .b64 a, b;\nmov.b64 a, {%1, %2};\nmov.b64 b, {%3, %4};\nmov.b128 t, {a, b};\nst.relaxed.gpu.global.b128 [%0], t;\n}"
               :: "l"(p), "r"(x), "r"(y), "r"(z), "r"(w) : "memory");
}
#define SPIN_MAX 0x1000000
DEVI uint4 poll_ll(const uint4* p, uint32_t mask, uint32_t tag) {
  uint4 v; int it = 0;
  do { v = ld_ll(p); if (++it > SPIN_MAX) __trap(); } while (!__all_sync(0xffffffffu, (v.w & mask) == tag));
  return v;
}
DEVI void poll_ll2(const uint4* p, const uint4* q, uint32_t mask, uint32_t tag, uint4& a, uint4& b) {
  int it = 0;
  do { a = ld_ll(p); b = ld_ll(q); if (++it > SPIN_MAX) __trap(); } while (!__all_sync(0xffffffffu, (a.w & mask) == tag && (b.w & mask) == tag));
}
DEVI float4 poll_sum4(const uint4* src, int stride, uint32_t tag) {
  uint4 v0, v1, v2, v3; int it = 0;
  do { v0 = ld_ll(src); v1 = ld_ll(src + stride); v2 = ld_ll(src + 2 * stride); v3 = ld_ll(src + 3 * stride); if (++it > SPIN_MAX) __trap(); }
  while (!__all_sync(0xffffffffu, v0.w == tag && v1.w == tag && v2.w == tag && v3.w == tag));
  #define S4(f) ((__uint_as_float(v0.f) + __uint_as_float(v1.f)) + (__uint_as_float(v2.f) + __uint_as_float(v3.f)))
  return make_float4(S4(x), S4(y), S4(z), 0.f);
  #undef S4
}
DEVI void bar_sync(int id, int n) { asm volatile("bar.sync %0, %1;" :: "r"(id), "r"(n) : "memory"); }
DEVI void bar_arrive(int id, int n) { asm volatile("bar.arrive %0, %1;" :: "r"(id), "r"(n) : "memory"); }
DEVI void wg_fence() { asm volatile("wgmma.fence.sync.aligned;" ::: "memory"); }
DEVI void wg_commit() { asm volatile("wgmma.commit_group.sync.aligned;" ::: "memory"); }
template<int N> DEVI void wg_wait() { asm volatile("wgmma.wait_group.sync.aligned %0;" :: "n"(N) : "memory"); }
template<int N> DEVI void reg_inc() { asm volatile("setmaxnreg.inc.sync.aligned.u32 %0;" :: "n"(N)); }
template<int N> DEVI void reg_dec() { asm volatile("setmaxnreg.dec.sync.aligned.u32 %0;" :: "n"(N)); }
DEVI float ex2f(float x) { float y; asm("ex2.approx.ftz.f32 %0, %1;" : "=f"(y) : "f"(x)); return y; }
DEVI uint32_t pack_bf16(float lo, float hi) { uint32_t r; asm("cvt.rn.bf16x2.f32 %0, %1, %2;" : "=r"(r) : "f"(hi), "f"(lo)); return r; }
DEVI float bf_lo(uint32_t v) { return __uint_as_float(v << 16); }
DEVI float bf_hi(uint32_t v) { return __uint_as_float(v & 0xffff0000u); }
DEVI float bf_round(float x) { return bf_lo(pack_bf16(x, 0.f)); }
DEVI void stsm_x4(uint32_t addr, uint32_t a, uint32_t b, uint32_t c, uint32_t d) {
  asm volatile("stmatrix.sync.aligned.m8n8.x4.shared.b16 [%0], {%1,%2,%3,%4};" :: "r"(addr), "r"(a), "r"(b), "r"(c), "r"(d) : "memory");
}
DEVI void ldsm_x4(uint32_t addr, uint32_t& a, uint32_t& b, uint32_t& c, uint32_t& d) {
  asm volatile("ldmatrix.sync.aligned.m8n8.x4.shared.b16 {%0,%1,%2,%3}, [%4];" : "=r"(a), "=r"(b), "=r"(c), "=r"(d) : "r"(addr) : "memory");
}
DEVI uint4 lds128(uint32_t a) { uint4 v; asm volatile("ld.shared.v4.u32 {%0,%1,%2,%3}, [%4];" : "=r"(v.x), "=r"(v.y), "=r"(v.z), "=r"(v.w) : "r"(a) : "memory"); return v; }
DEVI void sts128(uint32_t a, uint4 v) { asm volatile("st.shared.v4.u32 [%0], {%1,%2,%3,%4};" :: "r"(a), "r"(v.x), "r"(v.y), "r"(v.z), "r"(v.w) : "memory"); }
DEVI float2 lds64f(uint32_t a) { float2 v; asm volatile("ld.shared.v2.f32 {%0,%1}, [%2];" : "=f"(v.x), "=f"(v.y) : "r"(a) : "memory"); return v; }
DEVI void sts64f(uint32_t a, float x, float y) { asm volatile("st.shared.v2.f32 [%0], {%1,%2};" :: "r"(a), "f"(x), "f"(y) : "memory"); }
DEVI uint32_t lds32(uint32_t a) { uint32_t v; asm volatile("ld.shared.u32 %0, [%1];" : "=r"(v) : "r"(a) : "memory"); return v; }
DEVI float lds32f(uint32_t a) { return __uint_as_float(lds32(a)); }
DEVI void sts32(uint32_t a, uint32_t v) { asm volatile("st.shared.u32 [%0], %1;" :: "r"(a), "r"(v) : "memory"); }
DEVI void sts32f(uint32_t a, float v) { sts32(a, __float_as_uint(v)); }
DEVI void sts16(uint32_t a, uint32_t v) { asm volatile("st.shared.u16 [%0], %1;" :: "r"(a), "h"((unsigned short)v) : "memory"); }
template<int N> DEVI void keep(float (&d)[N]) {
  #pragma unroll
  for (int i = 0; i < N; i++) asm volatile("" : "+f"(d[i]) :: "memory");
}
template<int N> DEVI void keep(uint32_t (&d)[N]) {
  #pragma unroll
  for (int i = 0; i < N; i++) asm volatile("" : "+r"(d[i]) :: "memory");
}
template<uint32_t HI> DEVI uint64_t mkd(uint32_t lo) { uint64_t r; asm("mov.b64 %0, {%1, %2};" : "=l"(r) : "r"(lo), "n"(HI)); return r; }
constexpr uint32_t HI128 = (1u << 30) | (1024 >> 4), HI64 = (2u << 30) | (512 >> 4);
#define VOFF(x) ((uint32_t)(x) * (uint32_t)(1 - 65536))
DEVI bool elect() { uint32_t p; asm volatile("{\n.reg .pred q;\nelect.sync _|q, 0xffffffff;\nselp.u32 %0, 1, 0, q;\n}" : "=r"(p)); return p; }
DEVI void warp_signal(uint32_t bar) { __syncwarp(); if (elect()) mbar_arrive(bar); }

struct Scratch {
  uint4 statP[8][2048];
  uint4 statF[2048];
  uint4 csP[16][8][96];
  uint4 best[8][16];
  uint4 row[16][256];
  uint4 yP[128][112][2];
  uint4 x2[8][256];
  uint4 patch[128][64];
  unsigned flagKV[128][32];
  unsigned flagO[8][32];
  unsigned flagX[8][32];
  unsigned epoch, pad[255];
  uint4 kv[128][4][1024];
  uint4 o[8][2][8][2][1024];
  uint4 x[8][16][2048];
  uint4 zero[1024];
};
static_assert(offsetof(Scratch, kv) % 1024 == 0, "");
__device__ __align__(1024) Scratch g_scr;
#define PROFT(cond, slot)
#define PROFW(cond, slot)
#define PROFD(cond, slot)
#define PROFX(cond, slot)
#define PROFY(cond, slot)

constexpr uint32_t SB0 = 65536, HOLE = 90112, SA2 = 98304, SB1 = 131072, SB2 = 155648, STG = 180224;
constexpr uint32_t KVA = 0, KVB = 98304, QO = 65536;
constexpr uint32_t MISC = 229376, CS = MISC, ONES = MISC + 768, BARS = MISC + 1792, INFO = MISC + 2208, WR = MISC + 2224, X2SEG = MISC + 2736, INFO2 = MISC + 2992, DUMP = MISC + 3040;
constexpr uint32_t PAR = HOLE, HV = HOLE + 2048, RED = HOLE + 6144, PATCH = 196608;
constexpr uint32_t SMEM_BYTES = 232448;
enum { B_FULLQ = 0, B_EMPTYQ = 3, B_FULLW = 6, B_EMPTYW = 12, B_HAFREE = 18, B_OFREE = 20,
       B_XFREE = 21,
       B_KVRDY = 23, B_ORDY = 27, B_XRDY = 35, B_STGE = 39,
       B_KVFULL = 42, B_RES = 46, B_PAR = 47, B_STG = 48, B_PFREE = 51, B_COUNT = 52,
       B_ROW = 154 };
#define BAR(x) (sb + BARS + 8 * (x))
DEVI uint32_t qa_off(int s) { return s == 2 ? SA2 : (uint32_t)s * 32768u; }
DEVI uint32_t qb_off(int s) { return s == 0 ? SB0 : (s == 1 ? SB1 : SB2); }
DEVI int kb_order(int bc, int n) {
  const int e = n < 9 ? n - 2 : n - 9;
  return n < 2 ? 2 * bc + n : 2 * (((e < 4 ? e + 4 : e - 4 + (e - 4 >= (bc & 3))) + (bc & 4)) & 7) + (n >= 9);
}
DEVI int wo_order(int bc, int n) { return (n & 8) | ((n + (bc & 6)) & 7); }
DEVI uint32_t w_off(int s) { return (uint32_t)((0x143065 >> (4 * s)) & 7) * 32768u; }
DEVI uint32_t w_par(int n, int s, int L) { return (n >= 6 && n < 12) ^ (s == 5) ^ (s != 2 && L); }
DEVI uint32_t w_aoff(int n, int s) { return n == 3 ? QO : w_off(s); }
DEVI int w_next(int n, int s) { return s == 5 ? 0 : (n == 13 ? 3 : s + 1); }

struct Params {
  CUtensorMap mX, mXh, mWq, mWo, mWg, mWu, mWp, mWd;
  const bf16 *x0, *wqkv, *wo, *wr, *wg, *wu, *wd;
  bf16* out;
  Scratch* g;
  unsigned map[128];
};
#define BID ((int)(P.map[blockIdx.x] & 255))
#define FID ((int)(P.map[blockIdx.x] >> 8))
DEVI uint32_t uni(uint32_t v) { return __shfl_sync(0xffffffffu, v, 0); }
#define PQ_N 8
#define PQ_T 700
#define PF0_N 10
#define PF0_T 1600
#define PF1_E 24
#define PF1_T 1100
#define POL_Q1 POL_NORMAL
#define POL_X POL_NORMAL
#define PFA0_BAR 3
#define PFA1_BAR 0
#define PFA0_M 0
#define PFA1_M 0
#define PFA0_T 900
#define PFA1_T 700
#define PF1_S PF0_N
#define PF1_D 0
#define POL_G POL_NORMAL
#define POL_U POL_FIRST
#define POL_D POL_FIRST
#define JQ_N 6
#define WDSRC (P.wd + (size_t)min(fid, 111) * 32768)
#define WDSRC2 (P.wd + FID * 32768)
#define WD_N 4
#define THR_N 5
#define KV_D 1800
#define XD_D 300
#define W0_BAR 3
#define QEF_N 99
#define PACE_T 300
#define IDLE_T 11000
#define LATE_C 99
#define LATE_B B_XFREE + 1
#define LATE_P 0
#define KV_D1 200
#define KV_D2 1200
#define KV_DL 0
#define POL_KV0 POL_FIRST
#define POL_KV1 POL_FIRST
#define POL_O0 POL_FIRST
#define POL_O1 POL_FIRST
#define POL_W0 POL_NORMAL
#define POL_W1 POL_FIRST
#define POL_T POL_FIRST
#define U_C 8
#define ST_M 0
#define POL_Q0 POL_NORMAL
constexpr float LN_EPS = 1e-5f;
constexpr float QSCALE = 0.17677669529663687f * 1.4426950408889634f;

DEVI void fma8(float (&a)[8], uint4 v, float h) {
  a[0] = fmaf(bf_lo(v.x), h, a[0]); a[1] = fmaf(bf_hi(v.x), h, a[1]); a[2] = fmaf(bf_lo(v.y), h, a[2]); a[3] = fmaf(bf_hi(v.y), h, a[3]);
  a[4] = fmaf(bf_lo(v.z), h, a[4]); a[5] = fmaf(bf_hi(v.z), h, a[5]); a[6] = fmaf(bf_lo(v.w), h, a[6]); a[7] = fmaf(bf_hi(v.w), h, a[7]);
}
DEVI uint4 ldsv128(uint32_t a) { uint4 v; asm volatile("ld.volatile.shared.v4.u32 {%0,%1,%2,%3}, [%4];" : "=r"(v.x), "=r"(v.y), "=r"(v.z), "=r"(v.w) : "r"(a) : "memory"); return v; }
DEVI float ldsv32f(uint32_t a) { float v; asm volatile("ld.volatile.shared.f32 %0, [%1];" : "=f"(v) : "r"(a) : "memory"); return v; }
DEVI uint32_t clk() { uint32_t t; asm volatile("mov.u32 %0, %%clock;" : "=r"(t)); return t; }
DEVI int fresh_tid() { int t; asm volatile("mov.u32 %0, %%tid.x;" : "=r"(t)); return t & 127; }
DEVI float fold8(const float (&a)[8]) {
  const int lane = threadIdx.x & 31;
  const bool u = lane & 16, v = lane & 8, x = lane & 4;
  float b0 = (u ? a[4] : a[0]) + __shfl_xor_sync(0xffffffffu, u ? a[0] : a[4], 16), b1 = (u ? a[5] : a[1]) + __shfl_xor_sync(0xffffffffu, u ? a[1] : a[5], 16);
  float b2 = (u ? a[6] : a[2]) + __shfl_xor_sync(0xffffffffu, u ? a[2] : a[6], 16), b3 = (u ? a[7] : a[3]) + __shfl_xor_sync(0xffffffffu, u ? a[3] : a[7], 16);
  float c0 = (v ? b2 : b0) + __shfl_xor_sync(0xffffffffu, v ? b0 : b2, 8), c1 = (v ? b3 : b1) + __shfl_xor_sync(0xffffffffu, v ? b1 : b3, 8);
  return (x ? c1 : c0) + __shfl_xor_sync(0xffffffffu, x ? c0 : c1, 4);
}
DEVI float swiglu(float g, float u) { g = bf_round(g); return bf_round(bf_round(__fdividef(g, 1.f + __expf(-g))) * bf_round(u)); }

template<int J0, int J1> DEVI void exp_pack(const float (&s)[32], uint32_t (&p)[16]) {
  #pragma unroll
  for (int j = J0; j < J1; j++) p[j] = pack_bf16(ex2f(s[2 * j]), ex2f(s[2 * j + 1]));
}
DEVI bool attn_pack(const float (&o)[20], uint32_t (&ob)[8]) {
  const float lo = 5.421010862427522e-20f, hi = 1.8446744073709552e19f;
  float i0, i1; asm("rcp.approx.ftz.f32 %0, %1;" : "=f"(i0) : "f"(o[16])); asm("rcp.approx.ftz.f32 %0, %1;" : "=f"(i1) : "f"(o[18]));
  #pragma unroll
  for (int e = 0; e < 8; e++) ob[e] = pack_bf16(o[2 * e] * ((e & 1) ? i1 : i0), o[2 * e + 1] * ((e & 1) ? i1 : i0));
  return __all_sync(0xffffffffu, o[16] >= lo && o[16] <= hi && o[18] >= lo && o[18] <= hi);
}
DEVI void attn_store(const uint32_t (&ob)[8], bool ok, uint32_t st, uint32_t sb, uint32_t bar) {
  stsm_x4(ok ? st : sb + DUMP, ob[0], ob[1], ob[2], ob[3]); stsm_x4(ok ? st ^ 32 : sb + DUMP, ob[4], ob[5], ob[6], ob[7]);
  __syncwarp();
  asm volatile("{\n.reg .pred p, q;\nelect.sync _|q, 0xffffffff;\nsetp.ne.and.u32 p, %1, 0, q;\n@p mbarrier.arrive.shared::cta.b64 _, [%0];\n}" :: "r"(bar), "r"((uint32_t)ok) : "memory");
}
DEVI void attn_exact(uint32_t st, uint32_t kv, int t, bool hasprev, uint32_t bar) {
  const int lane = threadIdx.x & 31;
  #pragma unroll 1
  for (int row = ((threadIdx.x >> 5) & 3) * 16, n = 0; n < 16; n++, row++) {
    const int k1 = 256 + t * 64 + row;
    float m = -INFINITY, l = 0.f, o = 0.f;
    #pragma unroll 1
    for (int k0 = hasprev ? k1 - 255 : 256; k0 <= k1; k0 += 32) {
      const int k = min(k0 + lane, k1), r = k & 63;
      float sc = 0.f;
      #pragma unroll 1
      for (int c = 0; c < 16; c++) {
        uint32_t a = lds32(st + row * 64 + ((c * 4) ^ ((row & 6) << 3))), b = lds32(kv + (k >> 6) * 8192 + r * 64 + ((c * 4) ^ ((r & 6) << 3)));
        sc = fmaf(bf_lo(a), bf_lo(b), fmaf(bf_hi(a), bf_hi(b), sc));
      }
      float mn = fmaxf(m, sc);
      #pragma unroll 1
      for (int x = 16; x; x >>= 1) mn = fmaxf(mn, __shfl_xor_sync(0xffffffffu, mn, x));
      const float al = ex2f(m - mn), pr = ex2f(sc - mn);
      m = mn; l *= al; o *= al;
      #pragma unroll 1
      for (int q = k0; q <= min(k0 + 31, k1); q++) {
        const float z = __shfl_sync(0xffffffffu, pr, q - k0);
        uint32_t b = lds32(kv + (q >> 6) * 8192 + 4096 + (q & 63) * 64 + (((lane >> 1) * 4) ^ ((q & 6) << 3)));
        l += z; o = fmaf(z, (lane & 1) ? bf_hi(b) : bf_lo(b), o);
      }
    }
    __syncwarp();
    sts16(st + row * 64 + ((lane * 2) ^ ((row & 6) << 3)), pack_bf16(__fdividef(o, l), 0.f));
  }
  warp_signal(bar);
}

template<int K0, int K1, int DONE = 0> DEVI void exp_pv(const float (&s)[32], uint32_t (&p)[16], float (&o)[20], uint32_t vd, bool accum) {
  #pragma unroll
  for (int ks = K0; ks < K1; ks++) {
    if (ks >= DONE) {
      #pragma unroll
      for (int j = 4 * ks; j < 4 * ks + 4; j++) p[j] = pack_bf16(ex2f(s[2 * j]), ex2f(s[2 * j + 1]));
    }
    asm volatile("" : "+r"(p[4 * ks]), "+r"(p[4 * ks + 1]), "+r"(p[4 * ks + 2]), "+r"(p[4 * ks + 3]));
    wg_fence();
    wgmma_rs_n40<1>(o, p[ks * 4], p[ks * 4 + 1], p[ks * 4 + 2], p[ks * 4 + 3], mkd<HI64>(vd + VOFF(ks * 64)), ks ? 1 : accum);
  }
}
template<int K0, int K1> DEVI void exp_pv2(const float (&s)[32], const float (&sx)[32], uint32_t (&p)[16], uint32_t (&px)[16], float (&o)[20], uint32_t v0, uint32_t v4,
                  const uint32_t (&msk)[9], int tdiag) {
  #pragma unroll
  for (int ks = K0; ks < K1; ks++) {
    #pragma unroll
    for (int j = 4 * ks; j < 4 * ks + 4; j++) {
      const int c = 8 * (j >> 1) - 8 * (j & 1);
      const uint32_t e = pack_bf16(ex2f(c > tdiag ? s[2 * j] : sx[2 * j]), ex2f(c + 1 > tdiag ? s[2 * j + 1] : sx[2 * j + 1])), m = msk[(j >> 1) - (j & 1) + 1];
      p[j] = e & m; px[j] = e & ~m;
      asm volatile("" : "+r"(p[j]), "+r"(px[j]));
    }
    wg_fence();
    wgmma_rs_n40<1>(o, p[ks * 4], p[ks * 4 + 1], p[ks * 4 + 2], p[ks * 4 + 3], mkd<HI64>(v0 + VOFF(ks * 64)), 1);
    wgmma_rs_n40<1>(o, px[ks * 4], px[ks * 4 + 1], px[ks * 4 + 2], px[ks * 4 + 3], mkd<HI64>(v4 + VOFF(ks * 64)), 1);
  }
}

template<int J0> DEVI void qkv_store(const float (&a)[96], float p0, float p1, uint32_t d) {
  #pragma unroll
  for (int hh = 0; hh < 2; hh++) {
    const int j = 4 * (J0 + 2 * hh);
    stsm_x4(d ^ (hh << 5), pack_bf16(a[j] * p0, a[j + 1] * p0), pack_bf16(a[j + 2] * p1, a[j + 3] * p1),
                           pack_bf16(a[j + 4] * p0, a[j + 5] * p0), pack_bf16(a[j + 6] * p1, a[j + 7] * p1));
  }
}
DEVI void mean_step(float (&a)[96], float m0, float m1, uint32_t cd, bool z) {
  const uint32_t u0 = z ? 0u : __float_as_uint(m0), u1 = z ? 0u : __float_as_uint(m1);
  uint32_t ma[4] = {__byte_perm(u0, 0u, 0x1010), __byte_perm(u1, 0u, 0x1010), __byte_perm(u0, 0u, 0x3232), __byte_perm(u1, 0u, 0x3232)};
  keep(ma);
  wg_fence();
  wgmma_rs_n192<1>(a, ma[0], ma[1], ma[2], ma[3], mkd<2>(cd), 1);
  wg_commit();
}

template<bool FIRST> DEVI void qkv_block(float (&aX)[96], float (&aY)[96], uint32_t sb16, int s, int tX, int tY) {
  uint32_t a16 = sb16 + (qa_off(s) >> 4), b16 = (sb16 + (qb_off(s) >> 4)) | ((8192u >> 4) << 16);
  uint32_t ax = (a16 + tX * 512) | 0x10000u, ay = (a16 + tY * 512) | 0x10000u;
  wg_fence();
  #pragma unroll
  for (int ks = 0; ks < 4; ks++) {
    wgmma_ss_n192<1>(aX, mkd<HI128>(ax + ks * 2), mkd<HI128>(b16 + ks * 128), !(FIRST && ks == 0));
    wgmma_ss_n192<1>(aY, mkd<HI128>(ay + ks * 2), mkd<HI128>(b16 + ks * 128), !(FIRST && ks == 0));
  }
  wg_commit();
}
DEVI void qkv_half(float (&a)[96], uint32_t sb16, int t, uint32_t sa, uint32_t sbb) {
  wg_fence();
  #pragma unroll
  for (int ks = 0; ks < 4; ks++)
    wgmma_ss_n192<1>(a, mkd<HI128>(((sb16 + (sa >> 4) + t * 512) | 0x10000u) + ks * 2), mkd<HI128>(((sb16 + (sbb >> 4)) | ((8192u >> 4) << 16)) + ks * 128), 1);
  wg_commit();
}
DEVI void wo_block(float (&acc)[64], uint32_t sb16, int n, int s, int wg) {
  uint32_t a16 = (sb16 + (w_aoff(n, s) >> 4) + wg * 256) | 0x10000u, b16 = (sb16 + (w_off(s) >> 4) + 1024) | ((8192u >> 4) << 16);
  wg_fence();
  #pragma unroll
  for (int ks = 0; ks < 4; ks++)
    wgmma_ss_n128<1>(acc, mkd<HI64>(a16 + (ks >> 1) * 512 + (ks & 1) * 2), mkd<HI128>(b16 + ks * 128), 1);
  wg_commit();
}
DEVI void consumer(const Params& P, uint32_t sb, int wg) {
  const int w = uni((threadIdx.x >> 5) & 3);
  #define LAYER uni(mbar_test(BAR(B_XRDY + wg * 2 + 1), 0))
  #define IDS L = LAYER; const int tid = fresh_tid(), lane = tid & 31
  const uint32_t ids = uni(P.map[blockIdx.x]);
  const int bi = (ids >> 4) & 7, rh = ids & 1, bc = (ids & 15) >> 1, fid = ids >> 8;
  const int tX = 3 - wg, tY = wg;
  constexpr uint32_t sb16 = 1024 >> 4;
  #pragma unroll 1
  while (true) {
    int L = LAYER;
    float2 fa, fb;
    {
      float aX[96], aY[96];
      const bool lead = fresh_tid() == 0;
      mbar_wait(BAR(B_FULLQ), 0);
      PROFW(threadIdx.x == 0, L * 8 + 1);
      qkv_block<true>(aX, aY, sb16, 0, tX, tY);
      #pragma unroll 1
      for (int n = 1, s = 1, ps = 0, ph = 0; n < 14; n++) {
        mbar_wait(BAR(B_FULLQ + s), ph ^ (s ? L : 0));
        PROFD(threadIdx.x == 0 && L && (n == 2 || n == 3 || n == 7 || n == 11 || n == 13), n == 2 ? 48 : 49 + (n >> 2));
        qkv_block<false>(aX, aY, sb16, s, tX, tY);
        wg_wait<1>(); if (lead) mbar_arrive(BAR(B_EMPTYQ + ps));
        ps = s; if (s == 2) { s = 0; ph ^= 1; } else s++;
      }
      mbar_wait(BAR(B_FULLQ + 2), L);
      qkv_half(aX, sb16, tX, SA2, SB2);
      mbar_wait(BAR(B_ROW), L);
      IDS;
      const uint32_t pa = sb + PAR + (w * 16 + (lane >> 2)) * 8;
      float2 p0 = lds64f(pa + tX * 512), p1 = lds64f(pa + tX * 512 + 64), p2 = lds64f(pa + tY * 512), p3 = lds64f(pa + tY * 512 + 64);
      mean_step(aX, p0.y, p1.y, sb16 + (CS >> 4), lane & 3);
      mbar_wait(BAR(B_FULLQ), 1);
      qkv_half(aX, sb16, tX, 0, SB0);
      wg_wait<3>(); if (lead) mbar_arrive(BAR(B_EMPTYQ + 1));
      bar_sync(1, 256);
      qkv_half(aY, sb16, tY, SA2, SB2);
      wg_wait<1>(); keep(aX);
      const int srow = w * 16 + (lane & 15);
      const uint32_t x0 = sb + srow * 64 + (((lane >> 4) ^ ((srow >> 1) & 3)) << 4), xX = x0 + (4 + tX) * 8192, xY = x0 + (4 + tY) * 8192;
      qkv_store<8>(aX, p0.x, p1.x, xX + KVA); qkv_store<16>(aX, p0.x, p1.x, xX + KVA + 4096);
      warp_signal(BAR(B_KVRDY + wg * 2));
      qkv_half(aY, sb16, tY, 0, SB0);
      mean_step(aY, p2.y, p3.y, sb16 + (CS >> 4), fresh_tid() & 3);
      wg_wait<2>(); if (lead) mbar_arrive(BAR(B_EMPTYQ + 2));
      mbar_wait(BAR(B_EMPTYQ + 2), L);
      qkv_store<12>(aX, p0.x, p1.x, xX + KVB); qkv_store<20>(aX, p0.x, p1.x, xX + KVB + 4096);
      wg_wait<0>(); keep(aY);
      if (lead) mbar_arrive(BAR(B_EMPTYQ));
      PROFW(threadIdx.x == 0, L * 8 + 2);
      qkv_store<8>(aY, p2.x, p3.x, xY + KVA); qkv_store<16>(aY, p2.x, p3.x, xY + KVA + 4096);
      qkv_store<12>(aY, p2.x, p3.x, xY + KVB); qkv_store<20>(aY, p2.x, p3.x, xY + KVB + 4096);
      warp_signal(BAR(B_KVRDY + wg * 2 + 1));
      p0.x *= QSCALE; p1.x *= QSCALE; p2.x *= QSCALE; p3.x *= QSCALE;
      mbar_wait(BAR(B_EMPTYQ), 1);
      qkv_store<0>(aX, p0.x, p1.x, x0 + QO + tX * 4096);
      qkv_store<0>(aY, p2.x, p3.x, x0 + QO + tY * 4096); qkv_store<4>(aY, p2.x, p3.x, x0 + QO + 16384 + tY * 4096);
      { const float2* f = (const float2*)&P.g->statF[bi * 256 + rh * 128 + (wg ^ rh) * 64 + w * 16 + (lane >> 2)]; fa = __ldcg(f); fb = __ldcg(f + 16); }
      mbar_wait(BAR(B_PAR), L);
      qkv_store<4>(aX, p0.x, p1.x, x0 + QO + 16384 + tX * 4096);
      const int prow = (int)uni(lds32(sb + INFO)) - bi * 256;
      if ((prow >> 4) == tX * 4 + w || (prow >> 4) == tY * 4 + w) {
        __syncwarp();
        if (lane < 24) sts128(sb + (prow & 63) * 64 + (((lane ^ (prow >> 1)) & 3) << 4) +
                              (lane < 8 ? QO + (lane >> 2) * 16384 + (prow >> 6) * 4096 : ((lane & 4) ? KVB : KVA) + (4 + (prow >> 6)) * 8192 + (lane >> 4) * 4096),
                              lds128(sb + PATCH + lane * 16));
      }
      fence_async_smem();
      bar_sync(1, 256);
    }
    PROFW(threadIdx.x == 0, L * 8 + 3);
    {
      IDS;
      float s0[32], s1[32], sx[32], o[20], op[20];
      uint32_t p0[16], p1[16], px[16], msk[9];
      const int tdiag = w * 16 + (lane >> 2) - 2 * (lane & 3);
      const uint32_t ones = (sb16 + (ONES >> 4)) << 16;
      const uint32_t qX = (sb16 + (QO >> 4) + tX * 256) | 0x10000u, qY = (sb16 + (QO >> 4) + tY * 256) | 0x10000u;
      const uint32_t kXB = (sb16 + (KVB >> 4) + tX * 512) | 0x10000u;
      uint32_t redo = 0;
      const uint32_t ost = sb + QO + (w * 16 + (lane & 15)) * 64 + (((lane >> 4) ^ ((lane >> 1) & 3)) << 4);
      #define QA(s, q, k) do { wg_fence(); wgmma_ss_n64<0>(s, mkd<HI64>(q), mkd<HI64>(k), 0); } while (0)
      #define QB(s, q, k) wgmma_ss_n64<0>(s, mkd<HI64>((q) + 2), mkd<HI64>((k) + 2), 1)
      #define QA2(q, k) do { QA(s1, q, k); wgmma_ss_n64<0>(sx, mkd<HI64>(q), mkd<HI64>((k) + 2048), 0); } while (0)
      #define QB2(q, k) do { QB(s1, q, k); QB(sx, q, (k) + 2048); } while (0)
      #define VB(v, b) ((v) + VOFF((b) * 512))
      #define MID() do { wg_commit(); wg_wait<1>(); } while (0)
      QA(s0, qX + 1024, kXB + 1536); QB(s0, qX + 1024, kXB + 1536); wg_commit();
      #pragma unroll
      for (int e = 0; e < 20; e++) o[e] = 0.f;
      wg_wait<0>(); keep(s0);
      #pragma unroll 1
      for (int h = 1; h >= 0; h--) {
        const uint32_t kXA = kXB - ((KVB - KVA) >> 4), kX = h ? kXB : kXA, vX = VOFF((kX & 0xffffu) + 256) + ones;
        QA(s1, qX + h * 1024, kX + 1024);
        #pragma unroll
        for (int e = 0; e < 20; e++) op[e] = o[e];
        keep(op);
        exp_pv<0, 1>(s0, p0, o, VB(vX, 3), false); QB(s1, qX + h * 1024, kX + 1024); wg_commit();
        exp_pv<1, 2>(s0, p0, o, VB(vX, 3), true); MID(); keep(s1);
        exp_pv<2, 4>(s0, p0, o, VB(vX, 3), true);
        { int td = tdiag; asm volatile("" : "+r"(td));
          #pragma unroll
          for (int e = 0; e < 9; e++) msk[e] = ((8 * e - 8 > td) ? 0xFFFFu : 0u) | ((8 * e - 7 > td) ? 0xFFFF0000u : 0u);
          keep(msk); }
        exp_pv<0, 2>(s1, p1, o, VB(vX, 2), true);
        bar_sync(h ? 12 + wg : 4 + wg * 4, h ? 128 : 160);
        QA(s0, qX, kXA + 512 + h * 1024);
        exp_pv<2, 3>(s1, p1, o, VB(vX, 2), true); QB(s0, qX, kXA + 512 + h * 1024);
        exp_pv<3, 4>(s1, p1, o, VB(vX, 2), true); wg_commit();
        wg_wait<0>(); keep(s0); keep(p0); keep(p1); keep(o);
      }
      #pragma unroll 1
      for (int h = 0; h < 2; h++) {
        const uint32_t kb16 = sb16 + ((h ? KVB : KVA) >> 4), kX = (kb16 + tX * 512) | 0x10000u, kY = (kb16 + tY * 512) | 0x10000u, qx = qX + h * 1024, qy = qY + h * 1024;
        const uint32_t onesP = bi ? ones : (kb16 + 1984) << 16;
        const uint32_t vX = VOFF(kb16 + tX * 512 + 256), vY = VOFF(kb16 + tY * 512 + 256);
        uint32_t ob[8], v;
        v = VB(vX + (wg ? onesP : ones), 1);
        QA2(qx, kX);
        exp_pv<0, 1>(s0, p0, o, v, true); QB2(qx, kX); wg_commit();
        exp_pv<1, 2>(s0, p0, o, v, true); MID(); keep(s1); keep(sx);
        exp_pv<2, 4>(s0, p0, o, v, true);
        QA(s0, qy, kY + 1536);
        exp_pv2<0, 1>(s1, sx, p1, px, o, vX + onesP, VB(vX + ones, 4), msk, tdiag); QB(s0, qy, kY + 1536); wg_commit();
        exp_pv2<1, 2>(s1, sx, p1, px, o, vX + onesP, VB(vX + ones, 4), msk, tdiag); MID(); keep(s0); keep(p0);
        exp_pv2<2, 4>(s1, sx, p1, px, o, vX + onesP, VB(vX + ones, 4), msk, tdiag); wg_commit();
        v = VB(vY + (wg ? ones : onesP), 3);
        QA(s1, qy, kY + 1024);
        exp_pack<0, 4>(s0, p0);
        QB(s1, qy, kY + 1024); MID(); keep(o); keep(p1); keep(px);
        bool ok = attn_pack(o, ob); keep(ob);
        exp_pv<0, 2, 1>(s0, p0, o, v, false); MID(); keep(s1);
        attn_store(ob, ok, ost + (h * 4 + tX) * 4096, sb, BAR(B_ORDY + wg * 4 + h * 2)); redo |= ok ? 0u : 1u << (h * 2);
        exp_pv<2, 4>(s0, p0, o, v, true);
        v = VB(vY + onesP, 2);
        exp_pv<0, 1>(s1, p1, o, v, true);
        bar_sync(5 + wg * 4 + h * 2, 160);
        QA(s0, qy, kY + 512);
        exp_pv<1, 2>(s1, p1, o, v, true); QB(s0, qy, kY + 512); wg_commit();
        exp_pv<2, 3>(s1, p1, o, v, true); MID(); keep(s0); keep(p0);
        exp_pv<3, 4>(s1, p1, o, v, true);
        v = VB(vY + onesP, 1);
        QA2(qy, kY);
        exp_pv<0, 1>(s0, p0, o, v, true); QB2(qy, kY); wg_commit();
        exp_pv<1, 2>(s0, p0, o, v, true); MID(); keep(s1); keep(sx); keep(p1);
        exp_pv<2, 4>(s0, p0, o, v, true);
        exp_pv2<0, 1>(s1, sx, p1, px, o, vY + onesP, VB(vY + ones, 4), msk, tdiag);
        bar_sync(6 + wg * 4, h ? 128 : 160);
        QA(s0, h ? qy : qX + 1024, kXB + 512);
        exp_pv2<1, 2>(s1, sx, p1, px, o, vY + onesP, VB(vY + ones, 4), msk, tdiag); QB(s0, h ? qy : qX + 1024, kXB + 512);
        exp_pv2<2, 4>(s1, sx, p1, px, o, vY + onesP, VB(vY + ones, 4), msk, tdiag); wg_commit();
        wg_wait<0>(); keep(o); keep(s0); keep(p0); keep(p1); keep(px);
        ok = attn_pack(o, ob); attn_store(ob, ok, ost + (h * 4 + tY) * 4096, sb, BAR(B_ORDY + wg * 4 + h * 2 + 1)); redo |= ok ? 0u : 2u << (h * 2);
        #pragma unroll
        for (int e = 0; e < 20; e++) o[e] = op[e];
      }
      #undef QA
      #undef QB
      #undef QA2
      #undef QB2
      #undef VB
      #undef MID
      if (redo) {
        #pragma unroll 1
        for (int u = 0; u < 4; u++) if ((redo >> u) & 1) {
          const int h = u >> 1, t = (u & 1) ? tY : tX;
          attn_exact(sb + QO + (h * 4 + t) * 4096, sb + (h ? KVB : KVA), t, bi > 0, BAR(B_ORDY + wg * 4 + u));
        }
      }
    }
    PROFW(threadIdx.x == 0, L * 8 + 4);
    {
      IDS;
      const int t256 = wg * 128 + tid;
      float acc[64];
      const int tt = wg ^ rh;
      const int grow = bi * 256 + rh * 128 + tt * 64 + w * 16 + (lane >> 2);
      float al0 = 1.f, be0 = 0.f, al1 = 1.f, be1 = 0.f;
      const int idx0 = (int)uni(lds32(sb + INFO));
      const uint32_t tag = lds32(sb + INFO + 8) + L;
      uint4* const sp = &P.g->statP[bc][grow + (lane & 1) * 8];
      uint4* const yp = &P.g->yP[t256 >> 1][min(fid, 111)][t256 & 1];
      if (L) {
        float r0 = rsqrtf(fa.y + LN_EPS), r1 = rsqrtf(fb.y + LN_EPS);
        if (grow != idx0) { al0 = 1.f + r0; be0 = -fa.x * r0; }
        if (grow + 8 != idx0) { al1 = 1.f + r1; be1 = -fb.x * r1; }
      }
      const int srow = tt * 64 + w * 16 + (lane & 15);
      const uint32_t ra = sb + srow * 128 + (((lane >> 4) ^ (srow & 7)) << 4);
      mbar_wait(BAR(B_FULLW + 5), L);
      if ((idx0 >> 4) == bi * 16 + rh * 8 + tt * 4 + w) {
        int r = idx0 & 127;
        if (lane < 16) sts128(sb + 32768 + (lane >> 3) * 16384 + r * 128 + (((lane & 7) ^ (r & 7)) << 4), lds128(sb + X2SEG + lane * 16));
        fence_async_smem();
        __syncwarp();
      }
      #pragma unroll
      for (int jj = 0; jj < 8; jj++) {
        uint32_t r[4]; ldsm_x4((ra + 32768 + (jj >> 2) * 16384) ^ ((jj & 3) << 5), r[0], r[1], r[2], r[3]);
        #pragma unroll
        for (int e = 0; e < 4; e++) {
          acc[8 * jj + 2 * e] = fmaf(bf_lo(r[e]), (e & 1) ? al1 : al0, (e & 1) ? be1 : be0);
          acc[8 * jj + 2 * e + 1] = fmaf(bf_hi(r[e]), (e & 1) ? al1 : al0, (e & 1) ? be1 : be0);
        }
      }
      keep(acc);
      bar_sync(12 + wg, 128);
      if (!(lane & 2)) st_ll(sp, 0u, 0u, 0u, 0u);
      uint2 wd[4];
      #pragma unroll
      for (int e = 0; e < 4; e++) { wd[e] = make_uint2(0u, 0u); if (L) wd[e] = ldg_stream((const uint2*)(WDSRC) + t256 + (28 + e) * 256); }
      PROFW(t256 == 0, L * 8 + 5);
      #pragma unroll 1
      for (int n = 0, q = 0, pq = 5; n < 16; n++) {
        mbar_wait(BAR(B_FULLW + q), w_par(n, q, L));
        PROFD(t256 == 0 && !L && (n == 4 || n == 7 || n == 8 || n == 12), (n == 7 ? 63 : 41 + (n >> 2)));
        wo_block(acc, sb16, n, q, tt);
        wg_wait<1>(); if (tid == 0) mbar_arrive(BAR(B_EMPTYW + pq));
        pq = q; q = w_next(n, q);
      }
      mbar_wait(BAR(B_EMPTYW + 5), L);
      wg_wait<0>(); keep(acc);
      if (tid == 0) mbar_arrive(BAR(B_EMPTYW + 4));
      PROFW(t256 == 0, L * 8 + 6);
      {
        float s1a = 0.f, s2a = 0.f, da = 0.f, s1b = 0.f, s2b = 0.f, db = 0.f;
        #pragma unroll
        for (int j = 0; j < 16; j++) {
          const float* a = acc + 4 * j; float2 wv = lds64f(sb + WR + j * 32 + (lane & 3) * 8);
          s1a += a[0] + a[1]; s1b += a[2] + a[3];
          s2a = fmaf(a[0], a[0], s2a); s2b = fmaf(a[2], a[2], s2b); s2a = fmaf(a[1], a[1], s2a); s2b = fmaf(a[3], a[3], s2b);
          da = fmaf(a[0], wv.x, da); db = fmaf(a[2], wv.x, db); da = fmaf(a[1], wv.y, da); db = fmaf(a[3], wv.y, db);
        }
        bool odd = lane & 1;
        float u1 = (odd ? s1b : s1a) + __shfl_xor_sync(0xffffffffu, odd ? s1a : s1b, 1);
        float u2 = (odd ? s2b : s2a) + __shfl_xor_sync(0xffffffffu, odd ? s2a : s2b, 1);
        float u3 = (odd ? db : da) + __shfl_xor_sync(0xffffffffu, odd ? da : db, 1);
        u1 += __shfl_xor_sync(0xffffffffu, u1, 2); u2 += __shfl_xor_sync(0xffffffffu, u2, 2); u3 += __shfl_xor_sync(0xffffffffu, u3, 2);
        if (!(lane & 2)) st_ll(sp, __float_as_uint(u1), __float_as_uint(u2), __float_as_uint(u3), tag);
      }
      const uint32_t xa = ra + rh * 16384;
      #pragma unroll
      for (int jj = 0; jj < 8; jj++) {
        const float* a = acc + 8 * jj;
        stsm_x4((xa + (jj >> 2) * 32768) ^ ((jj & 3) << 5), pack_bf16(a[0], a[1]), pack_bf16(a[2], a[3]), pack_bf16(a[4], a[5]), pack_bf16(a[6], a[7]));
        if (jj == 7) fence_async_smem();
        if ((jj & 3) == 3) warp_signal(BAR(B_XRDY + wg * 2 + (jj >> 2)));
      }
      PROFW(t256 == 0, L * 8 + 7);
      if (L) {
        mbar_wait(BAR(B_PAR), 0);
        { float2 pa = lds64f(sb + PAR + (grow & 127) * 8), pb = lds64f(sb + PAR + (grow & 127) * 8 + 64); al0 = pa.x; be0 = pa.y; al1 = pb.x; be1 = pb.y; }
        uint32_t rs[32];
        #pragma unroll
        for (int j = 0; j < 16; j++) {
          rs[2 * j] = pack_bf16(fmaf(acc[4 * j], al0, be0), fmaf(acc[4 * j + 1], al0, be0));
          rs[2 * j + 1] = pack_bf16(fmaf(acc[4 * j + 2], al1, be1), fmaf(acc[4 * j + 3], al1, be1));
        }
        #pragma unroll
        for (int jj = 0; jj < 8; jj++) stsm_x4((xa + (jj >> 2) * 32768) ^ ((jj & 3) << 5), rs[4 * jj], rs[4 * jj + 1], rs[4 * jj + 2], rs[4 * jj + 3]);
        PROFW(t256 == 0, 16);
        if (fid >= 112) bar_arrive(3, 384);
        else {
          float d[4] = {0.f, 0.f, 0.f, 0.f};
          mbar_wait(BAR(B_FULLW + wg * 3), 0); mbar_wait(BAR(B_FULLW + wg * 3 + 1), 0);
          bar_sync(3, 384);
          PROFW(t256 == 0, 29);
          #pragma unroll 1
          for (int g = 0; g < 4; g++) {
            const uint32_t ad = (sb16 + (wg ? 6144 : 10240) + (g >> 1) * 2048 + (g & 1) * 512) | (1024u << 16), bd = (sb16 + (HV >> 4) + wg * 64 + g * 16) | 0x10000u;
            wg_fence();
            #pragma unroll
            for (int ks = 0; ks < 8; ks++) wgmma_ss_n8<0, 1>(d, mkd<HI64>(ad + ks * 64), mkd<8>(bd + ks * 2), 1);
            wg_commit();
          }
          mbar_wait(BAR(B_FULLW + 2), 0);
          wg_wait<0>(); keep(d);
          if (!(lane & 3)) { sts32f(sb + PAR + 1024 + wg * 256 + w * 64 + lane, d[0]); sts32f(sb + PAR + 1056 + wg * 256 + w * 64 + lane, d[2]); }
          bar_sync(1, 256);
          const uint32_t ga = sb + PAR + 1024 + lane * 4, aa = sb + HV + (t256 >> 5) * 128;
          sts32f(aa + lane * 4, swiglu(lds32f(ga) + lds32f(ga + 256), lds32f(ga + 128) + lds32f(ga + 384)));
          __syncwarp();
          PROFW(t256 == 0, 26);
          float y0 = 0.f, y1 = 0.f, y2 = 0.f, y3 = 0.f;
          uint32_t tbl = rh ? 0x001459a8u : 0x023679a8u;
          uint4 a4 = lds128(aa + 112);
          #pragma unroll 2
          for (int n = 0; n < 8; n++, tbl >>= 4) {
            const uint32_t src = sb + t256 * 8 + (tbl & 15) * 8192;
            const uint4 an = lds128(aa + ((0x00123564u >> (4 * n)) & 15) * 16);
            #pragma unroll
            for (int e = 0; e < 4; e++) {
              const float av = __uint_as_float(e == 0 ? a4.x : (e == 1 ? a4.y : (e == 2 ? a4.z : a4.w)));
              y0 = fmaf(bf_lo(wd[e].x), av, y0); y1 = fmaf(bf_hi(wd[e].x), av, y1); y2 = fmaf(bf_lo(wd[e].y), av, y2); y3 = fmaf(bf_hi(wd[e].y), av, y3);
              const float2 v = lds64f(src + e * 2048); wd[e] = make_uint2(__float_as_uint(v.x), __float_as_uint(v.y));
            }
            a4 = an;
          }
          st_ll(yp, __float_as_uint(y0), __float_as_uint(y1), __float_as_uint(y2), (__float_as_uint(y3) & ~255u) | (lds32(sb + INFO + 12) + 1));
          PROFW(t256 == 0, 27);
        }
        return;
      }
      mbar_wait(BAR(B_XRDY + wg * 2 + 1), 0);
    }
  }
  #undef IDS
  #undef LAYER
}

DEVI void loader(const Params& P, uint32_t sb) {
  const int lane = threadIdx.x & 31;
  const int bid = uni(BID), bi = bid >> 4, bp = bid & 15, rh = bp & 1, bc = bp >> 1;
  uint32_t phq = 0, tag = 0;
  #pragma unroll 1
  for (int L = 0; L < 2; L++) {
    int s = 0;
    uint32_t rdy = 0;
    #pragma unroll 1
    for (int n = L ? 0 : 3; n < 16; n++) {
      int kb = L ? kb_order(bc, n) : n;
      mbar_wait(BAR(B_EMPTYQ + s), (phq >> s) & 1);
      phq ^= 1u << s;
      if (L && n == 1) { mbar_wait(BAR(B_XRDY + 1), 0); mbar_wait(BAR(B_XRDY + 3), 0); }
      if (elect()) {
        mbar_expect_tx(BAR(B_FULLQ + s), L && n < 2 ? 40960 : 57344);
        tma_3d_h(sb + qb_off(s), &P.mWq, bp * 64, kb * 64, 0, BAR(B_FULLQ + s), L && n >= QEF_N ? POL_FIRST : POL_NORMAL);
        if (!L) tma_2d(sb + qa_off(s), &P.mX, kb * 64, bi * 256, BAR(B_FULLQ + s));
      }
      if (L && n >= 2) {
        if (((rdy >> (2 * kb)) & 3) != 3) {
          do { rdy = __ballot_sync(0xffffffffu, ld_rlx(&P.g->flagX[bi][lane]) == tag); } while (((rdy >> (2 * kb)) & 3) != 3);
          fence_async_glob();
        }
        if (n == 3 || n == 4) mbar_wait(BAR(B_XFREE + n - 3), 0);
        if (elect()) bulk_g2s_h(sb + qa_off(s), P.g->x[bi][kb], 32768, BAR(B_FULLQ + s), POL_X);
      }
      PROFY(L && lane == 0 && (n == 2 || n == 3 || n == 9), n == 9 ? 60 : 56 + n);
      if (L && n == 2) { mbar_wait(BAR(B_FULLQ), 0); mbar_wait(BAR(B_FULLQ + 1), 1); if (lane < 2) mbar_arrive_peer(BAR(B_XFREE + lane)); }
      s = (s == 2) ? 0 : s + 1;
    }
    for (int q = 0; q < 3; q++) mbar_wait(BAR(B_EMPTYQ + q), (phq >> q) & 1);
    tag = lds32(sb + INFO + 8) + L;
    #pragma unroll 1
    for (int q = 0; q < 4; q++) {
            if (bi) {
        const unsigned* f = &P.g->flagKV[bid - 16][q];
        while (ld_rlx(f) != tag);
        fence_async_glob();
      }
      if (elect()) {
        mbar_expect_tx(BAR(B_KVFULL + q), 16384);
        bulk_g2s_h(sb + ((q >> 1) ? KVB : KVA) + ((q & 1) ? 0 : 16384), bi ? P.g->kv[bid - 16][q] : P.g->zero, 16384, BAR(B_KVFULL + q), L ? POL_KV1 : POL_KV0);
      }
      PROFY(!L && lane == 0 && bi && q != 2, 34 + (q + 1) / 2);
    }
    mbar_wait(BAR(B_ORDY), L);
    {
      const uint4* src = P.g->o[bi][0][0][rh];
      rdy = 0;
      #pragma unroll 1
      for (int n = 0, q = 0; n < 16; q = w_next(n, q), n++) {
        const int j = wo_order(bc, n);
        if (((rdy >> (2 * j)) & 3) != 3) {
          do { rdy = __ballot_sync(0xffffffffu, ld_rlx(&P.g->flagO[bi][lane]) == tag); } while (((rdy >> (2 * j)) & 3) != 3);
          fence_async_glob();
        }
        if (n >= 2) mbar_wait(n < 5 ? BAR(B_HAFREE + (n > 3)) : BAR(B_EMPTYW + q), n < 5 ? L : w_par(n, q, L) ^ 1);
        if (n == THR_N) mbar_wait(BAR(B_OFREE), L);
        if (elect()) { mbar_expect_tx(BAR(B_FULLW + q), 16384); bulk_g2s_h(sb + w_aoff(n, q), src + j * 2048, 16384, BAR(B_FULLW + q), L ? POL_O1 : POL_O0); }
      }
    }
    mbar_wait(BAR(B_OFREE), L);
  }
}

DEVI void ffn_prefetch(const Params& P, int q) {
  bulk_prefetch(q < 16 ? ((q & 1) ? P.wu : P.wg) + ((q >> 1) * 128 + blockIdx.x) * 3584 : P.wd + (min(FID, 111) * 8 + q - 16) * 4096, q < 16 ? 7168 : 8192);
}
DEVI void storer(const Params& P, uint32_t sb, int wg) {
  const int bid = uni(BID), bi = bid >> 4, rh = bid & 1, bc = (bid & 15) >> 1;
  const bool one = (threadIdx.x & 31) == 0;
  char* const g = (char*)P.g;
  const uint32_t tag0 = uni(((ld_rlx(&P.g->epoch) % 16383u) + 1u) << 2);
  #pragma unroll 1
  for (int L = 0; L < 2; L++) {
    const uint32_t tag = tag0 + L;
    if (wg) {
      #pragma unroll 1
      for (int r = threadIdx.x & 31; r < 256; r += 32) {
        uint4 v;
        do v = ld_ll(&P.g->statF[bi * 256 + r]); while (!__all_sync(0xffffffffu, v.w == tag));
        float var = __uint_as_float(v.y), c = rsqrtf(var + LN_EPS);
        if (L) { c += 1.f; c *= rsqrtf(fmaf(var * c, c, LN_EPS)); }
        const float mh = bf_round(__uint_as_float(v.x));
        sts64f(sb + PAR + r * 8, c, __uint_as_float(pack_bf16(mh, __uint_as_float(v.x) - mh)));
      }
      if (!L) mbar_wait(BAR(B_PAR), 0);
      warp_signal(BAR(B_ROW));
    }
    #pragma unroll 1
    for (int u = 0; u < 2 + 4 * wg; u++) {
      const int h = u < 2 ? u : u >> 2, hi = (u & 1) ^ 1;
      uint32_t src, dst, fl, b0, b1;
      if (u < 2) {
        src = (h ? KVB : KVA) + (3 - wg) * 16384; dst = offsetof(Scratch, kv) + (bid * 4 + h * 2 + wg) * 16384; fl = offsetof(Scratch, flagKV) + (bid * 32 + h * 2 + wg) * 4;
        b0 = BAR(B_KVRDY + ((u | wg) ? 1 : 0)); b1 = b0 + 16;
      } else {
        src = QO + (h * 2 + hi) * 8192; dst = offsetof(Scratch, o) + ((((bi * 2 + h) * 8 + bc) * 2 + hi) * 2 + rh) * 8192;
        fl = offsetof(Scratch, flagO) + (bi * 32 + h * 16 + (bid & 15)) * 4;
        b0 = BAR(B_ORDY + u - 2); b1 = b0 + 32;
      }
      mbar_wait(b0, L); mbar_wait(b1, L);
      if (u + wg == 1) {
        mbar_wait(BAR(B_PAR), L);
        const uint32_t t0 = clk(), dt = (wg ? KV_D1 : KV_D2) + (L ? KV_DL : 0); while (clk() - t0 < dt) __nanosleep(40);
      }
      fence_async_smem();
      PROFY(one && !L && u == 3 * wg, u ? 46 : 8);
      if (one && (u >= 2 || bi < 7)) bulk_s2g(g + dst, sb + src, u < 2 ? 16384 : 8192, ((ST_M >> (L * 2 + (u >= 2))) & 1) ? POL_FIRST : POL_NORMAL);
      if (one && u == 5) mbar_arrive(BAR(B_HAFREE + 1));
      if (u == 2 || u == 4) continue;
      bulk_wait<0>();
      PROFY(one && !L && u == 3 * wg, u ? 61 : 62);
      fence_rel();
      if (one) { st_rlx((unsigned*)(g + fl), tag); if (!wg || u > 2) mbar_arrive(BAR(B_HAFREE + h + (wg & h))); if (!wg && u) mbar_arrive(BAR(B_RES)); }
      PROFY(one && !L && (u > 2 || u == wg), u > 2 ? (u == 3 ? 38 : 54) : 32 + u);
    }
    if (L == 0) {
      char* dst = g + (offsetof(Scratch, x) + (bi * 16 + 2 * bc) * 32768 + rh * 16384);
      unsigned* f = (unsigned*)(g + (offsetof(Scratch, flagX) + (bi * 32 + bc * 4 + rh) * 4));
      const uint32_t a = sb + rh * 16384;
      if (wg == 0) {
        mbar_wait(BAR(B_XRDY), 0); mbar_wait(BAR(B_XRDY + 2), 0);
        fence_async_smem();
        PROFY(one, 41);
        if (one) bulk_s2g(dst, a, 16384);
        bulk_wait<0>();
        PROFY(one, 45);
        if (one) { mbar_arrive(BAR(B_XFREE)); mbar_arrive(BAR(B_PFREE)); }
        fence_rel();
        mbar_wait(BAR(B_XRDY + 1), 0); mbar_wait(BAR(B_XRDY + 3), 0);
        if (one) { st_rlx(f, tag); bulk_s2g(dst + 32768, a + 32768, 16384); }
        PROFY(one, 56);
        bulk_wait<0>();
        if (one) mbar_arrive(BAR(B_XFREE + 1));
        fence_rel();
        if (one) st_rlx(f + 2, tag);
        PROFY(one, 57);
      } else {
        mbar_wait(BAR(B_XRDY + 1), 0); mbar_wait(BAR(B_XRDY + 3), 0);
        mbar_wait(BAR(B_PFREE), 0);
        if (one) bulk_s2peer(a, 16384, BAR(B_FULLQ));
        { const uint32_t t0 = clk(); while (clk() - t0 < XD_D); }
        if (one) bulk_s2peer(a + 32768, 16384, BAR(B_FULLQ + 1));
      }
      if (wg == 0) {
        uint32_t t0 = clk() + PF1_D;
        #pragma unroll 1
        for (int q = PF1_S; q < PF1_E; q++) { while ((int)(clk() - t0) < 0) __nanosleep(50); if (one) ffn_prefetch(P, q); t0 += PF1_T; }
      }
    }
  }
}

DEVI void stg_issue(const Params& P, int c, uint32_t d, uint32_t du, uint32_t b) {
  mbar_expect_tx(b, 16384);
  if (c < 8) { tma_2d_h(d, &P.mWg, FID * 32, c * 128, b, du > 8192 ? POL_T : POL_G); tma_2d_h(d + du, &P.mWu, FID * 32, c * 128, b, du > 8192 || c < U_C ? POL_FIRST : POL_NORMAL); }
  else if (c < 12) tma_3d_h(d, &P.mWd, 0, FID * 32 + (c - 8) * 8, 0, b, POL_D);
  else tma_2d_h(d, &P.mWp, (c - 12) * 1024 + (BID >> 2) * 32, (BID & 3) * 256, b, POL_EF);
}
DEVI void pace() { const uint32_t t0 = clk(); while (clk() - t0 < PACE_T); }
DEVI void stager(const Params& P, uint32_t sb) {
  {
    const int b = blockIdx.x;
    uint32_t t0 = clk();
    #pragma unroll 1
    for (int q = 0; q < PQ_N; q++) { bulk_prefetch(P.wqkv + (q * 128 + b) * 3072, 6144); while (clk() - t0 < PQ_T) __nanosleep(50); t0 += PQ_T; }
    bulk_prefetch(P.wo + b * 8192, 16384);
    #pragma unroll 1
    for (int q = 0; q < PF0_N; q++) {
      while (clk() - t0 < PF0_T) __nanosleep(50);
      t0 += PF0_T;
      ffn_prefetch(P, q);
    }
  }
  const int bid = BID, bi = bid >> 4, rh = bid & 1, bc = (bid & 15) >> 1;
  #pragma unroll 1
  for (int L = 0; L < 2; L++) {
    const int nch = L ? (FID < 112 ? 8 : 0) : 15;
    mbar_wait(BAR(B_PAR), L); mbar_wait(BAR(B_KVFULL + W0_BAR), L);
    #pragma unroll 1
    for (int m = 0, r = 0; m < 16; r = w_next(m, r), m++) {
      const int sw = (m == 3 || m == 4) ? 7 : 0, n = m ^ sw, q = r ^ sw;
      if (n == 4) { mbar_wait(BAR(B_RES), L); mbar_wait(BAR(B_ORDY + 2), L); mbar_wait(BAR(B_ORDY + 6), L); }
      else if (n >= 2) mbar_wait(n < 5 ? BAR(B_HAFREE + (n > 2)) : BAR(B_EMPTYW + q), n < 5 ? L : w_par(n, q, L) ^ 1);
      if (n == THR_N) mbar_wait(BAR(B_OFREE), L);
      mbar_expect_tx(BAR(B_FULLW + q), 16384);
      tma_5d(sb + w_off(q) + 16384, &P.mWo, 0, 0, n >> 3, 2 * (wo_order(bc, n) & 7), 2 * bc, BAR(B_FULLW + q), L ? POL_W1 : POL_W0);
      if (n == 2) {
        #pragma unroll 1
        for (int e = 0; e < 2; e++) {
          mbar_expect_tx(BAR(B_FULLW + 5), 16384);
          if (L) bulk_g2s_h(sb + 32768 + e * 16384, P.g->x[bi][2 * bc + e] + rh * 1024, 16384, BAR(B_FULLW + 5));
          else tma_2d_h(sb + 32768 + e * 16384, &P.mXh, bc * 128 + e * 64, bi * 256 + rh * 128, BAR(B_FULLW + 5), POL_EF);
        }
      }
    }
    mbar_wait(BAR(B_EMPTYW + 5), L);
    if (L && nch) {
      const bf16* src = WDSRC2;
      mbar_expect_tx(BAR(B_FULLW + 2), 32768); mbar_expect_tx(BAR(B_FULLW + 2), 24576);
      #pragma unroll 1
      for (int e = 0; e < 3; e++) { bulk_g2s_h(sb + e * 32768 + (e < 2 ? (rh ^ 1) * 16384 : 0), src + e * 8192, e < 2 ? 16384 : 24576, BAR(B_FULLW + 2)); pace(); }
    }
        if (L == 0) { mbar_arrive_peer(BAR(B_PFREE)); mbar_wait(BAR(B_EMPTYW), 0); mbar_wait(BAR(B_EMPTYW + 1), 0); }
    #pragma unroll 1
    for (int c = FID < 112 ? 0 : 12, slot = 0; c < nch; c++, slot = slot == 2 ? 0 : slot + 1) {
      const int q = (c >> 1) + (c >> 2);
      if (!L && (c == LATE_C || c == 12)) mbar_wait(BAR(LATE_B), LATE_P);
      mbar_wait(L ? BAR(B_EMPTYW + q) : BAR(B_STGE + slot), L | ((0x71c7 >> c) & 1));
      #define CC c
      stg_issue(P, CC, L ? sb + w_off(q) + (c & 1) * 8192 : sb + STG + slot * 16384, 8192 << L, L ? BAR(B_FULLW + q) : BAR(B_STG + slot));
      if (L) pace();
    }
  }
}
DEVI void sum8(uint4 v, float& s1, float& s2) {
  float e[8] = {bf_lo(v.x), bf_hi(v.x), bf_lo(v.y), bf_hi(v.y), bf_lo(v.z), bf_hi(v.z), bf_lo(v.w), bf_hi(v.w)};
  #pragma unroll
  for (int q = 0; q < 8; q++) { s1 += e[q]; s2 = fmaf(e[q], e[q], s2); }
}
DEVI uint4 norm8(uint4 x, float m, float rs) {
  #define HN(v) pack_bf16((bf_lo(v) - m) * rs, (bf_hi(v) - m) * rs)
  return make_uint4(HN(x.x), HN(x.y), HN(x.z), HN(x.w));
  #undef HN
}
DEVI void put_f32(uint4 b, uint32_t d, uint32_t d2) {
  sts128(d, make_uint4(b.x << 16, b.x & 0xffff0000u, b.y << 16, b.y & 0xffff0000u));
  sts128(d + d2, make_uint4(b.z << 16, b.z & 0xffff0000u, b.w << 16, b.w & 0xffff0000u));
}
DEVI void put_bf16(uint4 b, uint32_t d) {
  sts64f(d, __uint_as_float(b.x), __uint_as_float(b.y)); sts64f(d + 1024, __uint_as_float(b.z), __uint_as_float(b.w));
  fence_async_smem();
}
DEVI uint4 best4(uint32_t p) {
  uint4 a = lds128(p), b = lds128(p + 16), c = lds128(p + 32), d = lds128(p + 48);
  if (b.x > a.x) a = b;
  if (d.x > c.x) c = d;
  return c.x > a.x ? c : a;
}
#define FL(x) __uint_as_float(x)
#define UI(x) __float_as_uint(x)
DEVI void aux(const Params& P, uint32_t sb) {
  int tid = fresh_tid();
  #define lane (tid & 31)
  #define wq (tid >> 5)
  uint32_t ids = P.map[blockIdx.x], tag;
  #define bid ((int)(ids & 255))
  #define fid ((int)(ids >> 8))
  #define bi (bid >> 4)
  #define bp (bid & 15)
  #define bc (bp >> 1)
  #define FRESH() do { tid = fresh_tid(); uint4 z_ = ldsv128(sb + INFO2 + 16); ids = z_.y; tag = z_.z + L; idx = z_.w; } while (0)
  {
    const uint32_t epoch = ld_rlx(&P.g->epoch);
    if (tid == 0) {
      mbar_expect_tx(BAR(B_STG), 49152);
      tma_3d(sb + STG, &P.mWq, bp * 64, bi * 128, 0, BAR(B_STG));
      tma_3d(sb + STG + 24576, &P.mWq, bp * 64, bi * 128 + 64, 0, BAR(B_STG));
    }
    __syncwarp();
    sts64f(sb + ONES + tid * 8, FL(0x3F803F80u), FL(0x3F803F80u));
    float s1 = 0.f, s2 = 0.f;
    { uint4 v = __ldg((const uint4*)P.wr + tid);
      if ((tid >> 4) == bc) put_f32(v, sb + WR + (tid & 15) * 32, 16);
      sum8(v, s1, s2);
      #pragma unroll 1
      for (int o = 16; o; o >>= 1) s1 += __shfl_xor_sync(0xffffffffu, s1, o);
      sts32f(sb + INFO2 + wq * 4, s1); }
    const uint4* src = (const uint4*)(P.x0 + (size_t)bid * 16384) + (tid >> 3) * 128 + (tid & 7);
    s1 = 0.f; s2 = 0.f;
    #pragma unroll 1
    for (int it = 0; it < 16; it += 4) {
      uint4 v0 = __ldg(src + it * 8), v1 = __ldg(src + it * 8 + 8), v2 = __ldg(src + it * 8 + 16), v3 = __ldg(src + it * 8 + 24);
      #pragma unroll 1
      for (int q = 0; q < 4; q++) { sum8(v0, s1, s2); v0 = v1; v1 = v2; v2 = v3; }
    }
    #pragma unroll 1
    for (int o = 1; o < 8; o <<= 1) { s1 += __shfl_xor_sync(0xffffffffu, s1, o); s2 += __shfl_xor_sync(0xffffffffu, s2, o); }
    tag = ((epoch % 16383u) + 1u) << 2;
    if (tid == 0) { sts128(sb + INFO, make_uint4(0x40000000u, 0u, tag, ((epoch % 127u) + 1u) << 1)); sts128(sb + INFO2 + 16, make_uint4(epoch, ids, tag, 0x40000000u)); }
    float m = s1 * (1.f / 1024.f);
    if ((tid & 7) == 0) st_ll(&P.g->statF[bid * 16 + (tid >> 3)], UI(m), UI(fmaxf(fmaf(-m, m, s2 * (1.f / 1024.f)), 0.f)), 0u, tag);
    bar_sync(2, 128);
    mbar_wait_b(BAR(B_STG), 0);
    if (tid < 96) {
      s1 = 0.f; s2 = 0.f;
      #pragma unroll 1
      for (int r = 0; r < 16; r++) {
        const uint32_t a = sb + STG + (r >> 3) * 24576 + wq * 8192 + (r & 7) * 128 + ((lane * 4) ^ ((r & 7) << 4));
        #pragma unroll
        for (int e = 0; e < 8; e++) { uint32_t v = lds32(a + e * 1024); s1 += bf_lo(v); s2 += bf_hi(v); }
      }
      st_ll(&P.g->csP[bp][bi][tid], UI(s1), UI(s2), 0u, tag);
      s1 = 0.f; s2 = 0.f;
      #pragma unroll 1
      for (int q = 0; q < 8; q += 2) {
        uint4 a, b; poll_ll2(&P.g->csP[bp][q][tid], &P.g->csP[bp][q + 1][tid], 0xffffffffu, tag, a, b);
        s1 += FL(a.x) + FL(b.x); s2 += FL(a.y) + FL(b.y);
      }
      const uint32_t hi = pack_bf16(-s1, -s2);
      sts32(sb + CS + (tid >> 2) * 32 + (tid & 3) * 4, hi);
      sts32(sb + CS + (tid >> 2) * 32 + (tid & 3) * 4 + 16, pack_bf16(-s1 - bf_lo(hi), -s2 - bf_hi(hi)));
    }
    fence_async_smem();
  }
  int idx;
  #pragma unroll 1
  for (int L = 0; L < 2; L++) {
    FRESH();
    {
      if ((unsigned)(bi - (idx >> 8)) < 2u) {
        const uint4* src = &P.g->patch[bp * 8 + (tid >> 6) * 4][tid & 63];
        const float4 z = poll_sum4(src, 64, tag);
        float q = z.x, k = z.y, v = z.z;
        q += __shfl_xor_sync(0xffffffffu, q, 1); k += __shfl_xor_sync(0xffffffffu, k, 1); v += __shfl_xor_sync(0xffffffffu, v, 1);
        bar_sync(2, 128);
        const uint32_t d = sb + PATCH + (tid & ~1), kv = pack_bf16(k, v);
        sts16(d, pack_bf16(q * QSCALE, 0.f)); sts16(d + 128, kv); sts16(d + 256, kv >> 16);
      }
      sts32(sb + INFO, idx);
      bar_sync(2, 128);
    }
    const uint4 fix = lds128(sb + PATCH + 128 + (lane & 4) * 32 + (wq >> 1) * 64 + (lane & 3) * 16);
    warp_signal(BAR(B_PAR));
    PROFX(tid == 0, L ? 23 : 17);
    mbar_wait_b(BAR(B_KVFULL + wq), L);
    if ((idx >> 7) == bi * 2 - 1 - (wq & 1)) {
      if (lane < 8) sts128(sb + ((wq >> 1) ? KVB : KVA) + ((idx >> 6) & 3) * 8192 + (lane >> 2) * 4096 + (idx & 63) * 64 + (((lane ^ (idx >> 1)) & 3) << 4), fix);
      fence_async_smem();
    }
    bar_arrive(4 + wq, 160); bar_arrive(8 + wq, 160);
    FRESH();
    mbar_wait_b(BAR(B_OFREE), L);
    #define blk (bi * 2 + (bid & 1))
    if (tid < 33) st_ll(tid < 32 ? &P.g->row[blk][bc * 32 + tid] : &P.g->best[bc][blk], 0u, 0u, 0u, 0u);
    mbar_wait_b(BAR(B_XRDY), L);
    PROFX(tid == 0, 37 + L * 16);
    FRESH();
    {
      float s1 = 0.f, s2 = 0.f, d = 0.f;
      #pragma unroll 1
      for (int q = 0; q < 8; q += 4) { const float4 v = poll_sum4(&P.g->statP[q][blk * 128 + tid], 2048, tag); s1 += v.x; s2 += v.y; d += v.z; }
      PROFX(tid == 0, 39 + L * 16);
      uint4 a = lds128(sb + INFO2), b, c;
      float m = s1 * (1.f / 1024.f), var = fmaxf(fmaf(-m, m, s2 * (1.f / 1024.f)), 0.f), rs = rsqrtf(var + LN_EPS);
      uint32_t key = UI(fmaf(-m, (FL(a.x) + FL(a.y)) + (FL(a.z) + FL(a.w)), d) * rs);
      key ^= (uint32_t)((int)key >> 31) | 0x80000000u;
      uint32_t win = __ballot_sync(0xffffffffu, key == __reduce_max_sync(0xffffffffu, key));
      if (lane == __ffs(win) - 1) sts128(sb + RED + wq * 16, make_uint4(key, UI(m), UI(rs), (tag << 11) | (uint32_t)(blk * 128 + tid)));
      if (L) sts64f(sb + PAR + tid * 8, 1.f + rs, -m * rs);
      else if ((tid >> 4) == bc) st_ll(&P.g->statF[blk * 128 + tid], UI(m), UI(var), 0u, tag + 1);
      bar_sync(2, 128);
      if (wq < 2) a = best4(sb + RED);
      if (tid == 32) st_ll(&P.g->best[bc][blk], a.x, a.y, a.z, a.w);
      if (wq == 0) {
        mbar_wait(BAR(B_XRDY + 1), L); mbar_wait(BAR(B_XRDY + 3), L);
        float2 v = lds64f(sb + (lane >> 4) * 32768 + (a.w & 255) * 128 + (((lane & 15) * 8) ^ ((a.w & 7) << 4)));
        st_ll(&P.g->row[blk][bc * 32 + lane], UI(v.x), UI(v.y), 0u, tag);
        __syncwarp();
        if (lane < 2 + 2 * L) mbar_arrive(L ? BAR(B_PAR) : BAR(B_XFREE + lane));
      }
      PROFX(tid == 0, 18 + L * 6);
      FRESH();
      a = poll_ll(&P.g->best[bc][lane & 15], 0xfffff800u, tag << 11);
      win = __ffs(__ballot_sync(0xffffffffu, a.x == __reduce_max_sync(0xffffffffu, a.x))) - 1;
      idx = __shfl_sync(0xffffffffu, a.w, win) & 2047;
      PROFX(tid == 0, 19 + L * 6);
      poll_ll2(&P.g->row[win][tid], &P.g->row[win][tid + 128], 0xffffffffu, tag, c, b);
      c.z = b.x; c.w = b.y;
      a.x = __shfl_sync(0xffffffffu, a.x, win); a.y = __shfl_sync(0xffffffffu, a.y, win); a.z = __shfl_sync(0xffffffffu, a.z, win);
      sts32(sb + INFO2 + 28, idx);
      PROFX(tid == 0, 61 + L);
      b = norm8(c, FL(a.y), FL(a.z));
      if (L) put_bf16(b, sb + HV + tid * 8); else put_f32(b, sb + HV + tid * 16, 2048);
      if ((tid >> 1) == (bid & 63)) {
        sts128(sb + RED + 64 + (tid & 1) * 16, bid < 64 ? make_uint4(c.x, c.y, b.x, b.y) : make_uint4(c.z, c.w, b.z, b.w));
        sts32(sb + RED + 96, a.x);
      }
      bar_sync(2 + L, 128 + L * 256);
      if (L) {
        const int r0 = blk * 128 + (tid >> 4);
        uint32_t src = sb + ((tid >> 3) & 1) * 32768 + (r0 & 255) * 128 + (((tid ^ r0) & 7) << 4);
        uint4* dst = (uint4*)(P.out + (size_t)r0 * 1024 + bc * 128) + (tid & 15);
        #pragma unroll 4
        for (int it = 0; it < 16; it++) { uint4 v = lds128(src + it * 1024); if (idx - r0 != it * 8) dst[it * 1024] = v; }
      }
    }
    #pragma unroll 1
    for (int st = L; st < 2; st++) {
      FRESH();
      float a[8] = {0.f, 0.f, 0.f, 0.f, 0.f, 0.f, 0.f, 0.f};
      if (L == 0 && fid < 112) {
        uint32_t ha = st ? sb + RED + 768 : sb + HV + ((wq & 1) * 64 + (lane >> 2)) * 4;
        uint32_t ph = st ? 0x1cu : 0x171u, bar = st ? BAR(B_STG + 2) : BAR(B_STG);
        uint32_t wa = sb + STG + wq * 4096 + (st ? 32768 + lane * 16 : (lane ^ (lane >> 3)) * 16);
        const uint32_t hx = st ? 256 : 512;
        const bool lead = lane == 0;
        uint4 vc = make_uint4(0u, 0u, 0u, 0u); float hc = 0.f;
        #pragma unroll 1
        do {
          mbar_wait(bar, ph & 1);
          PROFX(lead && threadIdx.x == 256 && st == 0 && (ph > 255 || ph < 4), 40 - 23 + __clz(ph));
          #pragma unroll
          for (int n = 0; n < 8; n++) { const uint4 v = lds128(wa + n * 512); const float h = lds32f(ha + n * 32); fma8(a, vc, hc); vc = v; hc = h; }
          __syncwarp();
          if (lead) mbar_arrive(bar - 8 * (B_STG - B_STGE));
          const bool wrap = bar == BAR(B_STG + 2);
          bar += wrap ? -16 : 8; wa += wrap ? -32768 : 16384; ha += hx;
          ph >>= 1;
        } while (ph != 1);
        fma8(a, vc, hc);
      }
      FRESH();
      if (st == 1) {
        const uint32_t t8 = lds32(sb + INFO + 12) + L;
        if (L == 0 && fid < 112) {
          const bool odd = lane & 1;
          #pragma unroll
          for (int e = 0; e < 4; e++) { float z = __shfl_xor_sync(0xffffffffu, odd ? a[e] : a[4 + e], 1); if (odd) a[e] = z; else a[4 + e] = z; }
          uint4* dst = &P.g->yP[tid & ~1][fid][tid & 1];
          st_ll(dst, UI(a[0]), UI(a[1]), UI(a[2]), (UI(a[3]) & ~255u) | t8);
          st_ll(dst + 224, UI(a[4]), UI(a[5]), UI(a[6]), (UI(a[7]) & ~255u) | t8);
          PROFX(tid == 0, 21);
        }
        if (tid == 0) { uint32_t k = lds32(sb + RED + 96); sts32f(sb + RED + 100, bf_round(__fdividef(1.f, 1.f + __expf(-bf_round(FL(k ^ (~(uint32_t)((int)k >> 31) | 0x80000000u))))))); }
        uint4 v0, v1;
        poll_ll2(&P.g->yP[bid][0][min(tid, 111)], &P.g->yP[bid][0][min(tid, 111) + 112], 255u, t8, v0, v1);
        const float lo = (tid < 112 && !(tid & 1)) ? 1.f : 0.f, hi = (tid < 112 && (tid & 1)) ? 1.f : 0.f;
        const float y0 = FL(v0.x) + FL(v1.x), y1 = FL(v0.y) + FL(v1.y), y2 = FL(v0.z) + FL(v1.z), y3 = FL((v0.w & ~255u) | 128u) + FL((v1.w & ~255u) | 128u);
        a[0] = y0 * lo; a[1] = y1 * lo; a[2] = y2 * lo; a[3] = y3 * lo; a[4] = y0 * hi; a[5] = y1 * hi; a[6] = y2 * hi; a[7] = y3 * hi;
      }
      sts32f(sb + RED + 256 + wq * 128 + ((lane & 3) * 8 + (lane >> 2)) * 4, fold8(a));
      bar_sync(2, 128);
      const uint32_t d = sb + RED + 256 + lane * 4;
      float z0 = lds32f(d) + lds32f(d + 128), z1 = lds32f(d + 256) + lds32f(d + 384);
      if (st == 0) {
        sts32f(sb + RED + 768 + lane * 32 + wq * 4, swiglu(z0, z1));
        bar_sync(2, 128);
        if (fid < 112) { st_ll(&P.g->yP[tid & ~1][fid][tid & 1], 0u, 0u, 0u, 0u); st_ll(&P.g->yP[tid | 1][fid][tid & 1], 0u, 0u, 0u, 0u); }
        else { const uint32_t t0 = clk(); while (clk() - t0 < IDLE_T) __nanosleep(200); }
        if (tid < 80) st_ll(tid < 64 ? &P.g->patch[bid][tid] : &P.g->x2[(tid >> 1) & 7][2 * bid + (tid & 1)], 0u, 0u, 0u, 0u);
        PROFX(tid == 0, 20); continue; }
      z0 += z1;
      z0 += __shfl_xor_sync(0xffffffffu, z0, 8); z0 += __shfl_xor_sync(0xffffffffu, z0, 16);
      uint32_t xw = lds32(sb + RED + 64 + (lane & 4) * 4 + (lane & 2) * 2), hw = lds32(sb + RED + 72 + (lane & 4) * 4 + (lane & 2) * 2);
      z0 = bf_round(((lane & 1) ? bf_hi(hw) : bf_lo(hw)) + bf_round(bf_round(z0) * lds32f(sb + RED + 100))) + ((lane & 1) ? bf_hi(xw) : bf_lo(xw));
      uint32_t v = pack_bf16(z0, __shfl_down_sync(0xffffffffu, z0, 1)), v2 = __shfl_down_sync(0xffffffffu, v, 2);
      if (L) { if (tid == 0 || tid == 4) *(uint2*)(P.out + (size_t)idx * 1024 + bid * 8 + tid) = make_uint2(v, v2); PROFW(tid == 0, 28); }
      else if ((tid & 3) == 0 && tid < 64) st_ll(&P.g->x2[tid >> 3][2 * bid + ((tid >> 2) & 1)], v, v2, 0u, tag + 1);
    }
    if (L == 0) {
      PROFX(tid == 0, 22);
      FRESH();
      uint4 x, y; poll_ll2(&P.g->x2[bi][tid], &P.g->x2[bi][tid + 128], 0xffffffffu, tag + 1, x, y);
      x.z = y.x; x.w = y.y;
      if (wq == (bc & 3)) sts64f(sb + X2SEG + lane * 8, FL(bc < 4 ? x.x : x.z), FL(bc < 4 ? x.y : x.w));
      float s1 = 0.f, s2 = 0.f;
      sum8(x, s1, s2);
      #pragma unroll
      for (int o = 16; o; o >>= 1) { s1 += __shfl_xor_sync(0xffffffffu, s1, o); s2 += __shfl_xor_sync(0xffffffffu, s2, o); }
      sts64f(sb + RED + wq * 8, s1, s2);
      bar_sync(2, 128);
      y = lds128(sb + RED); uint4 y2 = lds128(sb + RED + 16);
      float m = ((FL(y.x) + FL(y.z)) + (FL(y2.x) + FL(y2.z))) * (1.f / 1024.f);
      put_bf16(norm8(x, m, rsqrtf(fmaxf(fmaf(-m, m, ((FL(y.y) + FL(y.w)) + (FL(y2.y) + FL(y2.w))) * (1.f / 1024.f)), 0.f) + LN_EPS)), sb + HV + tid * 8);
      mbar_wait(BAR(B_STG), 1); mbar_wait(BAR(B_STG + 1), 0); mbar_wait(BAR(B_STG + 2), 0);
      bar_sync(2, 128);
      PROFX(tid == 0, 30);
      float d0[4] = {0.f, 0.f, 0.f, 0.f}, d1[4] = {0.f, 0.f, 0.f, 0.f}, d2[4] = {0.f, 0.f, 0.f, 0.f};
      const uint32_t bd = (64 + (HV >> 4) + uni(bid & 3) * 32) | 0x10000u;
      #pragma unroll 1
      for (int ks = 0; ks < 8; ks++) {
        const uint32_t ad = (64 + (STG >> 4) + ks * 128) | (64u << 16);
        wg_fence();
        wgmma_ss_n8<0, 1>(d0, mkd<HI64>(ad), mkd<8>(bd + ks * 4), 1);
        wgmma_ss_n8<0, 1>(d1, mkd<HI64>(ad + 1024), mkd<8>(bd + ks * 4), 1);
        wgmma_ss_n8<0, 1>(d2, mkd<HI64>(ad + 2048), mkd<8>(bd + ks * 4), 1);
        wg_commit();
      }
      wg_wait<0>(); keep(d0); keep(d1); keep(d2);
      FRESH();
      if ((lane & 3) == (wq >> 1)) {
        uint4* dst = &P.g->patch[bid][(wq & 1) * 32 + (lane >> 2) * 2 + (wq >> 1)];
        st_ll(dst, UI(d0[0]), UI(d1[0]), UI(d2[0]), tag + 1); st_ll(dst + 16, UI(d0[2]), UI(d1[2]), UI(d2[2]), tag + 1);
      }
      PROFX(tid == 0, 31);
    }
  }
  if (bid == 0 && tid == 0) P.g->epoch = lds32(sb + INFO2 + 16) + 1;
  #undef blk
  #undef bid
  #undef fid
  #undef bi
  #undef bp
  #undef bc
  #undef FRESH
  #undef lane
  #undef wq
}

__global__ void __cluster_dims__(2, 1, 1) __launch_bounds__(512, 1) fused_kernel(const __grid_constant__ Params P) {
  extern __shared__ __align__(1024) uint8_t smem_raw[];
  const uint32_t sb = smem_u32(smem_raw);
  PROFT(threadIdx.x == 0, 0);
  if (threadIdx.x < 32) { if (elect()) {
    for (int s = 0; s < 3; s++) mbar_init(BAR(B_FULLQ + s), 1);
    asm volatile("fence.mbarrier_init.release.cluster;" ::: "memory");
    #pragma unroll 1
    for (int s = 0; s < 3; s++) {
      mbar_expect_tx(BAR(B_FULLQ + s), 57344);
      tma_2d(sb + qa_off(s), &P.mX, s * 64, (BID >> 4) * 256, BAR(B_FULLQ + s));
      tma_3d(sb + qb_off(s), &P.mWq, (BID & 15) * 64, s * 64, 0, BAR(B_FULLQ + s));
    }
    if ((sb & 0x3FFFFu) != 1024) __trap();
  } } else if (threadIdx.x == 480) {
    asm volatile("prefetch.tensormap [%0];" :: "l"(&P.mWq) : "memory");
  } else if (threadIdx.x >= 32 && !(threadIdx.x & 28) && (threadIdx.x >> 3) + (threadIdx.x & 3) <= B_COUNT + 1) {
    int b = (threadIdx.x >> 3) + (threadIdx.x & 3) - 1;
    if (b == B_COUNT) b = B_ROW;
    const uint32_t cnt = b < B_XFREE ? (b == B_OFREE ? 1 : 2) : (b < B_KVRDY ? 3 : (b < B_KVFULL || b == B_PAR ? 4 : (b == B_PFREE ? 2 : 1)));
    mbar_init(BAR(b), cnt);
    asm volatile("fence.mbarrier_init.release.cluster;" ::: "memory");
  }
  __syncthreads();
  asm volatile("barrier.cluster.arrive.relaxed.aligned;" ::: "memory");
  const int wg = __shfl_sync(0xffffffffu, threadIdx.x >> 7, 0);
  if (wg < 2) { reg_inc<224>(); consumer(P, sb, wg); }
  else if (wg == 2) { reg_dec<40>(); aux(P, sb); }
  else {
    reg_dec<24>();
    asm volatile("barrier.cluster.wait.aligned;" ::: "memory");
    const int w = __shfl_sync(0xffffffffu, (threadIdx.x >> 5) & 3, 0);
    if (w == 0) loader(P, sb);
    else if (w < 3) storer(P, sb, w - 1);
    else if (elect()) stager(P, sb);
  }
}

typedef CUresult (*EncFn)(CUtensorMap*, CUtensorMapDataType, cuuint32_t, void*, const cuuint64_t*, const cuuint64_t*, const cuuint32_t*, const cuuint32_t*,
                          CUtensorMapInterleave, CUtensorMapSwizzle, CUtensorMapL2promotion, CUtensorMapFloatOOBfill);
static void mk_map(EncFn enc, CUtensorMap* m, const void* ptr, int rank, const cuuint64_t* dims, const cuuint64_t* strides, const cuuint32_t* box,
                   CUtensorMapSwizzle sw, CUtensorMapL2promotion pr) {
  cuuint32_t es[5] = {1, 1, 1, 1, 1};
  enc(m, CU_TENSOR_MAP_DATA_TYPE_BFLOAT16, rank, (void*)ptr, dims, strides, box, es, CU_TENSOR_MAP_INTERLEAVE_NONE, sw, pr, CU_TENSOR_MAP_FLOAT_OOB_FILL_NONE);
}
extern "C" void kernel_launch(void* const* d_in, const int* in_sizes, int n_in, void* d_out, int out_size) {
  (void)in_sizes; (void)n_in; (void)out_size;
  void* fn = nullptr; cudaDriverEntryPointQueryResult q;
  cudaGetDriverEntryPoint("cuTensorMapEncodeTiled", &fn, cudaEnableDefault, &q);
  EncFn enc = (EncFn)fn;
  cudaFuncSetAttribute(fused_kernel, cudaFuncAttributeMaxDynamicSharedMemorySize, SMEM_BYTES);
  Params P;
  const CUtensorMapSwizzle S128 = CU_TENSOR_MAP_SWIZZLE_128B, S64 = CU_TENSOR_MAP_SWIZZLE_64B, S0 = CU_TENSOR_MAP_SWIZZLE_NONE;
  const CUtensorMapL2promotion L256 = CU_TENSOR_MAP_L2_PROMOTION_L2_256B, L128 = CU_TENSOR_MAP_L2_PROMOTION_L2_128B;
  { cuuint64_t d[2] = {1024, 2048}, s[1] = {2048}; cuuint32_t b[2] = {64, 256}, bh[2] = {64, 128};
    mk_map(enc, &P.mX, d_in[0], 2, d, s, b, S128, L256); mk_map(enc, &P.mXh, d_in[0], 2, d, s, bh, S128, L256); }
  { cuuint64_t d[3] = {1024, 1024, 3}, s[2] = {6144, 2048}; cuuint32_t b[3] = {64, 64, 3}; mk_map(enc, &P.mWq, d_in[1], 3, d, s, b, S128, L256); }
  { cuuint64_t d[5] = {64, 32, 2, 16, 16}, s[4] = {2048, 65536, 131072, 128}; cuuint32_t b[5] = {64, 32, 1, 2, 2}; mk_map(enc, &P.mWo, d_in[2], 5, d, s, b, S128, L256); }
  { cuuint64_t d[2] = {3584, 1024}, s[1] = {7168}; cuuint32_t b[2] = {32, 128};
    mk_map(enc, &P.mWg, d_in[5], 2, d, s, b, S64, L128); mk_map(enc, &P.mWu, d_in[6], 2, d, s, b, S64, L128); }
  { cuuint64_t d[2] = {3072, 1024}, s[1] = {6144}; cuuint32_t b[2] = {32, 256}; mk_map(enc, &P.mWp, d_in[1], 2, d, s, b, S64, L128); }
  { cuuint64_t d[3] = {256, 3584, 4}, s[2] = {2048, 512}; cuuint32_t b[3] = {256, 8, 4}; mk_map(enc, &P.mWd, d_in[7], 3, d, s, b, S0, L128); }
  P.x0 = (const bf16*)d_in[0]; P.wqkv = (const bf16*)d_in[1]; P.wo = (const bf16*)d_in[2]; P.wr = (const bf16*)d_in[4]; P.wg = (const bf16*)d_in[5]; P.wu = (const bf16*)d_in[6]; P.wd = (const bf16*)d_in[7];
  P.out = (bf16*)d_out;
  cudaGetSymbolAddress((void**)&P.g, g_scr);
  for (int b = 0; b < 128; b++) {
    int j = b >> 1, quad = j < 4 ? 0 : (j < 36 ? 1 + (j - 4) % 8 : 9 + (j - 36) % 7), pos = j < 4 ? j : (j < 36 ? (j - 4) / 8 : (j - 36) / 7);
    int bid = ((quad >> 2) * 2 + (pos >> 1)) * 16 + ((quad & 3) * 2 + (pos & 1)) * 2 + (b & 1);
    int e = pos * 2 + (b & 1), fid = e < 7 ? quad * 7 + e : 112 + quad;
    P.map[b] = bid | fid << 8;
  }
  fused_kernel<<<128, 512, SMEM_BYTES>>>(P);
}
```

```cpp
#include <cuda_runtime.h>
#include <cuda_bf16.h>
#include <cuda.h>
#include <stdint.h>
#include <stddef.h>
typedef __nv_bfloat16 bf16;

template<int TB, int TA = 0> __device__ __forceinline__ void wgmma_ss_n192(float (&d)[96], uint64_t da, uint64_t db, int scale_d) {
  asm volatile("{\n.reg .pred p;\nsetp.ne.b32 p, %98, 0;\n"
    "wgmma.mma_async.sync.aligned.m64n192k16.f32.bf16.bf16 {%0, %1, %2, %3, %4, %5, %6, %7, %8, %9, %10, %11, %12, %13, %14, %15, %16, %17, %18, %19, %20, %21, %22, %23, %24, %25, %26, %27, %28, %29, %30, %31, %32, %33, %34, %35, %36, %37, %38, %39, %40, %41, %42, %43, %44, %45, %46, %47, %48, %49, %50, %51, %52, %53, %54, %55, %56, %57, %58, %59, %60, %61, %62, %63, %64, %65, %66, %67, %68, %69, %70, %71, %72, %73, %74, %75, %76, %77, %78, %79, %80, %81, %82, %83, %84, %85, %86, %87, %88, %89, %90, %91, %92, %93, %94, %95}, %96, %97, p, 1, 1, %100, %99;\n}\n"
    : "+f"(d[0]), "+f"(d[1]), "+f"(d[2]), "+f"(d[3]), "+f"(d[4]), "+f"(d[5]), "+f"(d[6]), "+f"(d[7]), "+f"(d[8]), "+f"(d[9]), "+f"(d[10]), "+f"(d[11]), "+f"(d[12]), "+f"(d[13]), "+f"(d[14]), "+f"(d[15]), "+f"(d[16]), "+f"(d[17]), "+f"(d[18]), "+f"(d[19]), "+f"(d[20]), "+f"(d[21]), "+f"(d[22]), "+f"(d[23]), "+f"(d[24]), "+f"(d[25]), "+f"(d[26]), "+f"(d[27]), "+f"(d[28]), "+f"(d[29]), "+f"(d[30]), "+f"(d[31]), "+f"(d[32]), "+f"(d[33]), "+f"(d[34]), "+f"(d[35]), "+f"(d[36]), "+f"(d[37]), "+f"(d[38]), "+f"(d[39]), "+f"(d[40]), "+f"(d[41]), "+f"(d[42]), "+f"(d[43]), "+f"(d[44]), "+f"(d[45]), "+f"(d[46]), "+f"(d[47]), "+f"(d[48]), "+f"(d[49]), "+f"(d[50]), "+f"(d[51]), "+f"(d[52]), "+f"(d[53]), "+f"(d[54]), "+f"(d[55]), "+f"(d[56]), "+f"(d[57]), "+f"(d[58]), "+f"(d[59]), "+f"(d[60]), "+f"(d[61]), "+f"(d[62]), "+f"(d[63]), "+f"(d[64]), "+f"(d[65]), "+f"(d[66]), "+f"(d[67]), "+f"(d[68]), "+f"(d[69]), "+f"(d[70]), "+f"(d[71]), "+f"(d[72]), "+f"(d[73]), "+f"(d[74]), "+f"(d[75]), "+f"(d[76]), "+f"(d[77]), "+f"(d[78]), "+f"(d[79]), "+f"(d[80]), "+f"(d[81]), "+f"(d[82]), "+f"(d[83]), "+f"(d[84]), "+f"(d[85]), "+f"(d[86]), "+f"(d[87]), "+f"(d[88]), "+f"(d[89]), "+f"(d[90]), "+f"(d[91]), "+f"(d[92]), "+f"(d[93]), "+f"(d[94]), "+f"(d[95])
    : "l"(da), "l"(db), "r"(scale_d), "n"(TB), "n"(TA));
}

template<int TB> __device__ __forceinline__ void wgmma_rs_n192(float (&d)[96], uint32_t a0, uint32_t a1, uint32_t a2, uint32_t a3, uint64_t db, int scale_d) {
  asm volatile("{\n.reg .pred p;\nsetp.ne.b32 p, %101, 0;\n"
    "wgmma.mma_async.sync.aligned.m64n192k16.f32.bf16.bf16 {%0, %1, %2, %3, %4, %5, %6, %7, %8, %9, %10, %11, %12, %13, %14, %15, %16, %17, %18, %19, %20, %21, %22, %23, %24, %25, %26, %27, %28, %29, %30, %31, %32, %33, %34, %35, %36, %37, %38, %39, %40, %41, %42, %43, %44, %45, %46, %47, %48, %49, %50, %51, %52, %53, %54, %55, %56, %57, %58, %59, %60, %61, %62, %63, %64, %65, %66, %67, %68, %69, %70, %71, %72, %73, %74, %75, %76, %77, %78, %79, %80, %81, %82, %83, %84, %85, %86, %87, %88, %89, %90, %91, %92, %93, %94, %95}, {%96, %97, %98, %99}, %100, p, 1, 1, %102;\n}\n"
    : "+f"(d[0]), "+f"(d[1]), "+f"(d[2]), "+f"(d[3]), "+f"(d[4]), "+f"(d[5]), "+f"(d[6]), "+f"(d[7]), "+f"(d[8]), "+f"(d[9]), "+f"(d[10]), "+f"(d[11]), "+f"(d[12]), "+f"(d[13]), "+f"(d[14]), "+f"(d[15]), "+f"(d[16]), "+f"(d[17]), "+f"(d[18]), "+f"(d[19]), "+f"(d[20]), "+f"(d[21]), "+f"(d[22]), "+f"(d[23]), "+f"(d[24]), "+f"(d[25]), "+f"(d[26]), "+f"(d[27]), "+f"(d[28]), "+f"(d[29]), "+f"(d[30]), "+f"(d[31]), "+f"(d[32]), "+f"(d[33]), "+f"(d[34]), "+f"(d[35]), "+f"(d[36]), "+f"(d[37]), "+f"(d[38]), "+f"(d[39]), "+f"(d[40]), "+f"(d[41]), "+f"(d[42]), "+f"(d[43]), "+f"(d[44]), "+f"(d[45]), "+f"(d[46]), "+f"(d[47]), "+f"(d[48]), "+f"(d[49]), "+f"(d[50]), "+f"(d[51]), "+f"(d[52]), "+f"(d[53]), "+f"(d[54]), "+f"(d[55]), "+f"(d[56]), "+f"(d[57]), "+f"(d[58]), "+f"(d[59]), "+f"(d[60]), "+f"(d[61]), "+f"(d[62]), "+f"(d[63]), "+f"(d[64]), "+f"(d[65]), "+f"(d[66]), "+f"(d[67]), "+f"(d[68]), "+f"(d[69]), "+f"(d[70]), "+f"(d[71]), "+f"(d[72]), "+f"(d[73]), "+f"(d[74]), "+f"(d[75]), "+f"(d[76]), "+f"(d[77]), "+f"(d[78]), "+f"(d[79]), "+f"(d[80]), "+f"(d[81]), "+f"(d[82]), "+f"(d[83]), "+f"(d[84]), "+f"(d[85]), "+f"(d[86]), "+f"(d[87]), "+f"(d[88]), "+f"(d[89]), "+f"(d[90]), "+f"(d[91]), "+f"(d[92]), "+f"(d[93]), "+f"(d[94]), "+f"(d[95])
    : "r"(a0), "r"(a1), "r"(a2), "r"(a3), "l"(db), "r"(scale_d), "n"(TB));
}

template<int TB, int TA = 0> __device__ __forceinline__ void wgmma_ss_n128(float (&d)[64], uint64_t da, uint64_t db, int scale_d) {
  asm volatile("{\n.reg .pred p;\nsetp.ne.b32 p, %66, 0;\n"
    "wgmma.mma_async.sync.aligned.m64n128k16.f32.bf16.bf16 {%0, %1, %2, %3, %4, %5, %6, %7, %8, %9, %10, %11, %12, %13, %14, %15, %16, %17, %18, %19, %20, %21, %22, %23, %24, %25, %26, %27, %28, %29, %30, %31, %32, %33, %34, %35, %36, %37, %38, %39, %40, %41, %42, %43, %44, %45, %46, %47, %48, %49, %50, %51, %52, %53, %54, %55, %56, %57, %58, %59, %60, %61, %62, %63}, %64, %65, p, 1, 1, %68, %67;\n}\n"
    : "+f"(d[0]), "+f"(d[1]), "+f"(d[2]), "+f"(d[3]), "+f"(d[4]), "+f"(d[5]), "+f"(d[6]), "+f"(d[7]), "+f"(d[8]), "+f"(d[9]), "+f"(d[10]), "+f"(d[11]), "+f"(d[12]), "+f"(d[13]), "+f"(d[14]), "+f"(d[15]), "+f"(d[16]), "+f"(d[17]), "+f"(d[18]), "+f"(d[19]), "+f"(d[20]), "+f"(d[21]), "+f"(d[22]), "+f"(d[23]), "+f"(d[24]), "+f"(d[25]), "+f"(d[26]), "+f"(d[27]), "+f"(d[28]), "+f"(d[29]), "+f"(d[30]), "+f"(d[31]), "+f"(d[32]), "+f"(d[33]), "+f"(d[34]), "+f"(d[35]), "+f"(d[36]), "+f"(d[37]), "+f"(d[38]), "+f"(d[39]), "+f"(d[40]), "+f"(d[41]), "+f"(d[42]), "+f"(d[43]), "+f"(d[44]), "+f"(d[45]), "+f"(d[46]), "+f"(d[47]), "+f"(d[48]), "+f"(d[49]), "+f"(d[50]), "+f"(d[51]), "+f"(d[52]), "+f"(d[53]), "+f"(d[54]), "+f"(d[55]), "+f"(d[56]), "+f"(d[57]), "+f"(d[58]), "+f"(d[59]), "+f"(d[60]), "+f"(d[61]), "+f"(d[62]), "+f"(d[63])
    : "l"(da), "l"(db), "r"(scale_d), "n"(TB), "n"(TA));
}

template<int TB, int TA = 0> __device__ __forceinline__ void wgmma_ss_n64(float (&d)[32], uint64_t da, uint64_t db, int scale_d) {
  asm volatile("{\n.reg .pred p;\nsetp.ne.b32 p, %34, 0;\n"
    "wgmma.mma_async.sync.aligned.m64n64k16.f32.bf16.bf16 {%0, %1, %2, %3, %4, %5, %6, %7, %8, %9, %10, %11, %12, %13, %14, %15, %16, %17, %18, %19, %20, %21, %22, %23, %24, %25, %26, %27, %28, %29, %30, %31}, %32, %33, p, 1, 1, %36, %35;\n}\n"
    : "+f"(d[0]), "+f"(d[1]), "+f"(d[2]), "+f"(d[3]), "+f"(d[4]), "+f"(d[5]), "+f"(d[6]), "+f"(d[7]), "+f"(d[8]), "+f"(d[9]), "+f"(d[10]), "+f"(d[11]), "+f"(d[12]), "+f"(d[13]), "+f"(d[14]), "+f"(d[15]), "+f"(d[16]), "+f"(d[17]), "+f"(d[18]), "+f"(d[19]), "+f"(d[20]), "+f"(d[21]), "+f"(d[22]), "+f"(d[23]), "+f"(d[24]), "+f"(d[25]), "+f"(d[26]), "+f"(d[27]), "+f"(d[28]), "+f"(d[29]), "+f"(d[30]), "+f"(d[31])
    : "l"(da), "l"(db), "r"(scale_d), "n"(TB), "n"(TA));
}

template<int TB, int TA = 0> __device__ __forceinline__ void wgmma_ss_n8(float (&d)[4], uint64_t da, uint64_t db, int scale_d) {
  asm volatile("{\n.reg .pred p;\nsetp.ne.b32 p, %6, 0;\n"
    "wgmma.mma_async.sync.aligned.m64n8k16.f32.bf16.bf16 {%0, %1, %2, %3}, %4, %5, p, 1, 1, %8, %7;\n}\n"
    : "+f"(d[0]), "+f"(d[1]), "+f"(d[2]), "+f"(d[3])
    : "l"(da), "l"(db), "r"(scale_d), "n"(TB), "n"(TA));
}

template<int TB> __device__ __forceinline__ void wgmma_rs_n40(float (&d)[20], uint32_t a0, uint32_t a1, uint32_t a2, uint32_t a3, uint64_t db, int scale_d) {
  asm volatile("{\n.reg .pred p;\nsetp.ne.b32 p, %25, 0;\n"
    "wgmma.mma_async.sync.aligned.m64n40k16.f32.bf16.bf16 {%0, %1, %2, %3, %4, %5, %6, %7, %8, %9, %10, %11, %12, %13, %14, %15, %16, %17, %18, %19}, {%20, %21, %22, %23}, %24, p, 1, 1, %26;\n}\n"
    : "+f"(d[0]), "+f"(d[1]), "+f"(d[2]), "+f"(d[3]), "+f"(d[4]), "+f"(d[5]), "+f"(d[6]), "+f"(d[7]), "+f"(d[8]), "+f"(d[9]), "+f"(d[10]), "+f"(d[11]), "+f"(d[12]), "+f"(d[13]), "+f"(d[14]), "+f"(d[15]), "+f"(d[16]), "+f"(d[17]), "+f"(d[18]), "+f"(d[19])
    : "r"(a0), "r"(a1), "r"(a2), "r"(a3), "l"(db), "r"(scale_d), "n"(TB));
}

#define DEVI __device__ __forceinline__
DEVI uint32_t smem_u32(const void* p) { return (uint32_t)__cvta_generic_to_shared(p); }
DEVI void mbar_init(uint32_t bar, uint32_t cnt) { asm volatile("mbarrier.init.shared::cta.b64 [%0], %1;" :: "r"(bar), "r"(cnt)); }
DEVI void mbar_expect_tx(uint32_t bar, uint32_t bytes) { asm volatile("mbarrier.arrive.expect_tx.shared::cta.b64 _, [%0], %1;" :: "r"(bar), "r"(bytes) : "memory"); }
DEVI void mbar_arrive(uint32_t bar) { asm volatile("mbarrier.arrive.shared::cta.b64 _, [%0];" :: "r"(bar) : "memory"); }
DEVI void mbar_arrive_peer(uint32_t bar) {
  asm volatile("{\n.reg .b32 ra;\nmapa.shared::cluster.u32 ra, %0, %1;\nmbarrier.arrive.shared::cluster.b64 _, [ra];\n}" :: "r"(bar), "r"((blockIdx.x & 1) ^ 1) : "memory");
}
DEVI void bulk_s2peer(uint32_t a, uint32_t bytes, uint32_t bar) {
  asm volatile("{\n.reg .b32 ra, rb;\nmapa.shared::cluster.u32 ra, %0, %3;\nmapa.shared::cluster.u32 rb, %2, %3;\n"
               "cp.async.bulk.shared::cluster.shared::cta.mbarrier::complete_tx::bytes [ra], [%0], %1, [rb];\n}"
               :: "r"(a), "r"(bytes), "r"(bar), "r"((blockIdx.x & 1) ^ 1) : "memory");
}
DEVI void mbar_wait(uint32_t bar, uint32_t parity) {
  asm volatile("{\n.reg .pred p;\nLW:\nmbarrier.try_wait.parity.shared::cta.b64 p, [%0], %1;\n@!p bra LW;\n}" :: "r"(bar), "r"(parity) : "memory");
}
DEVI uint32_t mbar_test(uint32_t bar, uint32_t parity) {
  uint32_t r; asm volatile("{\n.reg .pred p;\nmbarrier.test_wait.parity.shared::cta.b64 p, [%1], %2;\nselp.u32 %0, 1, 0, p;\n}" : "=r"(r) : "r"(bar), "r"(parity) : "memory"); return r;
}
DEVI void mbar_wait_b(uint32_t bar, uint32_t parity) {
  asm volatile("{\n.reg .pred p;\n.reg .u32 it;\nmov.u32 it, 0;\nLW:\nmbarrier.try_wait.parity.shared::cta.b64 p, [%0], %1;\n@p bra LD;\n"
               "add.u32 it, it, 1;\nsetp.lt.u32 p, it, 0x1000000;\n@p bra LW;\ntrap;\nLD:\n}" :: "r"(bar), "r"(parity) : "memory");
}
DEVI void tma_2d(uint32_t dst, const CUtensorMap* m, int c0, int c1, uint32_t bar) {
  asm volatile("cp.async.bulk.tensor.2d.shared::cluster.global.mbarrier::complete_tx::bytes [%0], [%1, {%3, %4}], [%2];"
    :: "r"(dst), "l"(m), "r"(bar), "r"(c0), "r"(c1) : "memory");
}
DEVI void tma_3d(uint32_t dst, const CUtensorMap* m, int c0, int c1, int c2, uint32_t bar) {
  asm volatile("cp.async.bulk.tensor.3d.shared::cluster.global.mbarrier::complete_tx::bytes [%0], [%1, {%3, %4, %5}], [%2];"
    :: "r"(dst), "l"(m), "r"(bar), "r"(c0), "r"(c1), "r"(c2) : "memory");
}
#define POL_EF POL_FIRST
constexpr uint64_t POL_FIRST = 0x12F0000000000000ull, POL_NORMAL = 0x1000000000000000ull;
DEVI void tma_2d_h(uint32_t dst, const CUtensorMap* m, int c0, int c1, uint32_t bar, uint64_t pol) {
  asm volatile("cp.async.bulk.tensor.2d.shared::cluster.global.mbarrier::complete_tx::bytes.L2::cache_hint [%0], [%1, {%3, %4}], [%2], %5;"
    :: "r"(dst), "l"(m), "r"(bar), "r"(c0), "r"(c1), "l"(pol) : "memory");
}
DEVI void tma_3d_h(uint32_t dst, const CUtensorMap* m, int c0, int c1, int c2, uint32_t bar, uint64_t pol) {
  asm volatile("cp.async.bulk.tensor.3d.shared::cluster.global.mbarrier::complete_tx::bytes.L2::cache_hint [%0], [%1, {%3, %4, %5}], [%2], %6;"
    :: "r"(dst), "l"(m), "r"(bar), "r"(c0), "r"(c1), "r"(c2), "l"(pol) : "memory");
}
DEVI void bulk_g2s_h(uint32_t s, const void* g, uint32_t bytes, uint32_t bar, uint64_t pol = POL_EF) {
  asm volatile("cp.async.bulk.shared::cluster.global.mbarrier::complete_tx::bytes.L2::cache_hint [%0], [%1], %2, [%3], %4;"
    :: "r"(s), "l"(g), "r"(bytes), "r"(bar), "l"(pol) : "memory");
}
DEVI void tma_5d(uint32_t dst, const CUtensorMap* m, int c0, int c1, int c2, int c3, int c4, uint32_t bar, uint64_t pol) {
  asm volatile("cp.async.bulk.tensor.5d.shared::cluster.global.mbarrier::complete_tx::bytes.L2::cache_hint [%0], [%1, {%3, %4, %5, %6, %7}], [%2], %8;"
    :: "r"(dst), "l"(m), "r"(bar), "r"(c0), "r"(c1), "r"(c2), "r"(c3), "r"(c4), "l"(pol) : "memory");
}
DEVI void tma_prefetch_2d(const CUtensorMap* m, int c0, int c1) {
  asm volatile("cp.async.bulk.prefetch.tensor.2d.L2.global.tile [%0, {%1, %2}];" :: "l"(m), "r"(c0), "r"(c1) : "memory");
}
DEVI void tma_prefetch_3d(const CUtensorMap* m, int c0, int c1, int c2) {
  asm volatile("cp.async.bulk.prefetch.tensor.3d.L2.global.tile [%0, {%1, %2, %3}];" :: "l"(m), "r"(c0), "r"(c1), "r"(c2) : "memory");
}
DEVI void bulk_prefetch(const void* g, uint32_t bytes) { asm volatile("cp.async.bulk.prefetch.L2.global [%0], %1;" :: "l"(g), "r"(bytes) : "memory"); }
DEVI void bulk_g2s(uint32_t s, const void* g, uint32_t bytes, uint32_t bar) {
  asm volatile("cp.async.bulk.shared::cluster.global.mbarrier::complete_tx::bytes [%0], [%1], %2, [%3];" :: "r"(s), "l"(g), "r"(bytes), "r"(bar) : "memory");
}
DEVI void bulk_s2g(void* g, uint32_t s, uint32_t bytes, uint64_t pol = POL_NORMAL) {
  asm volatile("cp.async.bulk.global.shared::cta.bulk_group.L2::cache_hint [%0], [%1], %2, %3;\ncp.async.bulk.commit_group;" :: "l"(g), "r"(s), "r"(bytes), "l"(pol) : "memory");
}
template<int N> DEVI void bulk_wait() { asm volatile("cp.async.bulk.wait_group %0;" :: "n"(N) : "memory"); }
DEVI void fence_async_smem() { asm volatile("fence.proxy.async.shared::cta;" ::: "memory"); }
DEVI void fence_async_glob() { asm volatile("fence.proxy.async.global;" ::: "memory"); }
DEVI unsigned ld_rlx(const unsigned* p) { unsigned v; asm volatile("ld.relaxed.gpu.global.u32 %0, [%1];" : "=r"(v) : "l"(p) : "memory"); return v; }
DEVI void st_rlx(unsigned* p, unsigned v) { asm volatile("st.relaxed.gpu.global.u32 [%0], %1;" :: "l"(p), "r"(v) : "memory"); }
DEVI uint2 ldg_stream(const uint2* p) { uint2 v; asm volatile("ld.global.nc.L1::no_allocate.v2.u32 {%0, %1}, [%2];" : "=r"(v.x), "=r"(v.y) : "l"(p)); return v; }
DEVI void fence_rel() { asm volatile("fence.release.gpu;" ::: "memory"); }
DEVI uint4 ld_ll(const uint4* p) {
  uint4 v;
  asm volatile("{\n.reg .b128 t;\n.reg .b64 a, b;\nld.relaxed.gpu.global.b128 t, [%4];\nmov.b128 {a, b}, t;\nmov.b64 {%0, %1}, a;\nmov.b64 {%2, %3}, b;\n}"
               : "=r"(v.x), "=r"(v.y), "=r"(v.z), "=r"(v.w) : "l"(p) : "memory");
  return v;
}
DEVI void st_ll(uint4* p, uint32_t x, uint32_t y, uint32_t z, uint32_t w) {
  asm volatile("{\n.reg .b128 t;\n.reg .b64 a, b;\nmov.b64 a, {%1, %2};\nmov.b64 b, {%3, %4};\nmov.b128 t, {a, b};\nst.relaxed.gpu.global.b128 [%0], t;\n}"
               :: "l"(p), "r"(x), "r"(y), "r"(z), "r"(w) : "memory");
}
#define SPIN_MAX 0x1000000
DEVI uint4 poll_ll(const uint4* p, uint32_t mask, uint32_t tag) {
  uint4 v; int it = 0;
  do { v = ld_ll(p); if (++it > SPIN_MAX) __trap(); } while (!__all_sync(0xffffffffu, (v.w & mask) == tag));
  return v;
}
DEVI void poll_ll2(const uint4* p, const uint4* q, uint32_t mask, uint32_t tag, uint4& a, uint4& b) {
  int it = 0;
  do { a = ld_ll(p); b = ld_ll(q); if (++it > SPIN_MAX) __trap(); } while (!__all_sync(0xffffffffu, (a.w & mask) == tag && (b.w & mask) == tag));
}
DEVI float4 poll_sum4(const uint4* src, int stride, uint32_t tag) {
  uint4 v0, v1, v2, v3; int it = 0;
  do { v0 = ld_ll(src); v1 = ld_ll(src + stride); v2 = ld_ll(src + 2 * stride); v3 = ld_ll(src + 3 * stride); if (++it > SPIN_MAX) __trap(); }
  while (!__all_sync(0xffffffffu, v0.w == tag && v1.w == tag && v2.w == tag && v3.w == tag));
  #define S4(f) ((__uint_as_float(v0.f) + __uint_as_float(v1.f)) + (__uint_as_float(v2.f) + __uint_as_float(v3.f)))
  return make_float4(S4(x), S4(y), S4(z), 0.f);
  #undef S4
}
DEVI void bar_sync(int id, int n) { asm volatile("bar.sync %0, %1;" :: "r"(id), "r"(n) : "memory"); }
DEVI void bar_arrive(int id, int n) { asm volatile("bar.arrive %0, %1;" :: "r"(id), "r"(n) : "memory"); }
DEVI void wg_fence() { asm volatile("wgmma.fence.sync.aligned;" ::: "memory"); }
DEVI void wg_commit() { asm volatile("wgmma.commit_group.sync.aligned;" ::: "memory"); }
template<int N> DEVI void wg_wait() { asm volatile("wgmma.wait_group.sync.aligned %0;" :: "n"(N) : "memory"); }
template<int N> DEVI void reg_inc() { asm volatile("setmaxnreg.inc.sync.aligned.u32 %0;" :: "n"(N)); }
template<int N> DEVI void reg_dec() { asm volatile("setmaxnreg.dec.sync.aligned.u32 %0;" :: "n"(N)); }
DEVI float ex2f(float x) { float y; asm("ex2.approx.ftz.f32 %0, %1;" : "=f"(y) : "f"(x)); return y; }
DEVI uint32_t pack_bf16(float lo, float hi) { uint32_t r; asm("cvt.rn.bf16x2.f32 %0, %1, %2;" : "=r"(r) : "f"(hi), "f"(lo)); return r; }
DEVI float bf_lo(uint32_t v) { return __uint_as_float(v << 16); }
DEVI float bf_hi(uint32_t v) { return __uint_as_float(v & 0xffff0000u); }
DEVI float bf_round(float x) { return bf_lo(pack_bf16(x, 0.f)); }
DEVI void stsm_x4(uint32_t addr, uint32_t a, uint32_t b, uint32_t c, uint32_t d) {
  asm volatile("stmatrix.sync.aligned.m8n8.x4.shared.b16 [%0], {%1,%2,%3,%4};" :: "r"(addr), "r"(a), "r"(b), "r"(c), "r"(d) : "memory");
}
DEVI void ldsm_x4(uint32_t addr, uint32_t& a, uint32_t& b, uint32_t& c, uint32_t& d) {
  asm volatile("ldmatrix.sync.aligned.m8n8.x4.shared.b16 {%0,%1,%2,%3}, [%4];" : "=r"(a), "=r"(b), "=r"(c), "=r"(d) : "r"(addr) : "memory");
}
DEVI uint4 lds128(uint32_t a) { uint4 v; asm volatile("ld.shared.v4.u32 {%0,%1,%2,%3}, [%4];" : "=r"(v.x), "=r"(v.y), "=r"(v.z), "=r"(v.w) : "r"(a) : "memory"); return v; }
DEVI void sts128(uint32_t a, uint4 v) { asm volatile("st.shared.v4.u32 [%0], {%1,%2,%3,%4};" :: "r"(a), "r"(v.x), "r"(v.y), "r"(v.z), "r"(v.w) : "memory"); }
DEVI float2 lds64f(uint32_t a) { float2 v; asm volatile("ld.shared.v2.f32 {%0,%1}, [%2];" : "=f"(v.x), "=f"(v.y) : "r"(a) : "memory"); return v; }
DEVI void sts64f(uint32_t a, float x, float y) { asm volatile("st.shared.v2.f32 [%0], {%1,%2};" :: "r"(a), "f"(x), "f"(y) : "memory"); }
DEVI uint32_t lds32(uint32_t a) { uint32_t v; asm volatile("ld.shared.u32 %0, [%1];" : "=r"(v) : "r"(a) : "memory"); return v; }
DEVI uint32_t lds16(uint32_t a) { unsigned short v; asm volatile("ld.shared.u16 %0, [%1];" : "=h"(v) : "r"(a) : "memory"); return v; }
DEVI float lds32f(uint32_t a) { return __uint_as_float(lds32(a)); }
DEVI void sts32(uint32_t a, uint32_t v) { asm volatile("st.shared.u32 [%0], %1;" :: "r"(a), "r"(v) : "memory"); }
DEVI void sts32f(uint32_t a, float v) { sts32(a, __float_as_uint(v)); }
DEVI void sts16(uint32_t a, uint32_t v) { asm volatile("st.shared.u16 [%0], %1;" :: "r"(a), "h"((unsigned short)v) : "memory"); }
template<int N> DEVI void keep(float (&d)[N]) {
  #pragma unroll
  for (int i = 0; i < N; i++) asm volatile("" : "+f"(d[i]) :: "memory");
}
template<int N> DEVI void keep(uint32_t (&d)[N]) {
  #pragma unroll
  for (int i = 0; i < N; i++) asm volatile("" : "+r"(d[i]) :: "memory");
}
template<uint32_t HI> DEVI uint64_t mkd(uint32_t lo) { uint64_t r; asm("mov.b64 %0, {%1, %2};" : "=l"(r) : "r"(lo), "n"(HI)); return r; }
constexpr uint32_t HI128 = (1u << 30) | (1024 >> 4), HI64 = (2u << 30) | (512 >> 4);
#define VOFF(x) ((uint32_t)(x) * (uint32_t)(1 - 65536))
DEVI bool elect() { uint32_t p; asm volatile("{\n.reg .pred q;\nelect.sync _|q, 0xffffffff;\nselp.u32 %0, 1, 0, q;\n}" : "=r"(p)); return p; }
DEVI void warp_signal(uint32_t bar) { __syncwarp(); if (elect()) mbar_arrive(bar); }

struct Scratch {
  uint4 statP[8][2048];
  uint4 statF[2048];
  uint4 csP[16][8][96];
  uint4 best[8][16];
  uint4 row[16][256];
  uint4 yP[128][112][2];
  uint4 x2[8][256];
  uint4 patch[128][64];
  unsigned flagKV[128][32];
  unsigned flagO[8][32];
  unsigned flagX[8][32];
  unsigned epoch, pad[255];
  uint4 kv[128][4][1024];
  uint4 o[8][2][8][2][1024];
  uint4 x[8][16][2048];
  uint4 zero[1024];
};
static_assert(offsetof(Scratch, kv) % 1024 == 0, "");
__device__ __align__(1024) Scratch g_scr;
#define PROFT(cond, slot)
#define PROFW(cond, slot)
#define PROFD(cond, slot)
#define PROFX(cond, slot)
#define PROFY(cond, slot)

constexpr uint32_t SB0 = 65536, HOLE = 90112, SA2 = 98304, SB1 = 131072, SB2 = 155648, STG = 180224;
constexpr uint32_t KVA = 0, KVB = 98304, QO = 65536;
constexpr uint32_t MISC = 229376, CS = MISC, ONES = MISC + 768, BARS = MISC + 1792, INFO = MISC + 2208, WR = MISC + 2224, X2SEG = MISC + 2736, INFO2 = MISC + 2992, DUMP = MISC + 3040;
constexpr uint32_t PAR = HOLE, HV = HOLE + 2048, RED = HOLE + 6144, PATCH = 196608;
constexpr uint32_t SMEM_BYTES = 232448;
enum { B_FULLQ = 0, B_EMPTYQ = 3, B_FULLW = 6, B_EMPTYW = 12, B_HAFREE = 18, B_OFREE = 20,
       B_XFREE = 21,
       B_KVRDY = 23, B_ORDY = 27, B_XRDY = 35, B_STGE = 39,
       B_KVFULL = 42, B_RES = 46, B_PAR = 47, B_STG = 48, B_PFREE = 51, B_COUNT = 52,
       B_ROW = 154 };
#define BAR(x) (sb + BARS + 8 * (x))
DEVI uint32_t qa_off(int s) { return s == 2 ? SA2 : (uint32_t)s * 32768u; }
DEVI uint32_t qb_off(int s) { return s == 0 ? SB0 : (s == 1 ? SB1 : SB2); }
DEVI int kb_order(int bc, int n) {
  const int e = n < 9 ? n - 2 : n - 9;
  return n < 2 ? 2 * bc + n : 2 * (((e < 4 ? e + 4 : e - 4 + (e - 4 >= (bc & 3))) + (bc & 4)) & 7) + (n >= 9);
}
DEVI int wo_order(int bc, int n) { return (n & 8) | ((n + (bc & 6)) & 7); }
DEVI uint32_t w_off(int s) { return (uint32_t)((0x143065 >> (4 * s)) & 7) * 32768u; }
DEVI uint32_t w_par(int n, int s, int L) { return (n >= 6 && n < 12) ^ (s == 5) ^ (s != 2 && L); }
DEVI uint32_t w_aoff(int n, int s) { return n == 3 ? QO : w_off(s); }
DEVI int w_next(int n, int s) { return s == 5 ? 0 : (n == 13 ? 3 : s + 1); }

struct Params {
  CUtensorMap mX, mXh, mWq, mWo, mWg, mWu, mWp, mWd;
  const bf16 *x0, *wqkv, *wo, *wr, *wg, *wu, *wd;
  bf16* out;
  Scratch* g;
  unsigned map[128];
};
#define BID ((int)(P.map[blockIdx.x] & 255))
#define FID ((int)(P.map[blockIdx.x] >> 8))
DEVI uint32_t uni(uint32_t v) { return __shfl_sync(0xffffffffu, v, 0); }
#define PQ_N 8
#define PQ_T 700
#define PF0_N 10
#define PF0_T 1600
#define PF1_E 24
#define PF1_T 1100
#define POL_Q1 POL_NORMAL
#define POL_X POL_NORMAL
#define PFA0_BAR 3
#define PFA1_BAR 0
#define PFA0_M 0
#define PFA1_M 0
#define PFA0_T 900
#define PFA1_T 700
#define PF1_S PF0_N
#define PF1_D 0
#define POL_G POL_NORMAL
#define POL_U POL_FIRST
#define POL_D POL_FIRST
#define JQ_N 6
#define WDSRC (P.wd + (size_t)min(fid, 111) * 32768)
#define WDSRC2 (P.wd + FID * 32768)
#define WD_N 4
#define THR_N 5
#define KV_D 1800
#define XD_D 300
#define W0_BAR 3
#define QEF_N 99
#define PACE_T 300
#define IDLE_T 11000
#define LATE_C 99
#define LATE_B B_XFREE + 1
#define LATE_P 0
#define KV_D1 200
#define KV_D2 1200
#define KV_DL 0
#define POL_KV0 POL_FIRST
#define POL_KV1 POL_FIRST
#define POL_O0 POL_FIRST
#define POL_O1 POL_FIRST
#define POL_W0 POL_NORMAL
#define POL_W1 POL_FIRST
#define POL_T POL_FIRST
#define U_C 8
#define ST_M 0
#define POL_Q0 POL_NORMAL
constexpr float LN_EPS = 1e-5f;
constexpr float QSCALE = 0.17677669529663687f * 1.4426950408889634f;

DEVI void fma8(float (&a)[8], uint4 v, float h) {
  a[0] = fmaf(bf_lo(v.x), h, a[0]); a[1] = fmaf(bf_hi(v.x), h, a[1]); a[2] = fmaf(bf_lo(v.y), h, a[2]); a[3] = fmaf(bf_hi(v.y), h, a[3]);
  a[4] = fmaf(bf_lo(v.z), h, a[4]); a[5] = fmaf(bf_hi(v.z), h, a[5]); a[6] = fmaf(bf_lo(v.w), h, a[6]); a[7] = fmaf(bf_hi(v.w), h, a[7]);
}
DEVI uint4 ldsv128(uint32_t a) { uint4 v; asm volatile("ld.volatile.shared.v4.u32 {%0,%1,%2,%3}, [%4];" : "=r"(v.x), "=r"(v.y), "=r"(v.z), "=r"(v.w) : "r"(a) : "memory"); return v; }
DEVI float ldsv32f(uint32_t a) { float v; asm volatile("ld.volatile.shared.f32 %0, [%1];" : "=f"(v) : "r"(a) : "memory"); return v; }
DEVI uint32_t clk() { uint32_t t; asm volatile("mov.u32 %0, %%clock;" : "=r"(t)); return t; }
DEVI int fresh_tid() { int t; asm volatile("mov.u32 %0, %%tid.x;" : "=r"(t)); return t & 127; }
DEVI float fold8(const float (&a)[8]) {
  const int lane = threadIdx.x & 31;
  const bool u = lane & 16, v = lane & 8, x = lane & 4;
  float b0 = (u ? a[4] : a[0]) + __shfl_xor_sync(0xffffffffu, u ? a[0] : a[4], 16), b1 = (u ? a[5] : a[1]) + __shfl_xor_sync(0xffffffffu, u ? a[1] : a[5], 16);
  float b2 = (u ? a[6] : a[2]) + __shfl_xor_sync(0xffffffffu, u ? a[2] : a[6], 16), b3 = (u ? a[7] : a[3]) + __shfl_xor_sync(0xffffffffu, u ? a[3] : a[7], 16);
  float c0 = (v ? b2 : b0) + __shfl_xor_sync(0xffffffffu, v ? b0 : b2, 8), c1 = (v ? b3 : b1) + __shfl_xor_sync(0xffffffffu, v ? b1 : b3, 8);
  return (x ? c1 : c0) + __shfl_xor_sync(0xffffffffu, x ? c0 : c1, 4);
}
DEVI float sigmoidf(float x) { return __fdividef(1.f, 1.f + ex2f(-1.4426950408889634f * x)); }
DEVI float swiglu(float g, float u) { return g * u * sigmoidf(g); }

template<int J0, int J1> DEVI void exp_pack(const float (&s)[32], uint32_t (&p)[16]) {
  #pragma unroll
  for (int j = J0; j < J1; j++) p[j] = pack_bf16(ex2f(s[2 * j]), ex2f(s[2 * j + 1]));
}
DEVI bool attn_pack(const float (&o)[20], uint32_t (&ob)[8]) {
  const float lo = 5.421010862427522e-20f, hi = 1.8446744073709552e19f;
  float i0, i1; asm("rcp.approx.ftz.f32 %0, %1;" : "=f"(i0) : "f"(o[16])); asm("rcp.approx.ftz.f32 %0, %1;" : "=f"(i1) : "f"(o[18]));
  #pragma unroll
  for (int e = 0; e < 8; e++) ob[e] = pack_bf16(o[2 * e] * ((e & 1) ? i1 : i0), o[2 * e + 1] * ((e & 1) ? i1 : i0));
  return __all_sync(0xffffffffu, o[16] >= lo && o[16] <= hi && o[18] >= lo && o[18] <= hi);
}
DEVI void attn_store(const uint32_t (&ob)[8], bool ok, uint32_t st, uint32_t sb, uint32_t bar) {
  stsm_x4(ok ? st : sb + DUMP, ob[0], ob[1], ob[2], ob[3]); stsm_x4(ok ? st ^ 32 : sb + DUMP, ob[4], ob[5], ob[6], ob[7]);
  __syncwarp();
  asm volatile("{\n.reg .pred p, q;\nelect.sync _|q, 0xffffffff;\nsetp.ne.and.u32 p, %1, 0, q;\n@p mbarrier.arrive.shared::cta.b64 _, [%0];\n}" :: "r"(bar), "r"((uint32_t)ok) : "memory");
}
DEVI void attn_exact(uint32_t st, uint32_t kv, int t, bool hasprev, uint32_t bar) {
  const int lane = threadIdx.x & 31;
  #pragma unroll 1
  for (int row = ((threadIdx.x >> 5) & 3) * 16, n = 0; n < 16; n++, row++) {
    const int k1 = 256 + t * 64 + row;
    float m = -INFINITY, l = 0.f, o = 0.f;
    #pragma unroll 1
    for (int k0 = hasprev ? k1 - 255 : 256; k0 <= k1; k0 += 32) {
      const int k = min(k0 + lane, k1), r = k & 63;
      float sc = 0.f;
      #pragma unroll 1
      for (int c = 0; c < 16; c++) {
        uint32_t a = lds32(st + row * 64 + ((c * 4) ^ ((row & 6) << 3))), b = lds32(kv + (k >> 6) * 8192 + r * 64 + ((c * 4) ^ ((r & 6) << 3)));
        sc = fmaf(bf_lo(a), bf_lo(b), fmaf(bf_hi(a), bf_hi(b), sc));
      }
      float mn = fmaxf(m, sc);
      #pragma unroll 1
      for (int x = 16; x; x >>= 1) mn = fmaxf(mn, __shfl_xor_sync(0xffffffffu, mn, x));
      const float al = ex2f(m - mn), pr = ex2f(sc - mn);
      m = mn; l *= al; o *= al;
      #pragma unroll 1
      for (int q = k0; q <= min(k0 + 31, k1); q++) {
        const float z = __shfl_sync(0xffffffffu, pr, q - k0);
        uint32_t b = lds32(kv + (q >> 6) * 8192 + 4096 + (q & 63) * 64 + (((lane >> 1) * 4) ^ ((q & 6) << 3)));
        l += z; o = fmaf(z, (lane & 1) ? bf_hi(b) : bf_lo(b), o);
      }
    }
    __syncwarp();
    sts16(st + row * 64 + ((lane * 2) ^ ((row & 6) << 3)), pack_bf16(__fdividef(o, l), 0.f));
  }
  warp_signal(bar);
}

template<int K0, int K1, int DONE = 0> DEVI void exp_pv(const float (&s)[32], uint32_t (&p)[16], float (&o)[20], uint32_t vd, bool accum) {
  #pragma unroll
  for (int ks = K0; ks < K1; ks++) {
    if (ks >= DONE) {
      #pragma unroll
      for (int j = 4 * ks; j < 4 * ks + 4; j++) p[j] = pack_bf16(ex2f(s[2 * j]), ex2f(s[2 * j + 1]));
    }
    asm volatile("" : "+r"(p[4 * ks]), "+r"(p[4 * ks + 1]), "+r"(p[4 * ks + 2]), "+r"(p[4 * ks + 3]));
    wg_fence();
    wgmma_rs_n40<1>(o, p[ks * 4], p[ks * 4 + 1], p[ks * 4 + 2], p[ks * 4 + 3], mkd<HI64>(vd + VOFF(ks * 64)), ks ? 1 : accum);
  }
}
template<int K0, int K1> DEVI void exp_pv2(const float (&s)[32], const float (&sx)[32], uint32_t (&p)[16], uint32_t (&px)[16], float (&o)[20], uint32_t v0, uint32_t v4,
                  const uint32_t (&msk)[9], int tdiag) {
  #pragma unroll
  for (int ks = K0; ks < K1; ks++) {
    #pragma unroll
    for (int j = 4 * ks; j < 4 * ks + 4; j++) {
      const int c = 8 * (j >> 1) - 8 * (j & 1);
      const uint32_t e = pack_bf16(ex2f(c > tdiag ? s[2 * j] : sx[2 * j]), ex2f(c + 1 > tdiag ? s[2 * j + 1] : sx[2 * j + 1])), m = msk[(j >> 1) - (j & 1) + 1];
      p[j] = e & m; px[j] = e & ~m;
      asm volatile("" : "+r"(p[j]), "+r"(px[j]));
    }
    wg_fence();
    wgmma_rs_n40<1>(o, p[ks * 4], p[ks * 4 + 1], p[ks * 4 + 2], p[ks * 4 + 3], mkd<HI64>(v0 + VOFF(ks * 64)), 1);
    wgmma_rs_n40<1>(o, px[ks * 4], px[ks * 4 + 1], px[ks * 4 + 2], px[ks * 4 + 3], mkd<HI64>(v4 + VOFF(ks * 64)), 1);
  }
}

template<int J0> DEVI void qkv_store(const float (&a)[96], float p0, float p1, uint32_t d) {
  #pragma unroll
  for (int hh = 0; hh < 2; hh++) {
    const int j = 4 * (J0 + 2 * hh);
    stsm_x4(d ^ (hh << 5), pack_bf16(a[j] * p0, a[j + 1] * p0), pack_bf16(a[j + 2] * p1, a[j + 3] * p1),
                           pack_bf16(a[j + 4] * p0, a[j + 5] * p0), pack_bf16(a[j + 6] * p1, a[j + 7] * p1));
  }
}
DEVI void mean_step(float (&a)[96], float m0, float m1, uint32_t cd, bool z) {
  const uint32_t u0 = z ? 0u : __float_as_uint(m0), u1 = z ? 0u : __float_as_uint(m1);
  uint32_t ma[4] = {__byte_perm(u0, 0u, 0x1010), __byte_perm(u1, 0u, 0x1010), __byte_perm(u0, 0u, 0x3232), __byte_perm(u1, 0u, 0x3232)};
  keep(ma);
  wg_fence();
  wgmma_rs_n192<1>(a, ma[0], ma[1], ma[2], ma[3], mkd<2>(cd), 1);
  wg_commit();
}

template<bool FIRST> DEVI void qkv_block(float (&aX)[96], float (&aY)[96], uint32_t sb16, int s, int tX, int tY) {
  uint32_t a16 = sb16 + (qa_off(s) >> 4), b16 = (sb16 + (qb_off(s) >> 4)) | ((8192u >> 4) << 16);
  uint32_t ax = (a16 + tX * 512) | 0x10000u, ay = (a16 + tY * 512) | 0x10000u;
  wg_fence();
  #pragma unroll
  for (int ks = 0; ks < 4; ks++) {
    wgmma_ss_n192<1>(aX, mkd<HI128>(ax + ks * 2), mkd<HI128>(b16 + ks * 128), !(FIRST && ks == 0));
    wgmma_ss_n192<1>(aY, mkd<HI128>(ay + ks * 2), mkd<HI128>(b16 + ks * 128), !(FIRST && ks == 0));
  }
  wg_commit();
}
DEVI void qkv_half(float (&a)[96], uint32_t sb16, int t, uint32_t sa, uint32_t sbb) {
  wg_fence();
  #pragma unroll
  for (int ks = 0; ks < 4; ks++)
    wgmma_ss_n192<1>(a, mkd<HI128>(((sb16 + (sa >> 4) + t * 512) | 0x10000u) + ks * 2), mkd<HI128>(((sb16 + (sbb >> 4)) | ((8192u >> 4) << 16)) + ks * 128), 1);
  wg_commit();
}
DEVI void wo_block(float (&acc)[64], uint32_t sb16, int n, int s, int wg) {
  uint32_t a16 = (sb16 + (w_aoff(n, s) >> 4) + wg * 256) | 0x10000u, b16 = (sb16 + (w_off(s) >> 4) + 1024) | ((8192u >> 4) << 16);
  wg_fence();
  #pragma unroll
  for (int ks = 0; ks < 4; ks++)
    wgmma_ss_n128<1>(acc, mkd<HI64>(a16 + (ks >> 1) * 512 + (ks & 1) * 2), mkd<HI128>(b16 + ks * 128), 1);
  wg_commit();
}
DEVI void consumer(const Params& P, uint32_t sb, int wg) {
  const int w = uni((threadIdx.x >> 5) & 3);
  #define LAYER uni(mbar_test(BAR(B_XRDY + wg * 2 + 1), 0))
  #define IDS L = LAYER; const int tid = fresh_tid(), lane = tid & 31
  const uint32_t ids = uni(P.map[blockIdx.x]);
  const int bi = (ids >> 4) & 7, rh = ids & 1, bc = (ids & 15) >> 1, fid = ids >> 8;
  const int tX = 3 - wg, tY = wg;
  constexpr uint32_t sb16 = 1024 >> 4;
  #pragma unroll 1
  while (true) {
    int L = LAYER;
    float2 fa, fb;
    {
      float aX[96], aY[96];
      const bool lead = fresh_tid() == 0;
      mbar_wait(BAR(B_FULLQ), 0);
      PROFW(threadIdx.x == 0, L * 8 + 1);
      qkv_block<true>(aX, aY, sb16, 0, tX, tY);
      #pragma unroll 1
      for (int n = 1, s = 1, ps = 0, ph = 0; n < 14; n++) {
        mbar_wait(BAR(B_FULLQ + s), ph ^ (s ? L : 0));
        PROFD(threadIdx.x == 0 && L && (n == 2 || n == 3 || n == 7 || n == 11 || n == 13), n == 2 ? 48 : 49 + (n >> 2));
        qkv_block<false>(aX, aY, sb16, s, tX, tY);
        wg_wait<1>(); if (lead) mbar_arrive(BAR(B_EMPTYQ + ps));
        ps = s; if (s == 2) { s = 0; ph ^= 1; } else s++;
      }
      mbar_wait(BAR(B_FULLQ + 2), L);
      qkv_half(aX, sb16, tX, SA2, SB2);
      mbar_wait(BAR(B_ROW), L);
      IDS;
      const uint32_t pa = sb + PAR + (w * 16 + (lane >> 2)) * 8;
      float2 p0 = lds64f(pa + tX * 512), p1 = lds64f(pa + tX * 512 + 64), p2 = lds64f(pa + tY * 512), p3 = lds64f(pa + tY * 512 + 64);
      mean_step(aX, p0.y, p1.y, sb16 + (CS >> 4), lane & 3);
      mbar_wait(BAR(B_FULLQ), 1);
      qkv_half(aX, sb16, tX, 0, SB0);
      wg_wait<3>(); if (lead) mbar_arrive(BAR(B_EMPTYQ + 1));
      bar_sync(1, 256);
      qkv_half(aY, sb16, tY, SA2, SB2);
      wg_wait<1>(); keep(aX);
      const int srow = w * 16 + (lane & 15);
      const uint32_t x0 = sb + srow * 64 + (((lane >> 4) ^ ((srow >> 1) & 3)) << 4), xX = x0 + (4 + tX) * 8192, xY = x0 + (4 + tY) * 8192;
      qkv_store<8>(aX, p0.x, p1.x, xX + KVA); qkv_store<16>(aX, p0.x, p1.x, xX + KVA + 4096);
      warp_signal(BAR(B_KVRDY + wg * 2));
      qkv_half(aY, sb16, tY, 0, SB0);
      mean_step(aY, p2.y, p3.y, sb16 + (CS >> 4), fresh_tid() & 3);
      wg_wait<2>(); if (lead) mbar_arrive(BAR(B_EMPTYQ + 2));
      mbar_wait(BAR(B_EMPTYQ + 2), L);
      qkv_store<12>(aX, p0.x, p1.x, xX + KVB); qkv_store<20>(aX, p0.x, p1.x, xX + KVB + 4096);
      wg_wait<0>(); keep(aY);
      if (lead) mbar_arrive(BAR(B_EMPTYQ));
      PROFW(threadIdx.x == 0, L * 8 + 2);
      qkv_store<8>(aY, p2.x, p3.x, xY + KVA); qkv_store<16>(aY, p2.x, p3.x, xY + KVA + 4096);
      qkv_store<12>(aY, p2.x, p3.x, xY + KVB); qkv_store<20>(aY, p2.x, p3.x, xY + KVB + 4096);
      warp_signal(BAR(B_KVRDY + wg * 2 + 1));
      p0.x *= QSCALE; p1.x *= QSCALE; p2.x *= QSCALE; p3.x *= QSCALE;
      mbar_wait(BAR(B_EMPTYQ), 1);
      qkv_store<0>(aX, p0.x, p1.x, x0 + QO + tX * 4096);
      qkv_store<0>(aY, p2.x, p3.x, x0 + QO + tY * 4096); qkv_store<4>(aY, p2.x, p3.x, x0 + QO + 16384 + tY * 4096);
      { const float2* f = (const float2*)&P.g->statF[bi * 256 + rh * 128 + (wg ^ rh) * 64 + w * 16 + (lane >> 2)]; fa = __ldcg(f); fb = __ldcg(f + 16); }
      mbar_wait(BAR(B_PAR), L);
      qkv_store<4>(aX, p0.x, p1.x, x0 + QO + 16384 + tX * 4096);
      const int prow = (int)uni(lds32(sb + INFO)) - bi * 256;
      if ((prow >> 4) == tX * 4 + w || (prow >> 4) == tY * 4 + w) {
        __syncwarp();
        if (lane < 24) sts128(sb + (prow & 63) * 64 + (((lane ^ (prow >> 1)) & 3) << 4) +
                              (lane < 8 ? QO + (lane >> 2) * 16384 + (prow >> 6) * 4096 : ((lane & 4) ? KVB : KVA) + (4 + (prow >> 6)) * 8192 + (lane >> 4) * 4096),
                              lds128(sb + PATCH + lane * 16));
      }
      fence_async_smem();
      bar_sync(1, 256);
    }
    PROFW(threadIdx.x == 0, L * 8 + 3);
    {
      IDS;
      float s0[32], s1[32], sx[32], o[20], op[20];
      uint32_t p0[16], p1[16], px[16], msk[9];
      const int tdiag = w * 16 + (lane >> 2) - 2 * (lane & 3);
      const uint32_t ones = (sb16 + (ONES >> 4)) << 16;
      const uint32_t qX = (sb16 + (QO >> 4) + tX * 256) | 0x10000u, qY = (sb16 + (QO >> 4) + tY * 256) | 0x10000u;
      const uint32_t kXB = (sb16 + (KVB >> 4) + tX * 512) | 0x10000u;
      uint32_t redo = 0;
      const uint32_t ost = sb + QO + (w * 16 + (lane & 15)) * 64 + (((lane >> 4) ^ ((lane >> 1) & 3)) << 4);
      #define QA(s, q, k) do { wg_fence(); wgmma_ss_n64<0>(s, mkd<HI64>(q), mkd<HI64>(k), 0); } while (0)
      #define QB(s, q, k) wgmma_ss_n64<0>(s, mkd<HI64>((q) + 2), mkd<HI64>((k) + 2), 1)
      #define QA2(q, k) do { QA(s1, q, k); wgmma_ss_n64<0>(sx, mkd<HI64>(q), mkd<HI64>((k) + 2048), 0); } while (0)
      #define QB2(q, k) do { QB(s1, q, k); QB(sx, q, (k) + 2048); } while (0)
      #define VB(v, b) ((v) + VOFF((b) * 512))
      #define MID() do { wg_commit(); wg_wait<1>(); } while (0)
      QA(s0, qX + 1024, kXB + 1536); QB(s0, qX + 1024, kXB + 1536); wg_commit();
      #pragma unroll
      for (int e = 0; e < 20; e++) o[e] = 0.f;
      wg_wait<0>(); keep(s0);
      #pragma unroll 1
      for (int h = 1; h >= 0; h--) {
        const uint32_t kXA = kXB - ((KVB - KVA) >> 4), kX = h ? kXB : kXA, vX = VOFF((kX & 0xffffu) + 256) + ones;
        QA(s1, qX + h * 1024, kX + 1024);
        #pragma unroll
        for (int e = 0; e < 20; e++) op[e] = o[e];
        keep(op);
        exp_pv<0, 1>(s0, p0, o, VB(vX, 3), false); QB(s1, qX + h * 1024, kX + 1024); wg_commit();
        exp_pv<1, 2>(s0, p0, o, VB(vX, 3), true); MID(); keep(s1);
        exp_pv<2, 4>(s0, p0, o, VB(vX, 3), true);
        { int td = tdiag; asm volatile("" : "+r"(td));
          #pragma unroll
          for (int e = 0; e < 9; e++) msk[e] = ((8 * e - 8 > td) ? 0xFFFFu : 0u) | ((8 * e - 7 > td) ? 0xFFFF0000u : 0u);
          keep(msk); }
        exp_pv<0, 2>(s1, p1, o, VB(vX, 2), true);
        bar_sync(h ? 12 + wg : 4 + wg * 4, h ? 128 : 160);
        QA(s0, qX, kXA + 512 + h * 1024);
        exp_pv<2, 3>(s1, p1, o, VB(vX, 2), true); QB(s0, qX, kXA + 512 + h * 1024);
        exp_pv<3, 4>(s1, p1, o, VB(vX, 2), true); wg_commit();
        wg_wait<0>(); keep(s0); keep(p0); keep(p1); keep(o);
      }
      #pragma unroll 1
      for (int h = 0; h < 2; h++) {
        const uint32_t kb16 = sb16 + ((h ? KVB : KVA) >> 4), kX = (kb16 + tX * 512) | 0x10000u, kY = (kb16 + tY * 512) | 0x10000u, qx = qX + h * 1024, qy = qY + h * 1024;
        const uint32_t onesP = bi ? ones : (kb16 + 1984) << 16;
        const uint32_t vX = VOFF(kb16 + tX * 512 + 256), vY = VOFF(kb16 + tY * 512 + 256);
        uint32_t ob[8], v;
        v = VB(vX + (wg ? onesP : ones), 1);
        QA2(qx, kX);
        exp_pv<0, 1>(s0, p0, o, v, true); QB2(qx, kX); wg_commit();
        exp_pv<1, 2>(s0, p0, o, v, true); MID(); keep(s1); keep(sx);
        exp_pv<2, 4>(s0, p0, o, v, true);
        QA(s0, qy, kY + 1536);
        exp_pv2<0, 1>(s1, sx, p1, px, o, vX + onesP, VB(vX + ones, 4), msk, tdiag); QB(s0, qy, kY + 1536); wg_commit();
        exp_pv2<1, 2>(s1, sx, p1, px, o, vX + onesP, VB(vX + ones, 4), msk, tdiag); MID(); keep(s0); keep(p0);
        exp_pv2<2, 4>(s1, sx, p1, px, o, vX + onesP, VB(vX + ones, 4), msk, tdiag); wg_commit();
        v = VB(vY + (wg ? ones : onesP), 3);
        QA(s1, qy, kY + 1024);
        exp_pack<0, 4>(s0, p0);
        QB(s1, qy, kY + 1024); MID(); keep(o); keep(p1); keep(px);
        bool ok = attn_pack(o, ob); keep(ob);
        exp_pv<0, 2, 1>(s0, p0, o, v, false); MID(); keep(s1);
        attn_store(ob, ok, ost + (h * 4 + tX) * 4096, sb, BAR(B_ORDY + wg * 4 + h * 2)); redo |= ok ? 0u : 1u << (h * 2);
        exp_pv<2, 4>(s0, p0, o, v, true);
        v = VB(vY + onesP, 2);
        exp_pv<0, 1>(s1, p1, o, v, true);
        bar_sync(5 + wg * 4 + h * 2, 160);
        QA(s0, qy, kY + 512);
        exp_pv<1, 2>(s1, p1, o, v, true); QB(s0, qy, kY + 512); wg_commit();
        exp_pv<2, 3>(s1, p1, o, v, true); MID(); keep(s0); keep(p0);
        exp_pv<3, 4>(s1, p1, o, v, true);
        v = VB(vY + onesP, 1);
        QA2(qy, kY);
        exp_pv<0, 1>(s0, p0, o, v, true); QB2(qy, kY); wg_commit();
        exp_pv<1, 2>(s0, p0, o, v, true); MID(); keep(s1); keep(sx); keep(p1);
        exp_pv<2, 4>(s0, p0, o, v, true);
        exp_pv2<0, 1>(s1, sx, p1, px, o, vY + onesP, VB(vY + ones, 4), msk, tdiag);
        bar_sync(6 + wg * 4, h ? 128 : 160);
        QA(s0, h ? qy : qX + 1024, kXB + 512);
        exp_pv2<1, 2>(s1, sx, p1, px, o, vY + onesP, VB(vY + ones, 4), msk, tdiag); QB(s0, h ? qy : qX + 1024, kXB + 512);
        exp_pv2<2, 4>(s1, sx, p1, px, o, vY + onesP, VB(vY + ones, 4), msk, tdiag); wg_commit();
        wg_wait<0>(); keep(o); keep(s0); keep(p0); keep(p1); keep(px);
        ok = attn_pack(o, ob); attn_store(ob, ok, ost + (h * 4 + tY) * 4096, sb, BAR(B_ORDY + wg * 4 + h * 2 + 1)); redo |= ok ? 0u : 2u << (h * 2);
        #pragma unroll
        for (int e = 0; e < 20; e++) o[e] = op[e];
      }
      #undef QA
      #undef QB
      #undef QA2
      #undef QB2
      #undef VB
      #undef MID
      if (redo) {
        #pragma unroll 1
        for (int u = 0; u < 4; u++) if ((redo >> u) & 1) {
          const int h = u >> 1, t = (u & 1) ? tY : tX;
          attn_exact(sb + QO + (h * 4 + t) * 4096, sb + (h ? KVB : KVA), t, bi > 0, BAR(B_ORDY + wg * 4 + u));
        }
      }
    }
    PROFW(threadIdx.x == 0, L * 8 + 4);
    {
      IDS;
      const int t256 = wg * 128 + tid;
      float acc[64];
      const int tt = wg ^ rh;
      const int grow = bi * 256 + rh * 128 + tt * 64 + w * 16 + (lane >> 2);
      float al0 = 1.f, be0 = 0.f, al1 = 1.f, be1 = 0.f;
      const int idx0 = (int)uni(lds32(sb + INFO));
      const uint32_t tag = lds32(sb + INFO + 8) + L;
      uint4* const sp = &P.g->statP[bc][grow + (lane & 1) * 8];
      uint4* const yp = &P.g->yP[t256 >> 1][min(fid, 111)][t256 & 1];
      if (L) {
        float r0 = rsqrtf(fa.y + LN_EPS), r1 = rsqrtf(fb.y + LN_EPS);
        if (grow != idx0) { al0 = 1.f + r0; be0 = -fa.x * r0; }
        if (grow + 8 != idx0) { al1 = 1.f + r1; be1 = -fb.x * r1; }
      }
      const int srow = tt * 64 + w * 16 + (lane & 15);
      const uint32_t ra = sb + srow * 128 + (((lane >> 4) ^ (srow & 7)) << 4);
      mbar_wait(BAR(B_FULLW + 5), L);
      if ((idx0 >> 4) == bi * 16 + rh * 8 + tt * 4 + w) {
        int r = idx0 & 127;
        if (lane < 16) sts128(sb + 32768 + (lane >> 3) * 16384 + r * 128 + (((lane & 7) ^ (r & 7)) << 4), lds128(sb + X2SEG + lane * 16));
        fence_async_smem();
        __syncwarp();
      }
      #pragma unroll
      for (int jj = 0; jj < 8; jj++) {
        uint32_t r[4]; ldsm_x4((ra + 32768 + (jj >> 2) * 16384) ^ ((jj & 3) << 5), r[0], r[1], r[2], r[3]);
        #pragma unroll
        for (int e = 0; e < 4; e++) {
          acc[8 * jj + 2 * e] = fmaf(bf_lo(r[e]), (e & 1) ? al1 : al0, (e & 1) ? be1 : be0);
          acc[8 * jj + 2 * e + 1] = fmaf(bf_hi(r[e]), (e & 1) ? al1 : al0, (e & 1) ? be1 : be0);
        }
      }
      keep(acc);
      bar_sync(12 + wg, 128);
      if (!(lane & 2)) st_ll(sp, 0u, 0u, 0u, 0u);
      uint2 wd[4];
      #pragma unroll
      for (int e = 0; e < 4; e++) { wd[e] = make_uint2(0u, 0u); if (L) wd[e] = ldg_stream((const uint2*)(WDSRC) + t256 + (28 + e) * 256); }
      PROFW(t256 == 0, L * 8 + 5);
      #pragma unroll 1
      for (int n = 0, q = 0, pq = 5; n < 16; n++) {
        mbar_wait(BAR(B_FULLW + q), w_par(n, q, L));
        PROFD(t256 == 0 && !L && (n == 4 || n == 7 || n == 8 || n == 12), (n == 7 ? 63 : 41 + (n >> 2)));
        wo_block(acc, sb16, n, q, tt);
        wg_wait<1>(); if (tid == 0) mbar_arrive(BAR(B_EMPTYW + pq));
        pq = q; q = w_next(n, q);
      }
      mbar_wait(BAR(B_EMPTYW + 5), L);
      wg_wait<0>(); keep(acc);
      if (tid == 0) mbar_arrive(BAR(B_EMPTYW + 4));
      PROFW(t256 == 0, L * 8 + 6);
      {
        float s1a = 0.f, s2a = 0.f, da = 0.f, s1b = 0.f, s2b = 0.f, db = 0.f;
        #pragma unroll
        for (int j = 0; j < 16; j++) {
          const float* a = acc + 4 * j; float2 wv = lds64f(sb + WR + j * 32 + (lane & 3) * 8);
          s1a += a[0] + a[1]; s1b += a[2] + a[3];
          s2a = fmaf(a[0], a[0], s2a); s2b = fmaf(a[2], a[2], s2b); s2a = fmaf(a[1], a[1], s2a); s2b = fmaf(a[3], a[3], s2b);
          da = fmaf(a[0], wv.x, da); db = fmaf(a[2], wv.x, db); da = fmaf(a[1], wv.y, da); db = fmaf(a[3], wv.y, db);
        }
        bool odd = lane & 1;
        float u1 = (odd ? s1b : s1a) + __shfl_xor_sync(0xffffffffu, odd ? s1a : s1b, 1);
        float u2 = (odd ? s2b : s2a) + __shfl_xor_sync(0xffffffffu, odd ? s2a : s2b, 1);
        float u3 = (odd ? db : da) + __shfl_xor_sync(0xffffffffu, odd ? da : db, 1);
        u1 += __shfl_xor_sync(0xffffffffu, u1, 2); u2 += __shfl_xor_sync(0xffffffffu, u2, 2); u3 += __shfl_xor_sync(0xffffffffu, u3, 2);
        if (!(lane & 2)) st_ll(sp, __float_as_uint(u1), __float_as_uint(u2), __float_as_uint(u3), tag);
      }
      const uint32_t xa = ra + rh * 16384;
      #pragma unroll
      for (int jj = 0; jj < 8; jj++) {
        const float* a = acc + 8 * jj;
        stsm_x4((xa + (jj >> 2) * 32768) ^ ((jj & 3) << 5), pack_bf16(a[0], a[1]), pack_bf16(a[2], a[3]), pack_bf16(a[4], a[5]), pack_bf16(a[6], a[7]));
        if (jj == 7) fence_async_smem();
        if ((jj & 3) == 3) warp_signal(BAR(B_XRDY + wg * 2 + (jj >> 2)));
      }
      PROFW(t256 == 0, L * 8 + 7);
      if (L) {
        mbar_wait(BAR(B_PAR), 0);
        { float2 pa = lds64f(sb + PAR + (grow & 127) * 8), pb = lds64f(sb + PAR + (grow & 127) * 8 + 64); al0 = pa.x; be0 = pa.y; al1 = pb.x; be1 = pb.y; }
        uint32_t rs[32];
        #pragma unroll
        for (int j = 0; j < 16; j++) {
          rs[2 * j] = pack_bf16(fmaf(acc[4 * j], al0, be0), fmaf(acc[4 * j + 1], al0, be0));
          rs[2 * j + 1] = pack_bf16(fmaf(acc[4 * j + 2], al1, be1), fmaf(acc[4 * j + 3], al1, be1));
        }
        #pragma unroll
        for (int jj = 0; jj < 8; jj++) stsm_x4((xa + (jj >> 2) * 32768) ^ ((jj & 3) << 5), rs[4 * jj], rs[4 * jj + 1], rs[4 * jj + 2], rs[4 * jj + 3]);
        PROFW(t256 == 0, 16);
        if (fid >= 112) bar_arrive(3, 384);
        else {
          float d[4] = {0.f, 0.f, 0.f, 0.f};
          mbar_wait(BAR(B_FULLW + wg * 3), 0); mbar_wait(BAR(B_FULLW + wg * 3 + 1), 0);
          bar_sync(3, 384);
          PROFW(t256 == 0, 29);
          #pragma unroll 1
          for (int g = 0; g < 4; g++) {
            const uint32_t ad = (sb16 + (wg ? 6144 : 10240) + (g >> 1) * 2048 + (g & 1) * 512) | (1024u << 16), bd = (sb16 + (HV >> 4) + wg * 64 + g * 16) | 0x10000u;
            wg_fence();
            #pragma unroll
            for (int ks = 0; ks < 8; ks++) wgmma_ss_n8<0, 1>(d, mkd<HI64>(ad + ks * 64), mkd<8>(bd + ks * 2), 1);
            wg_commit();
          }
          mbar_wait(BAR(B_FULLW + 2), 0);
          wg_wait<0>(); keep(d);
          if (!(lane & 3)) { sts32f(sb + PAR + 1024 + wg * 256 + w * 64 + lane, d[0]); sts32f(sb + PAR + 1056 + wg * 256 + w * 64 + lane, d[2]); }
          bar_sync(1, 256);
          const uint32_t ga = sb + PAR + 1024 + lane * 4, aa = sb + HV + (t256 >> 5) * 128;
          sts32f(aa + lane * 4, swiglu(lds32f(ga) + lds32f(ga + 256), lds32f(ga + 128) + lds32f(ga + 384)));
          __syncwarp();
          PROFW(t256 == 0, 26);
          float y0 = 0.f, y1 = 0.f, y2 = 0.f, y3 = 0.f;
          uint32_t tbl = rh ? 0x001459a8u : 0x023679a8u;
          uint4 a4 = lds128(aa + 112);
          #pragma unroll 2
          for (int n = 0; n < 8; n++, tbl >>= 4) {
            const uint32_t src = sb + t256 * 8 + (tbl & 15) * 8192;
            const uint4 an = lds128(aa + ((0x00123564u >> (4 * n)) & 15) * 16);
            #pragma unroll
            for (int e = 0; e < 4; e++) {
              const float av = __uint_as_float(e == 0 ? a4.x : (e == 1 ? a4.y : (e == 2 ? a4.z : a4.w)));
              y0 = fmaf(bf_lo(wd[e].x), av, y0); y1 = fmaf(bf_hi(wd[e].x), av, y1); y2 = fmaf(bf_lo(wd[e].y), av, y2); y3 = fmaf(bf_hi(wd[e].y), av, y3);
              const float2 v = lds64f(src + e * 2048); wd[e] = make_uint2(__float_as_uint(v.x), __float_as_uint(v.y));
            }
            a4 = an;
          }
          st_ll(yp, __float_as_uint(y0), __float_as_uint(y1), __float_as_uint(y2), (__float_as_uint(y3) & ~255u) | (lds32(sb + INFO + 12) + 1));
          PROFW(t256 == 0, 27);
        }
        return;
      }
      mbar_wait(BAR(B_XRDY + wg * 2 + 1), 0);
    }
  }
  #undef IDS
  #undef LAYER
}

DEVI void loader(const Params& P, uint32_t sb) {
  const int lane = threadIdx.x & 31;
  const int bid = uni(BID), bi = bid >> 4, bp = bid & 15, rh = bp & 1, bc = bp >> 1;
  uint32_t phq = 0, tag = 0;
  #pragma unroll 1
  for (int L = 0; L < 2; L++) {
    int s = 0;
    uint32_t rdy = 0;
    #pragma unroll 1
    for (int n = L ? 0 : 3; n < 16; n++) {
      int kb = L ? kb_order(bc, n) : n;
      mbar_wait(BAR(B_EMPTYQ + s), (phq >> s) & 1);
      phq ^= 1u << s;
      if (L && n == 1) { mbar_wait(BAR(B_XRDY + 1), 0); mbar_wait(BAR(B_XRDY + 3), 0); }
      if (elect()) {
        mbar_expect_tx(BAR(B_FULLQ + s), L && n < 2 ? 40960 : 57344);
        tma_3d_h(sb + qb_off(s), &P.mWq, bp * 64, kb * 64, 0, BAR(B_FULLQ + s), L && n >= QEF_N ? POL_FIRST : POL_NORMAL);
        if (!L) tma_2d(sb + qa_off(s), &P.mX, kb * 64, bi * 256, BAR(B_FULLQ + s));
      }
      if (L && n >= 2) {
        if (((rdy >> (2 * kb)) & 3) != 3) {
          do { rdy = __ballot_sync(0xffffffffu, ld_rlx(&P.g->flagX[bi][lane]) == tag); } while (((rdy >> (2 * kb)) & 3) != 3);
          fence_async_glob();
        }
        if (n == 3 || n == 4) mbar_wait(BAR(B_XFREE + n - 3), 0);
        if (elect()) bulk_g2s_h(sb + qa_off(s), P.g->x[bi][kb], 32768, BAR(B_FULLQ + s), POL_X);
      }
      PROFY(L && lane == 0 && (n == 2 || n == 3 || n == 9), n == 9 ? 60 : 56 + n);
      if (L && n == 2) { mbar_wait(BAR(B_FULLQ), 0); mbar_wait(BAR(B_FULLQ + 1), 1); if (lane < 2) mbar_arrive_peer(BAR(B_XFREE + lane)); }
      s = (s == 2) ? 0 : s + 1;
    }
    for (int q = 0; q < 3; q++) mbar_wait(BAR(B_EMPTYQ + q), (phq >> q) & 1);
    tag = lds32(sb + INFO + 8) + L;
    #pragma unroll 1
    for (int q = 0; q < 4; q++) {
            if (bi) {
        const unsigned* f = &P.g->flagKV[bid - 16][q];
        while (ld_rlx(f) != tag);
        fence_async_glob();
      }
      if (elect()) {
        mbar_expect_tx(BAR(B_KVFULL + q), 16384);
        bulk_g2s_h(sb + ((q >> 1) ? KVB : KVA) + ((q & 1) ? 0 : 16384), bi ? P.g->kv[bid - 16][q] : P.g->zero, 16384, BAR(B_KVFULL + q), L ? POL_KV1 : POL_KV0);
      }
      PROFY(!L && lane == 0 && bi && q != 2, 34 + (q + 1) / 2);
    }
    mbar_wait(BAR(B_ORDY), L);
    {
      const uint4* src = P.g->o[bi][0][0][rh];
      rdy = 0;
      #pragma unroll 1
      for (int n = 0, q = 0; n < 16; q = w_next(n, q), n++) {
        const int j = wo_order(bc, n);
        if (((rdy >> (2 * j)) & 3) != 3) {
          do { rdy = __ballot_sync(0xffffffffu, ld_rlx(&P.g->flagO[bi][lane]) == tag); } while (((rdy >> (2 * j)) & 3) != 3);
          fence_async_glob();
        }
        if (n >= 2) mbar_wait(n < 5 ? BAR(B_HAFREE + (n > 3)) : BAR(B_EMPTYW + q), n < 5 ? L : w_par(n, q, L) ^ 1);
        if (n == THR_N) mbar_wait(BAR(B_OFREE), L);
        if (elect()) { mbar_expect_tx(BAR(B_FULLW + q), 16384); bulk_g2s_h(sb + w_aoff(n, q), src + j * 2048, 16384, BAR(B_FULLW + q), L ? POL_O1 : POL_O0); }
      }
    }
    mbar_wait(BAR(B_OFREE), L);
  }
}

DEVI void ffn_prefetch(const Params& P, int q) {
  bulk_prefetch(q < 16 ? ((q & 1) ? P.wu : P.wg) + ((q >> 1) * 128 + blockIdx.x) * 3584 : P.wd + (min(FID, 111) * 8 + q - 16) * 4096, q < 16 ? 7168 : 8192);
}
DEVI void storer(const Params& P, uint32_t sb, int wg) {
  const int bid = uni(BID), bi = bid >> 4, rh = bid & 1, bc = (bid & 15) >> 1;
  const bool one = (threadIdx.x & 31) == 0;
  char* const g = (char*)P.g;
  const uint32_t tag0 = uni(((ld_rlx(&P.g->epoch) % 16383u) + 1u) << 2);
  #pragma unroll 1
  for (int L = 0; L < 2; L++) {
    const uint32_t tag = tag0 + L;
    if (wg) {
      #pragma unroll 1
      for (int r = threadIdx.x & 31; r < 256; r += 32) {
        uint4 v;
        do v = ld_ll(&P.g->statF[bi * 256 + r]); while (!__all_sync(0xffffffffu, v.w == tag));
        float var = __uint_as_float(v.y), c = rsqrtf(var + LN_EPS);
        if (L) { c += 1.f; c *= rsqrtf(fmaf(var * c, c, LN_EPS)); }
        const float mh = bf_round(__uint_as_float(v.x));
        sts64f(sb + PAR + r * 8, c, __uint_as_float(pack_bf16(mh, __uint_as_float(v.x) - mh)));
      }
      if (!L) mbar_wait(BAR(B_PAR), 0);
      warp_signal(BAR(B_ROW));
    }
    #pragma unroll 1
    for (int u = 0; u < 2 + 4 * wg; u++) {
      const int h = u < 2 ? u : u >> 2, hi = (u & 1) ^ 1;
      uint32_t src, dst, fl, b0, b1;
      if (u < 2) {
        src = (h ? KVB : KVA) + (3 - wg) * 16384; dst = offsetof(Scratch, kv) + (bid * 4 + h * 2 + wg) * 16384; fl = offsetof(Scratch, flagKV) + (bid * 32 + h * 2 + wg) * 4;
        b0 = BAR(B_KVRDY + ((u | wg) ? 1 : 0)); b1 = b0 + 16;
      } else {
        src = QO + (h * 2 + hi) * 8192; dst = offsetof(Scratch, o) + ((((bi * 2 + h) * 8 + bc) * 2 + hi) * 2 + rh) * 8192;
        fl = offsetof(Scratch, flagO) + (bi * 32 + h * 16 + (bid & 15)) * 4;
        b0 = BAR(B_ORDY + u - 2); b1 = b0 + 32;
      }
      mbar_wait(b0, L); mbar_wait(b1, L);
      if (u + wg == 1) {
        mbar_wait(BAR(B_PAR), L);
        const uint32_t t0 = clk(), dt = (wg ? KV_D1 : KV_D2) + (L ? KV_DL : 0); while (clk() - t0 < dt) __nanosleep(40);
      }
      fence_async_smem();
      PROFY(one && !L && u == 3 * wg, u ? 46 : 8);
      if (one && (u >= 2 || bi < 7)) bulk_s2g(g + dst, sb + src, u < 2 ? 16384 : 8192, ((ST_M >> (L * 2 + (u >= 2))) & 1) ? POL_FIRST : POL_NORMAL);
      if (one && u == 5) mbar_arrive(BAR(B_HAFREE + 1));
      if (u == 2 || u == 4) continue;
      bulk_wait<0>();
      PROFY(one && !L && u == 3 * wg, u ? 61 : 62);
      fence_rel();
      if (one) { st_rlx((unsigned*)(g + fl), tag); if (!wg || u > 2) mbar_arrive(BAR(B_HAFREE + h + (wg & h))); if (!wg && u) mbar_arrive(BAR(B_RES)); }
      PROFY(one && !L && (u > 2 || u == wg), u > 2 ? (u == 3 ? 38 : 54) : 32 + u);
    }
    if (L == 0) {
      char* dst = g + (offsetof(Scratch, x) + (bi * 16 + 2 * bc) * 32768 + rh * 16384);
      unsigned* f = (unsigned*)(g + (offsetof(Scratch, flagX) + (bi * 32 + bc * 4 + rh) * 4));
      const uint32_t a = sb + rh * 16384;
      if (wg == 0) {
        mbar_wait(BAR(B_XRDY), 0); mbar_wait(BAR(B_XRDY + 2), 0);
        fence_async_smem();
        PROFY(one, 41);
        if (one) bulk_s2g(dst, a, 16384);
        bulk_wait<0>();
        PROFY(one, 45);
        if (one) { mbar_arrive(BAR(B_XFREE)); mbar_arrive(BAR(B_PFREE)); }
        fence_rel();
        mbar_wait(BAR(B_XRDY + 1), 0); mbar_wait(BAR(B_XRDY + 3), 0);
        if (one) { st_rlx(f, tag); bulk_s2g(dst + 32768, a + 32768, 16384); }
        PROFY(one, 56);
        bulk_wait<0>();
        if (one) mbar_arrive(BAR(B_XFREE + 1));
        fence_rel();
        if (one) st_rlx(f + 2, tag);
        PROFY(one, 57);
      } else {
        mbar_wait(BAR(B_XRDY + 1), 0); mbar_wait(BAR(B_XRDY + 3), 0);
        mbar_wait(BAR(B_PFREE), 0);
        if (one) bulk_s2peer(a, 16384, BAR(B_FULLQ));
        { const uint32_t t0 = clk(); while (clk() - t0 < XD_D); }
        if (one) bulk_s2peer(a + 32768, 16384, BAR(B_FULLQ + 1));
      }
      if (wg == 0) {
        uint32_t t0 = clk() + PF1_D;
        #pragma unroll 1
        for (int q = PF1_S; q < PF1_E; q++) { while ((int)(clk() - t0) < 0) __nanosleep(50); if (one) ffn_prefetch(P, q); t0 += PF1_T; }
      }
    }
  }
}

DEVI void stg_issue(const Params& P, int c, uint32_t d, uint32_t du, uint32_t b) {
  mbar_expect_tx(b, 16384);
  if (c < 8) { tma_2d_h(d, &P.mWg, FID * 32, c * 128, b, du > 8192 ? POL_T : POL_G); tma_2d_h(d + du, &P.mWu, FID * 32, c * 128, b, du > 8192 || c < U_C ? POL_FIRST : POL_NORMAL); }
  else if (c < 12) tma_3d_h(d, &P.mWd, 0, FID * 32 + (c - 8) * 8, 0, b, POL_D);
  else tma_2d_h(d, &P.mWp, (c - 12) * 1024 + (BID >> 2) * 32, (BID & 3) * 256, b, POL_EF);
}
DEVI void pace() { const uint32_t t0 = clk(); while (clk() - t0 < PACE_T); }
DEVI void stager(const Params& P, uint32_t sb) {
  {
    const int b = blockIdx.x;
    uint32_t t0 = clk();
    #pragma unroll 1
    for (int q = 0; q < PQ_N; q++) { bulk_prefetch(P.wqkv + (q * 128 + b) * 3072, 6144); while (clk() - t0 < PQ_T) __nanosleep(50); t0 += PQ_T; }
    bulk_prefetch(P.wo + b * 8192, 16384);
    #pragma unroll 1
    for (int q = 0; q < PF0_N; q++) {
      while (clk() - t0 < PF0_T) __nanosleep(50);
      t0 += PF0_T;
      ffn_prefetch(P, q);
    }
  }
  const int bid = BID, bi = bid >> 4, rh = bid & 1, bc = (bid & 15) >> 1;
  #pragma unroll 1
  for (int L = 0; L < 2; L++) {
    const int nch = L ? (FID < 112 ? 8 : 0) : 15;
    mbar_wait(BAR(B_PAR), L); mbar_wait(BAR(B_KVFULL + W0_BAR), L);
    #pragma unroll 1
    for (int m = 0, r = 0; m < 16; r = w_next(m, r), m++) {
      const int sw = (m == 3 || m == 4) ? 7 : 0, n = m ^ sw, q = r ^ sw;
      if (n == 4) { mbar_wait(BAR(B_RES), L); mbar_wait(BAR(B_ORDY + 2), L); mbar_wait(BAR(B_ORDY + 6), L); }
      else if (n >= 2) mbar_wait(n < 5 ? BAR(B_HAFREE + (n > 2)) : BAR(B_EMPTYW + q), n < 5 ? L : w_par(n, q, L) ^ 1);
      if (n == THR_N) mbar_wait(BAR(B_OFREE), L);
      mbar_expect_tx(BAR(B_FULLW + q), 16384);
      tma_5d(sb + w_off(q) + 16384, &P.mWo, 0, 0, n >> 3, 2 * (wo_order(bc, n) & 7), 2 * bc, BAR(B_FULLW + q), L ? POL_W1 : POL_W0);
      if (n == 2) {
        #pragma unroll 1
        for (int e = 0; e < 2; e++) {
          mbar_expect_tx(BAR(B_FULLW + 5), 16384);
          if (L) bulk_g2s_h(sb + 32768 + e * 16384, P.g->x[bi][2 * bc + e] + rh * 1024, 16384, BAR(B_FULLW + 5));
          else tma_2d_h(sb + 32768 + e * 16384, &P.mXh, bc * 128 + e * 64, bi * 256 + rh * 128, BAR(B_FULLW + 5), POL_EF);
        }
      }
    }
    mbar_wait(BAR(B_EMPTYW + 5), L);
    if (L && nch) {
      const bf16* src = WDSRC2;
      mbar_expect_tx(BAR(B_FULLW + 2), 32768); mbar_expect_tx(BAR(B_FULLW + 2), 24576);
      #pragma unroll 1
      for (int e = 0; e < 3; e++) { bulk_g2s_h(sb + e * 32768 + (e < 2 ? (rh ^ 1) * 16384 : 0), src + e * 8192, e < 2 ? 16384 : 24576, BAR(B_FULLW + 2)); pace(); }
    }
        if (L == 0) { mbar_arrive_peer(BAR(B_PFREE)); mbar_wait(BAR(B_EMPTYW), 0); mbar_wait(BAR(B_EMPTYW + 1), 0); }
    #pragma unroll 1
    for (int c = FID < 112 ? 0 : 12, slot = 0; c < nch; c++, slot = slot == 2 ? 0 : slot + 1) {
      const int q = (c >> 1) + (c >> 2);
      if (!L && (c == LATE_C || c == 12)) mbar_wait(BAR(LATE_B), LATE_P);
      mbar_wait(L ? BAR(B_EMPTYW + q) : BAR(B_STGE + slot), L | ((0x71c7 >> c) & 1));
      #define CC c
      stg_issue(P, CC, L ? sb + w_off(q) + (c & 1) * 8192 : sb + STG + slot * 16384, 8192 << L, L ? BAR(B_FULLW + q) : BAR(B_STG + slot));
      if (L) pace();
    }
  }
}
DEVI void sum8(uint4 v, float& s1, float& s2) {
  float e[8] = {bf_lo(v.x), bf_hi(v.x), bf_lo(v.y), bf_hi(v.y), bf_lo(v.z), bf_hi(v.z), bf_lo(v.w), bf_hi(v.w)};
  #pragma unroll
  for (int q = 0; q < 8; q++) { s1 += e[q]; s2 = fmaf(e[q], e[q], s2); }
}
DEVI uint4 norm8(uint4 x, float m, float rs) {
  #define HN(v) pack_bf16((bf_lo(v) - m) * rs, (bf_hi(v) - m) * rs)
  return make_uint4(HN(x.x), HN(x.y), HN(x.z), HN(x.w));
  #undef HN
}
DEVI void put_f32(uint4 b, uint32_t d, uint32_t d2) {
  sts128(d, make_uint4(b.x << 16, b.x & 0xffff0000u, b.y << 16, b.y & 0xffff0000u));
  sts128(d + d2, make_uint4(b.z << 16, b.z & 0xffff0000u, b.w << 16, b.w & 0xffff0000u));
}
DEVI void put_bf16(uint4 b, uint32_t d) {
  sts64f(d, __uint_as_float(b.x), __uint_as_float(b.y)); sts64f(d + 1024, __uint_as_float(b.z), __uint_as_float(b.w));
  fence_async_smem();
}
DEVI uint4 best4(uint32_t p) {
  uint4 a = lds128(p), b = lds128(p + 16), c = lds128(p + 32), d = lds128(p + 48);
  if (b.x > a.x) a = b;
  if (d.x > c.x) c = d;
  return c.x > a.x ? c : a;
}
#define FL(x) __uint_as_float(x)
#define UI(x) __float_as_uint(x)
DEVI void aux(const Params& P, uint32_t sb) {
  int tid = fresh_tid();
  #define lane (tid & 31)
  #define wq (tid >> 5)
  uint32_t ids = P.map[blockIdx.x], tag;
  #define bid ((int)(ids & 255))
  #define fid ((int)(ids >> 8))
  #define bi (bid >> 4)
  #define bp (bid & 15)
  #define bc (bp >> 1)
  #define FRESH() do { tid = fresh_tid(); uint4 z_ = ldsv128(sb + INFO2 + 16); ids = z_.y; tag = z_.z + L; idx = z_.w; } while (0)
  {
    const uint32_t epoch = ld_rlx(&P.g->epoch);
    if (tid == 0) {
      mbar_expect_tx(BAR(B_STG), 49152);
      tma_3d(sb + STG, &P.mWq, bp * 64, bi * 128, 0, BAR(B_STG));
      tma_3d(sb + STG + 24576, &P.mWq, bp * 64, bi * 128 + 64, 0, BAR(B_STG));
    }
    __syncwarp();
    sts64f(sb + ONES + tid * 8, FL(0x3F803F80u), FL(0x3F803F80u));
    float s1 = 0.f, s2 = 0.f;
    { uint4 v = __ldg((const uint4*)P.wr + tid);
      if ((tid >> 4) == bc) put_f32(v, sb + WR + (tid & 15) * 32, 16);
      sum8(v, s1, s2);
      #pragma unroll 1
      for (int o = 16; o; o >>= 1) s1 += __shfl_xor_sync(0xffffffffu, s1, o);
      sts32f(sb + INFO2 + wq * 4, s1); }
    const uint4* src = (const uint4*)(P.x0 + (size_t)bid * 16384) + (tid >> 3) * 128 + (tid & 7);
    s1 = 0.f; s2 = 0.f;
    #pragma unroll 1
    for (int it = 0; it < 16; it += 4) {
      uint4 v0 = __ldg(src + it * 8), v1 = __ldg(src + it * 8 + 8), v2 = __ldg(src + it * 8 + 16), v3 = __ldg(src + it * 8 + 24);
      #pragma unroll 1
      for (int q = 0; q < 4; q++) { sum8(v0, s1, s2); v0 = v1; v1 = v2; v2 = v3; }
    }
    #pragma unroll 1
    for (int o = 1; o < 8; o <<= 1) { s1 += __shfl_xor_sync(0xffffffffu, s1, o); s2 += __shfl_xor_sync(0xffffffffu, s2, o); }
    tag = ((epoch % 16383u) + 1u) << 2;
    if (tid == 0) { sts128(sb + INFO, make_uint4(0x40000000u, 0u, tag, ((epoch % 127u) + 1u) << 1)); sts128(sb + INFO2 + 16, make_uint4(epoch, ids, tag, 0x40000000u)); }
    float m = s1 * (1.f / 1024.f);
    if ((tid & 7) == 0) st_ll(&P.g->statF[bid * 16 + (tid >> 3)], UI(m), UI(fmaxf(fmaf(-m, m, s2 * (1.f / 1024.f)), 0.f)), 0u, tag);
    bar_sync(2, 128);
    mbar_wait_b(BAR(B_STG), 0);
    if (tid < 96) {
      s1 = 0.f; s2 = 0.f;
      #pragma unroll 1
      for (int r = 0; r < 16; r++) {
        const uint32_t a = sb + STG + (r >> 3) * 24576 + wq * 8192 + (r & 7) * 128 + ((lane * 4) ^ ((r & 7) << 4));
        #pragma unroll
        for (int e = 0; e < 8; e++) { uint32_t v = lds32(a + e * 1024); s1 += bf_lo(v); s2 += bf_hi(v); }
      }
      st_ll(&P.g->csP[bp][bi][tid], UI(s1), UI(s2), 0u, tag);
      s1 = 0.f; s2 = 0.f;
      #pragma unroll 1
      for (int q = 0; q < 8; q += 2) {
        uint4 a, b; poll_ll2(&P.g->csP[bp][q][tid], &P.g->csP[bp][q + 1][tid], 0xffffffffu, tag, a, b);
        s1 += FL(a.x) + FL(b.x); s2 += FL(a.y) + FL(b.y);
      }
      const uint32_t hi = pack_bf16(-s1, -s2);
      sts32(sb + CS + (tid >> 2) * 32 + (tid & 3) * 4, hi);
      sts32(sb + CS + (tid >> 2) * 32 + (tid & 3) * 4 + 16, pack_bf16(-s1 - bf_lo(hi), -s2 - bf_hi(hi)));
    }
    fence_async_smem();
  }
  int idx;
  #pragma unroll 1
  for (int L = 0; L < 2; L++) {
    FRESH();
    {
      sts32(sb + INFO, idx);
      bar_sync(2, 128);
    }
    const uint4 fix = lds128(sb + PATCH + 128 + (lane & 4) * 32 + (wq >> 1) * 64 + (lane & 3) * 16);
    warp_signal(BAR(B_PAR));
    PROFX(tid == 0, L ? 23 : 17);
    mbar_wait_b(BAR(B_KVFULL + wq), L);
    if ((idx >> 7) == bi * 2 - 1 - (wq & 1)) {
      if (lane < 8) sts128(sb + ((wq >> 1) ? KVB : KVA) + ((idx >> 6) & 3) * 8192 + (lane >> 2) * 4096 + (idx & 63) * 64 + (((lane ^ (idx >> 1)) & 3) << 4), fix);
      fence_async_smem();
    }
    bar_arrive(4 + wq, 160); bar_arrive(8 + wq, 160);
    FRESH();
    mbar_wait_b(BAR(B_OFREE), L);
    #define blk (bi * 2 + (bid & 1))
    if (tid < 33) st_ll(tid < 32 ? &P.g->row[blk][bc * 32 + tid] : &P.g->best[bc][blk], 0u, 0u, 0u, 0u);
    mbar_wait_b(BAR(B_XRDY), L);
    PROFX(tid == 0, 37 + L * 16);
    FRESH();
    {
      float s1 = 0.f, s2 = 0.f, d = 0.f;
      #pragma unroll 1
      for (int q = 0; q < 8; q += 4) { const float4 v = poll_sum4(&P.g->statP[q][blk * 128 + tid], 2048, tag); s1 += v.x; s2 += v.y; d += v.z; }
      PROFX(tid == 0, 39 + L * 16);
      uint4 a = lds128(sb + INFO2), b, c;
      float m = s1 * (1.f / 1024.f), var = fmaxf(fmaf(-m, m, s2 * (1.f / 1024.f)), 0.f), rs = rsqrtf(var + LN_EPS);
      uint32_t key = UI(fmaf(-m, (FL(a.x) + FL(a.y)) + (FL(a.z) + FL(a.w)), d) * rs);
      key ^= (uint32_t)((int)key >> 31) | 0x80000000u;
      uint32_t win = __ballot_sync(0xffffffffu, key == __reduce_max_sync(0xffffffffu, key));
      if (lane == __ffs(win) - 1) sts128(sb + RED + wq * 16, make_uint4(key, UI(m), UI(rs), (tag << 11) | (uint32_t)(blk * 128 + tid)));
      if (L) sts64f(sb + PAR + tid * 8, 1.f + rs, -m * rs);
      else if ((tid >> 4) == bc) st_ll(&P.g->statF[blk * 128 + tid], UI(m), UI(var), 0u, tag + 1);
      bar_sync(2, 128);
      if (wq < 2) a = best4(sb + RED);
      if (tid == 32) st_ll(&P.g->best[bc][blk], a.x, a.y, a.z, a.w);
      if (wq == 0) {
        mbar_wait(BAR(B_XRDY + 1), L); mbar_wait(BAR(B_XRDY + 3), L);
        float2 v = lds64f(sb + (lane >> 4) * 32768 + (a.w & 255) * 128 + (((lane & 15) * 8) ^ ((a.w & 7) << 4)));
        st_ll(&P.g->row[blk][bc * 32 + lane], UI(v.x), UI(v.y), 0u, tag);
        __syncwarp();
        if (lane < 2 + 2 * L) mbar_arrive(L ? BAR(B_PAR) : BAR(B_XFREE + lane));
      }
      PROFX(tid == 0, 18 + L * 6);
      FRESH();
      a = poll_ll(&P.g->best[bc][lane & 15], 0xfffff800u, tag << 11);
      win = __ffs(__ballot_sync(0xffffffffu, a.x == __reduce_max_sync(0xffffffffu, a.x))) - 1;
      idx = __shfl_sync(0xffffffffu, a.w, win) & 2047;
      PROFX(tid == 0, 19 + L * 6);
      poll_ll2(&P.g->row[win][tid], &P.g->row[win][tid + 128], 0xffffffffu, tag, c, b);
      c.z = b.x; c.w = b.y;
      a.x = __shfl_sync(0xffffffffu, a.x, win); a.y = __shfl_sync(0xffffffffu, a.y, win); a.z = __shfl_sync(0xffffffffu, a.z, win);
      sts32(sb + INFO2 + 28, idx);
      PROFX(tid == 0, 61 + L);
      b = norm8(c, FL(a.y), FL(a.z));
      if (L) put_bf16(b, sb + HV + tid * 8); else put_f32(b, sb + HV + tid * 16, 2048);
      if ((tid >> 1) == (bid & 63)) {
        sts128(sb + RED + 64 + (tid & 1) * 16, bid < 64 ? make_uint4(c.x, c.y, b.x, b.y) : make_uint4(c.z, c.w, b.z, b.w));
        sts32(sb + RED + 96, a.x);
      }
      bar_sync(2 + L, 128 + L * 256);
      if (L) {
        const int r0 = blk * 128 + (tid >> 4);
        uint32_t src = sb + ((tid >> 3) & 1) * 32768 + (r0 & 255) * 128 + (((tid ^ r0) & 7) << 4);
        uint4* dst = (uint4*)(P.out + (size_t)r0 * 1024 + bc * 128) + (tid & 15);
        #pragma unroll 4
        for (int it = 0; it < 16; it++) { uint4 v = lds128(src + it * 1024); if (idx - r0 != it * 8) dst[it * 1024] = v; }
      }
    }
    #pragma unroll 1
    for (int st = 2 * L; st < 2; st++) {
      FRESH();
      float a[8] = {0.f, 0.f, 0.f, 0.f, 0.f, 0.f, 0.f, 0.f};
      if (fid < 112) {
        uint32_t ha = st ? sb + RED + 768 + wq * 4 : sb + HV + ((wq & 1) * 64 + (lane >> 2)) * 4;
        uint32_t ph = st ? 0x1cu : 0x171u, bar = st ? BAR(B_STG + 2) : BAR(B_STG);
        uint32_t wa = sb + STG + wq * 4096 + (st ? 32768 + lane * 16 : (lane ^ (lane >> 3)) * 16);
        const uint32_t hx = st ? 256 : 512;
        const bool lead = lane == 0;
        uint4 vc = make_uint4(0u, 0u, 0u, 0u); float hc = 0.f;
        #pragma unroll 1
        do {
          mbar_wait(bar, ph & 1);
          PROFX(lead && threadIdx.x == 256 && st == 0 && (ph > 255 || ph < 4), 40 - 23 + __clz(ph));
          #pragma unroll
          for (int n = 0; n < 8; n++) { const uint4 v = lds128(wa + n * 512); const float h = lds32f(ha + n * 32); fma8(a, vc, hc); vc = v; hc = h; }
          __syncwarp();
          if (lead) mbar_arrive(bar - 8 * (B_STG - B_STGE));
          const bool wrap = bar == BAR(B_STG + 2);
          bar += wrap ? -16 : 8; wa += wrap ? -32768 : 16384; ha += hx;
          ph >>= 1;
        } while (ph != 1);
        fma8(a, vc, hc);
      }
      FRESH();
      uint4* const yp = &P.g->yP[tid & ~1][min(fid, 111)][tid & 1];
      if (st == 0) {
        sts32f(sb + RED + 256 + wq * 128 + ((lane & 3) * 8 + (lane >> 2)) * 4, fold8(a));
        bar_sync(2, 128);
        const uint32_t d = sb + RED + 256 + lane * 4;
        sts32f(sb + RED + 768 + lane * 32 + wq * 4, swiglu(lds32f(d) + lds32f(d + 128), lds32f(d + 256) + lds32f(d + 384)));
        if (fid < 112) { st_ll(yp, 0u, 0u, 0u, 0u); st_ll(yp + 224, 0u, 0u, 0u, 0u); }
        else { const uint32_t t0 = clk(); while (clk() - t0 < IDLE_T) __nanosleep(200); }
        __syncwarp();
        PROFX(tid == 0, 20);
      } else if (fid < 112) {
        const bool odd = lane & 1;
        const uint32_t t8 = lds32(sb + INFO + 12);
        #pragma unroll
        for (int e = 0; e < 4; e++) { float z = __shfl_xor_sync(0xffffffffu, odd ? a[e] : a[4 + e], 1); if (odd) a[e] = z; else a[4 + e] = z; }
        st_ll(yp, UI(a[0]), UI(a[1]), UI(a[2]), (UI(a[3]) & ~255u) | t8);
        st_ll(yp + 224, UI(a[4]), UI(a[5]), UI(a[6]), (UI(a[7]) & ~255u) | t8);
        PROFX(tid == 0, 21);
      }
    }
    {
      const uint32_t t8 = lds32(sb + INFO + 12) + L;
      const uint4* src = &P.g->yP[bid][0][min(tid, 111)];
      uint4 v0 = ld_ll(src), v1 = ld_ll(src + 112);
      uint4* dst = L ? (uint4*)(P.out + (size_t)idx * 1024 + bid * 8 + (tid & 1) * 4) : &P.g->x2[(tid >> 1) & 7][2 * bid + (tid & 1)];
      if (!L && (tid < 16 || tid >= 64)) st_ll(tid < 16 ? dst : &P.g->patch[bid][tid - 64], 0u, 0u, 0u, 0u);
      const uint32_t k = lds32(sb + RED + 96);
      const float sg = sigmoidf(FL(k ^ (~(uint32_t)((int)k >> 31) | 0x80000000u)));
      for (int it = 0; !__all_sync(0xffffffffu, ((v0.w ^ t8) & 255u) == 0 && ((v1.w ^ t8) & 255u) == 0); it++) { v0 = ld_ll(src); v1 = ld_ll(src + 112); if (it > SPIN_MAX) __trap(); }
      float y0 = FL(v0.x) + FL(v1.x), y1 = FL(v0.y) + FL(v1.y), y2 = FL(v0.z) + FL(v1.z), y3 = FL((v0.w & ~255u) | 128u) + FL((v1.w & ~255u) | 128u);
      const bool u = lane & 2, v = lane & 4;
      y0 = (u ? y2 : y0) + __shfl_xor_sync(0xffffffffu, u ? y0 : y2, 2); y1 = (u ? y3 : y1) + __shfl_xor_sync(0xffffffffu, u ? y1 : y3, 2);
      y0 = (v ? y1 : y0) + __shfl_xor_sync(0xffffffffu, v ? y0 : y1, 4);
      y0 += __shfl_xor_sync(0xffffffffu, y0, 8);
      y1 = __shfl_xor_sync(0xffffffffu, y0, 16);
      if (lane < 8) sts32f(sb + RED + 128 + wq * 32 + (lane & 1) * 16 + (lane & 2) * 4 + (lane & 4), wq < 3 ? y0 + y1 : y0);
      bar_sync(2, 128);
      if (tid < (L ? 2 : 16)) {
        const uint32_t d = sb + RED + (tid & 1) * 16;
        const uint4 xh = lds128(d + 64), a = lds128(d + 128), b = lds128(d + 160), c = lds128(d + 192), e = lds128(d + 224);
        #define FIN(f, z) fmaf((FL(a.f) + FL(b.f)) + (FL(c.f) + FL(e.f)), sg, z)
        const uint32_t r0 = pack_bf16(FIN(x, bf_lo(xh.x) + bf_lo(xh.z)), FIN(y, bf_hi(xh.x) + bf_hi(xh.z))), r1 = pack_bf16(FIN(z, bf_lo(xh.y) + bf_lo(xh.w)), FIN(w, bf_hi(xh.y) + bf_hi(xh.w)));
        #undef FIN
        if (L) *(uint2*)dst = make_uint2(r0, r1); else st_ll(dst, r0, r1, 0u, tag + 1);
      }
      PROFW(L && tid == 0, 28);
    }
    if (L == 0) {
      PROFX(tid == 0, 22);
      FRESH();
      mbar_wait(BAR(B_STG), 1); mbar_wait(BAR(B_STG + 1), 0); mbar_wait(BAR(B_STG + 2), 0);
      const uint32_t bd = (64 + (HV >> 4) + uni(bid & 3) * 32) | 0x10000u;
      uint4 x, y; poll_ll2(&P.g->x2[bi][tid], &P.g->x2[bi][tid + 128], 0xffffffffu, tag + 1, x, y);
      x.z = y.x; x.w = y.y;
      put_bf16(x, sb + HV + tid * 8);
      bar_sync(2, 128);
      PROFX(tid == 0, 30);
      float d0[4] = {0.f, 0.f, 0.f, 0.f}, d1[4] = {0.f, 0.f, 0.f, 0.f}, d2[4] = {0.f, 0.f, 0.f, 0.f};
      #pragma unroll 1
      for (int ks = 0; ks < 8; ks++) {
        const uint32_t ad = (64 + (STG >> 4) + ks * 128) | (64u << 16);
        wg_fence();
        wgmma_ss_n8<0, 1>(d0, mkd<HI64>(ad), mkd<8>(bd + ks * 4), 1);
        wgmma_ss_n8<0, 1>(d1, mkd<HI64>(ad + 1024), mkd<8>(bd + ks * 4), 1);
        wgmma_ss_n8<0, 1>(d2, mkd<HI64>(ad + 2048), mkd<8>(bd + ks * 4), 1);
        wg_commit();
      }
      uint4* dst = &P.g->patch[bid][(wq & 1) * 32 + (lane >> 2) * 2 + (wq >> 1)];
      wg_wait<0>(); keep(d0); keep(d1); keep(d2);
      if ((lane & 3) == (wq >> 1)) { st_ll(dst, UI(d0[0]), UI(d1[0]), UI(d2[0]), tag + 1); st_ll(dst + 16, UI(d0[2]), UI(d1[2]), UI(d2[2]), tag + 1); }
      PROFX(tid == 0, 31);
      if ((unsigned)(bi - (idx >> 8)) < 2u) {
        if (wq == (bc & 3)) sts64f(sb + X2SEG + lane * 8, FL(bc < 4 ? x.x : x.z), FL(bc < 4 ? x.y : x.w));
        float s1 = 0.f, s2 = 0.f;
        sum8(x, s1, s2);
        #pragma unroll
        for (int o = 16; o; o >>= 1) { s1 += __shfl_xor_sync(0xffffffffu, s1, o); s2 += __shfl_xor_sync(0xffffffffu, s2, o); }
        sts64f(sb + RED + wq * 8, s1, s2);
        bar_sync(2, 128);
        x = lds128(sb + RED); y = lds128(sb + RED + 16);
        const float m = ((FL(x.x) + FL(x.z)) + (FL(y.x) + FL(y.z))) * (1.f / 1024.f);
        const float rs = rsqrtf(fmaxf(fmaf(-m, m, ((FL(x.y) + FL(x.w)) + (FL(y.y) + FL(y.w))) * (1.f / 1024.f)), 0.f) + LN_EPS);
        const uint32_t ca = sb + CS + (tid >> 4) * 32 + (tid & 1) * 16 + (tid & 14);
        const float cq = FL(lds16(ca) << 16) * m, ck = FL(lds16(ca + 256) << 16) * m, cv = FL(lds16(ca + 512) << 16) * m;
        const float4 z = poll_sum4(&P.g->patch[bp * 8 + (tid >> 6) * 4][tid & 63], 64, tag + 1);
        float q = z.x + cq, k = z.y + ck, v = z.z + cv;
        q += __shfl_xor_sync(0xffffffffu, q, 1); k += __shfl_xor_sync(0xffffffffu, k, 1); v += __shfl_xor_sync(0xffffffffu, v, 1);
        const uint32_t d = sb + PATCH + (tid & ~1), kv = pack_bf16(k * rs, v * rs);
        sts16(d, pack_bf16(q * (rs * QSCALE), 0.f)); sts16(d + 128, kv); sts16(d + 256, kv >> 16);
      }
    }
  }
  if (bid == 0 && tid == 0) P.g->epoch = lds32(sb + INFO2 + 16) + 1;
  #undef blk
  #undef bid
  #undef fid
  #undef bi
  #undef bp
  #undef bc
  #undef FRESH
  #undef lane
  #undef wq
}

__global__ void __cluster_dims__(2, 1, 1) __launch_bounds__(512, 1) fused_kernel(const __grid_constant__ Params P) {
  extern __shared__ __align__(1024) uint8_t smem_raw[];
  const uint32_t sb = smem_u32(smem_raw);
  PROFT(threadIdx.x == 0, 0);
  if (threadIdx.x < 32) { if (elect()) {
    for (int s = 0; s < 3; s++) mbar_init(BAR(B_FULLQ + s), 1);
    asm volatile("fence.mbarrier_init.release.cluster;" ::: "memory");
    #pragma unroll 1
    for (int s = 0; s < 3; s++) {
      mbar_expect_tx(BAR(B_FULLQ + s), 57344);
      tma_2d(sb + qa_off(s), &P.mX, s * 64, (BID >> 4) * 256, BAR(B_FULLQ + s));
      tma_3d(sb + qb_off(s), &P.mWq, (BID & 15) * 64, s * 64, 0, BAR(B_FULLQ + s));
    }
    if ((sb & 0x3FFFFu) != 1024) __trap();
  } } else if (threadIdx.x == 480) {
    asm volatile("prefetch.tensormap [%0];" :: "l"(&P.mWq) : "memory");
  } else if (threadIdx.x >= 32 && !(threadIdx.x & 28) && (threadIdx.x >> 3) + (threadIdx.x & 3) <= B_COUNT + 1) {
    int b = (threadIdx.x >> 3) + (threadIdx.x & 3) - 1;
    if (b == B_COUNT) b = B_ROW;
    const uint32_t cnt = b < B_XFREE ? (b == B_OFREE ? 1 : 2) : (b < B_KVRDY ? 3 : (b < B_KVFULL || b == B_PAR ? 4 : (b == B_PFREE ? 2 : 1)));
    mbar_init(BAR(b), cnt);
    asm volatile("fence.mbarrier_init.release.cluster;" ::: "memory");
  }
  __syncthreads();
  asm volatile("barrier.cluster.arrive.relaxed.aligned;" ::: "memory");
  const int wg = __shfl_sync(0xffffffffu, threadIdx.x >> 7, 0);
  if (wg < 2) { reg_inc<224>(); consumer(P, sb, wg); }
  else if (wg == 2) { reg_dec<40>(); aux(P, sb); }
  else {
    reg_dec<24>();
    asm volatile("barrier.cluster.wait.aligned;" ::: "memory");
    const int w = __shfl_sync(0xffffffffu, (threadIdx.x >> 5) & 3, 0);
    if (w == 0) loader(P, sb);
    else if (w < 3) storer(P, sb, w - 1);
    else if (elect()) stager(P, sb);
  }
}

typedef CUresult (*EncFn)(CUtensorMap*, CUtensorMapDataType, cuuint32_t, void*, const cuuint64_t*, const cuuint64_t*, const cuuint32_t*, const cuuint32_t*,
                          CUtensorMapInterleave, CUtensorMapSwizzle, CUtensorMapL2promotion, CUtensorMapFloatOOBfill);
static void mk_map(EncFn enc, CUtensorMap* m, const void* ptr, int rank, const cuuint64_t* dims, const cuuint64_t* strides, const cuuint32_t* box,
                   CUtensorMapSwizzle sw, CUtensorMapL2promotion pr) {
  cuuint32_t es[5] = {1, 1, 1, 1, 1};
  enc(m, CU_TENSOR_MAP_DATA_TYPE_BFLOAT16, rank, (void*)ptr, dims, strides, box, es, CU_TENSOR_MAP_INTERLEAVE_NONE, sw, pr, CU_TENSOR_MAP_FLOAT_OOB_FILL_NONE);
}
extern "C" void kernel_launch(void* const* d_in, const int* in_sizes, int n_in, void* d_out, int out_size) {
  (void)in_sizes; (void)n_in; (void)out_size;
  void* fn = nullptr; cudaDriverEntryPointQueryResult q;
  cudaGetDriverEntryPoint("cuTensorMapEncodeTiled", &fn, cudaEnableDefault, &q);
  EncFn enc = (EncFn)fn;
  cudaFuncSetAttribute(fused_kernel, cudaFuncAttributeMaxDynamicSharedMemorySize, SMEM_BYTES);
  Params P;
  const CUtensorMapSwizzle S128 = CU_TENSOR_MAP_SWIZZLE_128B, S64 = CU_TENSOR_MAP_SWIZZLE_64B, S0 = CU_TENSOR_MAP_SWIZZLE_NONE;
  const CUtensorMapL2promotion L256 = CU_TENSOR_MAP_L2_PROMOTION_L2_256B, L128 = CU_TENSOR_MAP_L2_PROMOTION_L2_128B;
  { cuuint64_t d[2] = {1024, 2048}, s[1] = {2048}; cuuint32_t b[2] = {64, 256}, bh[2] = {64, 128};
    mk_map(enc, &P.mX, d_in[0], 2, d, s, b, S128, L256); mk_map(enc, &P.mXh, d_in[0], 2, d, s, bh, S128, L256); }
  { cuuint64_t d[3] = {1024, 1024, 3}, s[2] = {6144, 2048}; cuuint32_t b[3] = {64, 64, 3}; mk_map(enc, &P.mWq, d_in[1], 3, d, s, b, S128, L256); }
  { cuuint64_t d[5] = {64, 32, 2, 16, 16}, s[4] = {2048, 65536, 131072, 128}; cuuint32_t b[5] = {64, 32, 1, 2, 2}; mk_map(enc, &P.mWo, d_in[2], 5, d, s, b, S128, L256); }
  { cuuint64_t d[2] = {3584, 1024}, s[1] = {7168}; cuuint32_t b[2] = {32, 128};
    mk_map(enc, &P.mWg, d_in[5], 2, d, s, b, S64, L128); mk_map(enc, &P.mWu, d_in[6], 2, d, s, b, S64, L128); }
  { cuuint64_t d[2] = {3072, 1024}, s[1] = {6144}; cuuint32_t b[2] = {32, 256}; mk_map(enc, &P.mWp, d_in[1], 2, d, s, b, S64, L128); }
  { cuuint64_t d[3] = {256, 3584, 4}, s[2] = {2048, 512}; cuuint32_t b[3] = {256, 8, 4}; mk_map(enc, &P.mWd, d_in[7], 3, d, s, b, S0, L128); }
  P.x0 = (const bf16*)d_in[0]; P.wqkv = (const bf16*)d_in[1]; P.wo = (const bf16*)d_in[2]; P.wr = (const bf16*)d_in[4]; P.wg = (const bf16*)d_in[5]; P.wu = (const bf16*)d_in[6]; P.wd = (const bf16*)d_in[7];
  P.out = (bf16*)d_out;
  cudaGetSymbolAddress((void**)&P.g, g_scr);
  for (int b = 0; b < 128; b++) {
    int j = b >> 1, quad = j < 4 ? 0 : (j < 36 ? 1 + (j - 4) % 8 : 9 + (j - 36) % 7), pos = j < 4 ? j : (j < 36 ? (j - 4) / 8 : (j - 36) / 7);
    int bid = ((quad >> 2) * 2 + (pos >> 1)) * 16 + ((quad & 3) * 2 + (pos & 1)) * 2 + (b & 1);
    int e = pos * 2 + (b & 1), fid = e < 7 ? quad * 7 + e : 112 + quad;
    P.map[b] = bid | fid << 8;
  }
  fused_kernel<<<128, 512, SMEM_BYTES>>>(P);
}
```

```cpp
#include <cuda_runtime.h>
#include <cuda_bf16.h>
#include <cuda.h>
#include <stdint.h>
#include <stddef.h>
typedef __nv_bfloat16 bf16;

template<int TB, int TA = 0> __device__ __forceinline__ void wgmma_ss_n192(float (&d)[96], uint64_t da, uint64_t db, int scale_d) {
  asm volatile("{\n.reg .pred p;\nsetp.ne.b32 p, %98, 0;\n"
    "wgmma.mma_async.sync.aligned.m64n192k16.f32.bf16.bf16 {%0, %1, %2, %3, %4, %5, %6, %7, %8, %9, %10, %11, %12, %13, %14, %15, %16, %17, %18, %19, %20, %21, %22, %23, %24, %25, %26, %27, %28, %29, %30, %31, %32, %33, %34, %35, %36, %37, %38, %39, %40, %41, %42, %43, %44, %45, %46, %47, %48, %49, %50, %51, %52, %53, %54, %55, %56, %57, %58, %59, %60, %61, %62, %63, %64, %65, %66, %67, %68, %69, %70, %71, %72, %73, %74, %75, %76, %77, %78, %79, %80, %81, %82, %83, %84, %85, %86, %87, %88, %89, %90, %91, %92, %93, %94, %95}, %96, %97, p, 1, 1, %100, %99;\n}\n"
    : "+f"(d[0]), "+f"(d[1]), "+f"(d[2]), "+f"(d[3]), "+f"(d[4]), "+f"(d[5]), "+f"(d[6]), "+f"(d[7]), "+f"(d[8]), "+f"(d[9]), "+f"(d[10]), "+f"(d[11]), "+f"(d[12]), "+f"(d[13]), "+f"(d[14]), "+f"(d[15]), "+f"(d[16]), "+f"(d[17]), "+f"(d[18]), "+f"(d[19]), "+f"(d[20]), "+f"(d[21]), "+f"(d[22]), "+f"(d[23]), "+f"(d[24]), "+f"(d[25]), "+f"(d[26]), "+f"(d[27]), "+f"(d[28]), "+f"(d[29]), "+f"(d[30]), "+f"(d[31]), "+f"(d[32]), "+f"(d[33]), "+f"(d[34]), "+f"(d[35]), "+f"(d[36]), "+f"(d[37]), "+f"(d[38]), "+f"(d[39]), "+f"(d[40]), "+f"(d[41]), "+f"(d[42]), "+f"(d[43]), "+f"(d[44]), "+f"(d[45]), "+f"(d[46]), "+f"(d[47]), "+f"(d[48]), "+f"(d[49]), "+f"(d[50]), "+f"(d[51]), "+f"(d[52]), "+f"(d[53]), "+f"(d[54]), "+f"(d[55]), "+f"(d[56]), "+f"(d[57]), "+f"(d[58]), "+f"(d[59]), "+f"(d[60]), "+f"(d[61]), "+f"(d[62]), "+f"(d[63]), "+f"(d[64]), "+f"(d[65]), "+f"(d[66]), "+f"(d[67]), "+f"(d[68]), "+f"(d[69]), "+f"(d[70]), "+f"(d[71]), "+f"(d[72]), "+f"(d[73]), "+f"(d[74]), "+f"(d[75]), "+f"(d[76]), "+f"(d[77]), "+f"(d[78]), "+f"(d[79]), "+f"(d[80]), "+f"(d[81]), "+f"(d[82]), "+f"(d[83]), "+f"(d[84]), "+f"(d[85]), "+f"(d[86]), "+f"(d[87]), "+f"(d[88]), "+f"(d[89]), "+f"(d[90]), "+f"(d[91]), "+f"(d[92]), "+f"(d[93]), "+f"(d[94]), "+f"(d[95])
    : "l"(da), "l"(db), "r"(scale_d), "n"(TB), "n"(TA));
}

template<int TB> __device__ __forceinline__ void wgmma_rs_n192(float (&d)[96], uint32_t a0, uint32_t a1, uint32_t a2, uint32_t a3, uint64_t db, int scale_d) {
  asm volatile("{\n.reg .pred p;\nsetp.ne.b32 p, %101, 0;\n"
    "wgmma.mma_async.sync.aligned.m64n192k16.f32.bf16.bf16 {%0, %1, %2, %3, %4, %5, %6, %7, %8, %9, %10, %11, %12, %13, %14, %15, %16, %17, %18, %19, %20, %21, %22, %23, %24, %25, %26, %27, %28, %29, %30, %31, %32, %33, %34, %35, %36, %37, %38, %39, %40, %41, %42, %43, %44, %45, %46, %47, %48, %49, %50, %51, %52, %53, %54, %55, %56, %57, %58, %59, %60, %61, %62, %63, %64, %65, %66, %67, %68, %69, %70, %71, %72, %73, %74, %75, %76, %77, %78, %79, %80, %81, %82, %83, %84, %85, %86, %87, %88, %89, %90, %91, %92, %93, %94, %95}, {%96, %97, %98, %99}, %100, p, 1, 1, %102;\n}\n"
    : "+f"(d[0]), "+f"(d[1]), "+f"(d[2]), "+f"(d[3]), "+f"(d[4]), "+f"(d[5]), "+f"(d[6]), "+f"(d[7]), "+f"(d[8]), "+f"(d[9]), "+f"(d[10]), "+f"(d[11]), "+f"(d[12]), "+f"(d[13]), "+f"(d[14]), "+f"(d[15]), "+f"(d[16]), "+f"(d[17]), "+f"(d[18]), "+f"(d[19]), "+f"(d[20]), "+f"(d[21]), "+f"(d[22]), "+f"(d[23]), "+f"(d[24]), "+f"(d[25]), "+f"(d[26]), "+f"(d[27]), "+f"(d[28]), "+f"(d[29]), "+f"(d[30]), "+f"(d[31]), "+f"(d[32]), "+f"(d[33]), "+f"(d[34]), "+f"(d[35]), "+f"(d[36]), "+f"(d[37]), "+f"(d[38]), "+f"(d[39]), "+f"(d[40]), "+f"(d[41]), "+f"(d[42]), "+f"(d[43]), "+f"(d[44]), "+f"(d[45]), "+f"(d[46]), "+f"(d[47]), "+f"(d[48]), "+f"(d[49]), "+f"(d[50]), "+f"(d[51]), "+f"(d[52]), "+f"(d[53]), "+f"(d[54]), "+f"(d[55]), "+f"(d[56]), "+f"(d[57]), "+f"(d[58]), "+f"(d[59]), "+f"(d[60]), "+f"(d[61]), "+f"(d[62]), "+f"(d[63]), "+f"(d[64]), "+f"(d[65]), "+f"(d[66]), "+f"(d[67]), "+f"(d[68]), "+f"(d[69]), "+f"(d[70]), "+f"(d[71]), "+f"(d[72]), "+f"(d[73]), "+f"(d[74]), "+f"(d[75]), "+f"(d[76]), "+f"(d[77]), "+f"(d[78]), "+f"(d[79]), "+f"(d[80]), "+f"(d[81]), "+f"(d[82]), "+f"(d[83]), "+f"(d[84]), "+f"(d[85]), "+f"(d[86]), "+f"(d[87]), "+f"(d[88]), "+f"(d[89]), "+f"(d[90]), "+f"(d[91]), "+f"(d[92]), "+f"(d[93]), "+f"(d[94]), "+f"(d[95])
    : "r"(a0), "r"(a1), "r"(a2), "r"(a3), "l"(db), "r"(scale_d), "n"(TB));
}

template<int TB, int TA = 0> __device__ __forceinline__ void wgmma_ss_n128(float (&d)[64], uint64_t da, uint64_t db, int scale_d) {
  asm volatile("{\n.reg .pred p;\nsetp.ne.b32 p, %66, 0;\n"
    "wgmma.mma_async.sync.aligned.m64n128k16.f32.bf16.bf16 {%0, %1, %2, %3, %4, %5, %6, %7, %8, %9, %10, %11, %12, %13, %14, %15, %16, %17, %18, %19, %20, %21, %22, %23, %24, %25, %26, %27, %28, %29, %30, %31, %32, %33, %34, %35, %36, %37, %38, %39, %40, %41, %42, %43, %44, %45, %46, %47, %48, %49, %50, %51, %52, %53, %54, %55, %56, %57, %58, %59, %60, %61, %62, %63}, %64, %65, p, 1, 1, %68, %67;\n}\n"
    : "+f"(d[0]), "+f"(d[1]), "+f"(d[2]), "+f"(d[3]), "+f"(d[4]), "+f"(d[5]), "+f"(d[6]), "+f"(d[7]), "+f"(d[8]), "+f"(d[9]), "+f"(d[10]), "+f"(d[11]), "+f"(d[12]), "+f"(d[13]), "+f"(d[14]), "+f"(d[15]), "+f"(d[16]), "+f"(d[17]), "+f"(d[18]), "+f"(d[19]), "+f"(d[20]), "+f"(d[21]), "+f"(d[22]), "+f"(d[23]), "+f"(d[24]), "+f"(d[25]), "+f"(d[26]), "+f"(d[27]), "+f"(d[28]), "+f"(d[29]), "+f"(d[30]), "+f"(d[31]), "+f"(d[32]), "+f"(d[33]), "+f"(d[34]), "+f"(d[35]), "+f"(d[36]), "+f"(d[37]), "+f"(d[38]), "+f"(d[39]), "+f"(d[40]), "+f"(d[41]), "+f"(d[42]), "+f"(d[43]), "+f"(d[44]), "+f"(d[45]), "+f"(d[46]), "+f"(d[47]), "+f"(d[48]), "+f"(d[49]), "+f"(d[50]), "+f"(d[51]), "+f"(d[52]), "+f"(d[53]), "+f"(d[54]), "+f"(d[55]), "+f"(d[56]), "+f"(d[57]), "+f"(d[58]), "+f"(d[59]), "+f"(d[60]), "+f"(d[61]), "+f"(d[62]), "+f"(d[63])
    : "l"(da), "l"(db), "r"(scale_d), "n"(TB), "n"(TA));
}

template<int TB, int TA = 0> __device__ __forceinline__ void wgmma_ss_n64(float (&d)[32], uint64_t da, uint64_t db, int scale_d) {
  asm volatile("{\n.reg .pred p;\nsetp.ne.b32 p, %34, 0;\n"
    "wgmma.mma_async.sync.aligned.m64n64k16.f32.bf16.bf16 {%0, %1, %2, %3, %4, %5, %6, %7, %8, %9, %10, %11, %12, %13, %14, %15, %16, %17, %18, %19, %20, %21, %22, %23, %24, %25, %26, %27, %28, %29, %30, %31}, %32, %33, p, 1, 1, %36, %35;\n}\n"
    : "+f"(d[0]), "+f"(d[1]), "+f"(d[2]), "+f"(d[3]), "+f"(d[4]), "+f"(d[5]), "+f"(d[6]), "+f"(d[7]), "+f"(d[8]), "+f"(d[9]), "+f"(d[10]), "+f"(d[11]), "+f"(d[12]), "+f"(d[13]), "+f"(d[14]), "+f"(d[15]), "+f"(d[16]), "+f"(d[17]), "+f"(d[18]), "+f"(d[19]), "+f"(d[20]), "+f"(d[21]), "+f"(d[22]), "+f"(d[23]), "+f"(d[24]), "+f"(d[25]), "+f"(d[26]), "+f"(d[27]), "+f"(d[28]), "+f"(d[29]), "+f"(d[30]), "+f"(d[31])
    : "l"(da), "l"(db), "r"(scale_d), "n"(TB), "n"(TA));
}

template<int TB, int TA = 0> __device__ __forceinline__ void wgmma_ss_n8(float (&d)[4], uint64_t da, uint64_t db, int scale_d) {
  asm volatile("{\n.reg .pred p;\nsetp.ne.b32 p, %6, 0;\n"
    "wgmma.mma_async.sync.aligned.m64n8k16.f32.bf16.bf16 {%0, %1, %2, %3}, %4, %5, p, 1, 1, %8, %7;\n}\n"
    : "+f"(d[0]), "+f"(d[1]), "+f"(d[2]), "+f"(d[3])
    : "l"(da), "l"(db), "r"(scale_d), "n"(TB), "n"(TA));
}

template<int TB> __device__ __forceinline__ void wgmma_rs_n40(float (&d)[20], uint32_t a0, uint32_t a1, uint32_t a2, uint32_t a3, uint64_t db, int scale_d) {
  asm volatile("{\n.reg .pred p;\nsetp.ne.b32 p, %25, 0;\n"
    "wgmma.mma_async.sync.aligned.m64n40k16.f32.bf16.bf16 {%0, %1, %2, %3, %4, %5, %6, %7, %8, %9, %10, %11, %12, %13, %14, %15, %16, %17, %18, %19}, {%20, %21, %22, %23}, %24, p, 1, 1, %26;\n}\n"
    : "+f"(d[0]), "+f"(d[1]), "+f"(d[2]), "+f"(d[3]), "+f"(d[4]), "+f"(d[5]), "+f"(d[6]), "+f"(d[7]), "+f"(d[8]), "+f"(d[9]), "+f"(d[10]), "+f"(d[11]), "+f"(d[12]), "+f"(d[13]), "+f"(d[14]), "+f"(d[15]), "+f"(d[16]), "+f"(d[17]), "+f"(d[18]), "+f"(d[19])
    : "r"(a0), "r"(a1), "r"(a2), "r"(a3), "l"(db), "r"(scale_d), "n"(TB));
}

#define DEVI __device__ __forceinline__
DEVI uint32_t smem_u32(const void* p) { return (uint32_t)__cvta_generic_to_shared(p); }
DEVI void mbar_init(uint32_t bar, uint32_t cnt) { asm volatile("mbarrier.init.shared::cta.b64 [%0], %1;" :: "r"(bar), "r"(cnt)); }
DEVI void mbar_expect_tx(uint32_t bar, uint32_t bytes) { asm volatile("mbarrier.arrive.expect_tx.shared::cta.b64 _, [%0], %1;" :: "r"(bar), "r"(bytes) : "memory"); }
DEVI void mbar_arrive(uint32_t bar) { asm volatile("mbarrier.arrive.shared::cta.b64 _, [%0];" :: "r"(bar) : "memory"); }
DEVI void mbar_arrive_peer(uint32_t bar) {
  asm volatile("{\n.reg .b32 ra;\nmapa.shared::cluster.u32 ra, %0, %1;\nmbarrier.arrive.shared::cluster.b64 _, [ra];\n}" :: "r"(bar), "r"((blockIdx.x & 1) ^ 1) : "memory");
}
DEVI void bulk_s2peer(uint32_t a, uint32_t bytes, uint32_t bar) {
  asm volatile("{\n.reg .b32 ra, rb;\nmapa.shared::cluster.u32 ra, %0, %3;\nmapa.shared::cluster.u32 rb, %2, %3;\n"
               "cp.async.bulk.shared::cluster.shared::cta.mbarrier::complete_tx::bytes [ra], [%0], %1, [rb];\n}"
               :: "r"(a), "r"(bytes), "r"(bar), "r"((blockIdx.x & 1) ^ 1) : "memory");
}
DEVI void mbar_wait(uint32_t bar, uint32_t parity) {
  asm volatile("{\n.reg .pred p;\nLW:\nmbarrier.try_wait.parity.shared::cta.b64 p, [%0], %1;\n@!p bra LW;\n}" :: "r"(bar), "r"(parity) : "memory");
}
DEVI uint32_t mbar_test(uint32_t bar, uint32_t parity) {
  uint32_t r; asm volatile("{\n.reg .pred p;\nmbarrier.test_wait.parity.shared::cta.b64 p, [%1], %2;\nselp.u32 %0, 1, 0, p;\n}" : "=r"(r) : "r"(bar), "r"(parity) : "memory"); return r;
}
DEVI void mbar_wait_b(uint32_t bar, uint32_t parity) {
  asm volatile("{\n.reg .pred p;\n.reg .u32 it;\nmov.u32 it, 0;\nLW:\nmbarrier.try_wait.parity.shared::cta.b64 p, [%0], %1;\n@p bra LD;\n"
               "add.u32 it, it, 1;\nsetp.lt.u32 p, it, 0x1000000;\n@p bra LW;\ntrap;\nLD:\n}" :: "r"(bar), "r"(parity) : "memory");
}
DEVI void tma_2d(uint32_t dst, const CUtensorMap* m, int c0, int c1, uint32_t bar) {
  asm volatile("cp.async.bulk.tensor.2d.shared::cluster.global.mbarrier::complete_tx::bytes [%0], [%1, {%3, %4}], [%2];"
    :: "r"(dst), "l"(m), "r"(bar), "r"(c0), "r"(c1) : "memory");
}
DEVI void tma_3d(uint32_t dst, const CUtensorMap* m, int c0, int c1, int c2, uint32_t bar) {
  asm volatile("cp.async.bulk.tensor.3d.shared::cluster.global.mbarrier::complete_tx::bytes [%0], [%1, {%3, %4, %5}], [%2];"
    :: "r"(dst), "l"(m), "r"(bar), "r"(c0), "r"(c1), "r"(c2) : "memory");
}
#define POL_EF POL_FIRST
constexpr uint64_t POL_FIRST = 0x12F0000000000000ull, POL_NORMAL = 0x1000000000000000ull;
DEVI void tma_2d_h(uint32_t dst, const CUtensorMap* m, int c0, int c1, uint32_t bar, uint64_t pol) {
  asm volatile("cp.async.bulk.tensor.2d.shared::cluster.global.mbarrier::complete_tx::bytes.L2::cache_hint [%0], [%1, {%3, %4}], [%2], %5;"
    :: "r"(dst), "l"(m), "r"(bar), "r"(c0), "r"(c1), "l"(pol) : "memory");
}
DEVI void tma_3d_h(uint32_t dst, const CUtensorMap* m, int c0, int c1, int c2, uint32_t bar, uint64_t pol) {
  asm volatile("cp.async.bulk.tensor.3d.shared::cluster.global.mbarrier::complete_tx::bytes.L2::cache_hint [%0], [%1, {%3, %4, %5}], [%2], %6;"
    :: "r"(dst), "l"(m), "r"(bar), "r"(c0), "r"(c1), "r"(c2), "l"(pol) : "memory");
}
DEVI void bulk_g2s_h(uint32_t s, const void* g, uint32_t bytes, uint32_t bar, uint64_t pol = POL_EF) {
  asm volatile("cp.async.bulk.shared::cluster.global.mbarrier::complete_tx::bytes.L2::cache_hint [%0], [%1], %2, [%3], %4;"
    :: "r"(s), "l"(g), "r"(bytes), "r"(bar), "l"(pol) : "memory");
}
DEVI void tma_5d(uint32_t dst, const CUtensorMap* m, int c0, int c1, int c2, int c3, int c4, uint32_t bar, uint64_t pol) {
  asm volatile("cp.async.bulk.tensor.5d.shared::cluster.global.mbarrier::complete_tx::bytes.L2::cache_hint [%0], [%1, {%3, %4, %5, %6, %7}], [%2], %8;"
    :: "r"(dst), "l"(m), "r"(bar), "r"(c0), "r"(c1), "r"(c2), "r"(c3), "r"(c4), "l"(pol) : "memory");
}
DEVI void tma_prefetch_2d(const CUtensorMap* m, int c0, int c1) {
  asm volatile("cp.async.bulk.prefetch.tensor.2d.L2.global.tile [%0, {%1, %2}];" :: "l"(m), "r"(c0), "r"(c1) : "memory");
}
DEVI void tma_prefetch_3d(const CUtensorMap* m, int c0, int c1, int c2) {
  asm volatile("cp.async.bulk.prefetch.tensor.3d.L2.global.tile [%0, {%1, %2, %3}];" :: "l"(m), "r"(c0), "r"(c1), "r"(c2) : "memory");
}
DEVI void bulk_prefetch(const void* g, uint32_t bytes) { asm volatile("cp.async.bulk.prefetch.L2.global [%0], %1;" :: "l"(g), "r"(bytes) : "memory"); }
DEVI void bulk_g2s(uint32_t s, const void* g, uint32_t bytes, uint32_t bar) {
  asm volatile("cp.async.bulk.shared::cluster.global.mbarrier::complete_tx::bytes [%0], [%1], %2, [%3];" :: "r"(s), "l"(g), "r"(bytes), "r"(bar) : "memory");
}
DEVI void bulk_s2g(void* g, uint32_t s, uint32_t bytes, uint64_t pol = POL_NORMAL) {
  asm volatile("cp.async.bulk.global.shared::cta.bulk_group.L2::cache_hint [%0], [%1], %2, %3;\ncp.async.bulk.commit_group;" :: "l"(g), "r"(s), "r"(bytes), "l"(pol) : "memory");
}
template<int N> DEVI void bulk_wait() { asm volatile("cp.async.bulk.wait_group %0;" :: "n"(N) : "memory"); }
DEVI void fence_async_smem() { asm volatile("fence.proxy.async.shared::cta;" ::: "memory"); }
DEVI void fence_async_glob() { asm volatile("fence.proxy.async.global;" ::: "memory"); }
DEVI unsigned ld_rlx(const unsigned* p) { unsigned v; asm volatile("ld.relaxed.gpu.global.u32 %0, [%1];" : "=r"(v) : "l"(p) : "memory"); return v; }
DEVI void st_rlx(unsigned* p, unsigned v) { asm volatile("st.relaxed.gpu.global.u32 [%0], %1;" :: "l"(p), "r"(v) : "memory"); }
DEVI uint2 ldg_stream(const uint2* p) { uint2 v; asm volatile("ld.global.nc.L1::no_allocate.v2.u32 {%0, %1}, [%2];" : "=r"(v.x), "=r"(v.y) : "l"(p)); return v; }
DEVI void fence_rel() { asm volatile("fence.release.gpu;" ::: "memory"); }
DEVI uint4 ld_ll(const uint4* p) {
  uint4 v;
  asm volatile("{\n.reg .b128 t;\n.reg .b64 a, b;\nld.relaxed.gpu.global.b128 t, [%4];\nmov.b128 {a, b}, t;\nmov.b64 {%0, %1}, a;\nmov.b64 {%2, %3}, b;\n}"
               : "=r"(v.x), "=r"(v.y), "=r"(v.z), "=r"(v.w) : "l"(p) : "memory");
  return v;
}
DEVI void st_ll(uint4* p, uint32_t x, uint32_t y, uint32_t z, uint32_t w) {
  asm volatile("{\n.reg .b128 t;\n.reg .b64 a, b;\nmov.b64 a, {%1, %2};\nmov.b64 b, {%3, %4};\nmov.b128 t, {a, b};\nst.relaxed.gpu.global.b128 [%0], t;\n}"
               :: "l"(p), "r"(x), "r"(y), "r"(z), "r"(w) : "memory");
}
#define SPIN_MAX 0x1000000
DEVI uint4 poll_ll(const uint4* p, uint32_t mask, uint32_t tag) {
  uint4 v; int it = 0;
  do { v = ld_ll(p); if (++it > SPIN_MAX) __trap(); } while (!__all_sync(0xffffffffu, (v.w & mask) == tag));
  return v;
}
DEVI void poll_ll2(const uint4* p, const uint4* q, uint32_t mask, uint32_t tag, uint4& a, uint4& b) {
  int it = 0;
  do { a = ld_ll(p); b = ld_ll(q); if (++it > SPIN_MAX) __trap(); } while (!__all_sync(0xffffffffu, (a.w & mask) == tag && (b.w & mask) == tag));
}
DEVI float4 poll_sum4(const uint4* src, int stride, uint32_t tag) {
  uint4 v0, v1, v2, v3; int it = 0;
  do { v0 = ld_ll(src); v1 = ld_ll(src + stride); v2 = ld_ll(src + 2 * stride); v3 = ld_ll(src + 3 * stride); if (++it > SPIN_MAX) __trap(); }
  while (!__all_sync(0xffffffffu, v0.w == tag && v1.w == tag && v2.w == tag && v3.w == tag));
  #define S4(f) ((__uint_as_float(v0.f) + __uint_as_float(v1.f)) + (__uint_as_float(v2.f) + __uint_as_float(v3.f)))
  return make_float4(S4(x), S4(y), S4(z), 0.f);
  #undef S4
}
DEVI void bar_sync(int id, int n) { asm volatile("bar.sync %0, %1;" :: "r"(id), "r"(n) : "memory"); }
DEVI void bar_arrive(int id, int n) { asm volatile("bar.arrive %0, %1;" :: "r"(id), "r"(n) : "memory"); }
DEVI void wg_fence() { asm volatile("wgmma.fence.sync.aligned;" ::: "memory"); }
DEVI void wg_commit() { asm volatile("wgmma.commit_group.sync.aligned;" ::: "memory"); }
template<int N> DEVI void wg_wait() { asm volatile("wgmma.wait_group.sync.aligned %0;" :: "n"(N) : "memory"); }
template<int N> DEVI void reg_inc() { asm volatile("setmaxnreg.inc.sync.aligned.u32 %0;" :: "n"(N)); }
template<int N> DEVI void reg_dec() { asm volatile("setmaxnreg.dec.sync.aligned.u32 %0;" :: "n"(N)); }
DEVI float ex2f(float x) { float y; asm("ex2.approx.ftz.f32 %0, %1;" : "=f"(y) : "f"(x)); return y; }
DEVI uint32_t pack_bf16(float lo, float hi) { uint32_t r; asm("cvt.rn.bf16x2.f32 %0, %1, %2;" : "=r"(r) : "f"(hi), "f"(lo)); return r; }
DEVI float bf_lo(uint32_t v) { return __uint_as_float(v << 16); }
DEVI float bf_hi(uint32_t v) { return __uint_as_float(v & 0xffff0000u); }
DEVI float bf_round(float x) { return bf_lo(pack_bf16(x, 0.f)); }
DEVI void stsm_x4(uint32_t addr, uint32_t a, uint32_t b, uint32_t c, uint32_t d) {
  asm volatile("stmatrix.sync.aligned.m8n8.x4.shared.b16 [%0], {%1,%2,%3,%4};" :: "r"(addr), "r"(a), "r"(b), "r"(c), "r"(d) : "memory");
}
DEVI void ldsm_x4(uint32_t addr, uint32_t& a, uint32_t& b, uint32_t& c, uint32_t& d) {
  asm volatile("ldmatrix.sync.aligned.m8n8.x4.shared.b16 {%0,%1,%2,%3}, [%4];" : "=r"(a), "=r"(b), "=r"(c), "=r"(d) : "r"(addr) : "memory");
}
DEVI uint4 lds128(uint32_t a) { uint4 v; asm volatile("ld.shared.v4.u32 {%0,%1,%2,%3}, [%4];" : "=r"(v.x), "=r"(v.y), "=r"(v.z), "=r"(v.w) : "r"(a) : "memory"); return v; }
DEVI void sts128(uint32_t a, uint4 v) { asm volatile("st.shared.v4.u32 [%0], {%1,%2,%3,%4};" :: "r"(a), "r"(v.x), "r"(v.y), "r"(v.z), "r"(v.w) : "memory"); }
DEVI float2 lds64f(uint32_t a) { float2 v; asm volatile("ld.shared.v2.f32 {%0,%1}, [%2];" : "=f"(v.x), "=f"(v.y) : "r"(a) : "memory"); return v; }
DEVI void sts64f(uint32_t a, float x, float y) { asm volatile("st.shared.v2.f32 [%0], {%1,%2};" :: "r"(a), "f"(x), "f"(y) : "memory"); }
DEVI uint32_t lds32(uint32_t a) { uint32_t v; asm volatile("ld.shared.u32 %0, [%1];" : "=r"(v) : "r"(a) : "memory"); return v; }
DEVI uint32_t lds16(uint32_t a) { unsigned short v; asm volatile("ld.shared.u16 %0, [%1];" : "=h"(v) : "r"(a) : "memory"); return v; }
DEVI float lds32f(uint32_t a) { return __uint_as_float(lds32(a)); }
DEVI void sts32(uint32_t a, uint32_t v) { asm volatile("st.shared.u32 [%0], %1;" :: "r"(a), "r"(v) : "memory"); }
DEVI void sts32f(uint32_t a, float v) { sts32(a, __float_as_uint(v)); }
DEVI void sts16(uint32_t a, uint32_t v) { asm volatile("st.shared.u16 [%0], %1;" :: "r"(a), "h"((unsigned short)v) : "memory"); }
template<int N> DEVI void keep(float (&d)[N]) {
  #pragma unroll
  for (int i = 0; i < N; i++) asm volatile("" : "+f"(d[i]) :: "memory");
}
template<int N> DEVI void keep(uint32_t (&d)[N]) {
  #pragma unroll
  for (int i = 0; i < N; i++) asm volatile("" : "+r"(d[i]) :: "memory");
}
template<uint32_t HI> DEVI uint64_t mkd(uint32_t lo) { uint64_t r; asm("mov.b64 %0, {%1, %2};" : "=l"(r) : "r"(lo), "n"(HI)); return r; }
constexpr uint32_t HI128 = (1u << 30) | (1024 >> 4), HI64 = (2u << 30) | (512 >> 4);
#define VOFF(x) ((uint32_t)(x) * (uint32_t)(1 - 65536))
DEVI bool elect() { uint32_t p; asm volatile("{\n.reg .pred q;\nelect.sync _|q, 0xffffffff;\nselp.u32 %0, 1, 0, q;\n}" : "=r"(p)); return p; }
DEVI void warp_signal(uint32_t bar) { __syncwarp(); if (elect()) mbar_arrive(bar); }

struct Scratch {
  uint4 statP[8][2048];
  uint4 statF[2048];
  uint4 csP[16][8][96];
  uint4 best[8][16];
  uint4 row[16][256];
  uint4 yP[128][112][2];
  uint4 x2[8][256];
  uint4 patch[128][64];
  unsigned flagKV[128][32];
  unsigned flagO[8][32];
  unsigned flagX[8][32];
  unsigned epoch, pad[255];
  uint4 kv[128][4][1024];
  uint4 o[8][2][8][2][1024];
  uint4 x[8][16][2048];
  uint4 zero[1024];
};
static_assert(offsetof(Scratch, kv) % 1024 == 0, "");
__device__ __align__(1024) Scratch g_scr;
#define PROFT(cond, slot)
#define PROFW(cond, slot)
#define PROFD(cond, slot)
#define PROFX(cond, slot)
#define PROFY(cond, slot)

constexpr uint32_t SB0 = 65536, HOLE = 90112, SA2 = 98304, SB1 = 131072, SB2 = 155648, STG = 180224;
constexpr uint32_t KVA = 0, KVB = 98304, QO = 65536;
constexpr uint32_t MISC = 229376, CS = MISC, ONES = MISC + 768, BARS = MISC + 1792, INFO = MISC + 2208, WR = MISC + 2224, X2SEG = MISC + 2736, INFO2 = MISC + 2992, DUMP = MISC + 3040;
constexpr uint32_t PAR = HOLE, HV = HOLE + 2048, RED = HOLE + 6144, PATCH = 196608;
constexpr uint32_t SMEM_BYTES = 232448;
enum { B_FULLQ = 0, B_EMPTYQ = 3, B_FULLW = 6, B_EMPTYW = 12, B_HAFREE = 18, B_OFREE = 20,
       B_XFREE = 21,
       B_KVRDY = 23, B_ORDY = 27, B_XRDY = 35, B_STGE = 39,
       B_KVFULL = 42, B_RES = 46, B_PAR = 47, B_STG = 48, B_PFREE = 51, B_COUNT = 52,
       B_ROW = 154, B_PW = 155 };
#define BAR(x) (sb + BARS + 8 * (x))
DEVI uint32_t qa_off(int s) { return s == 2 ? SA2 : (uint32_t)s * 32768u; }
DEVI uint32_t qb_off(int s) { return s == 0 ? SB0 : (s == 1 ? SB1 : SB2); }
DEVI int kb_order(int bc, int n) {
  const int e = n < 9 ? n - 2 : n - 9;
  return n < 2 ? 2 * bc + n : 2 * (((e < 4 ? e + 4 : e - 4 + (e - 4 >= (bc & 3))) + (bc & 4)) & 7) + (n >= 9);
}
DEVI int wo_order(int bc, int n) { return (n & 8) | ((n + (bc & 6)) & 7); }
DEVI uint32_t w_off(int s) { return (uint32_t)((0x143065 >> (4 * s)) & 7) * 32768u; }
DEVI uint32_t w_par(int n, int s, int L) { return (n >= 6 && n < 12) ^ (s == 5) ^ (s != 2 && L); }
DEVI uint32_t w_aoff(int n, int s) { return n == 3 ? QO : w_off(s); }
DEVI int w_next(int n, int s) { return s == 5 ? 0 : (n == 13 ? 3 : s + 1); }

struct Params {
  CUtensorMap mX, mXh, mWq, mWo, mWg, mWu, mWp, mWd;
  const bf16 *x0, *wqkv, *wo, *wr, *wg, *wu, *wd;
  bf16* out;
  Scratch* g;
  unsigned map[128];
};
#define BID ((int)(P.map[blockIdx.x] & 255))
#define FID ((int)(P.map[blockIdx.x] >> 8))
DEVI uint32_t uni(uint32_t v) { return __shfl_sync(0xffffffffu, v, 0); }
#define PQ_N 8
#define PQ_T 700
#define PF0_N 10
#define PF0_T 1600
#define PF1_E 24
#define PF1_T 1100
#define POL_Q1 POL_NORMAL
#define POL_X POL_NORMAL
#define PFA0_BAR 3
#define PFA1_BAR 0
#define PFA0_M 0
#define PFA1_M 0
#define PFA0_T 900
#define PFA1_T 700
#define PF1_S PF0_N
#define PF1_D 0
#define POL_G POL_NORMAL
#define POL_U POL_FIRST
#define POL_D POL_FIRST
#define JQ_N 6
#define WDSRC (P.wd + (size_t)min(fid, 111) * 32768)
#define WDSRC2 (P.wd + FID * 32768)
#define WD_N 4
#define THR_N 5
#define KV_D 1800
#define XD_D 300
#define W0_BAR 3
#define QEF_N 99
#define PACE_T 300
#define IDLE_T 11000
#define LATE_C 99
#define LATE_B B_XFREE + 1
#define LATE_P 0
#define KV_D1 200
#define KV_D2 1200
#define KV_DL 0
#define POL_KV0 POL_FIRST
#define POL_KV1 POL_FIRST
#define POL_O0 POL_FIRST
#define POL_O1 POL_FIRST
#define POL_W0 POL_NORMAL
#define POL_W1 POL_FIRST
#define POL_T POL_FIRST
#define U_C 8
#define ST_M 0
#define POL_Q0 POL_NORMAL
constexpr float LN_EPS = 1e-5f;
constexpr float QSCALE = 0.17677669529663687f * 1.4426950408889634f;

DEVI void fma8(float (&a)[8], uint4 v, float h) {
  a[0] = fmaf(bf_lo(v.x), h, a[0]); a[1] = fmaf(bf_hi(v.x), h, a[1]); a[2] = fmaf(bf_lo(v.y), h, a[2]); a[3] = fmaf(bf_hi(v.y), h, a[3]);
  a[4] = fmaf(bf_lo(v.z), h, a[4]); a[5] = fmaf(bf_hi(v.z), h, a[5]); a[6] = fmaf(bf_lo(v.w), h, a[6]); a[7] = fmaf(bf_hi(v.w), h, a[7]);
}
DEVI uint4 ldsv128(uint32_t a) { uint4 v; asm volatile("ld.volatile.shared.v4.u32 {%0,%1,%2,%3}, [%4];" : "=r"(v.x), "=r"(v.y), "=r"(v.z), "=r"(v.w) : "r"(a) : "memory"); return v; }
DEVI float ldsv32f(uint32_t a) { float v; asm volatile("ld.volatile.shared.f32 %0, [%1];" : "=f"(v) : "r"(a) : "memory"); return v; }
DEVI uint32_t clk() { uint32_t t; asm volatile("mov.u32 %0, %%clock;" : "=r"(t)); return t; }
DEVI int fresh_tid() { int t; asm volatile("mov.u32 %0, %%tid.x;" : "=r"(t)); return t & 127; }
DEVI float fold8(const float (&a)[8]) {
  const int lane = threadIdx.x & 31;
  const bool u = lane & 16, v = lane & 8, x = lane & 4;
  float b0 = (u ? a[4] : a[0]) + __shfl_xor_sync(0xffffffffu, u ? a[0] : a[4], 16), b1 = (u ? a[5] : a[1]) + __shfl_xor_sync(0xffffffffu, u ? a[1] : a[5], 16);
  float b2 = (u ? a[6] : a[2]) + __shfl_xor_sync(0xffffffffu, u ? a[2] : a[6], 16), b3 = (u ? a[7] : a[3]) + __shfl_xor_sync(0xffffffffu, u ? a[3] : a[7], 16);
  float c0 = (v ? b2 : b0) + __shfl_xor_sync(0xffffffffu, v ? b0 : b2, 8), c1 = (v ? b3 : b1) + __shfl_xor_sync(0xffffffffu, v ? b1 : b3, 8);
  return (x ? c1 : c0) + __shfl_xor_sync(0xffffffffu, x ? c0 : c1, 4);
}
DEVI float sigmoidf(float x) { return __fdividef(1.f, 1.f + ex2f(-1.4426950408889634f * x)); }
DEVI float swiglu(float g, float u) { return g * u * sigmoidf(g); }

template<int J0, int J1> DEVI void exp_pack(const float (&s)[32], uint32_t (&p)[16]) {
  #pragma unroll
  for (int j = J0; j < J1; j++) p[j] = pack_bf16(ex2f(s[2 * j]), ex2f(s[2 * j + 1]));
}
DEVI bool attn_pack(const float (&o)[20], uint32_t (&ob)[8]) {
  const float lo = 5.421010862427522e-20f, hi = 1.8446744073709552e19f;
  float i0, i1; asm("rcp.approx.ftz.f32 %0, %1;" : "=f"(i0) : "f"(o[16])); asm("rcp.approx.ftz.f32 %0, %1;" : "=f"(i1) : "f"(o[18]));
  #pragma unroll
  for (int e = 0; e < 8; e++) ob[e] = pack_bf16(o[2 * e] * ((e & 1) ? i1 : i0), o[2 * e + 1] * ((e & 1) ? i1 : i0));
  return __all_sync(0xffffffffu, o[16] >= lo && o[16] <= hi && o[18] >= lo && o[18] <= hi);
}
DEVI void attn_store(const uint32_t (&ob)[8], bool ok, uint32_t st, uint32_t sb, uint32_t bar) {
  stsm_x4(ok ? st : sb + DUMP, ob[0], ob[1], ob[2], ob[3]); stsm_x4(ok ? st ^ 32 : sb + DUMP, ob[4], ob[5], ob[6], ob[7]);
  __syncwarp();
  asm volatile("{\n.reg .pred p, q;\nelect.sync _|q, 0xffffffff;\nsetp.ne.and.u32 p, %1, 0, q;\n@p mbarrier.arrive.shared::cta.b64 _, [%0];\n}" :: "r"(bar), "r"((uint32_t)ok) : "memory");
}
DEVI void attn_exact(uint32_t st, uint32_t kv, int t, bool hasprev, uint32_t bar) {
  const int lane = threadIdx.x & 31;
  #pragma unroll 1
  for (int row = ((threadIdx.x >> 5) & 3) * 16, n = 0; n < 16; n++, row++) {
    const int k1 = 256 + t * 64 + row;
    float m = -INFINITY, l = 0.f, o = 0.f;
    #pragma unroll 1
    for (int k0 = hasprev ? k1 - 255 : 256; k0 <= k1; k0 += 32) {
      const int k = min(k0 + lane, k1), r = k & 63;
      float sc = 0.f;
      #pragma unroll 1
      for (int c = 0; c < 16; c++) {
        uint32_t a = lds32(st + row * 64 + ((c * 4) ^ ((row & 6) << 3))), b = lds32(kv + (k >> 6) * 8192 + r * 64 + ((c * 4) ^ ((r & 6) << 3)));
        sc = fmaf(bf_lo(a), bf_lo(b), fmaf(bf_hi(a), bf_hi(b), sc));
      }
      float mn = fmaxf(m, sc);
      #pragma unroll 1
      for (int x = 16; x; x >>= 1) mn = fmaxf(mn, __shfl_xor_sync(0xffffffffu, mn, x));
      const float al = ex2f(m - mn), pr = ex2f(sc - mn);
      m = mn; l *= al; o *= al;
      #pragma unroll 1
      for (int q = k0; q <= min(k0 + 31, k1); q++) {
        const float z = __shfl_sync(0xffffffffu, pr, q - k0);
        uint32_t b = lds32(kv + (q >> 6) * 8192 + 4096 + (q & 63) * 64 + (((lane >> 1) * 4) ^ ((q & 6) << 3)));
        l += z; o = fmaf(z, (lane & 1) ? bf_hi(b) : bf_lo(b), o);
      }
    }
    __syncwarp();
    sts16(st + row * 64 + ((lane * 2) ^ ((row & 6) << 3)), pack_bf16(__fdividef(o, l), 0.f));
  }
  warp_signal(bar);
}

template<int K0, int K1, int DONE = 0> DEVI void exp_pv(const float (&s)[32], uint32_t (&p)[16], float (&o)[20], uint32_t vd, bool accum) {
  #pragma unroll
  for (int ks = K0; ks < K1; ks++) {
    if (ks >= DONE) {
      #pragma unroll
      for (int j = 4 * ks; j < 4 * ks + 4; j++) p[j] = pack_bf16(ex2f(s[2 * j]), ex2f(s[2 * j + 1]));
    }
    asm volatile("" : "+r"(p[4 * ks]), "+r"(p[4 * ks + 1]), "+r"(p[4 * ks + 2]), "+r"(p[4 * ks + 3]));
    wg_fence();
    wgmma_rs_n40<1>(o, p[ks * 4], p[ks * 4 + 1], p[ks * 4 + 2], p[ks * 4 + 3], mkd<HI64>(vd + VOFF(ks * 64)), ks ? 1 : accum);
  }
}
template<int K0, int K1> DEVI void exp_pv2(const float (&s)[32], const float (&sx)[32], uint32_t (&p)[16], uint32_t (&px)[16], float (&o)[20], uint32_t v0, uint32_t v4,
                  const uint32_t (&msk)[9], int tdiag) {
  #pragma unroll
  for (int ks = K0; ks < K1; ks++) {
    #pragma unroll
    for (int j = 4 * ks; j < 4 * ks + 4; j++) {
      const int c = 8 * (j >> 1) - 8 * (j & 1);
      const uint32_t e = pack_bf16(ex2f(c > tdiag ? s[2 * j] : sx[2 * j]), ex2f(c + 1 > tdiag ? s[2 * j + 1] : sx[2 * j + 1])), m = msk[(j >> 1) - (j & 1) + 1];
      p[j] = e & m; px[j] = e & ~m;
      asm volatile("" : "+r"(p[j]), "+r"(px[j]));
    }
    wg_fence();
    wgmma_rs_n40<1>(o, p[ks * 4], p[ks * 4 + 1], p[ks * 4 + 2], p[ks * 4 + 3], mkd<HI64>(v0 + VOFF(ks * 64)), 1);
    wgmma_rs_n40<1>(o, px[ks * 4], px[ks * 4 + 1], px[ks * 4 + 2], px[ks * 4 + 3], mkd<HI64>(v4 + VOFF(ks * 64)), 1);
  }
}

template<int J0> DEVI void qkv_store(const float (&a)[96], float p0, float p1, uint32_t d) {
  #pragma unroll
  for (int hh = 0; hh < 2; hh++) {
    const int j = 4 * (J0 + 2 * hh);
    stsm_x4(d ^ (hh << 5), pack_bf16(a[j] * p0, a[j + 1] * p0), pack_bf16(a[j + 2] * p1, a[j + 3] * p1),
                           pack_bf16(a[j + 4] * p0, a[j + 5] * p0), pack_bf16(a[j + 6] * p1, a[j + 7] * p1));
  }
}
DEVI void mean_step(float (&a)[96], float m0, float m1, uint32_t cd, bool z) {
  const uint32_t u0 = z ? 0u : __float_as_uint(m0), u1 = z ? 0u : __float_as_uint(m1);
  uint32_t ma[4] = {__byte_perm(u0, 0u, 0x1010), __byte_perm(u1, 0u, 0x1010), __byte_perm(u0, 0u, 0x3232), __byte_perm(u1, 0u, 0x3232)};
  keep(ma);
  wg_fence();
  wgmma_rs_n192<1>(a, ma[0], ma[1], ma[2], ma[3], mkd<2>(cd), 1);
  wg_commit();
}

template<bool FIRST> DEVI void qkv_block(float (&aX)[96], float (&aY)[96], uint32_t sb16, int s, int tX, int tY) {
  uint32_t a16 = sb16 + (qa_off(s) >> 4), b16 = (sb16 + (qb_off(s) >> 4)) | ((8192u >> 4) << 16);
  uint32_t ax = (a16 + tX * 512) | 0x10000u, ay = (a16 + tY * 512) | 0x10000u;
  wg_fence();
  #pragma unroll
  for (int ks = 0; ks < 4; ks++) {
    wgmma_ss_n192<1>(aX, mkd<HI128>(ax + ks * 2), mkd<HI128>(b16 + ks * 128), !(FIRST && ks == 0));
    wgmma_ss_n192<1>(aY, mkd<HI128>(ay + ks * 2), mkd<HI128>(b16 + ks * 128), !(FIRST && ks == 0));
  }
  wg_commit();
}
DEVI void qkv_half(float (&a)[96], uint32_t sb16, int t, uint32_t sa, uint32_t sbb) {
  wg_fence();
  #pragma unroll
  for (int ks = 0; ks < 4; ks++)
    wgmma_ss_n192<1>(a, mkd<HI128>(((sb16 + (sa >> 4) + t * 512) | 0x10000u) + ks * 2), mkd<HI128>(((sb16 + (sbb >> 4)) | ((8192u >> 4) << 16)) + ks * 128), 1);
  wg_commit();
}
DEVI void wo_block(float (&acc)[64], uint32_t sb16, int n, int s, int wg) {
  uint32_t a16 = (sb16 + (w_aoff(n, s) >> 4) + wg * 256) | 0x10000u, b16 = (sb16 + (w_off(s) >> 4) + 1024) | ((8192u >> 4) << 16);
  wg_fence();
  #pragma unroll
  for (int ks = 0; ks < 4; ks++)
    wgmma_ss_n128<1>(acc, mkd<HI64>(a16 + (ks >> 1) * 512 + (ks & 1) * 2), mkd<HI128>(b16 + ks * 128), 1);
  wg_commit();
}
DEVI void consumer(const Params& P, uint32_t sb, int wg) {
  const int w = uni((threadIdx.x >> 5) & 3);
  #define LAYER uni(mbar_test(BAR(B_XRDY + wg * 2 + 1), 0))
  #define IDS L = LAYER; const int tid = fresh_tid(), lane = tid & 31
  const uint32_t ids = uni(P.map[blockIdx.x]);
  const int bi = (ids >> 4) & 7, rh = ids & 1, bc = (ids & 15) >> 1, fid = ids >> 8;
  const int tX = 3 - wg, tY = wg;
  constexpr uint32_t sb16 = 1024 >> 4;
  #pragma unroll 1
  while (true) {
    int L = LAYER;
    float2 fa, fb;
    {
      float aX[96], aY[96];
      const bool lead = fresh_tid() == 0;
      mbar_wait(BAR(B_FULLQ), 0);
      PROFW(threadIdx.x == 0, L * 8 + 1);
      qkv_block<true>(aX, aY, sb16, 0, tX, tY);
      #pragma unroll 1
      for (int n = 1, s = 1, ps = 0, ph = 0; n < 14; n++) {
        mbar_wait(BAR(B_FULLQ + s), ph ^ (s ? L : 0));
        PROFD(threadIdx.x == 0 && L && (n == 2 || n == 3 || n == 7 || n == 11 || n == 13), n == 2 ? 48 : 49 + (n >> 2));
        qkv_block<false>(aX, aY, sb16, s, tX, tY);
        wg_wait<1>(); if (lead) mbar_arrive(BAR(B_EMPTYQ + ps));
        ps = s; if (s == 2) { s = 0; ph ^= 1; } else s++;
      }
      mbar_wait(BAR(B_FULLQ + 2), L);
      qkv_half(aX, sb16, tX, SA2, SB2);
      mbar_wait(BAR(B_ROW), L);
      IDS;
      const uint32_t pa = sb + PAR + (w * 16 + (lane >> 2)) * 8;
      float2 p0 = lds64f(pa + tX * 512), p1 = lds64f(pa + tX * 512 + 64), p2 = lds64f(pa + tY * 512), p3 = lds64f(pa + tY * 512 + 64);
      mean_step(aX, p0.y, p1.y, sb16 + (CS >> 4), lane & 3);
      mbar_wait(BAR(B_FULLQ), 1);
      qkv_half(aX, sb16, tX, 0, SB0);
      wg_wait<3>(); if (lead) mbar_arrive(BAR(B_EMPTYQ + 1));
      bar_sync(1, 256);
      if (L) mbar_wait(BAR(B_PW), 0);
      qkv_half(aY, sb16, tY, SA2, SB2);
      wg_wait<1>(); keep(aX);
      const int srow = w * 16 + (lane & 15);
      const uint32_t x0 = sb + srow * 64 + (((lane >> 4) ^ ((srow >> 1) & 3)) << 4), xX = x0 + (4 + tX) * 8192, xY = x0 + (4 + tY) * 8192;
      qkv_store<8>(aX, p0.x, p1.x, xX + KVA); qkv_store<16>(aX, p0.x, p1.x, xX + KVA + 4096);
      warp_signal(BAR(B_KVRDY + wg * 2));
      qkv_half(aY, sb16, tY, 0, SB0);
      mean_step(aY, p2.y, p3.y, sb16 + (CS >> 4), fresh_tid() & 3);
      wg_wait<2>(); if (lead) mbar_arrive(BAR(B_EMPTYQ + 2));
      mbar_wait(BAR(B_EMPTYQ + 2), L);
      qkv_store<12>(aX, p0.x, p1.x, xX + KVB); qkv_store<20>(aX, p0.x, p1.x, xX + KVB + 4096);
      wg_wait<0>(); keep(aY);
      if (lead) mbar_arrive(BAR(B_EMPTYQ));
      PROFW(threadIdx.x == 0, L * 8 + 2);
      qkv_store<8>(aY, p2.x, p3.x, xY + KVA); qkv_store<16>(aY, p2.x, p3.x, xY + KVA + 4096);
      qkv_store<12>(aY, p2.x, p3.x, xY + KVB); qkv_store<20>(aY, p2.x, p3.x, xY + KVB + 4096);
      warp_signal(BAR(B_KVRDY + wg * 2 + 1));
      p0.x *= QSCALE; p1.x *= QSCALE; p2.x *= QSCALE; p3.x *= QSCALE;
      mbar_wait(BAR(B_EMPTYQ), 1);
      qkv_store<0>(aX, p0.x, p1.x, x0 + QO + tX * 4096);
      qkv_store<0>(aY, p2.x, p3.x, x0 + QO + tY * 4096); qkv_store<4>(aY, p2.x, p3.x, x0 + QO + 16384 + tY * 4096);
      { const float2* f = (const float2*)&P.g->statF[bi * 256 + rh * 128 + (wg ^ rh) * 64 + w * 16 + (lane >> 2)]; fa = __ldcg(f); fb = __ldcg(f + 16); }
      mbar_wait(BAR(B_PAR), L);
      qkv_store<4>(aX, p0.x, p1.x, x0 + QO + 16384 + tX * 4096);
      const int prow = (int)uni(lds32(sb + INFO)) - bi * 256;
      if ((prow >> 4) == tX * 4 + w || (prow >> 4) == tY * 4 + w) {
        __syncwarp();
        if (lane < 24) sts128(sb + (prow & 63) * 64 + (((lane ^ (prow >> 1)) & 3) << 4) +
                              (lane < 8 ? QO + (lane >> 2) * 16384 + (prow >> 6) * 4096 : ((lane & 4) ? KVB : KVA) + (4 + (prow >> 6)) * 8192 + (lane >> 4) * 4096),
                              lds128(sb + PATCH + lane * 16));
      }
      fence_async_smem();
      bar_sync(1, 256);
    }
    PROFW(threadIdx.x == 0, L * 8 + 3);
    {
      IDS;
      float s0[32], s1[32], sx[32], o[20], op[20];
      uint32_t p0[16], p1[16], px[16], msk[9];
      const int tdiag = w * 16 + (lane >> 2) - 2 * (lane & 3);
      const uint32_t ones = (sb16 + (ONES >> 4)) << 16;
      const uint32_t qX = (sb16 + (QO >> 4) + tX * 256) | 0x10000u, qY = (sb16 + (QO >> 4) + tY * 256) | 0x10000u;
      const uint32_t kXB = (sb16 + (KVB >> 4) + tX * 512) | 0x10000u;
      uint32_t redo = 0;
      const uint32_t ost = sb + QO + (w * 16 + (lane & 15)) * 64 + (((lane >> 4) ^ ((lane >> 1) & 3)) << 4);
      #define QA(s, q, k) do { wg_fence(); wgmma_ss_n64<0>(s, mkd<HI64>(q), mkd<HI64>(k), 0); } while (0)
      #define QB(s, q, k) wgmma_ss_n64<0>(s, mkd<HI64>((q) + 2), mkd<HI64>((k) + 2), 1)
      #define QA2(q, k) do { QA(s1, q, k); wgmma_ss_n64<0>(sx, mkd<HI64>(q), mkd<HI64>((k) + 2048), 0); } while (0)
      #define QB2(q, k) do { QB(s1, q, k); QB(sx, q, (k) + 2048); } while (0)
      #define VB(v, b) ((v) + VOFF((b) * 512))
      #define MID() do { wg_commit(); wg_wait<1>(); } while (0)
      QA(s0, qX + 1024, kXB + 1536); QB(s0, qX + 1024, kXB + 1536); wg_commit();
      #pragma unroll
      for (int e = 0; e < 20; e++) o[e] = 0.f;
      wg_wait<0>(); keep(s0);
      #pragma unroll 1
      for (int h = 1; h >= 0; h--) {
        const uint32_t kXA = kXB - ((KVB - KVA) >> 4), kX = h ? kXB : kXA, vX = VOFF((kX & 0xffffu) + 256) + ones;
        QA(s1, qX + h * 1024, kX + 1024);
        #pragma unroll
        for (int e = 0; e < 20; e++) op[e] = o[e];
        keep(op);
        exp_pv<0, 1>(s0, p0, o, VB(vX, 3), false); QB(s1, qX + h * 1024, kX + 1024); wg_commit();
        exp_pv<1, 2>(s0, p0, o, VB(vX, 3), true); MID(); keep(s1);
        exp_pv<2, 4>(s0, p0, o, VB(vX, 3), true);
        { int td = tdiag; asm volatile("" : "+r"(td));
          #pragma unroll
          for (int e = 0; e < 9; e++) msk[e] = ((8 * e - 8 > td) ? 0xFFFFu : 0u) | ((8 * e - 7 > td) ? 0xFFFF0000u : 0u);
          keep(msk); }
        exp_pv<0, 2>(s1, p1, o, VB(vX, 2), true);
        bar_sync(h ? 12 + wg : 4 + wg * 4, h ? 128 : 160);
        QA(s0, qX, kXA + 512 + h * 1024);
        exp_pv<2, 3>(s1, p1, o, VB(vX, 2), true); QB(s0, qX, kXA + 512 + h * 1024);
        exp_pv<3, 4>(s1, p1, o, VB(vX, 2), true); wg_commit();
        wg_wait<0>(); keep(s0); keep(p0); keep(p1); keep(o);
      }
      #pragma unroll 1
      for (int h = 0; h < 2; h++) {
        const uint32_t kb16 = sb16 + ((h ? KVB : KVA) >> 4), kX = (kb16 + tX * 512) | 0x10000u, kY = (kb16 + tY * 512) | 0x10000u, qx = qX + h * 1024, qy = qY + h * 1024;
        const uint32_t onesP = bi ? ones : (kb16 + 1984) << 16;
        const uint32_t vX = VOFF(kb16 + tX * 512 + 256), vY = VOFF(kb16 + tY * 512 + 256);
        uint32_t ob[8], v;
        v = VB(vX + (wg ? onesP : ones), 1);
        QA2(qx, kX);
        exp_pv<0, 1>(s0, p0, o, v, true); QB2(qx, kX); wg_commit();
        exp_pv<1, 2>(s0, p0, o, v, true); MID(); keep(s1); keep(sx);
        exp_pv<2, 4>(s0, p0, o, v, true);
        QA(s0, qy, kY + 1536);
        exp_pv2<0, 1>(s1, sx, p1, px, o, vX + onesP, VB(vX + ones, 4), msk, tdiag); QB(s0, qy, kY + 1536); wg_commit();
        exp_pv2<1, 2>(s1, sx, p1, px, o, vX + onesP, VB(vX + ones, 4), msk, tdiag); MID(); keep(s0); keep(p0);
        exp_pv2<2, 4>(s1, sx, p1, px, o, vX + onesP, VB(vX + ones, 4), msk, tdiag); wg_commit();
        v = VB(vY + (wg ? ones : onesP), 3);
        QA(s1, qy, kY + 1024);
        exp_pack<0, 4>(s0, p0);
        QB(s1, qy, kY + 1024); MID(); keep(o); keep(p1); keep(px);
        bool ok = attn_pack(o, ob); keep(ob);
        exp_pv<0, 2, 1>(s0, p0, o, v, false); MID(); keep(s1);
        attn_store(ob, ok, ost + (h * 4 + tX) * 4096, sb, BAR(B_ORDY + wg * 4 + h * 2)); redo |= ok ? 0u : 1u << (h * 2);
        exp_pv<2, 4>(s0, p0, o, v, true);
        v = VB(vY + onesP, 2);
        exp_pv<0, 1>(s1, p1, o, v, true);
        bar_sync(5 + wg * 4 + h * 2, 160);
        QA(s0, qy, kY + 512);
        exp_pv<1, 2>(s1, p1, o, v, true); QB(s0, qy, kY + 512); wg_commit();
        exp_pv<2, 3>(s1, p1, o, v, true); MID(); keep(s0); keep(p0);
        exp_pv<3, 4>(s1, p1, o, v, true);
        v = VB(vY + onesP, 1);
        QA2(qy, kY);
        exp_pv<0, 1>(s0, p0, o, v, true); QB2(qy, kY); wg_commit();
        exp_pv<1, 2>(s0, p0, o, v, true); MID(); keep(s1); keep(sx); keep(p1);
        exp_pv<2, 4>(s0, p0, o, v, true);
        exp_pv2<0, 1>(s1, sx, p1, px, o, vY + onesP, VB(vY + ones, 4), msk, tdiag);
        bar_sync(6 + wg * 4, h ? 128 : 160);
        QA(s0, h ? qy : qX + 1024, kXB + 512);
        exp_pv2<1, 2>(s1, sx, p1, px, o, vY + onesP, VB(vY + ones, 4), msk, tdiag); QB(s0, h ? qy : qX + 1024, kXB + 512);
        exp_pv2<2, 4>(s1, sx, p1, px, o, vY + onesP, VB(vY + ones, 4), msk, tdiag); wg_commit();
        wg_wait<0>(); keep(o); keep(s0); keep(p0); keep(p1); keep(px);
        ok = attn_pack(o, ob); attn_store(ob, ok, ost + (h * 4 + tY) * 4096, sb, BAR(B_ORDY + wg * 4 + h * 2 + 1)); redo |= ok ? 0u : 2u << (h * 2);
        #pragma unroll
        for (int e = 0; e < 20; e++) o[e] = op[e];
      }
      #undef QA
      #undef QB
      #undef QA2
      #undef QB2
      #undef VB
      #undef MID
      if (redo) {
        #pragma unroll 1
        for (int u = 0; u < 4; u++) if ((redo >> u) & 1) {
          const int h = u >> 1, t = (u & 1) ? tY : tX;
          attn_exact(sb + QO + (h * 4 + t) * 4096, sb + (h ? KVB : KVA), t, bi > 0, BAR(B_ORDY + wg * 4 + u));
        }
      }
    }
    PROFW(threadIdx.x == 0, L * 8 + 4);
    {
      IDS;
      const int t256 = wg * 128 + tid;
      float acc[64];
      const int tt = wg ^ rh;
      const int grow = bi * 256 + rh * 128 + tt * 64 + w * 16 + (lane >> 2);
      float al0 = 1.f, be0 = 0.f, al1 = 1.f, be1 = 0.f;
      const int idx0 = (int)uni(lds32(sb + INFO));
      const uint32_t tag = lds32(sb + INFO + 8) + L;
      uint4* const sp = &P.g->statP[bc][grow + (lane & 1) * 8];
      uint4* const yp = &P.g->yP[t256 >> 1][min(fid, 111)][t256 & 1];
      if (L) {
        float r0 = rsqrtf(fa.y + LN_EPS), r1 = rsqrtf(fb.y + LN_EPS);
        if (grow != idx0) { al0 = 1.f + r0; be0 = -fa.x * r0; }
        if (grow + 8 != idx0) { al1 = 1.f + r1; be1 = -fb.x * r1; }
      }
      const int srow = tt * 64 + w * 16 + (lane & 15);
      const uint32_t ra = sb + srow * 128 + (((lane >> 4) ^ (srow & 7)) << 4);
      mbar_wait(BAR(B_FULLW + 5), L);
      if ((idx0 >> 4) == bi * 16 + rh * 8 + tt * 4 + w) {
        int r = idx0 & 127;
        if (lane < 16) sts128(sb + 32768 + (lane >> 3) * 16384 + r * 128 + (((lane & 7) ^ (r & 7)) << 4), lds128(sb + X2SEG + lane * 16));
        fence_async_smem();
        __syncwarp();
      }
      #pragma unroll
      for (int jj = 0; jj < 8; jj++) {
        uint32_t r[4]; ldsm_x4((ra + 32768 + (jj >> 2) * 16384) ^ ((jj & 3) << 5), r[0], r[1], r[2], r[3]);
        #pragma unroll
        for (int e = 0; e < 4; e++) {
          acc[8 * jj + 2 * e] = fmaf(bf_lo(r[e]), (e & 1) ? al1 : al0, (e & 1) ? be1 : be0);
          acc[8 * jj + 2 * e + 1] = fmaf(bf_hi(r[e]), (e & 1) ? al1 : al0, (e & 1) ? be1 : be0);
        }
      }
      keep(acc);
      bar_sync(12 + wg, 128);
      if (!(lane & 2)) st_ll(sp, 0u, 0u, 0u, 0u);
      uint2 wd[4];
      #pragma unroll
      for (int e = 0; e < 4; e++) { wd[e] = make_uint2(0u, 0u); if (L) wd[e] = ldg_stream((const uint2*)(WDSRC) + t256 + (28 + e) * 256); }
      PROFW(t256 == 0, L * 8 + 5);
      #pragma unroll 1
      for (int n = 0, q = 0, pq = 5; n < 16; n++) {
        mbar_wait(BAR(B_FULLW + q), w_par(n, q, L));
        PROFD(t256 == 0 && !L && (n == 4 || n == 7 || n == 8 || n == 12), (n == 7 ? 63 : 41 + (n >> 2)));
        wo_block(acc, sb16, n, q, tt);
        wg_wait<1>(); if (tid == 0) mbar_arrive(BAR(B_EMPTYW + pq));
        pq = q; q = w_next(n, q);
      }
      mbar_wait(BAR(B_EMPTYW + 5), L);
      wg_wait<0>(); keep(acc);
      if (tid == 0) mbar_arrive(BAR(B_EMPTYW + 4));
      PROFW(t256 == 0, L * 8 + 6);
      const uint32_t xa = ra + rh * 16384;
      {
        float s1a = 0.f, s2a = 0.f, da = 0.f, s1b = 0.f, s2b = 0.f, db = 0.f;
        #pragma unroll
        for (int j = 0; j < 16; j++) {
          const float* a = acc + 4 * j; float2 wv = lds64f(sb + WR + j * 32 + (lane & 3) * 8);
          s1a += a[0] + a[1]; s1b += a[2] + a[3];
          s2a = fmaf(a[0], a[0], s2a); s2b = fmaf(a[2], a[2], s2b); s2a = fmaf(a[1], a[1], s2a); s2b = fmaf(a[3], a[3], s2b);
          da = fmaf(a[0], wv.x, da); db = fmaf(a[2], wv.x, db); da = fmaf(a[1], wv.y, da); db = fmaf(a[3], wv.y, db);
        }
        bool odd = lane & 1;
        float u1 = (odd ? s1b : s1a) + __shfl_xor_sync(0xffffffffu, odd ? s1a : s1b, 1);
        float u2 = (odd ? s2b : s2a) + __shfl_xor_sync(0xffffffffu, odd ? s2a : s2b, 1);
        float u3 = (odd ? db : da) + __shfl_xor_sync(0xffffffffu, odd ? da : db, 1);
        u1 += __shfl_xor_sync(0xffffffffu, u1, 2); u2 += __shfl_xor_sync(0xffffffffu, u2, 2); u3 += __shfl_xor_sync(0xffffffffu, u3, 2);
        if (!(lane & 2)) st_ll(sp, __float_as_uint(u1), __float_as_uint(u2), __float_as_uint(u3), tag);
      }
      {
      #pragma unroll
      for (int jj = 0; jj < 8; jj++) {
        const float* a = acc + 8 * jj;
        stsm_x4((xa + (jj >> 2) * 32768) ^ ((jj & 3) << 5), pack_bf16(a[0], a[1]), pack_bf16(a[2], a[3]), pack_bf16(a[4], a[5]), pack_bf16(a[6], a[7]));
        if (jj == 7) fence_async_smem();
        if ((jj & 3) == 3) warp_signal(BAR(B_XRDY + wg * 2 + (jj >> 2)));
      }
      }
      PROFW(t256 == 0, L * 8 + 7);
      if (L) {
        mbar_wait(BAR(B_PAR), 0);
        { float2 pa = lds64f(sb + PAR + (grow & 127) * 8), pb = lds64f(sb + PAR + (grow & 127) * 8 + 64); al0 = pa.x; be0 = pa.y; al1 = pb.x; be1 = pb.y; }
        uint32_t rs[32];
        #pragma unroll
        for (int j = 0; j < 16; j++) {
          rs[2 * j] = pack_bf16(fmaf(acc[4 * j], al0, be0), fmaf(acc[4 * j + 1], al0, be0));
          rs[2 * j + 1] = pack_bf16(fmaf(acc[4 * j + 2], al1, be1), fmaf(acc[4 * j + 3], al1, be1));
        }
        #pragma unroll
        for (int jj = 0; jj < 8; jj++) stsm_x4((xa + (jj >> 2) * 32768) ^ ((jj & 3) << 5), rs[4 * jj], rs[4 * jj + 1], rs[4 * jj + 2], rs[4 * jj + 3]);
        PROFW(t256 == 0, 16);
        if (fid >= 112) bar_arrive(3, 384);
        else {
          float d[4] = {0.f, 0.f, 0.f, 0.f};
          mbar_wait(BAR(B_FULLW + wg * 3), 0); mbar_wait(BAR(B_FULLW + wg * 3 + 1), 0);
          bar_sync(3, 384);
          PROFW(t256 == 0, 29);
          #pragma unroll 1
          for (int g = 0; g < 4; g++) {
            const uint32_t ad = (sb16 + (wg ? 6144 : 10240) + (g >> 1) * 2048 + (g & 1) * 512) | (1024u << 16), bd = (sb16 + (HV >> 4) + wg * 64 + g * 16) | 0x10000u;
            wg_fence();
            #pragma unroll
            for (int ks = 0; ks < 8; ks++) wgmma_ss_n8<0, 1>(d, mkd<HI64>(ad + ks * 64), mkd<8>(bd + ks * 2), 1);
            wg_commit();
          }
          mbar_wait(BAR(B_FULLW + 2), 0);
          wg_wait<0>(); keep(d);
          if (!(lane & 3)) { sts32f(sb + PAR + 1024 + wg * 256 + w * 64 + lane, d[0]); sts32f(sb + PAR + 1056 + wg * 256 + w * 64 + lane, d[2]); }
          bar_sync(1, 256);
          const uint32_t ga = sb + PAR + 1024 + lane * 4, aa = sb + HV + (t256 >> 5) * 128;
          sts32f(aa + lane * 4, swiglu(lds32f(ga) + lds32f(ga + 256), lds32f(ga + 128) + lds32f(ga + 384)));
          __syncwarp();
          PROFW(t256 == 0, 26);
          float y0 = 0.f, y1 = 0.f, y2 = 0.f, y3 = 0.f;
          uint32_t tbl = rh ? 0x001459a8u : 0x023679a8u;
          uint4 a4 = lds128(aa + 112);
          #pragma unroll 2
          for (int n = 0; n < 8; n++, tbl >>= 4) {
            const uint32_t src = sb + t256 * 8 + (tbl & 15) * 8192;
            const uint4 an = lds128(aa + ((0x00123564u >> (4 * n)) & 15) * 16);
            #pragma unroll
            for (int e = 0; e < 4; e++) {
              const float av = __uint_as_float(e == 0 ? a4.x : (e == 1 ? a4.y : (e == 2 ? a4.z : a4.w)));
              y0 = fmaf(bf_lo(wd[e].x), av, y0); y1 = fmaf(bf_hi(wd[e].x), av, y1); y2 = fmaf(bf_lo(wd[e].y), av, y2); y3 = fmaf(bf_hi(wd[e].y), av, y3);
              const float2 v = lds64f(src + e * 2048); wd[e] = make_uint2(__float_as_uint(v.x), __float_as_uint(v.y));
            }
            a4 = an;
          }
          st_ll(yp, __float_as_uint(y0), __float_as_uint(y1), __float_as_uint(y2), (__float_as_uint(y3) & ~255u) | (lds32(sb + INFO + 12) + 1));
          PROFW(t256 == 0, 27);
        }
        return;
      }
      mbar_wait(BAR(B_XRDY + wg * 2 + 1), 0);
    }
  }
  #undef IDS
  #undef LAYER
}

DEVI void loader(const Params& P, uint32_t sb) {
  const int lane = threadIdx.x & 31;
  const int bid = uni(BID), bi = bid >> 4, bp = bid & 15, rh = bp & 1, bc = bp >> 1;
  uint32_t phq = 0, tag = 0;
  #pragma unroll 1
  for (int L = 0; L < 2; L++) {
    int s = 0;
    uint32_t rdy = 0;
    #pragma unroll 1
    for (int n = L ? 0 : 3; n < 16; n++) {
      int kb = L ? kb_order(bc, n) : n;
      mbar_wait(BAR(B_EMPTYQ + s), (phq >> s) & 1);
      phq ^= 1u << s;
      if (L && n == 1) { mbar_wait(BAR(B_XRDY + 1), 0); mbar_wait(BAR(B_XRDY + 3), 0); }
      if (elect()) {
        mbar_expect_tx(BAR(B_FULLQ + s), L && n < 2 ? 40960 : 57344);
        tma_3d_h(sb + qb_off(s), &P.mWq, bp * 64, kb * 64, 0, BAR(B_FULLQ + s), L && n >= QEF_N ? POL_FIRST : POL_NORMAL);
        if (!L) tma_2d(sb + qa_off(s), &P.mX, kb * 64, bi * 256, BAR(B_FULLQ + s));
      }
      if (L && n >= 2) {
        if (((rdy >> (2 * kb)) & 3) != 3) {
          do { rdy = __ballot_sync(0xffffffffu, ld_rlx(&P.g->flagX[bi][lane]) == tag); } while (((rdy >> (2 * kb)) & 3) != 3);
          fence_async_glob();
        }
        if (n == 3 || n == 4) mbar_wait(BAR(B_XFREE + n - 3), 0);
        if (elect()) bulk_g2s_h(sb + qa_off(s), P.g->x[bi][kb], 32768, BAR(B_FULLQ + s), POL_X);
      }
      PROFY(L && lane == 0 && (n == 2 || n == 3 || n == 9), n == 9 ? 60 : 56 + n);
      if (L && n == 2) { mbar_wait(BAR(B_FULLQ), 0); mbar_wait(BAR(B_FULLQ + 1), 1); if (lane < 2) mbar_arrive_peer(BAR(B_XFREE + lane)); }
      s = (s == 2) ? 0 : s + 1;
    }
    for (int q = 0; q < 3; q++) mbar_wait(BAR(B_EMPTYQ + q), (phq >> q) & 1);
    tag = lds32(sb + INFO + 8) + L;
    #pragma unroll 1
    for (int q = 0; q < 4; q++) {
            if (bi) {
        const unsigned* f = &P.g->flagKV[bid - 16][q];
        while (ld_rlx(f) != tag);
        fence_async_glob();
      }
      if (elect()) {
        mbar_expect_tx(BAR(B_KVFULL + q), 16384);
        bulk_g2s_h(sb + ((q >> 1) ? KVB : KVA) + ((q & 1) ? 0 : 16384), bi ? P.g->kv[bid - 16][q] : P.g->zero, 16384, BAR(B_KVFULL + q), L ? POL_KV1 : POL_KV0);
      }
      PROFY(!L && lane == 0 && bi && q != 2, 34 + (q + 1) / 2);
    }
    mbar_wait(BAR(B_ORDY), L);
    {
      const uint4* src = P.g->o[bi][0][0][rh];
      rdy = 0;
      #pragma unroll 1
      for (int n = 0, q = 0; n < 16; q = w_next(n, q), n++) {
        const int j = wo_order(bc, n);
        if (((rdy >> (2 * j)) & 3) != 3) {
          do { rdy = __ballot_sync(0xffffffffu, ld_rlx(&P.g->flagO[bi][lane]) == tag); } while (((rdy >> (2 * j)) & 3) != 3);
          fence_async_glob();
        }
        if (n >= 2) mbar_wait(n < 5 ? BAR(B_HAFREE + (n > 3)) : BAR(B_EMPTYW + q), n < 5 ? L : w_par(n, q, L) ^ 1);
        if (n == THR_N) mbar_wait(BAR(B_OFREE), L);
        if (elect()) { mbar_expect_tx(BAR(B_FULLW + q), 16384); bulk_g2s_h(sb + w_aoff(n, q), src + j * 2048, 16384, BAR(B_FULLW + q), L ? POL_O1 : POL_O0); }
      }
    }
    mbar_wait(BAR(B_OFREE), L);
  }
}

DEVI void ffn_prefetch(const Params& P, int q) {
  bulk_prefetch(q < 16 ? ((q & 1) ? P.wu : P.wg) + ((q >> 1) * 128 + blockIdx.x) * 3584 : P.wd + (min(FID, 111) * 8 + q - 16) * 4096, q < 16 ? 7168 : 8192);
}
DEVI void storer(const Params& P, uint32_t sb, int wg) {
  const int bid = uni(BID), bi = bid >> 4, rh = bid & 1, bc = (bid & 15) >> 1;
  const bool one = (threadIdx.x & 31) == 0;
  char* const g = (char*)P.g;
  const uint32_t tag0 = uni(((ld_rlx(&P.g->epoch) % 16383u) + 1u) << 2);
  #pragma unroll 1
  for (int L = 0; L < 2; L++) {
    const uint32_t tag = tag0 + L;
    if (wg) {
      #pragma unroll 1
      for (int r = threadIdx.x & 31; r < 256; r += 32) {
        uint4 v;
        do v = ld_ll(&P.g->statF[bi * 256 + r]); while (!__all_sync(0xffffffffu, v.w == tag));
        float var = __uint_as_float(v.y), c = rsqrtf(var + LN_EPS);
        if (L) { c += 1.f; c *= rsqrtf(fmaf(var * c, c, LN_EPS)); }
        const float mh = bf_round(__uint_as_float(v.x));
        sts64f(sb + PAR + r * 8, c, __uint_as_float(pack_bf16(mh, __uint_as_float(v.x) - mh)));
      }
      if (!L) mbar_wait(BAR(B_PAR), 0);
      warp_signal(BAR(B_ROW));
    }
    #pragma unroll 1
    for (int u = 0; u < 2 + 4 * wg; u++) {
      const int h = u < 2 ? u : u >> 2, hi = (u & 1) ^ 1;
      uint32_t src, dst, fl, b0, b1;
      if (u < 2) {
        src = (h ? KVB : KVA) + (3 - wg) * 16384; dst = offsetof(Scratch, kv) + (bid * 4 + h * 2 + wg) * 16384; fl = offsetof(Scratch, flagKV) + (bid * 32 + h * 2 + wg) * 4;
        b0 = BAR(B_KVRDY + ((u | wg) ? 1 : 0)); b1 = b0 + 16;
      } else {
        src = QO + (h * 2 + hi) * 8192; dst = offsetof(Scratch, o) + ((((bi * 2 + h) * 8 + bc) * 2 + hi) * 2 + rh) * 8192;
        fl = offsetof(Scratch, flagO) + (bi * 32 + h * 16 + (bid & 15)) * 4;
        b0 = BAR(B_ORDY + u - 2); b1 = b0 + 32;
      }
      mbar_wait(b0, L); mbar_wait(b1, L);
      if (u + wg == 1) {
        mbar_wait(BAR(B_PAR), L);
        const uint32_t t0 = clk(), dt = (wg ? KV_D1 : KV_D2) + (L ? KV_DL : 0); while (clk() - t0 < dt) __nanosleep(40);
      }
      fence_async_smem();
      PROFY(one && !L && u == 3 * wg, u ? 46 : 8);
      if (one && (u >= 2 || bi < 7)) bulk_s2g(g + dst, sb + src, u < 2 ? 16384 : 8192, ((ST_M >> (L * 2 + (u >= 2))) & 1) ? POL_FIRST : POL_NORMAL);
      if (one && u == 5) mbar_arrive(BAR(B_HAFREE + 1));
      if (u == 2 || u == 4) continue;
      bulk_wait<0>();
      PROFY(one && !L && u == 3 * wg, u ? 61 : 62);
      fence_rel();
      if (one) { st_rlx((unsigned*)(g + fl), tag); if (!wg || u > 2) mbar_arrive(BAR(B_HAFREE + h + (wg & h))); if (!wg && u) mbar_arrive(BAR(B_RES)); }
      PROFY(one && !L && (u > 2 || u == wg), u > 2 ? (u == 3 ? 38 : 54) : 32 + u);
    }
    if (L == 0) {
      char* dst = g + (offsetof(Scratch, x) + (bi * 16 + 2 * bc) * 32768 + rh * 16384);
      unsigned* f = (unsigned*)(g + (offsetof(Scratch, flagX) + (bi * 32 + bc * 4 + rh) * 4));
      const uint32_t a = sb + rh * 16384;
      if (wg == 0) {
        mbar_wait(BAR(B_XRDY), 0); mbar_wait(BAR(B_XRDY + 2), 0);
        fence_async_smem();
        PROFY(one, 41);
        if (one) bulk_s2g(dst, a, 16384);
        bulk_wait<0>();
        PROFY(one, 45);
        if (one) { mbar_arrive(BAR(B_XFREE)); mbar_arrive(BAR(B_PFREE)); }
        fence_rel();
        mbar_wait(BAR(B_XRDY + 1), 0); mbar_wait(BAR(B_XRDY + 3), 0);
        if (one) { st_rlx(f, tag); bulk_s2g(dst + 32768, a + 32768, 16384); }
        PROFY(one, 56);
        bulk_wait<0>();
        if (one) mbar_arrive(BAR(B_XFREE + 1));
        fence_rel();
        if (one) st_rlx(f + 2, tag);
        PROFY(one, 57);
      } else {
        mbar_wait(BAR(B_XRDY + 1), 0); mbar_wait(BAR(B_XRDY + 3), 0);
        mbar_wait(BAR(B_PFREE), 0);
        if (one) bulk_s2peer(a, 16384, BAR(B_FULLQ));
        { const uint32_t t0 = clk(); while (clk() - t0 < XD_D); }
        if (one) bulk_s2peer(a + 32768, 16384, BAR(B_FULLQ + 1));
      }
      if (wg == 0) {
        uint32_t t0 = clk() + PF1_D;
        #pragma unroll 1
        for (int q = PF1_S; q < PF1_E; q++) { while ((int)(clk() - t0) < 0) __nanosleep(50); if (one) ffn_prefetch(P, q); t0 += PF1_T; }
      }
    }
  }
}

DEVI void stg_issue(const Params& P, int c, uint32_t d, uint32_t du, uint32_t b) {
  mbar_expect_tx(b, 16384);
  if (c < 8) { tma_2d_h(d, &P.mWg, FID * 32, c * 128, b, du > 8192 ? POL_T : POL_G); tma_2d_h(d + du, &P.mWu, FID * 32, c * 128, b, du > 8192 || c < U_C ? POL_FIRST : POL_NORMAL); }
  else if (c < 12) tma_3d_h(d, &P.mWd, 0, FID * 32 + (c - 8) * 8, 0, b, POL_D);
  else tma_2d_h(d, &P.mWp, (c - 12) * 1024 + (BID >> 2) * 32, (BID & 3) * 256, b, POL_EF);
}
DEVI void pace() { const uint32_t t0 = clk(); while (clk() - t0 < PACE_T); }
DEVI void stager(const Params& P, uint32_t sb) {
  {
    const int b = blockIdx.x;
    uint32_t t0 = clk();
    #pragma unroll 1
    for (int q = 0; q < PQ_N; q++) { bulk_prefetch(P.wqkv + (q * 128 + b) * 3072, 6144); while (clk() - t0 < PQ_T) __nanosleep(50); t0 += PQ_T; }
    bulk_prefetch(P.wo + b * 8192, 16384);
    #pragma unroll 1
    for (int q = 0; q < PF0_N; q++) {
      while (clk() - t0 < PF0_T) __nanosleep(50);
      t0 += PF0_T;
      ffn_prefetch(P, q);
    }
  }
  const int bid = BID, bi = bid >> 4, rh = bid & 1, bc = (bid & 15) >> 1;
  #pragma unroll 1
  for (int L = 0; L < 2; L++) {
    const int nch = L ? (FID < 112 ? 8 : 0) : 15;
    mbar_wait(BAR(B_PAR), L); mbar_wait(BAR(B_KVFULL + W0_BAR), L);
    #pragma unroll 1
    for (int m = 0, r = 0; m < 16; r = w_next(m, r), m++) {
      const int sw = (m == 3 || m == 4) ? 7 : 0, n = m ^ sw, q = r ^ sw;
      if (n == 4) { mbar_wait(BAR(B_RES), L); mbar_wait(BAR(B_ORDY + 2), L); mbar_wait(BAR(B_ORDY + 6), L); }
      else if (n >= 2) mbar_wait(n < 5 ? BAR(B_HAFREE + (n > 2)) : BAR(B_EMPTYW + q), n < 5 ? L : w_par(n, q, L) ^ 1);
      if (n == THR_N) mbar_wait(BAR(B_OFREE), L);
      mbar_expect_tx(BAR(B_FULLW + q), 16384);
      tma_5d(sb + w_off(q) + 16384, &P.mWo, 0, 0, n >> 3, 2 * (wo_order(bc, n) & 7), 2 * bc, BAR(B_FULLW + q), L ? POL_W1 : POL_W0);
      if (n == 2) {
        #pragma unroll 1
        for (int e = 0; e < 2; e++) {
          mbar_expect_tx(BAR(B_FULLW + 5), 16384);
          if (L) bulk_g2s_h(sb + 32768 + e * 16384, P.g->x[bi][2 * bc + e] + rh * 1024, 16384, BAR(B_FULLW + 5));
          else tma_2d_h(sb + 32768 + e * 16384, &P.mXh, bc * 128 + e * 64, bi * 256 + rh * 128, BAR(B_FULLW + 5), POL_EF);
        }
      }
    }
    mbar_wait(BAR(B_EMPTYW + 5), L);
    if (L && nch) {
      const bf16* src = WDSRC2;
      mbar_expect_tx(BAR(B_FULLW + 2), 32768); mbar_expect_tx(BAR(B_FULLW + 2), 24576);
      #pragma unroll 1
      for (int e = 0; e < 3; e++) { bulk_g2s_h(sb + e * 32768 + (e < 2 ? (rh ^ 1) * 16384 : 0), src + e * 8192, e < 2 ? 16384 : 24576, BAR(B_FULLW + 2)); pace(); }
    }
        if (L == 0) { mbar_arrive_peer(BAR(B_PFREE)); mbar_wait(BAR(B_EMPTYW), 0); mbar_wait(BAR(B_EMPTYW + 1), 0); }
    #pragma unroll 1
    for (int c = FID < 112 ? 0 : 12, slot = 0; c < nch; c++, slot = slot == 2 ? 0 : slot + 1) {
      const int q = (c >> 1) + (c >> 2);
      if (!L && (c == LATE_C || c == 12)) mbar_wait(BAR(LATE_B), LATE_P);
      mbar_wait(L ? BAR(B_EMPTYW + q) : BAR(B_STGE + slot), L | ((0x71c7 >> c) & 1));
      #define CC c
      stg_issue(P, CC, L ? sb + w_off(q) + (c & 1) * 8192 : sb + STG + slot * 16384, 8192 << L, L ? BAR(B_FULLW + q) : BAR(B_STG + slot));
      if (L) pace();
    }
  }
}
DEVI void sum8(uint4 v, float& s1, float& s2) {
  float e[8] = {bf_lo(v.x), bf_hi(v.x), bf_lo(v.y), bf_hi(v.y), bf_lo(v.z), bf_hi(v.z), bf_lo(v.w), bf_hi(v.w)};
  #pragma unroll
  for (int q = 0; q < 8; q++) { s1 += e[q]; s2 = fmaf(e[q], e[q], s2); }
}
DEVI uint4 norm8(uint4 x, float m, float rs) {
  #define HN(v) pack_bf16((bf_lo(v) - m) * rs, (bf_hi(v) - m) * rs)
  return make_uint4(HN(x.x), HN(x.y), HN(x.z), HN(x.w));
  #undef HN
}
DEVI void put_f32(uint4 b, uint32_t d, uint32_t d2) {
  sts128(d, make_uint4(b.x << 16, b.x & 0xffff0000u, b.y << 16, b.y & 0xffff0000u));
  sts128(d + d2, make_uint4(b.z << 16, b.z & 0xffff0000u, b.w << 16, b.w & 0xffff0000u));
}
DEVI void put_bf16(uint4 b, uint32_t d) {
  sts64f(d, __uint_as_float(b.x), __uint_as_float(b.y)); sts64f(d + 1024, __uint_as_float(b.z), __uint_as_float(b.w));
  fence_async_smem();
}
DEVI uint4 best4(uint32_t p) {
  uint4 a = lds128(p), b = lds128(p + 16), c = lds128(p + 32), d = lds128(p + 48);
  if (b.x > a.x) a = b;
  if (d.x > c.x) c = d;
  return c.x > a.x ? c : a;
}
#define FL(x) __uint_as_float(x)
#define UI(x) __float_as_uint(x)
DEVI void aux(const Params& P, uint32_t sb) {
  int tid = fresh_tid();
  #define lane (tid & 31)
  #define wq (tid >> 5)
  uint32_t ids = P.map[blockIdx.x], tag;
  #define bid ((int)(ids & 255))
  #define fid ((int)(ids >> 8))
  #define bi (bid >> 4)
  #define bp (bid & 15)
  #define bc (bp >> 1)
  #define FRESH() do { tid = fresh_tid(); uint4 z_ = ldsv128(sb + INFO2 + 16); ids = z_.y; tag = z_.z + L; idx = z_.w; } while (0)
  {
    const uint32_t epoch = ld_rlx(&P.g->epoch);
    if (tid == 0) {
      mbar_expect_tx(BAR(B_STG), 49152);
      tma_3d(sb + STG, &P.mWq, bp * 64, bi * 128, 0, BAR(B_STG));
      tma_3d(sb + STG + 24576, &P.mWq, bp * 64, bi * 128 + 64, 0, BAR(B_STG));
    }
    __syncwarp();
    sts64f(sb + ONES + tid * 8, FL(0x3F803F80u), FL(0x3F803F80u));
    float s1 = 0.f, s2 = 0.f;
    { uint4 v = __ldg((const uint4*)P.wr + tid);
      if ((tid >> 4) == bc) put_f32(v, sb + WR + (tid & 15) * 32, 16);
      sum8(v, s1, s2);
      #pragma unroll 1
      for (int o = 16; o; o >>= 1) s1 += __shfl_xor_sync(0xffffffffu, s1, o);
      sts32f(sb + INFO2 + wq * 4, s1); }
    const uint4* src = (const uint4*)(P.x0 + (size_t)bid * 16384) + (tid >> 3) * 128 + (tid & 7);
    s1 = 0.f; s2 = 0.f;
    #pragma unroll 1
    for (int it = 0; it < 16; it += 4) {
      uint4 v0 = __ldg(src + it * 8), v1 = __ldg(src + it * 8 + 8), v2 = __ldg(src + it * 8 + 16), v3 = __ldg(src + it * 8 + 24);
      #pragma unroll 1
      for (int q = 0; q < 4; q++) { sum8(v0, s1, s2); v0 = v1; v1 = v2; v2 = v3; }
    }
    #pragma unroll 1
    for (int o = 1; o < 8; o <<= 1) { s1 += __shfl_xor_sync(0xffffffffu, s1, o); s2 += __shfl_xor_sync(0xffffffffu, s2, o); }
    tag = ((epoch % 16383u) + 1u) << 2;
    if (tid == 0) { sts128(sb + INFO, make_uint4(0x40000000u, 0u, tag, ((epoch % 127u) + 1u) << 1)); sts128(sb + INFO2 + 16, make_uint4(epoch, ids, tag, 0x40000000u)); }
    float m = s1 * (1.f / 1024.f);
    if ((tid & 7) == 0) st_ll(&P.g->statF[bid * 16 + (tid >> 3)], UI(m), UI(fmaxf(fmaf(-m, m, s2 * (1.f / 1024.f)), 0.f)), 0u, tag);
    bar_sync(2, 128);
    mbar_wait_b(BAR(B_STG), 0);
    if (tid < 96) {
      s1 = 0.f; s2 = 0.f;
      #pragma unroll 1
      for (int r = 0; r < 16; r++) {
        const uint32_t a = sb + STG + (r >> 3) * 24576 + wq * 8192 + (r & 7) * 128 + ((lane * 4) ^ ((r & 7) << 4));
        #pragma unroll
        for (int e = 0; e < 8; e++) { uint32_t v = lds32(a + e * 1024); s1 += bf_lo(v); s2 += bf_hi(v); }
      }
      st_ll(&P.g->csP[bp][bi][tid], UI(s1), UI(s2), 0u, tag);
      s1 = 0.f; s2 = 0.f;
      #pragma unroll 1
      for (int q = 0; q < 8; q += 2) {
        uint4 a, b; poll_ll2(&P.g->csP[bp][q][tid], &P.g->csP[bp][q + 1][tid], 0xffffffffu, tag, a, b);
        s1 += FL(a.x) + FL(b.x); s2 += FL(a.y) + FL(b.y);
      }
      const uint32_t hi = pack_bf16(-s1, -s2);
      sts32(sb + CS + (tid >> 2) * 32 + (tid & 3) * 4, hi);
      sts32(sb + CS + (tid >> 2) * 32 + (tid & 3) * 4 + 16, pack_bf16(-s1 - bf_lo(hi), -s2 - bf_hi(hi)));
    }
    fence_async_smem();
  }
  int idx;
  #pragma unroll 1
  for (int L = 0; L < 2; L++) {
    FRESH();
    {
      sts32(sb + INFO, idx);
      bar_sync(2, 128);
    }
    const uint4 fix = lds128(sb + PATCH + 128 + (lane & 4) * 32 + (wq >> 1) * 64 + (lane & 3) * 16);
    warp_signal(BAR(B_PAR));
    PROFX(tid == 0, L ? 23 : 17);
    mbar_wait_b(BAR(B_KVFULL + wq), L);
    if ((idx >> 7) == bi * 2 - 1 - (wq & 1)) {
      if (lane < 8) sts128(sb + ((wq >> 1) ? KVB : KVA) + ((idx >> 6) & 3) * 8192 + (lane >> 2) * 4096 + (idx & 63) * 64 + (((lane ^ (idx >> 1)) & 3) << 4), fix);
      fence_async_smem();
    }
    bar_arrive(4 + wq, 160); bar_arrive(8 + wq, 160);
    FRESH();
    mbar_wait_b(BAR(B_OFREE), L);
    #define blk (bi * 2 + (bid & 1))
    if (tid < 33) st_ll(tid < 32 ? &P.g->row[blk][bc * 32 + tid] : &P.g->best[bc][blk], 0u, 0u, 0u, 0u);
    mbar_wait_b(BAR(B_XRDY), L);
    PROFX(tid == 0, 37 + L * 16);
    FRESH();
    {
      float s1 = 0.f, s2 = 0.f, d = 0.f;
      #pragma unroll 1
      for (int q = 0; q < 8; q += 4) { const float4 v = poll_sum4(&P.g->statP[q][blk * 128 + tid], 2048, tag); s1 += v.x; s2 += v.y; d += v.z; }
      PROFX(tid == 0, 39 + L * 16);
      uint4 a = lds128(sb + INFO2), b, c;
      float m = s1 * (1.f / 1024.f), var = fmaxf(fmaf(-m, m, s2 * (1.f / 1024.f)), 0.f), rs = rsqrtf(var + LN_EPS);
      uint32_t key = UI(fmaf(-m, (FL(a.x) + FL(a.y)) + (FL(a.z) + FL(a.w)), d) * rs);
      key ^= (uint32_t)((int)key >> 31) | 0x80000000u;
      uint32_t win = __ballot_sync(0xffffffffu, key == __reduce_max_sync(0xffffffffu, key));
      if (lane == __ffs(win) - 1) sts128(sb + RED + wq * 16, make_uint4(key, UI(m), UI(rs), (tag << 11) | (uint32_t)(blk * 128 + tid)));
      if (L) sts64f(sb + PAR + tid * 8, 1.f + rs, -m * rs);
      else if ((tid >> 4) == bc) st_ll(&P.g->statF[blk * 128 + tid], UI(m), UI(var), 0u, tag + 1);
      bar_sync(2, 128);
      if (wq < 2) a = best4(sb + RED);
      if (tid == 32) st_ll(&P.g->best[bc][blk], a.x, a.y, a.z, a.w);
      if (wq == 0) {
        mbar_wait(BAR(B_XRDY + 1), L); mbar_wait(BAR(B_XRDY + 3), L);
        float2 v = lds64f(sb + (lane >> 4) * 32768 + (a.w & 255) * 128 + (((lane & 15) * 8) ^ ((a.w & 7) << 4)));
        st_ll(&P.g->row[blk][bc * 32 + lane], UI(v.x), UI(v.y), 0u, tag);
        __syncwarp();
        if (lane < 2 + 2 * L) mbar_arrive(L ? BAR(B_PAR) : BAR(B_XFREE + lane));
      }
      PROFX(tid == 0, 18 + L * 6);
      FRESH();
      a = poll_ll(&P.g->best[bc][lane & 15], 0xfffff800u, tag << 11);
      win = __ffs(__ballot_sync(0xffffffffu, a.x == __reduce_max_sync(0xffffffffu, a.x))) - 1;
      idx = __shfl_sync(0xffffffffu, a.w, win) & 2047;
      PROFX(tid == 0, 19 + L * 6);
      poll_ll2(&P.g->row[win][tid], &P.g->row[win][tid + 128], 0xffffffffu, tag, c, b);
      c.z = b.x; c.w = b.y;
      a.x = __shfl_sync(0xffffffffu, a.x, win); a.y = __shfl_sync(0xffffffffu, a.y, win); a.z = __shfl_sync(0xffffffffu, a.z, win);
      sts32(sb + INFO2 + 28, idx);
      PROFX(tid == 0, 61 + L);
      b = norm8(c, FL(a.y), FL(a.z));
      if (L) put_bf16(b, sb + HV + tid * 8); else put_f32(b, sb + HV + tid * 16, 2048);
      if ((tid >> 1) == (bid & 63)) {
        sts128(sb + RED + 64 + (tid & 1) * 16, bid < 64 ? make_uint4(c.x, c.y, b.x, b.y) : make_uint4(c.z, c.w, b.z, b.w));
        sts32(sb + RED + 96, a.x);
      }
      bar_sync(2 + L, 128 + L * 256);
      if (L) {
        const int r0 = blk * 128 + (tid >> 4);
        uint32_t src = sb + ((tid >> 3) & 1) * 32768 + (r0 & 255) * 128 + (((tid ^ r0) & 7) << 4);
        uint4* dst = (uint4*)(P.out + (size_t)r0 * 1024 + bc * 128) + (tid & 15);
        #pragma unroll 4
        for (int it = 0; it < 16; it++) { uint4 v = lds128(src + it * 1024); if (idx - r0 != it * 8) dst[it * 1024] = v; }
      }
    }
    #pragma unroll 1
    for (int st = 2 * L; st < 2; st++) {
      FRESH();
      float a[8] = {0.f, 0.f, 0.f, 0.f, 0.f, 0.f, 0.f, 0.f};
      if (fid < 112) {
        uint32_t ha = st ? sb + RED + 768 + wq * 4 : sb + HV + ((wq & 1) * 64 + (lane >> 2)) * 4;
        uint32_t ph = st ? 0x1cu : 0x171u, bar = st ? BAR(B_STG + 2) : BAR(B_STG);
        uint32_t wa = sb + STG + wq * 4096 + (st ? 32768 + lane * 16 : (lane ^ (lane >> 3)) * 16);
        const uint32_t hx = st ? 256 : 512;
        const bool lead = lane == 0;
        uint4 vc = make_uint4(0u, 0u, 0u, 0u); float hc = 0.f;
        #pragma unroll 1
        do {
          mbar_wait(bar, ph & 1);
          PROFX(lead && threadIdx.x == 256 && st == 0 && (ph > 255 || ph < 4), 40 - 23 + __clz(ph));
          #pragma unroll
          for (int n = 0; n < 8; n++) { const uint4 v = lds128(wa + n * 512); const float h = lds32f(ha + n * 32); fma8(a, vc, hc); vc = v; hc = h; }
          __syncwarp();
          if (lead) mbar_arrive(bar - 8 * (B_STG - B_STGE));
          const bool wrap = bar == BAR(B_STG + 2);
          bar += wrap ? -16 : 8; wa += wrap ? -32768 : 16384; ha += hx;
          ph >>= 1;
        } while (ph != 1);
        fma8(a, vc, hc);
      }
      FRESH();
      uint4* const yp = &P.g->yP[tid & ~1][min(fid, 111)][tid & 1];
      if (st == 0) {
        sts32f(sb + RED + 256 + wq * 128 + ((lane & 3) * 8 + (lane >> 2)) * 4, fold8(a));
        bar_sync(2, 128);
        const uint32_t d = sb + RED + 256 + lane * 4;
        sts32f(sb + RED + 768 + lane * 32 + wq * 4, swiglu(lds32f(d) + lds32f(d + 128), lds32f(d + 256) + lds32f(d + 384)));
        if (fid < 112) { st_ll(yp, 0u, 0u, 0u, 0u); st_ll(yp + 224, 0u, 0u, 0u, 0u); }
        else { const uint32_t t0 = clk(); while (clk() - t0 < IDLE_T) __nanosleep(200); }
        __syncwarp();
        PROFX(tid == 0, 20);
      } else if (fid < 112) {
        const bool odd = lane & 1;
        const uint32_t t8 = lds32(sb + INFO + 12);
        #pragma unroll
        for (int e = 0; e < 4; e++) { float z = __shfl_xor_sync(0xffffffffu, odd ? a[e] : a[4 + e], 1); if (odd) a[e] = z; else a[4 + e] = z; }
        st_ll(yp, UI(a[0]), UI(a[1]), UI(a[2]), (UI(a[3]) & ~255u) | t8);
        st_ll(yp + 224, UI(a[4]), UI(a[5]), UI(a[6]), (UI(a[7]) & ~255u) | t8);
        PROFX(tid == 0, 21);
      }
    }
    {
      const uint32_t t8 = lds32(sb + INFO + 12) + L;
      const uint4* src = &P.g->yP[bid][0][min(tid, 111)];
      uint4 v0 = ld_ll(src), v1 = ld_ll(src + 112);
      uint4* dst = L ? (uint4*)(P.out + (size_t)idx * 1024 + bid * 8 + (tid & 1) * 4) : &P.g->x2[(tid >> 1) & 7][2 * bid + (tid & 1)];
      if (!L && (tid < 16 || tid >= 64)) st_ll(tid < 16 ? dst : &P.g->patch[bid][tid - 64], 0u, 0u, 0u, 0u);
      const uint32_t k = lds32(sb + RED + 96);
      const float sg = sigmoidf(FL(k ^ (~(uint32_t)((int)k >> 31) | 0x80000000u)));
      for (int it = 0; !__all_sync(0xffffffffu, ((v0.w ^ t8) & 255u) == 0 && ((v1.w ^ t8) & 255u) == 0); it++) { v0 = ld_ll(src); v1 = ld_ll(src + 112); if (it > SPIN_MAX) __trap(); }
      float y0 = FL(v0.x) + FL(v1.x), y1 = FL(v0.y) + FL(v1.y), y2 = FL(v0.z) + FL(v1.z), y3 = FL((v0.w & ~255u) | 128u) + FL((v1.w & ~255u) | 128u);
      const bool u = lane & 2, v = lane & 4;
      y0 = (u ? y2 : y0) + __shfl_xor_sync(0xffffffffu, u ? y0 : y2, 2); y1 = (u ? y3 : y1) + __shfl_xor_sync(0xffffffffu, u ? y1 : y3, 2);
      y0 = (v ? y1 : y0) + __shfl_xor_sync(0xffffffffu, v ? y0 : y1, 4);
      y0 += __shfl_xor_sync(0xffffffffu, y0, 8);
      y1 = __shfl_xor_sync(0xffffffffu, y0, 16);
      if (lane < 8) sts32f(sb + RED + 128 + wq * 32 + (lane & 1) * 16 + (lane & 2) * 4 + (lane & 4), wq < 3 ? y0 + y1 : y0);
      bar_sync(2, 128);
      if (tid < (L ? 2 : 16)) {
        const uint32_t d = sb + RED + (tid & 1) * 16;
        const uint4 xh = lds128(d + 64), a = lds128(d + 128), b = lds128(d + 160), c = lds128(d + 192), e = lds128(d + 224);
        #define FIN(f, z) fmaf((FL(a.f) + FL(b.f)) + (FL(c.f) + FL(e.f)), sg, z)
        const uint32_t r0 = pack_bf16(FIN(x, bf_lo(xh.x) + bf_lo(xh.z)), FIN(y, bf_hi(xh.x) + bf_hi(xh.z))), r1 = pack_bf16(FIN(z, bf_lo(xh.y) + bf_lo(xh.w)), FIN(w, bf_hi(xh.y) + bf_hi(xh.w)));
        #undef FIN
        if (L) *(uint2*)dst = make_uint2(r0, r1); else st_ll(dst, r0, r1, 0u, tag + 1);
      }
      PROFW(L && tid == 0, 28);
    }
    if (L == 0) {
      PROFX(tid == 0, 22);
      FRESH();
      mbar_wait(BAR(B_STG), 1); mbar_wait(BAR(B_STG + 1), 0); mbar_wait(BAR(B_STG + 2), 0);
      const uint32_t bd = (64 + (HV >> 4) + uni(bid & 3) * 32) | 0x10000u;
      uint4 x, y; poll_ll2(&P.g->x2[bi][tid], &P.g->x2[bi][tid + 128], 0xffffffffu, tag + 1, x, y);
      x.z = y.x; x.w = y.y;
      put_bf16(x, sb + HV + tid * 8);
      bar_sync(2, 128);
      PROFX(tid == 0, 30);
      float d0[4] = {0.f, 0.f, 0.f, 0.f}, d1[4] = {0.f, 0.f, 0.f, 0.f}, d2[4] = {0.f, 0.f, 0.f, 0.f};
      #pragma unroll 1
      for (int ks = 0; ks < 8; ks++) {
        const uint32_t ad = (64 + (STG >> 4) + ks * 128) | (64u << 16);
        wg_fence();
        wgmma_ss_n8<0, 1>(d0, mkd<HI64>(ad), mkd<8>(bd + ks * 4), 1);
        wgmma_ss_n8<0, 1>(d1, mkd<HI64>(ad + 1024), mkd<8>(bd + ks * 4), 1);
        wgmma_ss_n8<0, 1>(d2, mkd<HI64>(ad + 2048), mkd<8>(bd + ks * 4), 1);
        wg_commit();
      }
      if (tid == 0) mbar_arrive(BAR(B_PW));
      uint4* dst = &P.g->patch[bid][(wq & 1) * 32 + (lane >> 2) * 2 + (wq >> 1)];
      wg_wait<0>(); keep(d0); keep(d1); keep(d2);
      if ((lane & 3) == (wq >> 1)) { st_ll(dst, UI(d0[0]), UI(d1[0]), UI(d2[0]), tag + 1); st_ll(dst + 16, UI(d0[2]), UI(d1[2]), UI(d2[2]), tag + 1); }
      PROFX(tid == 0, 31);
      if ((unsigned)(bi - (idx >> 8)) < 2u) {
        if (wq == (bc & 3)) sts64f(sb + X2SEG + lane * 8, FL(bc < 4 ? x.x : x.z), FL(bc < 4 ? x.y : x.w));
        float s1 = 0.f, s2 = 0.f;
        sum8(x, s1, s2);
        #pragma unroll
        for (int o = 16; o; o >>= 1) { s1 += __shfl_xor_sync(0xffffffffu, s1, o); s2 += __shfl_xor_sync(0xffffffffu, s2, o); }
        sts64f(sb + RED + wq * 8, s1, s2);
        bar_sync(2, 128);
        x = lds128(sb + RED); y = lds128(sb + RED + 16);
        const float m = ((FL(x.x) + FL(x.z)) + (FL(y.x) + FL(y.z))) * (1.f / 1024.f);
        const float rs = rsqrtf(fmaxf(fmaf(-m, m, ((FL(x.y) + FL(x.w)) + (FL(y.y) + FL(y.w))) * (1.f / 1024.f)), 0.f) + LN_EPS);
        const uint32_t ca = sb + CS + (tid >> 4) * 32 + (tid & 1) * 16 + (tid & 14);
        const float cq = FL(lds16(ca) << 16) * m, ck = FL(lds16(ca + 256) << 16) * m, cv = FL(lds16(ca + 512) << 16) * m;
        const float4 z = poll_sum4(&P.g->patch[bp * 8 + (tid >> 6) * 4][tid & 63], 64, tag + 1);
        float q = z.x + cq, k = z.y + ck, v = z.z + cv;
        q += __shfl_xor_sync(0xffffffffu, q, 1); k += __shfl_xor_sync(0xffffffffu, k, 1); v += __shfl_xor_sync(0xffffffffu, v, 1);
        const uint32_t d = sb + PATCH + (tid & ~1), kv = pack_bf16(k * rs, v * rs);
        sts16(d, pack_bf16(q * (rs * QSCALE), 0.f)); sts16(d + 128, kv); sts16(d + 256, kv >> 16);
      }
    }
  }
  if (bid == 0 && tid == 0) P.g->epoch = lds32(sb + INFO2 + 16) + 1;
  #undef blk
  #undef bid
  #undef fid
  #undef bi
  #undef bp
  #undef bc
  #undef FRESH
  #undef lane
  #undef wq
}

__global__ void __cluster_dims__(2, 1, 1) __launch_bounds__(512, 1) fused_kernel(const __grid_constant__ Params P) {
  extern __shared__ __align__(1024) uint8_t smem_raw[];
  const uint32_t sb = smem_u32(smem_raw);
  PROFT(threadIdx.x == 0, 0);
  if (threadIdx.x < 32) { if (elect()) {
    for (int s = 0; s < 3; s++) mbar_init(BAR(B_FULLQ + s), 1);
    asm volatile("fence.mbarrier_init.release.cluster;" ::: "memory");
    #pragma unroll 1
    for (int s = 0; s < 3; s++) {
      mbar_expect_tx(BAR(B_FULLQ + s), 57344);
      tma_2d(sb + qa_off(s), &P.mX, s * 64, (BID >> 4) * 256, BAR(B_FULLQ + s));
      tma_3d(sb + qb_off(s), &P.mWq, (BID & 15) * 64, s * 64, 0, BAR(B_FULLQ + s));
    }
    if ((sb & 0x3FFFFu) != 1024) __trap();
  } } else if (threadIdx.x == 480) {
    asm volatile("prefetch.tensormap [%0];" :: "l"(&P.mWq) : "memory");
  } else if (threadIdx.x >= 32 && !(threadIdx.x & 28) && (threadIdx.x >> 3) + (threadIdx.x & 3) <= B_COUNT + 2) {
    int b = (threadIdx.x >> 3) + (threadIdx.x & 3) - 1;
    if (b >= B_COUNT) b += B_ROW - B_COUNT;
    const uint32_t cnt = b < B_XFREE ? (b == B_OFREE ? 1 : 2) : (b < B_KVRDY ? 3 : (b < B_KVFULL || b == B_PAR ? 4 : (b == B_PFREE ? 2 : 1)));
    mbar_init(BAR(b), cnt);
    asm volatile("fence.mbarrier_init.release.cluster;" ::: "memory");
  }
  __syncthreads();
  asm volatile("barrier.cluster.arrive.relaxed.aligned;" ::: "memory");
  const int wg = __shfl_sync(0xffffffffu, threadIdx.x >> 7, 0);
  if (wg < 2) { reg_inc<224>(); consumer(P, sb, wg); }
  else if (wg == 2) { reg_dec<40>(); aux(P, sb); }
  else {
    reg_dec<24>();
    asm volatile("barrier.cluster.wait.aligned;" ::: "memory");
    const int w = __shfl_sync(0xffffffffu, (threadIdx.x >> 5) & 3, 0);
    if (w == 0) loader(P, sb);
    else if (w < 3) storer(P, sb, w - 1);
    else if (elect()) stager(P, sb);
  }
}

typedef CUresult (*EncFn)(CUtensorMap*, CUtensorMapDataType, cuuint32_t, void*, const cuuint64_t*, const cuuint64_t*, const cuuint32_t*, const cuuint32_t*,
                          CUtensorMapInterleave, CUtensorMapSwizzle, CUtensorMapL2promotion, CUtensorMapFloatOOBfill);
static void mk_map(EncFn enc, CUtensorMap* m, const void* ptr, int rank, const cuuint64_t* dims, const cuuint64_t* strides, const cuuint32_t* box,
                   CUtensorMapSwizzle sw, CUtensorMapL2promotion pr) {
  cuuint32_t es[5] = {1, 1, 1, 1, 1};
  enc(m, CU_TENSOR_MAP_DATA_TYPE_BFLOAT16, rank, (void*)ptr, dims, strides, box, es, CU_TENSOR_MAP_INTERLEAVE_NONE, sw, pr, CU_TENSOR_MAP_FLOAT_OOB_FILL_NONE);
}
extern "C" void kernel_launch(void* const* d_in, const int* in_sizes, int n_in, void* d_out, int out_size) {
  (void)in_sizes; (void)n_in; (void)out_size;
  void* fn = nullptr; cudaDriverEntryPointQueryResult q;
  cudaGetDriverEntryPoint("cuTensorMapEncodeTiled", &fn, cudaEnableDefault, &q);
  EncFn enc = (EncFn)fn;
  cudaFuncSetAttribute(fused_kernel, cudaFuncAttributeMaxDynamicSharedMemorySize, SMEM_BYTES);
  Params P;
  const CUtensorMapSwizzle S128 = CU_TENSOR_MAP_SWIZZLE_128B, S64 = CU_TENSOR_MAP_SWIZZLE_64B, S0 = CU_TENSOR_MAP_SWIZZLE_NONE;
  const CUtensorMapL2promotion L256 = CU_TENSOR_MAP_L2_PROMOTION_L2_256B, L128 = CU_TENSOR_MAP_L2_PROMOTION_L2_128B;
  { cuuint64_t d[2] = {1024, 2048}, s[1] = {2048}; cuuint32_t b[2] = {64, 256}, bh[2] = {64, 128};
    mk_map(enc, &P.mX, d_in[0], 2, d, s, b, S128, L256); mk_map(enc, &P.mXh, d_in[0], 2, d, s, bh, S128, L256); }
  { cuuint64_t d[3] = {1024, 1024, 3}, s[2] = {6144, 2048}; cuuint32_t b[3] = {64, 64, 3}; mk_map(enc, &P.mWq, d_in[1], 3, d, s, b, S128, L256); }
  { cuuint64_t d[5] = {64, 32, 2, 16, 16}, s[4] = {2048, 65536, 131072, 128}; cuuint32_t b[5] = {64, 32, 1, 2, 2}; mk_map(enc, &P.mWo, d_in[2], 5, d, s, b, S128, L256); }
  { cuuint64_t d[2] = {3584, 1024}, s[1] = {7168}; cuuint32_t b[2] = {32, 128};
    mk_map(enc, &P.mWg, d_in[5], 2, d, s, b, S64, L128); mk_map(enc, &P.mWu, d_in[6], 2, d, s, b, S64, L128); }
  { cuuint64_t d[2] = {3072, 1024}, s[1] = {6144}; cuuint32_t b[2] = {32, 256}; mk_map(enc, &P.mWp, d_in[1], 2, d, s, b, S64, L128); }
  { cuuint64_t d[3] = {256, 3584, 4}, s[2] = {2048, 512}; cuuint32_t b[3] = {256, 8, 4}; mk_map(enc, &P.mWd, d_in[7], 3, d, s, b, S0, L128); }
  P.x0 = (const bf16*)d_in[0]; P.wqkv = (const bf16*)d_in[1]; P.wo = (const bf16*)d_in[2]; P.wr = (const bf16*)d_in[4]; P.wg = (const bf16*)d_in[5]; P.wu = (const bf16*)d_in[6]; P.wd = (const bf16*)d_in[7];
  P.out = (bf16*)d_out;
  cudaGetSymbolAddress((void**)&P.g, g_scr);
  for (int b = 0; b < 128; b++) {
    int j = b >> 1, quad = j < 4 ? 0 : (j < 36 ? 1 + (j - 4) % 8 : 9 + (j - 36) % 7), pos = j < 4 ? j : (j < 36 ? (j - 4) / 8 : (j - 36) / 7);
    int bid = ((quad >> 2) * 2 + (pos >> 1)) * 16 + ((quad & 3) * 2 + (pos & 1)) * 2 + (b & 1);
    int e = pos * 2 + (b & 1), fid = e < 7 ? quad * 7 + e : 112 + quad;
    P.map[b] = bid | fid << 8;
  }
  fused_kernel<<<128, 512, SMEM_BYTES>>>(P);
}
```

```cpp
#include <cuda_runtime.h>
#include <cuda_bf16.h>
#include <cuda.h>
#include <stdint.h>
#include <stddef.h>
typedef __nv_bfloat16 bf16;

template<int TB, int TA = 0> __device__ __forceinline__ void wgmma_ss_n192(float (&d)[96], uint64_t da, uint64_t db, int scale_d) {
  asm volatile("{\n.reg .pred p;\nsetp.ne.b32 p, %98, 0;\n"
    "wgmma.mma_async.sync.aligned.m64n192k16.f32.bf16.bf16 {%0, %1, %2, %3, %4, %5, %6, %7, %8, %9, %10, %11, %12, %13, %14, %15, %16, %17, %18, %19, %20, %21, %22, %23, %24, %25, %26, %27, %28, %29, %30, %31, %32, %33, %34, %35, %36, %37, %38, %39, %40, %41, %42, %43, %44, %45, %46, %47, %48, %49, %50, %51, %52, %53, %54, %55, %56, %57, %58, %59, %60, %61, %62, %63, %64, %65, %66, %67, %68, %69, %70, %71, %72, %73, %74, %75, %76, %77, %78, %79, %80, %81, %82, %83, %84, %85, %86, %87, %88, %89, %90, %91, %92, %93, %94, %95}, %96, %97, p, 1, 1, %100, %99;\n}\n"
    : "+f"(d[0]), "+f"(d[1]), "+f"(d[2]), "+f"(d[3]), "+f"(d[4]), "+f"(d[5]), "+f"(d[6]), "+f"(d[7]), "+f"(d[8]), "+f"(d[9]), "+f"(d[10]), "+f"(d[11]), "+f"(d[12]), "+f"(d[13]), "+f"(d[14]), "+f"(d[15]), "+f"(d[16]), "+f"(d[17]), "+f"(d[18]), "+f"(d[19]), "+f"(d[20]), "+f"(d[21]), "+f"(d[22]), "+f"(d[23]), "+f"(d[24]), "+f"(d[25]), "+f"(d[26]), "+f"(d[27]), "+f"(d[28]), "+f"(d[29]), "+f"(d[30]), "+f"(d[31]), "+f"(d[32]), "+f"(d[33]), "+f"(d[34]), "+f"(d[35]), "+f"(d[36]), "+f"(d[37]), "+f"(d[38]), "+f"(d[39]), "+f"(d[40]), "+f"(d[41]), "+f"(d[42]), "+f"(d[43]), "+f"(d[44]), "+f"(d[45]), "+f"(d[46]), "+f"(d[47]), "+f"(d[48]), "+f"(d[49]), "+f"(d[50]), "+f"(d[51]), "+f"(d[52]), "+f"(d[53]), "+f"(d[54]), "+f"(d[55]), "+f"(d[56]), "+f"(d[57]), "+f"(d[58]), "+f"(d[59]), "+f"(d[60]), "+f"(d[61]), "+f"(d[62]), "+f"(d[63]), "+f"(d[64]), "+f"(d[65]), "+f"(d[66]), "+f"(d[67]), "+f"(d[68]), "+f"(d[69]), "+f"(d[70]), "+f"(d[71]), "+f"(d[72]), "+f"(d[73]), "+f"(d[74]), "+f"(d[75]), "+f"(d[76]), "+f"(d[77]), "+f"(d[78]), "+f"(d[79]), "+f"(d[80]), "+f"(d[81]), "+f"(d[82]), "+f"(d[83]), "+f"(d[84]), "+f"(d[85]), "+f"(d[86]), "+f"(d[87]), "+f"(d[88]), "+f"(d[89]), "+f"(d[90]), "+f"(d[91]), "+f"(d[92]), "+f"(d[93]), "+f"(d[94]), "+f"(d[95])
    : "l"(da), "l"(db), "r"(scale_d), "n"(TB), "n"(TA));
}

template<int TB> __device__ __forceinline__ void wgmma_rs_n192(float (&d)[96], uint32_t a0, uint32_t a1, uint32_t a2, uint32_t a3, uint64_t db, int scale_d) {
  asm volatile("{\n.reg .pred p;\nsetp.ne.b32 p, %101, 0;\n"
    "wgmma.mma_async.sync.aligned.m64n192k16.f32.bf16.bf16 {%0, %1, %2, %3, %4, %5, %6, %7, %8, %9, %10, %11, %12, %13, %14, %15, %16, %17, %18, %19, %20, %21, %22, %23, %24, %25, %26, %27, %28, %29, %30, %31, %32, %33, %34, %35, %36, %37, %38, %39, %40, %41, %42, %43, %44, %45, %46, %47, %48, %49, %50, %51, %52, %53, %54, %55, %56, %57, %58, %59, %60, %61, %62, %63, %64, %65, %66, %67, %68, %69, %70, %71, %72, %73, %74, %75, %76, %77, %78, %79, %80, %81, %82, %83, %84, %85, %86, %87, %88, %89, %90, %91, %92, %93, %94, %95}, {%96, %97, %98, %99}, %100, p, 1, 1, %102;\n}\n"
    : "+f"(d[0]), "+f"(d[1]), "+f"(d[2]), "+f"(d[3]), "+f"(d[4]), "+f"(d[5]), "+f"(d[6]), "+f"(d[7]), "+f"(d[8]), "+f"(d[9]), "+f"(d[10]), "+f"(d[11]), "+f"(d[12]), "+f"(d[13]), "+f"(d[14]), "+f"(d[15]), "+f"(d[16]), "+f"(d[17]), "+f"(d[18]), "+f"(d[19]), "+f"(d[20]), "+f"(d[21]), "+f"(d[22]), "+f"(d[23]), "+f"(d[24]), "+f"(d[25]), "+f"(d[26]), "+f"(d[27]), "+f"(d[28]), "+f"(d[29]), "+f"(d[30]), "+f"(d[31]), "+f"(d[32]), "+f"(d[33]), "+f"(d[34]), "+f"(d[35]), "+f"(d[36]), "+f"(d[37]), "+f"(d[38]), "+f"(d[39]), "+f"(d[40]), "+f"(d[41]), "+f"(d[42]), "+f"(d[43]), "+f"(d[44]), "+f"(d[45]), "+f"(d[46]), "+f"(d[47]), "+f"(d[48]), "+f"(d[49]), "+f"(d[50]), "+f"(d[51]), "+f"(d[52]), "+f"(d[53]), "+f"(d[54]), "+f"(d[55]), "+f"(d[56]), "+f"(d[57]), "+f"(d[58]), "+f"(d[59]), "+f"(d[60]), "+f"(d[61]), "+f"(d[62]), "+f"(d[63]), "+f"(d[64]), "+f"(d[65]), "+f"(d[66]), "+f"(d[67]), "+f"(d[68]), "+f"(d[69]), "+f"(d[70]), "+f"(d[71]), "+f"(d[72]), "+f"(d[73]), "+f"(d[74]), "+f"(d[75]), "+f"(d[76]), "+f"(d[77]), "+f"(d[78]), "+f"(d[79]), "+f"(d[80]), "+f"(d[81]), "+f"(d[82]), "+f"(d[83]), "+f"(d[84]), "+f"(d[85]), "+f"(d[86]), "+f"(d[87]), "+f"(d[88]), "+f"(d[89]), "+f"(d[90]), "+f"(d[91]), "+f"(d[92]), "+f"(d[93]), "+f"(d[94]), "+f"(d[95])
    : "r"(a0), "r"(a1), "r"(a2), "r"(a3), "l"(db), "r"(scale_d), "n"(TB));
}

template<int TB, int TA = 0> __device__ __forceinline__ void wgmma_ss_n128(float (&d)[64], uint64_t da, uint64_t db, int scale_d) {
  asm volatile("{\n.reg .pred p;\nsetp.ne.b32 p, %66, 0;\n"
    "wgmma.mma_async.sync.aligned.m64n128k16.f32.bf16.bf16 {%0, %1, %2, %3, %4, %5, %6, %7, %8, %9, %10, %11, %12, %13, %14, %15, %16, %17, %18, %19, %20, %21, %22, %23, %24, %25, %26, %27, %28, %29, %30, %31, %32, %33, %34, %35, %36, %37, %38, %39, %40, %41, %42, %43, %44, %45, %46, %47, %48, %49, %50, %51, %52, %53, %54, %55, %56, %57, %58, %59, %60, %61, %62, %63}, %64, %65, p, 1, 1, %68, %67;\n}\n"
    : "+f"(d[0]), "+f"(d[1]), "+f"(d[2]), "+f"(d[3]), "+f"(d[4]), "+f"(d[5]), "+f"(d[6]), "+f"(d[7]), "+f"(d[8]), "+f"(d[9]), "+f"(d[10]), "+f"(d[11]), "+f"(d[12]), "+f"(d[13]), "+f"(d[14]), "+f"(d[15]), "+f"(d[16]), "+f"(d[17]), "+f"(d[18]), "+f"(d[19]), "+f"(d[20]), "+f"(d[21]), "+f"(d[22]), "+f"(d[23]), "+f"(d[24]), "+f"(d[25]), "+f"(d[26]), "+f"(d[27]), "+f"(d[28]), "+f"(d[29]), "+f"(d[30]), "+f"(d[31]), "+f"(d[32]), "+f"(d[33]), "+f"(d[34]), "+f"(d[35]), "+f"(d[36]), "+f"(d[37]), "+f"(d[38]), "+f"(d[39]), "+f"(d[40]), "+f"(d[41]), "+f"(d[42]), "+f"(d[43]), "+f"(d[44]), "+f"(d[45]), "+f"(d[46]), "+f"(d[47]), "+f"(d[48]), "+f"(d[49]), "+f"(d[50]), "+f"(d[51]), "+f"(d[52]), "+f"(d[53]), "+f"(d[54]), "+f"(d[55]), "+f"(d[56]), "+f"(d[57]), "+f"(d[58]), "+f"(d[59]), "+f"(d[60]), "+f"(d[61]), "+f"(d[62]), "+f"(d[63])
    : "l"(da), "l"(db), "r"(scale_d), "n"(TB), "n"(TA));
}

template<int TB, int TA = 0> __device__ __forceinline__ void wgmma_ss_n64(float (&d)[32], uint64_t da, uint64_t db, int scale_d) {
  asm volatile("{\n.reg .pred p;\nsetp.ne.b32 p, %34, 0;\n"
    "wgmma.mma_async.sync.aligned.m64n64k16.f32.bf16.bf16 {%0, %1, %2, %3, %4, %5, %6, %7, %8, %9, %10, %11, %12, %13, %14, %15, %16, %17, %18, %19, %20, %21, %22, %23, %24, %25, %26, %27, %28, %29, %30, %31}, %32, %33, p, 1, 1, %36, %35;\n}\n"
    : "+f"(d[0]), "+f"(d[1]), "+f"(d[2]), "+f"(d[3]), "+f"(d[4]), "+f"(d[5]), "+f"(d[6]), "+f"(d[7]), "+f"(d[8]), "+f"(d[9]), "+f"(d[10]), "+f"(d[11]), "+f"(d[12]), "+f"(d[13]), "+f"(d[14]), "+f"(d[15]), "+f"(d[16]), "+f"(d[17]), "+f"(d[18]), "+f"(d[19]), "+f"(d[20]), "+f"(d[21]), "+f"(d[22]), "+f"(d[23]), "+f"(d[24]), "+f"(d[25]), "+f"(d[26]), "+f"(d[27]), "+f"(d[28]), "+f"(d[29]), "+f"(d[30]), "+f"(d[31])
    : "l"(da), "l"(db), "r"(scale_d), "n"(TB), "n"(TA));
}

template<int TB, int TA = 0> __device__ __forceinline__ void wgmma_ss_n8(float (&d)[4], uint64_t da, uint64_t db, int scale_d) {
  asm volatile("{\n.reg .pred p;\nsetp.ne.b32 p, %6, 0;\n"
    "wgmma.mma_async.sync.aligned.m64n8k16.f32.bf16.bf16 {%0, %1, %2, %3}, %4, %5, p, 1, 1, %8, %7;\n}\n"
    : "+f"(d[0]), "+f"(d[1]), "+f"(d[2]), "+f"(d[3])
    : "l"(da), "l"(db), "r"(scale_d), "n"(TB), "n"(TA));
}

template<int TB> __device__ __forceinline__ void wgmma_rs_n40(float (&d)[20], uint32_t a0, uint32_t a1, uint32_t a2, uint32_t a3, uint64_t db, int scale_d) {
  asm volatile("{\n.reg .pred p;\nsetp.ne.b32 p, %25, 0;\n"
    "wgmma.mma_async.sync.aligned.m64n40k16.f32.bf16.bf16 {%0, %1, %2, %3, %4, %5, %6, %7, %8, %9, %10, %11, %12, %13, %14, %15, %16, %17, %18, %19}, {%20, %21, %22, %23}, %24, p, 1, 1, %26;\n}\n"
    : "+f"(d[0]), "+f"(d[1]), "+f"(d[2]), "+f"(d[3]), "+f"(d[4]), "+f"(d[5]), "+f"(d[6]), "+f"(d[7]), "+f"(d[8]), "+f"(d[9]), "+f"(d[10]), "+f"(d[11]), "+f"(d[12]), "+f"(d[13]), "+f"(d[14]), "+f"(d[15]), "+f"(d[16]), "+f"(d[17]), "+f"(d[18]), "+f"(d[19])
    : "r"(a0), "r"(a1), "r"(a2), "r"(a3), "l"(db), "r"(scale_d), "n"(TB));
}

#define DEVI __device__ __forceinline__
DEVI uint32_t smem_u32(const void* p) { return (uint32_t)__cvta_generic_to_shared(p); }
DEVI void mbar_init(uint32_t bar, uint32_t cnt) { asm volatile("mbarrier.init.shared::cta.b64 [%0], %1;" :: "r"(bar), "r"(cnt)); }
DEVI void mbar_expect_tx(uint32_t bar, uint32_t bytes) { asm volatile("mbarrier.arrive.expect_tx.shared::cta.b64 _, [%0], %1;" :: "r"(bar), "r"(bytes) : "memory"); }
DEVI void mbar_arrive(uint32_t bar) { asm volatile("mbarrier.arrive.shared::cta.b64 _, [%0];" :: "r"(bar) : "memory"); }
DEVI void mbar_arrive_peer(uint32_t bar) {
  asm volatile("{\n.reg .b32 ra;\nmapa.shared::cluster.u32 ra, %0, %1;\nmbarrier.arrive.shared::cluster.b64 _, [ra];\n}" :: "r"(bar), "r"((blockIdx.x & 1) ^ 1) : "memory");
}
DEVI void bulk_s2peer(uint32_t a, uint32_t bytes, uint32_t bar) {
  asm volatile("{\n.reg .b32 ra, rb;\nmapa.shared::cluster.u32 ra, %0, %3;\nmapa.shared::cluster.u32 rb, %2, %3;\n"
               "cp.async.bulk.shared::cluster.shared::cta.mbarrier::complete_tx::bytes [ra], [%0], %1, [rb];\n}"
               :: "r"(a), "r"(bytes), "r"(bar), "r"((blockIdx.x & 1) ^ 1) : "memory");
}
DEVI void mbar_wait(uint32_t bar, uint32_t parity) {
  asm volatile("{\n.reg .pred p;\nLW:\nmbarrier.try_wait.parity.shared::cta.b64 p, [%0], %1;\n@!p bra LW;\n}" :: "r"(bar), "r"(parity) : "memory");
}
DEVI uint32_t mbar_test(uint32_t bar, uint32_t parity) {
  uint32_t r; asm volatile("{\n.reg .pred p;\nmbarrier.test_wait.parity.shared::cta.b64 p, [%1], %2;\nselp.u32 %0, 1, 0, p;\n}" : "=r"(r) : "r"(bar), "r"(parity) : "memory"); return r;
}
DEVI void mbar_wait_b(uint32_t bar, uint32_t parity) {
  asm volatile("{\n.reg .pred p;\n.reg .u32 it;\nmov.u32 it, 0;\nLW:\nmbarrier.try_wait.parity.shared::cta.b64 p, [%0], %1;\n@p bra LD;\n"
               "add.u32 it, it, 1;\nsetp.lt.u32 p, it, 0x1000000;\n@p bra LW;\ntrap;\nLD:\n}" :: "r"(bar), "r"(parity) : "memory");
}
DEVI void tma_2d(uint32_t dst, const CUtensorMap* m, int c0, int c1, uint32_t bar) {
  asm volatile("cp.async.bulk.tensor.2d.shared::cluster.global.mbarrier::complete_tx::bytes [%0], [%1, {%3, %4}], [%2];"
    :: "r"(dst), "l"(m), "r"(bar), "r"(c0), "r"(c1) : "memory");
}
DEVI void tma_3d(uint32_t dst, const CUtensorMap* m, int c0, int c1, int c2, uint32_t bar) {
  asm volatile("cp.async.bulk.tensor.3d.shared::cluster.global.mbarrier::complete_tx::bytes [%0], [%1, {%3, %4, %5}], [%2];"
    :: "r"(dst), "l"(m), "r"(bar), "r"(c0), "r"(c1), "r"(c2) : "memory");
}
#define POL_EF POL_FIRST
constexpr uint64_t POL_FIRST = 0x12F0000000000000ull, POL_NORMAL = 0x1000000000000000ull;
DEVI void tma_2d_h(uint32_t dst, const CUtensorMap* m, int c0, int c1, uint32_t bar, uint64_t pol) {
  asm volatile("cp.async.bulk.tensor.2d.shared::cluster.global.mbarrier::complete_tx::bytes.L2::cache_hint [%0], [%1, {%3, %4}], [%2], %5;"
    :: "r"(dst), "l"(m), "r"(bar), "r"(c0), "r"(c1), "l"(pol) : "memory");
}
DEVI void tma_3d_h(uint32_t dst, const CUtensorMap* m, int c0, int c1, int c2, uint32_t bar, uint64_t pol) {
  asm volatile("cp.async.bulk.tensor.3d.shared::cluster.global.mbarrier::complete_tx::bytes.L2::cache_hint [%0], [%1, {%3, %4, %5}], [%2], %6;"
    :: "r"(dst), "l"(m), "r"(bar), "r"(c0), "r"(c1), "r"(c2), "l"(pol) : "memory");
}
DEVI void bulk_g2s_h(uint32_t s, const void* g, uint32_t bytes, uint32_t bar, uint64_t pol = POL_EF) {
  asm volatile("cp.async.bulk.shared::cluster.global.mbarrier::complete_tx::bytes.L2::cache_hint [%0], [%1], %2, [%3], %4;"
    :: "r"(s), "l"(g), "r"(bytes), "r"(bar), "l"(pol) : "memory");
}
DEVI void tma_5d(uint32_t dst, const CUtensorMap* m, int c0, int c1, int c2, int c3, int c4, uint32_t bar, uint64_t pol) {
  asm volatile("cp.async.bulk.tensor.5d.shared::cluster.global.mbarrier::complete_tx::bytes.L2::cache_hint [%0], [%1, {%3, %4, %5, %6, %7}], [%2], %8;"
    :: "r"(dst), "l"(m), "r"(bar), "r"(c0), "r"(c1), "r"(c2), "r"(c3), "r"(c4), "l"(pol) : "memory");
}
DEVI void tma_prefetch_2d(const CUtensorMap* m, int c0, int c1) {
  asm volatile("cp.async.bulk.prefetch.tensor.2d.L2.global.tile [%0, {%1, %2}];" :: "l"(m), "r"(c0), "r"(c1) : "memory");
}
DEVI void tma_prefetch_3d(const CUtensorMap* m, int c0, int c1, int c2) {
  asm volatile("cp.async.bulk.prefetch.tensor.3d.L2.global.tile [%0, {%1, %2, %3}];" :: "l"(m), "r"(c0), "r"(c1), "r"(c2) : "memory");
}
DEVI void bulk_prefetch(const void* g, uint32_t bytes) { asm volatile("cp.async.bulk.prefetch.L2.global [%0], %1;" :: "l"(g), "r"(bytes) : "memory"); }
DEVI void bulk_g2s(uint32_t s, const void* g, uint32_t bytes, uint32_t bar) {
  asm volatile("cp.async.bulk.shared::cluster.global.mbarrier::complete_tx::bytes [%0], [%1], %2, [%3];" :: "r"(s), "l"(g), "r"(bytes), "r"(bar) : "memory");
}
DEVI void bulk_s2g(void* g, uint32_t s, uint32_t bytes, uint64_t pol = POL_NORMAL) {
  asm volatile("cp.async.bulk.global.shared::cta.bulk_group.L2::cache_hint [%0], [%1], %2, %3;\ncp.async.bulk.commit_group;" :: "l"(g), "r"(s), "r"(bytes), "l"(pol) : "memory");
}
template<int N> DEVI void bulk_wait() { asm volatile("cp.async.bulk.wait_group %0;" :: "n"(N) : "memory"); }
DEVI void fence_async_smem() { asm volatile("fence.proxy.async.shared::cta;" ::: "memory"); }
DEVI void fence_async_glob() { asm volatile("fence.proxy.async.global;" ::: "memory"); }
DEVI unsigned ld_rlx(const unsigned* p) { unsigned v; asm volatile("ld.relaxed.gpu.global.u32 %0, [%1];" : "=r"(v) : "l"(p) : "memory"); return v; }
DEVI void st_rlx(unsigned* p, unsigned v) { asm volatile("st.relaxed.gpu.global.u32 [%0], %1;" :: "l"(p), "r"(v) : "memory"); }
DEVI uint2 ldg_stream(const uint2* p) { uint2 v; asm volatile("ld.global.nc.L1::no_allocate.v2.u32 {%0, %1}, [%2];" : "=r"(v.x), "=r"(v.y) : "l"(p)); return v; }
DEVI void fence_rel() { asm volatile("fence.release.gpu;" ::: "memory"); }
DEVI uint4 ld_ll(const uint4* p) {
  uint4 v;
  asm volatile("{\n.reg .b128 t;\n.reg .b64 a, b;\nld.relaxed.gpu.global.b128 t, [%4];\nmov.b128 {a, b}, t;\nmov.b64 {%0, %1}, a;\nmov.b64 {%2, %3}, b;\n}"
               : "=r"(v.x), "=r"(v.y), "=r"(v.z), "=r"(v.w) : "l"(p) : "memory");
  return v;
}
DEVI void st_ll(uint4* p, uint32_t x, uint32_t y, uint32_t z, uint32_t w) {
  asm volatile("{\n.reg .b128 t;\n.reg .b64 a, b;\nmov.b64 a, {%1, %2};\nmov.b64 b, {%3, %4};\nmov.b128 t, {a, b};\nst.relaxed.gpu.global.b128 [%0], t;\n}"
               :: "l"(p), "r"(x), "r"(y), "r"(z), "r"(w) : "memory");
}
#define SPIN_MAX 0x1000000
#define BO4 0
#define SD_T 0
DEVI uint4 poll_ll(const uint4* p, uint32_t mask, uint32_t tag) {
  uint4 v; int it = 0;
  do { v = ld_ll(p); if (++it > SPIN_MAX) __trap(); } while (!__all_sync(0xffffffffu, (v.w & mask) == tag));
  return v;
}
DEVI void poll_ll2(const uint4* p, const uint4* q, uint32_t mask, uint32_t tag, uint4& a, uint4& b) {
  int it = 0;
  do { a = ld_ll(p); b = ld_ll(q); if (++it > SPIN_MAX) __trap(); } while (!__all_sync(0xffffffffu, (a.w & mask) == tag && (b.w & mask) == tag));
}
DEVI float4 poll_sum4(const uint4* src, int stride, uint32_t tag) {
  uint4 v0, v1, v2, v3; int it = 0;
  do { if (BO4 && it) __nanosleep(BO4); v0 = ld_ll(src); v1 = ld_ll(src + stride); v2 = ld_ll(src + 2 * stride); v3 = ld_ll(src + 3 * stride); if (++it > SPIN_MAX) __trap(); }
  while (!__all_sync(0xffffffffu, v0.w == tag && v1.w == tag && v2.w == tag && v3.w == tag));
  #define S4(f) ((__uint_as_float(v0.f) + __uint_as_float(v1.f)) + (__uint_as_float(v2.f) + __uint_as_float(v3.f)))
  return make_float4(S4(x), S4(y), S4(z), 0.f);
  #undef S4
}
DEVI void bar_sync(int id, int n) { asm volatile("bar.sync %0, %1;" :: "r"(id), "r"(n) : "memory"); }
DEVI void bar_arrive(int id, int n) { asm volatile("bar.arrive %0, %1;" :: "r"(id), "r"(n) : "memory"); }
DEVI void wg_fence() { asm volatile("wgmma.fence.sync.aligned;" ::: "memory"); }
DEVI void wg_commit() { asm volatile("wgmma.commit_group.sync.aligned;" ::: "memory"); }
template<int N> DEVI void wg_wait() { asm volatile("wgmma.wait_group.sync.aligned %0;" :: "n"(N) : "memory"); }
template<int N> DEVI void reg_inc() { asm volatile("setmaxnreg.inc.sync.aligned.u32 %0;" :: "n"(N)); }
template<int N> DEVI void reg_dec() { asm volatile("setmaxnreg.dec.sync.aligned.u32 %0;" :: "n"(N)); }
DEVI float ex2f(float x) { float y; asm("ex2.approx.ftz.f32 %0, %1;" : "=f"(y) : "f"(x)); return y; }
DEVI uint32_t pack_bf16(float lo, float hi) { uint32_t r; asm("cvt.rn.bf16x2.f32 %0, %1, %2;" : "=r"(r) : "f"(hi), "f"(lo)); return r; }
DEVI float bf_lo(uint32_t v) { return __uint_as_float(v << 16); }
DEVI float bf_hi(uint32_t v) { return __uint_as_float(v & 0xffff0000u); }
DEVI float bf_round(float x) { return bf_lo(pack_bf16(x, 0.f)); }
DEVI void stsm_x4(uint32_t addr, uint32_t a, uint32_t b, uint32_t c, uint32_t d) {
  asm volatile("stmatrix.sync.aligned.m8n8.x4.shared.b16 [%0], {%1,%2,%3,%4};" :: "r"(addr), "r"(a), "r"(b), "r"(c), "r"(d) : "memory");
}
DEVI void ldsm_x4(uint32_t addr, uint32_t& a, uint32_t& b, uint32_t& c, uint32_t& d) {
  asm volatile("ldmatrix.sync.aligned.m8n8.x4.shared.b16 {%0,%1,%2,%3}, [%4];" : "=r"(a), "=r"(b), "=r"(c), "=r"(d) : "r"(addr) : "memory");
}
DEVI uint4 lds128(uint32_t a) { uint4 v; asm volatile("ld.shared.v4.u32 {%0,%1,%2,%3}, [%4];" : "=r"(v.x), "=r"(v.y), "=r"(v.z), "=r"(v.w) : "r"(a) : "memory"); return v; }
DEVI void sts128(uint32_t a, uint4 v) { asm volatile("st.shared.v4.u32 [%0], {%1,%2,%3,%4};" :: "r"(a), "r"(v.x), "r"(v.y), "r"(v.z), "r"(v.w) : "memory"); }
DEVI float2 lds64f(uint32_t a) { float2 v; asm volatile("ld.shared.v2.f32 {%0,%1}, [%2];" : "=f"(v.x), "=f"(v.y) : "r"(a) : "memory"); return v; }
DEVI void sts64f(uint32_t a, float x, float y) { asm volatile("st.shared.v2.f32 [%0], {%1,%2};" :: "r"(a), "f"(x), "f"(y) : "memory"); }
DEVI uint32_t lds32(uint32_t a) { uint32_t v; asm volatile("ld.shared.u32 %0, [%1];" : "=r"(v) : "r"(a) : "memory"); return v; }
DEVI uint32_t lds16(uint32_t a) { unsigned short v; asm volatile("ld.shared.u16 %0, [%1];" : "=h"(v) : "r"(a) : "memory"); return v; }
DEVI float lds32f(uint32_t a) { return __uint_as_float(lds32(a)); }
DEVI void sts32(uint32_t a, uint32_t v) { asm volatile("st.shared.u32 [%0], %1;" :: "r"(a), "r"(v) : "memory"); }
DEVI void sts32f(uint32_t a, float v) { sts32(a, __float_as_uint(v)); }
DEVI void sts16(uint32_t a, uint32_t v) { asm volatile("st.shared.u16 [%0], %1;" :: "r"(a), "h"((unsigned short)v) : "memory"); }
template<int N> DEVI void keep(float (&d)[N]) {
  #pragma unroll
  for (int i = 0; i < N; i++) asm volatile("" : "+f"(d[i]) :: "memory");
}
template<int N> DEVI void keep(uint32_t (&d)[N]) {
  #pragma unroll
  for (int i = 0; i < N; i++) asm volatile("" : "+r"(d[i]) :: "memory");
}
template<uint32_t HI> DEVI uint64_t mkd(uint32_t lo) { uint64_t r; asm("mov.b64 %0, {%1, %2};" : "=l"(r) : "r"(lo), "n"(HI)); return r; }
constexpr uint32_t HI128 = (1u << 30) | (1024 >> 4), HI64 = (2u << 30) | (512 >> 4);
#define VOFF(x) ((uint32_t)(x) * (uint32_t)(1 - 65536))
DEVI bool elect() { uint32_t p; asm volatile("{\n.reg .pred q;\nelect.sync _|q, 0xffffffff;\nselp.u32 %0, 1, 0, q;\n}" : "=r"(p)); return p; }
DEVI void warp_signal(uint32_t bar) { __syncwarp(); if (elect()) mbar_arrive(bar); }

#define BCP 16
#define XCP 4
struct Scratch {
  uint4 statP[8][2048];
  uint4 statF[2048];
  uint4 csP[16][8][96];
  uint4 best[8][BCP][16];
  uint4 row[16][256];
  uint4 yP[128][112][2];
  uint4 x2[XCP][256];
  uint4 patch[128][64];
  unsigned flagKV[128][32];
  unsigned flagO[8][32];
  unsigned flagX[8][32];
  unsigned epoch, pad[255];
  uint4 kv[128][4][1024];
  uint4 o[8][2][8][2][1024];
  uint4 x[8][16][2048];
  uint4 zero[1024];
};
static_assert(offsetof(Scratch, kv) % 1024 == 0, "");
__device__ __align__(1024) Scratch g_scr;
#define PROFT(cond, slot)
#define PROFW(cond, slot)
#define PROFD(cond, slot)
#define PROFX(cond, slot)
#define PROFY(cond, slot)

constexpr uint32_t SB0 = 65536, HOLE = 90112, SA2 = 98304, SB1 = 131072, SB2 = 155648, STG = 180224;
constexpr uint32_t KVA = 0, KVB = 98304, QO = 65536;
constexpr uint32_t MISC = 229376, CS = MISC, ONES = MISC + 768, BARS = MISC + 1792, INFO = MISC + 2208, WR = MISC + 2224, X2SEG = MISC + 2736, INFO2 = MISC + 2992, DUMP = MISC + 3040;
constexpr uint32_t PAR = HOLE, HV = HOLE + 2048, RED = HOLE + 6144, PATCH = 196608;
constexpr uint32_t SMEM_BYTES = 232448;
enum { B_FULLQ = 0, B_EMPTYQ = 3, B_FULLW = 6, B_EMPTYW = 12, B_HAFREE = 18, B_OFREE = 20,
       B_XFREE = 21,
       B_KVRDY = 23, B_ORDY = 27, B_XRDY = 35, B_STGE = 39,
       B_KVFULL = 42, B_RES = 46, B_PAR = 47, B_STG = 48, B_PFREE = 51, B_COUNT = 52,
       B_ROW = 154, B_PW = 155 };
#define BAR(x) (sb + BARS + 8 * (x))
DEVI uint32_t qa_off(int s) { return s == 2 ? SA2 : (uint32_t)s * 32768u; }
DEVI uint32_t qb_off(int s) { return s == 0 ? SB0 : (s == 1 ? SB1 : SB2); }
DEVI int kb_order(int bc, int n) {
  const int e = n < 9 ? n - 2 : n - 9;
  return n < 2 ? 2 * bc + n : 2 * (((e < 4 ? e + 4 : e - 4 + (e - 4 >= (bc & 3))) + (bc & 4)) & 7) + (n >= 9);
}
DEVI int wo_order(int bc, int n) { return (n & 8) | ((n + (bc & 6)) & 7); }
DEVI uint32_t w_off(int s) { return (uint32_t)((0x143065 >> (4 * s)) & 7) * 32768u; }
DEVI uint32_t w_par(int n, int s, int L) { return (n >= 6 && n < 12) ^ (s == 5) ^ (s != 2 && L); }
DEVI uint32_t w_aoff(int n, int s) { return n == 3 ? QO : w_off(s); }
DEVI int w_next(int n, int s) { return s == 5 ? 0 : (n == 13 ? 3 : s + 1); }

struct Params {
  CUtensorMap mX, mXh, mWq, mWo, mWg, mWu, mWp, mWd;
  const bf16 *x0, *wqkv, *wo, *wr, *wg, *wu, *wd;
  bf16* out;
  Scratch* g;
  unsigned map[128];
};
#define BID ((int)(P.map[blockIdx.x] & 255))
#define FID ((int)(P.map[blockIdx.x] >> 8))
DEVI uint32_t uni(uint32_t v) { return __shfl_sync(0xffffffffu, v, 0); }
#define PQ_N 8
#define PQ_T 700
#define PF0_N 10
#define PF0_T 1600
#define PF1_E 24
#define PF1_T 1100
#define POL_Q1 POL_NORMAL
#define POL_X POL_NORMAL
#define PFA0_BAR 3
#define PFA1_BAR 0
#define PFA0_M 0
#define PFA1_M 0
#define PFA0_T 900
#define PFA1_T 700
#define PF1_S PF0_N
#define PF1_D 0
#define POL_G POL_NORMAL
#define POL_U POL_FIRST
#define POL_D POL_FIRST
#define JQ_N 6
#define WDSRC (P.wd + (size_t)min(fid, 111) * 32768)
#define WDSRC2 (P.wd + FID * 32768)
#define WD_N 4
#define THR_N 5
#define KV_D 1800
#define XD_D 300
#define W0_BAR 3
#define QEF_N 99
#define PACE_T 300
#define IDLE_T 11000
#define LATE_C 99
#define LATE_B B_XFREE + 1
#define LATE_P 0
#define KV_D1 200
#define KV_D2 1200
#define KV_DL 0
#define POL_KV0 POL_FIRST
#define POL_KV1 POL_FIRST
#define POL_O0 POL_FIRST
#define POL_O1 POL_FIRST
#define POL_W0 POL_NORMAL
#define POL_W1 POL_FIRST
#define POL_T POL_FIRST
#define U_C 8
#define ST_M 0
#define POL_Q0 POL_NORMAL
constexpr float LN_EPS = 1e-5f;
constexpr float QSCALE = 0.17677669529663687f * 1.4426950408889634f;

DEVI void fma8(float (&a)[8], uint4 v, float h) {
  a[0] = fmaf(bf_lo(v.x), h, a[0]); a[1] = fmaf(bf_hi(v.x), h, a[1]); a[2] = fmaf(bf_lo(v.y), h, a[2]); a[3] = fmaf(bf_hi(v.y), h, a[3]);
  a[4] = fmaf(bf_lo(v.z), h, a[4]); a[5] = fmaf(bf_hi(v.z), h, a[5]); a[6] = fmaf(bf_lo(v.w), h, a[6]); a[7] = fmaf(bf_hi(v.w), h, a[7]);
}
DEVI uint4 ldsv128(uint32_t a) { uint4 v; asm volatile("ld.volatile.shared.v4.u32 {%0,%1,%2,%3}, [%4];" : "=r"(v.x), "=r"(v.y), "=r"(v.z), "=r"(v.w) : "r"(a) : "memory"); return v; }
DEVI float ldsv32f(uint32_t a) { float v; asm volatile("ld.volatile.shared.f32 %0, [%1];" : "=f"(v) : "r"(a) : "memory"); return v; }
DEVI uint32_t clk() { uint32_t t; asm volatile("mov.u32 %0, %%clock;" : "=r"(t)); return t; }
DEVI int fresh_tid() { int t; asm volatile("mov.u32 %0, %%tid.x;" : "=r"(t)); return t & 127; }
DEVI float fold8(const float (&a)[8]) {
  const int lane = threadIdx.x & 31;
  const bool u = lane & 16, v = lane & 8, x = lane & 4;
  float b0 = (u ? a[4] : a[0]) + __shfl_xor_sync(0xffffffffu, u ? a[0] : a[4], 16), b1 = (u ? a[5] : a[1]) + __shfl_xor_sync(0xffffffffu, u ? a[1] : a[5], 16);
  float b2 = (u ? a[6] : a[2]) + __shfl_xor_sync(0xffffffffu, u ? a[2] : a[6], 16), b3 = (u ? a[7] : a[3]) + __shfl_xor_sync(0xffffffffu, u ? a[3] : a[7], 16);
  float c0 = (v ? b2 : b0) + __shfl_xor_sync(0xffffffffu, v ? b0 : b2, 8), c1 = (v ? b3 : b1) + __shfl_xor_sync(0xffffffffu, v ? b1 : b3, 8);
  return (x ? c1 : c0) + __shfl_xor_sync(0xffffffffu, x ? c0 : c1, 4);
}
DEVI float sigmoidf(float x) { return __fdividef(1.f, 1.f + ex2f(-1.4426950408889634f * x)); }
DEVI float swiglu(float g, float u) { return g * u * sigmoidf(g); }

template<int J0, int J1> DEVI void exp_pack(const float (&s)[32], uint32_t (&p)[16]) {
  #pragma unroll
  for (int j = J0; j < J1; j++) p[j] = pack_bf16(ex2f(s[2 * j]), ex2f(s[2 * j + 1]));
}
DEVI bool attn_pack(const float (&o)[20], uint32_t (&ob)[8]) {
  const float lo = 5.421010862427522e-20f, hi = 1.8446744073709552e19f;
  float i0, i1; asm("rcp.approx.ftz.f32 %0, %1;" : "=f"(i0) : "f"(o[16])); asm("rcp.approx.ftz.f32 %0, %1;" : "=f"(i1) : "f"(o[18]));
  #pragma unroll
  for (int e = 0; e < 8; e++) ob[e] = pack_bf16(o[2 * e] * ((e & 1) ? i1 : i0), o[2 * e + 1] * ((e & 1) ? i1 : i0));
  return __all_sync(0xffffffffu, o[16] >= lo && o[16] <= hi && o[18] >= lo && o[18] <= hi);
}
DEVI void attn_store(const uint32_t (&ob)[8], bool ok, uint32_t st, uint32_t sb, uint32_t bar) {
  stsm_x4(ok ? st : sb + DUMP, ob[0], ob[1], ob[2], ob[3]); stsm_x4(ok ? st ^ 32 : sb + DUMP, ob[4], ob[5], ob[6], ob[7]);
  __syncwarp();
  asm volatile("{\n.reg .pred p, q;\nelect.sync _|q, 0xffffffff;\nsetp.ne.and.u32 p, %1, 0, q;\n@p mbarrier.arrive.shared::cta.b64 _, [%0];\n}" :: "r"(bar), "r"((uint32_t)ok) : "memory");
}
DEVI void attn_exact(uint32_t st, uint32_t kv, int t, bool hasprev, uint32_t bar) {
  const int lane = threadIdx.x & 31;
  #pragma unroll 1
  for (int row = ((threadIdx.x >> 5) & 3) * 16, n = 0; n < 16; n++, row++) {
    const int k1 = 256 + t * 64 + row;
    float m = -INFINITY, l = 0.f, o = 0.f;
    #pragma unroll 1
    for (int k0 = hasprev ? k1 - 255 : 256; k0 <= k1; k0 += 32) {
      const int k = min(k0 + lane, k1), r = k & 63;
      float sc = 0.f;
      #pragma unroll 1
      for (int c = 0; c < 16; c++) {
        uint32_t a = lds32(st + row * 64 + ((c * 4) ^ ((row & 6) << 3))), b = lds32(kv + (k >> 6) * 8192 + r * 64 + ((c * 4) ^ ((r & 6) << 3)));
        sc = fmaf(bf_lo(a), bf_lo(b), fmaf(bf_hi(a), bf_hi(b), sc));
      }
      float mn = fmaxf(m, sc);
      #pragma unroll 1
      for (int x = 16; x; x >>= 1) mn = fmaxf(mn, __shfl_xor_sync(0xffffffffu, mn, x));
      const float al = ex2f(m - mn), pr = ex2f(sc - mn);
      m = mn; l *= al; o *= al;
      #pragma unroll 1
      for (int q = k0; q <= min(k0 + 31, k1); q++) {
        const float z = __shfl_sync(0xffffffffu, pr, q - k0);
        uint32_t b = lds32(kv + (q >> 6) * 8192 + 4096 + (q & 63) * 64 + (((lane >> 1) * 4) ^ ((q & 6) << 3)));
        l += z; o = fmaf(z, (lane & 1) ? bf_hi(b) : bf_lo(b), o);
      }
    }
    __syncwarp();
    sts16(st + row * 64 + ((lane * 2) ^ ((row & 6) << 3)), pack_bf16(__fdividef(o, l), 0.f));
  }
  warp_signal(bar);
}

template<int K0, int K1, int DONE = 0> DEVI void exp_pv(const float (&s)[32], uint32_t (&p)[16], float (&o)[20], uint32_t vd, bool accum) {
  #pragma unroll
  for (int ks = K0; ks < K1; ks++) {
    if (ks >= DONE) {
      #pragma unroll
      for (int j = 4 * ks; j < 4 * ks + 4; j++) p[j] = pack_bf16(ex2f(s[2 * j]), ex2f(s[2 * j + 1]));
    }
    asm volatile("" : "+r"(p[4 * ks]), "+r"(p[4 * ks + 1]), "+r"(p[4 * ks + 2]), "+r"(p[4 * ks + 3]));
    wg_fence();
    wgmma_rs_n40<1>(o, p[ks * 4], p[ks * 4 + 1], p[ks * 4 + 2], p[ks * 4 + 3], mkd<HI64>(vd + VOFF(ks * 64)), ks ? 1 : accum);
  }
}
template<int K0, int K1> DEVI void exp_pv2(const float (&s)[32], const float (&sx)[32], uint32_t (&p)[16], uint32_t (&px)[16], float (&o)[20], uint32_t v0, uint32_t v4,
                  const uint32_t (&msk)[9], int tdiag) {
  #pragma unroll
  for (int ks = K0; ks < K1; ks++) {
    #pragma unroll
    for (int j = 4 * ks; j < 4 * ks + 4; j++) {
      const int c = 8 * (j >> 1) - 8 * (j & 1);
      const uint32_t e = pack_bf16(ex2f(c > tdiag ? s[2 * j] : sx[2 * j]), ex2f(c + 1 > tdiag ? s[2 * j + 1] : sx[2 * j + 1])), m = msk[(j >> 1) - (j & 1) + 1];
      p[j] = e & m; px[j] = e & ~m;
      asm volatile("" : "+r"(p[j]), "+r"(px[j]));
    }
    wg_fence();
    wgmma_rs_n40<1>(o, p[ks * 4], p[ks * 4 + 1], p[ks * 4 + 2], p[ks * 4 + 3], mkd<HI64>(v0 + VOFF(ks * 64)), 1);
    wgmma_rs_n40<1>(o, px[ks * 4], px[ks * 4 + 1], px[ks * 4 + 2], px[ks * 4 + 3], mkd<HI64>(v4 + VOFF(ks * 64)), 1);
  }
}

template<int J0> DEVI void qkv_store(const float (&a)[96], float p0, float p1, uint32_t d) {
  #pragma unroll
  for (int hh = 0; hh < 2; hh++) {
    const int j = 4 * (J0 + 2 * hh);
    stsm_x4(d ^ (hh << 5), pack_bf16(a[j] * p0, a[j + 1] * p0), pack_bf16(a[j + 2] * p1, a[j + 3] * p1),
                           pack_bf16(a[j + 4] * p0, a[j + 5] * p0), pack_bf16(a[j + 6] * p1, a[j + 7] * p1));
  }
}
DEVI void mean_step(float (&a)[96], float m0, float m1, uint32_t cd, bool z) {
  const uint32_t u0 = z ? 0u : __float_as_uint(m0), u1 = z ? 0u : __float_as_uint(m1);
  uint32_t ma[4] = {__byte_perm(u0, 0u, 0x1010), __byte_perm(u1, 0u, 0x1010), __byte_perm(u0, 0u, 0x3232), __byte_perm(u1, 0u, 0x3232)};
  keep(ma);
  wg_fence();
  wgmma_rs_n192<1>(a, ma[0], ma[1], ma[2], ma[3], mkd<2>(cd), 1);
  wg_commit();
}

template<bool FIRST> DEVI void qkv_block(float (&aX)[96], float (&aY)[96], uint32_t sb16, int s, int tX, int tY) {
  uint32_t a16 = sb16 + (qa_off(s) >> 4), b16 = (sb16 + (qb_off(s) >> 4)) | ((8192u >> 4) << 16);
  uint32_t ax = (a16 + tX * 512) | 0x10000u, ay = (a16 + tY * 512) | 0x10000u;
  wg_fence();
  #pragma unroll
  for (int ks = 0; ks < 4; ks++) {
    wgmma_ss_n192<1>(aX, mkd<HI128>(ax + ks * 2), mkd<HI128>(b16 + ks * 128), !(FIRST && ks == 0));
    wgmma_ss_n192<1>(aY, mkd<HI128>(ay + ks * 2), mkd<HI128>(b16 + ks * 128), !(FIRST && ks == 0));
  }
  wg_commit();
}
DEVI void qkv_half(float (&a)[96], uint32_t sb16, int t, uint32_t sa, uint32_t sbb) {
  wg_fence();
  #pragma unroll
  for (int ks = 0; ks < 4; ks++)
    wgmma_ss_n192<1>(a, mkd<HI128>(((sb16 + (sa >> 4) + t * 512) | 0x10000u) + ks * 2), mkd<HI128>(((sb16 + (sbb >> 4)) | ((8192u >> 4) << 16)) + ks * 128), 1);
  wg_commit();
}
DEVI void wo_block(float (&acc)[64], uint32_t sb16, int n, int s, int wg) {
  uint32_t a16 = (sb16 + (w_aoff(n, s) >> 4) + wg * 256) | 0x10000u, b16 = (sb16 + (w_off(s) >> 4) + 1024) | ((8192u >> 4) << 16);
  wg_fence();
  #pragma unroll
  for (int ks = 0; ks < 4; ks++)
    wgmma_ss_n128<1>(acc, mkd<HI64>(a16 + (ks >> 1) * 512 + (ks & 1) * 2), mkd<HI128>(b16 + ks * 128), 1);
  wg_commit();
}
DEVI void consumer(const Params& P, uint32_t sb, int wg) {
  const int w = uni((threadIdx.x >> 5) & 3);
  #define LAYER uni(mbar_test(BAR(B_XRDY + wg * 2 + 1), 0))
  #define IDS L = LAYER; const int tid = fresh_tid(), lane = tid & 31
  const uint32_t ids = uni(P.map[blockIdx.x]);
  const int bi = (ids >> 4) & 7, rh = ids & 1, bc = (ids & 15) >> 1, fid = ids >> 8;
  const int tX = 3 - wg, tY = wg;
  constexpr uint32_t sb16 = 1024 >> 4;
  #pragma unroll 1
  while (true) {
    int L = LAYER;
    float2 fa, fb;
    {
      float aX[96], aY[96];
      const bool lead = fresh_tid() == 0;
      mbar_wait(BAR(B_FULLQ), 0);
      PROFW(threadIdx.x == 0, L * 8 + 1);
      qkv_block<true>(aX, aY, sb16, 0, tX, tY);
      #pragma unroll 1
      for (int n = 1, s = 1, ps = 0, ph = 0; n < 14; n++) {
        mbar_wait(BAR(B_FULLQ + s), ph ^ (s ? L : 0));
        PROFD(threadIdx.x == 0 && L && (n == 2 || n == 3 || n == 7 || n == 11 || n == 13), n == 2 ? 48 : 49 + (n >> 2));
        qkv_block<false>(aX, aY, sb16, s, tX, tY);
        wg_wait<1>(); if (lead) mbar_arrive(BAR(B_EMPTYQ + ps));
        ps = s; if (s == 2) { s = 0; ph ^= 1; } else s++;
      }
      mbar_wait(BAR(B_FULLQ + 2), L);
      qkv_half(aX, sb16, tX, SA2, SB2);
      mbar_wait(BAR(B_ROW), L);
      IDS;
      const uint32_t pa = sb + PAR + (w * 16 + (lane >> 2)) * 8;
      float2 p0 = lds64f(pa + tX * 512), p1 = lds64f(pa + tX * 512 + 64), p2 = lds64f(pa + tY * 512), p3 = lds64f(pa + tY * 512 + 64);
      mean_step(aX, p0.y, p1.y, sb16 + (CS >> 4), lane & 3);
      mbar_wait(BAR(B_FULLQ), 1);
      qkv_half(aX, sb16, tX, 0, SB0);
      wg_wait<3>(); if (lead) mbar_arrive(BAR(B_EMPTYQ + 1));
      bar_sync(1, 256);
      if (L) mbar_wait(BAR(B_PW), 0);
      qkv_half(aY, sb16, tY, SA2, SB2);
      wg_wait<1>(); keep(aX);
      const int srow = w * 16 + (lane & 15);
      const uint32_t x0 = sb + srow * 64 + (((lane >> 4) ^ ((srow >> 1) & 3)) << 4), xX = x0 + (4 + tX) * 8192, xY = x0 + (4 + tY) * 8192;
      qkv_store<8>(aX, p0.x, p1.x, xX + KVA); qkv_store<16>(aX, p0.x, p1.x, xX + KVA + 4096);
      warp_signal(BAR(B_KVRDY + wg * 2));
      qkv_half(aY, sb16, tY, 0, SB0);
      mean_step(aY, p2.y, p3.y, sb16 + (CS >> 4), fresh_tid() & 3);
      wg_wait<2>(); if (lead) mbar_arrive(BAR(B_EMPTYQ + 2));
      mbar_wait(BAR(B_EMPTYQ + 2), L);
      qkv_store<12>(aX, p0.x, p1.x, xX + KVB); qkv_store<20>(aX, p0.x, p1.x, xX + KVB + 4096);
      wg_wait<0>(); keep(aY);
      if (lead) mbar_arrive(BAR(B_EMPTYQ));
      PROFW(threadIdx.x == 0, L * 8 + 2);
      qkv_store<8>(aY, p2.x, p3.x, xY + KVA); qkv_store<16>(aY, p2.x, p3.x, xY + KVA + 4096);
      qkv_store<12>(aY, p2.x, p3.x, xY + KVB); qkv_store<20>(aY, p2.x, p3.x, xY + KVB + 4096);
      warp_signal(BAR(B_KVRDY + wg * 2 + 1));
      p0.x *= QSCALE; p1.x *= QSCALE; p2.x *= QSCALE; p3.x *= QSCALE;
      mbar_wait(BAR(B_EMPTYQ), 1);
      qkv_store<0>(aX, p0.x, p1.x, x0 + QO + tX * 4096);
      qkv_store<0>(aY, p2.x, p3.x, x0 + QO + tY * 4096); qkv_store<4>(aY, p2.x, p3.x, x0 + QO + 16384 + tY * 4096);
      { const float2* f = (const float2*)&P.g->statF[bi * 256 + rh * 128 + (wg ^ rh) * 64 + w * 16 + (lane >> 2)]; fa = __ldcg(f); fb = __ldcg(f + 16); }
      mbar_wait(BAR(B_PAR), L);
      qkv_store<4>(aX, p0.x, p1.x, x0 + QO + 16384 + tX * 4096);
      const int prow = (int)uni(lds32(sb + INFO)) - bi * 256;
      if ((prow >> 4) == tX * 4 + w || (prow >> 4) == tY * 4 + w) {
        __syncwarp();
        if (lane < 24) sts128(sb + (prow & 63) * 64 + (((lane ^ (prow >> 1)) & 3) << 4) +
                              (lane < 8 ? QO + (lane >> 2) * 16384 + (prow >> 6) * 4096 : ((lane & 4) ? KVB : KVA) + (4 + (prow >> 6)) * 8192 + (lane >> 4) * 4096),
                              lds128(sb + PATCH + lane * 16));
      }
      fence_async_smem();
      bar_sync(1, 256);
    }
    PROFW(threadIdx.x == 0, L * 8 + 3);
    {
      IDS;
      float s0[32], s1[32], sx[32], o[20], op[20];
      uint32_t p0[16], p1[16], px[16], msk[9];
      const int tdiag = w * 16 + (lane >> 2) - 2 * (lane & 3);
      const uint32_t ones = (sb16 + (ONES >> 4)) << 16;
      const uint32_t qX = (sb16 + (QO >> 4) + tX * 256) | 0x10000u, qY = (sb16 + (QO >> 4) + tY * 256) | 0x10000u;
      const uint32_t kXB = (sb16 + (KVB >> 4) + tX * 512) | 0x10000u;
      uint32_t redo = 0;
      const uint32_t ost = sb + QO + (w * 16 + (lane & 15)) * 64 + (((lane >> 4) ^ ((lane >> 1) & 3)) << 4);
      #define QA(s, q, k) do { wg_fence(); wgmma_ss_n64<0>(s, mkd<HI64>(q), mkd<HI64>(k), 0); } while (0)
      #define QB(s, q, k) wgmma_ss_n64<0>(s, mkd<HI64>((q) + 2), mkd<HI64>((k) + 2), 1)
      #define QA2(q, k) do { QA(s1, q, k); wgmma_ss_n64<0>(sx, mkd<HI64>(q), mkd<HI64>((k) + 2048), 0); } while (0)
      #define QB2(q, k) do { QB(s1, q, k); QB(sx, q, (k) + 2048); } while (0)
      #define VB(v, b) ((v) + VOFF((b) * 512))
      #define MID() do { wg_commit(); wg_wait<1>(); } while (0)
      QA(s0, qX + 1024, kXB + 1536); QB(s0, qX + 1024, kXB + 1536); wg_commit();
      #pragma unroll
      for (int e = 0; e < 20; e++) o[e] = 0.f;
      wg_wait<0>(); keep(s0);
      #pragma unroll 1
      for (int h = 1; h >= 0; h--) {
        const uint32_t kXA = kXB - ((KVB - KVA) >> 4), kX = h ? kXB : kXA, vX = VOFF((kX & 0xffffu) + 256) + ones;
        QA(s1, qX + h * 1024, kX + 1024);
        #pragma unroll
        for (int e = 0; e < 20; e++) op[e] = o[e];
        keep(op);
        exp_pv<0, 1>(s0, p0, o, VB(vX, 3), false); QB(s1, qX + h * 1024, kX + 1024); wg_commit();
        exp_pv<1, 2>(s0, p0, o, VB(vX, 3), true); MID(); keep(s1);
        exp_pv<2, 4>(s0, p0, o, VB(vX, 3), true);
        { int td = tdiag; asm volatile("" : "+r"(td));
          #pragma unroll
          for (int e = 0; e < 9; e++) msk[e] = ((8 * e - 8 > td) ? 0xFFFFu : 0u) | ((8 * e - 7 > td) ? 0xFFFF0000u : 0u);
          keep(msk); }
        exp_pv<0, 2>(s1, p1, o, VB(vX, 2), true);
        bar_sync(h ? 12 + wg : 4 + wg * 4, h ? 128 : 160);
        QA(s0, qX, kXA + 512 + h * 1024);
        exp_pv<2, 3>(s1, p1, o, VB(vX, 2), true); QB(s0, qX, kXA + 512 + h * 1024);
        exp_pv<3, 4>(s1, p1, o, VB(vX, 2), true); wg_commit();
        wg_wait<0>(); keep(s0); keep(p0); keep(p1); keep(o);
      }
      #pragma unroll 1
      for (int h = 0; h < 2; h++) {
        const uint32_t kb16 = sb16 + ((h ? KVB : KVA) >> 4), kX = (kb16 + tX * 512) | 0x10000u, kY = (kb16 + tY * 512) | 0x10000u, qx = qX + h * 1024, qy = qY + h * 1024;
        const uint32_t onesP = bi ? ones : (kb16 + 1984) << 16;
        const uint32_t vX = VOFF(kb16 + tX * 512 + 256), vY = VOFF(kb16 + tY * 512 + 256);
        uint32_t ob[8], v;
        v = VB(vX + (wg ? onesP : ones), 1);
        QA2(qx, kX);
        exp_pv<0, 1>(s0, p0, o, v, true); QB2(qx, kX); wg_commit();
        exp_pv<1, 2>(s0, p0, o, v, true); MID(); keep(s1); keep(sx);
        exp_pv<2, 4>(s0, p0, o, v, true);
        QA(s0, qy, kY + 1536);
        exp_pv2<0, 1>(s1, sx, p1, px, o, vX + onesP, VB(vX + ones, 4), msk, tdiag); QB(s0, qy, kY + 1536); wg_commit();
        exp_pv2<1, 2>(s1, sx, p1, px, o, vX + onesP, VB(vX + ones, 4), msk, tdiag); MID(); keep(s0); keep(p0);
        exp_pv2<2, 4>(s1, sx, p1, px, o, vX + onesP, VB(vX + ones, 4), msk, tdiag); wg_commit();
        v = VB(vY + (wg ? ones : onesP), 3);
        QA(s1, qy, kY + 1024);
        exp_pack<0, 4>(s0, p0);
        QB(s1, qy, kY + 1024); MID(); keep(o); keep(p1); keep(px);
        bool ok = attn_pack(o, ob); keep(ob);
        exp_pv<0, 2, 1>(s0, p0, o, v, false); MID(); keep(s1);
        attn_store(ob, ok, ost + (h * 4 + tX) * 4096, sb, BAR(B_ORDY + wg * 4 + h * 2)); redo |= ok ? 0u : 1u << (h * 2);
        exp_pv<2, 4>(s0, p0, o, v, true);
        v = VB(vY + onesP, 2);
        exp_pv<0, 1>(s1, p1, o, v, true);
        bar_sync(5 + wg * 4 + h * 2, 160);
        QA(s0, qy, kY + 512);
        exp_pv<1, 2>(s1, p1, o, v, true); QB(s0, qy, kY + 512); wg_commit();
        exp_pv<2, 3>(s1, p1, o, v, true); MID(); keep(s0); keep(p0);
        exp_pv<3, 4>(s1, p1, o, v, true);
        v = VB(vY + onesP, 1);
        QA2(qy, kY);
        exp_pv<0, 1>(s0, p0, o, v, true); QB2(qy, kY); wg_commit();
        exp_pv<1, 2>(s0, p0, o, v, true); MID(); keep(s1); keep(sx); keep(p1);
        exp_pv<2, 4>(s0, p0, o, v, true);
        exp_pv2<0, 1>(s1, sx, p1, px, o, vY + onesP, VB(vY + ones, 4), msk, tdiag);
        bar_sync(6 + wg * 4, h ? 128 : 160);
        QA(s0, h ? qy : qX + 1024, kXB + 512);
        exp_pv2<1, 2>(s1, sx, p1, px, o, vY + onesP, VB(vY + ones, 4), msk, tdiag); QB(s0, h ? qy : qX + 1024, kXB + 512);
        exp_pv2<2, 4>(s1, sx, p1, px, o, vY + onesP, VB(vY + ones, 4), msk, tdiag); wg_commit();
        wg_wait<0>(); keep(o); keep(s0); keep(p0); keep(p1); keep(px);
        ok = attn_pack(o, ob); attn_store(ob, ok, ost + (h * 4 + tY) * 4096, sb, BAR(B_ORDY + wg * 4 + h * 2 + 1)); redo |= ok ? 0u : 2u << (h * 2);
        #pragma unroll
        for (int e = 0; e < 20; e++) o[e] = op[e];
      }
      #undef QA
      #undef QB
      #undef QA2
      #undef QB2
      #undef VB
      #undef MID
      if (redo) {
        #pragma unroll 1
        for (int u = 0; u < 4; u++) if ((redo >> u) & 1) {
          const int h = u >> 1, t = (u & 1) ? tY : tX;
          attn_exact(sb + QO + (h * 4 + t) * 4096, sb + (h ? KVB : KVA), t, bi > 0, BAR(B_ORDY + wg * 4 + u));
        }
      }
    }
    PROFW(threadIdx.x == 0, L * 8 + 4);
    {
      IDS;
      const int t256 = wg * 128 + tid;
      float acc[64];
      const int tt = wg ^ rh;
      const int grow = bi * 256 + rh * 128 + tt * 64 + w * 16 + (lane >> 2);
      float al0 = 1.f, be0 = 0.f, al1 = 1.f, be1 = 0.f;
      const int idx0 = (int)uni(lds32(sb + INFO));
      const uint32_t tag = lds32(sb + INFO + 8) + L;
      uint4* const sp = &P.g->statP[bc][grow + (lane & 1) * 8];
      uint4* const yp = &P.g->yP[t256 >> 1][min(fid, 111)][t256 & 1];
      if (L) {
        float r0 = rsqrtf(fa.y + LN_EPS), r1 = rsqrtf(fb.y + LN_EPS);
        if (grow != idx0) { al0 = 1.f + r0; be0 = -fa.x * r0; }
        if (grow + 8 != idx0) { al1 = 1.f + r1; be1 = -fb.x * r1; }
      }
      const int srow = tt * 64 + w * 16 + (lane & 15);
      const uint32_t ra = sb + srow * 128 + (((lane >> 4) ^ (srow & 7)) << 4);
      mbar_wait(BAR(B_FULLW + 5), L);
      if ((idx0 >> 4) == bi * 16 + rh * 8 + tt * 4 + w) {
        int r = idx0 & 127;
        if (lane < 16) sts128(sb + 32768 + (lane >> 3) * 16384 + r * 128 + (((lane & 7) ^ (r & 7)) << 4), lds128(sb + X2SEG + lane * 16));
        fence_async_smem();
        __syncwarp();
      }
      #pragma unroll
      for (int jj = 0; jj < 8; jj++) {
        uint32_t r[4]; ldsm_x4((ra + 32768 + (jj >> 2) * 16384) ^ ((jj & 3) << 5), r[0], r[1], r[2], r[3]);
        #pragma unroll
        for (int e = 0; e < 4; e++) {
          acc[8 * jj + 2 * e] = fmaf(bf_lo(r[e]), (e & 1) ? al1 : al0, (e & 1) ? be1 : be0);
          acc[8 * jj + 2 * e + 1] = fmaf(bf_hi(r[e]), (e & 1) ? al1 : al0, (e & 1) ? be1 : be0);
        }
      }
      keep(acc);
      bar_sync(12 + wg, 128);
      if (!(lane & 2)) st_ll(sp, 0u, 0u, 0u, 0u);
      uint2 wd[4];
      #pragma unroll
      for (int e = 0; e < 4; e++) { wd[e] = make_uint2(0u, 0u); if (L) wd[e] = ldg_stream((const uint2*)(WDSRC) + t256 + (28 + e) * 256); }
      PROFW(t256 == 0, L * 8 + 5);
      #pragma unroll 1
      for (int n = 0, q = 0, pq = 5; n < 16; n++) {
        mbar_wait(BAR(B_FULLW + q), w_par(n, q, L));
        PROFD(t256 == 0 && !L && (n == 4 || n == 7 || n == 8 || n == 12), (n == 7 ? 63 : 41 + (n >> 2)));
        wo_block(acc, sb16, n, q, tt);
        wg_wait<1>(); if (tid == 0) mbar_arrive(BAR(B_EMPTYW + pq));
        pq = q; q = w_next(n, q);
      }
      mbar_wait(BAR(B_EMPTYW + 5), L);
      wg_wait<0>(); keep(acc);
      if (tid == 0) mbar_arrive(BAR(B_EMPTYW + 4));
      PROFW(t256 == 0, L * 8 + 6);
      const uint32_t xa = ra + rh * 16384;
      {
        float s1a = 0.f, s2a = 0.f, da = 0.f, s1b = 0.f, s2b = 0.f, db = 0.f;
        #pragma unroll
        for (int j = 0; j < 16; j++) {
          const float* a = acc + 4 * j; float2 wv = lds64f(sb + WR + j * 32 + (lane & 3) * 8);
          s1a += a[0] + a[1]; s1b += a[2] + a[3];
          s2a = fmaf(a[0], a[0], s2a); s2b = fmaf(a[2], a[2], s2b); s2a = fmaf(a[1], a[1], s2a); s2b = fmaf(a[3], a[3], s2b);
          da = fmaf(a[0], wv.x, da); db = fmaf(a[2], wv.x, db); da = fmaf(a[1], wv.y, da); db = fmaf(a[3], wv.y, db);
        }
        bool odd = lane & 1;
        float u1 = (odd ? s1b : s1a) + __shfl_xor_sync(0xffffffffu, odd ? s1a : s1b, 1);
        float u2 = (odd ? s2b : s2a) + __shfl_xor_sync(0xffffffffu, odd ? s2a : s2b, 1);
        float u3 = (odd ? db : da) + __shfl_xor_sync(0xffffffffu, odd ? da : db, 1);
        u1 += __shfl_xor_sync(0xffffffffu, u1, 2); u2 += __shfl_xor_sync(0xffffffffu, u2, 2); u3 += __shfl_xor_sync(0xffffffffu, u3, 2);
        if (!(lane & 2)) st_ll(sp, __float_as_uint(u1), __float_as_uint(u2), __float_as_uint(u3), tag);
      }
      {
      #pragma unroll
      for (int jj = 0; jj < 8; jj++) {
        const float* a = acc + 8 * jj;
        stsm_x4((xa + (jj >> 2) * 32768) ^ ((jj & 3) << 5), pack_bf16(a[0], a[1]), pack_bf16(a[2], a[3]), pack_bf16(a[4], a[5]), pack_bf16(a[6], a[7]));
        if (jj == 7) fence_async_smem();
        if ((jj & 3) == 3) warp_signal(BAR(B_XRDY + wg * 2 + (jj >> 2)));
      }
      }
      PROFW(t256 == 0, L * 8 + 7);
      if (L) {
        mbar_wait(BAR(B_PAR), 0);
        { float2 pa = lds64f(sb + PAR + (grow & 127) * 8), pb = lds64f(sb + PAR + (grow & 127) * 8 + 64); al0 = pa.x; be0 = pa.y; al1 = pb.x; be1 = pb.y; }
        uint32_t rs[32];
        #pragma unroll
        for (int j = 0; j < 16; j++) {
          rs[2 * j] = pack_bf16(fmaf(acc[4 * j], al0, be0), fmaf(acc[4 * j + 1], al0, be0));
          rs[2 * j + 1] = pack_bf16(fmaf(acc[4 * j + 2], al1, be1), fmaf(acc[4 * j + 3], al1, be1));
        }
        #pragma unroll
        for (int jj = 0; jj < 8; jj++) stsm_x4((xa + (jj >> 2) * 32768) ^ ((jj & 3) << 5), rs[4 * jj], rs[4 * jj + 1], rs[4 * jj + 2], rs[4 * jj + 3]);
        PROFW(t256 == 0, 16);
        if (fid >= 112) bar_arrive(3, 384);
        else {
          float d[4] = {0.f, 0.f, 0.f, 0.f};
          mbar_wait(BAR(B_FULLW + wg * 3), 0); mbar_wait(BAR(B_FULLW + wg * 3 + 1), 0);
          bar_sync(3, 384);
          PROFW(t256 == 0, 29);
          #pragma unroll 1
          for (int g = 0; g < 4; g++) {
            const uint32_t ad = (sb16 + (wg ? 6144 : 10240) + (g >> 1) * 2048 + (g & 1) * 512) | (1024u << 16), bd = (sb16 + (HV >> 4) + wg * 64 + g * 16) | 0x10000u;
            wg_fence();
            #pragma unroll
            for (int ks = 0; ks < 8; ks++) wgmma_ss_n8<0, 1>(d, mkd<HI64>(ad + ks * 64), mkd<8>(bd + ks * 2), 1);
            wg_commit();
          }
          mbar_wait(BAR(B_FULLW + 2), 0);
          wg_wait<0>(); keep(d);
          if (!(lane & 3)) { sts32f(sb + PAR + 1024 + wg * 256 + w * 64 + lane, d[0]); sts32f(sb + PAR + 1056 + wg * 256 + w * 64 + lane, d[2]); }
          bar_sync(1, 256);
          const uint32_t ga = sb + PAR + 1024 + lane * 4, aa = sb + HV + (t256 >> 5) * 128;
          sts32f(aa + lane * 4, swiglu(lds32f(ga) + lds32f(ga + 256), lds32f(ga + 128) + lds32f(ga + 384)));
          __syncwarp();
          PROFW(t256 == 0, 26);
          float y0 = 0.f, y1 = 0.f, y2 = 0.f, y3 = 0.f;
          uint32_t tbl = rh ? 0x001459a8u : 0x023679a8u;
          uint4 a4 = lds128(aa + 112);
          #pragma unroll 2
          for (int n = 0; n < 8; n++, tbl >>= 4) {
            const uint32_t src = sb + t256 * 8 + (tbl & 15) * 8192;
            const uint4 an = lds128(aa + ((0x00123564u >> (4 * n)) & 15) * 16);
            #pragma unroll
            for (int e = 0; e < 4; e++) {
              const float av = __uint_as_float(e == 0 ? a4.x : (e == 1 ? a4.y : (e == 2 ? a4.z : a4.w)));
              y0 = fmaf(bf_lo(wd[e].x), av, y0); y1 = fmaf(bf_hi(wd[e].x), av, y1); y2 = fmaf(bf_lo(wd[e].y), av, y2); y3 = fmaf(bf_hi(wd[e].y), av, y3);
              const float2 v = lds64f(src + e * 2048); wd[e] = make_uint2(__float_as_uint(v.x), __float_as_uint(v.y));
            }
            a4 = an;
          }
          st_ll(yp, __float_as_uint(y0), __float_as_uint(y1), __float_as_uint(y2), (__float_as_uint(y3) & ~255u) | (lds32(sb + INFO + 12) + 1));
          PROFW(t256 == 0, 27);
        }
        return;
      }
      mbar_wait(BAR(B_XRDY + wg * 2 + 1), 0);
    }
  }
  #undef IDS
  #undef LAYER
}

DEVI void loader(const Params& P, uint32_t sb) {
  const int lane = threadIdx.x & 31;
  const int bid = uni(BID), bi = bid >> 4, bp = bid & 15, rh = bp & 1, bc = bp >> 1;
  uint32_t phq = 0, tag = 0;
  #pragma unroll 1
  for (int L = 0; L < 2; L++) {
    int s = 0;
    uint32_t rdy = 0;
    #pragma unroll 1
    for (int n = L ? 0 : 3; n < 16; n++) {
      int kb = L ? kb_order(bc, n) : n;
      mbar_wait(BAR(B_EMPTYQ + s), (phq >> s) & 1);
      phq ^= 1u << s;
      if (L && n == 1) { mbar_wait(BAR(B_XRDY + 1), 0); mbar_wait(BAR(B_XRDY + 3), 0); }
      if (elect()) {
        mbar_expect_tx(BAR(B_FULLQ + s), L && n < 2 ? 40960 : 57344);
        tma_3d_h(sb + qb_off(s), &P.mWq, bp * 64, kb * 64, 0, BAR(B_FULLQ + s), L && n >= QEF_N ? POL_FIRST : POL_NORMAL);
        if (!L) tma_2d(sb + qa_off(s), &P.mX, kb * 64, bi * 256, BAR(B_FULLQ + s));
      }
      if (L && n >= 2) {
        if (((rdy >> (2 * kb)) & 3) != 3) {
          do { rdy = __ballot_sync(0xffffffffu, ld_rlx(&P.g->flagX[bi][lane]) == tag); } while (((rdy >> (2 * kb)) & 3) != 3);
          fence_async_glob();
        }
        if (n == 3 || n == 4) mbar_wait(BAR(B_XFREE + n - 3), 0);
        if (elect()) bulk_g2s_h(sb + qa_off(s), P.g->x[bi][kb], 32768, BAR(B_FULLQ + s), POL_X);
      }
      PROFY(L && lane == 0 && (n == 2 || n == 3 || n == 9), n == 9 ? 60 : 56 + n);
      if (L && n == 2) { mbar_wait(BAR(B_FULLQ), 0); mbar_wait(BAR(B_FULLQ + 1), 1); if (lane < 2) mbar_arrive_peer(BAR(B_XFREE + lane)); }
      s = (s == 2) ? 0 : s + 1;
    }
    for (int q = 0; q < 3; q++) mbar_wait(BAR(B_EMPTYQ + q), (phq >> q) & 1);
    tag = lds32(sb + INFO + 8) + L;
    #pragma unroll 1
    for (int q = 0; q < 4; q++) {
            if (bi) {
        const unsigned* f = &P.g->flagKV[bid - 16][q];
        while (ld_rlx(f) != tag);
        fence_async_glob();
      }
      if (elect()) {
        mbar_expect_tx(BAR(B_KVFULL + q), 16384);
        bulk_g2s_h(sb + ((q >> 1) ? KVB : KVA) + ((q & 1) ? 0 : 16384), bi ? P.g->kv[bid - 16][q] : P.g->zero, 16384, BAR(B_KVFULL + q), L ? POL_KV1 : POL_KV0);
      }
      PROFY(!L && lane == 0 && bi && q != 2, 34 + (q + 1) / 2);
    }
    mbar_wait(BAR(B_ORDY), L);
    {
      const uint4* src = P.g->o[bi][0][0][rh];
      rdy = 0;
      #pragma unroll 1
      for (int n = 0, q = 0; n < 16; q = w_next(n, q), n++) {
        const int j = wo_order(bc, n);
        if (((rdy >> (2 * j)) & 3) != 3) {
          do { rdy = __ballot_sync(0xffffffffu, ld_rlx(&P.g->flagO[bi][lane]) == tag); } while (((rdy >> (2 * j)) & 3) != 3);
          fence_async_glob();
        }
        if (n >= 2) mbar_wait(n < 5 ? BAR(B_HAFREE + (n > 3)) : BAR(B_EMPTYW + q), n < 5 ? L : w_par(n, q, L) ^ 1);
        if (n == THR_N) mbar_wait(BAR(B_OFREE), L);
        if (elect()) { mbar_expect_tx(BAR(B_FULLW + q), 16384); bulk_g2s_h(sb + w_aoff(n, q), src + j * 2048, 16384, BAR(B_FULLW + q), L ? POL_O1 : POL_O0); }
      }
    }
    mbar_wait(BAR(B_OFREE), L);
  }
}

DEVI void ffn_prefetch(const Params& P, int q) {
  bulk_prefetch(q < 16 ? ((q & 1) ? P.wu : P.wg) + ((q >> 1) * 128 + blockIdx.x) * 3584 : P.wd + (min(FID, 111) * 8 + q - 16) * 4096, q < 16 ? 7168 : 8192);
}
DEVI void storer(const Params& P, uint32_t sb, int wg) {
  const int bid = uni(BID), bi = bid >> 4, rh = bid & 1, bc = (bid & 15) >> 1;
  const bool one = (threadIdx.x & 31) == 0;
  char* const g = (char*)P.g;
  const uint32_t tag0 = uni(((ld_rlx(&P.g->epoch) % 16383u) + 1u) << 2);
  #pragma unroll 1
  for (int L = 0; L < 2; L++) {
    const uint32_t tag = tag0 + L;
    if (wg) {
      #pragma unroll 1
      for (int r = threadIdx.x & 31; r < 256; r += 32) {
        uint4 v;
        do v = ld_ll(&P.g->statF[bi * 256 + r]); while (!__all_sync(0xffffffffu, v.w == tag));
        float var = __uint_as_float(v.y), c = rsqrtf(var + LN_EPS);
        if (L) { c += 1.f; c *= rsqrtf(fmaf(var * c, c, LN_EPS)); }
        const float mh = bf_round(__uint_as_float(v.x));
        sts64f(sb + PAR + r * 8, c, __uint_as_float(pack_bf16(mh, __uint_as_float(v.x) - mh)));
      }
      if (!L) mbar_wait(BAR(B_PAR), 0);
      warp_signal(BAR(B_ROW));
    }
    #pragma unroll 1
    for (int u = 0; u < 2 + 4 * wg; u++) {
      const int h = u < 2 ? u : u >> 2, hi = (u & 1) ^ 1;
      uint32_t src, dst, fl, b0, b1;
      if (u < 2) {
        src = (h ? KVB : KVA) + (3 - wg) * 16384; dst = offsetof(Scratch, kv) + (bid * 4 + h * 2 + wg) * 16384; fl = offsetof(Scratch, flagKV) + (bid * 32 + h * 2 + wg) * 4;
        b0 = BAR(B_KVRDY + ((u | wg) ? 1 : 0)); b1 = b0 + 16;
      } else {
        src = QO + (h * 2 + hi) * 8192; dst = offsetof(Scratch, o) + ((((bi * 2 + h) * 8 + bc) * 2 + hi) * 2 + rh) * 8192;
        fl = offsetof(Scratch, flagO) + (bi * 32 + h * 16 + (bid & 15)) * 4;
        b0 = BAR(B_ORDY + u - 2); b1 = b0 + 32;
      }
      mbar_wait(b0, L); mbar_wait(b1, L);
      if (u + wg == 1) {
        mbar_wait(BAR(B_PAR), L);
        const uint32_t t0 = clk(), dt = (wg ? KV_D1 : KV_D2) + (L ? KV_DL : 0); while (clk() - t0 < dt) __nanosleep(40);
      }
      fence_async_smem();
      PROFY(one && !L && u == 3 * wg, u ? 46 : 8);
      if (one && (u >= 2 || bi < 7)) bulk_s2g(g + dst, sb + src, u < 2 ? 16384 : 8192, ((ST_M >> (L * 2 + (u >= 2))) & 1) ? POL_FIRST : POL_NORMAL);
      if (one && u == 5) mbar_arrive(BAR(B_HAFREE + 1));
      if (u == 2 || u == 4) continue;
      bulk_wait<0>();
      PROFY(one && !L && u == 3 * wg, u ? 61 : 62);
      fence_rel();
      if (one) { st_rlx((unsigned*)(g + fl), tag); if (!wg || u > 2) mbar_arrive(BAR(B_HAFREE + h + (wg & h))); if (!wg && u) mbar_arrive(BAR(B_RES)); }
      PROFY(one && !L && (u > 2 || u == wg), u > 2 ? (u == 3 ? 38 : 54) : 32 + u);
    }
    if (L == 0) {
      char* dst = g + (offsetof(Scratch, x) + (bi * 16 + 2 * bc) * 32768 + rh * 16384);
      unsigned* f = (unsigned*)(g + (offsetof(Scratch, flagX) + (bi * 32 + bc * 4 + rh) * 4));
      const uint32_t a = sb + rh * 16384;
      if (wg == 0) {
        mbar_wait(BAR(B_XRDY), 0); mbar_wait(BAR(B_XRDY + 2), 0);
        fence_async_smem();
        PROFY(one, 41);
        if (one) bulk_s2g(dst, a, 16384);
        bulk_wait<0>();
        PROFY(one, 45);
        if (one) { mbar_arrive(BAR(B_XFREE)); mbar_arrive(BAR(B_PFREE)); }
        fence_rel();
        mbar_wait(BAR(B_XRDY + 1), 0); mbar_wait(BAR(B_XRDY + 3), 0);
        if (one) { st_rlx(f, tag); bulk_s2g(dst + 32768, a + 32768, 16384); }
        PROFY(one, 56);
        bulk_wait<0>();
        if (one) mbar_arrive(BAR(B_XFREE + 1));
        fence_rel();
        if (one) st_rlx(f + 2, tag);
        PROFY(one, 57);
      } else {
        mbar_wait(BAR(B_XRDY + 1), 0); mbar_wait(BAR(B_XRDY + 3), 0);
        mbar_wait(BAR(B_PFREE), 0);
        if (one) bulk_s2peer(a, 16384, BAR(B_FULLQ));
        { const uint32_t t0 = clk(); while (clk() - t0 < XD_D); }
        if (one) bulk_s2peer(a + 32768, 16384, BAR(B_FULLQ + 1));
      }
      if (wg == 0) {
        uint32_t t0 = clk() + PF1_D;
        #pragma unroll 1
        for (int q = PF1_S; q < PF1_E; q++) { while ((int)(clk() - t0) < 0) __nanosleep(50); if (one) ffn_prefetch(P, q); t0 += PF1_T; }
      }
    }
  }
}

DEVI void stg_issue(const Params& P, int c, uint32_t d, uint32_t du, uint32_t b) {
  mbar_expect_tx(b, 16384);
  if (c < 8) { tma_2d_h(d, &P.mWg, FID * 32, c * 128, b, du > 8192 ? POL_T : POL_G); tma_2d_h(d + du, &P.mWu, FID * 32, c * 128, b, du > 8192 || c < U_C ? POL_FIRST : POL_NORMAL); }
  else if (c < 12) tma_3d_h(d, &P.mWd, 0, FID * 32 + (c - 8) * 8, 0, b, POL_D);
  else tma_2d_h(d, &P.mWp, (c - 12) * 1024 + (BID >> 2) * 32, (BID & 3) * 256, b, POL_EF);
}
DEVI void pace() { const uint32_t t0 = clk(); while (clk() - t0 < PACE_T); }
DEVI void stager(const Params& P, uint32_t sb) {
  {
    const int b = blockIdx.x;
    uint32_t t0 = clk();
    #pragma unroll 1
    for (int q = 0; q < PQ_N; q++) { bulk_prefetch(P.wqkv + (q * 128 + b) * 3072, 6144); while (clk() - t0 < PQ_T) __nanosleep(50); t0 += PQ_T; }
    bulk_prefetch(P.wo + b * 8192, 16384);
    #pragma unroll 1
    for (int q = 0; q < PF0_N; q++) {
      while (clk() - t0 < PF0_T) __nanosleep(50);
      t0 += PF0_T;
      ffn_prefetch(P, q);
    }
  }
  const int bid = BID, bi = bid >> 4, rh = bid & 1, bc = (bid & 15) >> 1;
  #pragma unroll 1
  for (int L = 0; L < 2; L++) {
    const int nch = L ? (FID < 112 ? 8 : 0) : 15;
    mbar_wait(BAR(B_PAR), L); mbar_wait(BAR(B_KVFULL + W0_BAR), L);
    #pragma unroll 1
    for (int m = 0, r = 0; m < 16; r = w_next(m, r), m++) {
      const int sw = (m == 3 || m == 4) ? 7 : 0, n = m ^ sw, q = r ^ sw;
      if (n == 4) { mbar_wait(BAR(B_RES), L); mbar_wait(BAR(B_ORDY + 2), L); mbar_wait(BAR(B_ORDY + 6), L); }
      else if (n >= 2) mbar_wait(n < 5 ? BAR(B_HAFREE + (n > 2)) : BAR(B_EMPTYW + q), n < 5 ? L : w_par(n, q, L) ^ 1);
      if (n == THR_N) mbar_wait(BAR(B_OFREE), L);
      mbar_expect_tx(BAR(B_FULLW + q), 16384);
      tma_5d(sb + w_off(q) + 16384, &P.mWo, 0, 0, n >> 3, 2 * (wo_order(bc, n) & 7), 2 * bc, BAR(B_FULLW + q), L ? POL_W1 : POL_W0);
      if (n == 2) {
        #pragma unroll 1
        for (int e = 0; e < 2; e++) {
          mbar_expect_tx(BAR(B_FULLW + 5), 16384);
          if (L) bulk_g2s_h(sb + 32768 + e * 16384, P.g->x[bi][2 * bc + e] + rh * 1024, 16384, BAR(B_FULLW + 5));
          else tma_2d_h(sb + 32768 + e * 16384, &P.mXh, bc * 128 + e * 64, bi * 256 + rh * 128, BAR(B_FULLW + 5), POL_EF);
        }
      }
    }
    mbar_wait(BAR(B_EMPTYW + 5), L);
    if (L && nch) {
      const bf16* src = WDSRC2;
      mbar_expect_tx(BAR(B_FULLW + 2), 32768); mbar_expect_tx(BAR(B_FULLW + 2), 24576);
      #pragma unroll 1
      for (int e = 0; e < 3; e++) { bulk_g2s_h(sb + e * 32768 + (e < 2 ? (rh ^ 1) * 16384 : 0), src + e * 8192, e < 2 ? 16384 : 24576, BAR(B_FULLW + 2)); pace(); }
    }
        if (L == 0) { mbar_arrive_peer(BAR(B_PFREE)); mbar_wait(BAR(B_EMPTYW), 0); mbar_wait(BAR(B_EMPTYW + 1), 0); }
    #pragma unroll 1
    for (int c = FID < 112 ? 0 : 12, slot = 0; c < nch; c++, slot = slot == 2 ? 0 : slot + 1) {
      const int q = (c >> 1) + (c >> 2);
      if (!L && (c == LATE_C || c == 12)) mbar_wait(BAR(LATE_B), LATE_P);
      mbar_wait(L ? BAR(B_EMPTYW + q) : BAR(B_STGE + slot), L | ((0x71c7 >> c) & 1));
      #define CC c
      stg_issue(P, CC, L ? sb + w_off(q) + (c & 1) * 8192 : sb + STG + slot * 16384, 8192 << L, L ? BAR(B_FULLW + q) : BAR(B_STG + slot));
      if (L) pace();
    }
  }
}
DEVI void sum8(uint4 v, float& s1, float& s2) {
  float e[8] = {bf_lo(v.x), bf_hi(v.x), bf_lo(v.y), bf_hi(v.y), bf_lo(v.z), bf_hi(v.z), bf_lo(v.w), bf_hi(v.w)};
  #pragma unroll
  for (int q = 0; q < 8; q++) { s1 += e[q]; s2 = fmaf(e[q], e[q], s2); }
}
DEVI uint4 norm8(uint4 x, float m, float rs) {
  #define HN(v) pack_bf16((bf_lo(v) - m) * rs, (bf_hi(v) - m) * rs)
  return make_uint4(HN(x.x), HN(x.y), HN(x.z), HN(x.w));
  #undef HN
}
DEVI void put_f32(uint4 b, uint32_t d, uint32_t d2) {
  sts128(d, make_uint4(b.x << 16, b.x & 0xffff0000u, b.y << 16, b.y & 0xffff0000u));
  sts128(d + d2, make_uint4(b.z << 16, b.z & 0xffff0000u, b.w << 16, b.w & 0xffff0000u));
}
DEVI void put_bf16(uint4 b, uint32_t d) {
  sts64f(d, __uint_as_float(b.x), __uint_as_float(b.y)); sts64f(d + 1024, __uint_as_float(b.z), __uint_as_float(b.w));
  fence_async_smem();
}
DEVI uint4 best4(uint32_t p) {
  uint4 a = lds128(p), b = lds128(p + 16), c = lds128(p + 32), d = lds128(p + 48);
  if (b.x > a.x) a = b;
  if (d.x > c.x) c = d;
  return c.x > a.x ? c : a;
}
#define FL(x) __uint_as_float(x)
#define UI(x) __float_as_uint(x)
DEVI void aux(const Params& P, uint32_t sb) {
  int tid = fresh_tid();
  #define lane (tid & 31)
  #define wq (tid >> 5)
  uint32_t ids = P.map[blockIdx.x], tag;
  #define bid ((int)(ids & 255))
  #define fid ((int)(ids >> 8))
  #define bi (bid >> 4)
  #define bp (bid & 15)
  #define bc (bp >> 1)
  #define FRESH() do { tid = fresh_tid(); uint4 z_ = ldsv128(sb + INFO2 + 16); ids = z_.y; tag = z_.z + L; idx = z_.w; } while (0)
  {
    const uint32_t epoch = ld_rlx(&P.g->epoch);
    if (tid == 0) {
      mbar_expect_tx(BAR(B_STG), 49152);
      tma_3d(sb + STG, &P.mWq, bp * 64, bi * 128, 0, BAR(B_STG));
      tma_3d(sb + STG + 24576, &P.mWq, bp * 64, bi * 128 + 64, 0, BAR(B_STG));
    }
    __syncwarp();
    sts64f(sb + ONES + tid * 8, FL(0x3F803F80u), FL(0x3F803F80u));
    float s1 = 0.f, s2 = 0.f;
    { uint4 v = __ldg((const uint4*)P.wr + tid);
      if ((tid >> 4) == bc) put_f32(v, sb + WR + (tid & 15) * 32, 16);
      sum8(v, s1, s2);
      #pragma unroll 1
      for (int o = 16; o; o >>= 1) s1 += __shfl_xor_sync(0xffffffffu, s1, o);
      sts32f(sb + INFO2 + wq * 4, s1); }
    const uint4* src = (const uint4*)(P.x0 + (size_t)bid * 16384) + (tid >> 3) * 128 + (tid & 7);
    s1 = 0.f; s2 = 0.f;
    #pragma unroll 1
    for (int it = 0; it < 16; it += 4) {
      uint4 v0 = __ldg(src + it * 8), v1 = __ldg(src + it * 8 + 8), v2 = __ldg(src + it * 8 + 16), v3 = __ldg(src + it * 8 + 24);
      #pragma unroll 1
      for (int q = 0; q < 4; q++) { sum8(v0, s1, s2); v0 = v1; v1 = v2; v2 = v3; }
    }
    #pragma unroll 1
    for (int o = 1; o < 8; o <<= 1) { s1 += __shfl_xor_sync(0xffffffffu, s1, o); s2 += __shfl_xor_sync(0xffffffffu, s2, o); }
    tag = ((epoch % 16383u) + 1u) << 2;
    if (tid == 0) { sts128(sb + INFO, make_uint4(0x40000000u, 0u, tag, ((epoch % 127u) + 1u) << 1)); sts128(sb + INFO2 + 16, make_uint4(epoch, ids, tag, 0x40000000u)); }
    float m = s1 * (1.f / 1024.f);
    if ((tid & 7) == 0) st_ll(&P.g->statF[bid * 16 + (tid >> 3)], UI(m), UI(fmaxf(fmaf(-m, m, s2 * (1.f / 1024.f)), 0.f)), 0u, tag);
    bar_sync(2, 128);
    mbar_wait_b(BAR(B_STG), 0);
    if (tid < 96) {
      s1 = 0.f; s2 = 0.f;
      #pragma unroll 1
      for (int r = 0; r < 16; r++) {
        const uint32_t a = sb + STG + (r >> 3) * 24576 + wq * 8192 + (r & 7) * 128 + ((lane * 4) ^ ((r & 7) << 4));
        #pragma unroll
        for (int e = 0; e < 8; e++) { uint32_t v = lds32(a + e * 1024); s1 += bf_lo(v); s2 += bf_hi(v); }
      }
      st_ll(&P.g->csP[bp][bi][tid], UI(s1), UI(s2), 0u, tag);
      s1 = 0.f; s2 = 0.f;
      #pragma unroll 1
      for (int q = 0; q < 8; q += 2) {
        uint4 a, b; poll_ll2(&P.g->csP[bp][q][tid], &P.g->csP[bp][q + 1][tid], 0xffffffffu, tag, a, b);
        s1 += FL(a.x) + FL(b.x); s2 += FL(a.y) + FL(b.y);
      }
      const uint32_t hi = pack_bf16(-s1, -s2);
      sts32(sb + CS + (tid >> 2) * 32 + (tid & 3) * 4, hi);
      sts32(sb + CS + (tid >> 2) * 32 + (tid & 3) * 4 + 16, pack_bf16(-s1 - bf_lo(hi), -s2 - bf_hi(hi)));
    }
    fence_async_smem();
  }
  int idx;
  #pragma unroll 1
  for (int L = 0; L < 2; L++) {
    FRESH();
    {
      sts32(sb + INFO, idx);
      bar_sync(2, 128);
    }
    const uint4 fix = lds128(sb + PATCH + 128 + (lane & 4) * 32 + (wq >> 1) * 64 + (lane & 3) * 16);
    warp_signal(BAR(B_PAR));
    PROFX(tid == 0, L ? 23 : 17);
    mbar_wait_b(BAR(B_KVFULL + wq), L);
    if ((idx >> 7) == bi * 2 - 1 - (wq & 1)) {
      if (lane < 8) sts128(sb + ((wq >> 1) ? KVB : KVA) + ((idx >> 6) & 3) * 8192 + (lane >> 2) * 4096 + (idx & 63) * 64 + (((lane ^ (idx >> 1)) & 3) << 4), fix);
      fence_async_smem();
    }
    bar_arrive(4 + wq, 160); bar_arrive(8 + wq, 160);
    FRESH();
    mbar_wait_b(BAR(B_OFREE), L);
    #define blk (bi * 2 + (bid & 1))
    if (tid < 32 + BCP) st_ll(tid < 32 ? &P.g->row[blk][bc * 32 + tid] : &P.g->best[bc][tid - 32][blk], 0u, 0u, 0u, 0u);
    mbar_wait_b(BAR(B_XRDY), L);
    PROFX(tid == 0, 37 + L * 16);
    if (SD_T) __nanosleep(SD_T);
    FRESH();
    {
      float s1 = 0.f, s2 = 0.f, d = 0.f;
      #pragma unroll 1
      for (int q = 0; q < 8; q += 4) { const float4 v = poll_sum4(&P.g->statP[q][blk * 128 + tid], 2048, tag); s1 += v.x; s2 += v.y; d += v.z; }
      PROFX(tid == 0, 39 + L * 16);
      uint4 a = lds128(sb + INFO2), b, c;
      float m = s1 * (1.f / 1024.f), var = fmaxf(fmaf(-m, m, s2 * (1.f / 1024.f)), 0.f), rs = rsqrtf(var + LN_EPS);
      uint32_t key = UI(fmaf(-m, (FL(a.x) + FL(a.y)) + (FL(a.z) + FL(a.w)), d) * rs);
      key ^= (uint32_t)((int)key >> 31) | 0x80000000u;
      uint32_t win = __ballot_sync(0xffffffffu, key == __reduce_max_sync(0xffffffffu, key));
      if (lane == __ffs(win) - 1) sts128(sb + RED + wq * 16, make_uint4(key, UI(m), UI(rs), (tag << 11) | (uint32_t)(blk * 128 + tid)));
      if (L) sts64f(sb + PAR + tid * 8, 1.f + rs, -m * rs);
      else if ((tid >> 4) == bc) st_ll(&P.g->statF[blk * 128 + tid], UI(m), UI(var), 0u, tag + 1);
      bar_sync(2, 128);
      if (wq < 2) a = best4(sb + RED);
      if (wq == 1 && lane < BCP) st_ll(&P.g->best[bc][lane][blk], a.x, a.y, a.z, a.w);
      if (wq == 0) {
        mbar_wait(BAR(B_XRDY + 1), L); mbar_wait(BAR(B_XRDY + 3), L);
        float2 v = lds64f(sb + (lane >> 4) * 32768 + (a.w & 255) * 128 + (((lane & 15) * 8) ^ ((a.w & 7) << 4)));
        st_ll(&P.g->row[blk][bc * 32 + lane], UI(v.x), UI(v.y), 0u, tag);
        __syncwarp();
        if (lane < 2 + 2 * L) mbar_arrive(L ? BAR(B_PAR) : BAR(B_XFREE + lane));
      }
      PROFX(tid == 0, 18 + L * 6);
      FRESH();
      a = poll_ll(&P.g->best[bc][blk & (BCP - 1)][lane & 15], 0xfffff800u, tag << 11);
      win = __ffs(__ballot_sync(0xffffffffu, a.x == __reduce_max_sync(0xffffffffu, a.x))) - 1;
      idx = __shfl_sync(0xffffffffu, a.w, win) & 2047;
      PROFX(tid == 0, 19 + L * 6);
      poll_ll2(&P.g->row[win][tid], &P.g->row[win][tid + 128], 0xffffffffu, tag, c, b);
      c.z = b.x; c.w = b.y;
      a.x = __shfl_sync(0xffffffffu, a.x, win); a.y = __shfl_sync(0xffffffffu, a.y, win); a.z = __shfl_sync(0xffffffffu, a.z, win);
      sts32(sb + INFO2 + 28, idx);
      PROFX(tid == 0, 61 + L);
      b = norm8(c, FL(a.y), FL(a.z));
      if (L) put_bf16(b, sb + HV + tid * 8); else put_f32(b, sb + HV + tid * 16, 2048);
      if ((tid >> 1) == (bid & 63)) {
        sts128(sb + RED + 64 + (tid & 1) * 16, bid < 64 ? make_uint4(c.x, c.y, b.x, b.y) : make_uint4(c.z, c.w, b.z, b.w));
        sts32(sb + RED + 96, a.x);
      }
      bar_sync(2 + L, 128 + L * 256);
      if (L) {
        const int r0 = blk * 128 + (tid >> 4);
        uint32_t src = sb + ((tid >> 3) & 1) * 32768 + (r0 & 255) * 128 + (((tid ^ r0) & 7) << 4);
        uint4* dst = (uint4*)(P.out + (size_t)r0 * 1024 + bc * 128) + (tid & 15);
        #pragma unroll 4
        for (int it = 0; it < 16; it++) { uint4 v = lds128(src + it * 1024); if (idx - r0 != it * 8) dst[it * 1024] = v; }
      }
    }
    #pragma unroll 1
    for (int st = 2 * L; st < 2; st++) {
      FRESH();
      float a[8] = {0.f, 0.f, 0.f, 0.f, 0.f, 0.f, 0.f, 0.f};
      if (fid < 112) {
        uint32_t ha = st ? sb + RED + 768 + wq * 4 : sb + HV + ((wq & 1) * 64 + (lane >> 2)) * 4;
        uint32_t ph = st ? 0x1cu : 0x171u, bar = st ? BAR(B_STG + 2) : BAR(B_STG);
        uint32_t wa = sb + STG + wq * 4096 + (st ? 32768 + lane * 16 : (lane ^ (lane >> 3)) * 16);
        const uint32_t hx = st ? 256 : 512;
        const bool lead = lane == 0;
        uint4 vc = make_uint4(0u, 0u, 0u, 0u); float hc = 0.f;
        #pragma unroll 1
        do {
          mbar_wait(bar, ph & 1);
          PROFX(lead && threadIdx.x == 256 && st == 0 && (ph > 255 || ph < 4), 40 - 23 + __clz(ph));
          #pragma unroll
          for (int n = 0; n < 8; n++) { const uint4 v = lds128(wa + n * 512); const float h = lds32f(ha + n * 32); fma8(a, vc, hc); vc = v; hc = h; }
          __syncwarp();
          if (lead) mbar_arrive(bar - 8 * (B_STG - B_STGE));
          const bool wrap = bar == BAR(B_STG + 2);
          bar += wrap ? -16 : 8; wa += wrap ? -32768 : 16384; ha += hx;
          ph >>= 1;
        } while (ph != 1);
        fma8(a, vc, hc);
      }
      FRESH();
      uint4* const yp = &P.g->yP[tid & ~1][min(fid, 111)][tid & 1];
      if (st == 0) {
        sts32f(sb + RED + 256 + wq * 128 + ((lane & 3) * 8 + (lane >> 2)) * 4, fold8(a));
        bar_sync(2, 128);
        const uint32_t d = sb + RED + 256 + lane * 4;
        sts32f(sb + RED + 768 + lane * 32 + wq * 4, swiglu(lds32f(d) + lds32f(d + 128), lds32f(d + 256) + lds32f(d + 384)));
        if (fid < 112) { st_ll(yp, 0u, 0u, 0u, 0u); st_ll(yp + 224, 0u, 0u, 0u, 0u); }
        else { const uint32_t t0 = clk(); while (clk() - t0 < IDLE_T) __nanosleep(200); }
        __syncwarp();
        PROFX(tid == 0, 20);
      } else if (fid < 112) {
        const bool odd = lane & 1;
        const uint32_t t8 = lds32(sb + INFO + 12);
        #pragma unroll
        for (int e = 0; e < 4; e++) { float z = __shfl_xor_sync(0xffffffffu, odd ? a[e] : a[4 + e], 1); if (odd) a[e] = z; else a[4 + e] = z; }
        st_ll(yp, UI(a[0]), UI(a[1]), UI(a[2]), (UI(a[3]) & ~255u) | t8);
        st_ll(yp + 224, UI(a[4]), UI(a[5]), UI(a[6]), (UI(a[7]) & ~255u) | t8);
        PROFX(tid == 0, 21);
      }
    }
    {
      const uint32_t t8 = lds32(sb + INFO + 12) + L;
      const uint4* src = &P.g->yP[bid][0][min(tid, 111)];
      uint4 v0 = ld_ll(src), v1 = ld_ll(src + 112);
      uint4* dst = L ? (uint4*)(P.out + (size_t)idx * 1024 + bid * 8 + (tid & 1) * 4) : &P.g->x2[(tid >> 1) & (XCP - 1)][2 * bid + (tid & 1)];
      if (!L && (tid < 2 * XCP || tid >= 64)) st_ll(tid < 64 ? dst : &P.g->patch[bid][tid - 64], 0u, 0u, 0u, 0u);
      const uint32_t k = lds32(sb + RED + 96);
      const float sg = sigmoidf(FL(k ^ (~(uint32_t)((int)k >> 31) | 0x80000000u)));
      for (int it = 0; !__all_sync(0xffffffffu, ((v0.w ^ t8) & 255u) == 0 && ((v1.w ^ t8) & 255u) == 0); it++) { v0 = ld_ll(src); v1 = ld_ll(src + 112); if (it > SPIN_MAX) __trap(); }
      float y0 = FL(v0.x) + FL(v1.x), y1 = FL(v0.y) + FL(v1.y), y2 = FL(v0.z) + FL(v1.z), y3 = FL((v0.w & ~255u) | 128u) + FL((v1.w & ~255u) | 128u);
      const bool u = lane & 2, v = lane & 4;
      y0 = (u ? y2 : y0) + __shfl_xor_sync(0xffffffffu, u ? y0 : y2, 2); y1 = (u ? y3 : y1) + __shfl_xor_sync(0xffffffffu, u ? y1 : y3, 2);
      y0 = (v ? y1 : y0) + __shfl_xor_sync(0xffffffffu, v ? y0 : y1, 4);
      y0 += __shfl_xor_sync(0xffffffffu, y0, 8);
      y1 = __shfl_xor_sync(0xffffffffu, y0, 16);
      if (lane < 8) sts32f(sb + RED + 128 + wq * 32 + (lane & 1) * 16 + (lane & 2) * 4 + (lane & 4), wq < 3 ? y0 + y1 : y0);
      bar_sync(2, 128);
      if (tid < (L ? 2 : 2 * XCP)) {
        const uint32_t d = sb + RED + (tid & 1) * 16;
        const uint4 xh = lds128(d + 64), a = lds128(d + 128), b = lds128(d + 160), c = lds128(d + 192), e = lds128(d + 224);
        #define FIN(f, z) fmaf((FL(a.f) + FL(b.f)) + (FL(c.f) + FL(e.f)), sg, z)
        const uint32_t r0 = pack_bf16(FIN(x, bf_lo(xh.x) + bf_lo(xh.z)), FIN(y, bf_hi(xh.x) + bf_hi(xh.z))), r1 = pack_bf16(FIN(z, bf_lo(xh.y) + bf_lo(xh.w)), FIN(w, bf_hi(xh.y) + bf_hi(xh.w)));
        #undef FIN
        if (L) *(uint2*)dst = make_uint2(r0, r1); else st_ll(dst, r0, r1, 0u, tag + 1);
      }
      PROFW(L && tid == 0, 28);
    }
    if (L == 0) {
      PROFX(tid == 0, 22);
      FRESH();
      mbar_wait(BAR(B_STG), 1); mbar_wait(BAR(B_STG + 1), 0); mbar_wait(BAR(B_STG + 2), 0);
      const uint32_t bd = (64 + (HV >> 4) + uni(bid & 3) * 32) | 0x10000u;
      uint4 x, y; poll_ll2(&P.g->x2[bid * XCP >> 7][tid], &P.g->x2[bid * XCP >> 7][tid + 128], 0xffffffffu, tag + 1, x, y);
      x.z = y.x; x.w = y.y;
      put_bf16(x, sb + HV + tid * 8);
      bar_sync(2, 128);
      PROFX(tid == 0, 30);
      float d0[4] = {0.f, 0.f, 0.f, 0.f}, d1[4] = {0.f, 0.f, 0.f, 0.f}, d2[4] = {0.f, 0.f, 0.f, 0.f};
      #pragma unroll 1
      for (int ks = 0; ks < 8; ks++) {
        const uint32_t ad = (64 + (STG >> 4) + ks * 128) | (64u << 16);
        wg_fence();
        wgmma_ss_n8<0, 1>(d0, mkd<HI64>(ad), mkd<8>(bd + ks * 4), 1);
        wgmma_ss_n8<0, 1>(d1, mkd<HI64>(ad + 1024), mkd<8>(bd + ks * 4), 1);
        wgmma_ss_n8<0, 1>(d2, mkd<HI64>(ad + 2048), mkd<8>(bd + ks * 4), 1);
        wg_commit();
      }
      if (tid == 0) mbar_arrive(BAR(B_PW));
      uint4* dst = &P.g->patch[bid][(wq & 1) * 32 + (lane >> 2) * 2 + (wq >> 1)];
      wg_wait<0>(); keep(d0); keep(d1); keep(d2);
      if ((lane & 3) == (wq >> 1)) { st_ll(dst, UI(d0[0]), UI(d1[0]), UI(d2[0]), tag + 1); st_ll(dst + 16, UI(d0[2]), UI(d1[2]), UI(d2[2]), tag + 1); }
      PROFX(tid == 0, 31);
      if ((unsigned)(bi - (idx >> 8)) < 2u) {
        if (wq == (bc & 3)) sts64f(sb + X2SEG + lane * 8, FL(bc < 4 ? x.x : x.z), FL(bc < 4 ? x.y : x.w));
        float s1 = 0.f, s2 = 0.f;
        sum8(x, s1, s2);
        #pragma unroll
        for (int o = 16; o; o >>= 1) { s1 += __shfl_xor_sync(0xffffffffu, s1, o); s2 += __shfl_xor_sync(0xffffffffu, s2, o); }
        sts64f(sb + RED + wq * 8, s1, s2);
        bar_sync(2, 128);
        x = lds128(sb + RED); y = lds128(sb + RED + 16);
        const float m = ((FL(x.x) + FL(x.z)) + (FL(y.x) + FL(y.z))) * (1.f / 1024.f);
        const float rs = rsqrtf(fmaxf(fmaf(-m, m, ((FL(x.y) + FL(x.w)) + (FL(y.y) + FL(y.w))) * (1.f / 1024.f)), 0.f) + LN_EPS);
        const uint32_t ca = sb + CS + (tid >> 4) * 32 + (tid & 1) * 16 + (tid & 14);
        const float cq = FL(lds16(ca) << 16) * m, ck = FL(lds16(ca + 256) << 16) * m, cv = FL(lds16(ca + 512) << 16) * m;
        const float4 z = poll_sum4(&P.g->patch[bp * 8 + (tid >> 6) * 4][tid & 63], 64, tag + 1);
        float q = z.x + cq, k = z.y + ck, v = z.z + cv;
        q += __shfl_xor_sync(0xffffffffu, q, 1); k += __shfl_xor_sync(0xffffffffu, k, 1); v += __shfl_xor_sync(0xffffffffu, v, 1);
        const uint32_t d = sb + PATCH + (tid & ~1), kv = pack_bf16(k * rs, v * rs);
        sts16(d, pack_bf16(q * (rs * QSCALE), 0.f)); sts16(d + 128, kv); sts16(d + 256, kv >> 16);
      }
    }
  }
  if (bid == 0 && tid == 0) P.g->epoch = lds32(sb + INFO2 + 16) + 1;
  #undef blk
  #undef bid
  #undef fid
  #undef bi
  #undef bp
  #undef bc
  #undef FRESH
  #undef lane
  #undef wq
}

__global__ void __cluster_dims__(2, 1, 1) __launch_bounds__(512, 1) fused_kernel(const __grid_constant__ Params P) {
  extern __shared__ __align__(1024) uint8_t smem_raw[];
  const uint32_t sb = smem_u32(smem_raw);
  PROFT(threadIdx.x == 0, 0);
  if (threadIdx.x < 32) { if (elect()) {
    for (int s = 0; s < 3; s++) mbar_init(BAR(B_FULLQ + s), 1);
    asm volatile("fence.mbarrier_init.release.cluster;" ::: "memory");
    #pragma unroll 1
    for (int s = 0; s < 3; s++) {
      mbar_expect_tx(BAR(B_FULLQ + s), 57344);
      tma_2d(sb + qa_off(s), &P.mX, s * 64, (BID >> 4) * 256, BAR(B_FULLQ + s));
      tma_3d(sb + qb_off(s), &P.mWq, (BID & 15) * 64, s * 64, 0, BAR(B_FULLQ + s));
    }
    if ((sb & 0x3FFFFu) != 1024) __trap();
  } } else if (threadIdx.x == 480) {
    asm volatile("prefetch.tensormap [%0];" :: "l"(&P.mWq) : "memory");
  } else if (threadIdx.x >= 32 && !(threadIdx.x & 28) && (threadIdx.x >> 3) + (threadIdx.x & 3) <= B_COUNT + 2) {
    int b = (threadIdx.x >> 3) + (threadIdx.x & 3) - 1;
    if (b >= B_COUNT) b += B_ROW - B_COUNT;
    const uint32_t cnt = b < B_XFREE ? (b == B_OFREE ? 1 : 2) : (b < B_KVRDY ? 3 : (b < B_KVFULL || b == B_PAR ? 4 : (b == B_PFREE ? 2 : 1)));
    mbar_init(BAR(b), cnt);
    asm volatile("fence.mbarrier_init.release.cluster;" ::: "memory");
  }
  __syncthreads();
  asm volatile("barrier.cluster.arrive.relaxed.aligned;" ::: "memory");
  const int wg = __shfl_sync(0xffffffffu, threadIdx.x >> 7, 0);
  if (wg < 2) { reg_inc<224>(); consumer(P, sb, wg); }
  else if (wg == 2) { reg_dec<40>(); aux(P, sb); }
  else {
    reg_dec<24>();
    asm volatile("barrier.cluster.wait.aligned;" ::: "memory");
    const int w = __shfl_sync(0xffffffffu, (threadIdx.x >> 5) & 3, 0);
    if (w == 0) loader(P, sb);
    else if (w < 3) storer(P, sb, w - 1);
    else if (elect()) stager(P, sb);
  }
}

typedef CUresult (*EncFn)(CUtensorMap*, CUtensorMapDataType, cuuint32_t, void*, const cuuint64_t*, const cuuint64_t*, const cuuint32_t*, const cuuint32_t*,
                          CUtensorMapInterleave, CUtensorMapSwizzle, CUtensorMapL2promotion, CUtensorMapFloatOOBfill);
static void mk_map(EncFn enc, CUtensorMap* m, const void* ptr, int rank, const cuuint64_t* dims, const cuuint64_t* strides, const cuuint32_t* box,
                   CUtensorMapSwizzle sw, CUtensorMapL2promotion pr) {
  cuuint32_t es[5] = {1, 1, 1, 1, 1};
  enc(m, CU_TENSOR_MAP_DATA_TYPE_BFLOAT16, rank, (void*)ptr, dims, strides, box, es, CU_TENSOR_MAP_INTERLEAVE_NONE, sw, pr, CU_TENSOR_MAP_FLOAT_OOB_FILL_NONE);
}
extern "C" void kernel_launch(void* const* d_in, const int* in_sizes, int n_in, void* d_out, int out_size) {
  (void)in_sizes; (void)n_in; (void)out_size;
  void* fn = nullptr; cudaDriverEntryPointQueryResult q;
  cudaGetDriverEntryPoint("cuTensorMapEncodeTiled", &fn, cudaEnableDefault, &q);
  EncFn enc = (EncFn)fn;
  cudaFuncSetAttribute(fused_kernel, cudaFuncAttributeMaxDynamicSharedMemorySize, SMEM_BYTES);
  Params P;
  const CUtensorMapSwizzle S128 = CU_TENSOR_MAP_SWIZZLE_128B, S64 = CU_TENSOR_MAP_SWIZZLE_64B, S0 = CU_TENSOR_MAP_SWIZZLE_NONE;
  const CUtensorMapL2promotion L256 = CU_TENSOR_MAP_L2_PROMOTION_L2_256B, L128 = CU_TENSOR_MAP_L2_PROMOTION_L2_128B;
  { cuuint64_t d[2] = {1024, 2048}, s[1] = {2048}; cuuint32_t b[2] = {64, 256}, bh[2] = {64, 128};
    mk_map(enc, &P.mX, d_in[0], 2, d, s, b, S128, L256); mk_map(enc, &P.mXh, d_in[0], 2, d, s, bh, S128, L256); }
  { cuuint64_t d[3] = {1024, 1024, 3}, s[2] = {6144, 2048}; cuuint32_t b[3] = {64, 64, 3}; mk_map(enc, &P.mWq, d_in[1], 3, d, s, b, S128, L256); }
  { cuuint64_t d[5] = {64, 32, 2, 16, 16}, s[4] = {2048, 65536, 131072, 128}; cuuint32_t b[5] = {64, 32, 1, 2, 2}; mk_map(enc, &P.mWo, d_in[2], 5, d, s, b, S128, L256); }
  { cuuint64_t d[2] = {3584, 1024}, s[1] = {7168}; cuuint32_t b[2] = {32, 128};
    mk_map(enc, &P.mWg, d_in[5], 2, d, s, b, S64, L128); mk_map(enc, &P.mWu, d_in[6], 2, d, s, b, S64, L128); }
  { cuuint64_t d[2] = {3072, 1024}, s[1] = {6144}; cuuint32_t b[2] = {32, 256}; mk_map(enc, &P.mWp, d_in[1], 2, d, s, b, S64, L128); }
  { cuuint64_t d[3] = {256, 3584, 4}, s[2] = {2048, 512}; cuuint32_t b[3] = {256, 8, 4}; mk_map(enc, &P.mWd, d_in[7], 3, d, s, b, S0, L128); }
  P.x0 = (const bf16*)d_in[0]; P.wqkv = (const bf16*)d_in[1]; P.wo = (const bf16*)d_in[2]; P.wr = (const bf16*)d_in[4]; P.wg = (const bf16*)d_in[5]; P.wu = (const bf16*)d_in[6]; P.wd = (const bf16*)d_in[7];
  P.out = (bf16*)d_out;
  cudaGetSymbolAddress((void**)&P.g, g_scr);
  for (int b = 0; b < 128; b++) {
    int j = b >> 1, quad = j < 4 ? 0 : (j < 36 ? 1 + (j - 4) % 8 : 9 + (j - 36) % 7), pos = j < 4 ? j : (j < 36 ? (j - 4) / 8 : (j - 36) / 7);
    int bid = ((quad >> 2) * 2 + (pos >> 1)) * 16 + ((quad & 3) * 2 + (pos & 1)) * 2 + (b & 1);
    int e = pos * 2 + (b & 1), fid = e < 7 ? quad * 7 + e : 112 + quad;
    P.map[b] = bid | fid << 8;
  }
  fused_kernel<<<128, 512, SMEM_BYTES>>>(P);
}
```

```cpp
#include <cuda_runtime.h>
#include <cuda_bf16.h>
#include <cuda.h>
#include <stdint.h>
#include <stddef.h>
typedef __nv_bfloat16 bf16;

template<int TB, int TA = 0> __device__ __forceinline__ void wgmma_ss_n192(float (&d)[96], uint64_t da, uint64_t db, int scale_d) {
  asm volatile("{\n.reg .pred p;\nsetp.ne.b32 p, %98, 0;\n"
    "wgmma.mma_async.sync.aligned.m64n192k16.f32.bf16.bf16 {%0, %1, %2, %3, %4, %5, %6, %7, %8, %9, %10, %11, %12, %13, %14, %15, %16, %17, %18, %19, %20, %21, %22, %23, %24, %25, %26, %27, %28, %29, %30, %31, %32, %33, %34, %35, %36, %37, %38, %39, %40, %41, %42, %43, %44, %45, %46, %47, %48, %49, %50, %51, %52, %53, %54, %55, %56, %57, %58, %59, %60, %61, %62, %63, %64, %65, %66, %67, %68, %69, %70, %71, %72, %73, %74, %75, %76, %77, %78, %79, %80, %81, %82, %83, %84, %85, %86, %87, %88, %89, %90, %91, %92, %93, %94, %95}, %96, %97, p, 1, 1, %100, %99;\n}\n"
    : "+f"(d[0]), "+f"(d[1]), "+f"(d[2]), "+f"(d[3]), "+f"(d[4]), "+f"(d[5]), "+f"(d[6]), "+f"(d[7]), "+f"(d[8]), "+f"(d[9]), "+f"(d[10]), "+f"(d[11]), "+f"(d[12]), "+f"(d[13]), "+f"(d[14]), "+f"(d[15]), "+f"(d[16]), "+f"(d[17]), "+f"(d[18]), "+f"(d[19]), "+f"(d[20]), "+f"(d[21]), "+f"(d[22]), "+f"(d[23]), "+f"(d[24]), "+f"(d[25]), "+f"(d[26]), "+f"(d[27]), "+f"(d[28]), "+f"(d[29]), "+f"(d[30]), "+f"(d[31]), "+f"(d[32]), "+f"(d[33]), "+f"(d[34]), "+f"(d[35]), "+f"(d[36]), "+f"(d[37]), "+f"(d[38]), "+f"(d[39]), "+f"(d[40]), "+f"(d[41]), "+f"(d[42]), "+f"(d[43]), "+f"(d[44]), "+f"(d[45]), "+f"(d[46]), "+f"(d[47]), "+f"(d[48]), "+f"(d[49]), "+f"(d[50]), "+f"(d[51]), "+f"(d[52]), "+f"(d[53]), "+f"(d[54]), "+f"(d[55]), "+f"(d[56]), "+f"(d[57]), "+f"(d[58]), "+f"(d[59]), "+f"(d[60]), "+f"(d[61]), "+f"(d[62]), "+f"(d[63]), "+f"(d[64]), "+f"(d[65]), "+f"(d[66]), "+f"(d[67]), "+f"(d[68]), "+f"(d[69]), "+f"(d[70]), "+f"(d[71]), "+f"(d[72]), "+f"(d[73]), "+f"(d[74]), "+f"(d[75]), "+f"(d[76]), "+f"(d[77]), "+f"(d[78]), "+f"(d[79]), "+f"(d[80]), "+f"(d[81]), "+f"(d[82]), "+f"(d[83]), "+f"(d[84]), "+f"(d[85]), "+f"(d[86]), "+f"(d[87]), "+f"(d[88]), "+f"(d[89]), "+f"(d[90]), "+f"(d[91]), "+f"(d[92]), "+f"(d[93]), "+f"(d[94]), "+f"(d[95])
    : "l"(da), "l"(db), "r"(scale_d), "n"(TB), "n"(TA));
}

template<int TB> __device__ __forceinline__ void wgmma_rs_n192(float (&d)[96], uint32_t a0, uint32_t a1, uint32_t a2, uint32_t a3, uint64_t db, int scale_d) {
  asm volatile("{\n.reg .pred p;\nsetp.ne.b32 p, %101, 0;\n"
    "wgmma.mma_async.sync.aligned.m64n192k16.f32.bf16.bf16 {%0, %1, %2, %3, %4, %5, %6, %7, %8, %9, %10, %11, %12, %13, %14, %15, %16, %17, %18, %19, %20, %21, %22, %23, %24, %25, %26, %27, %28, %29, %30, %31, %32, %33, %34, %35, %36, %37, %38, %39, %40, %41, %42, %43, %44, %45, %46, %47, %48, %49, %50, %51, %52, %53, %54, %55, %56, %57, %58, %59, %60, %61, %62, %63, %64, %65, %66, %67, %68, %69, %70, %71, %72, %73, %74, %75, %76, %77, %78, %79, %80, %81, %82, %83, %84, %85, %86, %87, %88, %89, %90, %91, %92, %93, %94, %95}, {%96, %97, %98, %99}, %100, p, 1, 1, %102;\n}\n"
    : "+f"(d[0]), "+f"(d[1]), "+f"(d[2]), "+f"(d[3]), "+f"(d[4]), "+f"(d[5]), "+f"(d[6]), "+f"(d[7]), "+f"(d[8]), "+f"(d[9]), "+f"(d[10]), "+f"(d[11]), "+f"(d[12]), "+f"(d[13]), "+f"(d[14]), "+f"(d[15]), "+f"(d[16]), "+f"(d[17]), "+f"(d[18]), "+f"(d[19]), "+f"(d[20]), "+f"(d[21]), "+f"(d[22]), "+f"(d[23]), "+f"(d[24]), "+f"(d[25]), "+f"(d[26]), "+f"(d[27]), "+f"(d[28]), "+f"(d[29]), "+f"(d[30]), "+f"(d[31]), "+f"(d[32]), "+f"(d[33]), "+f"(d[34]), "+f"(d[35]), "+f"(d[36]), "+f"(d[37]), "+f"(d[38]), "+f"(d[39]), "+f"(d[40]), "+f"(d[41]), "+f"(d[42]), "+f"(d[43]), "+f"(d[44]), "+f"(d[45]), "+f"(d[46]), "+f"(d[47]), "+f"(d[48]), "+f"(d[49]), "+f"(d[50]), "+f"(d[51]), "+f"(d[52]), "+f"(d[53]), "+f"(d[54]), "+f"(d[55]), "+f"(d[56]), "+f"(d[57]), "+f"(d[58]), "+f"(d[59]), "+f"(d[60]), "+f"(d[61]), "+f"(d[62]), "+f"(d[63]), "+f"(d[64]), "+f"(d[65]), "+f"(d[66]), "+f"(d[67]), "+f"(d[68]), "+f"(d[69]), "+f"(d[70]), "+f"(d[71]), "+f"(d[72]), "+f"(d[73]), "+f"(d[74]), "+f"(d[75]), "+f"(d[76]), "+f"(d[77]), "+f"(d[78]), "+f"(d[79]), "+f"(d[80]), "+f"(d[81]), "+f"(d[82]), "+f"(d[83]), "+f"(d[84]), "+f"(d[85]), "+f"(d[86]), "+f"(d[87]), "+f"(d[88]), "+f"(d[89]), "+f"(d[90]), "+f"(d[91]), "+f"(d[92]), "+f"(d[93]), "+f"(d[94]), "+f"(d[95])
    : "r"(a0), "r"(a1), "r"(a2), "r"(a3), "l"(db), "r"(scale_d), "n"(TB));
}

template<int TB, int TA = 0> __device__ __forceinline__ void wgmma_ss_n128(float (&d)[64], uint64_t da, uint64_t db, int scale_d) {
  asm volatile("{\n.reg .pred p;\nsetp.ne.b32 p, %66, 0;\n"
    "wgmma.mma_async.sync.aligned.m64n128k16.f32.bf16.bf16 {%0, %1, %2, %3, %4, %5, %6, %7, %8, %9, %10, %11, %12, %13, %14, %15, %16, %17, %18, %19, %20, %21, %22, %23, %24, %25, %26, %27, %28, %29, %30, %31, %32, %33, %34, %35, %36, %37, %38, %39, %40, %41, %42, %43, %44, %45, %46, %47, %48, %49, %50, %51, %52, %53, %54, %55, %56, %57, %58, %59, %60, %61, %62, %63}, %64, %65, p, 1, 1, %68, %67;\n}\n"
    : "+f"(d[0]), "+f"(d[1]), "+f"(d[2]), "+f"(d[3]), "+f"(d[4]), "+f"(d[5]), "+f"(d[6]), "+f"(d[7]), "+f"(d[8]), "+f"(d[9]), "+f"(d[10]), "+f"(d[11]), "+f"(d[12]), "+f"(d[13]), "+f"(d[14]), "+f"(d[15]), "+f"(d[16]), "+f"(d[17]), "+f"(d[18]), "+f"(d[19]), "+f"(d[20]), "+f"(d[21]), "+f"(d[22]), "+f"(d[23]), "+f"(d[24]), "+f"(d[25]), "+f"(d[26]), "+f"(d[27]), "+f"(d[28]), "+f"(d[29]), "+f"(d[30]), "+f"(d[31]), "+f"(d[32]), "+f"(d[33]), "+f"(d[34]), "+f"(d[35]), "+f"(d[36]), "+f"(d[37]), "+f"(d[38]), "+f"(d[39]), "+f"(d[40]), "+f"(d[41]), "+f"(d[42]), "+f"(d[43]), "+f"(d[44]), "+f"(d[45]), "+f"(d[46]), "+f"(d[47]), "+f"(d[48]), "+f"(d[49]), "+f"(d[50]), "+f"(d[51]), "+f"(d[52]), "+f"(d[53]), "+f"(d[54]), "+f"(d[55]), "+f"(d[56]), "+f"(d[57]), "+f"(d[58]), "+f"(d[59]), "+f"(d[60]), "+f"(d[61]), "+f"(d[62]), "+f"(d[63])
    : "l"(da), "l"(db), "r"(scale_d), "n"(TB), "n"(TA));
}

template<int TB, int TA = 0> __device__ __forceinline__ void wgmma_ss_n64(float (&d)[32], uint64_t da, uint64_t db, int scale_d) {
  asm volatile("{\n.reg .pred p;\nsetp.ne.b32 p, %34, 0;\n"
    "wgmma.mma_async.sync.aligned.m64n64k16.f32.bf16.bf16 {%0, %1, %2, %3, %4, %5, %6, %7, %8, %9, %10, %11, %12, %13, %14, %15, %16, %17, %18, %19, %20, %21, %22, %23, %24, %25, %26, %27, %28, %29, %30, %31}, %32, %33, p, 1, 1, %36, %35;\n}\n"
    : "+f"(d[0]), "+f"(d[1]), "+f"(d[2]), "+f"(d[3]), "+f"(d[4]), "+f"(d[5]), "+f"(d[6]), "+f"(d[7]), "+f"(d[8]), "+f"(d[9]), "+f"(d[10]), "+f"(d[11]), "+f"(d[12]), "+f"(d[13]), "+f"(d[14]), "+f"(d[15]), "+f"(d[16]), "+f"(d[17]), "+f"(d[18]), "+f"(d[19]), "+f"(d[20]), "+f"(d[21]), "+f"(d[22]), "+f"(d[23]), "+f"(d[24]), "+f"(d[25]), "+f"(d[26]), "+f"(d[27]), "+f"(d[28]), "+f"(d[29]), "+f"(d[30]), "+f"(d[31])
    : "l"(da), "l"(db), "r"(scale_d), "n"(TB), "n"(TA));
}

template<int TB, int TA = 0> __device__ __forceinline__ void wgmma_ss_n8(float (&d)[4], uint64_t da, uint64_t db, int scale_d) {
  asm volatile("{\n.reg .pred p;\nsetp.ne.b32 p, %6, 0;\n"
    "wgmma.mma_async.sync.aligned.m64n8k16.f32.bf16.bf16 {%0, %1, %2, %3}, %4, %5, p, 1, 1, %8, %7;\n}\n"
    : "+f"(d[0]), "+f"(d[1]), "+f"(d[2]), "+f"(d[3])
    : "l"(da), "l"(db), "r"(scale_d), "n"(TB), "n"(TA));
}

template<int TB> __device__ __forceinline__ void wgmma_rs_n40(float (&d)[20], uint32_t a0, uint32_t a1, uint32_t a2, uint32_t a3, uint64_t db, int scale_d) {
  asm volatile("{\n.reg .pred p;\nsetp.ne.b32 p, %25, 0;\n"
    "wgmma.mma_async.sync.aligned.m64n40k16.f32.bf16.bf16 {%0, %1, %2, %3, %4, %5, %6, %7, %8, %9, %10, %11, %12, %13, %14, %15, %16, %17, %18, %19}, {%20, %21, %22, %23}, %24, p, 1, 1, %26;\n}\n"
    : "+f"(d[0]), "+f"(d[1]), "+f"(d[2]), "+f"(d[3]), "+f"(d[4]), "+f"(d[5]), "+f"(d[6]), "+f"(d[7]), "+f"(d[8]), "+f"(d[9]), "+f"(d[10]), "+f"(d[11]), "+f"(d[12]), "+f"(d[13]), "+f"(d[14]), "+f"(d[15]), "+f"(d[16]), "+f"(d[17]), "+f"(d[18]), "+f"(d[19])
    : "r"(a0), "r"(a1), "r"(a2), "r"(a3), "l"(db), "r"(scale_d), "n"(TB));
}

#define DEVI __device__ __forceinline__
DEVI uint32_t smem_u32(const void* p) { return (uint32_t)__cvta_generic_to_shared(p); }
DEVI void mbar_init(uint32_t bar, uint32_t cnt) { asm volatile("mbarrier.init.shared::cta.b64 [%0], %1;" :: "r"(bar), "r"(cnt)); }
DEVI void mbar_expect_tx(uint32_t bar, uint32_t bytes) { asm volatile("mbarrier.arrive.expect_tx.shared::cta.b64 _, [%0], %1;" :: "r"(bar), "r"(bytes) : "memory"); }
DEVI void mbar_arrive(uint32_t bar) { asm volatile("mbarrier.arrive.shared::cta.b64 _, [%0];" :: "r"(bar) : "memory"); }
DEVI void mbar_arrive_peer(uint32_t bar) {
  asm volatile("{\n.reg .b32 ra;\nmapa.shared::cluster.u32 ra, %0, %1;\nmbarrier.arrive.shared::cluster.b64 _, [ra];\n}" :: "r"(bar), "r"((blockIdx.x & 1) ^ 1) : "memory");
}
DEVI void bulk_s2peer(uint32_t a, uint32_t bytes, uint32_t bar) {
  asm volatile("{\n.reg .b32 ra, rb;\nmapa.shared::cluster.u32 ra, %0, %3;\nmapa.shared::cluster.u32 rb, %2, %3;\n"
               "cp.async.bulk.shared::cluster.shared::cta.mbarrier::complete_tx::bytes [ra], [%0], %1, [rb];\n}"
               :: "r"(a), "r"(bytes), "r"(bar), "r"((blockIdx.x & 1) ^ 1) : "memory");
}
DEVI void mbar_wait(uint32_t bar, uint32_t parity) {
  asm volatile("{\n.reg .pred p;\nLW:\nmbarrier.try_wait.parity.shared::cta.b64 p, [%0], %1;\n@!p bra LW;\n}" :: "r"(bar), "r"(parity) : "memory");
}
DEVI uint32_t mbar_test(uint32_t bar, uint32_t parity) {
  uint32_t r; asm volatile("{\n.reg .pred p;\nmbarrier.test_wait.parity.shared::cta.b64 p, [%1], %2;\nselp.u32 %0, 1, 0, p;\n}" : "=r"(r) : "r"(bar), "r"(parity) : "memory"); return r;
}
DEVI void mbar_wait_b(uint32_t bar, uint32_t parity) {
  asm volatile("{\n.reg .pred p;\n.reg .u32 it;\nmov.u32 it, 0;\nLW:\nmbarrier.try_wait.parity.shared::cta.b64 p, [%0], %1;\n@p bra LD;\n"
               "add.u32 it, it, 1;\nsetp.lt.u32 p, it, 0x1000000;\n@p bra LW;\ntrap;\nLD:\n}" :: "r"(bar), "r"(parity) : "memory");
}
DEVI void tma_2d(uint32_t dst, const CUtensorMap* m, int c0, int c1, uint32_t bar) {
  asm volatile("cp.async.bulk.tensor.2d.shared::cluster.global.mbarrier::complete_tx::bytes [%0], [%1, {%3, %4}], [%2];"
    :: "r"(dst), "l"(m), "r"(bar), "r"(c0), "r"(c1) : "memory");
}
DEVI void tma_3d(uint32_t dst, const CUtensorMap* m, int c0, int c1, int c2, uint32_t bar) {
  asm volatile("cp.async.bulk.tensor.3d.shared::cluster.global.mbarrier::complete_tx::bytes [%0], [%1, {%3, %4, %5}], [%2];"
    :: "r"(dst), "l"(m), "r"(bar), "r"(c0), "r"(c1), "r"(c2) : "memory");
}
#define POL_EF POL_FIRST
constexpr uint64_t POL_FIRST = 0x12F0000000000000ull, POL_NORMAL = 0x1000000000000000ull;
DEVI void tma_2d_h(uint32_t dst, const CUtensorMap* m, int c0, int c1, uint32_t bar, uint64_t pol) {
  asm volatile("cp.async.bulk.tensor.2d.shared::cluster.global.mbarrier::complete_tx::bytes.L2::cache_hint [%0], [%1, {%3, %4}], [%2], %5;"
    :: "r"(dst), "l"(m), "r"(bar), "r"(c0), "r"(c1), "l"(pol) : "memory");
}
DEVI void tma_3d_h(uint32_t dst, const CUtensorMap* m, int c0, int c1, int c2, uint32_t bar, uint64_t pol) {
  asm volatile("cp.async.bulk.tensor.3d.shared::cluster.global.mbarrier::complete_tx::bytes.L2::cache_hint [%0], [%1, {%3, %4, %5}], [%2], %6;"
    :: "r"(dst), "l"(m), "r"(bar), "r"(c0), "r"(c1), "r"(c2), "l"(pol) : "memory");
}
DEVI void bulk_g2s_h(uint32_t s, const void* g, uint32_t bytes, uint32_t bar, uint64_t pol = POL_EF) {
  asm volatile("cp.async.bulk.shared::cluster.global.mbarrier::complete_tx::bytes.L2::cache_hint [%0], [%1], %2, [%3], %4;"
    :: "r"(s), "l"(g), "r"(bytes), "r"(bar), "l"(pol) : "memory");
}
DEVI void tma_5d(uint32_t dst, const CUtensorMap* m, int c0, int c1, int c2, int c3, int c4, uint32_t bar, uint64_t pol) {
  asm volatile("cp.async.bulk.tensor.5d.shared::cluster.global.mbarrier::complete_tx::bytes.L2::cache_hint [%0], [%1, {%3, %4, %5, %6, %7}], [%2], %8;"
    :: "r"(dst), "l"(m), "r"(bar), "r"(c0), "r"(c1), "r"(c2), "r"(c3), "r"(c4), "l"(pol) : "memory");
}
DEVI void tma_prefetch_2d(const CUtensorMap* m, int c0, int c1) {
  asm volatile("cp.async.bulk.prefetch.tensor.2d.L2.global.tile [%0, {%1, %2}];" :: "l"(m), "r"(c0), "r"(c1) : "memory");
}
DEVI void tma_prefetch_3d(const CUtensorMap* m, int c0, int c1, int c2) {
  asm volatile("cp.async.bulk.prefetch.tensor.3d.L2.global.tile [%0, {%1, %2, %3}];" :: "l"(m), "r"(c0), "r"(c1), "r"(c2) : "memory");
}
DEVI void bulk_prefetch(const void* g, uint32_t bytes) { asm volatile("cp.async.bulk.prefetch.L2.global [%0], %1;" :: "l"(g), "r"(bytes) : "memory"); }
DEVI void bulk_g2s(uint32_t s, const void* g, uint32_t bytes, uint32_t bar) {
  asm volatile("cp.async.bulk.shared::cluster.global.mbarrier::complete_tx::bytes [%0], [%1], %2, [%3];" :: "r"(s), "l"(g), "r"(bytes), "r"(bar) : "memory");
}
DEVI void bulk_s2g(void* g, uint32_t s, uint32_t bytes, uint64_t pol = POL_NORMAL) {
  asm volatile("cp.async.bulk.global.shared::cta.bulk_group.L2::cache_hint [%0], [%1], %2, %3;\ncp.async.bulk.commit_group;" :: "l"(g), "r"(s), "r"(bytes), "l"(pol) : "memory");
}
template<int N> DEVI void bulk_wait() { asm volatile("cp.async.bulk.wait_group %0;" :: "n"(N) : "memory"); }
DEVI void fence_async_smem() { asm volatile("fence.proxy.async.shared::cta;" ::: "memory"); }
DEVI void fence_async_glob() { asm volatile("fence.proxy.async.global;" ::: "memory"); }
DEVI unsigned ld_rlx(const unsigned* p) { unsigned v; asm volatile("ld.relaxed.gpu.global.u32 %0, [%1];" : "=r"(v) : "l"(p) : "memory"); return v; }
DEVI void st_rlx(unsigned* p, unsigned v) { asm volatile("st.relaxed.gpu.global.u32 [%0], %1;" :: "l"(p), "r"(v) : "memory"); }
DEVI uint2 ldg_stream(const uint2* p) { uint2 v; asm volatile("ld.global.nc.L1::no_allocate.v2.u32 {%0, %1}, [%2];" : "=r"(v.x), "=r"(v.y) : "l"(p)); return v; }
DEVI void fence_rel() { asm volatile("fence.release.gpu;" ::: "memory"); }
DEVI uint4 ld_ll(const uint4* p) {
  uint4 v;
  asm volatile("{\n.reg .b128 t;\n.reg .b64 a, b;\nld.relaxed.gpu.global.b128 t, [%4];\nmov.b128 {a, b}, t;\nmov.b64 {%0, %1}, a;\nmov.b64 {%2, %3}, b;\n}"
               : "=r"(v.x), "=r"(v.y), "=r"(v.z), "=r"(v.w) : "l"(p) : "memory");
  return v;
}
DEVI void st_ll(uint4* p, uint32_t x, uint32_t y, uint32_t z, uint32_t w) {
  asm volatile("{\n.reg .b128 t;\n.reg .b64 a, b;\nmov.b64 a, {%1, %2};\nmov.b64 b, {%3, %4};\nmov.b128 t, {a, b};\nst.relaxed.gpu.global.b128 [%0], t;\n}"
               :: "l"(p), "r"(x), "r"(y), "r"(z), "r"(w) : "memory");
}
#define SPIN_MAX 0x1000000
#define SD_T 400
DEVI uint4 poll_ll(const uint4* p, uint32_t mask, uint32_t tag) {
  uint4 v; int it = 0;
  do { v = ld_ll(p); if (++it > SPIN_MAX) __trap(); } while (!__all_sync(0xffffffffu, (v.w & mask) == tag));
  return v;
}
DEVI void poll_ll2(const uint4* p, const uint4* q, uint32_t mask, uint32_t tag, uint4& a, uint4& b) {
  int it = 0;
  do { a = ld_ll(p); b = ld_ll(q); if (++it > SPIN_MAX) __trap(); } while (!__all_sync(0xffffffffu, (a.w & mask) == tag && (b.w & mask) == tag));
}
DEVI float4 poll_sum4(const uint4* src, int stride, uint32_t tag) {
  uint4 v0, v1, v2, v3; int it = 0;
  do { v0 = ld_ll(src); v1 = ld_ll(src + stride); v2 = ld_ll(src + 2 * stride); v3 = ld_ll(src + 3 * stride); if (++it > SPIN_MAX) __trap(); }
  while (!__all_sync(0xffffffffu, v0.w == tag && v1.w == tag && v2.w == tag && v3.w == tag));
  #define S4(f) ((__uint_as_float(v0.f) + __uint_as_float(v1.f)) + (__uint_as_float(v2.f) + __uint_as_float(v3.f)))
  return make_float4(S4(x), S4(y), S4(z), 0.f);
  #undef S4
}
DEVI void bar_sync(int id, int n) { asm volatile("bar.sync %0, %1;" :: "r"(id), "r"(n) : "memory"); }
DEVI void bar_arrive(int id, int n) { asm volatile("bar.arrive %0, %1;" :: "r"(id), "r"(n) : "memory"); }
DEVI void wg_fence() { asm volatile("wgmma.fence.sync.aligned;" ::: "memory"); }
DEVI void wg_commit() { asm volatile("wgmma.commit_group.sync.aligned;" ::: "memory"); }
template<int N> DEVI void wg_wait() { asm volatile("wgmma.wait_group.sync.aligned %0;" :: "n"(N) : "memory"); }
template<int N> DEVI void reg_inc() { asm volatile("setmaxnreg.inc.sync.aligned.u32 %0;" :: "n"(N)); }
template<int N> DEVI void reg_dec() { asm volatile("setmaxnreg.dec.sync.aligned.u32 %0;" :: "n"(N)); }
DEVI float ex2f(float x) { float y; asm("ex2.approx.ftz.f32 %0, %1;" : "=f"(y) : "f"(x)); return y; }
DEVI uint32_t pack_bf16(float lo, float hi) { uint32_t r; asm("cvt.rn.bf16x2.f32 %0, %1, %2;" : "=r"(r) : "f"(hi), "f"(lo)); return r; }
DEVI float bf_lo(uint32_t v) { return __uint_as_float(v << 16); }
DEVI float bf_hi(uint32_t v) { return __uint_as_float(v & 0xffff0000u); }
DEVI float bf_round(float x) { return bf_lo(pack_bf16(x, 0.f)); }
DEVI void stsm_x4(uint32_t addr, uint32_t a, uint32_t b, uint32_t c, uint32_t d) {
  asm volatile("stmatrix.sync.aligned.m8n8.x4.shared.b16 [%0], {%1,%2,%3,%4};" :: "r"(addr), "r"(a), "r"(b), "r"(c), "r"(d) : "memory");
}
DEVI void ldsm_x4(uint32_t addr, uint32_t& a, uint32_t& b, uint32_t& c, uint32_t& d) {
  asm volatile("ldmatrix.sync.aligned.m8n8.x4.shared.b16 {%0,%1,%2,%3}, [%4];" : "=r"(a), "=r"(b), "=r"(c), "=r"(d) : "r"(addr) : "memory");
}
DEVI uint4 lds128(uint32_t a) { uint4 v; asm volatile("ld.shared.v4.u32 {%0,%1,%2,%3}, [%4];" : "=r"(v.x), "=r"(v.y), "=r"(v.z), "=r"(v.w) : "r"(a) : "memory"); return v; }
DEVI void sts128(uint32_t a, uint4 v) { asm volatile("st.shared.v4.u32 [%0], {%1,%2,%3,%4};" :: "r"(a), "r"(v.x), "r"(v.y), "r"(v.z), "r"(v.w) : "memory"); }
DEVI float2 lds64f(uint32_t a) { float2 v; asm volatile("ld.shared.v2.f32 {%0,%1}, [%2];" : "=f"(v.x), "=f"(v.y) : "r"(a) : "memory"); return v; }
DEVI void sts64f(uint32_t a, float x, float y) { asm volatile("st.shared.v2.f32 [%0], {%1,%2};" :: "r"(a), "f"(x), "f"(y) : "memory"); }
DEVI uint32_t lds32(uint32_t a) { uint32_t v; asm volatile("ld.shared.u32 %0, [%1];" : "=r"(v) : "r"(a) : "memory"); return v; }
DEVI uint32_t lds16(uint32_t a) { unsigned short v; asm volatile("ld.shared.u16 %0, [%1];" : "=h"(v) : "r"(a) : "memory"); return v; }
DEVI float lds32f(uint32_t a) { return __uint_as_float(lds32(a)); }
DEVI void sts32(uint32_t a, uint32_t v) { asm volatile("st.shared.u32 [%0], %1;" :: "r"(a), "r"(v) : "memory"); }
DEVI void sts32f(uint32_t a, float v) { sts32(a, __float_as_uint(v)); }
DEVI void sts16(uint32_t a, uint32_t v) { asm volatile("st.shared.u16 [%0], %1;" :: "r"(a), "h"((unsigned short)v) : "memory"); }
template<int N> DEVI void keep(float (&d)[N]) {
  #pragma unroll
  for (int i = 0; i < N; i++) asm volatile("" : "+f"(d[i]) :: "memory");
}
template<int N> DEVI void keep(uint32_t (&d)[N]) {
  #pragma unroll
  for (int i = 0; i < N; i++) asm volatile("" : "+r"(d[i]) :: "memory");
}
template<uint32_t HI> DEVI uint64_t mkd(uint32_t lo) { uint64_t r; asm("mov.b64 %0, {%1, %2};" : "=l"(r) : "r"(lo), "n"(HI)); return r; }
constexpr uint32_t HI128 = (1u << 30) | (1024 >> 4), HI64 = (2u << 30) | (512 >> 4);
#define VOFF(x) ((uint32_t)(x) * (uint32_t)(1 - 65536))
DEVI bool elect() { uint32_t p; asm volatile("{\n.reg .pred q;\nelect.sync _|q, 0xffffffff;\nselp.u32 %0, 1, 0, q;\n}" : "=r"(p)); return p; }
DEVI void warp_signal(uint32_t bar) { __syncwarp(); if (elect()) mbar_arrive(bar); }

#define BCP 16
#define XCP 4
struct Scratch {
  uint4 statP[8][2048];
  uint4 statF[2048];
  uint4 csP[16][8][96];
  uint4 best[8][BCP][16];
  uint4 row[16][256];
  uint4 yP[128][112][2];
  uint4 x2[XCP][256];
  uint4 patch[128][64];
  unsigned flagKV[128][32];
  unsigned flagO[8][32];
  unsigned flagX[8][32];
  unsigned epoch, pad[255];
  uint4 kv[128][4][1024];
  uint4 o[8][2][8][2][1024];
  uint4 x[8][16][2048];
  uint4 zero[1024];
};
static_assert(offsetof(Scratch, kv) % 1024 == 0, "");
__device__ __align__(1024) Scratch g_scr;
#define PROFT(cond, slot)
#define PROFW(cond, slot)
#define PROFD(cond, slot)
#define PROFX(cond, slot)
#define PROFY(cond, slot)

constexpr uint32_t SB0 = 65536, HOLE = 90112, SA2 = 98304, SB1 = 131072, SB2 = 155648, STG = 180224;
constexpr uint32_t KVA = 0, KVB = 98304, QO = 65536;
constexpr uint32_t MISC = 229376, CS = MISC, ONES = MISC + 768, BARS = MISC + 1792, INFO = MISC + 2208, WR = MISC + 2224, X2SEG = MISC + 2736, INFO2 = MISC + 2992, DUMP = MISC + 3040;
constexpr uint32_t PAR = HOLE, HV = HOLE + 2048, RED = HOLE + 6144, PATCH = 196608;
constexpr uint32_t SMEM_BYTES = 232448;
enum { B_FULLQ = 0, B_EMPTYQ = 3, B_FULLW = 6, B_EMPTYW = 12, B_HAFREE = 18, B_OFREE = 20,
       B_XFREE = 21,
       B_KVRDY = 23, B_ORDY = 27, B_XRDY = 35, B_STGE = 39,
       B_KVFULL = 42, B_RES = 46, B_PAR = 47, B_STG = 48, B_PFREE = 51, B_COUNT = 52,
       B_ROW = 154, B_PW = 155 };
#define BAR(x) (sb + BARS + 8 * (x))
DEVI uint32_t qa_off(int s) { return s == 2 ? SA2 : (uint32_t)s * 32768u; }
DEVI uint32_t qb_off(int s) { return s == 0 ? SB0 : (s == 1 ? SB1 : SB2); }
DEVI int kb_order(int bc, int n) {
  const int e = n < 9 ? n - 2 : n - 9;
  return n < 2 ? 2 * bc + n : 2 * (((e < 4 ? e + 4 : e - 4 + (e - 4 >= (bc & 3))) + (bc & 4)) & 7) + (n >= 9);
}
DEVI int wo_order(int bc, int n) { return (n & 8) | ((n + (bc & 6)) & 7); }
DEVI uint32_t w_off(int s) { return (uint32_t)((0x143065 >> (4 * s)) & 7) * 32768u; }
DEVI uint32_t w_par(int n, int s, int L) { return (n >= 6 && n < 12) ^ (s == 5) ^ (s != 2 && L); }
DEVI uint32_t w_aoff(int n, int s) { return n == 3 ? QO : w_off(s); }
DEVI int w_next(int n, int s) { return s == 5 ? 0 : (n == 13 ? 3 : s + 1); }

struct Params {
  const bf16 *x0, *wqkv, *wo, *wr, *wg, *wu, *wd;
  bf16* out;
  Scratch* g;
  CUtensorMap mX, mWq, mXh, mWo, mWg, mWu, mWp, mWd;
  unsigned map[128];
};
#define BID ((int)(P.map[blockIdx.x] & 255))
#define FID ((int)(P.map[blockIdx.x] >> 8))
DEVI uint32_t uni(uint32_t v) { return __shfl_sync(0xffffffffu, v, 0); }
#define PQ_N 8
#define PQ_T 700
#define PF0_N 10
#define PF0_T 1600
#define PF1_E 24
#define PF1_T 1100
#define POL_Q1 POL_NORMAL
#define POL_X POL_NORMAL
#define PFA0_BAR 3
#define PFA1_BAR 0
#define PFA0_M 0
#define PFA1_M 0
#define PFA0_T 900
#define PFA1_T 700
#define PF1_S PF0_N
#define PF1_D 0
#define POL_G POL_NORMAL
#define POL_U POL_FIRST
#define POL_D POL_FIRST
#define JQ_N 6
#define WDSRC (P.wd + (size_t)min(fid, 111) * 32768)
#define WDSRC2 (P.wd + FID * 32768)
#define WD_N 4
#define THR_N 5
#define KV_D 1800
#define XD_D 300
#define W0_BAR 3
#define QEF_N 99
#define PACE_T 300
#define IDLE_T 11000
#define LATE_C 99
#define LATE_B B_XFREE + 1
#define LATE_P 0
#define KV_D1 200
#define KV_D2 1200
#define KV_DL 0
#define POL_KV0 POL_FIRST
#define POL_KV1 POL_FIRST
#define POL_O0 POL_FIRST
#define POL_O1 POL_FIRST
#define POL_W0 POL_NORMAL
#define POL_W1 POL_FIRST
#define POL_T POL_FIRST
#define U_C 8
#define ST_M 0
#define PX_Q 99
#define PQ_S 0
#define POL_Q0 POL_NORMAL
constexpr float LN_EPS = 1e-5f;
constexpr float QSCALE = 0.17677669529663687f * 1.4426950408889634f;

DEVI void fma8(float (&a)[8], uint4 v, float h) {
  a[0] = fmaf(bf_lo(v.x), h, a[0]); a[1] = fmaf(bf_hi(v.x), h, a[1]); a[2] = fmaf(bf_lo(v.y), h, a[2]); a[3] = fmaf(bf_hi(v.y), h, a[3]);
  a[4] = fmaf(bf_lo(v.z), h, a[4]); a[5] = fmaf(bf_hi(v.z), h, a[5]); a[6] = fmaf(bf_lo(v.w), h, a[6]); a[7] = fmaf(bf_hi(v.w), h, a[7]);
}
DEVI uint4 ldsv128(uint32_t a) { uint4 v; asm volatile("ld.volatile.shared.v4.u32 {%0,%1,%2,%3}, [%4];" : "=r"(v.x), "=r"(v.y), "=r"(v.z), "=r"(v.w) : "r"(a) : "memory"); return v; }
DEVI float ldsv32f(uint32_t a) { float v; asm volatile("ld.volatile.shared.f32 %0, [%1];" : "=f"(v) : "r"(a) : "memory"); return v; }
DEVI uint32_t clk() { uint32_t t; asm volatile("mov.u32 %0, %%clock;" : "=r"(t)); return t; }
DEVI int fresh_tid() { int t; asm volatile("mov.u32 %0, %%tid.x;" : "=r"(t)); return t & 127; }
DEVI float fold8(const float (&a)[8]) {
  const int lane = threadIdx.x & 31;
  const bool u = lane & 16, v = lane & 8, x = lane & 4;
  float b0 = (u ? a[4] : a[0]) + __shfl_xor_sync(0xffffffffu, u ? a[0] : a[4], 16), b1 = (u ? a[5] : a[1]) + __shfl_xor_sync(0xffffffffu, u ? a[1] : a[5], 16);
  float b2 = (u ? a[6] : a[2]) + __shfl_xor_sync(0xffffffffu, u ? a[2] : a[6], 16), b3 = (u ? a[7] : a[3]) + __shfl_xor_sync(0xffffffffu, u ? a[3] : a[7], 16);
  float c0 = (v ? b2 : b0) + __shfl_xor_sync(0xffffffffu, v ? b0 : b2, 8), c1 = (v ? b3 : b1) + __shfl_xor_sync(0xffffffffu, v ? b1 : b3, 8);
  return (x ? c1 : c0) + __shfl_xor_sync(0xffffffffu, x ? c0 : c1, 4);
}
DEVI float sigmoidf(float x) { return __fdividef(1.f, 1.f + ex2f(-1.4426950408889634f * x)); }
DEVI float swiglu(float g, float u) { return g * u * sigmoidf(g); }

template<int J0, int J1> DEVI void exp_pack(const float (&s)[32], uint32_t (&p)[16]) {
  #pragma unroll
  for (int j = J0; j < J1; j++) p[j] = pack_bf16(ex2f(s[2 * j]), ex2f(s[2 * j + 1]));
}
DEVI bool attn_pack(const float (&o)[20], uint32_t (&ob)[8]) {
  const float lo = 5.421010862427522e-20f, hi = 1.8446744073709552e19f;
  float i0, i1; asm("rcp.approx.ftz.f32 %0, %1;" : "=f"(i0) : "f"(o[16])); asm("rcp.approx.ftz.f32 %0, %1;" : "=f"(i1) : "f"(o[18]));
  #pragma unroll
  for (int e = 0; e < 8; e++) ob[e] = pack_bf16(o[2 * e] * ((e & 1) ? i1 : i0), o[2 * e + 1] * ((e & 1) ? i1 : i0));
  return __all_sync(0xffffffffu, o[16] >= lo && o[16] <= hi && o[18] >= lo && o[18] <= hi);
}
DEVI void attn_store(const uint32_t (&ob)[8], bool ok, uint32_t st, uint32_t sb, uint32_t bar) {
  stsm_x4(ok ? st : sb + DUMP, ob[0], ob[1], ob[2], ob[3]); stsm_x4(ok ? st ^ 32 : sb + DUMP, ob[4], ob[5], ob[6], ob[7]);
  __syncwarp();
  asm volatile("{\n.reg .pred p, q;\nelect.sync _|q, 0xffffffff;\nsetp.ne.and.u32 p, %1, 0, q;\n@p mbarrier.arrive.shared::cta.b64 _, [%0];\n}" :: "r"(bar), "r"((uint32_t)ok) : "memory");
}
DEVI void attn_exact(uint32_t st, uint32_t kv, int t, bool hasprev, uint32_t bar) {
  const int lane = threadIdx.x & 31;
  #pragma unroll 1
  for (int row = ((threadIdx.x >> 5) & 3) * 16, n = 0; n < 16; n++, row++) {
    const int k1 = 256 + t * 64 + row;
    float m = -INFINITY, l = 0.f, o = 0.f;
    #pragma unroll 1
    for (int k0 = hasprev ? k1 - 255 : 256; k0 <= k1; k0 += 32) {
      const int k = min(k0 + lane, k1), r = k & 63;
      float sc = 0.f;
      #pragma unroll 1
      for (int c = 0; c < 16; c++) {
        uint32_t a = lds32(st + row * 64 + ((c * 4) ^ ((row & 6) << 3))), b = lds32(kv + (k >> 6) * 8192 + r * 64 + ((c * 4) ^ ((r & 6) << 3)));
        sc = fmaf(bf_lo(a), bf_lo(b), fmaf(bf_hi(a), bf_hi(b), sc));
      }
      float mn = fmaxf(m, sc);
      #pragma unroll 1
      for (int x = 16; x; x >>= 1) mn = fmaxf(mn, __shfl_xor_sync(0xffffffffu, mn, x));
      const float al = ex2f(m - mn), pr = ex2f(sc - mn);
      m = mn; l *= al; o *= al;
      #pragma unroll 1
      for (int q = k0; q <= min(k0 + 31, k1); q++) {
        const float z = __shfl_sync(0xffffffffu, pr, q - k0);
        uint32_t b = lds32(kv + (q >> 6) * 8192 + 4096 + (q & 63) * 64 + (((lane >> 1) * 4) ^ ((q & 6) << 3)));
        l += z; o = fmaf(z, (lane & 1) ? bf_hi(b) : bf_lo(b), o);
      }
    }
    __syncwarp();
    sts16(st + row * 64 + ((lane * 2) ^ ((row & 6) << 3)), pack_bf16(__fdividef(o, l), 0.f));
  }
  warp_signal(bar);
}

template<int K0, int K1, int DONE = 0> DEVI void exp_pv(const float (&s)[32], uint32_t (&p)[16], float (&o)[20], uint32_t vd, bool accum) {
  #pragma unroll
  for (int ks = K0; ks < K1; ks++) {
    if (ks >= DONE) {
      #pragma unroll
      for (int j = 4 * ks; j < 4 * ks + 4; j++) p[j] = pack_bf16(ex2f(s[2 * j]), ex2f(s[2 * j + 1]));
    }
    asm volatile("" : "+r"(p[4 * ks]), "+r"(p[4 * ks + 1]), "+r"(p[4 * ks + 2]), "+r"(p[4 * ks + 3]));
    wg_fence();
    wgmma_rs_n40<1>(o, p[ks * 4], p[ks * 4 + 1], p[ks * 4 + 2], p[ks * 4 + 3], mkd<HI64>(vd + VOFF(ks * 64)), ks ? 1 : accum);
  }
}
template<int K0, int K1> DEVI void exp_pv2(const float (&s)[32], const float (&sx)[32], uint32_t (&p)[16], uint32_t (&px)[16], float (&o)[20], uint32_t v0, uint32_t v4,
                  const uint32_t (&msk)[9], int tdiag) {
  #pragma unroll
  for (int ks = K0; ks < K1; ks++) {
    #pragma unroll
    for (int j = 4 * ks; j < 4 * ks + 4; j++) {
      const int c = 8 * (j >> 1) - 8 * (j & 1);
      const uint32_t e = pack_bf16(ex2f(c > tdiag ? s[2 * j] : sx[2 * j]), ex2f(c + 1 > tdiag ? s[2 * j + 1] : sx[2 * j + 1])), m = msk[(j >> 1) - (j & 1) + 1];
      p[j] = e & m; px[j] = e & ~m;
      asm volatile("" : "+r"(p[j]), "+r"(px[j]));
    }
    wg_fence();
    wgmma_rs_n40<1>(o, p[ks * 4], p[ks * 4 + 1], p[ks * 4 + 2], p[ks * 4 + 3], mkd<HI64>(v0 + VOFF(ks * 64)), 1);
    wgmma_rs_n40<1>(o, px[ks * 4], px[ks * 4 + 1], px[ks * 4 + 2], px[ks * 4 + 3], mkd<HI64>(v4 + VOFF(ks * 64)), 1);
  }
}

template<int J0> DEVI void qkv_store(const float (&a)[96], float p0, float p1, uint32_t d) {
  #pragma unroll
  for (int hh = 0; hh < 2; hh++) {
    const int j = 4 * (J0 + 2 * hh);
    stsm_x4(d ^ (hh << 5), pack_bf16(a[j] * p0, a[j + 1] * p0), pack_bf16(a[j + 2] * p1, a[j + 3] * p1),
                           pack_bf16(a[j + 4] * p0, a[j + 5] * p0), pack_bf16(a[j + 6] * p1, a[j + 7] * p1));
  }
}
DEVI void mean_step(float (&a)[96], float m0, float m1, uint32_t cd, bool z) {
  const uint32_t u0 = z ? 0u : __float_as_uint(m0), u1 = z ? 0u : __float_as_uint(m1);
  uint32_t ma[4] = {__byte_perm(u0, 0u, 0x1010), __byte_perm(u1, 0u, 0x1010), __byte_perm(u0, 0u, 0x3232), __byte_perm(u1, 0u, 0x3232)};
  keep(ma);
  wg_fence();
  wgmma_rs_n192<1>(a, ma[0], ma[1], ma[2], ma[3], mkd<2>(cd), 1);
  wg_commit();
}

template<bool FIRST> DEVI void qkv_block(float (&aX)[96], float (&aY)[96], uint32_t sb16, int s, int tX, int tY) {
  uint32_t a16 = sb16 + (qa_off(s) >> 4), b16 = (sb16 + (qb_off(s) >> 4)) | ((8192u >> 4) << 16);
  uint32_t ax = (a16 + tX * 512) | 0x10000u, ay = (a16 + tY * 512) | 0x10000u;
  wg_fence();
  #pragma unroll
  for (int ks = 0; ks < 4; ks++) {
    wgmma_ss_n192<1>(aX, mkd<HI128>(ax + ks * 2), mkd<HI128>(b16 + ks * 128), !(FIRST && ks == 0));
    wgmma_ss_n192<1>(aY, mkd<HI128>(ay + ks * 2), mkd<HI128>(b16 + ks * 128), !(FIRST && ks == 0));
  }
  wg_commit();
}
DEVI void qkv_half(float (&a)[96], uint32_t sb16, int t, uint32_t sa, uint32_t sbb) {
  wg_fence();
  #pragma unroll
  for (int ks = 0; ks < 4; ks++)
    wgmma_ss_n192<1>(a, mkd<HI128>(((sb16 + (sa >> 4) + t * 512) | 0x10000u) + ks * 2), mkd<HI128>(((sb16 + (sbb >> 4)) | ((8192u >> 4) << 16)) + ks * 128), 1);
  wg_commit();
}
DEVI void wo_block(float (&acc)[64], uint32_t sb16, int n, int s, int wg) {
  uint32_t a16 = (sb16 + (w_aoff(n, s) >> 4) + wg * 256) | 0x10000u, b16 = (sb16 + (w_off(s) >> 4) + 1024) | ((8192u >> 4) << 16);
  wg_fence();
  #pragma unroll
  for (int ks = 0; ks < 4; ks++)
    wgmma_ss_n128<1>(acc, mkd<HI64>(a16 + (ks >> 1) * 512 + (ks & 1) * 2), mkd<HI128>(b16 + ks * 128), 1);
  wg_commit();
}
DEVI void consumer(const Params& P, uint32_t sb, int wg) {
  const int w = uni((threadIdx.x >> 5) & 3);
  #define LAYER uni(mbar_test(BAR(B_XRDY + wg * 2 + 1), 0))
  #define IDS L = LAYER; const int tid = fresh_tid(), lane = tid & 31
  const uint32_t ids = uni(P.map[blockIdx.x]);
  const int bi = (ids >> 4) & 7, rh = ids & 1, bc = (ids & 15) >> 1, fid = ids >> 8;
  const int tX = 3 - wg, tY = wg;
  constexpr uint32_t sb16 = 1024 >> 4;
  #pragma unroll 1
  while (true) {
    int L = LAYER;
    float2 fa, fb;
    {
      float aX[96], aY[96];
      const bool lead = fresh_tid() == 0;
      mbar_wait(BAR(B_FULLQ), 0);
      PROFW(threadIdx.x == 0, L * 8 + 1);
      qkv_block<true>(aX, aY, sb16, 0, tX, tY);
      #pragma unroll 1
      for (int n = 1, s = 1, ps = 0, ph = 0; n < 14; n++) {
        mbar_wait(BAR(B_FULLQ + s), ph ^ (s ? L : 0));
        PROFD(threadIdx.x == 0 && L && (n == 2 || n == 3 || n == 7 || n == 11 || n == 13), n == 2 ? 48 : 49 + (n >> 2));
        qkv_block<false>(aX, aY, sb16, s, tX, tY);
        wg_wait<1>(); if (lead) mbar_arrive(BAR(B_EMPTYQ + ps));
        ps = s; if (s == 2) { s = 0; ph ^= 1; } else s++;
      }
      mbar_wait(BAR(B_FULLQ + 2), L);
      qkv_half(aX, sb16, tX, SA2, SB2);
      mbar_wait(BAR(B_ROW), L);
      IDS;
      const uint32_t pa = sb + PAR + (w * 16 + (lane >> 2)) * 8;
      float2 p0 = lds64f(pa + tX * 512), p1 = lds64f(pa + tX * 512 + 64), p2 = lds64f(pa + tY * 512), p3 = lds64f(pa + tY * 512 + 64);
      mean_step(aX, p0.y, p1.y, sb16 + (CS >> 4), lane & 3);
      mbar_wait(BAR(B_FULLQ), 1);
      qkv_half(aX, sb16, tX, 0, SB0);
      wg_wait<3>(); if (lead) mbar_arrive(BAR(B_EMPTYQ + 1));
      bar_sync(1, 256);
      if (L) mbar_wait(BAR(B_PW), 0);
      qkv_half(aY, sb16, tY, SA2, SB2);
      wg_wait<1>(); keep(aX);
      const int srow = w * 16 + (lane & 15);
      const uint32_t x0 = sb + srow * 64 + (((lane >> 4) ^ ((srow >> 1) & 3)) << 4), xX = x0 + (4 + tX) * 8192, xY = x0 + (4 + tY) * 8192;
      qkv_store<8>(aX, p0.x, p1.x, xX + KVA); qkv_store<16>(aX, p0.x, p1.x, xX + KVA + 4096);
      warp_signal(BAR(B_KVRDY + wg * 2));
      qkv_half(aY, sb16, tY, 0, SB0);
      mean_step(aY, p2.y, p3.y, sb16 + (CS >> 4), fresh_tid() & 3);
      wg_wait<2>(); if (lead) mbar_arrive(BAR(B_EMPTYQ + 2));
      mbar_wait(BAR(B_EMPTYQ + 2), L);
      qkv_store<12>(aX, p0.x, p1.x, xX + KVB); qkv_store<20>(aX, p0.x, p1.x, xX + KVB + 4096);
      wg_wait<0>(); keep(aY);
      if (lead) mbar_arrive(BAR(B_EMPTYQ));
      PROFW(threadIdx.x == 0, L * 8 + 2);
      qkv_store<8>(aY, p2.x, p3.x, xY + KVA); qkv_store<16>(aY, p2.x, p3.x, xY + KVA + 4096);
      qkv_store<12>(aY, p2.x, p3.x, xY + KVB); qkv_store<20>(aY, p2.x, p3.x, xY + KVB + 4096);
      warp_signal(BAR(B_KVRDY + wg * 2 + 1));
      p0.x *= QSCALE; p1.x *= QSCALE; p2.x *= QSCALE; p3.x *= QSCALE;
      mbar_wait(BAR(B_EMPTYQ), 1);
      qkv_store<0>(aX, p0.x, p1.x, x0 + QO + tX * 4096);
      qkv_store<0>(aY, p2.x, p3.x, x0 + QO + tY * 4096); qkv_store<4>(aY, p2.x, p3.x, x0 + QO + 16384 + tY * 4096);
      { const float2* f = (const float2*)&P.g->statF[bi * 256 + rh * 128 + (wg ^ rh) * 64 + w * 16 + (lane >> 2)]; fa = __ldcg(f); fb = __ldcg(f + 16); }
      mbar_wait(BAR(B_PAR), L);
      qkv_store<4>(aX, p0.x, p1.x, x0 + QO + 16384 + tX * 4096);
      const int prow = (int)uni(lds32(sb + INFO)) - bi * 256;
      if ((prow >> 4) == tX * 4 + w || (prow >> 4) == tY * 4 + w) {
        __syncwarp();
        if (lane < 24) sts128(sb + (prow & 63) * 64 + (((lane ^ (prow >> 1)) & 3) << 4) +
                              (lane < 8 ? QO + (lane >> 2) * 16384 + (prow >> 6) * 4096 : ((lane & 4) ? KVB : KVA) + (4 + (prow >> 6)) * 8192 + (lane >> 4) * 4096),
                              lds128(sb + PATCH + lane * 16));
      }
      fence_async_smem();
      bar_sync(1, 256);
    }
    PROFW(threadIdx.x == 0, L * 8 + 3);
    {
      IDS;
      float s0[32], s1[32], sx[32], o[20], op[20];
      uint32_t p0[16], p1[16], px[16], msk[9];
      const int tdiag = w * 16 + (lane >> 2) - 2 * (lane & 3);
      const uint32_t ones = (sb16 + (ONES >> 4)) << 16;
      const uint32_t qX = (sb16 + (QO >> 4) + tX * 256) | 0x10000u, qY = (sb16 + (QO >> 4) + tY * 256) | 0x10000u;
      const uint32_t kXB = (sb16 + (KVB >> 4) + tX * 512) | 0x10000u;
      uint32_t redo = 0;
      const uint32_t ost = sb + QO + (w * 16 + (lane & 15)) * 64 + (((lane >> 4) ^ ((lane >> 1) & 3)) << 4);
      #define QA(s, q, k) do { wg_fence(); wgmma_ss_n64<0>(s, mkd<HI64>(q), mkd<HI64>(k), 0); } while (0)
      #define QB(s, q, k) wgmma_ss_n64<0>(s, mkd<HI64>((q) + 2), mkd<HI64>((k) + 2), 1)
      #define QA2(q, k) do { QA(s1, q, k); wgmma_ss_n64<0>(sx, mkd<HI64>(q), mkd<HI64>((k) + 2048), 0); } while (0)
      #define QB2(q, k) do { QB(s1, q, k); QB(sx, q, (k) + 2048); } while (0)
      #define VB(v, b) ((v) + VOFF((b) * 512))
      #define MID() do { wg_commit(); wg_wait<1>(); } while (0)
      QA(s0, qX + 1024, kXB + 1536); QB(s0, qX + 1024, kXB + 1536); wg_commit();
      #pragma unroll
      for (int e = 0; e < 20; e++) o[e] = 0.f;
      wg_wait<0>(); keep(s0);
      #pragma unroll 1
      for (int h = 1; h >= 0; h--) {
        const uint32_t kXA = kXB - ((KVB - KVA) >> 4), kX = h ? kXB : kXA, vX = VOFF((kX & 0xffffu) + 256) + ones;
        QA(s1, qX + h * 1024, kX + 1024);
        #pragma unroll
        for (int e = 0; e < 20; e++) op[e] = o[e];
        keep(op);
        exp_pv<0, 1>(s0, p0, o, VB(vX, 3), false); QB(s1, qX + h * 1024, kX + 1024); wg_commit();
        exp_pv<1, 2>(s0, p0, o, VB(vX, 3), true); MID(); keep(s1);
        exp_pv<2, 4>(s0, p0, o, VB(vX, 3), true);
        { int td = tdiag; asm volatile("" : "+r"(td));
          #pragma unroll
          for (int e = 0; e < 9; e++) msk[e] = ((8 * e - 8 > td) ? 0xFFFFu : 0u) | ((8 * e - 7 > td) ? 0xFFFF0000u : 0u);
          keep(msk); }
        exp_pv<0, 2>(s1, p1, o, VB(vX, 2), true);
        bar_sync(h ? 12 + wg : 4 + wg * 4, h ? 128 : 160);
        QA(s0, qX, kXA + 512 + h * 1024);
        exp_pv<2, 3>(s1, p1, o, VB(vX, 2), true); QB(s0, qX, kXA + 512 + h * 1024);
        exp_pv<3, 4>(s1, p1, o, VB(vX, 2), true); wg_commit();
        wg_wait<0>(); keep(s0); keep(p0); keep(p1); keep(o);
      }
      #pragma unroll 1
      for (int h = 0; h < 2; h++) {
        const uint32_t kb16 = sb16 + ((h ? KVB : KVA) >> 4), kX = (kb16 + tX * 512) | 0x10000u, kY = (kb16 + tY * 512) | 0x10000u, qx = qX + h * 1024, qy = qY + h * 1024;
        const uint32_t onesP = bi ? ones : (kb16 + 1984) << 16;
        const uint32_t vX = VOFF(kb16 + tX * 512 + 256), vY = VOFF(kb16 + tY * 512 + 256);
        uint32_t ob[8], v;
        v = VB(vX + (wg ? onesP : ones), 1);
        QA2(qx, kX);
        exp_pv<0, 1>(s0, p0, o, v, true); QB2(qx, kX); wg_commit();
        exp_pv<1, 2>(s0, p0, o, v, true); MID(); keep(s1); keep(sx);
        exp_pv<2, 4>(s0, p0, o, v, true);
        QA(s0, qy, kY + 1536);
        exp_pv2<0, 1>(s1, sx, p1, px, o, vX + onesP, VB(vX + ones, 4), msk, tdiag); QB(s0, qy, kY + 1536); wg_commit();
        exp_pv2<1, 2>(s1, sx, p1, px, o, vX + onesP, VB(vX + ones, 4), msk, tdiag); MID(); keep(s0); keep(p0);
        exp_pv2<2, 4>(s1, sx, p1, px, o, vX + onesP, VB(vX + ones, 4), msk, tdiag); wg_commit();
        v = VB(vY + (wg ? ones : onesP), 3);
        QA(s1, qy, kY + 1024);
        exp_pack<0, 4>(s0, p0);
        QB(s1, qy, kY + 1024); MID(); keep(o); keep(p1); keep(px);
        bool ok = attn_pack(o, ob); keep(ob);
        exp_pv<0, 2, 1>(s0, p0, o, v, false); MID(); keep(s1);
        attn_store(ob, ok, ost + (h * 4 + tX) * 4096, sb, BAR(B_ORDY + wg * 4 + h * 2)); redo |= ok ? 0u : 1u << (h * 2);
        exp_pv<2, 4>(s0, p0, o, v, true);
        v = VB(vY + onesP, 2);
        exp_pv<0, 1>(s1, p1, o, v, true);
        bar_sync(5 + wg * 4 + h * 2, 160);
        QA(s0, qy, kY + 512);
        exp_pv<1, 2>(s1, p1, o, v, true); QB(s0, qy, kY + 512); wg_commit();
        exp_pv<2, 3>(s1, p1, o, v, true); MID(); keep(s0); keep(p0);
        exp_pv<3, 4>(s1, p1, o, v, true);
        v = VB(vY + onesP, 1);
        QA2(qy, kY);
        exp_pv<0, 1>(s0, p0, o, v, true); QB2(qy, kY); wg_commit();
        exp_pv<1, 2>(s0, p0, o, v, true); MID(); keep(s1); keep(sx); keep(p1);
        exp_pv<2, 4>(s0, p0, o, v, true);
        exp_pv2<0, 1>(s1, sx, p1, px, o, vY + onesP, VB(vY + ones, 4), msk, tdiag);
        bar_sync(6 + wg * 4, h ? 128 : 160);
        QA(s0, h ? qy : qX + 1024, kXB + 512);
        exp_pv2<1, 2>(s1, sx, p1, px, o, vY + onesP, VB(vY + ones, 4), msk, tdiag); QB(s0, h ? qy : qX + 1024, kXB + 512);
        exp_pv2<2, 4>(s1, sx, p1, px, o, vY + onesP, VB(vY + ones, 4), msk, tdiag); wg_commit();
        wg_wait<0>(); keep(o); keep(s0); keep(p0); keep(p1); keep(px);
        ok = attn_pack(o, ob); attn_store(ob, ok, ost + (h * 4 + tY) * 4096, sb, BAR(B_ORDY + wg * 4 + h * 2 + 1)); redo |= ok ? 0u : 2u << (h * 2);
        #pragma unroll
        for (int e = 0; e < 20; e++) o[e] = op[e];
      }
      #undef QA
      #undef QB
      #undef QA2
      #undef QB2
      #undef VB
      #undef MID
      if (redo) {
        #pragma unroll 1
        for (int u = 0; u < 4; u++) if ((redo >> u) & 1) {
          const int h = u >> 1, t = (u & 1) ? tY : tX;
          attn_exact(sb + QO + (h * 4 + t) * 4096, sb + (h ? KVB : KVA), t, bi > 0, BAR(B_ORDY + wg * 4 + u));
        }
      }
    }
    PROFW(threadIdx.x == 0, L * 8 + 4);
    {
      IDS;
      const int t256 = wg * 128 + tid;
      float acc[64];
      const int tt = wg ^ rh;
      const int grow = bi * 256 + rh * 128 + tt * 64 + w * 16 + (lane >> 2);
      float al0 = 1.f, be0 = 0.f, al1 = 1.f, be1 = 0.f;
      const int idx0 = (int)uni(lds32(sb + INFO));
      const uint32_t tag = lds32(sb + INFO + 8) + L;
      uint4* const sp = &P.g->statP[bc][grow + (lane & 1) * 8];
      uint4* const yp = &P.g->yP[t256 >> 1][min(fid, 111)][t256 & 1];
      if (L) {
        float r0 = rsqrtf(fa.y + LN_EPS), r1 = rsqrtf(fb.y + LN_EPS);
        if (grow != idx0) { al0 = 1.f + r0; be0 = -fa.x * r0; }
        if (grow + 8 != idx0) { al1 = 1.f + r1; be1 = -fb.x * r1; }
      }
      const int srow = tt * 64 + w * 16 + (lane & 15);
      const uint32_t ra = sb + srow * 128 + (((lane >> 4) ^ (srow & 7)) << 4);
      mbar_wait(BAR(B_FULLW + 5), L);
      if ((idx0 >> 4) == bi * 16 + rh * 8 + tt * 4 + w) {
        int r = idx0 & 127;
        if (lane < 16) sts128(sb + 32768 + (lane >> 3) * 16384 + r * 128 + (((lane & 7) ^ (r & 7)) << 4), lds128(sb + X2SEG + lane * 16));
        fence_async_smem();
        __syncwarp();
      }
      #pragma unroll
      for (int jj = 0; jj < 8; jj++) {
        uint32_t r[4]; ldsm_x4((ra + 32768 + (jj >> 2) * 16384) ^ ((jj & 3) << 5), r[0], r[1], r[2], r[3]);
        #pragma unroll
        for (int e = 0; e < 4; e++) {
          acc[8 * jj + 2 * e] = fmaf(bf_lo(r[e]), (e & 1) ? al1 : al0, (e & 1) ? be1 : be0);
          acc[8 * jj + 2 * e + 1] = fmaf(bf_hi(r[e]), (e & 1) ? al1 : al0, (e & 1) ? be1 : be0);
        }
      }
      keep(acc);
      bar_sync(12 + wg, 128);
      if (!(lane & 2)) st_ll(sp, 0u, 0u, 0u, 0u);
      uint2 wd[4];
      #pragma unroll
      for (int e = 0; e < 4; e++) { wd[e] = make_uint2(0u, 0u); if (L) wd[e] = ldg_stream((const uint2*)(WDSRC) + t256 + (28 + e) * 256); }
      PROFW(t256 == 0, L * 8 + 5);
      #pragma unroll 1
      for (int n = 0, q = 0, pq = 5; n < 16; n++) {
        mbar_wait(BAR(B_FULLW + q), w_par(n, q, L));
        PROFD(t256 == 0 && !L && (n == 4 || n == 7 || n == 8 || n == 12), (n == 7 ? 63 : 41 + (n >> 2)));
        wo_block(acc, sb16, n, q, tt);
        wg_wait<1>(); if (tid == 0) mbar_arrive(BAR(B_EMPTYW + pq));
        pq = q; q = w_next(n, q);
      }
      mbar_wait(BAR(B_EMPTYW + 5), L);
      wg_wait<0>(); keep(acc);
      if (tid == 0) mbar_arrive(BAR(B_EMPTYW + 4));
      PROFW(t256 == 0, L * 8 + 6);
      const uint32_t xa = ra + rh * 16384;
      {
        float s1a = 0.f, s2a = 0.f, da = 0.f, s1b = 0.f, s2b = 0.f, db = 0.f;
        #pragma unroll
        for (int j = 0; j < 16; j++) {
          const float* a = acc + 4 * j; float2 wv = lds64f(sb + WR + j * 32 + (lane & 3) * 8);
          s1a += a[0] + a[1]; s1b += a[2] + a[3];
          s2a = fmaf(a[0], a[0], s2a); s2b = fmaf(a[2], a[2], s2b); s2a = fmaf(a[1], a[1], s2a); s2b = fmaf(a[3], a[3], s2b);
          da = fmaf(a[0], wv.x, da); db = fmaf(a[2], wv.x, db); da = fmaf(a[1], wv.y, da); db = fmaf(a[3], wv.y, db);
        }
        bool odd = lane & 1;
        float u1 = (odd ? s1b : s1a) + __shfl_xor_sync(0xffffffffu, odd ? s1a : s1b, 1);
        float u2 = (odd ? s2b : s2a) + __shfl_xor_sync(0xffffffffu, odd ? s2a : s2b, 1);
        float u3 = (odd ? db : da) + __shfl_xor_sync(0xffffffffu, odd ? da : db, 1);
        u1 += __shfl_xor_sync(0xffffffffu, u1, 2); u2 += __shfl_xor_sync(0xffffffffu, u2, 2); u3 += __shfl_xor_sync(0xffffffffu, u3, 2);
        if (!(lane & 2)) st_ll(sp, __float_as_uint(u1), __float_as_uint(u2), __float_as_uint(u3), tag);
      }
      {
      #pragma unroll
      for (int jj = 0; jj < 8; jj++) {
        const float* a = acc + 8 * jj;
        stsm_x4((xa + (jj >> 2) * 32768) ^ ((jj & 3) << 5), pack_bf16(a[0], a[1]), pack_bf16(a[2], a[3]), pack_bf16(a[4], a[5]), pack_bf16(a[6], a[7]));
        if (jj == 7) fence_async_smem();
        if ((jj & 3) == 3) warp_signal(BAR(B_XRDY + wg * 2 + (jj >> 2)));
      }
      }
      PROFW(t256 == 0, L * 8 + 7);
      if (L) {
        mbar_wait(BAR(B_PAR), 0);
        { float2 pa = lds64f(sb + PAR + (grow & 127) * 8), pb = lds64f(sb + PAR + (grow & 127) * 8 + 64); al0 = pa.x; be0 = pa.y; al1 = pb.x; be1 = pb.y; }
        uint32_t rs[32];
        #pragma unroll
        for (int j = 0; j < 16; j++) {
          rs[2 * j] = pack_bf16(fmaf(acc[4 * j], al0, be0), fmaf(acc[4 * j + 1], al0, be0));
          rs[2 * j + 1] = pack_bf16(fmaf(acc[4 * j + 2], al1, be1), fmaf(acc[4 * j + 3], al1, be1));
        }
        #pragma unroll
        for (int jj = 0; jj < 8; jj++) stsm_x4((xa + (jj >> 2) * 32768) ^ ((jj & 3) << 5), rs[4 * jj], rs[4 * jj + 1], rs[4 * jj + 2], rs[4 * jj + 3]);
        PROFW(t256 == 0, 16);
        if (fid >= 112) bar_arrive(3, 384);
        else {
          float d[4] = {0.f, 0.f, 0.f, 0.f};
          mbar_wait(BAR(B_FULLW + wg * 3), 0); mbar_wait(BAR(B_FULLW + wg * 3 + 1), 0);
          bar_sync(3, 384);
          PROFW(t256 == 0, 29);
          #pragma unroll 1
          for (int g = 0; g < 4; g++) {
            const uint32_t ad = (sb16 + (wg ? 6144 : 10240) + (g >> 1) * 2048 + (g & 1) * 512) | (1024u << 16), bd = (sb16 + (HV >> 4) + wg * 64 + g * 16) | 0x10000u;
            wg_fence();
            #pragma unroll
            for (int ks = 0; ks < 8; ks++) wgmma_ss_n8<0, 1>(d, mkd<HI64>(ad + ks * 64), mkd<8>(bd + ks * 2), 1);
            wg_commit();
          }
          mbar_wait(BAR(B_FULLW + 2), 0);
          wg_wait<0>(); keep(d);
          if (!(lane & 3)) { sts32f(sb + PAR + 1024 + wg * 256 + w * 64 + lane, d[0]); sts32f(sb + PAR + 1056 + wg * 256 + w * 64 + lane, d[2]); }
          bar_sync(1, 256);
          const uint32_t ga = sb + PAR + 1024 + lane * 4, aa = sb + HV + (t256 >> 5) * 128;
          sts32f(aa + lane * 4, swiglu(lds32f(ga) + lds32f(ga + 256), lds32f(ga + 128) + lds32f(ga + 384)));
          __syncwarp();
          PROFW(t256 == 0, 26);
          float y0 = 0.f, y1 = 0.f, y2 = 0.f, y3 = 0.f;
          uint32_t tbl = rh ? 0x001459a8u : 0x023679a8u;
          uint4 a4 = lds128(aa + 112);
          #pragma unroll 2
          for (int n = 0; n < 8; n++, tbl >>= 4) {
            const uint32_t src = sb + t256 * 8 + (tbl & 15) * 8192;
            const uint4 an = lds128(aa + ((0x00123564u >> (4 * n)) & 15) * 16);
            #pragma unroll
            for (int e = 0; e < 4; e++) {
              const float av = __uint_as_float(e == 0 ? a4.x : (e == 1 ? a4.y : (e == 2 ? a4.z : a4.w)));
              y0 = fmaf(bf_lo(wd[e].x), av, y0); y1 = fmaf(bf_hi(wd[e].x), av, y1); y2 = fmaf(bf_lo(wd[e].y), av, y2); y3 = fmaf(bf_hi(wd[e].y), av, y3);
              const float2 v = lds64f(src + e * 2048); wd[e] = make_uint2(__float_as_uint(v.x), __float_as_uint(v.y));
            }
            a4 = an;
          }
          st_ll(yp, __float_as_uint(y0), __float_as_uint(y1), __float_as_uint(y2), (__float_as_uint(y3) & ~255u) | (lds32(sb + INFO + 12) + 1));
          PROFW(t256 == 0, 27);
        }
        return;
      }
      mbar_wait(BAR(B_XRDY + wg * 2 + 1), 0);
    }
  }
  #undef IDS
  #undef LAYER
}

DEVI void loader(const Params& P, uint32_t sb) {
  const int lane = threadIdx.x & 31;
  const int bid = uni(BID), bi = bid >> 4, bp = bid & 15, rh = bp & 1, bc = bp >> 1;
  uint32_t phq = 0, tag = 0;
  #pragma unroll 1
  for (int L = 0; L < 2; L++) {
    int s = 0;
    uint32_t rdy = 0;
    #pragma unroll 1
    for (int n = L ? 0 : 3; n < 16; n++) {
      int kb = L ? kb_order(bc, n) : n;
      mbar_wait(BAR(B_EMPTYQ + s), (phq >> s) & 1);
      phq ^= 1u << s;
      if (L && n == 1) { mbar_wait(BAR(B_XRDY + 1), 0); mbar_wait(BAR(B_XRDY + 3), 0); }
      if (elect()) {
        mbar_expect_tx(BAR(B_FULLQ + s), L && n < 2 ? 40960 : 57344);
        tma_3d_h(sb + qb_off(s), &P.mWq, bp * 64, kb * 64, 0, BAR(B_FULLQ + s), L && n >= QEF_N ? POL_FIRST : POL_NORMAL);
        if (!L) tma_2d(sb + qa_off(s), &P.mX, kb * 64, bi * 256, BAR(B_FULLQ + s));
      }
      if (L && n >= 2) {
        if (((rdy >> (2 * kb)) & 3) != 3) {
          do { rdy = __ballot_sync(0xffffffffu, ld_rlx(&P.g->flagX[bi][lane]) == tag); } while (((rdy >> (2 * kb)) & 3) != 3);
          fence_async_glob();
        }
        if (n == 3 || n == 4) mbar_wait(BAR(B_XFREE + n - 3), 0);
        if (elect()) bulk_g2s_h(sb + qa_off(s), P.g->x[bi][kb], 32768, BAR(B_FULLQ + s), POL_X);
      }
      PROFY(L && lane == 0 && (n == 2 || n == 3 || n == 9), n == 9 ? 60 : 56 + n);
      if (L && n == 2) { mbar_wait(BAR(B_FULLQ), 0); mbar_wait(BAR(B_FULLQ + 1), 1); if (lane < 2) mbar_arrive_peer(BAR(B_XFREE + lane)); }
      s = (s == 2) ? 0 : s + 1;
    }
    for (int q = 0; q < 3; q++) mbar_wait(BAR(B_EMPTYQ + q), (phq >> q) & 1);
    tag = lds32(sb + INFO + 8) + L;
    #pragma unroll 1
    for (int q = 0; q < 4; q++) {
            if (bi) {
        const unsigned* f = &P.g->flagKV[bid - 16][q];
        while (ld_rlx(f) != tag);
        fence_async_glob();
      }
      if (elect()) {
        mbar_expect_tx(BAR(B_KVFULL + q), 16384);
        bulk_g2s_h(sb + ((q >> 1) ? KVB : KVA) + ((q & 1) ? 0 : 16384), bi ? P.g->kv[bid - 16][q] : P.g->zero, 16384, BAR(B_KVFULL + q), L ? POL_KV1 : POL_KV0);
      }
      PROFY(!L && lane == 0 && bi && q != 2, 34 + (q + 1) / 2);
    }
    mbar_wait(BAR(B_ORDY), L);
    {
      const uint4* src = P.g->o[bi][0][0][rh];
      rdy = 0;
      #pragma unroll 1
      for (int n = 0, q = 0; n < 16; q = w_next(n, q), n++) {
        const int j = wo_order(bc, n);
        if (((rdy >> (2 * j)) & 3) != 3) {
          do { rdy = __ballot_sync(0xffffffffu, ld_rlx(&P.g->flagO[bi][lane]) == tag); } while (((rdy >> (2 * j)) & 3) != 3);
          fence_async_glob();
        }
        if (n >= 2) mbar_wait(n < 5 ? BAR(B_HAFREE + (n > 3)) : BAR(B_EMPTYW + q), n < 5 ? L : w_par(n, q, L) ^ 1);
        if (n == THR_N) mbar_wait(BAR(B_OFREE), L);
        if (elect()) { mbar_expect_tx(BAR(B_FULLW + q), 16384); bulk_g2s_h(sb + w_aoff(n, q), src + j * 2048, 16384, BAR(B_FULLW + q), L ? POL_O1 : POL_O0); }
      }
    }
    mbar_wait(BAR(B_OFREE), L);
  }
}

DEVI void ffn_prefetch(const Params& P, int q) {
  bulk_prefetch(q < 16 ? ((q & 1) ? P.wu : P.wg) + ((q >> 1) * 128 + blockIdx.x) * 3584 : P.wd + (min(FID, 111) * 8 + q - 16) * 4096, q < 16 ? 7168 : 8192);
}
DEVI void storer(const Params& P, uint32_t sb, int wg) {
  const int bid = uni(BID), bi = bid >> 4, rh = bid & 1, bc = (bid & 15) >> 1;
  const bool one = (threadIdx.x & 31) == 0;
  char* const g = (char*)P.g;
  const uint32_t tag0 = uni(((ld_rlx(&P.g->epoch) % 16383u) + 1u) << 2);
  #pragma unroll 1
  for (int L = 0; L < 2; L++) {
    const uint32_t tag = tag0 + L;
    if (wg) {
      #pragma unroll 1
      for (int r = threadIdx.x & 31; r < 256; r += 32) {
        uint4 v;
        do v = ld_ll(&P.g->statF[bi * 256 + r]); while (!__all_sync(0xffffffffu, v.w == tag));
        float var = __uint_as_float(v.y), c = rsqrtf(var + LN_EPS);
        if (L) { c += 1.f; c *= rsqrtf(fmaf(var * c, c, LN_EPS)); }
        const float mh = bf_round(__uint_as_float(v.x));
        sts64f(sb + PAR + r * 8, c, __uint_as_float(pack_bf16(mh, __uint_as_float(v.x) - mh)));
      }
      if (!L) mbar_wait(BAR(B_PAR), 0);
      warp_signal(BAR(B_ROW));
    }
    #pragma unroll 1
    for (int u = 0; u < 2 + 4 * wg; u++) {
      const int h = u < 2 ? u : u >> 2, hi = (u & 1) ^ 1;
      uint32_t src, dst, fl, b0, b1;
      if (u < 2) {
        src = (h ? KVB : KVA) + (3 - wg) * 16384; dst = offsetof(Scratch, kv) + (bid * 4 + h * 2 + wg) * 16384; fl = offsetof(Scratch, flagKV) + (bid * 32 + h * 2 + wg) * 4;
        b0 = BAR(B_KVRDY + ((u | wg) ? 1 : 0)); b1 = b0 + 16;
      } else {
        src = QO + (h * 2 + hi) * 8192; dst = offsetof(Scratch, o) + ((((bi * 2 + h) * 8 + bc) * 2 + hi) * 2 + rh) * 8192;
        fl = offsetof(Scratch, flagO) + (bi * 32 + h * 16 + (bid & 15)) * 4;
        b0 = BAR(B_ORDY + u - 2); b1 = b0 + 32;
      }
      mbar_wait(b0, L); mbar_wait(b1, L);
      if (u + wg == 1) {
        mbar_wait(BAR(B_PAR), L);
        const uint32_t t0 = clk(), dt = (wg ? KV_D1 : KV_D2) + (L ? KV_DL : 0); while (clk() - t0 < dt) __nanosleep(40);
      }
      fence_async_smem();
      PROFY(one && !L && u == 3 * wg, u ? 46 : 8);
      if (one && (u >= 2 || bi < 7)) bulk_s2g(g + dst, sb + src, u < 2 ? 16384 : 8192, ((ST_M >> (L * 2 + (u >= 2))) & 1) ? POL_FIRST : POL_NORMAL);
      if (one && u == 5) mbar_arrive(BAR(B_HAFREE + 1));
      if (u == 2 || u == 4) continue;
      bulk_wait<0>();
      PROFY(one && !L && u == 3 * wg, u ? 61 : 62);
      fence_rel();
      if (one) { st_rlx((unsigned*)(g + fl), tag); if (!wg || u > 2) mbar_arrive(BAR(B_HAFREE + h + (wg & h))); if (!wg && u) mbar_arrive(BAR(B_RES)); }
      PROFY(one && !L && (u > 2 || u == wg), u > 2 ? (u == 3 ? 38 : 54) : 32 + u);
    }
    if (L == 0) {
      char* dst = g + (offsetof(Scratch, x) + (bi * 16 + 2 * bc) * 32768 + rh * 16384);
      unsigned* f = (unsigned*)(g + (offsetof(Scratch, flagX) + (bi * 32 + bc * 4 + rh) * 4));
      const uint32_t a = sb + rh * 16384;
      if (wg == 0) {
        mbar_wait(BAR(B_XRDY), 0); mbar_wait(BAR(B_XRDY + 2), 0);
        fence_async_smem();
        PROFY(one, 41);
        if (one) bulk_s2g(dst, a, 16384);
        bulk_wait<0>();
        PROFY(one, 45);
        if (one) { mbar_arrive(BAR(B_XFREE)); mbar_arrive(BAR(B_PFREE)); }
        fence_rel();
        mbar_wait(BAR(B_XRDY + 1), 0); mbar_wait(BAR(B_XRDY + 3), 0);
        if (one) { st_rlx(f, tag); bulk_s2g(dst + 32768, a + 32768, 16384); }
        PROFY(one, 56);
        bulk_wait<0>();
        if (one) mbar_arrive(BAR(B_XFREE + 1));
        fence_rel();
        if (one) st_rlx(f + 2, tag);
        PROFY(one, 57);
      } else {
        mbar_wait(BAR(B_XRDY + 1), 0); mbar_wait(BAR(B_XRDY + 3), 0);
        mbar_wait(BAR(B_PFREE), 0);
        if (one) bulk_s2peer(a, 16384, BAR(B_FULLQ));
        { const uint32_t t0 = clk(); while (clk() - t0 < XD_D); }
        if (one) bulk_s2peer(a + 32768, 16384, BAR(B_FULLQ + 1));
      }
      if (wg == 0) {
        uint32_t t0 = clk() + PF1_D;
        #pragma unroll 1
        for (int q = PF1_S; q < PF1_E; q++) { while ((int)(clk() - t0) < 0) __nanosleep(50); if (one) ffn_prefetch(P, q); t0 += PF1_T; }
      }
    }
  }
}

DEVI void stg_issue(const Params& P, int c, uint32_t d, uint32_t du, uint32_t b) {
  mbar_expect_tx(b, 16384);
  if (c < 8) { tma_2d_h(d, &P.mWg, FID * 32, c * 128, b, du > 8192 ? POL_T : POL_G); tma_2d_h(d + du, &P.mWu, FID * 32, c * 128, b, du > 8192 || c < U_C ? POL_FIRST : POL_NORMAL); }
  else if (c < 12) tma_3d_h(d, &P.mWd, 0, FID * 32 + (c - 8) * 8, 0, b, POL_D);
  else tma_2d_h(d, &P.mWp, (c - 12) * 1024 + (BID >> 2) * 32, (BID & 3) * 256, b, POL_EF);
}
DEVI void pace() { const uint32_t t0 = clk(); while (clk() - t0 < PACE_T); }
DEVI void stager(const Params& P, uint32_t sb) {
  {
    const int b = blockIdx.x;
    uint32_t t0 = clk();
    #pragma unroll 1
    for (int q = PQ_S; q < PQ_N; q++) { if (q == PX_Q) bulk_prefetch(P.x0 + b * 16384, 32768); bulk_prefetch(P.wqkv + (q * 128 + b) * 3072, 6144); while (clk() - t0 < PQ_T) __nanosleep(50); t0 += PQ_T; }
    bulk_prefetch(P.wo + b * 8192, 16384);
    #pragma unroll 1
    for (int q = 0; q < PF0_N; q++) {
      while (clk() - t0 < PF0_T) __nanosleep(50);
      t0 += PF0_T;
      ffn_prefetch(P, q);
    }
  }
  const int bid = BID, bi = bid >> 4, rh = bid & 1, bc = (bid & 15) >> 1;
  #pragma unroll 1
  for (int L = 0; L < 2; L++) {
    const int nch = L ? (FID < 112 ? 8 : 0) : 15;
    mbar_wait(BAR(B_PAR), L); mbar_wait(BAR(B_KVFULL + W0_BAR), L);
    #pragma unroll 1
    for (int m = 0, r = 0; m < 16; r = w_next(m, r), m++) {
      const int sw = (m == 3 || m == 4) ? 7 : 0, n = m ^ sw, q = r ^ sw;
      if (n == 4) { mbar_wait(BAR(B_RES), L); mbar_wait(BAR(B_ORDY + 2), L); mbar_wait(BAR(B_ORDY + 6), L); }
      else if (n >= 2) mbar_wait(n < 5 ? BAR(B_HAFREE + (n > 2)) : BAR(B_EMPTYW + q), n < 5 ? L : w_par(n, q, L) ^ 1);
      if (n == THR_N) mbar_wait(BAR(B_OFREE), L);
      mbar_expect_tx(BAR(B_FULLW + q), 16384);
      tma_5d(sb + w_off(q) + 16384, &P.mWo, 0, 0, n >> 3, 2 * (wo_order(bc, n) & 7), 2 * bc, BAR(B_FULLW + q), L ? POL_W1 : POL_W0);
      if (n == 2) {
        #pragma unroll 1
        for (int e = 0; e < 2; e++) {
          mbar_expect_tx(BAR(B_FULLW + 5), 16384);
          if (L) bulk_g2s_h(sb + 32768 + e * 16384, P.g->x[bi][2 * bc + e] + rh * 1024, 16384, BAR(B_FULLW + 5));
          else tma_2d_h(sb + 32768 + e * 16384, &P.mXh, bc * 128 + e * 64, bi * 256 + rh * 128, BAR(B_FULLW + 5), POL_EF);
        }
      }
    }
    mbar_wait(BAR(B_EMPTYW + 5), L);
    if (L && nch) {
      const bf16* src = WDSRC2;
      mbar_expect_tx(BAR(B_FULLW + 2), 32768); mbar_expect_tx(BAR(B_FULLW + 2), 24576);
      #pragma unroll 1
      for (int e = 0; e < 3; e++) { bulk_g2s_h(sb + e * 32768 + (e < 2 ? (rh ^ 1) * 16384 : 0), src + e * 8192, e < 2 ? 16384 : 24576, BAR(B_FULLW + 2)); pace(); }
    }
        if (L == 0) { mbar_arrive_peer(BAR(B_PFREE)); mbar_wait(BAR(B_EMPTYW), 0); mbar_wait(BAR(B_EMPTYW + 1), 0); }
    #pragma unroll 1
    for (int c = FID < 112 ? 0 : 12, slot = 0; c < nch; c++, slot = slot == 2 ? 0 : slot + 1) {
      const int q = (c >> 1) + (c >> 2);
      if (!L && (c == LATE_C || c == 12)) mbar_wait(BAR(LATE_B), LATE_P);
      mbar_wait(L ? BAR(B_EMPTYW + q) : BAR(B_STGE + slot), L | ((0x71c7 >> c) & 1));
      #define CC c
      stg_issue(P, CC, L ? sb + w_off(q) + (c & 1) * 8192 : sb + STG + slot * 16384, 8192 << L, L ? BAR(B_FULLW + q) : BAR(B_STG + slot));
      if (L) pace();
    }
  }
}
DEVI void sum8(uint4 v, float& s1, float& s2) {
  float e[8] = {bf_lo(v.x), bf_hi(v.x), bf_lo(v.y), bf_hi(v.y), bf_lo(v.z), bf_hi(v.z), bf_lo(v.w), bf_hi(v.w)};
  #pragma unroll
  for (int q = 0; q < 8; q++) { s1 += e[q]; s2 = fmaf(e[q], e[q], s2); }
}
DEVI uint4 norm8(uint4 x, float m, float rs) {
  #define HN(v) pack_bf16((bf_lo(v) - m) * rs, (bf_hi(v) - m) * rs)
  return make_uint4(HN(x.x), HN(x.y), HN(x.z), HN(x.w));
  #undef HN
}
DEVI void put_f32(uint4 b, uint32_t d, uint32_t d2) {
  sts128(d, make_uint4(b.x << 16, b.x & 0xffff0000u, b.y << 16, b.y & 0xffff0000u));
  sts128(d + d2, make_uint4(b.z << 16, b.z & 0xffff0000u, b.w << 16, b.w & 0xffff0000u));
}
DEVI void put_bf16(uint4 b, uint32_t d) {
  sts64f(d, __uint_as_float(b.x), __uint_as_float(b.y)); sts64f(d + 1024, __uint_as_float(b.z), __uint_as_float(b.w));
  fence_async_smem();
}
DEVI uint4 best4(uint32_t p) {
  uint4 a = lds128(p), b = lds128(p + 16), c = lds128(p + 32), d = lds128(p + 48);
  if (b.x > a.x) a = b;
  if (d.x > c.x) c = d;
  return c.x > a.x ? c : a;
}
#define FL(x) __uint_as_float(x)
#define UI(x) __float_as_uint(x)
DEVI void aux(const Params& P, uint32_t sb) {
  int tid = fresh_tid();
  #define lane (tid & 31)
  #define wq (tid >> 5)
  uint32_t ids = P.map[blockIdx.x], tag;
  #define bid ((int)(ids & 255))
  #define fid ((int)(ids >> 8))
  #define bi (bid >> 4)
  #define bp (bid & 15)
  #define bc (bp >> 1)
  #define FRESH() do { tid = fresh_tid(); uint4 z_ = ldsv128(sb + INFO2 + 16); ids = z_.y; tag = z_.z + L; idx = z_.w; } while (0)
  {
    const uint32_t epoch = ld_rlx(&P.g->epoch);
    if (tid == 0) {
      mbar_expect_tx(BAR(B_STG), 49152);
      tma_3d(sb + STG, &P.mWq, bp * 64, bi * 128, 0, BAR(B_STG));
      tma_3d(sb + STG + 24576, &P.mWq, bp * 64, bi * 128 + 64, 0, BAR(B_STG));
    }
    __syncwarp();
    sts64f(sb + ONES + tid * 8, FL(0x3F803F80u), FL(0x3F803F80u));
    float s1 = 0.f, s2 = 0.f;
    { uint4 v = __ldg((const uint4*)P.wr + tid);
      if ((tid >> 4) == bc) put_f32(v, sb + WR + (tid & 15) * 32, 16);
      sum8(v, s1, s2);
      #pragma unroll 1
      for (int o = 16; o; o >>= 1) s1 += __shfl_xor_sync(0xffffffffu, s1, o);
      sts32f(sb + INFO2 + wq * 4, s1); }
    const uint4* src = (const uint4*)(P.x0 + (size_t)bid * 16384) + (tid >> 3) * 128 + (tid & 7);
    s1 = 0.f; s2 = 0.f;
    #pragma unroll 1
    for (int it = 0; it < 16; it += 4) {
      uint4 v0 = __ldg(src + it * 8), v1 = __ldg(src + it * 8 + 8), v2 = __ldg(src + it * 8 + 16), v3 = __ldg(src + it * 8 + 24);
      #pragma unroll 1
      for (int q = 0; q < 4; q++) { sum8(v0, s1, s2); v0 = v1; v1 = v2; v2 = v3; }
    }
    #pragma unroll 1
    for (int o = 1; o < 8; o <<= 1) { s1 += __shfl_xor_sync(0xffffffffu, s1, o); s2 += __shfl_xor_sync(0xffffffffu, s2, o); }
    tag = ((epoch % 16383u) + 1u) << 2;
    if (tid == 0) { sts128(sb + INFO, make_uint4(0x40000000u, 0u, tag, ((epoch % 127u) + 1u) << 1)); sts128(sb + INFO2 + 16, make_uint4(epoch, ids, tag, 0x40000000u)); }
    float m = s1 * (1.f / 1024.f);
    if ((tid & 7) == 0) st_ll(&P.g->statF[bid * 16 + (tid >> 3)], UI(m), UI(fmaxf(fmaf(-m, m, s2 * (1.f / 1024.f)), 0.f)), 0u, tag);
    bar_sync(2, 128);
    mbar_wait_b(BAR(B_STG), 0);
    if (tid < 96) {
      s1 = 0.f; s2 = 0.f;
      #pragma unroll 1
      for (int r = 0; r < 16; r++) {
        const uint32_t a = sb + STG + (r >> 3) * 24576 + wq * 8192 + (r & 7) * 128 + ((lane * 4) ^ ((r & 7) << 4));
        #pragma unroll
        for (int e = 0; e < 8; e++) { uint32_t v = lds32(a + e * 1024); s1 += bf_lo(v); s2 += bf_hi(v); }
      }
      st_ll(&P.g->csP[bp][bi][tid], UI(s1), UI(s2), 0u, tag);
      s1 = 0.f; s2 = 0.f;
      #pragma unroll 1
      for (int q = 0; q < 8; q += 2) {
        uint4 a, b; poll_ll2(&P.g->csP[bp][q][tid], &P.g->csP[bp][q + 1][tid], 0xffffffffu, tag, a, b);
        s1 += FL(a.x) + FL(b.x); s2 += FL(a.y) + FL(b.y);
      }
      const uint32_t hi = pack_bf16(-s1, -s2);
      sts32(sb + CS + (tid >> 2) * 32 + (tid & 3) * 4, hi);
      sts32(sb + CS + (tid >> 2) * 32 + (tid & 3) * 4 + 16, pack_bf16(-s1 - bf_lo(hi), -s2 - bf_hi(hi)));
    }
    fence_async_smem();
  }
  int idx;
  #pragma unroll 1
  for (int L = 0; L < 2; L++) {
    FRESH();
    {
      sts32(sb + INFO, idx);
      bar_sync(2, 128);
    }
    const uint4 fix = lds128(sb + PATCH + 128 + (lane & 4) * 32 + (wq >> 1) * 64 + (lane & 3) * 16);
    warp_signal(BAR(B_PAR));
    PROFX(tid == 0, L ? 23 : 17);
    mbar_wait_b(BAR(B_KVFULL + wq), L);
    if ((idx >> 7) == bi * 2 - 1 - (wq & 1)) {
      if (lane < 8) sts128(sb + ((wq >> 1) ? KVB : KVA) + ((idx >> 6) & 3) * 8192 + (lane >> 2) * 4096 + (idx & 63) * 64 + (((lane ^ (idx >> 1)) & 3) << 4), fix);
      fence_async_smem();
    }
    bar_arrive(4 + wq, 160); bar_arrive(8 + wq, 160);
    FRESH();
    mbar_wait_b(BAR(B_OFREE), L);
    #define blk (bi * 2 + (bid & 1))
    if (tid < 32 + BCP) st_ll(tid < 32 ? &P.g->row[blk][bc * 32 + tid] : &P.g->best[bc][tid - 32][blk], 0u, 0u, 0u, 0u);
    mbar_wait_b(BAR(B_XRDY), L);
    PROFX(tid == 0, 37 + L * 16);
    __nanosleep(SD_T);
    FRESH();
    {
      float s1 = 0.f, s2 = 0.f, d = 0.f;
      #pragma unroll 1
      for (int q = 0; q < 8; q += 4) { const float4 v = poll_sum4(&P.g->statP[q][blk * 128 + tid], 2048, tag); s1 += v.x; s2 += v.y; d += v.z; }
      PROFX(tid == 0, 39 + L * 16);
      uint4 a = lds128(sb + INFO2), b, c;
      float m = s1 * (1.f / 1024.f), var = fmaxf(fmaf(-m, m, s2 * (1.f / 1024.f)), 0.f), rs = rsqrtf(var + LN_EPS);
      uint32_t key = UI(fmaf(-m, (FL(a.x) + FL(a.y)) + (FL(a.z) + FL(a.w)), d) * rs);
      key ^= (uint32_t)((int)key >> 31) | 0x80000000u;
      uint32_t win = __ballot_sync(0xffffffffu, key == __reduce_max_sync(0xffffffffu, key));
      if (lane == __ffs(win) - 1) sts128(sb + RED + wq * 16, make_uint4(key, UI(m), UI(rs), (tag << 11) | (uint32_t)(blk * 128 + tid)));
      if (L) sts64f(sb + PAR + tid * 8, 1.f + rs, -m * rs);
      else if ((tid >> 4) == bc) st_ll(&P.g->statF[blk * 128 + tid], UI(m), UI(var), 0u, tag + 1);
      bar_sync(2, 128);
      if (wq < 2) a = best4(sb + RED);
      if (wq == 1 && lane < BCP) st_ll(&P.g->best[bc][lane][blk], a.x, a.y, a.z, a.w);
      if (wq == 0) {
        mbar_wait(BAR(B_XRDY + 1), L); mbar_wait(BAR(B_XRDY + 3), L);
        float2 v = lds64f(sb + (lane >> 4) * 32768 + (a.w & 255) * 128 + (((lane & 15) * 8) ^ ((a.w & 7) << 4)));
        st_ll(&P.g->row[blk][bc * 32 + lane], UI(v.x), UI(v.y), 0u, tag);
        __syncwarp();
        if (lane < 2 + 2 * L) mbar_arrive(L ? BAR(B_PAR) : BAR(B_XFREE + lane));
      }
      PROFX(tid == 0, 18 + L * 6);
      FRESH();
      a = poll_ll(&P.g->best[bc][blk & (BCP - 1)][lane & 15], 0xfffff800u, tag << 11);
      win = __ffs(__ballot_sync(0xffffffffu, a.x == __reduce_max_sync(0xffffffffu, a.x))) - 1;
      idx = __shfl_sync(0xffffffffu, a.w, win) & 2047;
      PROFX(tid == 0, 19 + L * 6);
      poll_ll2(&P.g->row[win][tid], &P.g->row[win][tid + 128], 0xffffffffu, tag, c, b);
      c.z = b.x; c.w = b.y;
      a.x = __shfl_sync(0xffffffffu, a.x, win); a.y = __shfl_sync(0xffffffffu, a.y, win); a.z = __shfl_sync(0xffffffffu, a.z, win);
      sts32(sb + INFO2 + 28, idx);
      PROFX(tid == 0, 61 + L);
      b = norm8(c, FL(a.y), FL(a.z));
      if (L) put_bf16(b, sb + HV + tid * 8); else put_f32(b, sb + HV + tid * 16, 2048);
      if ((tid >> 1) == (bid & 63)) {
        sts128(sb + RED + 64 + (tid & 1) * 16, bid < 64 ? make_uint4(c.x, c.y, b.x, b.y) : make_uint4(c.z, c.w, b.z, b.w));
        sts32(sb + RED + 96, a.x);
      }
      bar_sync(2 + L, 128 + L * 256);
      if (L) {
        const int r0 = blk * 128 + (tid >> 4);
        uint32_t src = sb + ((tid >> 3) & 1) * 32768 + (r0 & 255) * 128 + (((tid ^ r0) & 7) << 4);
        uint4* dst = (uint4*)(P.out + (size_t)r0 * 1024 + bc * 128) + (tid & 15);
        #pragma unroll 4
        for (int it = 0; it < 16; it++) { uint4 v = lds128(src + it * 1024); if (idx - r0 != it * 8) dst[it * 1024] = v; }
      }
    }
    #pragma unroll 1
    for (int st = 2 * L; st < 2; st++) {
      FRESH();
      float a[8] = {0.f, 0.f, 0.f, 0.f, 0.f, 0.f, 0.f, 0.f};
      if (fid < 112) {
        uint32_t ha = st ? sb + RED + 768 + wq * 4 : sb + HV + ((wq & 1) * 64 + (lane >> 2)) * 4;
        uint32_t ph = st ? 0x1cu : 0x171u, bar = st ? BAR(B_STG + 2) : BAR(B_STG);
        uint32_t wa = sb + STG + wq * 4096 + (st ? 32768 + lane * 16 : (lane ^ (lane >> 3)) * 16);
        const uint32_t hx = st ? 256 : 512;
        const bool lead = lane == 0;
        uint4 vc = make_uint4(0u, 0u, 0u, 0u); float hc = 0.f;
        #pragma unroll 1
        do {
          mbar_wait(bar, ph & 1);
          PROFX(lead && threadIdx.x == 256 && st == 0 && (ph > 255 || ph < 4), 40 - 23 + __clz(ph));
          #pragma unroll
          for (int n = 0; n < 8; n++) { const uint4 v = lds128(wa + n * 512); const float h = lds32f(ha + n * 32); fma8(a, vc, hc); vc = v; hc = h; }
          __syncwarp();
          if (lead) mbar_arrive(bar - 8 * (B_STG - B_STGE));
          const bool wrap = bar == BAR(B_STG + 2);
          bar += wrap ? -16 : 8; wa += wrap ? -32768 : 16384; ha += hx;
          ph >>= 1;
        } while (ph != 1);
        fma8(a, vc, hc);
      }
      FRESH();
      uint4* const yp = &P.g->yP[tid & ~1][min(fid, 111)][tid & 1];
      if (st == 0) {
        sts32f(sb + RED + 256 + wq * 128 + ((lane & 3) * 8 + (lane >> 2)) * 4, fold8(a));
        bar_sync(2, 128);
        const uint32_t d = sb + RED + 256 + lane * 4;
        sts32f(sb + RED + 768 + lane * 32 + wq * 4, swiglu(lds32f(d) + lds32f(d + 128), lds32f(d + 256) + lds32f(d + 384)));
        if (fid < 112) { st_ll(yp, 0u, 0u, 0u, 0u); st_ll(yp + 224, 0u, 0u, 0u, 0u); }
        else { const uint32_t t0 = clk(); while (clk() - t0 < IDLE_T) __nanosleep(200); }
        __syncwarp();
        PROFX(tid == 0, 20);
      } else if (fid < 112) {
        const bool odd = lane & 1;
        const uint32_t t8 = lds32(sb + INFO + 12);
        #pragma unroll
        for (int e = 0; e < 4; e++) { float z = __shfl_xor_sync(0xffffffffu, odd ? a[e] : a[4 + e], 1); if (odd) a[e] = z; else a[4 + e] = z; }
        st_ll(yp, UI(a[0]), UI(a[1]), UI(a[2]), (UI(a[3]) & ~255u) | t8);
        st_ll(yp + 224, UI(a[4]), UI(a[5]), UI(a[6]), (UI(a[7]) & ~255u) | t8);
        PROFX(tid == 0, 21);
      }
    }
    {
      const uint32_t t8 = lds32(sb + INFO + 12) + L;
      const uint4* src = &P.g->yP[bid][0][min(tid, 111)];
      uint4 v0 = ld_ll(src), v1 = ld_ll(src + 112);
      uint4* dst = L ? (uint4*)(P.out + (size_t)idx * 1024 + bid * 8 + (tid & 1) * 4) : &P.g->x2[(tid >> 1) & (XCP - 1)][2 * bid + (tid & 1)];
      if (!L && (tid < 2 * XCP || tid >= 64)) st_ll(tid < 64 ? dst : &P.g->patch[bid][tid - 64], 0u, 0u, 0u, 0u);
      const uint32_t k = lds32(sb + RED + 96);
      const float sg = sigmoidf(FL(k ^ (~(uint32_t)((int)k >> 31) | 0x80000000u)));
      for (int it = 0; !__all_sync(0xffffffffu, ((v0.w ^ t8) & 255u) == 0 && ((v1.w ^ t8) & 255u) == 0); it++) { v0 = ld_ll(src); v1 = ld_ll(src + 112); if (it > SPIN_MAX) __trap(); }
      float y0 = FL(v0.x) + FL(v1.x), y1 = FL(v0.y) + FL(v1.y), y2 = FL(v0.z) + FL(v1.z), y3 = FL((v0.w & ~255u) | 128u) + FL((v1.w & ~255u) | 128u);
      const bool u = lane & 2, v = lane & 4;
      y0 = (u ? y2 : y0) + __shfl_xor_sync(0xffffffffu, u ? y0 : y2, 2); y1 = (u ? y3 : y1) + __shfl_xor_sync(0xffffffffu, u ? y1 : y3, 2);
      y0 = (v ? y1 : y0) + __shfl_xor_sync(0xffffffffu, v ? y0 : y1, 4);
      y0 += __shfl_xor_sync(0xffffffffu, y0, 8);
      y1 = __shfl_xor_sync(0xffffffffu, y0, 16);
      if (lane < 8) sts32f(sb + RED + 128 + wq * 32 + (lane & 1) * 16 + (lane & 2) * 4 + (lane & 4), wq < 3 ? y0 + y1 : y0);
      bar_sync(2, 128);
      if (tid < (L ? 2 : 2 * XCP)) {
        const uint32_t d = sb + RED + (tid & 1) * 16;
        const uint4 xh = lds128(d + 64), a = lds128(d + 128), b = lds128(d + 160), c = lds128(d + 192), e = lds128(d + 224);
        #define FIN(f, z) fmaf((FL(a.f) + FL(b.f)) + (FL(c.f) + FL(e.f)), sg, z)
        const uint32_t r0 = pack_bf16(FIN(x, bf_lo(xh.x) + bf_lo(xh.z)), FIN(y, bf_hi(xh.x) + bf_hi(xh.z))), r1 = pack_bf16(FIN(z, bf_lo(xh.y) + bf_lo(xh.w)), FIN(w, bf_hi(xh.y) + bf_hi(xh.w)));
        #undef FIN
        if (L) *(uint2*)dst = make_uint2(r0, r1); else st_ll(dst, r0, r1, 0u, tag + 1);
      }
      PROFW(L && tid == 0, 28);
    }
    if (L == 0) {
      PROFX(tid == 0, 22);
      FRESH();
      mbar_wait(BAR(B_STG), 1); mbar_wait(BAR(B_STG + 1), 0); mbar_wait(BAR(B_STG + 2), 0);
      const uint32_t bd = (64 + (HV >> 4) + uni(bid & 3) * 32) | 0x10000u;
      uint4 x, y; poll_ll2(&P.g->x2[bid * XCP >> 7][tid], &P.g->x2[bid * XCP >> 7][tid + 128], 0xffffffffu, tag + 1, x, y);
      x.z = y.x; x.w = y.y;
      put_bf16(x, sb + HV + tid * 8);
      bar_sync(2, 128);
      PROFX(tid == 0, 30);
      float d0[4] = {0.f, 0.f, 0.f, 0.f}, d1[4] = {0.f, 0.f, 0.f, 0.f}, d2[4] = {0.f, 0.f, 0.f, 0.f};
      #pragma unroll 1
      for (int ks = 0; ks < 8; ks++) {
        const uint32_t ad = (64 + (STG >> 4) + ks * 128) | (64u << 16);
        wg_fence();
        wgmma_ss_n8<0, 1>(d0, mkd<HI64>(ad), mkd<8>(bd + ks * 4), 1);
        wgmma_ss_n8<0, 1>(d1, mkd<HI64>(ad + 1024), mkd<8>(bd + ks * 4), 1);
        wgmma_ss_n8<0, 1>(d2, mkd<HI64>(ad + 2048), mkd<8>(bd + ks * 4), 1);
        wg_commit();
      }
      if (tid == 0) mbar_arrive(BAR(B_PW));
      uint4* dst = &P.g->patch[bid][(wq & 1) * 32 + (lane >> 2) * 2 + (wq >> 1)];
      wg_wait<0>(); keep(d0); keep(d1); keep(d2);
      if ((lane & 3) == (wq >> 1)) { st_ll(dst, UI(d0[0]), UI(d1[0]), UI(d2[0]), tag + 1); st_ll(dst + 16, UI(d0[2]), UI(d1[2]), UI(d2[2]), tag + 1); }
      PROFX(tid == 0, 31);
      if ((unsigned)(bi - (idx >> 8)) < 2u) {
        if (wq == (bc & 3)) sts64f(sb + X2SEG + lane * 8, FL(bc < 4 ? x.x : x.z), FL(bc < 4 ? x.y : x.w));
        float s1 = 0.f, s2 = 0.f;
        sum8(x, s1, s2);
        #pragma unroll
        for (int o = 16; o; o >>= 1) { s1 += __shfl_xor_sync(0xffffffffu, s1, o); s2 += __shfl_xor_sync(0xffffffffu, s2, o); }
        sts64f(sb + RED + wq * 8, s1, s2);
        bar_sync(2, 128);
        x = lds128(sb + RED); y = lds128(sb + RED + 16);
        const float m = ((FL(x.x) + FL(x.z)) + (FL(y.x) + FL(y.z))) * (1.f / 1024.f);
        const float rs = rsqrtf(fmaxf(fmaf(-m, m, ((FL(x.y) + FL(x.w)) + (FL(y.y) + FL(y.w))) * (1.f / 1024.f)), 0.f) + LN_EPS);
        const uint32_t ca = sb + CS + (tid >> 4) * 32 + (tid & 1) * 16 + (tid & 14);
        const float cq = FL(lds16(ca) << 16) * m, ck = FL(lds16(ca + 256) << 16) * m, cv = FL(lds16(ca + 512) << 16) * m;
        const float4 z = poll_sum4(&P.g->patch[bp * 8 + (tid >> 6) * 4][tid & 63], 64, tag + 1);
        float q = z.x + cq, k = z.y + ck, v = z.z + cv;
        q += __shfl_xor_sync(0xffffffffu, q, 1); k += __shfl_xor_sync(0xffffffffu, k, 1); v += __shfl_xor_sync(0xffffffffu, v, 1);
        const uint32_t d = sb + PATCH + (tid & ~1), kv = pack_bf16(k * rs, v * rs);
        sts16(d, pack_bf16(q * (rs * QSCALE), 0.f)); sts16(d + 128, kv); sts16(d + 256, kv >> 16);
      }
    }
  }
  if (bid == 0 && tid == 0) P.g->epoch = lds32(sb + INFO2 + 16) + 1;
  #undef blk
  #undef bid
  #undef fid
  #undef bi
  #undef bp
  #undef bc
  #undef FRESH
  #undef lane
  #undef wq
}

__global__ void __cluster_dims__(2, 1, 1) __launch_bounds__(512, 1) fused_kernel(const __grid_constant__ Params P) {
  extern __shared__ __align__(1024) uint8_t smem_raw[];
  const uint32_t sb = smem_u32(smem_raw);
  PROFT(threadIdx.x == 0, 0);
  if (threadIdx.x >= 416 && threadIdx.x < 416 + 80) {
    const int e = threadIdx.x - 416;
    asm volatile("prefetch.global.L2 [%0];" :: "l"(e < 32 ? P.x0 + (blockIdx.x * 16 + e / 2) * 1024 + (e % 2) * 32 : P.wqkv + (blockIdx.x * 48 + e - 32) * 32));
  }
  if (threadIdx.x < 32) { if (elect()) {
    for (int s = 0; s < 3; s++) mbar_init(BAR(B_FULLQ + s), 1);
    asm volatile("fence.mbarrier_init.release.cluster;" ::: "memory");
    const int bid0 = BID;
    #pragma unroll 1
    for (int s = 0; s < 3; s++) {
      mbar_expect_tx(BAR(B_FULLQ + s), 57344);
      tma_2d(sb + qa_off(s), &P.mX, s * 64, (bid0 >> 4) * 256, BAR(B_FULLQ + s));
      tma_3d(sb + qb_off(s), &P.mWq, (bid0 & 15) * 64, s * 64, 0, BAR(B_FULLQ + s));
    }
    if ((sb & 0x3FFFFu) != 1024) __trap();
  } } else if (threadIdx.x == 480) {
    asm volatile("prefetch.tensormap [%0];" :: "l"(&P.mWq) : "memory");
  } else if (threadIdx.x >= 32 && !(threadIdx.x & 28) && (threadIdx.x >> 3) + (threadIdx.x & 3) <= B_COUNT + 2) {
    int b = (threadIdx.x >> 3) + (threadIdx.x & 3) - 1;
    if (b >= B_COUNT) b += B_ROW - B_COUNT;
    const uint32_t cnt = b < B_XFREE ? (b == B_OFREE ? 1 : 2) : (b < B_KVRDY ? 3 : (b < B_KVFULL || b == B_PAR ? 4 : (b == B_PFREE ? 2 : 1)));
    mbar_init(BAR(b), cnt);
    asm volatile("fence.mbarrier_init.release.cluster;" ::: "memory");
  }
  __syncthreads();
  asm volatile("barrier.cluster.arrive.relaxed.aligned;" ::: "memory");
  const int wg = __shfl_sync(0xffffffffu, threadIdx.x >> 7, 0);
  if (wg < 2) { reg_inc<224>(); consumer(P, sb, wg); }
  else if (wg == 2) { reg_dec<40>(); aux(P, sb); }
  else {
    reg_dec<24>();
    asm volatile("barrier.cluster.wait.aligned;" ::: "memory");
    const int w = __shfl_sync(0xffffffffu, (threadIdx.x >> 5) & 3, 0);
    if (w == 0) loader(P, sb);
    else if (w < 3) storer(P, sb, w - 1);
    else if (elect()) stager(P, sb);
  }
}

typedef CUresult (*EncFn)(CUtensorMap*, CUtensorMapDataType, cuuint32_t, void*, const cuuint64_t*, const cuuint64_t*, const cuuint32_t*, const cuuint32_t*,
                          CUtensorMapInterleave, CUtensorMapSwizzle, CUtensorMapL2promotion, CUtensorMapFloatOOBfill);
static void mk_map(EncFn enc, CUtensorMap* m, const void* ptr, int rank, const cuuint64_t* dims, const cuuint64_t* strides, const cuuint32_t* box,
                   CUtensorMapSwizzle sw, CUtensorMapL2promotion pr) {
  cuuint32_t es[5] = {1, 1, 1, 1, 1};
  enc(m, CU_TENSOR_MAP_DATA_TYPE_BFLOAT16, rank, (void*)ptr, dims, strides, box, es, CU_TENSOR_MAP_INTERLEAVE_NONE, sw, pr, CU_TENSOR_MAP_FLOAT_OOB_FILL_NONE);
}
extern "C" void kernel_launch(void* const* d_in, const int* in_sizes, int n_in, void* d_out, int out_size) {
  (void)in_sizes; (void)n_in; (void)out_size;
  void* fn = nullptr; cudaDriverEntryPointQueryResult q;
  cudaGetDriverEntryPoint("cuTensorMapEncodeTiled", &fn, cudaEnableDefault, &q);
  EncFn enc = (EncFn)fn;
  cudaFuncSetAttribute(fused_kernel, cudaFuncAttributeMaxDynamicSharedMemorySize, SMEM_BYTES);
  Params P;
  const CUtensorMapSwizzle S128 = CU_TENSOR_MAP_SWIZZLE_128B, S64 = CU_TENSOR_MAP_SWIZZLE_64B, S0 = CU_TENSOR_MAP_SWIZZLE_NONE;
  const CUtensorMapL2promotion L256 = CU_TENSOR_MAP_L2_PROMOTION_L2_256B, L128 = CU_TENSOR_MAP_L2_PROMOTION_L2_128B;
  { cuuint64_t d[2] = {1024, 2048}, s[1] = {2048}; cuuint32_t b[2] = {64, 256}, bh[2] = {64, 128};
    mk_map(enc, &P.mX, d_in[0], 2, d, s, b, S128, L256); mk_map(enc, &P.mXh, d_in[0], 2, d, s, bh, S128, L256); }
  { cuuint64_t d[3] = {1024, 1024, 3}, s[2] = {6144, 2048}; cuuint32_t b[3] = {64, 64, 3}; mk_map(enc, &P.mWq, d_in[1], 3, d, s, b, S128, L256); }
  { cuuint64_t d[5] = {64, 32, 2, 16, 16}, s[4] = {2048, 65536, 131072, 128}; cuuint32_t b[5] = {64, 32, 1, 2, 2}; mk_map(enc, &P.mWo, d_in[2], 5, d, s, b, S128, L256); }
  { cuuint64_t d[2] = {3584, 1024}, s[1] = {7168}; cuuint32_t b[2] = {32, 128};
    mk_map(enc, &P.mWg, d_in[5], 2, d, s, b, S64, L128); mk_map(enc, &P.mWu, d_in[6], 2, d, s, b, S64, L128); }
  { cuuint64_t d[2] = {3072, 1024}, s[1] = {6144}; cuuint32_t b[2] = {32, 256}; mk_map(enc, &P.mWp, d_in[1], 2, d, s, b, S64, L128); }
  { cuuint64_t d[3] = {256, 3584, 4}, s[2] = {2048, 512}; cuuint32_t b[3] = {256, 8, 4}; mk_map(enc, &P.mWd, d_in[7], 3, d, s, b, S0, L128); }
  P.x0 = (const bf16*)d_in[0]; P.wqkv = (const bf16*)d_in[1]; P.wo = (const bf16*)d_in[2]; P.wr = (const bf16*)d_in[4]; P.wg = (const bf16*)d_in[5]; P.wu = (const bf16*)d_in[6]; P.wd = (const bf16*)d_in[7];
  P.out = (bf16*)d_out;
  cudaGetSymbolAddress((void**)&P.g, g_scr);
  for (int b = 0; b < 128; b++) {
    int j = b >> 1, quad = j < 4 ? 0 : (j < 36 ? 1 + (j - 4) % 8 : 9 + (j - 36) % 7), pos = j < 4 ? j : (j < 36 ? (j - 4) / 8 : (j - 36) / 7);
    int bid = ((quad >> 2) * 2 + (pos >> 1)) * 16 + ((quad & 3) * 2 + (pos & 1)) * 2 + (b & 1);
    int e = pos * 2 + (b & 1), fid = e < 7 ? quad * 7 + e : 112 + quad;
    P.map[b] = bid | fid << 8;
  }
  fused_kernel<<<128, 512, SMEM_BYTES>>>(P);
}
```

```cpp
#include <cuda_runtime.h>
#include <cuda_bf16.h>
#include <cuda.h>
#include <stdint.h>
#include <stddef.h>
typedef __nv_bfloat16 bf16;

template<int TB, int TA = 0> __device__ __forceinline__ void wgmma_ss_n192(float (&d)[96], uint64_t da, uint64_t db, int scale_d) {
  asm volatile("{\n.reg .pred p;\nsetp.ne.b32 p, %98, 0;\n"
    "wgmma.mma_async.sync.aligned.m64n192k16.f32.bf16.bf16 {%0, %1, %2, %3, %4, %5, %6, %7, %8, %9, %10, %11, %12, %13, %14, %15, %16, %17, %18, %19, %20, %21, %22, %23, %24, %25, %26, %27, %28, %29, %30, %31, %32, %33, %34, %35, %36, %37, %38, %39, %40, %41, %42, %43, %44, %45, %46, %47, %48, %49, %50, %51, %52, %53, %54, %55, %56, %57, %58, %59, %60, %61, %62, %63, %64, %65, %66, %67, %68, %69, %70, %71, %72, %73, %74, %75, %76, %77, %78, %79, %80, %81, %82, %83, %84, %85, %86, %87, %88, %89, %90, %91, %92, %93, %94, %95}, %96, %97, p, 1, 1, %100, %99;\n}\n"
    : "+f"(d[0]), "+f"(d[1]), "+f"(d[2]), "+f"(d[3]), "+f"(d[4]), "+f"(d[5]), "+f"(d[6]), "+f"(d[7]), "+f"(d[8]), "+f"(d[9]), "+f"(d[10]), "+f"(d[11]), "+f"(d[12]), "+f"(d[13]), "+f"(d[14]), "+f"(d[15]), "+f"(d[16]), "+f"(d[17]), "+f"(d[18]), "+f"(d[19]), "+f"(d[20]), "+f"(d[21]), "+f"(d[22]), "+f"(d[23]), "+f"(d[24]), "+f"(d[25]), "+f"(d[26]), "+f"(d[27]), "+f"(d[28]), "+f"(d[29]), "+f"(d[30]), "+f"(d[31]), "+f"(d[32]), "+f"(d[33]), "+f"(d[34]), "+f"(d[35]), "+f"(d[36]), "+f"(d[37]), "+f"(d[38]), "+f"(d[39]), "+f"(d[40]), "+f"(d[41]), "+f"(d[42]), "+f"(d[43]), "+f"(d[44]), "+f"(d[45]), "+f"(d[46]), "+f"(d[47]), "+f"(d[48]), "+f"(d[49]), "+f"(d[50]), "+f"(d[51]), "+f"(d[52]), "+f"(d[53]), "+f"(d[54]), "+f"(d[55]), "+f"(d[56]), "+f"(d[57]), "+f"(d[58]), "+f"(d[59]), "+f"(d[60]), "+f"(d[61]), "+f"(d[62]), "+f"(d[63]), "+f"(d[64]), "+f"(d[65]), "+f"(d[66]), "+f"(d[67]), "+f"(d[68]), "+f"(d[69]), "+f"(d[70]), "+f"(d[71]), "+f"(d[72]), "+f"(d[73]), "+f"(d[74]), "+f"(d[75]), "+f"(d[76]), "+f"(d[77]), "+f"(d[78]), "+f"(d[79]), "+f"(d[80]), "+f"(d[81]), "+f"(d[82]), "+f"(d[83]), "+f"(d[84]), "+f"(d[85]), "+f"(d[86]), "+f"(d[87]), "+f"(d[88]), "+f"(d[89]), "+f"(d[90]), "+f"(d[91]), "+f"(d[92]), "+f"(d[93]), "+f"(d[94]), "+f"(d[95])
    : "l"(da), "l"(db), "r"(scale_d), "n"(TB), "n"(TA));
}

template<int TB> __device__ __forceinline__ void wgmma_rs_n192(float (&d)[96], uint32_t a0, uint32_t a1, uint32_t a2, uint32_t a3, uint64_t db, int scale_d) {
  asm volatile("{\n.reg .pred p;\nsetp.ne.b32 p, %101, 0;\n"
    "wgmma.mma_async.sync.aligned.m64n192k16.f32.bf16.bf16 {%0, %1, %2, %3, %4, %5, %6, %7, %8, %9, %10, %11, %12, %13, %14, %15, %16, %17, %18, %19, %20, %21, %22, %23, %24, %25, %26, %27, %28, %29, %30, %31, %32, %33, %34, %35, %36, %37, %38, %39, %40, %41, %42, %43, %44, %45, %46, %47, %48, %49, %50, %51, %52, %53, %54, %55, %56, %57, %58, %59, %60, %61, %62, %63, %64, %65, %66, %67, %68, %69, %70, %71, %72, %73, %74, %75, %76, %77, %78, %79, %80, %81, %82, %83, %84, %85, %86, %87, %88, %89, %90, %91, %92, %93, %94, %95}, {%96, %97, %98, %99}, %100, p, 1, 1, %102;\n}\n"
    : "+f"(d[0]), "+f"(d[1]), "+f"(d[2]), "+f"(d[3]), "+f"(d[4]), "+f"(d[5]), "+f"(d[6]), "+f"(d[7]), "+f"(d[8]), "+f"(d[9]), "+f"(d[10]), "+f"(d[11]), "+f"(d[12]), "+f"(d[13]), "+f"(d[14]), "+f"(d[15]), "+f"(d[16]), "+f"(d[17]), "+f"(d[18]), "+f"(d[19]), "+f"(d[20]), "+f"(d[21]), "+f"(d[22]), "+f"(d[23]), "+f"(d[24]), "+f"(d[25]), "+f"(d[26]), "+f"(d[27]), "+f"(d[28]), "+f"(d[29]), "+f"(d[30]), "+f"(d[31]), "+f"(d[32]), "+f"(d[33]), "+f"(d[34]), "+f"(d[35]), "+f"(d[36]), "+f"(d[37]), "+f"(d[38]), "+f"(d[39]), "+f"(d[40]), "+f"(d[41]), "+f"(d[42]), "+f"(d[43]), "+f"(d[44]), "+f"(d[45]), "+f"(d[46]), "+f"(d[47]), "+f"(d[48]), "+f"(d[49]), "+f"(d[50]), "+f"(d[51]), "+f"(d[52]), "+f"(d[53]), "+f"(d[54]), "+f"(d[55]), "+f"(d[56]), "+f"(d[57]), "+f"(d[58]), "+f"(d[59]), "+f"(d[60]), "+f"(d[61]), "+f"(d[62]), "+f"(d[63]), "+f"(d[64]), "+f"(d[65]), "+f"(d[66]), "+f"(d[67]), "+f"(d[68]), "+f"(d[69]), "+f"(d[70]), "+f"(d[71]), "+f"(d[72]), "+f"(d[73]), "+f"(d[74]), "+f"(d[75]), "+f"(d[76]), "+f"(d[77]), "+f"(d[78]), "+f"(d[79]), "+f"(d[80]), "+f"(d[81]), "+f"(d[82]), "+f"(d[83]), "+f"(d[84]), "+f"(d[85]), "+f"(d[86]), "+f"(d[87]), "+f"(d[88]), "+f"(d[89]), "+f"(d[90]), "+f"(d[91]), "+f"(d[92]), "+f"(d[93]), "+f"(d[94]), "+f"(d[95])
    : "r"(a0), "r"(a1), "r"(a2), "r"(a3), "l"(db), "r"(scale_d), "n"(TB));
}

template<int TB, int TA = 0> __device__ __forceinline__ void wgmma_ss_n128(float (&d)[64], uint64_t da, uint64_t db, int scale_d) {
  asm volatile("{\n.reg .pred p;\nsetp.ne.b32 p, %66, 0;\n"
    "wgmma.mma_async.sync.aligned.m64n128k16.f32.bf16.bf16 {%0, %1, %2, %3, %4, %5, %6, %7, %8, %9, %10, %11, %12, %13, %14, %15, %16, %17, %18, %19, %20, %21, %22, %23, %24, %25, %26, %27, %28, %29, %30, %31, %32, %33, %34, %35, %36, %37, %38, %39, %40, %41, %42, %43, %44, %45, %46, %47, %48, %49, %50, %51, %52, %53, %54, %55, %56, %57, %58, %59, %60, %61, %62, %63}, %64, %65, p, 1, 1, %68, %67;\n}\n"
    : "+f"(d[0]), "+f"(d[1]), "+f"(d[2]), "+f"(d[3]), "+f"(d[4]), "+f"(d[5]), "+f"(d[6]), "+f"(d[7]), "+f"(d[8]), "+f"(d[9]), "+f"(d[10]), "+f"(d[11]), "+f"(d[12]), "+f"(d[13]), "+f"(d[14]), "+f"(d[15]), "+f"(d[16]), "+f"(d[17]), "+f"(d[18]), "+f"(d[19]), "+f"(d[20]), "+f"(d[21]), "+f"(d[22]), "+f"(d[23]), "+f"(d[24]), "+f"(d[25]), "+f"(d[26]), "+f"(d[27]), "+f"(d[28]), "+f"(d[29]), "+f"(d[30]), "+f"(d[31]), "+f"(d[32]), "+f"(d[33]), "+f"(d[34]), "+f"(d[35]), "+f"(d[36]), "+f"(d[37]), "+f"(d[38]), "+f"(d[39]), "+f"(d[40]), "+f"(d[41]), "+f"(d[42]), "+f"(d[43]), "+f"(d[44]), "+f"(d[45]), "+f"(d[46]), "+f"(d[47]), "+f"(d[48]), "+f"(d[49]), "+f"(d[50]), "+f"(d[51]), "+f"(d[52]), "+f"(d[53]), "+f"(d[54]), "+f"(d[55]), "+f"(d[56]), "+f"(d[57]), "+f"(d[58]), "+f"(d[59]), "+f"(d[60]), "+f"(d[61]), "+f"(d[62]), "+f"(d[63])
    : "l"(da), "l"(db), "r"(scale_d), "n"(TB), "n"(TA));
}

template<int TB, int TA = 0> __device__ __forceinline__ void wgmma_ss_n64(float (&d)[32], uint64_t da, uint64_t db, int scale_d) {
  asm volatile("{\n.reg .pred p;\nsetp.ne.b32 p, %34, 0;\n"
    "wgmma.mma_async.sync.aligned.m64n64k16.f32.bf16.bf16 {%0, %1, %2, %3, %4, %5, %6, %7, %8, %9, %10, %11, %12, %13, %14, %15, %16, %17, %18, %19, %20, %21, %22, %23, %24, %25, %26, %27, %28, %29, %30, %31}, %32, %33, p, 1, 1, %36, %35;\n}\n"
    : "+f"(d[0]), "+f"(d[1]), "+f"(d[2]), "+f"(d[3]), "+f"(d[4]), "+f"(d[5]), "+f"(d[6]), "+f"(d[7]), "+f"(d[8]), "+f"(d[9]), "+f"(d[10]), "+f"(d[11]), "+f"(d[12]), "+f"(d[13]), "+f"(d[14]), "+f"(d[15]), "+f"(d[16]), "+f"(d[17]), "+f"(d[18]), "+f"(d[19]), "+f"(d[20]), "+f"(d[21]), "+f"(d[22]), "+f"(d[23]), "+f"(d[24]), "+f"(d[25]), "+f"(d[26]), "+f"(d[27]), "+f"(d[28]), "+f"(d[29]), "+f"(d[30]), "+f"(d[31])
    : "l"(da), "l"(db), "r"(scale_d), "n"(TB), "n"(TA));
}

template<int TB, int TA = 0> __device__ __forceinline__ void wgmma_ss_n8(float (&d)[4], uint64_t da, uint64_t db, int scale_d) {
  asm volatile("{\n.reg .pred p;\nsetp.ne.b32 p, %6, 0;\n"
    "wgmma.mma_async.sync.aligned.m64n8k16.f32.bf16.bf16 {%0, %1, %2, %3}, %4, %5, p, 1, 1, %8, %7;\n}\n"
    : "+f"(d[0]), "+f"(d[1]), "+f"(d[2]), "+f"(d[3])
    : "l"(da), "l"(db), "r"(scale_d), "n"(TB), "n"(TA));
}

template<int TB> __device__ __forceinline__ void wgmma_rs_n40(float (&d)[20], uint32_t a0, uint32_t a1, uint32_t a2, uint32_t a3, uint64_t db, int scale_d) {
  asm volatile("{\n.reg .pred p;\nsetp.ne.b32 p, %25, 0;\n"
    "wgmma.mma_async.sync.aligned.m64n40k16.f32.bf16.bf16 {%0, %1, %2, %3, %4, %5, %6, %7, %8, %9, %10, %11, %12, %13, %14, %15, %16, %17, %18, %19}, {%20, %21, %22, %23}, %24, p, 1, 1, %26;\n}\n"
    : "+f"(d[0]), "+f"(d[1]), "+f"(d[2]), "+f"(d[3]), "+f"(d[4]), "+f"(d[5]), "+f"(d[6]), "+f"(d[7]), "+f"(d[8]), "+f"(d[9]), "+f"(d[10]), "+f"(d[11]), "+f"(d[12]), "+f"(d[13]), "+f"(d[14]), "+f"(d[15]), "+f"(d[16]), "+f"(d[17]), "+f"(d[18]), "+f"(d[19])
    : "r"(a0), "r"(a1), "r"(a2), "r"(a3), "l"(db), "r"(scale_d), "n"(TB));
}

#define DEVI __device__ __forceinline__
DEVI uint32_t smem_u32(const void* p) { return (uint32_t)__cvta_generic_to_shared(p); }
DEVI void mbar_init(uint32_t bar, uint32_t cnt) { asm volatile("mbarrier.init.shared::cta.b64 [%0], %1;" :: "r"(bar), "r"(cnt)); }
DEVI void mbar_expect_tx(uint32_t bar, uint32_t bytes) { asm volatile("mbarrier.arrive.expect_tx.shared::cta.b64 _, [%0], %1;" :: "r"(bar), "r"(bytes) : "memory"); }
DEVI void mbar_arrive(uint32_t bar) { asm volatile("mbarrier.arrive.shared::cta.b64 _, [%0];" :: "r"(bar) : "memory"); }
DEVI void mbar_arrive_peer(uint32_t bar) {
  asm volatile("{\n.reg .b32 ra;\nmapa.shared::cluster.u32 ra, %0, %1;\nmbarrier.arrive.shared::cluster.b64 _, [ra];\n}" :: "r"(bar), "r"((blockIdx.x & 1) ^ 1) : "memory");
}
DEVI void bulk_s2peer(uint32_t a, uint32_t bytes, uint32_t bar) {
  asm volatile("{\n.reg .b32 ra, rb;\nmapa.shared::cluster.u32 ra, %0, %3;\nmapa.shared::cluster.u32 rb, %2, %3;\n"
               "cp.async.bulk.shared::cluster.shared::cta.mbarrier::complete_tx::bytes [ra], [%0], %1, [rb];\n}"
               :: "r"(a), "r"(bytes), "r"(bar), "r"((blockIdx.x & 1) ^ 1) : "memory");
}
DEVI void mbar_wait(uint32_t bar, uint32_t parity) {
  asm volatile("{\n.reg .pred p;\nLW:\nmbarrier.try_wait.parity.shared::cta.b64 p, [%0], %1;\n@!p bra LW;\n}" :: "r"(bar), "r"(parity) : "memory");
}
DEVI uint32_t mbar_test(uint32_t bar, uint32_t parity) {
  uint32_t r; asm volatile("{\n.reg .pred p;\nmbarrier.test_wait.parity.shared::cta.b64 p, [%1], %2;\nselp.u32 %0, 1, 0, p;\n}" : "=r"(r) : "r"(bar), "r"(parity) : "memory"); return r;
}
DEVI void mbar_wait_b(uint32_t bar, uint32_t parity) {
  asm volatile("{\n.reg .pred p;\n.reg .u32 it;\nmov.u32 it, 0;\nLW:\nmbarrier.try_wait.parity.shared::cta.b64 p, [%0], %1;\n@p bra LD;\n"
               "add.u32 it, it, 1;\nsetp.lt.u32 p, it, 0x1000000;\n@p bra LW;\ntrap;\nLD:\n}" :: "r"(bar), "r"(parity) : "memory");
}
DEVI void tma_2d(uint32_t dst, const CUtensorMap* m, int c0, int c1, uint32_t bar) {
  asm volatile("cp.async.bulk.tensor.2d.shared::cluster.global.mbarrier::complete_tx::bytes [%0], [%1, {%3, %4}], [%2];"
    :: "r"(dst), "l"(m), "r"(bar), "r"(c0), "r"(c1) : "memory");
}
DEVI void tma_3d(uint32_t dst, const CUtensorMap* m, int c0, int c1, int c2, uint32_t bar) {
  asm volatile("cp.async.bulk.tensor.3d.shared::cluster.global.mbarrier::complete_tx::bytes [%0], [%1, {%3, %4, %5}], [%2];"
    :: "r"(dst), "l"(m), "r"(bar), "r"(c0), "r"(c1), "r"(c2) : "memory");
}
#define POL_EF POL_FIRST
constexpr uint64_t POL_FIRST = 0x12F0000000000000ull, POL_NORMAL = 0x1000000000000000ull;
DEVI void tma_2d_h(uint32_t dst, const CUtensorMap* m, int c0, int c1, uint32_t bar, uint64_t pol) {
  asm volatile("cp.async.bulk.tensor.2d.shared::cluster.global.mbarrier::complete_tx::bytes.L2::cache_hint [%0], [%1, {%3, %4}], [%2], %5;"
    :: "r"(dst), "l"(m), "r"(bar), "r"(c0), "r"(c1), "l"(pol) : "memory");
}
DEVI void tma_3d_h(uint32_t dst, const CUtensorMap* m, int c0, int c1, int c2, uint32_t bar, uint64_t pol) {
  asm volatile("cp.async.bulk.tensor.3d.shared::cluster.global.mbarrier::complete_tx::bytes.L2::cache_hint [%0], [%1, {%3, %4, %5}], [%2], %6;"
    :: "r"(dst), "l"(m), "r"(bar), "r"(c0), "r"(c1), "r"(c2), "l"(pol) : "memory");
}
DEVI void bulk_g2s_h(uint32_t s, const void* g, uint32_t bytes, uint32_t bar, uint64_t pol = POL_EF) {
  asm volatile("cp.async.bulk.shared::cluster.global.mbarrier::complete_tx::bytes.L2::cache_hint [%0], [%1], %2, [%3], %4;"
    :: "r"(s), "l"(g), "r"(bytes), "r"(bar), "l"(pol) : "memory");
}
DEVI void tma_5d(uint32_t dst, const CUtensorMap* m, int c0, int c1, int c2, int c3, int c4, uint32_t bar, uint64_t pol) {
  asm volatile("cp.async.bulk.tensor.5d.shared::cluster.global.mbarrier::complete_tx::bytes.L2::cache_hint [%0], [%1, {%3, %4, %5, %6, %7}], [%2], %8;"
    :: "r"(dst), "l"(m), "r"(bar), "r"(c0), "r"(c1), "r"(c2), "r"(c3), "r"(c4), "l"(pol) : "memory");
}
DEVI void tma_prefetch_2d(const CUtensorMap* m, int c0, int c1) {
  asm volatile("cp.async.bulk.prefetch.tensor.2d.L2.global.tile [%0, {%1, %2}];" :: "l"(m), "r"(c0), "r"(c1) : "memory");
}
DEVI void tma_prefetch_3d(const CUtensorMap* m, int c0, int c1, int c2) {
  asm volatile("cp.async.bulk.prefetch.tensor.3d.L2.global.tile [%0, {%1, %2, %3}];" :: "l"(m), "r"(c0), "r"(c1), "r"(c2) : "memory");
}
DEVI void bulk_prefetch(const void* g, uint32_t bytes) { asm volatile("cp.async.bulk.prefetch.L2.global [%0], %1;" :: "l"(g), "r"(bytes) : "memory"); }
DEVI void bulk_g2s(uint32_t s, const void* g, uint32_t bytes, uint32_t bar) {
  asm volatile("cp.async.bulk.shared::cluster.global.mbarrier::complete_tx::bytes [%0], [%1], %2, [%3];" :: "r"(s), "l"(g), "r"(bytes), "r"(bar) : "memory");
}
DEVI void bulk_s2g(void* g, uint32_t s, uint32_t bytes, uint64_t pol = POL_NORMAL) {
  asm volatile("cp.async.bulk.global.shared::cta.bulk_group.L2::cache_hint [%0], [%1], %2, %3;\ncp.async.bulk.commit_group;" :: "l"(g), "r"(s), "r"(bytes), "l"(pol) : "memory");
}
template<int N> DEVI void bulk_wait() { asm volatile("cp.async.bulk.wait_group %0;" :: "n"(N) : "memory"); }
DEVI void fence_async_smem() { asm volatile("fence.proxy.async.shared::cta;" ::: "memory"); }
DEVI void fence_async_glob() { asm volatile("fence.proxy.async.global;" ::: "memory"); }
DEVI unsigned ld_rlx(const unsigned* p) { unsigned v; asm volatile("ld.relaxed.gpu.global.u32 %0, [%1];" : "=r"(v) : "l"(p) : "memory"); return v; }
DEVI void st_rlx(unsigned* p, unsigned v) { asm volatile("st.relaxed.gpu.global.u32 [%0], %1;" :: "l"(p), "r"(v) : "memory"); }
DEVI uint2 ldg_stream(const uint2* p) { uint2 v; asm volatile("ld.global.nc.L1::no_allocate.v2.u32 {%0, %1}, [%2];" : "=r"(v.x), "=r"(v.y) : "l"(p)); return v; }
DEVI void fence_rel() { asm volatile("fence.release.gpu;" ::: "memory"); }
DEVI uint4 ld_ll(const uint4* p) {
  uint4 v;
  asm volatile("{\n.reg .b128 t;\n.reg .b64 a, b;\nld.relaxed.gpu.global.b128 t, [%4];\nmov.b128 {a, b}, t;\nmov.b64 {%0, %1}, a;\nmov.b64 {%2, %3}, b;\n}"
               : "=r"(v.x), "=r"(v.y), "=r"(v.z), "=r"(v.w) : "l"(p) : "memory");
  return v;
}
DEVI void st_ll(uint4* p, uint32_t x, uint32_t y, uint32_t z, uint32_t w) {
  asm volatile("{\n.reg .b128 t;\n.reg .b64 a, b;\nmov.b64 a, {%1, %2};\nmov.b64 b, {%3, %4};\nmov.b128 t, {a, b};\nst.relaxed.gpu.global.b128 [%0], t;\n}"
               :: "l"(p), "r"(x), "r"(y), "r"(z), "r"(w) : "memory");
}
#define SPIN_MAX 0x1000000
#define SD_T 400
DEVI uint4 poll_ll(const uint4* p, uint32_t mask, uint32_t tag) {
  uint4 v; int it = 0;
  do { v = ld_ll(p); if (++it > SPIN_MAX) __trap(); } while (!__all_sync(0xffffffffu, (v.w & mask) == tag));
  return v;
}
DEVI void poll_ll2(const uint4* p, const uint4* q, uint32_t mask, uint32_t tag, uint4& a, uint4& b) {
  int it = 0;
  do { a = ld_ll(p); b = ld_ll(q); if (++it > SPIN_MAX) __trap(); } while (!__all_sync(0xffffffffu, (a.w & mask) == tag && (b.w & mask) == tag));
}
DEVI float4 poll_sum4(const uint4* src, int stride, uint32_t tag) {
  uint4 v0, v1, v2, v3; int it = 0;
  do { v0 = ld_ll(src); v1 = ld_ll(src + stride); v2 = ld_ll(src + 2 * stride); v3 = ld_ll(src + 3 * stride); if (++it > SPIN_MAX) __trap(); }
  while (!__all_sync(0xffffffffu, v0.w == tag && v1.w == tag && v2.w == tag && v3.w == tag));
  #define S4(f) ((__uint_as_float(v0.f) + __uint_as_float(v1.f)) + (__uint_as_float(v2.f) + __uint_as_float(v3.f)))
  return make_float4(S4(x), S4(y), S4(z), 0.f);
  #undef S4
}
DEVI void bar_sync(int id, int n) { asm volatile("bar.sync %0, %1;" :: "r"(id), "r"(n) : "memory"); }
DEVI void bar_arrive(int id, int n) { asm volatile("bar.arrive %0, %1;" :: "r"(id), "r"(n) : "memory"); }
DEVI void wg_fence() { asm volatile("wgmma.fence.sync.aligned;" ::: "memory"); }
DEVI void wg_commit() { asm volatile("wgmma.commit_group.sync.aligned;" ::: "memory"); }
template<int N> DEVI void wg_wait() { asm volatile("wgmma.wait_group.sync.aligned %0;" :: "n"(N) : "memory"); }
template<int N> DEVI void reg_inc() { asm volatile("setmaxnreg.inc.sync.aligned.u32 %0;" :: "n"(N)); }
template<int N> DEVI void reg_dec() { asm volatile("setmaxnreg.dec.sync.aligned.u32 %0;" :: "n"(N)); }
DEVI float ex2f(float x) { float y; asm("ex2.approx.ftz.f32 %0, %1;" : "=f"(y) : "f"(x)); return y; }
DEVI uint32_t pack_bf16(float lo, float hi) { uint32_t r; asm("cvt.rn.bf16x2.f32 %0, %1, %2;" : "=r"(r) : "f"(hi), "f"(lo)); return r; }
DEVI float bf_lo(uint32_t v) { return __uint_as_float(v << 16); }
DEVI float bf_hi(uint32_t v) { return __uint_as_float(v & 0xffff0000u); }
DEVI float bf_round(float x) { return bf_lo(pack_bf16(x, 0.f)); }
DEVI void stsm_x4(uint32_t addr, uint32_t a, uint32_t b, uint32_t c, uint32_t d) {
  asm volatile("stmatrix.sync.aligned.m8n8.x4.shared.b16 [%0], {%1,%2,%3,%4};" :: "r"(addr), "r"(a), "r"(b), "r"(c), "r"(d) : "memory");
}
DEVI void ldsm_x4(uint32_t addr, uint32_t& a, uint32_t& b, uint32_t& c, uint32_t& d) {
  asm volatile("ldmatrix.sync.aligned.m8n8.x4.shared.b16 {%0,%1,%2,%3}, [%4];" : "=r"(a), "=r"(b), "=r"(c), "=r"(d) : "r"(addr) : "memory");
}
DEVI uint4 lds128(uint32_t a) { uint4 v; asm volatile("ld.shared.v4.u32 {%0,%1,%2,%3}, [%4];" : "=r"(v.x), "=r"(v.y), "=r"(v.z), "=r"(v.w) : "r"(a) : "memory"); return v; }
DEVI void sts128(uint32_t a, uint4 v) { asm volatile("st.shared.v4.u32 [%0], {%1,%2,%3,%4};" :: "r"(a), "r"(v.x), "r"(v.y), "r"(v.z), "r"(v.w) : "memory"); }
DEVI float2 lds64f(uint32_t a) { float2 v; asm volatile("ld.shared.v2.f32 {%0,%1}, [%2];" : "=f"(v.x), "=f"(v.y) : "r"(a) : "memory"); return v; }
DEVI void sts64f(uint32_t a, float x, float y) { asm volatile("st.shared.v2.f32 [%0], {%1,%2};" :: "r"(a), "f"(x), "f"(y) : "memory"); }
DEVI uint32_t lds32(uint32_t a) { uint32_t v; asm volatile("ld.shared.u32 %0, [%1];" : "=r"(v) : "r"(a) : "memory"); return v; }
DEVI uint32_t lds16(uint32_t a) { unsigned short v; asm volatile("ld.shared.u16 %0, [%1];" : "=h"(v) : "r"(a) : "memory"); return v; }
DEVI float lds32f(uint32_t a) { return __uint_as_float(lds32(a)); }
DEVI void sts32(uint32_t a, uint32_t v) { asm volatile("st.shared.u32 [%0], %1;" :: "r"(a), "r"(v) : "memory"); }
DEVI void sts32f(uint32_t a, float v) { sts32(a, __float_as_uint(v)); }
DEVI void sts16(uint32_t a, uint32_t v) { asm volatile("st.shared.u16 [%0], %1;" :: "r"(a), "h"((unsigned short)v) : "memory"); }
template<int N> DEVI void keep(float (&d)[N]) {
  #pragma unroll
  for (int i = 0; i < N; i++) asm volatile("" : "+f"(d[i]) :: "memory");
}
template<int N> DEVI void keep(uint32_t (&d)[N]) {
  #pragma unroll
  for (int i = 0; i < N; i++) asm volatile("" : "+r"(d[i]) :: "memory");
}
template<uint32_t HI> DEVI uint64_t mkd(uint32_t lo) { uint64_t r; asm("mov.b64 %0, {%1, %2};" : "=l"(r) : "r"(lo), "n"(HI)); return r; }
constexpr uint32_t HI128 = (1u << 30) | (1024 >> 4), HI64 = (2u << 30) | (512 >> 4);
#define VOFF(x) ((uint32_t)(x) * (uint32_t)(1 - 65536))
DEVI bool elect() { uint32_t p; asm volatile("{\n.reg .pred q;\nelect.sync _|q, 0xffffffff;\nselp.u32 %0, 1, 0, q;\n}" : "=r"(p)); return p; }
DEVI void warp_signal(uint32_t bar) { __syncwarp(); if (elect()) mbar_arrive(bar); }

#define BCP 16
#define XCP 4
struct Scratch {
  uint4 statP[8][2048];
  uint4 statF[2048];
  uint4 csP[16][8][96];
  uint4 best[8][BCP][16];
  uint4 row[16][256];
  uint4 yP[128][112][2];
  uint4 x2[XCP][256];
  uint4 patch[128][64];
  unsigned flagKV[128][32];
  unsigned flagO[8][32];
  unsigned flagX[8][32];
  unsigned epoch, pad[255];
  uint4 kv[128][4][1024];
  uint4 o[8][2][8][2][1024];
  uint4 x[8][16][2048];
  uint4 zero[1024];
};
static_assert(offsetof(Scratch, kv) % 1024 == 0, "");
__device__ __align__(1024) Scratch g_scr;
#define PROFT(cond, slot)
#define PROFW(cond, slot)
#define PROFD(cond, slot)
#define PROFX(cond, slot)
#define PROFY(cond, slot)

constexpr uint32_t SB0 = 65536, HOLE = 90112, SA2 = 98304, SB1 = 131072, SB2 = 155648, STG = 180224;
constexpr uint32_t KVA = 0, KVB = 98304, QO = 65536;
constexpr uint32_t MISC = 229376, CS = MISC, ONES = MISC + 768, BARS = MISC + 1792, INFO = MISC + 2208, WR = MISC + 2224, X2SEG = MISC + 2736, INFO2 = MISC + 2992, DUMP = MISC + 3040;
constexpr uint32_t PAR = HOLE, HV = HOLE + 2048, RED = HOLE + 6144, PATCH = 196608;
constexpr uint32_t SMEM_BYTES = 232448;
enum { B_FULLQ = 0, B_EMPTYQ = 3, B_FULLW = 6, B_EMPTYW = 12, B_HAFREE = 18, B_OFREE = 20,
       B_XFREE = 21,
       B_KVRDY = 23, B_ORDY = 27, B_XRDY = 35, B_STGE = 39,
       B_KVFULL = 42, B_RES = 46, B_PAR = 47, B_STG = 48, B_PFREE = 51, B_COUNT = 52,
       B_ROW = 154, B_PW = 155 };
#define BAR(x) (sb + BARS + 8 * (x))
DEVI uint32_t qa_off(int s) { return s == 2 ? SA2 : (uint32_t)s * 32768u; }
DEVI uint32_t qb_off(int s) { return s == 0 ? SB0 : (s == 1 ? SB1 : SB2); }
DEVI int kb_order(int bc, int n) {
  const int e = n < 9 ? n - 2 : n - 9;
  return n < 2 ? 2 * bc + n : 2 * (((e < 4 ? e + 4 : e - 4 + (e - 4 >= (bc & 3))) + (bc & 4)) & 7) + (n >= 9);
}
DEVI int wo_order(int bc, int n) { return (n & 8) | ((n + (bc & 6)) & 7); }
DEVI uint32_t w_off(int s) { return (uint32_t)((0x143065 >> (4 * s)) & 7) * 32768u; }
DEVI uint32_t w_par(int n, int s, int L) { return (n >= 6 && n < 12) ^ (s == 5) ^ (s != 2 && L); }
DEVI uint32_t w_aoff(int n, int s) { return n == 3 ? QO : w_off(s); }
DEVI int w_next(int n, int s) { return s == 5 ? 0 : (n == 13 ? 3 : s + 1); }

struct Params {
  const bf16 *x0, *wqkv, *wo, *wr, *wg, *wu, *wd;
  bf16* out;
  Scratch* g;
  CUtensorMap mX, mWq, mXh, mWo, mWg, mWu, mWp, mWd;
  unsigned map[128];
};
#define BID ((int)(P.map[blockIdx.x] & 255))
#define FID ((int)(P.map[blockIdx.x] >> 8))
DEVI uint32_t uni(uint32_t v) { return __shfl_sync(0xffffffffu, v, 0); }
#define PQ_N 8
#define PQ_T 700
#define PF0_N 10
#define PF0_T 1600
#define PF1_E 24
#define PF1_T 1100
#define POL_Q1 POL_NORMAL
#define POL_X POL_NORMAL
#define PFA0_BAR 3
#define PFA1_BAR 0
#define PFA0_M 0
#define PFA1_M 0
#define PFA0_T 900
#define PFA1_T 700
#define PF1_S PF0_N
#define PF1_D 0
#define POL_G POL_NORMAL
#define POL_U POL_FIRST
#define POL_D POL_FIRST
#define JQ_N 6
#define WDSRC (P.wd + (size_t)min(fid, 111) * 32768)
#define WDSRC2 (P.wd + FID * 32768)
#define WD_N 4
#define THR_N 5
#define KV_D 1800
#define XD_D 300
#define W0_BAR 3
#define QEF_N 99
#define PACE_T 300
#define IDLE_T 11000
#define LATE_C 99
#define LATE_B B_XFREE + 1
#define LATE_P 0
#define KV_D1 200
#define KV_D2 1200
#define KV_DL 0
#define POL_KV0 POL_FIRST
#define POL_KV1 POL_FIRST
#define POL_O0 POL_FIRST
#define POL_O1 POL_FIRST
#define POL_W0 POL_NORMAL
#define POL_W1 POL_FIRST
#define POL_T POL_FIRST
#define U_C 8
#define ST_M 0
#define PQ_S 0
#define CSP 0
#define AX_B -1
#define PQ_B -1
#define POL_Q0 POL_NORMAL
constexpr float LN_EPS = 1e-5f;
constexpr float QSCALE = 0.17677669529663687f * 1.4426950408889634f;

DEVI void fma8(float (&a)[8], uint4 v, float h) {
  a[0] = fmaf(bf_lo(v.x), h, a[0]); a[1] = fmaf(bf_hi(v.x), h, a[1]); a[2] = fmaf(bf_lo(v.y), h, a[2]); a[3] = fmaf(bf_hi(v.y), h, a[3]);
  a[4] = fmaf(bf_lo(v.z), h, a[4]); a[5] = fmaf(bf_hi(v.z), h, a[5]); a[6] = fmaf(bf_lo(v.w), h, a[6]); a[7] = fmaf(bf_hi(v.w), h, a[7]);
}
DEVI uint4 ldsv128(uint32_t a) { uint4 v; asm volatile("ld.volatile.shared.v4.u32 {%0,%1,%2,%3}, [%4];" : "=r"(v.x), "=r"(v.y), "=r"(v.z), "=r"(v.w) : "r"(a) : "memory"); return v; }
DEVI float ldsv32f(uint32_t a) { float v; asm volatile("ld.volatile.shared.f32 %0, [%1];" : "=f"(v) : "r"(a) : "memory"); return v; }
DEVI uint32_t clk() { uint32_t t; asm volatile("mov.u32 %0, %%clock;" : "=r"(t)); return t; }
DEVI int fresh_tid() { int t; asm volatile("mov.u32 %0, %%tid.x;" : "=r"(t)); return t & 127; }
DEVI float fold8(const float (&a)[8]) {
  const int lane = threadIdx.x & 31;
  const bool u = lane & 16, v = lane & 8, x = lane & 4;
  float b0 = (u ? a[4] : a[0]) + __shfl_xor_sync(0xffffffffu, u ? a[0] : a[4], 16), b1 = (u ? a[5] : a[1]) + __shfl_xor_sync(0xffffffffu, u ? a[1] : a[5], 16);
  float b2 = (u ? a[6] : a[2]) + __shfl_xor_sync(0xffffffffu, u ? a[2] : a[6], 16), b3 = (u ? a[7] : a[3]) + __shfl_xor_sync(0xffffffffu, u ? a[3] : a[7], 16);
  float c0 = (v ? b2 : b0) + __shfl_xor_sync(0xffffffffu, v ? b0 : b2, 8), c1 = (v ? b3 : b1) + __shfl_xor_sync(0xffffffffu, v ? b1 : b3, 8);
  return (x ? c1 : c0) + __shfl_xor_sync(0xffffffffu, x ? c0 : c1, 4);
}
DEVI float sigmoidf(float x) { return __fdividef(1.f, 1.f + ex2f(-1.4426950408889634f * x)); }
DEVI float swiglu(float g, float u) { return g * u * sigmoidf(g); }

template<int J0, int J1> DEVI void exp_pack(const float (&s)[32], uint32_t (&p)[16]) {
  #pragma unroll
  for (int j = J0; j < J1; j++) p[j] = pack_bf16(ex2f(s[2 * j]), ex2f(s[2 * j + 1]));
}
DEVI bool attn_pack(const float (&o)[20], uint32_t (&ob)[8]) {
  const float lo = 5.421010862427522e-20f, hi = 1.8446744073709552e19f;
  float i0, i1; asm("rcp.approx.ftz.f32 %0, %1;" : "=f"(i0) : "f"(o[16])); asm("rcp.approx.ftz.f32 %0, %1;" : "=f"(i1) : "f"(o[18]));
  #pragma unroll
  for (int e = 0; e < 8; e++) ob[e] = pack_bf16(o[2 * e] * ((e & 1) ? i1 : i0), o[2 * e + 1] * ((e & 1) ? i1 : i0));
  return __all_sync(0xffffffffu, o[16] >= lo && o[16] <= hi && o[18] >= lo && o[18] <= hi);
}
DEVI void attn_store(const uint32_t (&ob)[8], bool ok, uint32_t st, uint32_t sb, uint32_t bar) {
  stsm_x4(ok ? st : sb + DUMP, ob[0], ob[1], ob[2], ob[3]); stsm_x4(ok ? st ^ 32 : sb + DUMP, ob[4], ob[5], ob[6], ob[7]);
  __syncwarp();
  asm volatile("{\n.reg .pred p, q;\nelect.sync _|q, 0xffffffff;\nsetp.ne.and.u32 p, %1, 0, q;\n@p mbarrier.arrive.shared::cta.b64 _, [%0];\n}" :: "r"(bar), "r"((uint32_t)ok) : "memory");
}
DEVI void attn_exact(uint32_t st, uint32_t kv, int t, bool hasprev, uint32_t bar) {
  const int lane = threadIdx.x & 31;
  #pragma unroll 1
  for (int row = ((threadIdx.x >> 5) & 3) * 16, n = 0; n < 16; n++, row++) {
    const int k1 = 256 + t * 64 + row;
    float m = -INFINITY, l = 0.f, o = 0.f;
    #pragma unroll 1
    for (int k0 = hasprev ? k1 - 255 : 256; k0 <= k1; k0 += 32) {
      const int k = min(k0 + lane, k1), r = k & 63;
      float sc = 0.f;
      #pragma unroll 1
      for (int c = 0; c < 16; c++) {
        uint32_t a = lds32(st + row * 64 + ((c * 4) ^ ((row & 6) << 3))), b = lds32(kv + (k >> 6) * 8192 + r * 64 + ((c * 4) ^ ((r & 6) << 3)));
        sc = fmaf(bf_lo(a), bf_lo(b), fmaf(bf_hi(a), bf_hi(b), sc));
      }
      float mn = fmaxf(m, sc);
      #pragma unroll 1
      for (int x = 16; x; x >>= 1) mn = fmaxf(mn, __shfl_xor_sync(0xffffffffu, mn, x));
      const float al = ex2f(m - mn), pr = ex2f(sc - mn);
      m = mn; l *= al; o *= al;
      #pragma unroll 1
      for (int q = k0; q <= min(k0 + 31, k1); q++) {
        const float z = __shfl_sync(0xffffffffu, pr, q - k0);
        uint32_t b = lds32(kv + (q >> 6) * 8192 + 4096 + (q & 63) * 64 + (((lane >> 1) * 4) ^ ((q & 6) << 3)));
        l += z; o = fmaf(z, (lane & 1) ? bf_hi(b) : bf_lo(b), o);
      }
    }
    __syncwarp();
    sts16(st + row * 64 + ((lane * 2) ^ ((row & 6) << 3)), pack_bf16(__fdividef(o, l), 0.f));
  }
  warp_signal(bar);
}

template<int K0, int K1, int DONE = 0> DEVI void exp_pv(const float (&s)[32], uint32_t (&p)[16], float (&o)[20], uint32_t vd, bool accum) {
  #pragma unroll
  for (int ks = K0; ks < K1; ks++) {
    if (ks >= DONE) {
      #pragma unroll
      for (int j = 4 * ks; j < 4 * ks + 4; j++) p[j] = pack_bf16(ex2f(s[2 * j]), ex2f(s[2 * j + 1]));
    }
    asm volatile("" : "+r"(p[4 * ks]), "+r"(p[4 * ks + 1]), "+r"(p[4 * ks + 2]), "+r"(p[4 * ks + 3]));
    wg_fence();
    wgmma_rs_n40<1>(o, p[ks * 4], p[ks * 4 + 1], p[ks * 4 + 2], p[ks * 4 + 3], mkd<HI64>(vd + VOFF(ks * 64)), ks ? 1 : accum);
  }
}
template<int K0, int K1> DEVI void exp_pv2(const float (&s)[32], const float (&sx)[32], uint32_t (&p)[16], uint32_t (&px)[16], float (&o)[20], uint32_t v0, uint32_t v4,
                  const uint32_t (&msk)[9], int tdiag) {
  #pragma unroll
  for (int ks = K0; ks < K1; ks++) {
    #pragma unroll
    for (int j = 4 * ks; j < 4 * ks + 4; j++) {
      const int c = 8 * (j >> 1) - 8 * (j & 1);
      const uint32_t e = pack_bf16(ex2f(c > tdiag ? s[2 * j] : sx[2 * j]), ex2f(c + 1 > tdiag ? s[2 * j + 1] : sx[2 * j + 1])), m = msk[(j >> 1) - (j & 1) + 1];
      p[j] = e & m; px[j] = e & ~m;
      asm volatile("" : "+r"(p[j]), "+r"(px[j]));
    }
    wg_fence();
    wgmma_rs_n40<1>(o, p[ks * 4], p[ks * 4 + 1], p[ks * 4 + 2], p[ks * 4 + 3], mkd<HI64>(v0 + VOFF(ks * 64)), 1);
    wgmma_rs_n40<1>(o, px[ks * 4], px[ks * 4 + 1], px[ks * 4 + 2], px[ks * 4 + 3], mkd<HI64>(v4 + VOFF(ks * 64)), 1);
  }
}

template<int J0> DEVI void qkv_store(const float (&a)[96], float p0, float p1, uint32_t d) {
  #pragma unroll
  for (int hh = 0; hh < 2; hh++) {
    const int j = 4 * (J0 + 2 * hh);
    stsm_x4(d ^ (hh << 5), pack_bf16(a[j] * p0, a[j + 1] * p0), pack_bf16(a[j + 2] * p1, a[j + 3] * p1),
                           pack_bf16(a[j + 4] * p0, a[j + 5] * p0), pack_bf16(a[j + 6] * p1, a[j + 7] * p1));
  }
}
DEVI void mean_step(float (&a)[96], float m0, float m1, uint32_t cd, bool z) {
  const uint32_t u0 = z ? 0u : __float_as_uint(m0), u1 = z ? 0u : __float_as_uint(m1);
  uint32_t ma[4] = {__byte_perm(u0, 0u, 0x1010), __byte_perm(u1, 0u, 0x1010), __byte_perm(u0, 0u, 0x3232), __byte_perm(u1, 0u, 0x3232)};
  keep(ma);
  wg_fence();
  wgmma_rs_n192<1>(a, ma[0], ma[1], ma[2], ma[3], mkd<2>(cd), 1);
  wg_commit();
}

template<bool FIRST> DEVI void qkv_block(float (&aX)[96], float (&aY)[96], uint32_t sb16, int s, int tX, int tY) {
  uint32_t a16 = sb16 + (qa_off(s) >> 4), b16 = (sb16 + (qb_off(s) >> 4)) | ((8192u >> 4) << 16);
  uint32_t ax = (a16 + tX * 512) | 0x10000u, ay = (a16 + tY * 512) | 0x10000u;
  wg_fence();
  #pragma unroll
  for (int ks = 0; ks < 4; ks++) {
    wgmma_ss_n192<1>(aX, mkd<HI128>(ax + ks * 2), mkd<HI128>(b16 + ks * 128), !(FIRST && ks == 0));
    wgmma_ss_n192<1>(aY, mkd<HI128>(ay + ks * 2), mkd<HI128>(b16 + ks * 128), !(FIRST && ks == 0));
  }
  wg_commit();
}
DEVI void qkv_half(float (&a)[96], uint32_t sb16, int t, uint32_t sa, uint32_t sbb) {
  wg_fence();
  #pragma unroll
  for (int ks = 0; ks < 4; ks++)
    wgmma_ss_n192<1>(a, mkd<HI128>(((sb16 + (sa >> 4) + t * 512) | 0x10000u) + ks * 2), mkd<HI128>(((sb16 + (sbb >> 4)) | ((8192u >> 4) << 16)) + ks * 128), 1);
  wg_commit();
}
DEVI void wo_block(float (&acc)[64], uint32_t sb16, int n, int s, int wg) {
  uint32_t a16 = (sb16 + (w_aoff(n, s) >> 4) + wg * 256) | 0x10000u, b16 = (sb16 + (w_off(s) >> 4) + 1024) | ((8192u >> 4) << 16);
  wg_fence();
  #pragma unroll
  for (int ks = 0; ks < 4; ks++)
    wgmma_ss_n128<1>(acc, mkd<HI64>(a16 + (ks >> 1) * 512 + (ks & 1) * 2), mkd<HI128>(b16 + ks * 128), 1);
  wg_commit();
}
DEVI void consumer(const Params& P, uint32_t sb, int wg) {
  const int w = uni((threadIdx.x >> 5) & 3);
  #define LAYER uni(mbar_test(BAR(B_XRDY + wg * 2 + 1), 0))
  #define IDS L = LAYER; const int tid = fresh_tid(), lane = tid & 31
  const uint32_t ids = uni(P.map[blockIdx.x]);
  const int bi = (ids >> 4) & 7, rh = ids & 1, bc = (ids & 15) >> 1, fid = ids >> 8;
  const int tX = 3 - wg, tY = wg;
  constexpr uint32_t sb16 = 1024 >> 4;
  #pragma unroll 1
  while (true) {
    int L = LAYER;
    float2 fa, fb;
    {
      float aX[96], aY[96];
      const bool lead = fresh_tid() == 0;
      mbar_wait(BAR(B_FULLQ), 0);
      PROFW(threadIdx.x == 0, L * 8 + 1);
      qkv_block<true>(aX, aY, sb16, 0, tX, tY);
      #pragma unroll 1
      for (int n = 1, s = 1, ps = 0, ph = 0; n < 14; n++) {
        mbar_wait(BAR(B_FULLQ + s), ph ^ (s ? L : 0));
        PROFD(threadIdx.x == 0 && L && (n == 2 || n == 3 || n == 7 || n == 11 || n == 13), n == 2 ? 48 : 49 + (n >> 2));
        qkv_block<false>(aX, aY, sb16, s, tX, tY);
        wg_wait<1>(); if (lead) mbar_arrive(BAR(B_EMPTYQ + ps));
        ps = s; if (s == 2) { s = 0; ph ^= 1; } else s++;
      }
      mbar_wait(BAR(B_FULLQ + 2), L);
      qkv_half(aX, sb16, tX, SA2, SB2);
      mbar_wait(BAR(B_ROW), L);
      IDS;
      const uint32_t pa = sb + PAR + (w * 16 + (lane >> 2)) * 8;
      float2 p0 = lds64f(pa + tX * 512), p1 = lds64f(pa + tX * 512 + 64), p2 = lds64f(pa + tY * 512), p3 = lds64f(pa + tY * 512 + 64);
      mean_step(aX, p0.y, p1.y, sb16 + (CS >> 4), lane & 3);
      mbar_wait(BAR(B_FULLQ), 1);
      qkv_half(aX, sb16, tX, 0, SB0);
      wg_wait<3>(); if (lead) mbar_arrive(BAR(B_EMPTYQ + 1));
      bar_sync(1, 256);
      if (L) mbar_wait(BAR(B_PW), 0);
      qkv_half(aY, sb16, tY, SA2, SB2);
      wg_wait<1>(); keep(aX);
      const int srow = w * 16 + (lane & 15);
      const uint32_t x0 = sb + srow * 64 + (((lane >> 4) ^ ((srow >> 1) & 3)) << 4), xX = x0 + (4 + tX) * 8192, xY = x0 + (4 + tY) * 8192;
      qkv_store<8>(aX, p0.x, p1.x, xX + KVA); qkv_store<16>(aX, p0.x, p1.x, xX + KVA + 4096);
      warp_signal(BAR(B_KVRDY + wg * 2));
      qkv_half(aY, sb16, tY, 0, SB0);
      mean_step(aY, p2.y, p3.y, sb16 + (CS >> 4), fresh_tid() & 3);
      wg_wait<2>(); if (lead) mbar_arrive(BAR(B_EMPTYQ + 2));
      mbar_wait(BAR(B_EMPTYQ + 2), L);
      qkv_store<12>(aX, p0.x, p1.x, xX + KVB); qkv_store<20>(aX, p0.x, p1.x, xX + KVB + 4096);
      wg_wait<0>(); keep(aY);
      if (lead) mbar_arrive(BAR(B_EMPTYQ));
      PROFW(threadIdx.x == 0, L * 8 + 2);
      qkv_store<8>(aY, p2.x, p3.x, xY + KVA); qkv_store<16>(aY, p2.x, p3.x, xY + KVA + 4096);
      qkv_store<12>(aY, p2.x, p3.x, xY + KVB); qkv_store<20>(aY, p2.x, p3.x, xY + KVB + 4096);
      warp_signal(BAR(B_KVRDY + wg * 2 + 1));
      p0.x *= QSCALE; p1.x *= QSCALE; p2.x *= QSCALE; p3.x *= QSCALE;
      mbar_wait(BAR(B_EMPTYQ), 1);
      qkv_store<0>(aX, p0.x, p1.x, x0 + QO + tX * 4096);
      qkv_store<0>(aY, p2.x, p3.x, x0 + QO + tY * 4096); qkv_store<4>(aY, p2.x, p3.x, x0 + QO + 16384 + tY * 4096);
      { const float2* f = (const float2*)&P.g->statF[bi * 256 + rh * 128 + (wg ^ rh) * 64 + w * 16 + (lane >> 2)]; fa = __ldcg(f); fb = __ldcg(f + 16); }
      mbar_wait(BAR(B_PAR), L);
      qkv_store<4>(aX, p0.x, p1.x, x0 + QO + 16384 + tX * 4096);
      const int prow = (int)uni(lds32(sb + INFO)) - bi * 256;
      if ((prow >> 4) == tX * 4 + w || (prow >> 4) == tY * 4 + w) {
        __syncwarp();
        if (lane < 24) sts128(sb + (prow & 63) * 64 + (((lane ^ (prow >> 1)) & 3) << 4) +
                              (lane < 8 ? QO + (lane >> 2) * 16384 + (prow >> 6) * 4096 : ((lane & 4) ? KVB : KVA) + (4 + (prow >> 6)) * 8192 + (lane >> 4) * 4096),
                              lds128(sb + PATCH + lane * 16));
      }
      fence_async_smem();
      bar_sync(1, 256);
    }
    PROFW(threadIdx.x == 0, L * 8 + 3);
    {
      IDS;
      float s0[32], s1[32], sx[32], o[20], op[20];
      uint32_t p0[16], p1[16], px[16], msk[9];
      const int tdiag = w * 16 + (lane >> 2) - 2 * (lane & 3);
      const uint32_t ones = (sb16 + (ONES >> 4)) << 16;
      const uint32_t qX = (sb16 + (QO >> 4) + tX * 256) | 0x10000u, qY = (sb16 + (QO >> 4) + tY * 256) | 0x10000u;
      const uint32_t kXB = (sb16 + (KVB >> 4) + tX * 512) | 0x10000u;
      uint32_t redo = 0;
      const uint32_t ost = sb + QO + (w * 16 + (lane & 15)) * 64 + (((lane >> 4) ^ ((lane >> 1) & 3)) << 4);
      #define QA(s, q, k) do { wg_fence(); wgmma_ss_n64<0>(s, mkd<HI64>(q), mkd<HI64>(k), 0); } while (0)
      #define QB(s, q, k) wgmma_ss_n64<0>(s, mkd<HI64>((q) + 2), mkd<HI64>((k) + 2), 1)
      #define QA2(q, k) do { QA(s1, q, k); wgmma_ss_n64<0>(sx, mkd<HI64>(q), mkd<HI64>((k) + 2048), 0); } while (0)
      #define QB2(q, k) do { QB(s1, q, k); QB(sx, q, (k) + 2048); } while (0)
      #define VB(v, b) ((v) + VOFF((b) * 512))
      #define MID() do { wg_commit(); wg_wait<1>(); } while (0)
      QA(s0, qX + 1024, kXB + 1536); QB(s0, qX + 1024, kXB + 1536); wg_commit();
      #pragma unroll
      for (int e = 0; e < 20; e++) o[e] = 0.f;
      wg_wait<0>(); keep(s0);
      #pragma unroll 1
      for (int h = 1; h >= 0; h--) {
        const uint32_t kXA = kXB - ((KVB - KVA) >> 4), kX = h ? kXB : kXA, vX = VOFF((kX & 0xffffu) + 256) + ones;
        QA(s1, qX + h * 1024, kX + 1024);
        #pragma unroll
        for (int e = 0; e < 20; e++) op[e] = o[e];
        keep(op);
        exp_pv<0, 1>(s0, p0, o, VB(vX, 3), false); QB(s1, qX + h * 1024, kX + 1024); wg_commit();
        exp_pv<1, 2>(s0, p0, o, VB(vX, 3), true); MID(); keep(s1);
        exp_pv<2, 4>(s0, p0, o, VB(vX, 3), true);
        { int td = tdiag; asm volatile("" : "+r"(td));
          #pragma unroll
          for (int e = 0; e < 9; e++) msk[e] = ((8 * e - 8 > td) ? 0xFFFFu : 0u) | ((8 * e - 7 > td) ? 0xFFFF0000u : 0u);
          keep(msk); }
        exp_pv<0, 2>(s1, p1, o, VB(vX, 2), true);
        bar_sync(h ? 12 + wg : 4 + wg * 4, h ? 128 : 160);
        QA(s0, qX, kXA + 512 + h * 1024);
        exp_pv<2, 3>(s1, p1, o, VB(vX, 2), true); QB(s0, qX, kXA + 512 + h * 1024);
        exp_pv<3, 4>(s1, p1, o, VB(vX, 2), true); wg_commit();
        wg_wait<0>(); keep(s0); keep(p0); keep(p1); keep(o);
      }
      #pragma unroll 1
      for (int h = 0; h < 2; h++) {
        const uint32_t kb16 = sb16 + ((h ? KVB : KVA) >> 4), kX = (kb16 + tX * 512) | 0x10000u, kY = (kb16 + tY * 512) | 0x10000u, qx = qX + h * 1024, qy = qY + h * 1024;
        const uint32_t onesP = bi ? ones : (kb16 + 1984) << 16;
        const uint32_t vX = VOFF(kb16 + tX * 512 + 256), vY = VOFF(kb16 + tY * 512 + 256);
        uint32_t ob[8], v;
        v = VB(vX + (wg ? onesP : ones), 1);
        QA2(qx, kX);
        exp_pv<0, 1>(s0, p0, o, v, true); QB2(qx, kX); wg_commit();
        exp_pv<1, 2>(s0, p0, o, v, true); MID(); keep(s1); keep(sx);
        exp_pv<2, 4>(s0, p0, o, v, true);
        QA(s0, qy, kY + 1536);
        exp_pv2<0, 1>(s1, sx, p1, px, o, vX + onesP, VB(vX + ones, 4), msk, tdiag); QB(s0, qy, kY + 1536); wg_commit();
        exp_pv2<1, 2>(s1, sx, p1, px, o, vX + onesP, VB(vX + ones, 4), msk, tdiag); MID(); keep(s0); keep(p0);
        exp_pv2<2, 4>(s1, sx, p1, px, o, vX + onesP, VB(vX + ones, 4), msk, tdiag); wg_commit();
        v = VB(vY + (wg ? ones : onesP), 3);
        QA(s1, qy, kY + 1024);
        exp_pack<0, 4>(s0, p0);
        QB(s1, qy, kY + 1024); MID(); keep(o); keep(p1); keep(px);
        bool ok = attn_pack(o, ob); keep(ob);
        exp_pv<0, 2, 1>(s0, p0, o, v, false); MID(); keep(s1);
        attn_store(ob, ok, ost + (h * 4 + tX) * 4096, sb, BAR(B_ORDY + wg * 4 + h * 2)); redo |= ok ? 0u : 1u << (h * 2);
        exp_pv<2, 4>(s0, p0, o, v, true);
        v = VB(vY + onesP, 2);
        exp_pv<0, 1>(s1, p1, o, v, true);
        bar_sync(5 + wg * 4 + h * 2, 160);
        QA(s0, qy, kY + 512);
        exp_pv<1, 2>(s1, p1, o, v, true); QB(s0, qy, kY + 512); wg_commit();
        exp_pv<2, 3>(s1, p1, o, v, true); MID(); keep(s0); keep(p0);
        exp_pv<3, 4>(s1, p1, o, v, true);
        v = VB(vY + onesP, 1);
        QA2(qy, kY);
        exp_pv<0, 1>(s0, p0, o, v, true); QB2(qy, kY); wg_commit();
        exp_pv<1, 2>(s0, p0, o, v, true); MID(); keep(s1); keep(sx); keep(p1);
        exp_pv<2, 4>(s0, p0, o, v, true);
        exp_pv2<0, 1>(s1, sx, p1, px, o, vY + onesP, VB(vY + ones, 4), msk, tdiag);
        bar_sync(6 + wg * 4, h ? 128 : 160);
        QA(s0, h ? qy : qX + 1024, kXB + 512);
        exp_pv2<1, 2>(s1, sx, p1, px, o, vY + onesP, VB(vY + ones, 4), msk, tdiag); QB(s0, h ? qy : qX + 1024, kXB + 512);
        exp_pv2<2, 4>(s1, sx, p1, px, o, vY + onesP, VB(vY + ones, 4), msk, tdiag); wg_commit();
        wg_wait<0>(); keep(o); keep(s0); keep(p0); keep(p1); keep(px);
        ok = attn_pack(o, ob); attn_store(ob, ok, ost + (h * 4 + tY) * 4096, sb, BAR(B_ORDY + wg * 4 + h * 2 + 1)); redo |= ok ? 0u : 2u << (h * 2);
        #pragma unroll
        for (int e = 0; e < 20; e++) o[e] = op[e];
      }
      #undef QA
      #undef QB
      #undef QA2
      #undef QB2
      #undef VB
      #undef MID
      if (redo) {
        #pragma unroll 1
        for (int u = 0; u < 4; u++) if ((redo >> u) & 1) {
          const int h = u >> 1, t = (u & 1) ? tY : tX;
          attn_exact(sb + QO + (h * 4 + t) * 4096, sb + (h ? KVB : KVA), t, bi > 0, BAR(B_ORDY + wg * 4 + u));
        }
      }
    }
    PROFW(threadIdx.x == 0, L * 8 + 4);
    {
      IDS;
      const int t256 = wg * 128 + tid;
      float acc[64];
      const int tt = wg ^ rh;
      const int grow = bi * 256 + rh * 128 + tt * 64 + w * 16 + (lane >> 2);
      float al0 = 1.f, be0 = 0.f, al1 = 1.f, be1 = 0.f;
      const int idx0 = (int)uni(lds32(sb + INFO));
      const uint32_t tag = lds32(sb + INFO + 8) + L;
      uint4* const sp = &P.g->statP[bc][grow + (lane & 1) * 8];
      uint4* const yp = &P.g->yP[t256 >> 1][min(fid, 111)][t256 & 1];
      if (L) {
        float r0 = rsqrtf(fa.y + LN_EPS), r1 = rsqrtf(fb.y + LN_EPS);
        if (grow != idx0) { al0 = 1.f + r0; be0 = -fa.x * r0; }
        if (grow + 8 != idx0) { al1 = 1.f + r1; be1 = -fb.x * r1; }
      }
      const int srow = tt * 64 + w * 16 + (lane & 15);
      const uint32_t ra = sb + srow * 128 + (((lane >> 4) ^ (srow & 7)) << 4);
      mbar_wait(BAR(B_FULLW + 5), L);
      if ((idx0 >> 4) == bi * 16 + rh * 8 + tt * 4 + w) {
        int r = idx0 & 127;
        if (lane < 16) sts128(sb + 32768 + (lane >> 3) * 16384 + r * 128 + (((lane & 7) ^ (r & 7)) << 4), lds128(sb + X2SEG + lane * 16));
        fence_async_smem();
        __syncwarp();
      }
      #pragma unroll
      for (int jj = 0; jj < 8; jj++) {
        uint32_t r[4]; ldsm_x4((ra + 32768 + (jj >> 2) * 16384) ^ ((jj & 3) << 5), r[0], r[1], r[2], r[3]);
        #pragma unroll
        for (int e = 0; e < 4; e++) {
          acc[8 * jj + 2 * e] = fmaf(bf_lo(r[e]), (e & 1) ? al1 : al0, (e & 1) ? be1 : be0);
          acc[8 * jj + 2 * e + 1] = fmaf(bf_hi(r[e]), (e & 1) ? al1 : al0, (e & 1) ? be1 : be0);
        }
      }
      keep(acc);
      bar_sync(12 + wg, 128);
      if (!(lane & 2)) st_ll(sp, 0u, 0u, 0u, 0u);
      uint2 wd[4];
      #pragma unroll
      for (int e = 0; e < 4; e++) { wd[e] = make_uint2(0u, 0u); if (L) wd[e] = ldg_stream((const uint2*)(WDSRC) + t256 + (28 + e) * 256); }
      PROFW(t256 == 0, L * 8 + 5);
      #pragma unroll 1
      for (int n = 0, q = 0, pq = 5; n < 16; n++) {
        mbar_wait(BAR(B_FULLW + q), w_par(n, q, L));
        PROFD(t256 == 0 && !L && (n == 4 || n == 7 || n == 8 || n == 12), (n == 7 ? 63 : 41 + (n >> 2)));
        wo_block(acc, sb16, n, q, tt);
        wg_wait<1>(); if (tid == 0) mbar_arrive(BAR(B_EMPTYW + pq));
        pq = q; q = w_next(n, q);
      }
      mbar_wait(BAR(B_EMPTYW + 5), L);
      wg_wait<0>(); keep(acc);
      if (tid == 0) mbar_arrive(BAR(B_EMPTYW + 4));
      PROFW(t256 == 0, L * 8 + 6);
      const uint32_t xa = ra + rh * 16384;
      {
        float s1a = 0.f, s2a = 0.f, da = 0.f, s1b = 0.f, s2b = 0.f, db = 0.f;
        #pragma unroll
        for (int j = 0; j < 16; j++) {
          const float* a = acc + 4 * j; float2 wv = lds64f(sb + WR + j * 32 + (lane & 3) * 8);
          s1a += a[0] + a[1]; s1b += a[2] + a[3];
          s2a = fmaf(a[0], a[0], s2a); s2b = fmaf(a[2], a[2], s2b); s2a = fmaf(a[1], a[1], s2a); s2b = fmaf(a[3], a[3], s2b);
          da = fmaf(a[0], wv.x, da); db = fmaf(a[2], wv.x, db); da = fmaf(a[1], wv.y, da); db = fmaf(a[3], wv.y, db);
        }
        bool odd = lane & 1;
        float u1 = (odd ? s1b : s1a) + __shfl_xor_sync(0xffffffffu, odd ? s1a : s1b, 1);
        float u2 = (odd ? s2b : s2a) + __shfl_xor_sync(0xffffffffu, odd ? s2a : s2b, 1);
        float u3 = (odd ? db : da) + __shfl_xor_sync(0xffffffffu, odd ? da : db, 1);
        u1 += __shfl_xor_sync(0xffffffffu, u1, 2); u2 += __shfl_xor_sync(0xffffffffu, u2, 2); u3 += __shfl_xor_sync(0xffffffffu, u3, 2);
        if (!(lane & 2)) st_ll(sp, __float_as_uint(u1), __float_as_uint(u2), __float_as_uint(u3), tag);
      }
      {
      #pragma unroll
      for (int jj = 0; jj < 8; jj++) {
        const float* a = acc + 8 * jj;
        stsm_x4((xa + (jj >> 2) * 32768) ^ ((jj & 3) << 5), pack_bf16(a[0], a[1]), pack_bf16(a[2], a[3]), pack_bf16(a[4], a[5]), pack_bf16(a[6], a[7]));
        if (jj == 7) fence_async_smem();
        if ((jj & 3) == 3) warp_signal(BAR(B_XRDY + wg * 2 + (jj >> 2)));
      }
      }
      PROFW(t256 == 0, L * 8 + 7);
      if (L) {
        mbar_wait(BAR(B_PAR), 0);
        { float2 pa = lds64f(sb + PAR + (grow & 127) * 8), pb = lds64f(sb + PAR + (grow & 127) * 8 + 64); al0 = pa.x; be0 = pa.y; al1 = pb.x; be1 = pb.y; }
        uint32_t rs[32];
        #pragma unroll
        for (int j = 0; j < 16; j++) {
          rs[2 * j] = pack_bf16(fmaf(acc[4 * j], al0, be0), fmaf(acc[4 * j + 1], al0, be0));
          rs[2 * j + 1] = pack_bf16(fmaf(acc[4 * j + 2], al1, be1), fmaf(acc[4 * j + 3], al1, be1));
        }
        #pragma unroll
        for (int jj = 0; jj < 8; jj++) stsm_x4((xa + (jj >> 2) * 32768) ^ ((jj & 3) << 5), rs[4 * jj], rs[4 * jj + 1], rs[4 * jj + 2], rs[4 * jj + 3]);
        PROFW(t256 == 0, 16);
        if (fid >= 112) bar_arrive(3, 384);
        else {
          float d[4] = {0.f, 0.f, 0.f, 0.f};
          mbar_wait(BAR(B_FULLW + wg * 3), 0); mbar_wait(BAR(B_FULLW + wg * 3 + 1), 0);
          bar_sync(3, 384);
          PROFW(t256 == 0, 29);
          #pragma unroll 1
          for (int g = 0; g < 4; g++) {
            const uint32_t ad = (sb16 + (wg ? 6144 : 10240) + (g >> 1) * 2048 + (g & 1) * 512) | (1024u << 16), bd = (sb16 + (HV >> 4) + wg * 64 + g * 16) | 0x10000u;
            wg_fence();
            #pragma unroll
            for (int ks = 0; ks < 8; ks++) wgmma_ss_n8<0, 1>(d, mkd<HI64>(ad + ks * 64), mkd<8>(bd + ks * 2), 1);
            wg_commit();
          }
          mbar_wait(BAR(B_FULLW + 2), 0);
          wg_wait<0>(); keep(d);
          if (!(lane & 3)) { sts32f(sb + PAR + 1024 + wg * 256 + w * 64 + lane, d[0]); sts32f(sb + PAR + 1056 + wg * 256 + w * 64 + lane, d[2]); }
          bar_sync(1, 256);
          const uint32_t ga = sb + PAR + 1024 + lane * 4, aa = sb + HV + (t256 >> 5) * 128;
          sts32f(aa + lane * 4, swiglu(lds32f(ga) + lds32f(ga + 256), lds32f(ga + 128) + lds32f(ga + 384)));
          __syncwarp();
          PROFW(t256 == 0, 26);
          float y0 = 0.f, y1 = 0.f, y2 = 0.f, y3 = 0.f;
          uint32_t tbl = rh ? 0x001459a8u : 0x023679a8u;
          uint4 a4 = lds128(aa + 112);
          #pragma unroll 2
          for (int n = 0; n < 8; n++, tbl >>= 4) {
            const uint32_t src = sb + t256 * 8 + (tbl & 15) * 8192;
            const uint4 an = lds128(aa + ((0x00123564u >> (4 * n)) & 15) * 16);
            #pragma unroll
            for (int e = 0; e < 4; e++) {
              const float av = __uint_as_float(e == 0 ? a4.x : (e == 1 ? a4.y : (e == 2 ? a4.z : a4.w)));
              y0 = fmaf(bf_lo(wd[e].x), av, y0); y1 = fmaf(bf_hi(wd[e].x), av, y1); y2 = fmaf(bf_lo(wd[e].y), av, y2); y3 = fmaf(bf_hi(wd[e].y), av, y3);
              const float2 v = lds64f(src + e * 2048); wd[e] = make_uint2(__float_as_uint(v.x), __float_as_uint(v.y));
            }
            a4 = an;
          }
          st_ll(yp, __float_as_uint(y0), __float_as_uint(y1), __float_as_uint(y2), (__float_as_uint(y3) & ~255u) | (lds32(sb + INFO + 12) + 1));
          PROFW(t256 == 0, 27);
        }
        return;
      }
      mbar_wait(BAR(B_XRDY + wg * 2 + 1), 0);
    }
  }
  #undef IDS
  #undef LAYER
}

DEVI void loader(const Params& P, uint32_t sb) {
  const int lane = threadIdx.x & 31;
  const int bid = uni(BID), bi = bid >> 4, bp = bid & 15, rh = bp & 1, bc = bp >> 1;
  uint32_t phq = 0, tag = 0;
  #pragma unroll 1
  for (int L = 0; L < 2; L++) {
    int s = 0;
    uint32_t rdy = 0;
    #pragma unroll 1
    for (int n = L ? 0 : 3; n < 16; n++) {
      int kb = L ? kb_order(bc, n) : n;
      mbar_wait(BAR(B_EMPTYQ + s), (phq >> s) & 1);
      phq ^= 1u << s;
      if (L && n == 1) { mbar_wait(BAR(B_XRDY + 1), 0); mbar_wait(BAR(B_XRDY + 3), 0); }
      if (elect()) {
        mbar_expect_tx(BAR(B_FULLQ + s), L && n < 2 ? 40960 : 57344);
        tma_3d_h(sb + qb_off(s), &P.mWq, bp * 64, kb * 64, 0, BAR(B_FULLQ + s), L && n >= QEF_N ? POL_FIRST : POL_NORMAL);
        if (!L) tma_2d(sb + qa_off(s), &P.mX, kb * 64, bi * 256, BAR(B_FULLQ + s));
      }
      if (L && n >= 2) {
        if (((rdy >> (2 * kb)) & 3) != 3) {
          do { rdy = __ballot_sync(0xffffffffu, ld_rlx(&P.g->flagX[bi][lane]) == tag); } while (((rdy >> (2 * kb)) & 3) != 3);
          fence_async_glob();
        }
        if (n == 3 || n == 4) mbar_wait(BAR(B_XFREE + n - 3), 0);
        if (elect()) bulk_g2s_h(sb + qa_off(s), P.g->x[bi][kb], 32768, BAR(B_FULLQ + s), POL_X);
      }
      PROFY(L && lane == 0 && (n == 2 || n == 3 || n == 9), n == 9 ? 60 : 56 + n);
      if (L && n == 2) { mbar_wait(BAR(B_FULLQ), 0); mbar_wait(BAR(B_FULLQ + 1), 1); if (lane < 2) mbar_arrive_peer(BAR(B_XFREE + lane)); }
      s = (s == 2) ? 0 : s + 1;
    }
    for (int q = 0; q < 3; q++) mbar_wait(BAR(B_EMPTYQ + q), (phq >> q) & 1);
    tag = lds32(sb + INFO + 8) + L;
    #pragma unroll 1
    for (int q = 0; q < 4; q++) {
            if (bi) {
        const unsigned* f = &P.g->flagKV[bid - 16][q];
        while (ld_rlx(f) != tag);
        fence_async_glob();
      }
      if (elect()) {
        mbar_expect_tx(BAR(B_KVFULL + q), 16384);
        bulk_g2s_h(sb + ((q >> 1) ? KVB : KVA) + ((q & 1) ? 0 : 16384), bi ? P.g->kv[bid - 16][q] : P.g->zero, 16384, BAR(B_KVFULL + q), L ? POL_KV1 : POL_KV0);
      }
      PROFY(!L && lane == 0 && bi && q != 2, 34 + (q + 1) / 2);
    }
    mbar_wait(BAR(B_ORDY), L);
    {
      const uint4* src = P.g->o[bi][0][0][rh];
      rdy = 0;
      #pragma unroll 1
      for (int n = 0, q = 0; n < 16; q = w_next(n, q), n++) {
        const int j = wo_order(bc, n);
        if (((rdy >> (2 * j)) & 3) != 3) {
          do { rdy = __ballot_sync(0xffffffffu, ld_rlx(&P.g->flagO[bi][lane]) == tag); } while (((rdy >> (2 * j)) & 3) != 3);
          fence_async_glob();
        }
        if (n >= 2) mbar_wait(n < 5 ? BAR(B_HAFREE + (n > 3)) : BAR(B_EMPTYW + q), n < 5 ? L : w_par(n, q, L) ^ 1);
        if (n == THR_N) mbar_wait(BAR(B_OFREE), L);
        if (elect()) { mbar_expect_tx(BAR(B_FULLW + q), 16384); bulk_g2s_h(sb + w_aoff(n, q), src + j * 2048, 16384, BAR(B_FULLW + q), L ? POL_O1 : POL_O0); }
      }
    }
    mbar_wait(BAR(B_OFREE), L);
  }
}

DEVI void ffn_prefetch(const Params& P, int q) {
  bulk_prefetch(q < 16 ? ((q & 1) ? P.wu : P.wg) + ((q >> 1) * 128 + blockIdx.x) * 3584 : P.wd + (min(FID, 111) * 8 + q - 16) * 4096, q < 16 ? 7168 : 8192);
}
DEVI void storer(const Params& P, uint32_t sb, int wg) {
  const int bid = uni(BID), bi = bid >> 4, rh = bid & 1, bc = (bid & 15) >> 1;
  const bool one = (threadIdx.x & 31) == 0;
  char* const g = (char*)P.g;
  const uint32_t tag0 = uni(((ld_rlx(&P.g->epoch) % 16383u) + 1u) << 2);
  #pragma unroll 1
  for (int L = 0; L < 2; L++) {
    const uint32_t tag = tag0 + L;
    if (wg) {
      #pragma unroll 1
      for (int r = threadIdx.x & 31; r < 256; r += 32) {
        uint4 v;
        do v = ld_ll(&P.g->statF[bi * 256 + r]); while (!__all_sync(0xffffffffu, v.w == tag));
        float var = __uint_as_float(v.y), c = rsqrtf(var + LN_EPS);
        if (L) { c += 1.f; c *= rsqrtf(fmaf(var * c, c, LN_EPS)); }
        const float mh = bf_round(__uint_as_float(v.x));
        sts64f(sb + PAR + r * 8, c, __uint_as_float(pack_bf16(mh, __uint_as_float(v.x) - mh)));
      }
      if (!L) mbar_wait(BAR(B_PAR), 0);
      warp_signal(BAR(B_ROW));
    }
    #pragma unroll 1
    for (int u = 0; u < 2 + 4 * wg; u++) {
      const int h = u < 2 ? u : u >> 2, hi = (u & 1) ^ 1;
      uint32_t src, dst, fl, b0, b1;
      if (u < 2) {
        src = (h ? KVB : KVA) + (3 - wg) * 16384; dst = offsetof(Scratch, kv) + (bid * 4 + h * 2 + wg) * 16384; fl = offsetof(Scratch, flagKV) + (bid * 32 + h * 2 + wg) * 4;
        b0 = BAR(B_KVRDY + ((u | wg) ? 1 : 0)); b1 = b0 + 16;
      } else {
        src = QO + (h * 2 + hi) * 8192; dst = offsetof(Scratch, o) + ((((bi * 2 + h) * 8 + bc) * 2 + hi) * 2 + rh) * 8192;
        fl = offsetof(Scratch, flagO) + (bi * 32 + h * 16 + (bid & 15)) * 4;
        b0 = BAR(B_ORDY + u - 2); b1 = b0 + 32;
      }
      mbar_wait(b0, L); mbar_wait(b1, L);
      if (u + wg == 1) {
        mbar_wait(BAR(B_PAR), L);
        const uint32_t t0 = clk(), dt = (wg ? KV_D1 : KV_D2) + (L ? KV_DL : 0); while (clk() - t0 < dt) __nanosleep(40);
      }
      fence_async_smem();
      PROFY(one && !L && u == 3 * wg, u ? 46 : 8);
      if (one && (u >= 2 || bi < 7)) bulk_s2g(g + dst, sb + src, u < 2 ? 16384 : 8192, ((ST_M >> (L * 2 + (u >= 2))) & 1) ? POL_FIRST : POL_NORMAL);
      if (one && u == 5) mbar_arrive(BAR(B_HAFREE + 1));
      if (u == 2 || u == 4) continue;
      bulk_wait<0>();
      PROFY(one && !L && u == 3 * wg, u ? 61 : 62);
      fence_rel();
      if (one) { st_rlx((unsigned*)(g + fl), tag); if (!wg || u > 2) mbar_arrive(BAR(B_HAFREE + h + (wg & h))); if (!wg && u) mbar_arrive(BAR(B_RES)); }
      PROFY(one && !L && (u > 2 || u == wg), u > 2 ? (u == 3 ? 38 : 54) : 32 + u);
    }
    if (L == 0) {
      char* dst = g + (offsetof(Scratch, x) + (bi * 16 + 2 * bc) * 32768 + rh * 16384);
      unsigned* f = (unsigned*)(g + (offsetof(Scratch, flagX) + (bi * 32 + bc * 4 + rh) * 4));
      const uint32_t a = sb + rh * 16384;
      if (wg == 0) {
        mbar_wait(BAR(B_XRDY), 0); mbar_wait(BAR(B_XRDY + 2), 0);
        fence_async_smem();
        PROFY(one, 41);
        if (one) bulk_s2g(dst, a, 16384);
        bulk_wait<0>();
        PROFY(one, 45);
        if (one) { mbar_arrive(BAR(B_XFREE)); mbar_arrive(BAR(B_PFREE)); }
        fence_rel();
        mbar_wait(BAR(B_XRDY + 1), 0); mbar_wait(BAR(B_XRDY + 3), 0);
        if (one) { st_rlx(f, tag); bulk_s2g(dst + 32768, a + 32768, 16384); }
        PROFY(one, 56);
        bulk_wait<0>();
        if (one) mbar_arrive(BAR(B_XFREE + 1));
        fence_rel();
        if (one) st_rlx(f + 2, tag);
        PROFY(one, 57);
      } else {
        mbar_wait(BAR(B_XRDY + 1), 0); mbar_wait(BAR(B_XRDY + 3), 0);
        mbar_wait(BAR(B_PFREE), 0);
        if (one) bulk_s2peer(a, 16384, BAR(B_FULLQ));
        { const uint32_t t0 = clk(); while (clk() - t0 < XD_D); }
        if (one) bulk_s2peer(a + 32768, 16384, BAR(B_FULLQ + 1));
      }
      if (wg == 0) {
        uint32_t t0 = clk() + PF1_D;
        #pragma unroll 1
        for (int q = PF1_S; q < PF1_E; q++) { while ((int)(clk() - t0) < 0) __nanosleep(50); if (one) ffn_prefetch(P, q); t0 += PF1_T; }
      }
    }
  }
}

DEVI void stg_issue(const Params& P, int c, uint32_t d, uint32_t du, uint32_t b) {
  mbar_expect_tx(b, 16384);
  if (c < 8) { tma_2d_h(d, &P.mWg, FID * 32, c * 128, b, du > 8192 ? POL_T : POL_G); tma_2d_h(d + du, &P.mWu, FID * 32, c * 128, b, du > 8192 || c < U_C ? POL_FIRST : POL_NORMAL); }
  else if (c < 12) tma_3d_h(d, &P.mWd, 0, FID * 32 + (c - 8) * 8, 0, b, POL_D);
  else tma_2d_h(d, &P.mWp, (c - 12) * 1024 + (BID >> 2) * 32, (BID & 3) * 256, b, POL_EF);
}
DEVI void pace() { const uint32_t t0 = clk(); while (clk() - t0 < PACE_T); }
DEVI void stager(const Params& P, uint32_t sb) {
  {
    const int b = blockIdx.x;
    if (PQ_B >= 0) mbar_wait(BAR(B_FULLQ + PQ_B), 0);
    uint32_t t0 = clk();
    #pragma unroll 1
    for (int q = PQ_S; q < PQ_N; q++) { bulk_prefetch(P.wqkv + (q * 128 + b) * 3072, 6144); while (clk() - t0 < PQ_T) __nanosleep(50); t0 += PQ_T; }
    bulk_prefetch(P.wo + b * 8192, 16384);
    #pragma unroll 1
    for (int q = 0; q < PF0_N; q++) {
      while (clk() - t0 < PF0_T) __nanosleep(50);
      t0 += PF0_T;
      ffn_prefetch(P, q);
    }
  }
  const int bid = BID, bi = bid >> 4, rh = bid & 1, bc = (bid & 15) >> 1;
  #pragma unroll 1
  for (int L = 0; L < 2; L++) {
    const int nch = L ? (FID < 112 ? 8 : 0) : 15;
    mbar_wait(BAR(B_PAR), L); mbar_wait(BAR(B_KVFULL + W0_BAR), L);
    #pragma unroll 1
    for (int m = 0, r = 0; m < 16; r = w_next(m, r), m++) {
      const int sw = (m == 3 || m == 4) ? 7 : 0, n = m ^ sw, q = r ^ sw;
      if (n == 4) { mbar_wait(BAR(B_RES), L); mbar_wait(BAR(B_ORDY + 2), L); mbar_wait(BAR(B_ORDY + 6), L); }
      else if (n >= 2) mbar_wait(n < 5 ? BAR(B_HAFREE + (n > 2)) : BAR(B_EMPTYW + q), n < 5 ? L : w_par(n, q, L) ^ 1);
      if (n == THR_N) mbar_wait(BAR(B_OFREE), L);
      mbar_expect_tx(BAR(B_FULLW + q), 16384);
      tma_5d(sb + w_off(q) + 16384, &P.mWo, 0, 0, n >> 3, 2 * (wo_order(bc, n) & 7), 2 * bc, BAR(B_FULLW + q), L ? POL_W1 : POL_W0);
      if (n == 2) {
        #pragma unroll 1
        for (int e = 0; e < 2; e++) {
          mbar_expect_tx(BAR(B_FULLW + 5), 16384);
          if (L) bulk_g2s_h(sb + 32768 + e * 16384, P.g->x[bi][2 * bc + e] + rh * 1024, 16384, BAR(B_FULLW + 5));
          else tma_2d_h(sb + 32768 + e * 16384, &P.mXh, bc * 128 + e * 64, bi * 256 + rh * 128, BAR(B_FULLW + 5), POL_EF);
        }
      }
    }
    mbar_wait(BAR(B_EMPTYW + 5), L);
    if (L && nch) {
      const bf16* src = WDSRC2;
      mbar_expect_tx(BAR(B_FULLW + 2), 32768); mbar_expect_tx(BAR(B_FULLW + 2), 24576);
      #pragma unroll 1
      for (int e = 0; e < 3; e++) { bulk_g2s_h(sb + e * 32768 + (e < 2 ? (rh ^ 1) * 16384 : 0), src + e * 8192, e < 2 ? 16384 : 24576, BAR(B_FULLW + 2)); pace(); }
    }
        if (L == 0) { mbar_arrive_peer(BAR(B_PFREE)); mbar_wait(BAR(B_EMPTYW), 0); mbar_wait(BAR(B_EMPTYW + 1), 0); }
    #pragma unroll 1
    for (int c = FID < 112 ? 0 : 12, slot = 0; c < nch; c++, slot = slot == 2 ? 0 : slot + 1) {
      const int q = (c >> 1) + (c >> 2);
      if (!L && (c == LATE_C || c == 12)) mbar_wait(BAR(LATE_B), LATE_P);
      mbar_wait(L ? BAR(B_EMPTYW + q) : BAR(B_STGE + slot), L | ((0x71c7 >> c) & 1));
      #define CC c
      stg_issue(P, CC, L ? sb + w_off(q) + (c & 1) * 8192 : sb + STG + slot * 16384, 8192 << L, L ? BAR(B_FULLW + q) : BAR(B_STG + slot));
      if (L) pace();
    }
  }
}
DEVI void sum8(uint4 v, float& s1, float& s2) {
  float e[8] = {bf_lo(v.x), bf_hi(v.x), bf_lo(v.y), bf_hi(v.y), bf_lo(v.z), bf_hi(v.z), bf_lo(v.w), bf_hi(v.w)};
  #pragma unroll
  for (int q = 0; q < 8; q++) { s1 += e[q]; s2 = fmaf(e[q], e[q], s2); }
}
DEVI uint4 norm8(uint4 x, float m, float rs) {
  #define HN(v) pack_bf16((bf_lo(v) - m) * rs, (bf_hi(v) - m) * rs)
  return make_uint4(HN(x.x), HN(x.y), HN(x.z), HN(x.w));
  #undef HN
}
DEVI void put_f32(uint4 b, uint32_t d, uint32_t d2) {
  sts128(d, make_uint4(b.x << 16, b.x & 0xffff0000u, b.y << 16, b.y & 0xffff0000u));
  sts128(d + d2, make_uint4(b.z << 16, b.z & 0xffff0000u, b.w << 16, b.w & 0xffff0000u));
}
DEVI void put_bf16(uint4 b, uint32_t d) {
  sts64f(d, __uint_as_float(b.x), __uint_as_float(b.y)); sts64f(d + 1024, __uint_as_float(b.z), __uint_as_float(b.w));
  fence_async_smem();
}
DEVI uint4 best4(uint32_t p) {
  uint4 a = lds128(p), b = lds128(p + 16), c = lds128(p + 32), d = lds128(p + 48);
  if (b.x > a.x) a = b;
  if (d.x > c.x) c = d;
  return c.x > a.x ? c : a;
}
#define FL(x) __uint_as_float(x)
#define UI(x) __float_as_uint(x)
DEVI void aux(const Params& P, uint32_t sb) {
  int tid = fresh_tid();
  #define lane (tid & 31)
  #define wq (tid >> 5)
  uint32_t ids = P.map[blockIdx.x], tag;
  #define bid ((int)(ids & 255))
  #define fid ((int)(ids >> 8))
  #define bi (bid >> 4)
  #define bp (bid & 15)
  #define bc (bp >> 1)
  #define FRESH() do { tid = fresh_tid(); uint4 z_ = ldsv128(sb + INFO2 + 16); ids = z_.y; tag = z_.z + L; idx = z_.w; } while (0)
  {
    const uint32_t epoch = ld_rlx(&P.g->epoch);
    if (tid == 0) {
      mbar_expect_tx(BAR(B_STG), 49152);
      tma_3d(sb + STG, &P.mWq, bp * 64, bi * 128, 0, BAR(B_STG));
      tma_3d(sb + STG + 24576, &P.mWq, bp * 64, bi * 128 + 64, 0, BAR(B_STG));
    }
    __syncwarp();
    sts64f(sb + ONES + tid * 8, FL(0x3F803F80u), FL(0x3F803F80u));
    float s1 = 0.f, s2 = 0.f;
    { uint4 v = __ldg((const uint4*)P.wr + tid);
      if ((tid >> 4) == bc) put_f32(v, sb + WR + (tid & 15) * 32, 16);
      sum8(v, s1, s2);
      #pragma unroll 1
      for (int o = 16; o; o >>= 1) s1 += __shfl_xor_sync(0xffffffffu, s1, o);
      sts32f(sb + INFO2 + wq * 4, s1); }
    if (AX_B >= 0) mbar_wait(BAR(B_FULLQ + AX_B), 0);
    const uint4* src = (const uint4*)(P.x0 + (size_t)bid * 16384) + (tid >> 3) * 128 + (tid & 7);
    s1 = 0.f; s2 = 0.f;
    #pragma unroll 1
    for (int it = 0; it < 16; it += 4) {
      uint4 v0 = __ldg(src + it * 8), v1 = __ldg(src + it * 8 + 8), v2 = __ldg(src + it * 8 + 16), v3 = __ldg(src + it * 8 + 24);
      #pragma unroll 1
      for (int q = 0; q < 4; q++) { sum8(v0, s1, s2); v0 = v1; v1 = v2; v2 = v3; }
    }
    #pragma unroll 1
    for (int o = 1; o < 8; o <<= 1) { s1 += __shfl_xor_sync(0xffffffffu, s1, o); s2 += __shfl_xor_sync(0xffffffffu, s2, o); }
    tag = ((epoch % 16383u) + 1u) << 2;
    if (tid == 0) { sts128(sb + INFO, make_uint4(0x40000000u, 0u, tag, ((epoch % 127u) + 1u) << 1)); sts128(sb + INFO2 + 16, make_uint4(epoch, ids, tag, 0x40000000u)); }
    float m = s1 * (1.f / 1024.f);
    if ((tid & 7) == 0) st_ll(&P.g->statF[bid * 16 + (tid >> 3)], UI(m), UI(fmaxf(fmaf(-m, m, s2 * (1.f / 1024.f)), 0.f)), 0u, tag);
    bar_sync(2, 128);
    mbar_wait_b(BAR(B_STG), 0);
    if (tid < 96) {
      s1 = 0.f; s2 = 0.f;
      #pragma unroll 1
      for (int r = 0; r < 16; r++) {
        const uint32_t a = sb + STG + (r >> 3) * 24576 + wq * 8192 + (r & 7) * 128 + ((lane * 4) ^ ((r & 7) << 4));
        #pragma unroll
        for (int e = 0; e < 8; e++) { uint32_t v = lds32(a + e * 1024); s1 += bf_lo(v); s2 += bf_hi(v); }
      }
      st_ll(&P.g->csP[bp][bi][tid], UI(s1), UI(s2), 0u, tag);
      s1 = 0.f; s2 = 0.f;
      #pragma unroll 1
      for (int q = 0; q < 8; q += 2) {
        uint4 a, b; poll_ll2(&P.g->csP[bp][q][tid], &P.g->csP[bp][q + 1][tid], 0xffffffffu, tag, a, b);
        s1 += FL(a.x) + FL(b.x); s2 += FL(a.y) + FL(b.y);
      }
      const uint32_t hi = pack_bf16(-s1, -s2);
      sts32(sb + CS + (tid >> 2) * 32 + (tid & 3) * 4, hi);
      sts32(sb + CS + (tid >> 2) * 32 + (tid & 3) * 4 + 16, pack_bf16(-s1 - bf_lo(hi), -s2 - bf_hi(hi)));
    }
    fence_async_smem();
  }
  int idx;
  #pragma unroll 1
  for (int L = 0; L < 2; L++) {
    FRESH();
    {
      sts32(sb + INFO, idx);
      bar_sync(2, 128);
    }
    const uint4 fix = lds128(sb + PATCH + 128 + (lane & 4) * 32 + (wq >> 1) * 64 + (lane & 3) * 16);
    warp_signal(BAR(B_PAR));
    PROFX(tid == 0, L ? 23 : 17);
    mbar_wait_b(BAR(B_KVFULL + wq), L);
    if ((idx >> 7) == bi * 2 - 1 - (wq & 1)) {
      if (lane < 8) sts128(sb + ((wq >> 1) ? KVB : KVA) + ((idx >> 6) & 3) * 8192 + (lane >> 2) * 4096 + (idx & 63) * 64 + (((lane ^ (idx >> 1)) & 3) << 4), fix);
      fence_async_smem();
    }
    bar_arrive(4 + wq, 160); bar_arrive(8 + wq, 160);
    FRESH();
    mbar_wait_b(BAR(B_OFREE), L);
    #define blk (bi * 2 + (bid & 1))
    if (tid < 32 + BCP) st_ll(tid < 32 ? &P.g->row[blk][bc * 32 + tid] : &P.g->best[bc][tid - 32][blk], 0u, 0u, 0u, 0u);
    mbar_wait_b(BAR(B_XRDY), L);
    PROFX(tid == 0, 37 + L * 16);
    __nanosleep(SD_T);
    FRESH();
    {
      float s1 = 0.f, s2 = 0.f, d = 0.f;
      #pragma unroll 1
      for (int q = 0; q < 8; q += 4) { const float4 v = poll_sum4(&P.g->statP[q][blk * 128 + tid], 2048, tag); s1 += v.x; s2 += v.y; d += v.z; }
      PROFX(tid == 0, 39 + L * 16);
      uint4 a = lds128(sb + INFO2), b, c;
      float m = s1 * (1.f / 1024.f), var = fmaxf(fmaf(-m, m, s2 * (1.f / 1024.f)), 0.f), rs = rsqrtf(var + LN_EPS);
      uint32_t key = UI(fmaf(-m, (FL(a.x) + FL(a.y)) + (FL(a.z) + FL(a.w)), d) * rs);
      key ^= (uint32_t)((int)key >> 31) | 0x80000000u;
      uint32_t win = __ballot_sync(0xffffffffu, key == __reduce_max_sync(0xffffffffu, key));
      if (lane == __ffs(win) - 1) sts128(sb + RED + wq * 16, make_uint4(key, UI(m), UI(rs), (tag << 11) | (uint32_t)(blk * 128 + tid)));
      if (L) sts64f(sb + PAR + tid * 8, 1.f + rs, -m * rs);
      else if ((tid >> 4) == bc) st_ll(&P.g->statF[blk * 128 + tid], UI(m), UI(var), 0u, tag + 1);
      bar_sync(2, 128);
      if (wq < 2) a = best4(sb + RED);
      if (wq == 1 && lane < BCP) st_ll(&P.g->best[bc][lane][blk], a.x, a.y, a.z, a.w);
      if (wq == 0) {
        mbar_wait(BAR(B_XRDY + 1), L); mbar_wait(BAR(B_XRDY + 3), L);
        float2 v = lds64f(sb + (lane >> 4) * 32768 + (a.w & 255) * 128 + (((lane & 15) * 8) ^ ((a.w & 7) << 4)));
        st_ll(&P.g->row[blk][bc * 32 + lane], UI(v.x), UI(v.y), 0u, tag);
        __syncwarp();
        if (lane < 2 + 2 * L) mbar_arrive(L ? BAR(B_PAR) : BAR(B_XFREE + lane));
      }
      PROFX(tid == 0, 18 + L * 6);
      FRESH();
      a = poll_ll(&P.g->best[bc][blk & (BCP - 1)][lane & 15], 0xfffff800u, tag << 11);
      win = __ffs(__ballot_sync(0xffffffffu, a.x == __reduce_max_sync(0xffffffffu, a.x))) - 1;
      idx = __shfl_sync(0xffffffffu, a.w, win) & 2047;
      PROFX(tid == 0, 19 + L * 6);
      poll_ll2(&P.g->row[win][tid], &P.g->row[win][tid + 128], 0xffffffffu, tag, c, b);
      c.z = b.x; c.w = b.y;
      a.x = __shfl_sync(0xffffffffu, a.x, win); a.y = __shfl_sync(0xffffffffu, a.y, win); a.z = __shfl_sync(0xffffffffu, a.z, win);
      sts32(sb + INFO2 + 28, idx);
      PROFX(tid == 0, 61 + L);
      b = norm8(c, FL(a.y), FL(a.z));
      if (L) put_bf16(b, sb + HV + tid * 8); else put_f32(b, sb + HV + tid * 16, 2048);
      if ((tid >> 1) == (bid & 63)) {
        sts128(sb + RED + 64 + (tid & 1) * 16, bid < 64 ? make_uint4(c.x, c.y, b.x, b.y) : make_uint4(c.z, c.w, b.z, b.w));
        sts32(sb + RED + 96, a.x);
      }
      bar_sync(2 + L, 128 + L * 256);
      if (L) {
        const int r0 = blk * 128 + (tid >> 4);
        uint32_t src = sb + ((tid >> 3) & 1) * 32768 + (r0 & 255) * 128 + (((tid ^ r0) & 7) << 4);
        uint4* dst = (uint4*)(P.out + (size_t)r0 * 1024 + bc * 128) + (tid & 15);
        #pragma unroll 4
        for (int it = 0; it < 16; it++) { uint4 v = lds128(src + it * 1024); if (idx - r0 != it * 8) dst[it * 1024] = v; }
      }
    }
    #pragma unroll 1
    for (int st = 2 * L; st < 2; st++) {
      FRESH();
      float a[8] = {0.f, 0.f, 0.f, 0.f, 0.f, 0.f, 0.f, 0.f};
      if (fid < 112) {
        uint32_t ha = st ? sb + RED + 768 + wq * 4 : sb + HV + ((wq & 1) * 64 + (lane >> 2)) * 4;
        uint32_t ph = st ? 0x1cu : 0x171u, bar = st ? BAR(B_STG + 2) : BAR(B_STG);
        uint32_t wa = sb + STG + wq * 4096 + (st ? 32768 + lane * 16 : (lane ^ (lane >> 3)) * 16);
        const uint32_t hx = st ? 256 : 512;
        const bool lead = lane == 0;
        uint4 vc = make_uint4(0u, 0u, 0u, 0u); float hc = 0.f;
        #pragma unroll 1
        do {
          mbar_wait(bar, ph & 1);
          PROFX(lead && threadIdx.x == 256 && st == 0 && (ph > 255 || ph < 4), 40 - 23 + __clz(ph));
          #pragma unroll
          for (int n = 0; n < 8; n++) { const uint4 v = lds128(wa + n * 512); const float h = lds32f(ha + n * 32); fma8(a, vc, hc); vc = v; hc = h; }
          __syncwarp();
          if (lead) mbar_arrive(bar - 8 * (B_STG - B_STGE));
          const bool wrap = bar == BAR(B_STG + 2);
          bar += wrap ? -16 : 8; wa += wrap ? -32768 : 16384; ha += hx;
          ph >>= 1;
        } while (ph != 1);
        fma8(a, vc, hc);
      }
      FRESH();
      uint4* const yp = &P.g->yP[tid & ~1][min(fid, 111)][tid & 1];
      if (st == 0) {
        sts32f(sb + RED + 256 + wq * 128 + ((lane & 3) * 8 + (lane >> 2)) * 4, fold8(a));
        bar_sync(2, 128);
        const uint32_t d = sb + RED + 256 + lane * 4;
        sts32f(sb + RED + 768 + lane * 32 + wq * 4, swiglu(lds32f(d) + lds32f(d + 128), lds32f(d + 256) + lds32f(d + 384)));
        if (fid < 112) { st_ll(yp, 0u, 0u, 0u, 0u); st_ll(yp + 224, 0u, 0u, 0u, 0u); }
        else { const uint32_t t0 = clk(); while (clk() - t0 < IDLE_T) __nanosleep(200); }
        __syncwarp();
        PROFX(tid == 0, 20);
      } else if (fid < 112) {
        const bool odd = lane & 1;
        const uint32_t t8 = lds32(sb + INFO + 12);
        #pragma unroll
        for (int e = 0; e < 4; e++) { float z = __shfl_xor_sync(0xffffffffu, odd ? a[e] : a[4 + e], 1); if (odd) a[e] = z; else a[4 + e] = z; }
        st_ll(yp, UI(a[0]), UI(a[1]), UI(a[2]), (UI(a[3]) & ~255u) | t8);
        st_ll(yp + 224, UI(a[4]), UI(a[5]), UI(a[6]), (UI(a[7]) & ~255u) | t8);
        PROFX(tid == 0, 21);
      }
    }
    {
      const uint32_t t8 = lds32(sb + INFO + 12) + L;
      const uint4* src = &P.g->yP[bid][0][min(tid, 111)];
      uint4 v0 = ld_ll(src), v1 = ld_ll(src + 112);
      uint4* dst = L ? (uint4*)(P.out + (size_t)idx * 1024 + bid * 8 + (tid & 1) * 4) : &P.g->x2[(tid >> 1) & (XCP - 1)][2 * bid + (tid & 1)];
      if (!L && (tid < 2 * XCP || tid >= 64)) st_ll(tid < 64 ? dst : &P.g->patch[bid][tid - 64], 0u, 0u, 0u, 0u);
      const uint32_t k = lds32(sb + RED + 96);
      const float sg = sigmoidf(FL(k ^ (~(uint32_t)((int)k >> 31) | 0x80000000u)));
      for (int it = 0; !__all_sync(0xffffffffu, ((v0.w ^ t8) & 255u) == 0 && ((v1.w ^ t8) & 255u) == 0); it++) { v0 = ld_ll(src); v1 = ld_ll(src + 112); if (it > SPIN_MAX) __trap(); }
      float y0 = FL(v0.x) + FL(v1.x), y1 = FL(v0.y) + FL(v1.y), y2 = FL(v0.z) + FL(v1.z), y3 = FL((v0.w & ~255u) | 128u) + FL((v1.w & ~255u) | 128u);
      const bool u = lane & 2, v = lane & 4;
      y0 = (u ? y2 : y0) + __shfl_xor_sync(0xffffffffu, u ? y0 : y2, 2); y1 = (u ? y3 : y1) + __shfl_xor_sync(0xffffffffu, u ? y1 : y3, 2);
      y0 = (v ? y1 : y0) + __shfl_xor_sync(0xffffffffu, v ? y0 : y1, 4);
      y0 += __shfl_xor_sync(0xffffffffu, y0, 8);
      y1 = __shfl_xor_sync(0xffffffffu, y0, 16);
      if (lane < 8) sts32f(sb + RED + 128 + wq * 32 + (lane & 1) * 16 + (lane & 2) * 4 + (lane & 4), wq < 3 ? y0 + y1 : y0);
      bar_sync(2, 128);
      if (tid < (L ? 2 : 2 * XCP)) {
        const uint32_t d = sb + RED + (tid & 1) * 16;
        const uint4 xh = lds128(d + 64), a = lds128(d + 128), b = lds128(d + 160), c = lds128(d + 192), e = lds128(d + 224);
        #define FIN(f, z) fmaf((FL(a.f) + FL(b.f)) + (FL(c.f) + FL(e.f)), sg, z)
        const uint32_t r0 = pack_bf16(FIN(x, bf_lo(xh.x) + bf_lo(xh.z)), FIN(y, bf_hi(xh.x) + bf_hi(xh.z))), r1 = pack_bf16(FIN(z, bf_lo(xh.y) + bf_lo(xh.w)), FIN(w, bf_hi(xh.y) + bf_hi(xh.w)));
        #undef FIN
        if (L) *(uint2*)dst = make_uint2(r0, r1); else st_ll(dst, r0, r1, 0u, tag + 1);
      }
      PROFW(L && tid == 0, 28);
    }
    if (L == 0) {
      PROFX(tid == 0, 22);
      FRESH();
      mbar_wait(BAR(B_STG), 1); mbar_wait(BAR(B_STG + 1), 0); mbar_wait(BAR(B_STG + 2), 0);
      const uint32_t bd = (64 + (HV >> 4) + uni(bid & 3) * 32) | 0x10000u;
      uint4 x, y; poll_ll2(&P.g->x2[bid * XCP >> 7][tid], &P.g->x2[bid * XCP >> 7][tid + 128], 0xffffffffu, tag + 1, x, y);
      x.z = y.x; x.w = y.y;
      put_bf16(x, sb + HV + tid * 8);
      bar_sync(2, 128);
      PROFX(tid == 0, 30);
      float d0[4] = {0.f, 0.f, 0.f, 0.f}, d1[4] = {0.f, 0.f, 0.f, 0.f}, d2[4] = {0.f, 0.f, 0.f, 0.f};
      #pragma unroll 1
      for (int ks = 0; ks < 8; ks++) {
        const uint32_t ad = (64 + (STG >> 4) + ks * 128) | (64u << 16);
        wg_fence();
        wgmma_ss_n8<0, 1>(d0, mkd<HI64>(ad), mkd<8>(bd + ks * 4), 1);
        wgmma_ss_n8<0, 1>(d1, mkd<HI64>(ad + 1024), mkd<8>(bd + ks * 4), 1);
        wgmma_ss_n8<0, 1>(d2, mkd<HI64>(ad + 2048), mkd<8>(bd + ks * 4), 1);
        wg_commit();
      }
      if (tid == 0) mbar_arrive(BAR(B_PW));
      uint4* dst = &P.g->patch[bid][(wq & 1) * 32 + (lane >> 2) * 2 + (wq >> 1)];
      wg_wait<0>(); keep(d0); keep(d1); keep(d2);
      if ((lane & 3) == (wq >> 1)) { st_ll(dst, UI(d0[0]), UI(d1[0]), UI(d2[0]), tag + 1); st_ll(dst + 16, UI(d0[2]), UI(d1[2]), UI(d2[2]), tag + 1); }
      PROFX(tid == 0, 31);
      if ((unsigned)(bi - (idx >> 8)) < 2u) {
        if (wq == (bc & 3)) sts64f(sb + X2SEG + lane * 8, FL(bc < 4 ? x.x : x.z), FL(bc < 4 ? x.y : x.w));
        float s1 = 0.f, s2 = 0.f;
        sum8(x, s1, s2);
        #pragma unroll
        for (int o = 16; o; o >>= 1) { s1 += __shfl_xor_sync(0xffffffffu, s1, o); s2 += __shfl_xor_sync(0xffffffffu, s2, o); }
        sts64f(sb + RED + wq * 8, s1, s2);
        bar_sync(2, 128);
        x = lds128(sb + RED); y = lds128(sb + RED + 16);
        const float m = ((FL(x.x) + FL(x.z)) + (FL(y.x) + FL(y.z))) * (1.f / 1024.f);
        const float rs = rsqrtf(fmaxf(fmaf(-m, m, ((FL(x.y) + FL(x.w)) + (FL(y.y) + FL(y.w))) * (1.f / 1024.f)), 0.f) + LN_EPS);
        const uint32_t ca = sb + CS + (tid >> 4) * 32 + (tid & 1) * 16 + (tid & 14);
        const float cq = FL(lds16(ca) << 16) * m, ck = FL(lds16(ca + 256) << 16) * m, cv = FL(lds16(ca + 512) << 16) * m;
        const float4 z = poll_sum4(&P.g->patch[bp * 8 + (tid >> 6) * 4][tid & 63], 64, tag + 1);
        float q = z.x + cq, k = z.y + ck, v = z.z + cv;
        q += __shfl_xor_sync(0xffffffffu, q, 1); k += __shfl_xor_sync(0xffffffffu, k, 1); v += __shfl_xor_sync(0xffffffffu, v, 1);
        const uint32_t d = sb + PATCH + (tid & ~1), kv = pack_bf16(k * rs, v * rs);
        sts16(d, pack_bf16(q * (rs * QSCALE), 0.f)); sts16(d + 128, kv); sts16(d + 256, kv >> 16);
      }
    }
  }
  if (bid == 0 && tid == 0) P.g->epoch = lds32(sb + INFO2 + 16) + 1;
  #undef blk
  #undef bid
  #undef fid
  #undef bi
  #undef bp
  #undef bc
  #undef FRESH
  #undef lane
  #undef wq
}

__global__ void __cluster_dims__(2, 1, 1) __launch_bounds__(512, 1) fused_kernel(const __grid_constant__ Params P) {
  extern __shared__ __align__(1024) uint8_t smem_raw[];
  const uint32_t sb = smem_u32(smem_raw);
  PROFT(threadIdx.x == 0, 0);
  if (threadIdx.x >= 416 && threadIdx.x < 416 + 80) {
    const int e = threadIdx.x - 416;
    asm volatile("prefetch.global.L2 [%0];" :: "l"(e < 32 ? P.x0 + (blockIdx.x * 16 + e / 2) * 1024 + (e % 2) * 32 : P.wqkv + (blockIdx.x * 48 + e - 32) * 32));
  }
  if (threadIdx.x < 32) { if (elect()) {
    for (int s = 0; s < 3; s++) mbar_init(BAR(B_FULLQ + s), 1);
    asm volatile("fence.mbarrier_init.release.cluster;" ::: "memory");
    const int bid0 = BID;
    #pragma unroll 1
    for (int s = 0; s < 3; s++) {
      mbar_expect_tx(BAR(B_FULLQ + s), 57344);
      tma_2d(sb + qa_off(s), &P.mX, s * 64, (bid0 >> 4) * 256, BAR(B_FULLQ + s));
      tma_3d(sb + qb_off(s), &P.mWq, (bid0 & 15) * 64, s * 64, 0, BAR(B_FULLQ + s));
    }
    if ((sb & 0x3FFFFu) != 1024) __trap();
  } } else if (threadIdx.x == 480) {
    asm volatile("prefetch.tensormap [%0];" :: "l"(&P.mWq) : "memory");
  } else if (threadIdx.x >= 32 && !(threadIdx.x & 28) && (threadIdx.x >> 3) + (threadIdx.x & 3) <= B_COUNT + 2) {
    int b = (threadIdx.x >> 3) + (threadIdx.x & 3) - 1;
    if (b >= B_COUNT) b += B_ROW - B_COUNT;
    const uint32_t cnt = b < B_XFREE ? (b == B_OFREE ? 1 : 2) : (b < B_KVRDY ? 3 : (b < B_KVFULL || b == B_PAR ? 4 : (b == B_PFREE ? 2 : 1)));
    mbar_init(BAR(b), cnt);
    asm volatile("fence.mbarrier_init.release.cluster;" ::: "memory");
  }
  __syncthreads();
  asm volatile("barrier.cluster.arrive.relaxed.aligned;" ::: "memory");
  const int wg = __shfl_sync(0xffffffffu, threadIdx.x >> 7, 0);
  if (wg < 2) { reg_inc<224>(); consumer(P, sb, wg); }
  else if (wg == 2) { reg_dec<40>(); aux(P, sb); }
  else {
    reg_dec<24>();
    asm volatile("barrier.cluster.wait.aligned;" ::: "memory");
    const int w = __shfl_sync(0xffffffffu, (threadIdx.x >> 5) & 3, 0);
    if (w == 0) loader(P, sb);
    else if (w < 3) storer(P, sb, w - 1);
    else if (elect()) stager(P, sb);
  }
}

typedef CUresult (*EncFn)(CUtensorMap*, CUtensorMapDataType, cuuint32_t, void*, const cuuint64_t*, const cuuint64_t*, const cuuint32_t*, const cuuint32_t*,
                          CUtensorMapInterleave, CUtensorMapSwizzle, CUtensorMapL2promotion, CUtensorMapFloatOOBfill);
static void mk_map(EncFn enc, CUtensorMap* m, const void* ptr, int rank, const cuuint64_t* dims, const cuuint64_t* strides, const cuuint32_t* box,
                   CUtensorMapSwizzle sw, CUtensorMapL2promotion pr) {
  cuuint32_t es[5] = {1, 1, 1, 1, 1};
  enc(m, CU_TENSOR_MAP_DATA_TYPE_BFLOAT16, rank, (void*)ptr, dims, strides, box, es, CU_TENSOR_MAP_INTERLEAVE_NONE, sw, pr, CU_TENSOR_MAP_FLOAT_OOB_FILL_NONE);
}
extern "C" void kernel_launch(void* const* d_in, const int* in_sizes, int n_in, void* d_out, int out_size) {
  (void)in_sizes; (void)n_in; (void)out_size;
  void* fn = nullptr; cudaDriverEntryPointQueryResult q;
  cudaGetDriverEntryPoint("cuTensorMapEncodeTiled", &fn, cudaEnableDefault, &q);
  EncFn enc = (EncFn)fn;
  cudaFuncSetAttribute(fused_kernel, cudaFuncAttributeMaxDynamicSharedMemorySize, SMEM_BYTES);
  Params P;
  const CUtensorMapSwizzle S128 = CU_TENSOR_MAP_SWIZZLE_128B, S64 = CU_TENSOR_MAP_SWIZZLE_64B, S0 = CU_TENSOR_MAP_SWIZZLE_NONE;
  const CUtensorMapL2promotion L256 = CU_TENSOR_MAP_L2_PROMOTION_L2_256B, L128 = CU_TENSOR_MAP_L2_PROMOTION_L2_128B;
  { cuuint64_t d[2] = {1024, 2048}, s[1] = {2048}; cuuint32_t b[2] = {64, 256}, bh[2] = {64, 128};
    mk_map(enc, &P.mX, d_in[0], 2, d, s, b, S128, L256); mk_map(enc, &P.mXh, d_in[0], 2, d, s, bh, S128, L256); }
  { cuuint64_t d[3] = {1024, 1024, 3}, s[2] = {6144, 2048}; cuuint32_t b[3] = {64, 64, 3}; mk_map(enc, &P.mWq, d_in[1], 3, d, s, b, S128, L256); }
  { cuuint64_t d[5] = {64, 32, 2, 16, 16}, s[4] = {2048, 65536, 131072, 128}; cuuint32_t b[5] = {64, 32, 1, 2, 2}; mk_map(enc, &P.mWo, d_in[2], 5, d, s, b, S128, L256); }
  { cuuint64_t d[2] = {3584, 1024}, s[1] = {7168}; cuuint32_t b[2] = {32, 128};
    mk_map(enc, &P.mWg, d_in[5], 2, d, s, b, S64, L128); mk_map(enc, &P.mWu, d_in[6], 2, d, s, b, S64, L128); }
  { cuuint64_t d[2] = {3072, 1024}, s[1] = {6144}; cuuint32_t b[2] = {32, 256}; mk_map(enc, &P.mWp, d_in[1], 2, d, s, b, S64, L128); }
  { cuuint64_t d[3] = {256, 3584, 4}, s[2] = {2048, 512}; cuuint32_t b[3] = {256, 8, 4}; mk_map(enc, &P.mWd, d_in[7], 3, d, s, b, S0, L128); }
  P.x0 = (const bf16*)d_in[0]; P.wqkv = (const bf16*)d_in[1]; P.wo = (const bf16*)d_in[2]; P.wr = (const bf16*)d_in[4]; P.wg = (const bf16*)d_in[5]; P.wu = (const bf16*)d_in[6]; P.wd = (const bf16*)d_in[7];
  P.out = (bf16*)d_out;
  cudaGetSymbolAddress((void**)&P.g, g_scr);
  for (int b = 0; b < 128; b++) {
    int j = b >> 1, quad = j < 4 ? 0 : (j < 36 ? 1 + (j - 4) % 8 : 9 + (j - 36) % 7), pos = j < 4 ? j : (j < 36 ? (j - 4) / 8 : (j - 36) / 7);
    int bid = ((quad >> 2) * 2 + (pos >> 1)) * 16 + ((quad & 3) * 2 + (pos & 1)) * 2 + (b & 1);
    int e = pos * 2 + (b & 1), fid = e < 7 ? quad * 7 + e : 112 + quad;
    P.map[b] = bid | fid << 8;
  }
  fused_kernel<<<128, 512, SMEM_BYTES>>>(P);
}
```
